```python
import torch

def _softmax(x, axis=-1):
    return torch.softmax(x, dim=axis)
def _gelu(x):
    return torch.nn.functional.gelu(x, approximate="tanh")
def _silu(x):
    return torch.nn.functional.silu(x)
def _sigmoid(x):
    return torch.sigmoid(x)
def _layernorm(x, axis=-1, eps=1e-5):
    m = x.mean(dim=axis, keepdim=True)
    v = x.var(dim=axis, keepdim=True, unbiased=False)
    return (x - m) / torch.sqrt(v + eps)
def _scatter_add(tgt, idx, src, axis=0):
    return tgt.clone().index_add_(axis, idx, src)
def _segment_sum(src, seg, n):
    out = torch.zeros((n,) + src.shape[1:], dtype=src.dtype)
    return out.index_add_(0, seg, src)
def _pad(x, pw):
    flat = tuple(v for pair in reversed(pw) for v in pair)
    return torch.nn.functional.pad(x, flat)

kernel_name = 'interleave_layers__sliding_local_dilated__dense_activation_gelu__prompt'

def setup_inputs():

    _w = (lambda a: (lambda t: t.to(torch.bfloat16) if t.is_floating_point() else t)(torch.as_tensor(a)))
    def _A_setup():
        B, S, D = 1, 2048, 1024
        return {
            "x": _w((lambda *s: torch.randn(*s, dtype=torch.bfloat16) * 0.05)(B, S, D)),
            "wqkv": _w((lambda *s: torch.randn(*s, dtype=torch.bfloat16) * 0.05)(D, 3 * D)),
            "wo": _w((lambda *s: torch.randn(*s, dtype=torch.bfloat16) * 0.05)(D, D)),
        }
    _A_in = _A_setup()

    def _B_setup():
        B, S, D, F = 1, 2048, 1024, 3584
        return {
            "x": _w((lambda *s: torch.randn(*s, dtype=torch.bfloat16) * 0.05)(B, S, D)),
            "w1": _w((lambda *s: torch.randn(*s, dtype=torch.bfloat16) * 1.6)(D, F) * (D ** -0.5)),
            "b1": _w((lambda *s: torch.randn(*s, dtype=torch.bfloat16) * 1.6)(F) * 0.01),
            "w2": _w((lambda *s: torch.randn(*s, dtype=torch.bfloat16) * 1.6)(F, D) * (F ** -0.5)),
            "b2": _w((lambda *s: torch.randn(*s, dtype=torch.bfloat16) * 1.6)(D) * 0.01),
        }
    _B_in = _B_setup()

    return {
        "A_x": _A_in["x"],
        "A_wqkv": _A_in["wqkv"],
        "A_wo": _A_in["wo"],
        "B_x": _B_in["x"],
        "B_w1": _B_in["w1"],
        "B_b1": _B_in["b1"],
        "B_w2": _B_in["w2"],
        "B_b2": _B_in["b2"],
    }

def reference(A_x, A_wqkv, A_wo, B_x, B_w1, B_b1, B_w2, B_b2):
    def _A_ref(x, wqkv, wo):
        B, S, D = x.shape
        H = 32; Dh = D // H
        W, dil = 8, 2
        qkv = (lambda x, *d: x.permute(*d))((x @ wqkv).reshape(B, S, 3, H, Dh), 2, 0, 3, 1, 4)
        q, k, v = qkv[0], qkv[1], qkv[2]
        scale = Dh ** -0.5
        pos = torch.arange(S)
        off = torch.arange(W) * dil
        idx = pos[:, None] - off[None, :]
        mask = idx >= 0
        idx_c = torch.where(mask, idx, 0).reshape(-1)
        kg = k[:, :, idx_c, :].reshape(B, H, S, W, Dh)
        vg = v[:, :, idx_c, :].reshape(B, H, S, W, Dh)
        logits = torch.einsum("bhsd,bhswd->bhsw", q, kg) * scale
        logits = torch.where(mask[None, None, :, :], logits, -1e9)
        attn = _softmax(logits, axis=-1)
        o = torch.einsum("bhsw,bhswd->bhsd", attn, vg)
        return (lambda x, *d: x.permute(*d))(o, 0, 2, 1, 3).reshape(B, S, D) @ wo

    def _B_ref(x, w1, b1, w2, b2):
        h = torch.einsum("bsd,df->bsf", x, w1) + b1
        h = _gelu(h)
        return torch.einsum("bsf,fd->bsd", h, w2) + b2

    x = A_x
    x = x + _A_ref(_layernorm(x, axis=-1), A_wqkv, A_wo)
    x = x + _B_ref(_layernorm(x, axis=-1), B_w1, B_b1, B_w2, B_b2)
    x = x + _A_ref(_layernorm(x, axis=-1), A_wqkv, A_wo)
    x = x + _B_ref(_layernorm(x, axis=-1), B_w1, B_b1, B_w2, B_b2)
    return x
```

```cpp
#include <cuda.h>
#include <cuda_bf16.h>
#include <cuda_runtime.h>
#include <stdint.h>

namespace {

constexpr int kD = 1024;
constexpr int kF = 3584;
constexpr int kCtas = 128;
constexpr int kTiles = 14;
constexpr int kRunTiles = kTiles;
constexpr int kTileBytes = 16384;

constexpr int kSmRing = 0;
constexpr int kSmX = 163840;
constexpr int kSmStg = kSmX + 32768;
constexpr int kSmHalo = kSmStg + 16384;
constexpr int kSmCsQ = kSmHalo + 8192;
constexpr int kSmV1 = kSmCsQ + 384 * 4;
constexpr int kSmB2 = kSmV1 + 448 * 8;
constexpr int kSmStat = kSmB2 + 128 * 4;
constexpr int kSmRed = kSmStat + 128 * 8;
constexpr int kSmBar = kSmRed + 512;
constexpr int kBarFull = kSmBar;
constexpr int kBarEmpty = kBarFull + 64;
constexpr int kBarTurn = kBarEmpty + 64;
constexpr int kBarEpi = kBarTurn + kTiles * 8;
constexpr int kBarX = kBarEpi + kTiles * 8;
constexpr int kBarStat = kBarX + 32;
constexpr int kSmEpoch = kBarStat + 32;
constexpr int kSmBytes = kSmEpoch + 16;

constexpr int kFlagX = 0;
constexpr int kFlagS = kFlagX + 3 * 16;
constexpr int kFlagO = kFlagS + 4 * 16;
constexpr int kFlagH = kFlagO + 4 * 16;
constexpr int kFlagC = kFlagH + 6 * 16;
constexpr int kFlagLines = kFlagC + 7;

constexpr unsigned kSpinLimit = 1u << 24;

__device__ __align__(1024) uint8_t g_x[16 * 16 * kTileBytes];
__device__ __align__(1024) uint8_t g_o[16 * 16 * kTileBytes];
__device__ __align__(1024) uint8_t g_h[16 * 56 * kTileBytes];
__device__ __align__(128) float2 g_stat[16 * 128 * 8];
__device__ __align__(128) float g_cs[3 * kD + kF];
__device__ __align__(128) uint4 g_halo[2 * 16 * 16 * 256];
__device__ __align__(128) unsigned g_flag[kFlagLines * 32];
__device__ unsigned g_ticket;

#define TRACE_AT(tile, k)

struct Params {
  const __nv_bfloat16* wqkv;
  const __nv_bfloat16* wo;
  const __nv_bfloat16* w1;
  const __nv_bfloat16* b1;
  const __nv_bfloat16* w2;
  const __nv_bfloat16* b2;
};

__device__ __forceinline__ uint32_t smem_u32(const void* p) {
  return (uint32_t)__cvta_generic_to_shared(p);
}
__device__ __forceinline__ uint32_t mapa(uint32_t a, uint32_t cta) {
  uint32_t r;
  asm("mapa.shared::cluster.u32 %0, %1, %2;" : "=r"(r) : "r"(a), "r"(cta));
  return r;
}
__device__ __forceinline__ void mbar_init(uint32_t bar, int cnt) {
  asm volatile("mbarrier.init.shared::cta.b64 [%0], %1;" ::"r"(bar), "r"(cnt) : "memory");
}
__device__ __forceinline__ void mbar_expect_tx(uint32_t bar, uint32_t bytes) {
  asm volatile("mbarrier.arrive.expect_tx.shared::cta.b64 _, [%0], %1;" ::"r"(bar), "r"(bytes) : "memory");
}
__device__ __forceinline__ void mbar_arrive(uint32_t bar) {
  asm volatile("mbarrier.arrive.shared::cta.b64 _, [%0];" ::"r"(bar) : "memory");
}
__device__ __forceinline__ void mbar_arrive_cluster(uint32_t cluster_addr) {
  asm volatile("mbarrier.arrive.shared::cluster.b64 _, [%0];" ::"r"(cluster_addr) : "memory");
}
__device__ __forceinline__ void mbar_wait(uint32_t bar, uint32_t parity) {
  asm volatile(
      "{\n.reg .pred p;\n.reg .u32 c;\n"
      "mbarrier.try_wait.parity.shared::cta.b64 p, [%0], %1;\n"
      "@p bra DONE;\n"
      "mov.u32 c, 0;\n"
      "RETRY:\n"
      "mbarrier.try_wait.parity.shared::cta.b64 p, [%0], %1;\n"
      "@p bra DONE;\n"
      "add.u32 c, c, 1;\n"
      "setp.lt.u32 p, c, %2;\n"
      "@p bra RETRY;\n"
      "trap;\n"
      "DONE:\n}" ::"r"(bar), "r"(parity), "n"(kSpinLimit)
      : "memory");
}
__device__ __forceinline__ void tma3d(uint32_t dst, const CUtensorMap* m, uint32_t bar, int c0, int c1, int c2) {
  asm volatile(
      "cp.async.bulk.tensor.3d.shared::cluster.global.mbarrier::complete_tx::bytes [%0], [%1, {%3, %4, %5}], [%2];"
      ::"r"(dst), "l"(m), "r"(bar), "r"(c0), "r"(c1), "r"(c2) : "memory");
}
__device__ __forceinline__ void tma4d(uint32_t dst, const CUtensorMap* m, uint32_t bar, int c0, int c3) {
  asm volatile(
      "cp.async.bulk.tensor.4d.shared::cluster.global.mbarrier::complete_tx::bytes [%0], [%1, {%3, 0, 0, %4}], [%2];"
      ::"r"(dst), "l"(m), "r"(bar), "r"(c0), "r"(c3) : "memory");
}
__device__ __forceinline__ void tma4d_mc(uint32_t dst, const CUtensorMap* m, uint32_t bar, int c0, int c3) {
  asm volatile(
      "cp.async.bulk.tensor.4d.shared::cluster.global.mbarrier::complete_tx::bytes.multicast::cluster"
      " [%0], [%1, {%3, 0, 0, %4}], [%2], %5;"
      ::"r"(dst), "l"(m), "r"(bar), "r"(c0), "r"(c3), "h"((uint16_t)3) : "memory");
}
__device__ __forceinline__ void tma4d_store(const CUtensorMap* m, uint32_t src, int c0, int c3) {
  asm volatile("cp.async.bulk.tensor.4d.global.shared::cta.bulk_group [%0, {%2, 0, 0, %3}], [%1];"
               ::"l"(m), "r"(src), "r"(c0), "r"(c3) : "memory");
}
__device__ __forceinline__ void bulk_load_mc(uint32_t dst, const void* src, uint32_t bytes, uint32_t bar) {
  asm volatile(
      "cp.async.bulk.shared::cluster.global.mbarrier::complete_tx::bytes.multicast::cluster [%0], [%1], %2, [%3], %4;"
      ::"r"(dst), "l"(src), "r"(bytes), "r"(bar), "h"((uint16_t)3) : "memory");
}
__device__ __forceinline__ void bulk_copy_peer(uint32_t dst_cl, uint32_t src, uint32_t bytes, uint32_t bar_cl) {
  asm volatile("cp.async.bulk.shared::cluster.shared::cta.mbarrier::complete_tx::bytes [%0], [%1], %2, [%3];"
               ::"r"(dst_cl), "r"(src), "r"(bytes), "r"(bar_cl) : "memory");
}
__device__ __forceinline__ void bulk_store(void* dst, uint32_t src, uint32_t bytes) {
  asm volatile("cp.async.bulk.global.shared::cta.bulk_group [%0], [%1], %2;" ::"l"(dst), "r"(src), "r"(bytes)
               : "memory");
}
__device__ __forceinline__ void bulk_commit() { asm volatile("cp.async.bulk.commit_group;" ::: "memory"); }
__device__ __forceinline__ void bulk_wait_read() { asm volatile("cp.async.bulk.wait_group.read 0;" ::: "memory"); }
__device__ __forceinline__ void bulk_wait() { asm volatile("cp.async.bulk.wait_group 0;" ::: "memory"); }
__device__ __forceinline__ void l2_prefetch(const void* p, uint32_t bytes) {
  asm volatile("cp.async.bulk.prefetch.L2.global [%0], %1;" ::"l"(p), "r"(bytes) : "memory");
}
__device__ __forceinline__ void fence_async_smem() { asm volatile("fence.proxy.async.shared::cta;" ::: "memory"); }
__device__ __forceinline__ void fence_async_global() { asm volatile("fence.proxy.async.global;" ::: "memory"); }
__device__ __forceinline__ unsigned ld_acquire(const unsigned* p) {
  unsigned v;
  asm volatile("ld.acquire.gpu.global.u32 %0, [%1];" : "=r"(v) : "l"(p) : "memory");
  return v;
}
__device__ __forceinline__ void st_release(unsigned* p, unsigned v) {
  asm volatile("st.release.gpu.global.u32 [%0], %1;" ::"l"(p), "r"(v) : "memory");
}
__device__ __forceinline__ void wait_flags(const unsigned* p, bool need, unsigned epoch) {
  unsigned spins = 0;
  while (true) {
    unsigned v = need ? ld_acquire(p) : epoch;
    if (__all_sync(0xffffffffu, v == epoch)) break;
    if (++spins > kSpinLimit) __trap();
  }
  __syncwarp();
}
__device__ __forceinline__ void stsm4(uint32_t a, uint32_t r0, uint32_t r1, uint32_t r2, uint32_t r3) {
  asm volatile("stmatrix.sync.aligned.m8n8.x4.shared.b16 [%0], {%1, %2, %3, %4};" ::"r"(a), "r"(r0), "r"(r1),
               "r"(r2), "r"(r3) : "memory");
}
__device__ __forceinline__ void ldsm4(uint32_t a, uint32_t (&r)[4]) {
  asm volatile("ldmatrix.sync.aligned.m8n8.x4.shared.b16 {%0, %1, %2, %3}, [%4];"
               : "=r"(r[0]), "=r"(r[1]), "=r"(r[2]), "=r"(r[3]) : "r"(a) : "memory");
}
__device__ __forceinline__ uint32_t pack2(float lo, float hi) {
  uint32_t r;
  asm("cvt.rn.bf16x2.f32 %0, %1, %2;" : "=r"(r) : "f"(hi), "f"(lo));
  return r;
}
__device__ __forceinline__ float bf_lo(uint32_t r) { return __uint_as_float(r << 16); }
__device__ __forceinline__ float bf_hi(uint32_t r) { return __uint_as_float(r & 0xffff0000u); }
__device__ __forceinline__ float ex2(float x) {
  float r;
  asm("ex2.approx.ftz.f32 %0, %1;" : "=f"(r) : "f"(x));
  return r;
}
__device__ __forceinline__ float rcp(float x) {
  float r;
  asm("rcp.approx.ftz.f32 %0, %1;" : "=f"(r) : "f"(x));
  return r;
}
__device__ __forceinline__ void wg_fence() { asm volatile("wgmma.fence.sync.aligned;" ::: "memory"); }
__device__ __forceinline__ void wg_commit() { asm volatile("wgmma.commit_group.sync.aligned;" ::: "memory"); }
template <int N>
__device__ __forceinline__ void wg_wait() {
  asm volatile("wgmma.wait_group.sync.aligned %0;" ::"n"(N) : "memory");
}
__device__ __forceinline__ void wg_bar(int wg) { asm volatile("bar.sync %0, 128;" ::"r"(wg + 1) : "memory"); }

template <int N>
__device__ __forceinline__ void wgmma(float (&d)[96], uint64_t da, uint64_t db);

template <>
__device__ __forceinline__ void wgmma<128>(float (&d)[96], uint64_t da, uint64_t db) {
  asm volatile(
      "wgmma.mma_async.sync.aligned.m64n128k16.f32.bf16.bf16 {"
      "%0, %1, %2, %3, %4, %5, %6, %7, %8, %9, %10, %11, %12, %13, %14, %15, "
      "%16, %17, %18, %19, %20, %21, %22, %23, %24, %25, %26, %27, %28, %29, %30, %31, "
      "%32, %33, %34, %35, %36, %37, %38, %39, %40, %41, %42, %43, %44, %45, %46, %47, "
      "%48, %49, %50, %51, %52, %53, %54, %55, %56, %57, %58, %59, %60, %61, %62, %63"
      "}, %64, %65, 1, 1, 1, 0, 1;\n"
      : "+f"(d[0]), "+f"(d[1]), "+f"(d[2]), "+f"(d[3]), "+f"(d[4]), "+f"(d[5]), "+f"(d[6]), "+f"(d[7]),
        "+f"(d[8]), "+f"(d[9]), "+f"(d[10]), "+f"(d[11]), "+f"(d[12]), "+f"(d[13]), "+f"(d[14]), "+f"(d[15]),
        "+f"(d[16]), "+f"(d[17]), "+f"(d[18]), "+f"(d[19]), "+f"(d[20]), "+f"(d[21]), "+f"(d[22]), "+f"(d[23]),
        "+f"(d[24]), "+f"(d[25]), "+f"(d[26]), "+f"(d[27]), "+f"(d[28]), "+f"(d[29]), "+f"(d[30]), "+f"(d[31]),
        "+f"(d[32]), "+f"(d[33]), "+f"(d[34]), "+f"(d[35]), "+f"(d[36]), "+f"(d[37]), "+f"(d[38]), "+f"(d[39]),
        "+f"(d[40]), "+f"(d[41]), "+f"(d[42]), "+f"(d[43]), "+f"(d[44]), "+f"(d[45]), "+f"(d[46]), "+f"(d[47]),
        "+f"(d[48]), "+f"(d[49]), "+f"(d[50]), "+f"(d[51]), "+f"(d[52]), "+f"(d[53]), "+f"(d[54]), "+f"(d[55]),
        "+f"(d[56]), "+f"(d[57]), "+f"(d[58]), "+f"(d[59]), "+f"(d[60]), "+f"(d[61]), "+f"(d[62]), "+f"(d[63])
      : "l"(da), "l"(db));
}

template <>
__device__ __forceinline__ void wgmma<192>(float (&d)[96], uint64_t da, uint64_t db) {
  asm volatile(
      "wgmma.mma_async.sync.aligned.m64n192k16.f32.bf16.bf16 {"
      "%0, %1, %2, %3, %4, %5, %6, %7, %8, %9, %10, %11, %12, %13, %14, %15, "
      "%16, %17, %18, %19, %20, %21, %22, %23, %24, %25, %26, %27, %28, %29, %30, %31, "
      "%32, %33, %34, %35, %36, %37, %38, %39, %40, %41, %42, %43, %44, %45, %46, %47, "
      "%48, %49, %50, %51, %52, %53, %54, %55, %56, %57, %58, %59, %60, %61, %62, %63, "
      "%64, %65, %66, %67, %68, %69, %70, %71, %72, %73, %74, %75, %76, %77, %78, %79, "
      "%80, %81, %82, %83, %84, %85, %86, %87, %88, %89, %90, %91, %92, %93, %94, %95"
      "}, %96, %97, 1, 1, 1, 0, 1;\n"
      : "+f"(d[0]), "+f"(d[1]), "+f"(d[2]), "+f"(d[3]), "+f"(d[4]), "+f"(d[5]), "+f"(d[6]), "+f"(d[7]),
        "+f"(d[8]), "+f"(d[9]), "+f"(d[10]), "+f"(d[11]), "+f"(d[12]), "+f"(d[13]), "+f"(d[14]), "+f"(d[15]),
        "+f"(d[16]), "+f"(d[17]), "+f"(d[18]), "+f"(d[19]), "+f"(d[20]), "+f"(d[21]), "+f"(d[22]), "+f"(d[23]),
        "+f"(d[24]), "+f"(d[25]), "+f"(d[26]), "+f"(d[27]), "+f"(d[28]), "+f"(d[29]), "+f"(d[30]), "+f"(d[31]),
        "+f"(d[32]), "+f"(d[33]), "+f"(d[34]), "+f"(d[35]), "+f"(d[36]), "+f"(d[37]), "+f"(d[38]), "+f"(d[39]),
        "+f"(d[40]), "+f"(d[41]), "+f"(d[42]), "+f"(d[43]), "+f"(d[44]), "+f"(d[45]), "+f"(d[46]), "+f"(d[47]),
        "+f"(d[48]), "+f"(d[49]), "+f"(d[50]), "+f"(d[51]), "+f"(d[52]), "+f"(d[53]), "+f"(d[54]), "+f"(d[55]),
        "+f"(d[56]), "+f"(d[57]), "+f"(d[58]), "+f"(d[59]), "+f"(d[60]), "+f"(d[61]), "+f"(d[62]), "+f"(d[63]),
        "+f"(d[64]), "+f"(d[65]), "+f"(d[66]), "+f"(d[67]), "+f"(d[68]), "+f"(d[69]), "+f"(d[70]), "+f"(d[71]),
        "+f"(d[72]), "+f"(d[73]), "+f"(d[74]), "+f"(d[75]), "+f"(d[76]), "+f"(d[77]), "+f"(d[78]), "+f"(d[79]),
        "+f"(d[80]), "+f"(d[81]), "+f"(d[82]), "+f"(d[83]), "+f"(d[84]), "+f"(d[85]), "+f"(d[86]), "+f"(d[87]),
        "+f"(d[88]), "+f"(d[89]), "+f"(d[90]), "+f"(d[91]), "+f"(d[92]), "+f"(d[93]), "+f"(d[94]), "+f"(d[95])
      : "l"(da), "l"(db));
}

__device__ __forceinline__ int tile_first_seq(int layer, int ty) { return layer * 152 + ty * 16; }
__device__ __forceinline__ int tile_first_slot(int i) { return (int)((0x21004333211000ull >> (4 * i)) & 7); }
__device__ __forceinline__ bool tile_wide(int ty) { return ty == 0 || ty == 1 || ty == 3; }
__device__ __forceinline__ bool tile_uses_x(int ty) { return ty != 2 && ty != 6; }
__device__ __forceinline__ int ring_depth(int ty, int kk) {
  return (tile_wide(ty) || ((ty == 2 || ty == 4) && kk < 4)) ? 4 : 5;
}
__device__ __forceinline__ int x_kblock(int j, int kk) {
  return kk < 4 ? ((2 * j) ^ kk) : ((2 * (j & 6) + kk) & 15);
}

template <int N>
__device__ __forceinline__ void fence_acc(float (&acc)[2][96]) {
#pragma unroll
  for (int h = 0; h < 2; h++)
#pragma unroll
    for (int i = 0; i < N / 2; i++) asm volatile("" : "+f"(acc[h][i])::"memory");
}

template <int N, bool USEX>
__device__ __forceinline__ void mainloop(float (&acc)[2][96], uint32_t sb, int tile, int n0, int nkb, int xver,
                                         uint32_t rel_addr, bool rel) {
  constexpr int kSlotBytes = (N == 192 ? 5 : 4) * 8192;
  constexpr int kSlots = N == 192 ? 4 : 5;
  constexpr uint64_t kDescA = (1ull << 62) | ((uint64_t)(2048 >> 4) << 32) | (1ull << 16);
  constexpr uint64_t kDescB = (1ull << 62) | ((uint64_t)(1024 >> 4) << 32) | ((uint64_t)(8192 >> 4) << 16);
  int slot = tile_first_slot(tile);
  if (USEX) {
#pragma unroll
    for (int h = 0; h < 2; h++)
#pragma unroll
      for (int i = 0; i < N / 2; i++) acc[h][i] = 0.f;
  }
  fence_acc<N>(acc);
  if (tile > 0) mbar_wait(sb + kBarTurn + (tile - 1) * 8, 0);
  if (USEX) mbar_wait(sb + kBarX + xver * 8, 0);
  TRACE_AT(tile, 0);
#pragma unroll 1
  for (int kk = 0; kk < nkb; kk++) {
    const int n = n0 + kk;
    mbar_wait(sb + kBarFull + (n & 7) * 8, (n >> 3) & 1);
    if (kk == 0) TRACE_AT(tile, 1);
    const uint32_t st = (sb & 0x3FFFF) + kSmRing + slot * kSlotBytes;
    const uint32_t a = (USEX && kk < 2) ? (sb & 0x3FFFF) + kSmX + kk * kTileBytes : st;
    const uint64_t da = kDescA | (uint64_t)(a >> 4);
    const uint64_t db = kDescB | (uint64_t)((st + kTileBytes) >> 4);
    wg_fence();
#pragma unroll
    for (int k = 0; k < 4; k++) {
      wgmma<N>(acc[0], da + k * 2, db + k * 128);
      wgmma<N>(acc[1], da + k * 2 + 64, db + k * 128);
    }
    wg_commit();
    if (kk == nkb - 1 && (threadIdx.x & 127) == 64) mbar_arrive(sb + kBarTurn + tile * 8);
    wg_wait<1>();
    if (rel && kk > 0) mbar_arrive_cluster(rel_addr + ((n - 1) & 7) * 8);
    slot = slot + 1 == kSlots ? 0 : slot + 1;
  }
  wg_wait<0>();
  if (rel) mbar_arrive_cluster(rel_addr + ((n0 + nkb - 1) & 7) * 8);
  fence_acc<N>(acc);
}

__device__ __forceinline__ void publish_stats(const uint32_t (&pk)[16][4], int b, int j, int w, int lane) {
  float s[4], q[4];
#pragma unroll
  for (int c = 0; c < 4; c++) {
    float a0 = 0.f, a1 = 0.f;
#pragma unroll
    for (int J = 0; J < 16; J++) {
      a0 += bf_lo(pk[J][c]);
      a1 += bf_hi(pk[J][c]);
    }
    s[c] = a0 + a1;
  }
#pragma unroll
  for (int c = 0; c < 4; c++) {
    s[c] += __shfl_xor_sync(0xffffffffu, s[c], 1);
    s[c] += __shfl_xor_sync(0xffffffffu, s[c], 2);
  }
#pragma unroll
  for (int c = 0; c < 4; c++) {
    const float m = s[c] * (1.f / 128.f);
    float a0 = 0.f, a1 = 0.f;
#pragma unroll
    for (int J = 0; J < 16; J++) {
      const float d0 = bf_lo(pk[J][c]) - m, d1 = bf_hi(pk[J][c]) - m;
      a0 = fmaf(d0, d0, a0);
      a1 = fmaf(d1, d1, a1);
    }
    q[c] = a0 + a1;
  }
#pragma unroll
  for (int c = 0; c < 4; c++) {
    q[c] += __shfl_xor_sync(0xffffffffu, q[c], 1);
    q[c] += __shfl_xor_sync(0xffffffffu, q[c], 2);
  }
  const int t = lane & 3, g = lane >> 2;
  const float so = t == 0 ? s[0] : t == 1 ? s[1] : t == 2 ? s[2] : s[3];
  const float qo = t == 0 ? q[0] : t == 1 ? q[1] : t == 2 ? q[2] : q[3];
  g_stat[(b * 128 + 32 * w + 8 * t + g) * 8 + j] = make_float2(so, qo);
}

__device__ __forceinline__ void colsum_slab(const __nv_bfloat16* wt, int ld, int col0, float* out, unsigned* flag,
                                            unsigned epoch, uint8_t* sm, int wg) {
  const int tid = threadIdx.x & 127, lane = tid & 31, w = tid >> 5;
  const uint4* p = reinterpret_cast<const uint4*>(wt + (size_t)(tid >> 2) * ld + col0 + (tid & 3) * 8);
  uint4 v[32];
#pragma unroll
  for (int i = 0; i < 32; i++) v[i] = __ldg(p + (size_t)i * ld * 4);
  float a[8];
#pragma unroll
  for (int e = 0; e < 8; e++) a[e] = 0.f;
#pragma unroll
  for (int i = 0; i < 32; i++) {
    a[0] += bf_lo(v[i].x); a[1] += bf_hi(v[i].x);
    a[2] += bf_lo(v[i].y); a[3] += bf_hi(v[i].y);
    a[4] += bf_lo(v[i].z); a[5] += bf_hi(v[i].z);
    a[6] += bf_lo(v[i].w); a[7] += bf_hi(v[i].w);
  }
#pragma unroll
  for (int e = 0; e < 8; e++) {
    a[e] += __shfl_xor_sync(0xffffffffu, a[e], 4);
    a[e] += __shfl_xor_sync(0xffffffffu, a[e], 8);
    a[e] += __shfl_xor_sync(0xffffffffu, a[e], 16);
  }
  float* red = reinterpret_cast<float*>(sm + kSmRed);
  if (lane < 4) {
#pragma unroll
    for (int e = 0; e < 8; e++) red[w * 32 + lane * 8 + e] = a[e];
  }
  wg_bar(wg);
  if (w == 0) {
    out[col0 + lane] = (red[lane] + red[32 + lane]) + (red[64 + lane] + red[96 + lane]);
    __syncwarp();
    if (lane == 0) st_release(flag, epoch);
  }
}

__device__ __forceinline__ float gelu_tanh(float u) {
  constexpr float c0 = -2.f * 0.7978845608028654f * 1.4426950408889634f;
  constexpr float c1 = c0 * 0.044715f;
  const float e = ex2(u * fmaf(u * u, c1, c0));
  return u * rcp(1.f + e);
}

template <int N>
__device__ __forceinline__ void epilogue_gelu(float (&acc)[2][96], uint8_t* sm, uint32_t sb, int vcol0,
                                              uint8_t* dst, unsigned* flag, unsigned epoch, int tile) {
  const int lane = threadIdx.x & 31, w = (threadIdx.x >> 5) & 3, t = lane & 3, g = lane >> 2;
  float2 st[4];
#pragma unroll
  for (int c = 0; c < 4; c++) st[c] = reinterpret_cast<const float2*>(sm + kSmStat)[32 * w + 8 * c + g];
  const float4* vec = reinterpret_cast<const float4*>(sm + kSmV1) + vcol0 / 2 + t;
  const uint32_t stg = sb + kSmStg + w * 4096;
  const uint32_t row = stg + lane * 128;
#pragma unroll
  for (int ch = 0; ch < N / 64; ch++) {
    uint32_t pk[8][4];
#pragma unroll
    for (int jj = 0; jj < 8; jj++) {
      const int J = ch * 8 + jj;
      const float4 v = vec[J * 4];
#pragma unroll
      for (int c = 0; c < 4; c++) {
        const float u0 = fmaf(acc[c & 1][4 * J + (c & 2)], st[c].x, fmaf(st[c].y, v.x, v.z));
        const float u1 = fmaf(acc[c & 1][4 * J + (c & 2) + 1], st[c].x, fmaf(st[c].y, v.y, v.w));
        pk[jj][c] = pack2(gelu_tanh(u0), gelu_tanh(u1));
      }
    }
    if (ch > 0) {
      if (lane == 0) bulk_wait_read();
      __syncwarp();
    }
#pragma unroll
    for (int jj = 0; jj < 8; jj++) stsm4(row + ((jj ^ (lane & 7)) << 4), pk[jj][0], pk[jj][1], pk[jj][2], pk[jj][3]);
    fence_async_smem();
    __syncwarp();
    if (lane == 0) {
      bulk_store(dst + ch * kTileBytes + w * 4096, stg, 4096);
      bulk_commit();
    }
  }
  if (lane == 0) {
    bulk_wait();
    mbar_arrive(sb + kBarEpi + tile * 8);
    st_release(flag, epoch);
  }
  __syncwarp();
}

template <int M>
__device__ __forceinline__ void window_row(const uint32_t (&x)[4][4], uint32_t halo, int lane, float (&f)[8]) {
  uint32_t r[4];
  if (M >= 7) {
#pragma unroll
    for (int i = 0; i < 4; i++) r[i] = x[M >= 7 ? M - 7 : 0][i];
  } else {
    constexpr int c = M >= 3 ? M - 3 : M + 1;
    constexpr int sh = M >= 3 ? 4 : 8;
#pragma unroll
    for (int i = 0; i < 4; i++) r[i] = __shfl_up_sync(0xffffffffu, x[c & 3][i], sh);
    asm volatile("{\n.reg .pred p;\nsetp.lt.s32 p, %5, %6;\n@p ld.shared.v4.u32 {%0, %1, %2, %3}, [%4];\n}"
                 : "+r"(r[0]), "+r"(r[1]), "+r"(r[2]), "+r"(r[3])
                 : "r"(halo + c * 128 + (8 - sh) * 16), "r"(lane), "n"(sh));
  }
#pragma unroll
  for (int i = 0; i < 4; i++) {
    f[2 * i] = bf_lo(r[i]);
    f[2 * i + 1] = bf_hi(r[i]);
  }
}

template <int M>
__device__ __forceinline__ void score_row(const uint32_t (&k)[4][4], uint32_t halo, int lane,
                                          const float (&q)[4][8], float (&s)[4][8]) {
  float f[8];
  window_row<M>(k, halo, lane, f);
#pragma unroll
  for (int c = 0; c < 4; c++) {
    if (M - c >= 0 && M - c < 8) {
      float a = q[c][0] * f[0];
#pragma unroll
      for (int e = 1; e < 8; e++) a = fmaf(q[c][e], f[e], a);
      s[c][(M - c) & 7] = a;
    }
  }
}

template <int M>
__device__ __forceinline__ void value_row(const uint32_t (&v)[4][4], uint32_t halo, int lane,
                                          const float (&p)[4][8], float (&o)[4][8]) {
  float f[8];
  window_row<M>(v, halo, lane, f);
#pragma unroll
  for (int c = 0; c < 4; c++) {
    if (M - c >= 0 && M - c < 8) {
#pragma unroll
      for (int e = 0; e < 8; e++) o[c][e] = fmaf(p[c][(M - c) & 7], f[e], o[c][e]);
    }
  }
}

__device__ __forceinline__ void attend_head(const float (&q)[4][8], const uint32_t (&k)[4][4],
                                            const uint32_t (&v)[4][4], uint32_t halo_k, uint32_t halo_v, int lane,
                                            int tokpos, uint32_t row, int chunk0) {
  float s[4][8];
  score_row<10>(k, halo_k, lane, q, s); score_row<9>(k, halo_k, lane, q, s);
  score_row<8>(k, halo_k, lane, q, s);  score_row<7>(k, halo_k, lane, q, s);
  score_row<6>(k, halo_k, lane, q, s);  score_row<5>(k, halo_k, lane, q, s);
  score_row<4>(k, halo_k, lane, q, s);  score_row<3>(k, halo_k, lane, q, s);
  score_row<2>(k, halo_k, lane, q, s);  score_row<1>(k, halo_k, lane, q, s);
  score_row<0>(k, halo_k, lane, q, s);
  const bool hi2 = lane & 2, hi1 = lane & 1;
  float r2[2][8], r1[8];
#pragma unroll
  for (int c = 0; c < 2; c++)
#pragma unroll
    for (int u = 0; u < 8; u++) {
      const float keep = hi2 ? s[c + 2][u] : s[c][u];
      const float send = hi2 ? s[c][u] : s[c + 2][u];
      r2[c][u] = keep + __shfl_xor_sync(0xffffffffu, send, 2);
    }
#pragma unroll
  for (int u = 0; u < 8; u++) {
    const float keep = hi1 ? r2[1][u] : r2[0][u];
    const float send = hi1 ? r2[0][u] : r2[1][u];
    r1[u] = keep + __shfl_xor_sync(0xffffffffu, send, 1);
  }
  constexpr float kScale = 0.17677669529663687f * 1.4426950408889634f;
  float mx = r1[7];
#pragma unroll
  for (int u = 0; u < 7; u++) {
    if (tokpos + u < 7) r1[u] = -INFINITY;
    mx = fmaxf(mx, r1[u]);
  }
  float sum = 0.f;
#pragma unroll
  for (int u = 0; u < 8; u++) {
    r1[u] = ex2((r1[u] - mx) * kScale);
    sum += r1[u];
  }
  const float inv = rcp(sum);
  float p[4][8];
#pragma unroll
  for (int u = 0; u < 8; u++) {
    const float pn = r1[u] * inv;
#pragma unroll
    for (int c = 0; c < 4; c++) p[c][u] = __shfl_sync(0xffffffffu, pn, c, 4);
  }
  float o[4][8];
#pragma unroll
  for (int c = 0; c < 4; c++)
#pragma unroll
    for (int e = 0; e < 8; e++) o[c][e] = 0.f;
  value_row<10>(v, halo_v, lane, p, o); value_row<9>(v, halo_v, lane, p, o);
  value_row<8>(v, halo_v, lane, p, o);  value_row<7>(v, halo_v, lane, p, o);
  value_row<6>(v, halo_v, lane, p, o);  value_row<5>(v, halo_v, lane, p, o);
  value_row<4>(v, halo_v, lane, p, o);  value_row<3>(v, halo_v, lane, p, o);
  value_row<2>(v, halo_v, lane, p, o);  value_row<1>(v, halo_v, lane, p, o);
  value_row<0>(v, halo_v, lane, p, o);
#pragma unroll
  for (int jj = 0; jj < 4; jj++)
    stsm4(row + (((chunk0 + jj) ^ (lane & 7)) << 4), pack2(o[0][2 * jj], o[0][2 * jj + 1]),
          pack2(o[1][2 * jj], o[1][2 * jj + 1]), pack2(o[2][2 * jj], o[2][2 * jj + 1]),
          pack2(o[3][2 * jj], o[3][2 * jj + 1]));
}

__device__ __forceinline__ void epilogue_attn(float (&acc)[2][96], uint8_t* sm, uint32_t sb, int layer, int tq,
                                              int b, int j, unsigned epoch, int tile, int wg) {
  const int lane = threadIdx.x & 31, w = (threadIdx.x >> 5) & 3, t = lane & 3, g = lane >> 2;
  const int hp = j + 8 * tq;
  float2 st[4];
#pragma unroll
  for (int c = 0; c < 4; c++) st[c] = reinterpret_cast<const float2*>(sm + kSmStat)[32 * w + 8 * c + g];
  const float2* cs = reinterpret_cast<const float2*>(sm + kSmCsQ) + tq * 96 + t;
  uint32_t kv[4][4][4];
#pragma unroll
  for (int a = 0; a < 4; a++)
#pragma unroll
    for (int jj = 0; jj < 4; jj++) {
      const int J = 8 + 4 * a + jj;
      const float2 v = cs[J * 4];
#pragma unroll
      for (int c = 0; c < 4; c++)
        kv[a][c][jj] = pack2(fmaf(acc[c & 1][4 * J + (c & 2)], st[c].x, st[c].y * v.x),
                             fmaf(acc[c & 1][4 * J + (c & 2) + 1], st[c].x, st[c].y * v.y));
    }
  uint8_t* hout = w < 3 ? sm + kSmHalo + (w + 1) * 2048 : sm + kSmStg + 3 * 4096;
  if (lane >= 24) {
#pragma unroll
    for (int a = 0; a < 4; a++)
#pragma unroll
      for (int c = 0; c < 4; c++)
        *reinterpret_cast<uint4*>(hout + (a * 4 + c) * 128 + (lane - 24) * 16) =
            make_uint4(kv[a][c][0], kv[a][c][1], kv[a][c][2], kv[a][c][3]);
  }
  if (w == 3 && (b & 7) != 7) {
    __syncwarp();
    uint4* gh = g_halo + ((layer * 16 + b) * 16 + hp) * 256 + lane;
#pragma unroll
    for (int i = 0; i < 8; i++) {
      const uint2 d = *reinterpret_cast<const uint2*>(hout + (i * 32 + lane) * 8);
      asm volatile("st.relaxed.gpu.global.v2.b64 [%0], {%1, %2};" ::"l"(gh + i * 32),
                   "l"(((uint64_t)epoch << 32) | d.x), "l"(((uint64_t)epoch << 32) | d.y) : "memory");
    }
  }
  float q[2][4][8];
#pragma unroll
  for (int J = 0; J < 8; J++) {
    const float2 v = cs[J * 4];
#pragma unroll
    for (int c = 0; c < 4; c++) {
      q[J >> 2][c][2 * (J & 3)] = fmaf(acc[c & 1][4 * J + (c & 2)], st[c].x, st[c].y * v.x);
      q[J >> 2][c][2 * (J & 3) + 1] = fmaf(acc[c & 1][4 * J + (c & 2) + 1], st[c].x, st[c].y * v.y);
    }
  }
  wg_bar(wg);
  if (w == 0) {
    uint2* hin = reinterpret_cast<uint2*>(sm + kSmHalo) + lane;
    if ((b & 7) == 0) {
#pragma unroll
      for (int i = 0; i < 8; i++) hin[i * 32] = make_uint2(0u, 0u);
    } else {
      const uint4* gh = g_halo + ((layer * 16 + b - 1) * 16 + hp) * 256 + lane;
      unsigned spins = 0;
      while (true) {
        uint64_t d[8][2];
#pragma unroll
        for (int i = 0; i < 8; i++)
          asm volatile("ld.relaxed.gpu.global.v2.b64 {%0, %1}, [%2];"
                       : "=l"(d[i][0]), "=l"(d[i][1]) : "l"(gh + i * 32) : "memory");
        bool ok = true;
#pragma unroll
        for (int i = 0; i < 8; i++) {
          ok = ok && (unsigned)(d[i][0] >> 32) == epoch && (unsigned)(d[i][1] >> 32) == epoch;
          hin[i * 32] = make_uint2((unsigned)d[i][0], (unsigned)d[i][1]);
        }
        if (__all_sync(0xffffffffu, ok)) break;
        if (++spins > kSpinLimit) __trap();
      }
    }
    __syncwarp();
  }
  const uint32_t halo = sb + kSmHalo + w * 2048 + lane * 16;
  const uint32_t stg = sb + kSmStg + w * 4096;
  const int tokpos = (b & 7) * 128 + 32 * w + lane;
  attend_head(q[0], kv[0], kv[2], halo, halo + 1024, lane, tokpos, stg + lane * 128, 0);
  attend_head(q[1], kv[1], kv[3], halo + 512, halo + 1536, lane, tokpos, stg + lane * 128, 4);
  fence_async_smem();
  __syncwarp();
  if (lane == 0) {
    bulk_store(g_o + (b * 16 + hp) * kTileBytes + w * 4096, stg, 4096);
    bulk_commit();
    bulk_wait();
    st_release(&g_flag[(kFlagO + (layer * 2 + tq) * 16 + b) * 32 + j * 4 + w], epoch);
    mbar_arrive(sb + kBarEpi + tile * 8);
  }
  __syncwarp();
}

__device__ __forceinline__ void reduce_stats(uint8_t* sm, int b, int lane) {
#pragma unroll 1
  for (int i = 0; i < 4; i++) {
    const int r = i * 32 + lane;
    const float4* p = reinterpret_cast<const float4*>(g_stat + (b * 128 + r) * 8);
    const float4 a0 = __ldcg(p), a1 = __ldcg(p + 1), a2 = __ldcg(p + 2), a3 = __ldcg(p + 3);
    const float mean = (((a0.x + a0.z) + (a1.x + a1.z)) + ((a2.x + a2.z) + (a3.x + a3.z))) * (1.f / 1024.f);
    float m2 = ((a0.y + a0.w) + (a1.y + a1.w)) + ((a2.y + a2.w) + (a3.y + a3.w));
    const float sj[8] = {a0.x, a0.z, a1.x, a1.z, a2.x, a2.z, a3.x, a3.z};
    float dd = 0.f;
#pragma unroll
    for (int e = 0; e < 8; e++) {
      const float d = fmaf(sj[e], 1.f / 128.f, -mean);
      dd = fmaf(d, d, dd);
    }
    m2 = fmaf(dd, 128.f, m2);
    const float rstd = rsqrtf(fmaf(m2, 1.f / 1024.f, 1e-5f));
    reinterpret_cast<float2*>(sm + kSmStat)[r] = make_float2(rstd, -mean * rstd);
  }
}

__global__ void __cluster_dims__(2, 1, 1) __launch_bounds__(384, 1)
fused_layers_kernel(const __grid_constant__ CUtensorMap map_x, const __grid_constant__ CUtensorMap map_out,
                    const __grid_constant__ CUtensorMap map_qkv, const __grid_constant__ CUtensorMap map_wo,
                    const __grid_constant__ CUtensorMap map_w1a, const __grid_constant__ CUtensorMap map_w1b,
                    const __grid_constant__ CUtensorMap map_w2, const Params prm) {
  extern __shared__ __align__(1024) uint8_t sm[];
  const uint32_t sb = smem_u32(sm);
  const int warp = threadIdx.x >> 5, lane = threadIdx.x & 31;
  const int cta = blockIdx.x, b = cta >> 3, j = cta & 7, rank = cta & 1;
  const int xcol = (b >> 3) * kD, xrow = (b & 7) * 4;

  if (threadIdx.x == 256) {
    if (sb & 1023) __trap();
    for (int s = 0; s < 8; s++) {
      mbar_init(sb + kBarFull + s * 8, 1);
      mbar_init(sb + kBarEmpty + s * 8, 2);
    }
    for (int s = 0; s < kTiles; s++) {
      mbar_init(sb + kBarTurn + s * 8, 1);
      mbar_init(sb + kBarEpi + s * 8, 4);
    }
    for (int s = 0; s < 4; s++) {
      mbar_init(sb + kBarX + s * 8, s == 0 ? 1 : 4);
      mbar_init(sb + kBarStat + s * 8, 1);
    }
    asm volatile("fence.mbarrier_init.release.cluster;" ::: "memory");
    fence_async_smem();
    mbar_expect_tx(sb + kBarX, 32768);
    for (int s = 0; s < 4; s++)
      tma4d(sb + kSmX + s * 8192, &map_x, sb + kBarX, xcol + j * 128 + (s >> 1) * 64, xrow + (s & 1) * 2);
  }
  if (threadIdx.x == 0) *reinterpret_cast<unsigned*>(sm + kSmEpoch) = atomicAdd(&g_ticket, 1u) / kCtas + 1;
  __syncwarp();
  asm volatile("barrier.cluster.arrive.release.aligned;" ::: "memory");

  if (warp >= 8) {
    asm volatile("setmaxnreg.dec.sync.aligned.u32 40;");
    if (warp == 8) {
      if (lane == 0) {
        int n = 0, m = 0;
        for (int i = 0; i < kRunTiles; i++) {
          const int ty = i >= 7 ? i - 7 : i;
          const bool wide = tile_wide(ty), usex = tile_uses_x(ty);
          const int nkb = ty == 6 ? 56 : 16;
          const CUtensorMap* map = ty < 2 ? &map_qkv : ty == 2 ? &map_wo : ty == 3 ? &map_w1a : ty < 6 ? &map_w1b : &map_w2;
          const int c0 = ty < 2 ? (j + 8 * ty) * 64 : 0;
          const int c2 = ty < 2 ? 0 : ty == 3 ? 3 * j : ty == 4 ? 24 + 2 * j : ty == 5 ? 40 + 2 * j : 2 * j;
          int slot = tile_first_slot(i);
          for (int kk = 0; kk < nkb; kk++, n++) {
            const int lim = n - ring_depth(ty, kk);
            for (; m <= lim; m++) mbar_wait(sb + kBarEmpty + (m & 7) * 8, (m >> 3) & 1);
            const uint32_t full = sb + kBarFull + (n & 7) * 8;
            mbar_expect_tx(full, (wide ? 24576 : 16384) + ((usex && kk < 2) ? 0 : kTileBytes));
            const int kb = usex ? x_kblock(j, kk) : kk;
            tma3d(sb + kSmRing + slot * (wide ? 40960 : 32768) + kTileBytes, map, full, c0, kb * 64, c2);
            slot = slot + 1 == (wide ? 4 : 5) ? 0 : slot + 1;
          }
        }
      }
      __syncwarp();
      asm volatile("barrier.cluster.wait.acquire.aligned;" ::: "memory");
    } else {
      asm volatile("barrier.cluster.wait.acquire.aligned;" ::: "memory");
      const unsigned epoch = *reinterpret_cast<volatile unsigned*>(sm + kSmEpoch);
      if (warp == 9) {
        int n = 0, m = 0;
        const bool my_rows = ((lane >> 1) & 1) == rank;
        const uint32_t peer = mapa(sb, rank ^ 1);
        for (int i = 0; i < kRunTiles; i++) {
          const int layer = i >= 7, ty = i - 7 * layer;
          const bool wide = tile_wide(ty), usex = tile_uses_x(ty);
          const int nkb = ty == 6 ? 56 : 16;
          const int xver = 2 * layer + (ty >= 3);
          const uint8_t* src = (ty == 6 ? g_h + b * 56 * kTileBytes : (ty == 2 ? g_o : g_x) + b * 16 * kTileBytes) + rank * 8192;
          int slot = tile_first_slot(i);
          for (int kk = 0; kk < nkb; kk++, n++) {
            if (!(usex && kk < 2)) {
              int line = -1;
              if (ty == 2) {
                if ((kk & 7) == 0) line = kFlagO + (layer * 2 + (kk >> 3)) * 16;
              } else if (ty == 6) {
                if (kk == 0 || kk == 24 || kk == 40) line = kFlagH + (layer * 3 + (kk >> 4)) * 16;
              } else if (kk == 4 && (ty == 0 || ty == 3) && xver > 0) {
                line = kFlagX + (xver - 1) * 16;
              }
              if (line >= 0) {
                wait_flags(&g_flag[(line + b) * 32 + lane], my_rows, epoch);
                fence_async_global();
              }
              if (lane == 0) {
                const int lim = n - ring_depth(ty, kk);
                for (; m <= lim; m++) mbar_wait(sb + kBarEmpty + (m & 7) * 8, (m >> 3) & 1);
                const uint32_t off = kSmRing + slot * (wide ? 40960 : 32768);
                const uint32_t full = kBarFull + (n & 7) * 8;
                if (usex && kk < 4) {
                  mbar_wait(sb + kBarX + xver * 8, 0);
                  bulk_copy_peer(peer + off, sb + kSmX + (kk - 2) * kTileBytes, kTileBytes, peer + full);
                } else {
                  const int kb = usex ? x_kblock(j, kk) : kk;
                  if (i < 2) tma4d_mc(sb + off + rank * 8192, &map_x, sb + full, xcol + kb * 64, xrow + rank * 2);
                  else bulk_load_mc(sb + off + rank * 8192, src + kb * kTileBytes, 8192, sb + full);
                }
              }
              __syncwarp();
            }
            slot = slot + 1 == (wide ? 4 : 5) ? 0 : slot + 1;
          }
        }
      } else if (warp == 10) {
        float* v1 = reinterpret_cast<float*>(sm + kSmV1);
        for (int i = lane; i < 448; i += 32) {
          const int col = i < 192 ? 192 * j + i : i < 320 ? 1536 + 128 * j + (i - 192) : 2560 + 128 * j + (i - 320);
          v1[(i >> 1) * 4 + 2 + (i & 1)] = __bfloat162float(prm.b1[col]);
        }
        for (int i = lane; i < 128; i += 32)
          reinterpret_cast<float*>(sm + kSmB2)[i] = __bfloat162float(prm.b2[128 * j + i]);
        {
          const int blk = lane >> 1;
          const int slab = (blk % 3) * 32 + (j + 8 * (blk / 3)) * 2 + (lane & 1);
          wait_flags(&g_flag[kFlagC * 32 + slab], lane < 12, epoch);
          for (int i = 0; i < 12; i++) {
            const int s = __shfl_sync(0xffffffffu, slab, i);
            reinterpret_cast<float*>(sm + kSmCsQ)[i * 32 + lane] = __ldcg(&g_cs[s * 32 + lane]);
          }
        }
        for (int q = 0; q < 1 + (kRunTiles > 2) + (kRunTiles > 6) + (kRunTiles > 9); q++) {
          if (q == 1) {
            const int slab = lane < 6 ? 6 * j + lane : lane < 10 ? 48 + 4 * j + (lane - 6) : 80 + 4 * j + (lane - 10);
            wait_flags(&g_flag[kFlagC * 32 + 96 + (lane < 14 ? slab : 0)], lane < 14, epoch);
            for (int i = 0; i < 14; i++) {
              const int s = __shfl_sync(0xffffffffu, slab, i), li = i * 32 + lane;
              v1[(li >> 1) * 4 + (li & 1)] = __ldcg(&g_cs[3 * kD + s * 32 + lane]);
            }
          }
          mbar_wait(sb + kBarX + q * 8, 0);
          wait_flags(&g_flag[(kFlagS + q * 16 + b) * 32 + lane], true, epoch);
          reduce_stats(sm, b, lane);
          __syncwarp();
          if (lane == 0) mbar_arrive(sb + kBarStat + q * 8);
        }
      } else if (lane == 0 && kRunTiles == kTiles) {
        const uint8_t* pq = reinterpret_cast<const uint8_t*>(prm.wqkv) + cta * 49152;
        const uint8_t* po = reinterpret_cast<const uint8_t*>(prm.wo) + cta * 16384;
        const uint8_t* p1 = reinterpret_cast<const uint8_t*>(prm.w1) + cta * 57344;
        const uint8_t* p2 = reinterpret_cast<const uint8_t*>(prm.w2) + cta * 57344;
        mbar_wait(sb + kBarTurn + 0 * 8, 0);
        l2_prefetch(po, 16384);
        mbar_wait(sb + kBarTurn + 3 * 8, 0);
        for (int s = 0; s < 7; s++) l2_prefetch(p2 + s * 8192, 8192);
        mbar_wait(sb + kBarTurn + 5 * 8, 0);
        for (int s = 0; s < 6; s++) l2_prefetch(pq + s * 8192, 8192);
        mbar_wait(sb + kBarTurn + 7 * 8, 0);
        l2_prefetch(po, 16384);
        for (int s = 0; s < 7; s++) l2_prefetch(p1 + s * 8192, 8192);
        mbar_wait(sb + kBarTurn + 10 * 8, 0);
        for (int s = 0; s < 7; s++) l2_prefetch(p2 + s * 8192, 8192);
      }
    }
    __syncwarp();
    asm volatile("barrier.cluster.arrive.relaxed.aligned;\nbarrier.cluster.wait.aligned;" ::: "memory");
  } else {
    asm volatile("setmaxnreg.inc.sync.aligned.u32 232;");
    asm volatile("barrier.cluster.wait.acquire.aligned;" ::: "memory");
    const unsigned epoch = *reinterpret_cast<volatile unsigned*>(sm + kSmEpoch);
    const int wg = warp >> 2, w = warp & 3, t = lane & 3;
    const bool rel = (threadIdx.x & 95) == 0;
    const uint32_t rel_addr = mapa(sb + kBarEmpty, w & 1);
    const uint32_t xrow_addr = sb + kSmX + (32 * w + lane) * 128;

    if (wg == 1) {
      uint32_t pk[16][4];
      mbar_wait(sb + kBarX, 0);
#pragma unroll
      for (int J = 0; J < 16; J++) ldsm4(xrow_addr + (J >> 3) * kTileBytes + (((J & 7) ^ (lane & 7)) << 4), pk[J]);
      publish_stats(pk, b, j, w, lane);
      __syncwarp();
      if (lane == 0) st_release(&g_flag[(kFlagS + b) * 32 + j * 4 + w], epoch);
      if (cta < 96) colsum_slab(prm.wqkv, 3 * kD, cta * 32, g_cs, &g_flag[kFlagC * 32 + cta], epoch, sm, wg);
    }

#pragma unroll 1
    for (int i = wg; i < kRunTiles; i += 2) {
      const int layer = i >= 7, ty = i - 7 * layer;
      const int n0 = tile_first_seq(layer, ty);
      float acc[2][96];
      if (ty == 2 || ty == 6) {
        const float2* b2 = reinterpret_cast<const float2*>(sm + kSmB2) + t;
#pragma unroll
        for (int J = 0; J < 16; J++) {
          uint32_t r[4];
          ldsm4(xrow_addr + (J >> 3) * kTileBytes + (((J & 7) ^ (lane & 7)) << 4), r);
          float2 bias = make_float2(0.f, 0.f);
          if (ty == 6) bias = b2[J * 4];
#pragma unroll
          for (int c = 0; c < 4; c++) {
            acc[c & 1][4 * J + (c & 2)] = bf_lo(r[c]) + bias.x;
            acc[c & 1][4 * J + (c & 2) + 1] = bf_hi(r[c]) + bias.y;
          }
        }
        mainloop<128, false>(acc, sb, i, n0, ty == 6 ? 56 : 16, 0, rel_addr, rel);
        TRACE_AT(i, 2);
        uint32_t pk[16][4];
#pragma unroll
        for (int J = 0; J < 16; J++) {
#pragma unroll
          for (int c = 0; c < 4; c++) pk[J][c] = pack2(acc[c & 1][4 * J + (c & 2)], acc[c & 1][4 * J + (c & 2) + 1]);
          stsm4(xrow_addr + (J >> 3) * kTileBytes + (((J & 7) ^ (lane & 7)) << 4), pk[J][0], pk[J][1], pk[J][2], pk[J][3]);
        }
        fence_async_smem();
        __syncwarp();
        const int xver = 2 * layer + (ty == 6 ? 2 : 1);
        const uint32_t src = sb + kSmX + w * 4096;
        if (xver == 4) {
          if (lane == 0) {
            tma4d_store(&map_out, src, xcol + j * 128, xrow + w);
            tma4d_store(&map_out, src + kTileBytes, xcol + j * 128 + 64, xrow + w);
            bulk_commit();
            bulk_wait();
          }
        } else {
          if (lane == 0) {
            mbar_arrive(sb + kBarX + xver * 8);
            uint8_t* dst = g_x + (b * 16 + 2 * j) * kTileBytes + w * 4096;
            bulk_store(dst, src, 4096);
            bulk_store(dst + kTileBytes, src + kTileBytes, 4096);
            bulk_commit();
          }
          __syncwarp();
          publish_stats(pk, b, j, w, lane);
          __syncwarp();
          if (lane == 0) {
            bulk_wait();
            st_release(&g_flag[(kFlagX + (xver - 1) * 16 + b) * 32 + j * 4 + w], epoch);
            st_release(&g_flag[(kFlagS + xver * 16 + b) * 32 + j * 4 + w], epoch);
          }
        }
        __syncwarp();
      } else {
        const int xver = 2 * layer + (ty >= 3);
        if (ty < 4) {
          mainloop<192, true>(acc, sb, i, n0, 16, xver, rel_addr, rel);
          TRACE_AT(i, 2);
          mbar_wait(sb + kBarStat + xver * 8, 0);
          if (ty < 2) {
            if (ty == 1) mbar_wait(sb + kBarEpi + (i - 1) * 8, 0);
            epilogue_attn(acc, sm, sb, layer, ty, b, j, epoch, i, wg);
          } else {
            epilogue_gelu<192>(acc, sm, sb, 0, g_h + (b * 56 + 3 * j) * kTileBytes,
                               &g_flag[(kFlagH + layer * 48 + b) * 32 + j * 4 + w], epoch, i);
          }
        } else {
          mainloop<128, true>(acc, sb, i, n0, 16, xver, rel_addr, rel);
          TRACE_AT(i, 2);
          mbar_wait(sb + kBarStat + xver * 8, 0);
          mbar_wait(sb + kBarEpi + (i - 1) * 8, 0);
          epilogue_gelu<128>(acc, sm, sb, ty == 4 ? 192 : 320, g_h + (b * 56 + (ty == 4 ? 24 : 40) + 2 * j) * kTileBytes,
                             &g_flag[(kFlagH + (layer * 3 + ty - 3) * 16 + b) * 32 + j * 4 + w], epoch, i);
        }
      }
      TRACE_AT(i, 3);
      if (i == 0 && cta < 112)
        colsum_slab(prm.w1, kF, cta * 32, g_cs + 3 * kD, &g_flag[kFlagC * 32 + 96 + cta], epoch, sm, wg);
    }
    asm volatile("barrier.cluster.arrive.relaxed.aligned;\nbarrier.cluster.wait.aligned;" ::: "memory");
  }
}

typedef CUresult (*EncodeTiledFn)(CUtensorMap*, CUtensorMapDataType, cuuint32_t, void*, const cuuint64_t*,
                                  const cuuint64_t*, const cuuint32_t*, const cuuint32_t*, CUtensorMapInterleave,
                                  CUtensorMapSwizzle, CUtensorMapL2promotion, CUtensorMapFloatOOBfill);

CUtensorMap make_map(EncodeTiledFn enc, const void* p, int rank, const cuuint64_t* dims, const cuuint64_t* strides,
                     const cuuint32_t* box) {
  CUtensorMap m;
  const cuuint32_t es[5] = {1, 1, 1, 1, 1};
  enc(&m, CU_TENSOR_MAP_DATA_TYPE_BFLOAT16, rank, const_cast<void*>(p), dims, strides, box, es,
      CU_TENSOR_MAP_INTERLEAVE_NONE, CU_TENSOR_MAP_SWIZZLE_128B, CU_TENSOR_MAP_L2_PROMOTION_L2_128B,
      CU_TENSOR_MAP_FLOAT_OOB_FILL_NONE);
  return m;
}

CUtensorMap weight_map(EncodeTiledFn enc, const void* p, int k, int n, int blocks) {
  const cuuint64_t dims[3] = {64, (cuuint64_t)k, (cuuint64_t)n / 64};
  const cuuint64_t strides[2] = {(cuuint64_t)n * 2, 128};
  const cuuint32_t box[3] = {64, 64, (cuuint32_t)blocks};
  return make_map(enc, p, 3, dims, strides, box);
}

CUtensorMap token_map(EncodeTiledFn enc, const void* p, int groups) {
  const cuuint64_t dims[4] = {2 * kD, 8, 4, 32};
  const cuuint64_t strides[3] = {4 * 4096, 4096, 32 * 4096};
  const cuuint32_t box[4] = {64, 8, 4, (cuuint32_t)groups};
  return make_map(enc, p, 4, dims, strides, box);
}

}

extern "C" void kernel_launch(void* const* d_in, const int* in_sizes, int n_in, void* d_out, int out_size) {
  (void)in_sizes; (void)n_in; (void)out_size;
  static EncodeTiledFn enc = nullptr;
  if (!enc) {
    void* fn = nullptr;
    cudaDriverEntryPointQueryResult q;
    cudaGetDriverEntryPoint("cuTensorMapEncodeTiled", &fn, cudaEnableDefault, &q);
    enc = (EncodeTiledFn)fn;
    cudaFuncSetAttribute(fused_layers_kernel, cudaFuncAttributeMaxDynamicSharedMemorySize, kSmBytes);
  }
  Params prm;
  prm.wqkv = (const __nv_bfloat16*)d_in[1];
  prm.wo = (const __nv_bfloat16*)d_in[2];
  prm.w1 = (const __nv_bfloat16*)d_in[4];
  prm.b1 = (const __nv_bfloat16*)d_in[5];
  prm.w2 = (const __nv_bfloat16*)d_in[6];
  prm.b2 = (const __nv_bfloat16*)d_in[7];
  const cuuint64_t qd[3] = {kD, kD, 3}, qs[2] = {3 * kD * 2, kD * 2};
  const cuuint32_t qb[3] = {64, 64, 3};
  const CUtensorMap map_x = token_map(enc, d_in[0], 2);
  const CUtensorMap map_out = token_map(enc, d_out, 1);
  const CUtensorMap map_qkv = make_map(enc, prm.wqkv, 3, qd, qs, qb);
  const CUtensorMap map_wo = weight_map(enc, prm.wo, kD, kD, 2);
  const CUtensorMap map_w1a = weight_map(enc, prm.w1, kD, kF, 3);
  const CUtensorMap map_w1b = weight_map(enc, prm.w1, kD, kF, 2);
  const CUtensorMap map_w2 = weight_map(enc, prm.w2, kF, kD, 2);
  fused_layers_kernel<<<kCtas, 384, kSmBytes>>>(map_x, map_out, map_qkv, map_wo, map_w1a, map_w1b, map_w2, prm);
}
```

```cpp
#include <cuda.h>
#include <cuda_bf16.h>
#include <cuda_runtime.h>
#include <stdint.h>

namespace {

constexpr int kD = 1024;
constexpr int kF = 3584;
constexpr int kCtas = 128;
constexpr int kTiles = 14;
constexpr int kRunTiles = kTiles;
constexpr int kTileBytes = 16384;

constexpr int kSmRing = 0;
constexpr int kSmX = 163840;
constexpr int kSmStg = kSmX + 32768;
constexpr int kSmHalo = kSmStg + 16384;
constexpr int kSmCsQ = kSmHalo + 6144;
constexpr int kSmV1 = kSmCsQ + 384 * 4;
constexpr int kSmB2 = kSmV1 + 448 * 8;
constexpr int kSmStat = kSmB2 + 128 * 4;
constexpr int kSmRed = kSmStat + 128 * 8;
constexpr int kSmBar = kSmRed + 512;
constexpr int kBarFull = kSmBar;
constexpr int kBarEmpty = kBarFull + 64;
constexpr int kBarTurn = kBarEmpty + 64;
constexpr int kBarEpi = kBarTurn + kTiles * 8;
constexpr int kBarX = kBarEpi + kTiles * 8;
constexpr int kBarStat = kBarX + 32;
constexpr int kBarPause = kBarStat + 32;
constexpr int kBarResume = kBarPause + 32;
constexpr int kSmEpoch = kBarResume + 32;
constexpr int kSmBytes = kSmEpoch + 16;

constexpr int kFlagX = 0;
constexpr int kFlagS = kFlagX + 3 * 16;
constexpr int kFlagO = kFlagS + 4 * 16;
constexpr int kFlagH = kFlagO + 4 * 16;
constexpr int kFlagC = kFlagH + 6 * 16;
constexpr int kFlagLines = kFlagC + 7;

constexpr unsigned kSpinLimit = 1u << 24;

__device__ __align__(1024) uint8_t g_x[16 * 16 * kTileBytes];
__device__ __align__(1024) uint8_t g_o[16 * 16 * kTileBytes];
__device__ __align__(1024) uint8_t g_h[16 * 56 * kTileBytes];
__device__ __align__(128) float2 g_stat[16 * 128 * 8];
__device__ __align__(128) float g_cs[3 * kD + kF];
__device__ __align__(128) uint4 g_halo[2 * 16 * 16 * 256];
__device__ __align__(128) unsigned g_flag[kFlagLines * 32];
__device__ unsigned g_ticket;

#define TRACE_AT(tile, k)

struct Params {
  const __nv_bfloat16* wqkv;
  const __nv_bfloat16* wo;
  const __nv_bfloat16* w1;
  const __nv_bfloat16* b1;
  const __nv_bfloat16* w2;
  const __nv_bfloat16* b2;
};

__device__ __forceinline__ uint32_t smem_u32(const void* p) {
  return (uint32_t)__cvta_generic_to_shared(p);
}
__device__ __forceinline__ uint32_t mapa(uint32_t a, uint32_t cta) {
  uint32_t r;
  asm("mapa.shared::cluster.u32 %0, %1, %2;" : "=r"(r) : "r"(a), "r"(cta));
  return r;
}
__device__ __forceinline__ void mbar_init(uint32_t bar, int cnt) {
  asm volatile("mbarrier.init.shared::cta.b64 [%0], %1;" ::"r"(bar), "r"(cnt) : "memory");
}
__device__ __forceinline__ void mbar_expect_tx(uint32_t bar, uint32_t bytes) {
  asm volatile("mbarrier.arrive.expect_tx.shared::cta.b64 _, [%0], %1;" ::"r"(bar), "r"(bytes) : "memory");
}
__device__ __forceinline__ void mbar_arrive(uint32_t bar) {
  asm volatile("mbarrier.arrive.shared::cta.b64 _, [%0];" ::"r"(bar) : "memory");
}
__device__ __forceinline__ void mbar_arrive_cluster(uint32_t cluster_addr) {
  asm volatile("mbarrier.arrive.shared::cluster.b64 _, [%0];" ::"r"(cluster_addr) : "memory");
}
__device__ __forceinline__ void mbar_wait(uint32_t bar, uint32_t parity) {
  asm volatile(
      "{\n.reg .pred p;\n.reg .u32 c;\n"
      "mbarrier.try_wait.parity.shared::cta.b64 p, [%0], %1;\n"
      "@p bra.uni DONE;\n"
      "mov.u32 c, 0;\n"
      "RETRY:\n"
      "mbarrier.try_wait.parity.shared::cta.b64 p, [%0], %1;\n"
      "@p bra.uni DONE;\n"
      "add.u32 c, c, 1;\n"
      "setp.lt.u32 p, c, %2;\n"
      "@p bra.uni RETRY;\n"
      "trap;\n"
      "DONE:\n}" ::"r"(bar), "r"(parity), "n"(kSpinLimit)
      : "memory");
}
__device__ __forceinline__ void tma3d(uint32_t dst, const CUtensorMap* m, uint32_t bar, int c0, int c1, int c2) {
  asm volatile(
      "cp.async.bulk.tensor.3d.shared::cluster.global.mbarrier::complete_tx::bytes [%0], [%1, {%3, %4, %5}], [%2];"
      ::"r"(dst), "l"(m), "r"(bar), "r"(c0), "r"(c1), "r"(c2) : "memory");
}
__device__ __forceinline__ void tma2d(uint32_t dst, const CUtensorMap* m, uint32_t bar, int c0, int c1) {
  asm volatile(
      "cp.async.bulk.tensor.2d.shared::cluster.global.mbarrier::complete_tx::bytes [%0], [%1, {%3, %4}], [%2];"
      ::"r"(dst), "l"(m), "r"(bar), "r"(c0), "r"(c1) : "memory");
}
__device__ __forceinline__ void tma2d_mc(uint32_t dst, const CUtensorMap* m, uint32_t bar, int c0, int c1) {
  asm volatile(
      "cp.async.bulk.tensor.2d.shared::cluster.global.mbarrier::complete_tx::bytes.multicast::cluster"
      " [%0], [%1, {%3, %4}], [%2], %5;"
      ::"r"(dst), "l"(m), "r"(bar), "r"(c0), "r"(c1), "h"((uint16_t)3) : "memory");
}
__device__ __forceinline__ void tma2d_store(const CUtensorMap* m, uint32_t src, int c0, int c1) {
  asm volatile("cp.async.bulk.tensor.2d.global.shared::cta.bulk_group [%0, {%2, %3}], [%1];"
               ::"l"(m), "r"(src), "r"(c0), "r"(c1) : "memory");
}
__device__ __forceinline__ bool elect() {
  uint32_t p;
  asm volatile("{\n.reg .pred p;\nelect.sync _|p, 0xffffffff;\nselp.b32 %0, 1, 0, p;\n}" : "=r"(p));
  return p;
}
__device__ __forceinline__ void bulk_load_mc(uint32_t dst, const void* src, uint32_t bytes, uint32_t bar) {
  asm volatile(
      "cp.async.bulk.shared::cluster.global.mbarrier::complete_tx::bytes.multicast::cluster [%0], [%1], %2, [%3], %4;"
      ::"r"(dst), "l"(src), "r"(bytes), "r"(bar), "h"((uint16_t)3) : "memory");
}
__device__ __forceinline__ void bulk_copy_peer(uint32_t dst_cl, uint32_t src, uint32_t bytes, uint32_t bar_cl) {
  asm volatile("cp.async.bulk.shared::cluster.shared::cta.mbarrier::complete_tx::bytes [%0], [%1], %2, [%3];"
               ::"r"(dst_cl), "r"(src), "r"(bytes), "r"(bar_cl) : "memory");
}
__device__ __forceinline__ void bulk_store(void* dst, uint32_t src, uint32_t bytes) {
  asm volatile("cp.async.bulk.global.shared::cta.bulk_group [%0], [%1], %2;" ::"l"(dst), "r"(src), "r"(bytes)
               : "memory");
}
__device__ __forceinline__ void bulk_commit() { asm volatile("cp.async.bulk.commit_group;" ::: "memory"); }
__device__ __forceinline__ void bulk_wait_read() { asm volatile("cp.async.bulk.wait_group.read 0;" ::: "memory"); }
__device__ __forceinline__ void bulk_wait() { asm volatile("cp.async.bulk.wait_group 0;" ::: "memory"); }
__device__ __forceinline__ void l2_prefetch(const void* p, uint32_t bytes) {
  asm volatile("cp.async.bulk.prefetch.L2.global [%0], %1;" ::"l"(p), "r"(bytes) : "memory");
}
__device__ __forceinline__ void fence_async_smem() { asm volatile("fence.proxy.async.shared::cta;" ::: "memory"); }
__device__ __forceinline__ void fence_async_global() { asm volatile("fence.proxy.async.global;" ::: "memory"); }
__device__ __forceinline__ unsigned ld_acquire(const unsigned* p) {
  unsigned v;
  asm volatile("ld.acquire.gpu.global.u32 %0, [%1];" : "=r"(v) : "l"(p) : "memory");
  return v;
}
__device__ __forceinline__ void st_release(unsigned* p, unsigned v) {
  asm volatile("st.release.gpu.global.u32 [%0], %1;" ::"l"(p), "r"(v) : "memory");
}
__device__ __forceinline__ void wait_flags(const unsigned* p, bool need, unsigned epoch) {
  unsigned spins = 0;
  while (true) {
    unsigned v = need ? ld_acquire(p) : epoch;
    if (__all_sync(0xffffffffu, v == epoch)) break;
    if (++spins > kSpinLimit) __trap();
  }
  __syncwarp();
}
__device__ __forceinline__ void stsm4(uint32_t a, uint32_t r0, uint32_t r1, uint32_t r2, uint32_t r3) {
  asm volatile("stmatrix.sync.aligned.m8n8.x4.shared.b16 [%0], {%1, %2, %3, %4};" ::"r"(a), "r"(r0), "r"(r1),
               "r"(r2), "r"(r3) : "memory");
}
__device__ __forceinline__ void stsm4_t(uint32_t a, uint32_t r0, uint32_t r1, uint32_t r2, uint32_t r3) {
  asm volatile("stmatrix.sync.aligned.m8n8.x4.trans.shared.b16 [%0], {%1, %2, %3, %4};" ::"r"(a), "r"(r0),
               "r"(r1), "r"(r2), "r"(r3) : "memory");
}
__device__ __forceinline__ uint32_t transpose8(uint32_t a) {
  uint32_t d;
  asm volatile("movmatrix.sync.aligned.m8n8.trans.b16 %0, %1;" : "=r"(d) : "r"(a));
  return d;
}
__device__ __forceinline__ void mma16816(float (&c)[4], uint32_t a0, uint32_t a1, uint32_t a2, uint32_t a3,
                                         uint32_t b0, uint32_t b1) {
  asm volatile("mma.sync.aligned.m16n8k16.row.col.f32.bf16.bf16.f32 {%0, %1, %2, %3}, {%4, %5, %6, %7}, {%8, %9}, "
               "{%0, %1, %2, %3};"
               : "+f"(c[0]), "+f"(c[1]), "+f"(c[2]), "+f"(c[3])
               : "r"(a0), "r"(a1), "r"(a2), "r"(a3), "r"(b0), "r"(b1));
}
__device__ __forceinline__ float shfl_xor(float v, int m) {
  float r;
  asm volatile("shfl.sync.bfly.b32 %0, %1, %2, 31, 0xffffffff;" : "=f"(r) : "f"(v), "r"(m));
  return r;
}
__device__ __forceinline__ float tanh_fast(float x) {
  float r;
  asm("tanh.approx.f32 %0, %1;" : "=f"(r) : "f"(x));
  return r;
}
__device__ __forceinline__ void ldsm4(uint32_t a, uint32_t (&r)[4]) {
  asm volatile("ldmatrix.sync.aligned.m8n8.x4.shared.b16 {%0, %1, %2, %3}, [%4];"
               : "=r"(r[0]), "=r"(r[1]), "=r"(r[2]), "=r"(r[3]) : "r"(a) : "memory");
}
__device__ __forceinline__ uint32_t pack2(float lo, float hi) {
  uint32_t r;
  asm("cvt.rn.bf16x2.f32 %0, %1, %2;" : "=r"(r) : "f"(hi), "f"(lo));
  return r;
}
__device__ __forceinline__ float bf_lo(uint32_t r) { return __uint_as_float(r << 16); }
__device__ __forceinline__ float bf_hi(uint32_t r) { return __uint_as_float(r & 0xffff0000u); }
__device__ __forceinline__ float ex2(float x) {
  float r;
  asm("ex2.approx.ftz.f32 %0, %1;" : "=f"(r) : "f"(x));
  return r;
}
__device__ __forceinline__ float rcp(float x) {
  float r;
  asm("rcp.approx.ftz.f32 %0, %1;" : "=f"(r) : "f"(x));
  return r;
}
template <int N>
__device__ __forceinline__ void wg_wait() {
  asm volatile("wgmma.wait_group.sync.aligned %0;" ::"n"(N) : "memory");
}
__device__ __forceinline__ void wg_bar(int wg) { asm volatile("bar.sync %0, 128;" ::"r"(wg + 1) : "memory"); }

template <int N>
__device__ __forceinline__ void mma_kblock(float (&acc)[2][96], uint32_t a, uint32_t b);

#define F8(d, i) \
  "+f"(d[i]), "+f"(d[i + 1]), "+f"(d[i + 2]), "+f"(d[i + 3]), "+f"(d[i + 4]), "+f"(d[i + 5]), "+f"(d[i + 6]), "+f"(d[i + 7])
#define KSTEP(N, A, B, oa0, oa1, ob)                                                       \
  "add.u32 t, " B ", " #ob ";\nmov.b64 db, {t, hb};\n"                                      \
  "add.u32 t, " A ", " #oa0 ";\nmov.b64 da, {t, ha};\n"                                     \
  "wgmma.mma_async.sync.aligned.m64n" #N "k16.f32.bf16.bf16 {" ACC##N##_0 "}, da, db, 1, 1, 1, 0, 1;\n" \
  "add.u32 t, " A ", " #oa1 ";\nmov.b64 da, {t, ha};\n"                                     \
  "wgmma.mma_async.sync.aligned.m64n" #N "k16.f32.bf16.bf16 {" ACC##N##_1 "}, da, db, 1, 1, 1, 0, 1;\n"

#define ACC128_0 \
  "%0, %1, %2, %3, %4, %5, %6, %7, %8, %9, %10, %11, %12, %13, %14, %15, " \
  "%16, %17, %18, %19, %20, %21, %22, %23, %24, %25, %26, %27, %28, %29, %30, %31, " \
  "%32, %33, %34, %35, %36, %37, %38, %39, %40, %41, %42, %43, %44, %45, %46, %47, " \
  "%48, %49, %50, %51, %52, %53, %54, %55, %56, %57, %58, %59, %60, %61, %62, %63"
#define ACC128_1 \
  "%64, %65, %66, %67, %68, %69, %70, %71, %72, %73, %74, %75, %76, %77, %78, %79, " \
  "%80, %81, %82, %83, %84, %85, %86, %87, %88, %89, %90, %91, %92, %93, %94, %95, " \
  "%96, %97, %98, %99, %100, %101, %102, %103, %104, %105, %106, %107, %108, %109, %110, %111, " \
  "%112, %113, %114, %115, %116, %117, %118, %119, %120, %121, %122, %123, %124, %125, %126, %127"
template <>
__device__ __forceinline__ void mma_kblock<128>(float (&acc)[2][96], uint32_t a, uint32_t b) {
  asm volatile("{\n.reg .b32 t, ha, hb;\n.reg .b64 da, db;\n"
               "mov.b32 ha, 0x40000080;\nmov.b32 hb, 0x40000040;\n"
               "wgmma.fence.sync.aligned;\n"
               KSTEP(128, "%128", "%129", 0, 64, 0) KSTEP(128, "%128", "%129", 2, 66, 128)
               KSTEP(128, "%128", "%129", 4, 68, 256) KSTEP(128, "%128", "%129", 6, 70, 384)
               "wgmma.commit_group.sync.aligned;\n}\n"
      : F8(acc[0], 0), F8(acc[0], 8), F8(acc[0], 16), F8(acc[0], 24), F8(acc[0], 32), F8(acc[0], 40), F8(acc[0], 48), F8(acc[0], 56),
        F8(acc[1], 0), F8(acc[1], 8), F8(acc[1], 16), F8(acc[1], 24), F8(acc[1], 32), F8(acc[1], 40), F8(acc[1], 48), F8(acc[1], 56)
      : "r"(a), "r"(b)
      : "memory");
}

#define ACC192_0 \
  "%0, %1, %2, %3, %4, %5, %6, %7, %8, %9, %10, %11, %12, %13, %14, %15, " \
  "%16, %17, %18, %19, %20, %21, %22, %23, %24, %25, %26, %27, %28, %29, %30, %31, " \
  "%32, %33, %34, %35, %36, %37, %38, %39, %40, %41, %42, %43, %44, %45, %46, %47, " \
  "%48, %49, %50, %51, %52, %53, %54, %55, %56, %57, %58, %59, %60, %61, %62, %63, " \
  "%64, %65, %66, %67, %68, %69, %70, %71, %72, %73, %74, %75, %76, %77, %78, %79, " \
  "%80, %81, %82, %83, %84, %85, %86, %87, %88, %89, %90, %91, %92, %93, %94, %95"
#define ACC192_1 \
  "%96, %97, %98, %99, %100, %101, %102, %103, %104, %105, %106, %107, %108, %109, %110, %111, " \
  "%112, %113, %114, %115, %116, %117, %118, %119, %120, %121, %122, %123, %124, %125, %126, %127, " \
  "%128, %129, %130, %131, %132, %133, %134, %135, %136, %137, %138, %139, %140, %141, %142, %143, " \
  "%144, %145, %146, %147, %148, %149, %150, %151, %152, %153, %154, %155, %156, %157, %158, %159, " \
  "%160, %161, %162, %163, %164, %165, %166, %167, %168, %169, %170, %171, %172, %173, %174, %175, " \
  "%176, %177, %178, %179, %180, %181, %182, %183, %184, %185, %186, %187, %188, %189, %190, %191"
template <>
__device__ __forceinline__ void mma_kblock<192>(float (&acc)[2][96], uint32_t a, uint32_t b) {
  asm volatile("{\n.reg .b32 t, ha, hb;\n.reg .b64 da, db;\n"
               "mov.b32 ha, 0x40000080;\nmov.b32 hb, 0x40000040;\n"
               "wgmma.fence.sync.aligned;\n"
               KSTEP(192, "%192", "%193", 0, 64, 0) KSTEP(192, "%192", "%193", 2, 66, 128)
               KSTEP(192, "%192", "%193", 4, 68, 256) KSTEP(192, "%192", "%193", 6, 70, 384)
               "wgmma.commit_group.sync.aligned;\n}\n"
      : F8(acc[0], 0), F8(acc[0], 8), F8(acc[0], 16), F8(acc[0], 24), F8(acc[0], 32), F8(acc[0], 40), F8(acc[0], 48), F8(acc[0], 56), F8(acc[0], 64), F8(acc[0], 72), F8(acc[0], 80), F8(acc[0], 88),
        F8(acc[1], 0), F8(acc[1], 8), F8(acc[1], 16), F8(acc[1], 24), F8(acc[1], 32), F8(acc[1], 40), F8(acc[1], 48), F8(acc[1], 56), F8(acc[1], 64), F8(acc[1], 72), F8(acc[1], 80), F8(acc[1], 88)
      : "r"(a), "r"(b)
      : "memory");
}

__device__ __forceinline__ int tile_first_seq(int layer, int ty) { return layer * 152 + ty * 16; }
__device__ __forceinline__ int tile_first_slot(int i) { return (int)((0x21004333211000ull >> (4 * i)) & 7); }
__device__ __forceinline__ bool tile_wide(int ty) { return ty == 0 || ty == 1 || ty == 3; }
__device__ __forceinline__ bool tile_uses_x(int ty) { return ty != 2 && ty != 6; }
__device__ __forceinline__ int ring_depth(int ty, int kk) {
  return (tile_wide(ty) || ((ty == 2 || ty == 4) && kk < 4)) ? 4 : 5;
}

template <int N>
__device__ __forceinline__ void fence_acc(float (&acc)[2][96]) {
#pragma unroll
  for (int h = 0; h < 2; h++)
#pragma unroll
    for (int i = 0; i < N / 2; i++) asm volatile("" : "+f"(acc[h][i])::"memory");
}

template <int N>
__device__ __forceinline__ void zero_acc(float (&acc)[2][96]) {
#pragma unroll
  for (int h = 0; h < 2; h++)
#pragma unroll
    for (int i = 0; i < N / 2; i++) acc[h][i] = 0.f;
}

template <int N, bool USEX>
__device__ __forceinline__ void mainloop(float (&acc)[2][96], uint32_t sb, int tile, int n0, int nkb, int xver,
                                         int pause_kk, int att, uint32_t rel_addr, bool rel) {
  constexpr uint32_t kStep = (N == 192 ? 5 : 4) * 512;
  const uint32_t ring = (((sb & 0x3FFFF) + kSmRing) >> 4) | (1u << 16);
  const uint32_t xdesc = (((sb & 0x3FFFF) + kSmX) >> 4) | (1u << 16);
  constexpr uint32_t kToB = (kTileBytes >> 4) + ((8192u >> 4) << 16) - (1u << 16);
  uint32_t st = ring + tile_first_slot(tile) * kStep;
  uint32_t nb = n0 * 8;
  const bool signal = (threadIdx.x & 127) == 64;
  fence_acc<N>(acc);
  if (tile > 0) mbar_wait(sb + kBarTurn + (tile - 1) * 8, 0);
  if (USEX) mbar_wait(sb + kBarX + xver * 8, 0);
  TRACE_AT(tile, 0);
  int kk = 0;
#pragma unroll 1
  do {
    if (kk == pause_kk) {
      if (signal) mbar_arrive(sb + kBarPause + att * 8);
      mbar_wait(sb + kBarResume + att * 8, 0);
    }
    mbar_wait(sb + kBarFull + (nb & 56), (nb >> 6) & 1);
    if (kk == 0) TRACE_AT(tile, 1);
    mma_kblock<N>(acc, (USEX && kk < 2) ? xdesc + kk * (kTileBytes >> 4) : st, st + kToB);
    if (kk == nkb - 1 && signal) mbar_arrive(sb + kBarTurn + tile * 8);
    wg_wait<1>();
    if (rel && kk > 0) mbar_arrive_cluster(rel_addr + ((nb - 8) & 56));
    st += kStep;
    if (st == ring + 10240) st = ring;
    nb += 8;
  } while (++kk < nkb);
  wg_wait<0>();
  if (rel) mbar_arrive_cluster(rel_addr + ((nb - 8) & 56));
  fence_acc<N>(acc);
}

__device__ __forceinline__ void publish_stats(const uint32_t (&pk)[16][4], int b, int j, int w, int lane) {
  float s[4], q[4];
#pragma unroll
  for (int c = 0; c < 4; c++) {
    s[c] = 0.f;
    q[c] = 0.f;
#pragma unroll
    for (int J = 0; J < 16; J++) {
      const float lo = bf_lo(pk[J][c]), hi = bf_hi(pk[J][c]);
      s[c] += lo;
      q[c] = fmaf(lo, lo, q[c]);
      s[c] += hi;
      q[c] = fmaf(hi, hi, q[c]);
    }
  }
#pragma unroll
  for (int c = 0; c < 4; c++) {
    s[c] += shfl_xor(s[c], 1);
    q[c] += shfl_xor(q[c], 1);
    s[c] += shfl_xor(s[c], 2);
    q[c] += shfl_xor(q[c], 2);
  }
  const int t = lane & 3, g = lane >> 2;
  const float so = t == 0 ? s[0] : t == 1 ? s[1] : t == 2 ? s[2] : s[3];
  const float qo = t == 0 ? q[0] : t == 1 ? q[1] : t == 2 ? q[2] : q[3];
  g_stat[(b * 128 + 32 * w + 8 * t + g) * 8 + j] = make_float2(so, qo);
}

__device__ __forceinline__ void colsum_slab(const __nv_bfloat16* wt, int ld, int col0, float* out, unsigned* flag,
                                            unsigned epoch, uint8_t* sm, int wg, int w) {
  const int tid = threadIdx.x & 127, lane = tid & 31;
  const uint4* p = reinterpret_cast<const uint4*>(wt + (size_t)(tid >> 2) * ld + col0 + (tid & 3) * 8);
  float a[8];
#pragma unroll
  for (int e = 0; e < 8; e++) a[e] = 0.f;
#pragma unroll 1
  for (int it = 0; it < 2; it++) {
    uint4 v[16];
#pragma unroll
    for (int i = 0; i < 16; i++) {
      v[i] = __ldg(p);
      p += ld * 4;
    }
#pragma unroll
    for (int i = 0; i < 16; i++) {
      a[0] += bf_lo(v[i].x); a[1] += bf_hi(v[i].x);
      a[2] += bf_lo(v[i].y); a[3] += bf_hi(v[i].y);
      a[4] += bf_lo(v[i].z); a[5] += bf_hi(v[i].z);
      a[6] += bf_lo(v[i].w); a[7] += bf_hi(v[i].w);
    }
  }
#pragma unroll
  for (int e = 0; e < 8; e++) {
    a[e] += shfl_xor(a[e], 4);
    a[e] += shfl_xor(a[e], 8);
    a[e] += shfl_xor(a[e], 16);
  }
  float* red = reinterpret_cast<float*>(sm + kSmRed);
  if (lane < 4) {
#pragma unroll
    for (int e = 0; e < 8; e++) red[w * 32 + lane * 8 + e] = a[e];
  }
  wg_bar(wg);
  if (w == 0) {
    out[col0 + lane] = (red[lane] + red[32 + lane]) + (red[64 + lane] + red[96 + lane]);
    __syncwarp();
    if (elect()) st_release(flag, epoch);
  }
}

__device__ __forceinline__ float gelu_half(float v) {
  constexpr float c0 = 2.f * 0.7978845608028654f;
  constexpr float c1 = 8.f * 0.7978845608028654f * 0.044715f;
  return fmaf(v, tanh_fast(v * fmaf(v * v, c1, c0)), v);
}

template <int CH>
__device__ __forceinline__ void gelu_chunk(const float (&acc)[2][96], const float2 (&st)[4], const float4* vec,
                                           uint32_t stg, int lane, uint8_t* dst) {
  uint32_t pk[8][4];
#pragma unroll
  for (int jj = 0; jj < 8; jj++) {
    const int J = CH * 8 + jj;
    const float4 v = vec[J * 4];
#pragma unroll
    for (int c = 0; c < 4; c++) {
      const float u0 = fmaf(acc[c & 1][4 * J + (c & 2)], st[c].x, fmaf(st[c].y, v.x, v.z));
      const float u1 = fmaf(acc[c & 1][4 * J + (c & 2) + 1], st[c].x, fmaf(st[c].y, v.y, v.w));
      pk[jj][c] = pack2(gelu_half(u0), gelu_half(u1));
    }
  }
  if (CH > 0) {
    if (elect()) bulk_wait_read();
    __syncwarp();
  }
#pragma unroll
  for (int jj = 0; jj < 8; jj++)
    stsm4(stg + lane * 128 + ((jj ^ (lane & 7)) << 4), pk[jj][0], pk[jj][1], pk[jj][2], pk[jj][3]);
  fence_async_smem();
  __syncwarp();
  if (elect()) {
    bulk_store(dst + CH * kTileBytes, stg, 4096);
    bulk_commit();
  }
}

__device__ __forceinline__ void epilogue_gelu(const float (&acc)[2][96], uint8_t* sm, uint32_t sb, bool wide,
                                              int vcol0, uint8_t* dst, unsigned* flag, unsigned epoch, int tile,
                                              int w) {
  const int lane = threadIdx.x & 31, t = lane & 3, g = lane >> 2;
  float2 st[4];
#pragma unroll
  for (int c = 0; c < 4; c++) {
    const float2 v = reinterpret_cast<const float2*>(sm + kSmStat)[32 * w + 8 * c + g];
    st[c].x = 0.5f * v.x;
    st[c].y = st[c].x * v.y;
  }
  const float4* vec = reinterpret_cast<const float4*>(sm + kSmV1) + vcol0 / 2 + t;
  const uint32_t stg = sb + kSmStg + w * 4096;
  gelu_chunk<0>(acc, st, vec, stg, lane, dst);
  gelu_chunk<1>(acc, st, vec, stg, lane, dst);
  if (wide) gelu_chunk<2>(acc, st, vec, stg, lane, dst);
  if (elect()) {
    bulk_wait();
    mbar_arrive(sb + kBarEpi + tile * 8);
    st_release(flag, epoch);
  }
  __syncwarp();
}

__device__ __forceinline__ void add_mean_term(float (&acc)[2][96], uint8_t* sm, int tq, int w, int lane) {
  const int t = lane & 3, g = lane >> 2;
  float nm[4];
#pragma unroll
  for (int c = 0; c < 4; c++) nm[c] = reinterpret_cast<const float2*>(sm + kSmStat)[32 * w + 8 * c + g].y;
  const float2* cs = reinterpret_cast<const float2*>(sm + kSmCsQ) + tq * 96 + t;
#pragma unroll
  for (int J = 0; J < 24; J++) {
    const float2 v = cs[J * 4];
#pragma unroll
    for (int c = 0; c < 4; c++) {
      acc[c & 1][4 * J + (c & 2)] = fmaf(nm[c], v.x, acc[c & 1][4 * J + (c & 2)]);
      acc[c & 1][4 * J + (c & 2) + 1] = fmaf(nm[c], v.y, acc[c & 1][4 * J + (c & 2) + 1]);
    }
  }
}

__device__ __forceinline__ void epilogue_attn(const float (&acc)[2][96], uint8_t* sm, uint32_t sb, int layer, int tq,
                                              int b, int j, unsigned epoch, int tile, int wg, int w) {
  const int lane = threadIdx.x & 31, t = lane & 3, g = lane >> 2;
  const int hp = j + 8 * tq, att = 2 * layer + tq;
  float rs[4];
#pragma unroll
  for (int c = 0; c < 4; c++) rs[c] = reinterpret_cast<const float2*>(sm + kSmStat)[32 * w + 8 * c + g].x;
  uint32_t q[4][8], k[5][8], vt[5][8];
#define SCALED(c, J) pack2(acc[(c) & 1][4 * (J) + ((c) & 2)] * rs[c], acc[(c) & 1][4 * (J) + ((c) & 2) + 1] * rs[c])
#pragma unroll
  for (int J = 0; J < 8; J++) {
    k[4][J] = SCALED(3, 8 + J);
    vt[4][J] = transpose8(SCALED(3, 16 + J));
  }
  if (w < 3) {
    uint4* hs = reinterpret_cast<uint4*>(sm + kSmHalo + w * 2048) + lane;
    hs[0] = make_uint4(k[4][0], k[4][1], k[4][2], k[4][3]);
    hs[32] = make_uint4(k[4][4], k[4][5], k[4][6], k[4][7]);
    hs[64] = make_uint4(vt[4][0], vt[4][1], vt[4][2], vt[4][3]);
    hs[96] = make_uint4(vt[4][4], vt[4][5], vt[4][6], vt[4][7]);
  } else if ((b & 7) != 7) {
    uint4* gh = g_halo + ((layer * 16 + b) * 16 + hp) * 256 + lane;
#pragma unroll
    for (int i = 0; i < 8; i++)
      asm volatile("{\n.reg .b64 x, y;\nmov.b64 x, {%1, %3};\nmov.b64 y, {%2, %3};\n"
                   "st.relaxed.gpu.global.v2.b64 [%0], {x, y};\n}" ::"l"(gh + i * 32),
                   "r"(k[4][i]), "r"(vt[4][i]), "r"(epoch) : "memory");
  }
#pragma unroll
  for (int c = 0; c < 3; c++)
#pragma unroll
    for (int J = 0; J < 8; J++) {
      k[c + 1][J] = SCALED(c, 8 + J);
      vt[c + 1][J] = transpose8(SCALED(c, 16 + J));
    }
#pragma unroll
  for (int c = 0; c < 4; c++)
#pragma unroll
    for (int J = 0; J < 8; J++) q[c][J] = SCALED(c, J);
#undef SCALED
  wg_bar(wg);
  const bool first = w == 0 && (b & 7) == 0;
  if (w > 0) {
    const uint4* hs = reinterpret_cast<const uint4*>(sm + kSmHalo + (w - 1) * 2048) + lane;
    const uint4 a0 = hs[0], a1 = hs[32], a2 = hs[64], a3 = hs[96];
    k[0][0] = a0.x; k[0][1] = a0.y; k[0][2] = a0.z; k[0][3] = a0.w;
    k[0][4] = a1.x; k[0][5] = a1.y; k[0][6] = a1.z; k[0][7] = a1.w;
    vt[0][0] = a2.x; vt[0][1] = a2.y; vt[0][2] = a2.z; vt[0][3] = a2.w;
    vt[0][4] = a3.x; vt[0][5] = a3.y; vt[0][6] = a3.z; vt[0][7] = a3.w;
  } else if (first) {
#pragma unroll
    for (int i = 0; i < 8; i++) k[0][i] = vt[0][i] = 0u;
  } else {
    const uint4* gh = g_halo + ((layer * 16 + b - 1) * 16 + hp) * 256 + lane;
    unsigned spins = 0;
    while (true) {
      unsigned diff = 0;
#pragma unroll
      for (int i = 0; i < 8; i++) {
        unsigned t0, t1;
        asm volatile("{\n.reg .b64 x, y;\nld.relaxed.gpu.global.v2.b64 {x, y}, [%4];\n"
                     "mov.b64 {%0, %1}, x;\nmov.b64 {%2, %3}, y;\n}"
                     : "=r"(k[0][i]), "=r"(t0), "=r"(vt[0][i]), "=r"(t1) : "l"(gh + i * 32) : "memory");
        diff |= (t0 ^ epoch) | (t1 ^ epoch);
      }
      if (__all_sync(0xffffffffu, diff == 0)) break;
      if (++spins > kSpinLimit) __trap();
    }
  }
  mbar_wait(sb + kBarPause + att * 8, 0);

  float s[2][5][4];
#pragma unroll
  for (int hd = 0; hd < 2; hd++)
#pragma unroll
    for (int kg = 0; kg < 5; kg++) {
      const int ca = kg > 0 ? kg - 1 : 0, cb = kg < 4 ? kg : 3;
#pragma unroll
      for (int e = 0; e < 4; e++) s[hd][kg][e] = 0.f;
#pragma unroll
      for (int ks = 0; ks < 2; ks++) {
        const int J = 4 * hd + 2 * ks;
        mma16816(s[hd][kg], q[ca][J], q[cb][J], q[ca][J + 1], q[cb][J + 1], k[kg][J], k[kg][J + 1]);
      }
    }
  constexpr float kScale = 0.17677669529663687f * 1.4426950408889634f;
  const bool own0 = 2 * t <= g, own1 = 2 * t + 1 <= g;
  const uint32_t own_mask = (own0 ? 0xffffu : 0u) | (own1 ? 0xffff0000u : 0u);
  float o[2][4][2][4];
#pragma unroll
  for (int hd = 0; hd < 2; hd++) {
    float v0[4], v1[4], m[4];
#pragma unroll
    for (int c = 0; c < 4; c++) {
      float p0 = s[hd][c][2], p1 = s[hd][c][3];
      if (c == 0 && first) p0 = p1 = -INFINITY;
      v0[c] = own0 ? s[hd][c + 1][0] : p0;
      v1[c] = own1 ? s[hd][c + 1][1] : p1;
      m[c] = fmaxf(v0[c], v1[c]);
    }
#pragma unroll
    for (int c = 0; c < 4; c++) m[c] = fmaxf(m[c], shfl_xor(m[c], 1));
#pragma unroll
    for (int c = 0; c < 4; c++) m[c] = fmaxf(m[c], shfl_xor(m[c], 2));
#pragma unroll
    for (int c = 0; c < 4; c++) {
      const float nm = -m[c] * kScale;
      v0[c] = ex2(fmaf(v0[c], kScale, nm));
      v1[c] = ex2(fmaf(v1[c], kScale, nm));
      m[c] = v0[c] + v1[c];
    }
#pragma unroll
    for (int c = 0; c < 4; c++) m[c] += shfl_xor(m[c], 1);
#pragma unroll
    for (int c = 0; c < 4; c++) m[c] += shfl_xor(m[c], 2);
#pragma unroll
    for (int c = 0; c < 4; c++) {
      const float inv = rcp(m[c]);
      const uint32_t p = pack2(v0[c] * inv, v1[c] * inv);
#pragma unroll
      for (int ds = 0; ds < 2; ds++) {
        const int J = 4 * hd + 2 * ds;
#pragma unroll
        for (int e = 0; e < 4; e++) o[hd][c][ds][e] = 0.f;
        mma16816(o[hd][c][ds], vt[c][J], vt[c][J + 1], vt[c + 1][J], vt[c + 1][J + 1], p & ~own_mask, p & own_mask);
      }
    }
  }
  if (elect()) mbar_arrive(sb + kBarResume + att * 8);
  const uint32_t stg = sb + kSmStg + w * 4096;
#pragma unroll
  for (int J = 0; J < 8; J++) {
    const int hd = J >> 2, ds = (J >> 1) & 1, e = 2 * (J & 1);
    stsm4_t(stg + lane * 128 + ((J ^ (lane & 7)) << 4), pack2(o[hd][0][ds][e], o[hd][0][ds][e + 1]),
            pack2(o[hd][1][ds][e], o[hd][1][ds][e + 1]), pack2(o[hd][2][ds][e], o[hd][2][ds][e + 1]),
            pack2(o[hd][3][ds][e], o[hd][3][ds][e + 1]));
  }
  fence_async_smem();
  __syncwarp();
  if (elect()) {
    bulk_store(g_o + (b * 16 + hp) * kTileBytes + w * 4096, stg, 4096);
    bulk_commit();
    bulk_wait();
    st_release(&g_flag[(kFlagO + att * 16 + b) * 32 + j * 4 + w], epoch);
    mbar_arrive(sb + kBarEpi + tile * 8);
  }
  __syncwarp();
}

__device__ __forceinline__ void reduce_stats(uint8_t* sm, int b, int lane) {
#pragma unroll 1
  for (int i = 0; i < 4; i++) {
    const int r = i * 32 + lane;
    const float4* p = reinterpret_cast<const float4*>(g_stat + (b * 128 + r) * 8);
    const float4 a0 = __ldcg(p), a1 = __ldcg(p + 1), a2 = __ldcg(p + 2), a3 = __ldcg(p + 3);
    const float mean = (((a0.x + a0.z) + (a1.x + a1.z)) + ((a2.x + a2.z) + (a3.x + a3.z))) * (1.f / 1024.f);
    const float sq = (((a0.y + a0.w) + (a1.y + a1.w)) + ((a2.y + a2.w) + (a3.y + a3.w))) * (1.f / 1024.f);
    const float var = fmaxf(fmaf(-mean, mean, sq), 0.f);
    reinterpret_cast<float2*>(sm + kSmStat)[r] = make_float2(rsqrtf(var + 1e-5f), -mean);
  }
}

#define PAUSE_QKV2 8
#define PAUSE_WO 3

__global__ void __cluster_dims__(2, 1, 1) __launch_bounds__(384, 1)
fused_layers_kernel(const __grid_constant__ CUtensorMap map_x, const __grid_constant__ CUtensorMap map_out,
                    const __grid_constant__ CUtensorMap map_qkv, const __grid_constant__ CUtensorMap map_wo,
                    const __grid_constant__ CUtensorMap map_w1a, const __grid_constant__ CUtensorMap map_w1b,
                    const __grid_constant__ CUtensorMap map_w2, const Params prm) {
  extern __shared__ __align__(1024) uint8_t sm[];
  const uint32_t sb = smem_u32(sm);
  const int warp = __shfl_sync(0xffffffffu, threadIdx.x >> 5, 0), lane = threadIdx.x & 31;
  const int cta = blockIdx.x, b = cta >> 3, j = cta & 7, rank = cta & 1;
  const int xcol = (b >> 3) * kD, xrow = (b & 7) * 128;

  if (warp == 8 && elect()) {
    if (sb & 1023) __trap();
    for (int s = 0; s < 8; s++) {
      mbar_init(sb + kBarFull + s * 8, 1);
      mbar_init(sb + kBarEmpty + s * 8, 2);
    }
    for (int s = 0; s < kTiles; s++) {
      mbar_init(sb + kBarTurn + s * 8, 1);
      mbar_init(sb + kBarEpi + s * 8, 4);
    }
    for (int s = 0; s < 4; s++) {
      mbar_init(sb + kBarX + s * 8, s == 0 ? 1 : 4);
      mbar_init(sb + kBarStat + s * 8, 1);
      mbar_init(sb + kBarPause + s * 8, 1);
      mbar_init(sb + kBarResume + s * 8, 4);
    }
    asm volatile("fence.mbarrier_init.release.cluster;" ::: "memory");
    fence_async_smem();
    mbar_expect_tx(sb + kBarX, 32768);
    for (int s = 0; s < 4; s++)
      tma2d(sb + kSmX + s * 8192, &map_x, sb + kBarX, xcol + j * 128 + (s >> 1) * 64, xrow + (s & 1) * 64);
  }
  if (threadIdx.x == 0) *reinterpret_cast<unsigned*>(sm + kSmEpoch) = atomicAdd(&g_ticket, 1u) / kCtas + 1;
  __syncwarp();
  asm volatile("barrier.cluster.arrive.release.aligned;" ::: "memory");

  if (warp >= 8) {
    asm volatile("setmaxnreg.dec.sync.aligned.u32 40;");
    if (warp == 8) {
      int nb = 0, mb = 0;
#pragma unroll 1
      for (int i = 0; i < kRunTiles; i++) {
        const int ty = i >= 7 ? i - 7 : i;
        const bool wide = tile_wide(ty), usex = tile_uses_x(ty);
        const int nkb = ty == 6 ? 56 : 16;
        const CUtensorMap* map = ty < 2 ? &map_qkv : ty == 2 ? &map_wo : ty == 3 ? &map_w1a : ty < 6 ? &map_w1b : &map_w2;
        const int c0 = ty < 2 ? (j + 8 * ty) * 64 : 0;
        const int c2 = ty < 2 ? 0 : ty == 3 ? 3 * j : ty == 4 ? 24 + 2 * j : ty == 5 ? 40 + 2 * j : 2 * j;
        const uint32_t step = wide ? 40960 : 32768;
        const int rot = usex ? 2 * (j & 6) : 0, flip = usex ? 2 * rank : 0, kmask = usex ? 15 : 63;
        const int head_depth = 8 * ring_depth(ty, 0), tail_depth = 8 * ring_depth(ty, 4);
        uint32_t off = tile_first_slot(i) * step;
#pragma unroll 1
        for (int kk = 0; kk < nkb; kk++) {
          const int lim = nb - (kk < 4 ? head_depth : tail_depth);
          for (; mb <= lim; mb += 8) mbar_wait(sb + kBarEmpty + (mb & 56), (mb >> 6) & 1);
          const int kb = ((rot + kk) & kmask) ^ (kk < 4 ? flip : 0);
          if (elect()) {
            const uint32_t full = sb + kBarFull + (nb & 56);
            mbar_expect_tx(full, (usex && kk < 2) ? step - kTileBytes : step);
            tma3d(sb + kSmRing + kTileBytes + off, map, full, c0, kb * 64, c2);
          }
          off += step;
          if (off == 163840) off = 0;
          nb += 8;
        }
      }
      asm volatile("barrier.cluster.wait.acquire.aligned;" ::: "memory");
    } else {
      asm volatile("barrier.cluster.wait.acquire.aligned;" ::: "memory");
      const unsigned epoch = *reinterpret_cast<volatile unsigned*>(sm + kSmEpoch);
      if (warp == 9) {
        int nb = 0, mb = 0;
        const bool my_rows = ((lane >> 1) & 1) == rank;
        const uint32_t peer = mapa(sb, rank ^ 1);
        const unsigned* flags = g_flag + b * 32 + lane;
#pragma unroll 1
        for (int i = 0; i < kRunTiles; i++) {
          const int layer = i >= 7, ty = i - 7 * layer;
          const bool wide = tile_wide(ty), usex = tile_uses_x(ty);
          const uint32_t step = wide ? 40960 : 32768;
          const int head_depth = 8 * ring_depth(ty, 0), tail_depth = 8 * ring_depth(ty, 4);
          const uint8_t* src = (ty == 6 ? g_h + b * 56 * kTileBytes : (ty == 2 ? g_o : g_x) + b * 16 * kTileBytes) + rank * 8192;
          uint32_t off = tile_first_slot(i) * step;
          int kk = 0, rot = 0, kmask = 63, nseg, line;
          if (usex) {
            const int xver = 2 * layer + (ty >= 3);
            for (; kk < 4; kk++) {
              if (kk >= 2) {
                for (; mb <= nb - head_depth; mb += 8) mbar_wait(sb + kBarEmpty + (mb & 56), (mb >> 6) & 1);
                mbar_wait(sb + kBarX + xver * 8, 0);
                if (elect())
                  bulk_copy_peer(peer + kSmRing + off, sb + kSmX + (kk - 2) * kTileBytes, kTileBytes,
                                 peer + kBarFull + (nb & 56));
              }
              off += step;
              if (off == 163840) off = 0;
              nb += 8;
            }
            rot = 2 * (j & 6);
            kmask = 15;
            nseg = 1;
            line = ((ty == 0 || ty == 3) && xver > 0) ? kFlagX + (xver - 1) * 16 : -1;
          } else {
            nseg = ty == 2 ? 2 : 3;
            line = ty == 2 ? kFlagO + layer * 32 : kFlagH + layer * 48;
          }
#pragma unroll 1
          for (int seg = 0; seg < nseg; seg++) {
            if (line >= 0) {
              wait_flags(flags + (line + seg * 16) * 32, my_rows, epoch);
              fence_async_global();
            }
            const int kend = ty == 6 ? 24 + 16 * seg : ty == 2 ? 8 + 8 * seg : 16;
#pragma unroll 1
            for (; kk < kend; kk++) {
              const int lim = nb - (kk < 4 ? head_depth : tail_depth);
              for (; mb <= lim; mb += 8) mbar_wait(sb + kBarEmpty + (mb & 56), (mb >> 6) & 1);
              const int kb = (rot + kk) & kmask;
              if (elect()) {
                const uint32_t dst = sb + kSmRing + rank * 8192 + off, full = sb + kBarFull + (nb & 56);
                if (i < 2) tma2d_mc(dst, &map_x, full, xcol + kb * 64, xrow + rank * 64);
                else bulk_load_mc(dst, src + kb * kTileBytes, 8192, full);
              }
              off += step;
              if (off == 163840) off = 0;
              nb += 8;
            }
          }
        }
      } else if (warp == 10) {
        float* v1 = reinterpret_cast<float*>(sm + kSmV1);
#pragma unroll 1
        for (int i = lane; i < 448; i += 32) {
          const int col = i < 192 ? 192 * j + i : i < 320 ? 1536 + 128 * j + (i - 192) : 2560 + 128 * j + (i - 320);
          v1[(i >> 1) * 4 + 2 + (i & 1)] = 0.5f * __bfloat162float(prm.b1[col]);
        }
#pragma unroll 1
        for (int i = lane; i < 128; i += 32)
          reinterpret_cast<float*>(sm + kSmB2)[i] = __bfloat162float(prm.b2[128 * j + i]);
        {
          const int blk = lane >> 1;
          const int slab = (blk % 3) * 32 + (j + 8 * (blk / 3)) * 2 + (lane & 1);
          wait_flags(&g_flag[kFlagC * 32 + slab], lane < 12, epoch);
#pragma unroll 4
          for (int i = 0; i < 12; i++) {
            const int s = __shfl_sync(0xffffffffu, slab, i);
            reinterpret_cast<float*>(sm + kSmCsQ)[i * 32 + lane] = __ldcg(&g_cs[s * 32 + lane]);
          }
        }
#pragma unroll 1
        for (int q = 0; q < 1 + (kRunTiles > 2) + (kRunTiles > 6) + (kRunTiles > 9); q++) {
          mbar_wait(sb + kBarX + q * 8, 0);
          if (q == 1) {
            const int slab = lane < 6 ? 6 * j + lane : lane < 10 ? 48 + 4 * j + (lane - 6) : 80 + 4 * j + (lane - 10);
            wait_flags(&g_flag[kFlagC * 32 + 96 + (lane < 14 ? slab : 0)], lane < 14, epoch);
#pragma unroll 2
            for (int i = 0; i < 14; i++) {
              const int s = __shfl_sync(0xffffffffu, slab, i), li = i * 32 + lane;
              v1[(li >> 1) * 4 + (li & 1)] = __ldcg(&g_cs[3 * kD + s * 32 + lane]);
            }
          }
          wait_flags(&g_flag[(kFlagS + q * 16 + b) * 32 + lane], true, epoch);
          reduce_stats(sm, b, lane);
          __syncwarp();
          if (elect()) mbar_arrive(sb + kBarStat + q * 8);
        }
      } else if (kRunTiles == kTiles) {
#pragma unroll 1
        for (int s = 0; s < 6; s++) {
          const int after = (0xA77530 >> (4 * s)) & 15;
          const void* base = s == 0 || s == 3 ? prm.wo : s == 2 ? prm.wqkv : s == 4 ? prm.w1 : prm.w2;
          const int chunks = s == 0 || s == 3 ? 2 : s == 2 ? 6 : 7;
          mbar_wait(sb + kBarTurn + after * 8, 0);
          if (lane < chunks) l2_prefetch(reinterpret_cast<const uint8_t*>(base) + (cta * chunks + lane) * 8192, 8192);
          __syncwarp();
        }
      }
    }
    __syncwarp();
    asm volatile("barrier.cluster.arrive.relaxed.aligned;\nbarrier.cluster.wait.aligned;" ::: "memory");
  } else {
    asm volatile("setmaxnreg.inc.sync.aligned.u32 232;");
    asm volatile("barrier.cluster.wait.acquire.aligned;" ::: "memory");
    const unsigned epoch = *reinterpret_cast<volatile unsigned*>(sm + kSmEpoch);
    const int wg = warp >> 2, w = warp & 3;
    const bool rel = (threadIdx.x & 95) == 0;
    const uint32_t rel_addr = mapa(sb + kBarEmpty, w & 1);

#pragma unroll 1
    for (int i = -wg; i < kRunTiles; i += 2) {
      const int layer = i >= 7, ty = i - 7 * layer;
      const int n0 = tile_first_seq(layer, ty);
      float acc[2][96];
      if (ty == -1 || ty == 2 || ty == 6) {
        const uint32_t xrow_addr = sb + kSmX + (32 * w + lane) * 128;
        const float2* b2 = reinterpret_cast<const float2*>(sm + kSmB2) + (lane & 3);
        const int xver = 2 * layer + (ty + 2) / 4;
        if (i < 0) mbar_wait(sb + kBarX, 0);
#pragma unroll
        for (int J = 0; J < 16; J++) {
          uint32_t r[4];
          ldsm4(xrow_addr + (J >> 3) * kTileBytes + (((J & 7) ^ (lane & 7)) << 4), r);
          float2 bias = make_float2(0.f, 0.f);
          if (ty == 6) bias = b2[J * 4];
#pragma unroll
          for (int c = 0; c < 4; c++) {
            acc[c & 1][4 * J + (c & 2)] = bf_lo(r[c]) + bias.x;
            acc[c & 1][4 * J + (c & 2) + 1] = bf_hi(r[c]) + bias.y;
          }
        }
        if (i >= 0)
          mainloop<128, false>(acc, sb, i, n0, ty == 6 ? 56 : 16, 0, ty == 2 ? PAUSE_WO : -1, 2 * layer + 1, rel_addr, rel);
        if (i >= 0) TRACE_AT(i, 2);
        uint32_t pk[16][4];
#pragma unroll
        for (int J = 0; J < 16; J++)
#pragma unroll
          for (int c = 0; c < 4; c++) pk[J][c] = pack2(acc[c & 1][4 * J + (c & 2)], acc[c & 1][4 * J + (c & 2) + 1]);
        if (i >= 0) {
#pragma unroll
          for (int J = 0; J < 16; J++)
            stsm4(xrow_addr + (J >> 3) * kTileBytes + (((J & 7) ^ (lane & 7)) << 4), pk[J][0], pk[J][1], pk[J][2], pk[J][3]);
          fence_async_smem();
          __syncwarp();
          if (elect()) {
            const uint32_t src = sb + kSmX + w * 4096;
            if (xver == 4) {
              tma2d_store(&map_out, src, xcol + j * 128, xrow + 32 * w);
              tma2d_store(&map_out, src + kTileBytes, xcol + j * 128 + 64, xrow + 32 * w);
            } else {
              mbar_arrive(sb + kBarX + xver * 8);
              uint8_t* dst = g_x + (b * 16 + 2 * j) * kTileBytes + w * 4096;
              bulk_store(dst, src, 4096);
              bulk_store(dst + kTileBytes, src + kTileBytes, 4096);
            }
            bulk_commit();
            bulk_wait();
            if (xver < 4) st_release(&g_flag[(kFlagX + (xver - 1) * 16 + b) * 32 + j * 4 + w], epoch);
          }
          __syncwarp();
        }
        if (xver < 4) {
          publish_stats(pk, b, j, w, lane);
          __syncwarp();
          if (elect()) st_release(&g_flag[(kFlagS + xver * 16 + b) * 32 + j * 4 + w], epoch);
        }
      } else if (ty < 2) {
        zero_acc<192>(acc);
        if (ty == 1) {
          mbar_wait(sb + kBarStat + layer * 16, 0);
          add_mean_term(acc, sm, 1, w, lane);
        }
        mainloop<192, true>(acc, sb, i, n0, 16, 2 * layer, ty == 1 ? PAUSE_QKV2 : -1, 2 * layer, rel_addr, rel);
        TRACE_AT(i, 2);
        if (ty == 0) {
          mbar_wait(sb + kBarStat + layer * 16, 0);
          add_mean_term(acc, sm, 0, w, lane);
        } else {
          mbar_wait(sb + kBarEpi + (i - 1) * 8, 0);
        }
        epilogue_attn(acc, sm, sb, layer, ty, b, j, epoch, i, wg, w);
      } else {
        zero_acc<192>(acc);
        if (ty == 3) mainloop<192, true>(acc, sb, i, n0, 16, 2 * layer + 1, -1, 0, rel_addr, rel);
        else mainloop<128, true>(acc, sb, i, n0, 16, 2 * layer + 1, -1, 0, rel_addr, rel);
        TRACE_AT(i, 2);
        mbar_wait(sb + kBarStat + layer * 16 + 8, 0);
        if (ty > 3) mbar_wait(sb + kBarEpi + (i - 1) * 8, 0);
        const int blk = ty == 3 ? 3 * j : 16 * ty - 40 + 2 * j;
        epilogue_gelu(acc, sm, sb, ty == 3, ty == 3 ? 0 : 128 * ty - 320, g_h + (b * 56 + blk) * kTileBytes + w * 4096,
                      &g_flag[(kFlagH + (layer * 3 + ty - 3) * 16 + b) * 32 + j * 4 + w], epoch, i, w);
      }
      if (i >= 0) TRACE_AT(i, 3);
      if (i <= 0 && cta < (i < 0 ? 96 : 112))
        colsum_slab(i < 0 ? prm.wqkv : prm.w1, i < 0 ? 3 * kD : kF, cta * 32, g_cs + (i < 0 ? 0 : 3 * kD),
                    &g_flag[kFlagC * 32 + (i < 0 ? 0 : 96) + cta], epoch, sm, wg, w);
    }
    asm volatile("barrier.cluster.arrive.relaxed.aligned;\nbarrier.cluster.wait.aligned;" ::: "memory");
  }
}

typedef CUresult (*EncodeTiledFn)(CUtensorMap*, CUtensorMapDataType, cuuint32_t, void*, const cuuint64_t*,
                                  const cuuint64_t*, const cuuint32_t*, const cuuint32_t*, CUtensorMapInterleave,
                                  CUtensorMapSwizzle, CUtensorMapL2promotion, CUtensorMapFloatOOBfill);

CUtensorMap make_map(EncodeTiledFn enc, const void* p, int rank, const cuuint64_t* dims, const cuuint64_t* strides,
                     const cuuint32_t* box) {
  CUtensorMap m;
  const cuuint32_t es[5] = {1, 1, 1, 1, 1};
  enc(&m, CU_TENSOR_MAP_DATA_TYPE_BFLOAT16, rank, const_cast<void*>(p), dims, strides, box, es,
      CU_TENSOR_MAP_INTERLEAVE_NONE, CU_TENSOR_MAP_SWIZZLE_128B, CU_TENSOR_MAP_L2_PROMOTION_L2_128B,
      CU_TENSOR_MAP_FLOAT_OOB_FILL_NONE);
  return m;
}

CUtensorMap weight_map(EncodeTiledFn enc, const void* p, int k, int n, int blocks) {
  const cuuint64_t dims[3] = {64, (cuuint64_t)k, (cuuint64_t)n / 64};
  const cuuint64_t strides[2] = {(cuuint64_t)n * 2, 128};
  const cuuint32_t box[3] = {64, 64, (cuuint32_t)blocks};
  return make_map(enc, p, 3, dims, strides, box);
}

CUtensorMap token_map(EncodeTiledFn enc, const void* p, int rows) {
  const cuuint64_t dims[2] = {2 * kD, 1024};
  const cuuint64_t strides[1] = {4 * kD};
  const cuuint32_t box[2] = {64, (cuuint32_t)rows};
  return make_map(enc, p, 2, dims, strides, box);
}

}

extern "C" void kernel_launch(void* const* d_in, const int* in_sizes, int n_in, void* d_out, int out_size) {
  (void)in_sizes; (void)n_in; (void)out_size;
  static EncodeTiledFn enc = nullptr;
  if (!enc) {
    void* fn = nullptr;
    cudaDriverEntryPointQueryResult q;
    cudaGetDriverEntryPoint("cuTensorMapEncodeTiled", &fn, cudaEnableDefault, &q);
    enc = (EncodeTiledFn)fn;
    cudaFuncSetAttribute(fused_layers_kernel, cudaFuncAttributeMaxDynamicSharedMemorySize, kSmBytes);
  }
  Params prm;
  prm.wqkv = (const __nv_bfloat16*)d_in[1];
  prm.wo = (const __nv_bfloat16*)d_in[2];
  prm.w1 = (const __nv_bfloat16*)d_in[4];
  prm.b1 = (const __nv_bfloat16*)d_in[5];
  prm.w2 = (const __nv_bfloat16*)d_in[6];
  prm.b2 = (const __nv_bfloat16*)d_in[7];
  const cuuint64_t qd[3] = {kD, kD, 3}, qs[2] = {3 * kD * 2, kD * 2};
  const cuuint32_t qb[3] = {64, 64, 3};
  const CUtensorMap map_x = token_map(enc, d_in[0], 64);
  const CUtensorMap map_out = token_map(enc, d_out, 32);
  const CUtensorMap map_qkv = make_map(enc, prm.wqkv, 3, qd, qs, qb);
  const CUtensorMap map_wo = weight_map(enc, prm.wo, kD, kD, 2);
  const CUtensorMap map_w1a = weight_map(enc, prm.w1, kD, kF, 3);
  const CUtensorMap map_w1b = weight_map(enc, prm.w1, kD, kF, 2);
  const CUtensorMap map_w2 = weight_map(enc, prm.w2, kF, kD, 2);
  fused_layers_kernel<<<kCtas, 384, kSmBytes>>>(map_x, map_out, map_qkv, map_wo, map_w1a, map_w1b, map_w2, prm);
}
```

```cpp
#include <cuda.h>
#include <cuda_bf16.h>
#include <cuda_runtime.h>
#include <stdint.h>

namespace {

constexpr int kD = 1024;
constexpr int kF = 3584;
constexpr int kCtas = 128;
constexpr int kTiles = 14;
constexpr int kRunTiles = kTiles;
constexpr int kTileBytes = 16384;

constexpr int kSmRing = 0;
constexpr int kSmX = 163840;
constexpr int kSmStg = kSmX + 32768;
constexpr int kSmHalo = kSmStg + 16384;
constexpr int kSmCsQ = kSmHalo + 6144;
constexpr int kSmV1 = kSmCsQ + 384 * 4;
constexpr int kSmB2 = kSmV1 + 448 * 8;
constexpr int kSmStat = kSmB2 + 128 * 4;
constexpr int kSmRed = kSmStat + 128 * 8;
constexpr int kSmBar = kSmRed + 512;
constexpr int kBarFull = kSmBar;
constexpr int kBarEmpty = kBarFull + 64;
constexpr int kBarTurn = kBarEmpty + 64;
constexpr int kBarEpi = kBarTurn + kTiles * 8;
constexpr int kBarX = kBarEpi + kTiles * 8;
constexpr int kBarStat = kBarX + 32;
constexpr int kBarPause = kBarStat + 32;
constexpr int kBarResume = kBarPause + 32;
constexpr int kBarReady = kBarResume + 32;
constexpr int kSmEpoch = kBarReady + 14 * 8;
constexpr int kSmBytes = kSmEpoch + 16;

constexpr int kFlagLines = kTiles * 16;

constexpr unsigned kSpinLimit = 1u << 24;

__device__ __align__(1024) uint8_t g_x[16 * 16 * kTileBytes];
__device__ __align__(1024) uint8_t g_o[16 * 16 * kTileBytes];
__device__ __align__(1024) uint8_t g_h[16 * 56 * kTileBytes];
__device__ __align__(128) uint2 g_stat[4 * 16 * 128 * 8];
__device__ __align__(128) unsigned g_cs[3 * kD + kF];
__device__ __align__(128) uint4 g_halo[2 * 16 * 16 * 256];
__device__ __align__(128) unsigned g_flag[kFlagLines * 32];
__device__ unsigned g_ticket;

#define TRACE_AT(tile, k)

struct Params {
  const __nv_bfloat16* wqkv;
  const __nv_bfloat16* wo;
  const __nv_bfloat16* w1;
  const __nv_bfloat16* b1;
  const __nv_bfloat16* w2;
  const __nv_bfloat16* b2;
};

__device__ __forceinline__ uint32_t smem_u32(const void* p) {
  return (uint32_t)__cvta_generic_to_shared(p);
}
__device__ __forceinline__ uint32_t mapa(uint32_t a, uint32_t cta) {
  uint32_t r;
  asm("mapa.shared::cluster.u32 %0, %1, %2;" : "=r"(r) : "r"(a), "r"(cta));
  return r;
}
__device__ __forceinline__ void mbar_init(uint32_t bar, int cnt) {
  asm volatile("mbarrier.init.shared::cta.b64 [%0], %1;" ::"r"(bar), "r"(cnt) : "memory");
}
__device__ __forceinline__ void mbar_expect_tx(uint32_t bar, uint32_t bytes) {
  asm volatile("mbarrier.arrive.expect_tx.shared::cta.b64 _, [%0], %1;" ::"r"(bar), "r"(bytes) : "memory");
}
__device__ __forceinline__ void mbar_arrive(uint32_t bar) {
  asm volatile("mbarrier.arrive.shared::cta.b64 _, [%0];" ::"r"(bar) : "memory");
}
__device__ __forceinline__ void mbar_arrive_cluster(uint32_t cluster_addr) {
  asm volatile("mbarrier.arrive.shared::cluster.b64 _, [%0];" ::"r"(cluster_addr) : "memory");
}
__device__ __forceinline__ void mbar_wait(uint32_t bar, uint32_t parity) {
  asm volatile(
      "{\n.reg .pred p;\n.reg .u32 c;\n"
      "mbarrier.try_wait.parity.shared::cta.b64 p, [%0], %1;\n"
      "@p bra.uni DONE;\n"
      "mov.u32 c, 0;\n"
      "RETRY:\n"
      "mbarrier.try_wait.parity.shared::cta.b64 p, [%0], %1;\n"
      "@p bra.uni DONE;\n"
      "add.u32 c, c, 1;\n"
      "setp.lt.u32 p, c, %2;\n"
      "@p bra.uni RETRY;\n"
      "trap;\n"
      "DONE:\n}" ::"r"(bar), "r"(parity), "n"(kSpinLimit)
      : "memory");
}
__device__ __forceinline__ void tma3d_mc(uint32_t dst, const CUtensorMap* m, uint32_t bar, int c0, int c1, int c2) {
  asm volatile(
      "cp.async.bulk.tensor.3d.shared::cluster.global.mbarrier::complete_tx::bytes.multicast::cluster"
      " [%0], [%1, {%3, %4, %5}], [%2], %6;"
      ::"r"(dst), "l"(m), "r"(bar), "r"(c0), "r"(c1), "r"(c2), "h"((uint16_t)3) : "memory");
}
__device__ __forceinline__ void tma2d(uint32_t dst, const CUtensorMap* m, uint32_t bar, int c0, int c1) {
  asm volatile(
      "cp.async.bulk.tensor.2d.shared::cluster.global.mbarrier::complete_tx::bytes [%0], [%1, {%3, %4}], [%2];"
      ::"r"(dst), "l"(m), "r"(bar), "r"(c0), "r"(c1) : "memory");
}
__device__ __forceinline__ void tma2d_store(const CUtensorMap* m, uint32_t src, int c0, int c1) {
  asm volatile("cp.async.bulk.tensor.2d.global.shared::cta.bulk_group [%0, {%2, %3}], [%1];"
               ::"l"(m), "r"(src), "r"(c0), "r"(c1) : "memory");
}
__device__ __forceinline__ bool elect() {
  uint32_t p;
  asm volatile("{\n.reg .pred p;\nelect.sync _|p, 0xffffffff;\nselp.b32 %0, 1, 0, p;\n}" : "=r"(p));
  return p;
}
__device__ __forceinline__ void bulk_load(uint32_t dst, const void* src, uint32_t bytes, uint32_t bar) {
  asm volatile("cp.async.bulk.shared::cluster.global.mbarrier::complete_tx::bytes [%0], [%1], %2, [%3];"
               ::"r"(dst), "l"(src), "r"(bytes), "r"(bar) : "memory");
}
__device__ __forceinline__ void bulk_store(void* dst, uint32_t src, uint32_t bytes) {
  asm volatile("cp.async.bulk.global.shared::cta.bulk_group [%0], [%1], %2;" ::"l"(dst), "r"(src), "r"(bytes)
               : "memory");
}
__device__ __forceinline__ void bulk_commit() { asm volatile("cp.async.bulk.commit_group;" ::: "memory"); }
__device__ __forceinline__ void bulk_wait_read() { asm volatile("cp.async.bulk.wait_group.read 0;" ::: "memory"); }
__device__ __forceinline__ void bulk_wait() { asm volatile("cp.async.bulk.wait_group 0;" ::: "memory"); }
__device__ __forceinline__ void l2_prefetch(const void* p, uint32_t bytes) {
  asm volatile("cp.async.bulk.prefetch.L2.global [%0], %1;" ::"l"(p), "r"(bytes) : "memory");
}
__device__ __forceinline__ void fence_async_smem() { asm volatile("fence.proxy.async.shared::cta;" ::: "memory"); }
__device__ __forceinline__ unsigned ld_relaxed(const unsigned* p) {
  unsigned v;
  asm volatile("ld.relaxed.gpu.global.u32 %0, [%1];" : "=r"(v) : "l"(p) : "memory");
  return v;
}
__device__ __forceinline__ uint4 ld_relaxed4(const void* p) {
  uint4 v;
  asm volatile("ld.relaxed.gpu.global.v4.u32 {%0, %1, %2, %3}, [%4];"
               : "=r"(v.x), "=r"(v.y), "=r"(v.z), "=r"(v.w) : "l"(p) : "memory");
  return v;
}
__device__ __forceinline__ void st_relaxed(unsigned* p, unsigned v) {
  asm volatile("st.relaxed.gpu.global.u32 [%0], %1;" ::"l"(p), "r"(v) : "memory");
}
__device__ __forceinline__ void wait_flags(const unsigned* p, unsigned epoch) {
  unsigned spins = 0;
  while (true) {
    const unsigned v = ld_relaxed(p);
    if (__all_sync(0xffffffffu, v == epoch)) break;
    if (++spins > kSpinLimit) __trap();
  }
}
__device__ __forceinline__ unsigned tag_value(float v, unsigned epoch) {
  return (__float_as_uint(v) & ~7u) | (epoch & 7u);
}
__device__ __forceinline__ float untag_value(unsigned v) { return __uint_as_float(v & ~7u); }
__device__ __forceinline__ void stsm4(uint32_t a, uint32_t r0, uint32_t r1, uint32_t r2, uint32_t r3) {
  asm volatile("stmatrix.sync.aligned.m8n8.x4.shared.b16 [%0], {%1, %2, %3, %4};" ::"r"(a), "r"(r0), "r"(r1),
               "r"(r2), "r"(r3) : "memory");
}
__device__ __forceinline__ void stsm4_t(uint32_t a, uint32_t r0, uint32_t r1, uint32_t r2, uint32_t r3) {
  asm volatile("stmatrix.sync.aligned.m8n8.x4.trans.shared.b16 [%0], {%1, %2, %3, %4};" ::"r"(a), "r"(r0),
               "r"(r1), "r"(r2), "r"(r3) : "memory");
}
__device__ __forceinline__ uint32_t transpose8(uint32_t a) {
  uint32_t d;
  asm volatile("movmatrix.sync.aligned.m8n8.trans.b16 %0, %1;" : "=r"(d) : "r"(a));
  return d;
}
__device__ __forceinline__ void mma16816(float (&c)[4], uint32_t a0, uint32_t a1, uint32_t a2, uint32_t a3,
                                         uint32_t b0, uint32_t b1) {
  asm volatile("mma.sync.aligned.m16n8k16.row.col.f32.bf16.bf16.f32 {%0, %1, %2, %3}, {%4, %5, %6, %7}, {%8, %9}, "
               "{%0, %1, %2, %3};"
               : "+f"(c[0]), "+f"(c[1]), "+f"(c[2]), "+f"(c[3])
               : "r"(a0), "r"(a1), "r"(a2), "r"(a3), "r"(b0), "r"(b1));
}
__device__ __forceinline__ float shfl_xor(float v, int m) {
  float r;
  asm volatile("shfl.sync.bfly.b32 %0, %1, %2, 31, 0xffffffff;" : "=f"(r) : "f"(v), "r"(m));
  return r;
}
__device__ __forceinline__ float tanh_fast(float x) {
  float r;
  asm("tanh.approx.f32 %0, %1;" : "=f"(r) : "f"(x));
  return r;
}
__device__ __forceinline__ void ldsm4(uint32_t a, uint32_t (&r)[4]) {
  asm volatile("ldmatrix.sync.aligned.m8n8.x4.shared.b16 {%0, %1, %2, %3}, [%4];"
               : "=r"(r[0]), "=r"(r[1]), "=r"(r[2]), "=r"(r[3]) : "r"(a) : "memory");
}
__device__ __forceinline__ uint32_t pack2(float lo, float hi) {
  uint32_t r;
  asm("cvt.rn.bf16x2.f32 %0, %1, %2;" : "=r"(r) : "f"(hi), "f"(lo));
  return r;
}
__device__ __forceinline__ float bf_lo(uint32_t r) { return __uint_as_float(r << 16); }
__device__ __forceinline__ float bf_hi(uint32_t r) { return __uint_as_float(r & 0xffff0000u); }
__device__ __forceinline__ float ex2(float x) {
  float r;
  asm("ex2.approx.ftz.f32 %0, %1;" : "=f"(r) : "f"(x));
  return r;
}
__device__ __forceinline__ float rcp(float x) {
  float r;
  asm("rcp.approx.ftz.f32 %0, %1;" : "=f"(r) : "f"(x));
  return r;
}
template <int N>
__device__ __forceinline__ void wg_wait() {
  asm volatile("wgmma.wait_group.sync.aligned %0;" ::"n"(N) : "memory");
}
__device__ __forceinline__ void wg_bar(int wg) { asm volatile("bar.sync %0, 128;" ::"r"(wg + 1) : "memory"); }

template <int N>
__device__ __forceinline__ void mma_kblock(float (&acc)[2][96], uint32_t a, uint32_t b);

#define F8(d, i) \
  "+f"(d[i]), "+f"(d[i + 1]), "+f"(d[i + 2]), "+f"(d[i + 3]), "+f"(d[i + 4]), "+f"(d[i + 5]), "+f"(d[i + 6]), "+f"(d[i + 7])
#define KSTEP(N, A, B, oa0, oa1, ob)                                                       \
  "add.u32 t, " B ", " #ob ";\nmov.b64 db, {t, hb};\n"                                      \
  "add.u32 t, " A ", " #oa0 ";\nmov.b64 da, {t, ha};\n"                                     \
  "wgmma.mma_async.sync.aligned.m64n" #N "k16.f32.bf16.bf16 {" ACC##N##_0 "}, da, db, 1, 1, 1, 0, 1;\n" \
  "add.u32 t, " A ", " #oa1 ";\nmov.b64 da, {t, ha};\n"                                     \
  "wgmma.mma_async.sync.aligned.m64n" #N "k16.f32.bf16.bf16 {" ACC##N##_1 "}, da, db, 1, 1, 1, 0, 1;\n"

#define ACC128_0 \
  "%0, %1, %2, %3, %4, %5, %6, %7, %8, %9, %10, %11, %12, %13, %14, %15, " \
  "%16, %17, %18, %19, %20, %21, %22, %23, %24, %25, %26, %27, %28, %29, %30, %31, " \
  "%32, %33, %34, %35, %36, %37, %38, %39, %40, %41, %42, %43, %44, %45, %46, %47, " \
  "%48, %49, %50, %51, %52, %53, %54, %55, %56, %57, %58, %59, %60, %61, %62, %63"
#define ACC128_1 \
  "%64, %65, %66, %67, %68, %69, %70, %71, %72, %73, %74, %75, %76, %77, %78, %79, " \
  "%80, %81, %82, %83, %84, %85, %86, %87, %88, %89, %90, %91, %92, %93, %94, %95, " \
  "%96, %97, %98, %99, %100, %101, %102, %103, %104, %105, %106, %107, %108, %109, %110, %111, " \
  "%112, %113, %114, %115, %116, %117, %118, %119, %120, %121, %122, %123, %124, %125, %126, %127"
template <>
__device__ __forceinline__ void mma_kblock<128>(float (&acc)[2][96], uint32_t a, uint32_t b) {
  asm volatile("{\n.reg .b32 t, ha, hb;\n.reg .b64 da, db;\n"
               "mov.b32 ha, 0x40000080;\nmov.b32 hb, 0x40000040;\n"
               "wgmma.fence.sync.aligned;\n"
               KSTEP(128, "%128", "%129", 0, 64, 0) KSTEP(128, "%128", "%129", 2, 66, 128)
               KSTEP(128, "%128", "%129", 4, 68, 512) KSTEP(128, "%128", "%129", 6, 70, 640)
               "wgmma.commit_group.sync.aligned;\n}\n"
      : F8(acc[0], 0), F8(acc[0], 8), F8(acc[0], 16), F8(acc[0], 24), F8(acc[0], 32), F8(acc[0], 40), F8(acc[0], 48), F8(acc[0], 56),
        F8(acc[1], 0), F8(acc[1], 8), F8(acc[1], 16), F8(acc[1], 24), F8(acc[1], 32), F8(acc[1], 40), F8(acc[1], 48), F8(acc[1], 56)
      : "r"(a), "r"(b)
      : "memory");
}

#define ACC192_0 \
  "%0, %1, %2, %3, %4, %5, %6, %7, %8, %9, %10, %11, %12, %13, %14, %15, " \
  "%16, %17, %18, %19, %20, %21, %22, %23, %24, %25, %26, %27, %28, %29, %30, %31, " \
  "%32, %33, %34, %35, %36, %37, %38, %39, %40, %41, %42, %43, %44, %45, %46, %47, " \
  "%48, %49, %50, %51, %52, %53, %54, %55, %56, %57, %58, %59, %60, %61, %62, %63, " \
  "%64, %65, %66, %67, %68, %69, %70, %71, %72, %73, %74, %75, %76, %77, %78, %79, " \
  "%80, %81, %82, %83, %84, %85, %86, %87, %88, %89, %90, %91, %92, %93, %94, %95"
#define ACC192_1 \
  "%96, %97, %98, %99, %100, %101, %102, %103, %104, %105, %106, %107, %108, %109, %110, %111, " \
  "%112, %113, %114, %115, %116, %117, %118, %119, %120, %121, %122, %123, %124, %125, %126, %127, " \
  "%128, %129, %130, %131, %132, %133, %134, %135, %136, %137, %138, %139, %140, %141, %142, %143, " \
  "%144, %145, %146, %147, %148, %149, %150, %151, %152, %153, %154, %155, %156, %157, %158, %159, " \
  "%160, %161, %162, %163, %164, %165, %166, %167, %168, %169, %170, %171, %172, %173, %174, %175, " \
  "%176, %177, %178, %179, %180, %181, %182, %183, %184, %185, %186, %187, %188, %189, %190, %191"
template <>
__device__ __forceinline__ void mma_kblock<192>(float (&acc)[2][96], uint32_t a, uint32_t b) {
  asm volatile("{\n.reg .b32 t, ha, hb;\n.reg .b64 da, db;\n"
               "mov.b32 ha, 0x40000080;\nmov.b32 hb, 0x40000040;\n"
               "wgmma.fence.sync.aligned;\n"
               KSTEP(192, "%192", "%193", 0, 64, 0) KSTEP(192, "%192", "%193", 2, 66, 128)
               KSTEP(192, "%192", "%193", 4, 68, 768) KSTEP(192, "%192", "%193", 6, 70, 896)
               "wgmma.commit_group.sync.aligned;\n}\n"
      : F8(acc[0], 0), F8(acc[0], 8), F8(acc[0], 16), F8(acc[0], 24), F8(acc[0], 32), F8(acc[0], 40), F8(acc[0], 48), F8(acc[0], 56), F8(acc[0], 64), F8(acc[0], 72), F8(acc[0], 80), F8(acc[0], 88),
        F8(acc[1], 0), F8(acc[1], 8), F8(acc[1], 16), F8(acc[1], 24), F8(acc[1], 32), F8(acc[1], 40), F8(acc[1], 48), F8(acc[1], 56), F8(acc[1], 64), F8(acc[1], 72), F8(acc[1], 80), F8(acc[1], 88)
      : "r"(a), "r"(b)
      : "memory");
}

__device__ __forceinline__ int tile_first_seq(int layer, int ty) { return layer * 152 + ty * 16; }
__device__ __forceinline__ int tile_first_slot(int i) { return (int)((0x21004333211000ull >> (4 * i)) & 7); }
__device__ __forceinline__ bool tile_wide(int ty) { return ty == 0 || ty == 1 || ty == 3; }
__device__ __forceinline__ bool tile_uses_x(int ty) { return ty != 2 && ty != 6; }
__device__ __forceinline__ int ring_depth(int ty, int kk) {
  return (tile_wide(ty) || ((ty == 2 || ty == 4) && kk < 4)) ? 4 : 5;
}
__device__ __forceinline__ int x_kblock(int j, int kk) { return kk < 2 ? 2 * j + kk : kk - 2 < 2 * j ? kk - 2 : kk; }

template <int N>
__device__ __forceinline__ void fence_acc(float (&acc)[2][96]) {
#pragma unroll
  for (int h = 0; h < 2; h++)
#pragma unroll
    for (int i = 0; i < N / 2; i++) asm volatile("" : "+f"(acc[h][i])::"memory");
}

template <int N>
__device__ __forceinline__ void zero_acc(float (&acc)[2][96]) {
#pragma unroll
  for (int h = 0; h < 2; h++)
#pragma unroll
    for (int i = 0; i < N / 2; i++) acc[h][i] = 0.f;
}

template <int N, bool USEX>
__device__ __forceinline__ void mainloop(float (&acc)[2][96], uint32_t sb, int tile, int n0, int nkb, int xver,
                                         int pause_kk, int att, uint32_t rel_addr, bool rel) {
  constexpr uint32_t kStep = (N == 192 ? 5 : 4) * 512;
  const uint32_t ring = (((sb & 0x3FFFF) + kSmRing) >> 4) | (1u << 16);
  const uint32_t xdesc = (((sb & 0x3FFFF) + kSmX) >> 4) | (1u << 16);
  constexpr uint32_t kToB = (kTileBytes >> 4) + ((4096u >> 4) << 16) - (1u << 16);
  uint32_t st = ring + tile_first_slot(tile) * kStep;
  uint32_t nb = n0 * 8;
  const bool signal = (threadIdx.x & 127) == 64;
  fence_acc<N>(acc);
  if (tile > 0) mbar_wait(sb + kBarTurn + (tile - 1) * 8, 0);
  if (USEX) mbar_wait(sb + kBarX + xver * 8, 0);
  TRACE_AT(tile, 0);
  int kk = 0;
#pragma unroll 1
  do {
    if (kk == pause_kk) {
      if (signal) mbar_arrive(sb + kBarPause + att * 8);
      mbar_wait(sb + kBarResume + att * 8, 0);
    }
    mbar_wait(sb + kBarFull + (nb & 56), (nb >> 6) & 1);
    if (kk == 0) TRACE_AT(tile, 1);
    mma_kblock<N>(acc, (USEX && kk < 2) ? xdesc + kk * (kTileBytes >> 4) : st, st + kToB);
    if (kk == nkb - 1 && signal) mbar_arrive(sb + kBarTurn + tile * 8);
    wg_wait<1>();
    if (rel && kk > 0) mbar_arrive_cluster(rel_addr + ((nb - 8) & 56));
    st += kStep;
    if (st == ring + 10240) st = ring;
    nb += 8;
  } while (++kk < nkb);
  wg_wait<0>();
  if (rel) mbar_arrive_cluster(rel_addr + ((nb - 8) & 56));
  fence_acc<N>(acc);
}

__device__ __forceinline__ void publish_stats(const uint32_t (&pk)[16][4], uint2* stat, int j, int w, int lane,
                                              unsigned epoch) {
  float s[4], q[4];
#pragma unroll
  for (int c = 0; c < 4; c++) {
    s[c] = 0.f;
    q[c] = 0.f;
#pragma unroll
    for (int J = 0; J < 16; J++) {
      const float lo = bf_lo(pk[J][c]), hi = bf_hi(pk[J][c]);
      s[c] += lo;
      q[c] = fmaf(lo, lo, q[c]);
      s[c] += hi;
      q[c] = fmaf(hi, hi, q[c]);
    }
  }
#pragma unroll
  for (int c = 0; c < 4; c++) {
    s[c] += shfl_xor(s[c], 1);
    q[c] += shfl_xor(q[c], 1);
    s[c] += shfl_xor(s[c], 2);
    q[c] += shfl_xor(q[c], 2);
  }
  const int t = lane & 3, g = lane >> 2;
  const float so = t == 0 ? s[0] : t == 1 ? s[1] : t == 2 ? s[2] : s[3];
  const float qo = t == 0 ? q[0] : t == 1 ? q[1] : t == 2 ? q[2] : q[3];
  asm volatile("st.relaxed.gpu.global.v2.u32 [%0], {%1, %2};" ::"l"(stat + (32 * w + 8 * t + g) * 8 + j),
               "r"(tag_value(so, epoch)), "r"(tag_value(qo, epoch)) : "memory");
}

__device__ __forceinline__ void colsum_slab(const __nv_bfloat16* wt, int ld, int col0, unsigned* out,
                                            unsigned epoch, uint8_t* sm, int wg, int w) {
  const int tid = threadIdx.x & 127, lane = tid & 31;
  const uint4* p = reinterpret_cast<const uint4*>(wt + (size_t)(tid >> 2) * ld + col0 + (tid & 3) * 8);
  float a[8];
#pragma unroll
  for (int e = 0; e < 8; e++) a[e] = 0.f;
  {
    uint4 v[32];
#pragma unroll
    for (int i = 0; i < 32; i++) {
      v[i] = __ldg(p);
      p += ld * 4;
    }
#pragma unroll
    for (int i = 0; i < 32; i++) {
      a[0] += bf_lo(v[i].x); a[1] += bf_hi(v[i].x);
      a[2] += bf_lo(v[i].y); a[3] += bf_hi(v[i].y);
      a[4] += bf_lo(v[i].z); a[5] += bf_hi(v[i].z);
      a[6] += bf_lo(v[i].w); a[7] += bf_hi(v[i].w);
    }
  }
#pragma unroll
  for (int e = 0; e < 8; e++) {
    a[e] += shfl_xor(a[e], 4);
    a[e] += shfl_xor(a[e], 8);
    a[e] += shfl_xor(a[e], 16);
  }
  float* red = reinterpret_cast<float*>(sm + kSmRed);
  if (lane < 4) {
#pragma unroll
    for (int e = 0; e < 8; e++) red[w * 32 + lane * 8 + e] = a[e];
  }
  wg_bar(wg);
  if (w == 0)
    st_relaxed(out + col0 + lane, tag_value((red[lane] + red[32 + lane]) + (red[64 + lane] + red[96 + lane]), epoch));
}

__device__ __forceinline__ float gelu_half(float v) {
  constexpr float c0 = 2.f * 0.7978845608028654f;
  constexpr float c1 = 8.f * 0.7978845608028654f * 0.044715f;
  return fmaf(v, tanh_fast(v * fmaf(v * v, c1, c0)), v);
}

template <int CH>
__device__ __forceinline__ void gelu_chunk(const float (&acc)[2][96], const float2 (&st)[4], const float4* vec,
                                           uint32_t stg, int lane, uint8_t* dst) {
  uint32_t pk[8][4];
#pragma unroll
  for (int jj = 0; jj < 8; jj++) {
    const int J = CH * 8 + jj;
    const float4 v = vec[J * 4];
#pragma unroll
    for (int c = 0; c < 4; c++) {
      const float u0 = fmaf(acc[c & 1][4 * J + (c & 2)], st[c].x, fmaf(st[c].y, v.x, v.z));
      const float u1 = fmaf(acc[c & 1][4 * J + (c & 2) + 1], st[c].x, fmaf(st[c].y, v.y, v.w));
      pk[jj][c] = pack2(gelu_half(u0), gelu_half(u1));
    }
  }
  if (CH > 0) {
    if (elect()) bulk_wait_read();
    __syncwarp();
  }
#pragma unroll
  for (int jj = 0; jj < 8; jj++)
    stsm4(stg + lane * 128 + ((jj ^ (lane & 7)) << 4), pk[jj][0], pk[jj][1], pk[jj][2], pk[jj][3]);
  fence_async_smem();
  __syncwarp();
  if (elect()) {
    bulk_store(dst + CH * kTileBytes, stg, 4096);
    bulk_commit();
  }
}

__device__ __forceinline__ void epilogue_gelu(const float (&acc)[2][96], uint8_t* sm, uint32_t sb, bool wide,
                                              int vcol0, uint8_t* dst, unsigned* flag, unsigned epoch, int tile,
                                              int w) {
  const int lane = threadIdx.x & 31, t = lane & 3, g = lane >> 2;
  float2 st[4];
#pragma unroll
  for (int c = 0; c < 4; c++) {
    const float2 v = reinterpret_cast<const float2*>(sm + kSmStat)[32 * w + 8 * c + g];
    st[c].x = 0.5f * v.x;
    st[c].y = st[c].x * v.y;
  }
  const float4* vec = reinterpret_cast<const float4*>(sm + kSmV1) + vcol0 / 2 + t;
  const uint32_t stg = sb + kSmStg + w * 4096;
  TRACE_AT(tile, 8);
  gelu_chunk<0>(acc, st, vec, stg, lane, dst);
  TRACE_AT(tile, 9);
  gelu_chunk<1>(acc, st, vec, stg, lane, dst);
  TRACE_AT(tile, 10);
  if (wide) gelu_chunk<2>(acc, st, vec, stg, lane, dst);
  TRACE_AT(tile, 11);
  if (elect()) {
    bulk_wait();
    TRACE_AT(tile, 12);
    mbar_arrive(sb + kBarEpi + tile * 8);
    st_relaxed(flag, epoch);
  }
  __syncwarp();
}

__device__ __forceinline__ void add_mean_term(float (&acc)[2][96], uint8_t* sm, int tq, int w, int lane) {
  const int t = lane & 3, g = lane >> 2;
  float nm[4];
#pragma unroll
  for (int c = 0; c < 4; c++) nm[c] = reinterpret_cast<const float2*>(sm + kSmStat)[32 * w + 8 * c + g].y;
  const float2* cs = reinterpret_cast<const float2*>(sm + kSmCsQ) + tq * 96 + t;
#pragma unroll
  for (int J = 0; J < 24; J++) {
    const float2 v = cs[J * 4];
#pragma unroll
    for (int c = 0; c < 4; c++) {
      acc[c & 1][4 * J + (c & 2)] = fmaf(nm[c], v.x, acc[c & 1][4 * J + (c & 2)]);
      acc[c & 1][4 * J + (c & 2) + 1] = fmaf(nm[c], v.y, acc[c & 1][4 * J + (c & 2) + 1]);
    }
  }
}

__device__ __forceinline__ void epilogue_attn(const float (&acc)[2][96], uint8_t* sm, uint32_t sb, int layer, int tq,
                                              int b, int j, unsigned epoch, int tile, int wg, int w) {
  const int lane = threadIdx.x & 31, t = lane & 3, g = lane >> 2;
  const int hp = j + 8 * tq, att = 2 * layer + tq;
  float rs[4];
#pragma unroll
  for (int c = 0; c < 4; c++) rs[c] = reinterpret_cast<const float2*>(sm + kSmStat)[32 * w + 8 * c + g].x;
  uint32_t q[4][8], k[5][8], vt[5][8];
#define SCALED(c, J) pack2(acc[(c) & 1][4 * (J) + ((c) & 2)] * rs[c], acc[(c) & 1][4 * (J) + ((c) & 2) + 1] * rs[c])
#pragma unroll
  for (int J = 0; J < 8; J++) {
    k[4][J] = SCALED(3, 8 + J);
    vt[4][J] = transpose8(SCALED(3, 16 + J));
  }
  if (w < 3) {
    uint4* hs = reinterpret_cast<uint4*>(sm + kSmHalo + w * 2048) + lane;
    hs[0] = make_uint4(k[4][0], k[4][1], k[4][2], k[4][3]);
    hs[32] = make_uint4(k[4][4], k[4][5], k[4][6], k[4][7]);
    hs[64] = make_uint4(vt[4][0], vt[4][1], vt[4][2], vt[4][3]);
    hs[96] = make_uint4(vt[4][4], vt[4][5], vt[4][6], vt[4][7]);
  } else if ((b & 7) != 7) {
    uint4* gh = g_halo + ((layer * 16 + b) * 16 + hp) * 256 + lane;
#pragma unroll
    for (int i = 0; i < 8; i++)
      asm volatile("{\n.reg .b64 x, y;\nmov.b64 x, {%1, %3};\nmov.b64 y, {%2, %3};\n"
                   "st.relaxed.gpu.global.v2.b64 [%0], {x, y};\n}" ::"l"(gh + i * 32),
                   "r"(k[4][i]), "r"(vt[4][i]), "r"(epoch) : "memory");
  }
#pragma unroll
  for (int c = 0; c < 3; c++)
#pragma unroll
    for (int J = 0; J < 8; J++) {
      k[c + 1][J] = SCALED(c, 8 + J);
      vt[c + 1][J] = transpose8(SCALED(c, 16 + J));
    }
#pragma unroll
  for (int c = 0; c < 4; c++)
#pragma unroll
    for (int J = 0; J < 8; J++) q[c][J] = SCALED(c, J);
#undef SCALED
  TRACE_AT(tile, 8);
  wg_bar(wg);
  const bool first = w == 0 && (b & 7) == 0;
  if (w > 0) {
    const uint4* hs = reinterpret_cast<const uint4*>(sm + kSmHalo + (w - 1) * 2048) + lane;
    const uint4 a0 = hs[0], a1 = hs[32], a2 = hs[64], a3 = hs[96];
    k[0][0] = a0.x; k[0][1] = a0.y; k[0][2] = a0.z; k[0][3] = a0.w;
    k[0][4] = a1.x; k[0][5] = a1.y; k[0][6] = a1.z; k[0][7] = a1.w;
    vt[0][0] = a2.x; vt[0][1] = a2.y; vt[0][2] = a2.z; vt[0][3] = a2.w;
    vt[0][4] = a3.x; vt[0][5] = a3.y; vt[0][6] = a3.z; vt[0][7] = a3.w;
  } else if (first) {
#pragma unroll
    for (int i = 0; i < 8; i++) k[0][i] = vt[0][i] = 0u;
  } else {
    const uint4* gh = g_halo + ((layer * 16 + b - 1) * 16 + hp) * 256 + lane;
    unsigned spins = 0;
    while (true) {
      unsigned diff = 0;
#pragma unroll
      for (int i = 0; i < 8; i++) {
        unsigned t0, t1;
        asm volatile("{\n.reg .b64 x, y;\nld.relaxed.gpu.global.v2.b64 {x, y}, [%4];\n"
                     "mov.b64 {%0, %1}, x;\nmov.b64 {%2, %3}, y;\n}"
                     : "=r"(k[0][i]), "=r"(t0), "=r"(vt[0][i]), "=r"(t1) : "l"(gh + i * 32) : "memory");
        diff |= (t0 ^ epoch) | (t1 ^ epoch);
      }
      if (__all_sync(0xffffffffu, diff == 0)) break;
      if (++spins > kSpinLimit) __trap();
    }
  }
  TRACE_AT(tile, 9);
  mbar_wait(sb + kBarPause + att * 8, 0);
  TRACE_AT(tile, 10);

  float s[2][5][4];
#pragma unroll
  for (int hd = 0; hd < 2; hd++)
#pragma unroll
    for (int kg = 0; kg < 5; kg++) {
      const int ca = kg > 0 ? kg - 1 : 0, cb = kg < 4 ? kg : 3;
#pragma unroll
      for (int e = 0; e < 4; e++) s[hd][kg][e] = 0.f;
#pragma unroll
      for (int ks = 0; ks < 2; ks++) {
        const int J = 4 * hd + 2 * ks;
        mma16816(s[hd][kg], q[ca][J], q[cb][J], q[ca][J + 1], q[cb][J + 1], k[kg][J], k[kg][J + 1]);
      }
    }
  constexpr float kScale = 0.17677669529663687f * 1.4426950408889634f;
  const bool own0 = 2 * t <= g, own1 = 2 * t + 1 <= g;
  const uint32_t own_mask = (own0 ? 0xffffu : 0u) | (own1 ? 0xffff0000u : 0u);
  float o[2][4][2][4];
#pragma unroll
  for (int hd = 0; hd < 2; hd++) {
    float v0[4], v1[4], m[4];
#pragma unroll
    for (int c = 0; c < 4; c++) {
      float p0 = s[hd][c][2], p1 = s[hd][c][3];
      if (c == 0 && first) p0 = p1 = -INFINITY;
      v0[c] = own0 ? s[hd][c + 1][0] : p0;
      v1[c] = own1 ? s[hd][c + 1][1] : p1;
      m[c] = fmaxf(v0[c], v1[c]);
    }
#pragma unroll
    for (int c = 0; c < 4; c++) m[c] = fmaxf(m[c], shfl_xor(m[c], 1));
#pragma unroll
    for (int c = 0; c < 4; c++) m[c] = fmaxf(m[c], shfl_xor(m[c], 2));
#pragma unroll
    for (int c = 0; c < 4; c++) {
      const float nm = -m[c] * kScale;
      v0[c] = ex2(fmaf(v0[c], kScale, nm));
      v1[c] = ex2(fmaf(v1[c], kScale, nm));
      m[c] = v0[c] + v1[c];
    }
#pragma unroll
    for (int c = 0; c < 4; c++) m[c] += shfl_xor(m[c], 1);
#pragma unroll
    for (int c = 0; c < 4; c++) m[c] += shfl_xor(m[c], 2);
#pragma unroll
    for (int c = 0; c < 4; c++) {
      const float inv = rcp(m[c]);
      const uint32_t p = pack2(v0[c] * inv, v1[c] * inv);
#pragma unroll
      for (int ds = 0; ds < 2; ds++) {
        const int J = 4 * hd + 2 * ds;
#pragma unroll
        for (int e = 0; e < 4; e++) o[hd][c][ds][e] = 0.f;
        mma16816(o[hd][c][ds], vt[c][J], vt[c][J + 1], vt[c + 1][J], vt[c + 1][J + 1], p & ~own_mask, p & own_mask);
      }
    }
  }
  if (elect()) mbar_arrive(sb + kBarResume + att * 8);
  TRACE_AT(tile, 11);
  const uint32_t stg = sb + kSmStg + w * 4096;
#pragma unroll
  for (int J = 0; J < 8; J++) {
    const int hd = J >> 2, ds = (J >> 1) & 1, e = 2 * (J & 1);
    stsm4_t(stg + lane * 128 + ((J ^ (lane & 7)) << 4), pack2(o[hd][0][ds][e], o[hd][0][ds][e + 1]),
            pack2(o[hd][1][ds][e], o[hd][1][ds][e + 1]), pack2(o[hd][2][ds][e], o[hd][2][ds][e + 1]),
            pack2(o[hd][3][ds][e], o[hd][3][ds][e + 1]));
  }
  fence_async_smem();
  __syncwarp();
  TRACE_AT(tile, 12);
  if (elect()) {
    bulk_store(g_o + (b * 16 + hp) * kTileBytes + w * 4096, stg, 4096);
    bulk_commit();
    bulk_wait();
    TRACE_AT(tile, 13);
    st_relaxed(&g_flag[(tile * 16 + b) * 32 + j * 4 + w], epoch);
    mbar_arrive(sb + kBarEpi + tile * 8);
  }
  __syncwarp();
}

__device__ __forceinline__ void gather_stats(uint8_t* sm, const uint2* stat, unsigned epoch) {
  const int r = threadIdx.x & 127;
  uint4 a[4];
  unsigned spins = 0;
  while (true) {
    unsigned diff = 0;
#pragma unroll
    for (int i = 0; i < 4; i++) {
      a[i] = ld_relaxed4(stat + r * 8 + 2 * i);
      diff |= (a[i].x ^ epoch) | (a[i].y ^ epoch) | (a[i].z ^ epoch) | (a[i].w ^ epoch);
    }
    if (__all_sync(0xffffffffu, (diff & 7u) == 0)) break;
    if (++spins > kSpinLimit) __trap();
  }
  float s = 0.f, q = 0.f;
#pragma unroll
  for (int i = 0; i < 4; i++) {
    s += untag_value(a[i].x) + untag_value(a[i].z);
    q += untag_value(a[i].y) + untag_value(a[i].w);
  }
  const float mean = s * (1.f / 1024.f);
  const float var = fmaxf(fmaf(-mean, mean, q * (1.f / 1024.f)), 0.f);
  reinterpret_cast<float2*>(sm + kSmStat)[r] = make_float2(rsqrtf(var + 1e-5f), -mean);
}

__device__ __forceinline__ void gather_colsums(uint8_t* sm, int which, int j, unsigned epoch) {
  const int tid = threadIdx.x & 127;
  const unsigned* src[4];
#pragma unroll
  for (int i = 0; i < 4; i++) {
    const int li = i * 128 + tid, blk = li >> 6;
    const int col0 = (blk % 3) * kD + (j + 8 * (blk / 3)) * 64 + (li & 63);
    const int col1 = 3 * kD + (li < 192 ? 192 * j + li : li < 320 ? 1344 + 128 * j + li : 2240 + 128 * j + li);
    src[i] = g_cs + (which ? col1 : col0);
  }
  const bool last = which && tid < 64;
  unsigned v[4], spins = 0;
  while (true) {
    v[0] = ld_relaxed(src[0]);
    v[1] = ld_relaxed(src[1]);
    v[2] = ld_relaxed(src[2]);
    v[3] = last ? ld_relaxed(src[3]) : epoch;
    const unsigned diff = (v[0] ^ epoch) | (v[1] ^ epoch) | (v[2] ^ epoch) | (v[3] ^ epoch);
    if (__all_sync(0xffffffffu, (diff & 7u) == 0)) break;
    if (++spins > kSpinLimit) __trap();
  }
#pragma unroll
  for (int i = 0; i < 4; i++) {
    const int li = i * 128 + tid;
    float* dst = which ? reinterpret_cast<float*>(sm + kSmV1) + (li >> 1) * 4 + (li & 1)
                       : reinterpret_cast<float*>(sm + kSmCsQ) + li;
    if (i < 3 || last) *dst = untag_value(v[i]);
  }
}

#define PAUSE_QKV2 8
#define PAUSE_WO 3

__global__ void __cluster_dims__(2, 1, 1) __launch_bounds__(384, 1)
fused_layers_kernel(const __grid_constant__ CUtensorMap map_x, const __grid_constant__ CUtensorMap map_out,
                    const __grid_constant__ CUtensorMap map_qkv, const __grid_constant__ CUtensorMap map_wo,
                    const __grid_constant__ CUtensorMap map_w1a, const __grid_constant__ CUtensorMap map_w1b,
                    const __grid_constant__ CUtensorMap map_w2, const Params prm) {
  extern __shared__ __align__(1024) uint8_t sm[];
  const uint32_t sb = smem_u32(sm);
  const int warp = __shfl_sync(0xffffffffu, threadIdx.x >> 5, 0), lane = threadIdx.x & 31;
  const int cta = blockIdx.x, rank = cta & 1, cl = cta >> 1;
  const int grp = cl < 4 ? 0 : cl < 36 ? (cl - 4) & 7 : 1 + (cl - 36) % 7;
  const int j = cl < 4 ? 4 + cl : cl < 36 ? (cl - 4) >> 3 : 4 + (cl - 36) / 7;
  const int b = 2 * grp + rank;
  const int xcol = (b >> 3) * kD, xrow = (b & 7) * 128;

  if (warp == 8 && elect()) {
    if (sb & 1023) __trap();
    for (int s = 0; s < 8; s++) {
      mbar_init(sb + kBarFull + s * 8, 1);
      mbar_init(sb + kBarEmpty + s * 8, 2);
    }
    for (int s = 0; s < kTiles; s++) {
      mbar_init(sb + kBarTurn + s * 8, 1);
      mbar_init(sb + kBarEpi + s * 8, 4);
      mbar_init(sb + kBarReady + s * 8, 1);
    }
    for (int s = 0; s < 4; s++) {
      mbar_init(sb + kBarX + s * 8, s == 0 ? 1 : 4);
      mbar_init(sb + kBarStat + s * 8, s == 0 ? 5 : 4);
      mbar_init(sb + kBarPause + s * 8, 1);
      mbar_init(sb + kBarResume + s * 8, 4);
    }
    asm volatile("fence.mbarrier_init.release.cluster;" ::: "memory");
    fence_async_smem();
    mbar_expect_tx(sb + kBarX, 32768);
    tma2d(sb + kSmX, &map_x, sb + kBarX, xcol + j * 128, xrow);
    tma2d(sb + kSmX + kTileBytes, &map_x, sb + kBarX, xcol + j * 128 + 64, xrow);
  }
  if (threadIdx.x == 0) *reinterpret_cast<unsigned*>(sm + kSmEpoch) = atomicAdd(&g_ticket, 1u) / kCtas + 1;
  __syncwarp();
  asm volatile("barrier.cluster.arrive.release.aligned;" ::: "memory");

  if (warp >= 8) {
    asm volatile("setmaxnreg.dec.sync.aligned.u32 40;");
    asm volatile("barrier.cluster.wait.acquire.aligned;" ::: "memory");
    if (warp == 8) {
      int nb = 0, mb = 0;
#pragma unroll 1
      for (int i = 0; i < kRunTiles; i++) {
        const int ty = i >= 7 ? i - 7 : i;
        const bool wide = tile_wide(ty), usex = tile_uses_x(ty);
        const int nkb = ty == 6 ? 56 : 16;
        const CUtensorMap* map = ty < 2 ? &map_qkv : ty == 2 ? &map_wo : ty == 3 ? &map_w1a : ty < 6 ? &map_w1b : &map_w2;
        const int c0 = ty < 2 ? (j + 8 * ty) * 64 : 0;
        const int c2 = ty < 2 ? 0 : ty == 3 ? 3 * j : ty == 4 ? 24 + 2 * j : ty == 5 ? 40 + 2 * j : 2 * j;
        const uint32_t step = wide ? 40960 : 32768;
        const uint32_t dst = sb + kSmRing + kTileBytes + rank * (wide ? 12288 : 8192);
        const int head_depth = 8 * ring_depth(ty, 0), tail_depth = 8 * ring_depth(ty, 4);
        uint32_t off = tile_first_slot(i) * step;
#pragma unroll 1
        for (int kk = 0; kk < nkb; kk++) {
          const int lim = nb - (kk < 4 ? head_depth : tail_depth);
          for (; mb <= lim; mb += 8) mbar_wait(sb + kBarEmpty + (mb & 56), (mb >> 6) & 1);
          const int kb = usex ? x_kblock(j, kk) : kk;
          if (elect()) {
            const uint32_t full = sb + kBarFull + (nb & 56);
            mbar_expect_tx(full, (usex && kk < 2) ? step - kTileBytes : step);
            tma3d_mc(dst + off, map, full, c0, kb * 64 + rank * 32, c2);
          }
          off += step;
          if (off == 163840) off = 0;
          nb += 8;
        }
      }
    } else {
      const unsigned epoch = *reinterpret_cast<volatile unsigned*>(sm + kSmEpoch);
      if (warp == 9) {
        int nb = 0, mb = 0;
#pragma unroll 1
        for (int i = 0; i < kRunTiles; i++) {
          const int ty = i >= 7 ? i - 7 : i;
          const bool wide = tile_wide(ty), usex = tile_uses_x(ty);
          const uint32_t step = wide ? 40960 : 32768;
          const int head_depth = 8 * ring_depth(ty, 0), tail_depth = 8 * ring_depth(ty, 4);
          const uint8_t* src = ty == 6 ? g_h + b * 56 * kTileBytes : (ty == 2 ? g_o : g_x) + b * 16 * kTileBytes;
          uint32_t off = tile_first_slot(i) * step;
          int kk = 0, skip = 0;
          if (usex) {
            kk = 2;
            skip = 2 * j + 2;
            nb += 16;
            off += 2 * step;
            if (off >= 163840) off -= 163840;
          }
          const int nseg = ty == 2 ? 2 : ty == 6 ? 3 : 1;
          const int dep = (ty == 1 || ty == 4 || ty == 5) ? -1 : i - nseg;
#pragma unroll 1
          for (int seg = 0; seg < nseg; seg++) {
            if (dep >= 0) mbar_wait(sb + kBarReady + (dep + seg) * 8, 0);
            const int kend = ty == 6 ? 24 + 16 * seg : ty == 2 ? 8 + 8 * seg : 16;
#pragma unroll 1
            for (; kk < kend; kk++) {
              const int lim = nb - (kk < 4 ? head_depth : tail_depth);
              for (; mb <= lim; mb += 8) mbar_wait(sb + kBarEmpty + (mb & 56), (mb >> 6) & 1);
              const int kb = kk < skip ? kk - 2 : kk;
              const uint32_t dst = sb + kSmRing + off, full = sb + kBarFull + (nb & 56);
              if (i < 2) {
                if (elect()) tma2d(dst, &map_x, full, xcol + kb * 64, xrow);
              } else {
                if (elect()) bulk_load(dst, src + kb * kTileBytes, kTileBytes, full);
              }
              off += step;
              if (off == 163840) off = 0;
              nb += 8;
            }
          }
        }
      } else if (warp == 10) {
        float* v1 = reinterpret_cast<float*>(sm + kSmV1);
#pragma unroll 1
        for (int i = lane; i < 448; i += 32) {
          const int col = i < 192 ? 192 * j + i : i < 320 ? 1536 + 128 * j + (i - 192) : 2560 + 128 * j + (i - 320);
          v1[(i >> 1) * 4 + 2 + (i & 1)] = 0.5f * __bfloat162float(prm.b1[col]);
        }
#pragma unroll 1
        for (int i = lane; i < 128; i += 32)
          reinterpret_cast<float*>(sm + kSmB2)[i] = __bfloat162float(prm.b2[128 * j + i]);
        __syncwarp();
        if (elect()) mbar_arrive(sb + kBarStat);
#pragma unroll 1
        for (int i = 0; i < kRunTiles - 1; i++) {
          mbar_wait(sb + kBarTurn + i * 8, 0);
          wait_flags(g_flag + (i * 16 + b) * 32 + lane, epoch);
          if (elect()) mbar_arrive(sb + kBarReady + i * 8);
        }
      } else if (kRunTiles == kTiles) {
#pragma unroll 1
        for (int s = 0; s < 6; s++) {
          const int after = (0xA77530 >> (4 * s)) & 15;
          const void* base = s == 0 || s == 3 ? prm.wo : s == 2 ? prm.wqkv : s == 4 ? prm.w1 : prm.w2;
          const int chunks = s == 0 || s == 3 ? 2 : s == 2 ? 6 : 7;
          mbar_wait(sb + kBarTurn + after * 8, 0);
          if (lane < chunks) l2_prefetch(reinterpret_cast<const uint8_t*>(base) + (cta * chunks + lane) * 8192, 8192);
          __syncwarp();
        }
      }
    }
    __syncwarp();
    asm volatile("barrier.cluster.arrive.relaxed.aligned;\nbarrier.cluster.wait.aligned;" ::: "memory");
  } else {
    asm volatile("setmaxnreg.inc.sync.aligned.u32 232;");
    asm volatile("barrier.cluster.wait.acquire.aligned;" ::: "memory");
    const unsigned epoch = *reinterpret_cast<volatile unsigned*>(sm + kSmEpoch);
    const int wg = warp >> 2, w = warp & 3;
    const bool rel = (threadIdx.x & 95) == 0;
    const uint32_t rel_addr = mapa(sb + kBarEmpty, w & 1);

    if (wg == 1) TRACE_AT(-1, 0);
#pragma unroll 1
    for (int i = -wg; i < kRunTiles; i += 2) {
      const int layer = i >= 7, ty = i - 7 * layer;
      const int n0 = tile_first_seq(layer, ty);
      float acc[2][96];
      if (ty == -1 || ty == 2 || ty == 6) {
        const uint32_t xrow_addr = sb + kSmX + (32 * w + lane) * 128;
        const float2* b2 = reinterpret_cast<const float2*>(sm + kSmB2) + (lane & 3);
        const int xver = 2 * layer + (ty + 2) / 4;
        if (i <= 2 && cta < (i < 0 ? 96 : 112))
          colsum_slab(i < 0 ? prm.wqkv : prm.w1, i < 0 ? 3 * kD : kF, cta * 32, g_cs + (i < 0 ? 0 : 3 * kD), epoch,
                      sm, wg, w);
        TRACE_AT(i, 15);
        if (i < 0) mbar_wait(sb + kBarX, 0);
#pragma unroll
        for (int J = 0; J < 16; J++) {
          uint32_t r[4];
          ldsm4(xrow_addr + (J >> 3) * kTileBytes + (((J & 7) ^ (lane & 7)) << 4), r);
          float2 bias = make_float2(0.f, 0.f);
          if (ty == 6) bias = b2[J * 4];
#pragma unroll
          for (int c = 0; c < 4; c++) {
            acc[c & 1][4 * J + (c & 2)] = bf_lo(r[c]) + bias.x;
            acc[c & 1][4 * J + (c & 2) + 1] = bf_hi(r[c]) + bias.y;
          }
        }
        if (i >= 0)
          mainloop<128, false>(acc, sb, i, n0, ty == 6 ? 56 : 16, 0, ty == 2 ? PAUSE_WO : -1, 2 * layer + 1, rel_addr, rel);
        TRACE_AT(i, 2);
        uint32_t pk[16][4];
#pragma unroll
        for (int J = 0; J < 16; J++)
#pragma unroll
          for (int c = 0; c < 4; c++) pk[J][c] = pack2(acc[c & 1][4 * J + (c & 2)], acc[c & 1][4 * J + (c & 2) + 1]);
        if (i >= 0) {
#pragma unroll
          for (int J = 0; J < 16; J++)
            stsm4(xrow_addr + (J >> 3) * kTileBytes + (((J & 7) ^ (lane & 7)) << 4), pk[J][0], pk[J][1], pk[J][2], pk[J][3]);
          fence_async_smem();
          __syncwarp();
          TRACE_AT(i, 8);
          if (elect()) {
            const uint32_t src = sb + kSmX + w * 4096;
            if (xver == 4) {
              tma2d_store(&map_out, src, xcol + j * 128, xrow + 32 * w);
              tma2d_store(&map_out, src + kTileBytes, xcol + j * 128 + 64, xrow + 32 * w);
            } else {
              mbar_arrive(sb + kBarX + xver * 8);
              uint8_t* dst = g_x + (b * 16 + 2 * j) * kTileBytes + w * 4096;
              bulk_store(dst, src, 4096);
              bulk_store(dst + kTileBytes, src + kTileBytes, 4096);
            }
            bulk_commit();
            bulk_wait();
            TRACE_AT(i, 9);
            if (xver < 4) st_relaxed(&g_flag[(i * 16 + b) * 32 + j * 4 + w], epoch);
          }
          __syncwarp();
        }
        if (xver < 4) {
          TRACE_AT(i, 10);
          uint2* stat = g_stat + (xver * 16 + b) * 1024;
          publish_stats(pk, stat, j, w, lane, epoch);
          TRACE_AT(i, 11);
          if (xver < 2) gather_colsums(sm, xver, j, epoch);
          TRACE_AT(i, 12);
          gather_stats(sm, stat, epoch);
          __syncwarp();
          if (elect()) mbar_arrive(sb + kBarStat + xver * 8);
        }
      } else if (ty < 2) {
        zero_acc<192>(acc);
        if (ty == 1) {
          mbar_wait(sb + kBarStat + layer * 16, 0);
          add_mean_term(acc, sm, 1, w, lane);
        }
        mainloop<192, true>(acc, sb, i, n0, 16, 2 * layer, ty == 1 ? PAUSE_QKV2 : -1, 2 * layer, rel_addr, rel);
        TRACE_AT(i, 2);
        if (ty == 0) {
          mbar_wait(sb + kBarStat + layer * 16, 0);
          add_mean_term(acc, sm, 0, w, lane);
        } else {
          mbar_wait(sb + kBarEpi + (i - 1) * 8, 0);
        }
        epilogue_attn(acc, sm, sb, layer, ty, b, j, epoch, i, wg, w);
      } else {
        zero_acc<192>(acc);
        if (ty == 3) mainloop<192, true>(acc, sb, i, n0, 16, 2 * layer + 1, -1, 0, rel_addr, rel);
        else mainloop<128, true>(acc, sb, i, n0, 16, 2 * layer + 1, -1, 0, rel_addr, rel);
        TRACE_AT(i, 2);
        mbar_wait(sb + kBarStat + layer * 16 + 8, 0);
        if (ty > 3) mbar_wait(sb + kBarEpi + (i - 1) * 8, 0);
        const int blk = ty == 3 ? 3 * j : 16 * ty - 40 + 2 * j;
        epilogue_gelu(acc, sm, sb, ty == 3, ty == 3 ? 0 : 128 * ty - 320, g_h + (b * 56 + blk) * kTileBytes + w * 4096,
                      &g_flag[(i * 16 + b) * 32 + j * 4 + w], epoch, i, w);
      }
      TRACE_AT(i, 3);
    }
    asm volatile("barrier.cluster.arrive.relaxed.aligned;\nbarrier.cluster.wait.aligned;" ::: "memory");
  }
}

typedef CUresult (*EncodeTiledFn)(CUtensorMap*, CUtensorMapDataType, cuuint32_t, void*, const cuuint64_t*,
                                  const cuuint64_t*, const cuuint32_t*, const cuuint32_t*, CUtensorMapInterleave,
                                  CUtensorMapSwizzle, CUtensorMapL2promotion, CUtensorMapFloatOOBfill);

CUtensorMap make_map(EncodeTiledFn enc, const void* p, int rank, const cuuint64_t* dims, const cuuint64_t* strides,
                     const cuuint32_t* box) {
  CUtensorMap m;
  const cuuint32_t es[5] = {1, 1, 1, 1, 1};
  enc(&m, CU_TENSOR_MAP_DATA_TYPE_BFLOAT16, rank, const_cast<void*>(p), dims, strides, box, es,
      CU_TENSOR_MAP_INTERLEAVE_NONE, CU_TENSOR_MAP_SWIZZLE_128B, CU_TENSOR_MAP_L2_PROMOTION_L2_128B,
      CU_TENSOR_MAP_FLOAT_OOB_FILL_NONE);
  return m;
}

CUtensorMap weight_map(EncodeTiledFn enc, const void* p, int k, int n, int blocks) {
  const cuuint64_t dims[3] = {64, (cuuint64_t)k, (cuuint64_t)n / 64};
  const cuuint64_t strides[2] = {(cuuint64_t)n * 2, 128};
  const cuuint32_t box[3] = {64, 32, (cuuint32_t)blocks};
  return make_map(enc, p, 3, dims, strides, box);
}

CUtensorMap token_map(EncodeTiledFn enc, const void* p, int rows) {
  const cuuint64_t dims[2] = {2 * kD, 1024};
  const cuuint64_t strides[1] = {4 * kD};
  const cuuint32_t box[2] = {64, (cuuint32_t)rows};
  return make_map(enc, p, 2, dims, strides, box);
}

}

extern "C" void kernel_launch(void* const* d_in, const int* in_sizes, int n_in, void* d_out, int out_size) {
  (void)in_sizes; (void)n_in; (void)out_size;
  static EncodeTiledFn enc = nullptr;
  if (!enc) {
    void* fn = nullptr;
    cudaDriverEntryPointQueryResult q;
    cudaGetDriverEntryPoint("cuTensorMapEncodeTiled", &fn, cudaEnableDefault, &q);
    enc = (EncodeTiledFn)fn;
    cudaFuncSetAttribute(fused_layers_kernel, cudaFuncAttributeMaxDynamicSharedMemorySize, kSmBytes);
  }
  Params prm;
  prm.wqkv = (const __nv_bfloat16*)d_in[1];
  prm.wo = (const __nv_bfloat16*)d_in[2];
  prm.w1 = (const __nv_bfloat16*)d_in[4];
  prm.b1 = (const __nv_bfloat16*)d_in[5];
  prm.w2 = (const __nv_bfloat16*)d_in[6];
  prm.b2 = (const __nv_bfloat16*)d_in[7];
  const cuuint64_t qd[3] = {kD, kD, 3}, qs[2] = {3 * kD * 2, kD * 2};
  const cuuint32_t qb[3] = {64, 32, 3};
  const CUtensorMap map_x = token_map(enc, d_in[0], 128);
  const CUtensorMap map_out = token_map(enc, d_out, 32);
  const CUtensorMap map_qkv = make_map(enc, prm.wqkv, 3, qd, qs, qb);
  const CUtensorMap map_wo = weight_map(enc, prm.wo, kD, kD, 2);
  const CUtensorMap map_w1a = weight_map(enc, prm.w1, kD, kF, 3);
  const CUtensorMap map_w1b = weight_map(enc, prm.w1, kD, kF, 2);
  const CUtensorMap map_w2 = weight_map(enc, prm.w2, kF, kD, 2);
  fused_layers_kernel<<<kCtas, 384, kSmBytes>>>(map_x, map_out, map_qkv, map_wo, map_w1a, map_w1b, map_w2, prm);
}
```

```cpp
#include <cuda.h>
#include <cuda_bf16.h>
#include <cuda_runtime.h>
#include <stdint.h>

namespace {

constexpr int kD = 1024;
constexpr int kF = 3584;
constexpr int kCtas = 128;
constexpr int kTiles = 14;
constexpr int kTileBytes = 16384;

constexpr int kSmRing = 0;
constexpr int kSmX = 163840;
constexpr int kSmStg = kSmX + 32768;
constexpr int kSmHalo = kSmStg + 16384;
constexpr int kSmCsQ = kSmHalo + 6144;
constexpr int kSmV1 = kSmCsQ + 384 * 4;
constexpr int kSmB2 = kSmV1 + 448 * 8;
constexpr int kSmStat = kSmB2 + 128 * 4;
constexpr int kSmRed = kSmStat + 128 * 8;
constexpr int kSmBar = kSmRed + 512;
constexpr int kBarFull = kSmBar;
constexpr int kBarTurn = kBarFull + 8 * 8;
constexpr int kBarReady = kBarTurn + 14 * 8;
constexpr int kBarPause = kBarReady + 17 * 8;
constexpr int kBarInit = kBarPause + 4 * 8;
constexpr int kBarEpoch = kBarInit + 8;
constexpr int kBarEmpty = kBarEpoch + 8;
constexpr int kBarEpi = kBarEmpty + 8 * 8;
constexpr int kBarX = kBarEpi + 14 * 8;
constexpr int kBarStat = kBarX + 6 * 8;
constexpr int kBarResume = kBarStat + 4 * 8;
constexpr int kSmEpoch = kBarResume + 4 * 8;
constexpr int kSmBytes = kSmEpoch + 16;
constexpr int kSegs = 36;

constexpr int kFlagLines = kTiles * 16;

constexpr unsigned kSpinLimit = 1u << 24;

__device__ __align__(1024) uint8_t g_x[16 * 16 * kTileBytes];
__device__ __align__(1024) uint8_t g_o[16 * 16 * kTileBytes];
__device__ __align__(1024) uint8_t g_h[16 * 56 * kTileBytes];
__device__ __align__(128) uint2 g_stat[4 * 16 * 128 * 8];
__device__ __align__(128) unsigned g_cs[3 * kD + kF];
__device__ __align__(128) uint4 g_halo[2 * 16 * 16 * 256];
__device__ __align__(128) unsigned g_flag[kFlagLines * 32];
__device__ unsigned g_ticket;

#define TRACE_AT(tile, k)

struct Params {
  const __nv_bfloat16* wqkv;
  const __nv_bfloat16* wo;
  const __nv_bfloat16* w1;
  const __nv_bfloat16* b1;
  const __nv_bfloat16* w2;
  const __nv_bfloat16* b2;
  uint32_t seg[kSegs];
};

__device__ __forceinline__ uint32_t smem_u32(const void* p) {
  return (uint32_t)__cvta_generic_to_shared(p);
}
__device__ __forceinline__ uint32_t mapa(uint32_t a, uint32_t cta) {
  uint32_t r;
  asm("mapa.shared::cluster.u32 %0, %1, %2;" : "=r"(r) : "r"(a), "r"(cta));
  return r;
}
__device__ __forceinline__ void mbar_init(uint32_t bar, int cnt) {
  asm volatile("mbarrier.init.shared::cta.b64 [%0], %1;" ::"r"(bar), "r"(cnt) : "memory");
}
__device__ __forceinline__ void mbar_expect_tx(uint32_t bar, uint32_t bytes) {
  asm volatile("mbarrier.arrive.expect_tx.shared::cta.b64 _, [%0], %1;" ::"r"(bar), "r"(bytes) : "memory");
}
__device__ __forceinline__ void mbar_arrive(uint32_t bar) {
  asm volatile("mbarrier.arrive.shared::cta.b64 _, [%0];" ::"r"(bar) : "memory");
}
__device__ __forceinline__ void mbar_arrive_cluster(uint32_t cluster_addr) {
  asm volatile("mbarrier.arrive.shared::cluster.b64 _, [%0];" ::"r"(cluster_addr) : "memory");
}
__device__ __forceinline__ void mbar_wait(uint32_t bar, uint32_t parity) {
  asm volatile(
      "{\n.reg .pred p;\n.reg .u32 c;\n"
      "mbarrier.try_wait.parity.shared::cta.b64 p, [%0], %1;\n"
      "@p bra.uni DONE;\n"
      "mov.u32 c, 0;\n"
      "RETRY:\n"
      "mbarrier.try_wait.parity.shared::cta.b64 p, [%0], %1;\n"
      "@p bra.uni DONE;\n"
      "add.u32 c, c, 1;\n"
      "setp.lt.u32 p, c, %2;\n"
      "@p bra.uni RETRY;\n"
      "trap;\n"
      "DONE:\n}" ::"r"(bar), "r"(parity), "n"(kSpinLimit)
      : "memory");
}
__device__ __forceinline__ void tma3d_mc(uint32_t dst, const CUtensorMap* m, uint32_t bar, int c0, int c1, int c2) {
  asm volatile(
      "cp.async.bulk.tensor.3d.shared::cluster.global.mbarrier::complete_tx::bytes.multicast::cluster"
      " [%0], [%1, {%3, %4, %5}], [%2], %6;"
      ::"r"(dst), "l"(m), "r"(bar), "r"(c0), "r"(c1), "r"(c2), "h"((uint16_t)3) : "memory");
}
__device__ __forceinline__ void tma2d(uint32_t dst, const CUtensorMap* m, uint32_t bar, int c0, int c1) {
  asm volatile(
      "cp.async.bulk.tensor.2d.shared::cluster.global.mbarrier::complete_tx::bytes [%0], [%1, {%3, %4}], [%2];"
      ::"r"(dst), "l"(m), "r"(bar), "r"(c0), "r"(c1) : "memory");
}
__device__ __forceinline__ void tma2d_store(const CUtensorMap* m, uint32_t src, int c0, int c1) {
  asm volatile("cp.async.bulk.tensor.2d.global.shared::cta.bulk_group [%0, {%2, %3}], [%1];"
               ::"l"(m), "r"(src), "r"(c0), "r"(c1) : "memory");
}
__device__ __forceinline__ bool elect() {
  uint32_t p;
  asm volatile("{\n.reg .pred p;\nelect.sync _|p, 0xffffffff;\nselp.b32 %0, 1, 0, p;\n}" : "=r"(p));
  return p;
}
__device__ __forceinline__ void bulk_load(uint32_t dst, const void* src, uint32_t bytes, uint32_t bar) {
  asm volatile("cp.async.bulk.shared::cluster.global.mbarrier::complete_tx::bytes [%0], [%1], %2, [%3];"
               ::"r"(dst), "l"(src), "r"(bytes), "r"(bar) : "memory");
}
__device__ __forceinline__ void bulk_store(void* dst, uint32_t src, uint32_t bytes) {
  asm volatile("cp.async.bulk.global.shared::cta.bulk_group [%0], [%1], %2;" ::"l"(dst), "r"(src), "r"(bytes)
               : "memory");
}
__device__ __forceinline__ void bulk_commit() { asm volatile("cp.async.bulk.commit_group;" ::: "memory"); }
__device__ __forceinline__ void bulk_wait_read() { asm volatile("cp.async.bulk.wait_group.read 0;" ::: "memory"); }
__device__ __forceinline__ void bulk_wait() { asm volatile("cp.async.bulk.wait_group 0;" ::: "memory"); }
__device__ __forceinline__ void l2_prefetch(const void* p, uint32_t bytes) {
  asm volatile("cp.async.bulk.prefetch.L2.global [%0], %1;" ::"l"(p), "r"(bytes) : "memory");
}
__device__ __forceinline__ void fence_async_smem() { asm volatile("fence.proxy.async.shared::cta;" ::: "memory"); }
__device__ __forceinline__ unsigned ld_relaxed(const unsigned* p) {
  unsigned v;
  asm volatile("ld.relaxed.gpu.global.u32 %0, [%1];" : "=r"(v) : "l"(p) : "memory");
  return v;
}
__device__ __forceinline__ uint2 ld_relaxed2(const uint2* p) {
  uint2 v;
  asm volatile("ld.relaxed.gpu.global.v2.u32 {%0, %1}, [%2];" : "=r"(v.x), "=r"(v.y) : "l"(p) : "memory");
  return v;
}
__device__ __forceinline__ void st_relaxed(unsigned* p, unsigned v) {
  asm volatile("st.relaxed.gpu.global.u32 [%0], %1;" ::"l"(p), "r"(v) : "memory");
}
__device__ __forceinline__ void wait_flags(const unsigned* p, unsigned epoch) {
  unsigned spins = 0;
  while (true) {
    const unsigned v = ld_relaxed(p);
    if (__all_sync(0xffffffffu, v == epoch)) break;
    if (++spins > kSpinLimit) __trap();
  }
}
__device__ __forceinline__ unsigned tag_value(float v, unsigned epoch) {
  return (__float_as_uint(v) & ~7u) | (epoch & 7u);
}
__device__ __forceinline__ float untag_value(unsigned v) { return __uint_as_float(v & ~7u); }
__device__ __forceinline__ void stsm4(uint32_t a, uint32_t r0, uint32_t r1, uint32_t r2, uint32_t r3) {
  asm volatile("stmatrix.sync.aligned.m8n8.x4.shared.b16 [%0], {%1, %2, %3, %4};" ::"r"(a), "r"(r0), "r"(r1),
               "r"(r2), "r"(r3) : "memory");
}
__device__ __forceinline__ void stsm4_t(uint32_t a, uint32_t r0, uint32_t r1, uint32_t r2, uint32_t r3) {
  asm volatile("stmatrix.sync.aligned.m8n8.x4.trans.shared.b16 [%0], {%1, %2, %3, %4};" ::"r"(a), "r"(r0),
               "r"(r1), "r"(r2), "r"(r3) : "memory");
}
__device__ __forceinline__ uint32_t transpose8(uint32_t a) {
  uint32_t d;
  asm volatile("movmatrix.sync.aligned.m8n8.trans.b16 %0, %1;" : "=r"(d) : "r"(a));
  return d;
}
__device__ __forceinline__ void mma16816(float (&c)[4], uint32_t a0, uint32_t a1, uint32_t a2, uint32_t a3,
                                         uint32_t b0, uint32_t b1) {
  asm volatile("mma.sync.aligned.m16n8k16.row.col.f32.bf16.bf16.f32 {%0, %1, %2, %3}, {%4, %5, %6, %7}, {%8, %9}, "
               "{%0, %1, %2, %3};"
               : "+f"(c[0]), "+f"(c[1]), "+f"(c[2]), "+f"(c[3])
               : "r"(a0), "r"(a1), "r"(a2), "r"(a3), "r"(b0), "r"(b1));
}
__device__ __forceinline__ float shfl_xor(float v, int m) {
  float r;
  asm volatile("shfl.sync.bfly.b32 %0, %1, %2, 31, 0xffffffff;" : "=f"(r) : "f"(v), "r"(m));
  return r;
}
__device__ __forceinline__ float tanh_fast(float x) {
  float r;
  asm("tanh.approx.f32 %0, %1;" : "=f"(r) : "f"(x));
  return r;
}
__device__ __forceinline__ void ldsm4(uint32_t a, uint32_t (&r)[4]) {
  asm volatile("ldmatrix.sync.aligned.m8n8.x4.shared.b16 {%0, %1, %2, %3}, [%4];"
               : "=r"(r[0]), "=r"(r[1]), "=r"(r[2]), "=r"(r[3]) : "r"(a) : "memory");
}
__device__ __forceinline__ uint32_t pack2(float lo, float hi) {
  uint32_t r;
  asm("cvt.rn.bf16x2.f32 %0, %1, %2;" : "=r"(r) : "f"(hi), "f"(lo));
  return r;
}
__device__ __forceinline__ float bf_lo(uint32_t r) { return __uint_as_float(r << 16); }
__device__ __forceinline__ float bf_hi(uint32_t r) { return __uint_as_float(r & 0xffff0000u); }
__device__ __forceinline__ float ex2(float x) {
  float r;
  asm("ex2.approx.ftz.f32 %0, %1;" : "=f"(r) : "f"(x));
  return r;
}
__device__ __forceinline__ float rcp(float x) {
  float r;
  asm("rcp.approx.ftz.f32 %0, %1;" : "=f"(r) : "f"(x));
  return r;
}
template <int N>
__device__ __forceinline__ void wg_wait() {
  asm volatile("wgmma.wait_group.sync.aligned %0;" ::"n"(N) : "memory");
}
__device__ __forceinline__ void yield_slot() { asm volatile("pmevent 0;"); }
__device__ __forceinline__ void wg_bar(int wg) { asm volatile("bar.sync %0, 128;" ::"r"(wg + 1) : "memory"); }

template <int N>
__device__ __forceinline__ void mma_kblock(float (&acc)[2][96], uint32_t a, uint32_t b);

#define F8(d, i) \
  "+f"(d[i]), "+f"(d[i + 1]), "+f"(d[i + 2]), "+f"(d[i + 3]), "+f"(d[i + 4]), "+f"(d[i + 5]), "+f"(d[i + 6]), "+f"(d[i + 7])
#define KSTEP(N, A, B, oa0, oa1, ob)                                                       \
  "add.u32 t, " B ", " #ob ";\nmov.b64 db, {t, hb};\n"                                      \
  "add.u32 t, " A ", " #oa0 ";\nmov.b64 da, {t, ha};\n"                                     \
  "wgmma.mma_async.sync.aligned.m64n" #N "k16.f32.bf16.bf16 {" ACC##N##_0 "}, da, db, 1, 1, 1, 0, 1;\n" \
  "add.u32 t, " A ", " #oa1 ";\nmov.b64 da, {t, ha};\n"                                     \
  "wgmma.mma_async.sync.aligned.m64n" #N "k16.f32.bf16.bf16 {" ACC##N##_1 "}, da, db, 1, 1, 1, 0, 1;\n"

#define ACC128_0 \
  "%0, %1, %2, %3, %4, %5, %6, %7, %8, %9, %10, %11, %12, %13, %14, %15, " \
  "%16, %17, %18, %19, %20, %21, %22, %23, %24, %25, %26, %27, %28, %29, %30, %31, " \
  "%32, %33, %34, %35, %36, %37, %38, %39, %40, %41, %42, %43, %44, %45, %46, %47, " \
  "%48, %49, %50, %51, %52, %53, %54, %55, %56, %57, %58, %59, %60, %61, %62, %63"
#define ACC128_1 \
  "%64, %65, %66, %67, %68, %69, %70, %71, %72, %73, %74, %75, %76, %77, %78, %79, " \
  "%80, %81, %82, %83, %84, %85, %86, %87, %88, %89, %90, %91, %92, %93, %94, %95, " \
  "%96, %97, %98, %99, %100, %101, %102, %103, %104, %105, %106, %107, %108, %109, %110, %111, " \
  "%112, %113, %114, %115, %116, %117, %118, %119, %120, %121, %122, %123, %124, %125, %126, %127"
template <>
__device__ __forceinline__ void mma_kblock<128>(float (&acc)[2][96], uint32_t a, uint32_t b) {
  asm volatile("{\n.reg .b32 t, ha, hb;\n.reg .b64 da, db;\n"
               "mov.b32 ha, 0x40000080;\nmov.b32 hb, 0x40000040;\n"
               "wgmma.fence.sync.aligned;\n"
               KSTEP(128, "%128", "%129", 0, 64, 0) KSTEP(128, "%128", "%129", 2, 66, 128)
               KSTEP(128, "%128", "%129", 4, 68, 512) KSTEP(128, "%128", "%129", 6, 70, 640)
               "wgmma.commit_group.sync.aligned;\n}\n"
      : F8(acc[0], 0), F8(acc[0], 8), F8(acc[0], 16), F8(acc[0], 24), F8(acc[0], 32), F8(acc[0], 40), F8(acc[0], 48), F8(acc[0], 56),
        F8(acc[1], 0), F8(acc[1], 8), F8(acc[1], 16), F8(acc[1], 24), F8(acc[1], 32), F8(acc[1], 40), F8(acc[1], 48), F8(acc[1], 56)
      : "r"(a), "r"(b)
      : "memory");
}

#define ACC192_0 \
  "%0, %1, %2, %3, %4, %5, %6, %7, %8, %9, %10, %11, %12, %13, %14, %15, " \
  "%16, %17, %18, %19, %20, %21, %22, %23, %24, %25, %26, %27, %28, %29, %30, %31, " \
  "%32, %33, %34, %35, %36, %37, %38, %39, %40, %41, %42, %43, %44, %45, %46, %47, " \
  "%48, %49, %50, %51, %52, %53, %54, %55, %56, %57, %58, %59, %60, %61, %62, %63, " \
  "%64, %65, %66, %67, %68, %69, %70, %71, %72, %73, %74, %75, %76, %77, %78, %79, " \
  "%80, %81, %82, %83, %84, %85, %86, %87, %88, %89, %90, %91, %92, %93, %94, %95"
#define ACC192_1 \
  "%96, %97, %98, %99, %100, %101, %102, %103, %104, %105, %106, %107, %108, %109, %110, %111, " \
  "%112, %113, %114, %115, %116, %117, %118, %119, %120, %121, %122, %123, %124, %125, %126, %127, " \
  "%128, %129, %130, %131, %132, %133, %134, %135, %136, %137, %138, %139, %140, %141, %142, %143, " \
  "%144, %145, %146, %147, %148, %149, %150, %151, %152, %153, %154, %155, %156, %157, %158, %159, " \
  "%160, %161, %162, %163, %164, %165, %166, %167, %168, %169, %170, %171, %172, %173, %174, %175, " \
  "%176, %177, %178, %179, %180, %181, %182, %183, %184, %185, %186, %187, %188, %189, %190, %191"
template <>
__device__ __forceinline__ void mma_kblock<192>(float (&acc)[2][96], uint32_t a, uint32_t b) {
  asm volatile("{\n.reg .b32 t, ha, hb;\n.reg .b64 da, db;\n"
               "mov.b32 ha, 0x40000080;\nmov.b32 hb, 0x40000040;\n"
               "wgmma.fence.sync.aligned;\n"
               KSTEP(192, "%192", "%193", 0, 64, 0) KSTEP(192, "%192", "%193", 2, 66, 128)
               KSTEP(192, "%192", "%193", 4, 68, 768) KSTEP(192, "%192", "%193", 6, 70, 896)
               "wgmma.commit_group.sync.aligned;\n}\n"
      : F8(acc[0], 0), F8(acc[0], 8), F8(acc[0], 16), F8(acc[0], 24), F8(acc[0], 32), F8(acc[0], 40), F8(acc[0], 48), F8(acc[0], 56), F8(acc[0], 64), F8(acc[0], 72), F8(acc[0], 80), F8(acc[0], 88),
        F8(acc[1], 0), F8(acc[1], 8), F8(acc[1], 16), F8(acc[1], 24), F8(acc[1], 32), F8(acc[1], 40), F8(acc[1], 48), F8(acc[1], 56), F8(acc[1], 64), F8(acc[1], 72), F8(acc[1], 80), F8(acc[1], 88)
      : "r"(a), "r"(b)
      : "memory");
}

enum { kModePlain = 0, kModeHead = 1, kModeSkip = 2, kModeContinue = 3 };

template <int N>
__device__ __forceinline__ void fence_acc(float (&acc)[2][96]) {
#pragma unroll
  for (int h = 0; h < 2; h++)
#pragma unroll
    for (int i = 0; i < N / 2; i++) asm volatile("" : "+f"(acc[h][i])::"memory");
}

template <int N>
__device__ __forceinline__ void zero_acc(float (&acc)[2][96]) {
#pragma unroll
  for (int h = 0; h < 2; h++)
#pragma unroll
    for (int i = 0; i < N / 2; i++) acc[h][i] = 0.f;
}

constexpr uint32_t kToB = (kTileBytes >> 4) + ((4096u >> 4) << 16) - (1u << 16);

#define TRACE_KB(nb)

template <int N>
__device__ __forceinline__ void head_blocks(float (&acc)[2][96], uint32_t sb, int n0, int slot, uint32_t xbar,
                                            uint32_t rel_addr, bool rel) {
  const uint32_t ring = (((sb & 0x3FFFF) + kSmRing) >> 4) | (1u << 16);
  const uint32_t xdesc = (((sb & 0x3FFFF) + kSmX) >> 4) | (1u << 16);
  const uint32_t nb = n0 * 8;
  fence_acc<N>(acc);
  mbar_wait(xbar, 0);
  mbar_wait(sb + kBarFull + (nb & 56), (nb >> 6) & 1);
  TRACE_KB(nb);
  mma_kblock<N>(acc, xdesc, ring + slot * 2560 + kToB);
  mbar_wait(xbar + 8, 0);
  mbar_wait(sb + kBarFull + (nb & 56) + 8, (nb >> 6) & 1);
  TRACE_KB(nb + 8);
  mma_kblock<N>(acc, xdesc + (kTileBytes >> 4), ring + ((slot + 1) & 3) * 2560 + kToB);
  wg_wait<1>();
  if (rel) mbar_arrive_cluster(rel_addr + (nb & 56));
  wg_wait<0>();
  if (rel) mbar_arrive_cluster(rel_addr + (nb & 56) + 8);
  fence_acc<N>(acc);
}

template <int N>
__device__ __forceinline__ void mainloop(float (&acc)[2][96], uint32_t sb, int tile, int n0, int slot, int nkb,
                                         int pause_kk, int att, uint32_t rel_addr, bool rel) {
  constexpr uint32_t kStep = (N == 192 ? 5 : 4) * 512;
  const uint32_t ring = (((sb & 0x3FFFF) + kSmRing) >> 4) | (1u << 16);
  uint32_t st = ring + slot * kStep;
  uint32_t nb = n0 * 8;
  const bool signal = (threadIdx.x & 127) == 64;
  fence_acc<N>(acc);
  if (tile > 0) mbar_wait(sb + kBarTurn + (tile - 1) * 8, 0);
  TRACE_AT(tile, 0);
  int kk = 0;
#pragma unroll 1
  do {
    if (kk == pause_kk) {
      if (signal) mbar_arrive(sb + kBarPause + att * 8);
      mbar_wait(sb + kBarResume + att * 8, 0);
    }
    mbar_wait(sb + kBarFull + (nb & 56), (nb >> 6) & 1);
    if (kk == 0) TRACE_AT(tile, 1);
    TRACE_KB(nb);
    mma_kblock<N>(acc, st, st + kToB);
    if (kk == nkb - 1 && signal) mbar_arrive(sb + kBarTurn + tile * 8);
    wg_wait<1>();
    if (rel && kk > 0) mbar_arrive_cluster(rel_addr + ((nb - 8) & 56));
    st += kStep;
    if (st == ring + 10240) st = ring;
    nb += 8;
  } while (++kk < nkb);
  wg_wait<0>();
  if (rel) mbar_arrive_cluster(rel_addr + ((nb - 8) & 56));
  fence_acc<N>(acc);
}

__device__ __forceinline__ void publish_stats(uint32_t sb, uint2* stat, int w, int lane, unsigned epoch) {
  const uint32_t row = sb + kSmX + (32 * w + lane) * 128;
  float s[4], q[4];
#pragma unroll
  for (int c = 0; c < 4; c++) s[c] = q[c] = 0.f;
#pragma unroll 1
  for (int J = 0; J < 16; J++) {
    uint32_t r[4];
    ldsm4(row + (J >> 3) * kTileBytes + (((J ^ lane) & 7) << 4), r);
#pragma unroll
    for (int c = 0; c < 4; c++) {
      const float lo = bf_lo(r[c]);
      s[c] += lo;
      q[c] = fmaf(lo, lo, q[c]);
    }
    yield_slot();
#pragma unroll
    for (int c = 0; c < 4; c++) {
      const float hi = bf_hi(r[c]);
      s[c] += hi;
      q[c] = fmaf(hi, hi, q[c]);
    }
  }
#pragma unroll
  for (int c = 0; c < 4; c++) {
    s[c] += shfl_xor(s[c], 1);
    q[c] += shfl_xor(q[c], 1);
    s[c] += shfl_xor(s[c], 2);
    q[c] += shfl_xor(q[c], 2);
  }
  const int t = lane & 3, g = lane >> 2;
  const float so = t == 0 ? s[0] : t == 1 ? s[1] : t == 2 ? s[2] : s[3];
  const float qo = t == 0 ? q[0] : t == 1 ? q[1] : t == 2 ? q[2] : q[3];
  asm volatile("st.relaxed.gpu.global.v2.u32 [%0], {%1, %2};" ::"l"(stat + 32 * w + 8 * t + g),
               "r"(tag_value(so, epoch)), "r"(tag_value(qo, epoch)) : "memory");
}

__device__ __forceinline__ void colsum_slab(const __nv_bfloat16* wt, int ld, int col0, unsigned* out,
                                            unsigned epoch, uint8_t* sm, int wg, int w) {
  const int tid = threadIdx.x & 127, lane = tid & 31;
  const uint4* p = reinterpret_cast<const uint4*>(wt + (size_t)(tid >> 2) * ld + col0 + (tid & 3) * 8);
  float a[8];
#pragma unroll
  for (int e = 0; e < 8; e++) a[e] = 0.f;
  {
    uint4 v[32];
#pragma unroll
    for (int i = 0; i < 32; i++) {
      v[i] = __ldg(p);
      p += ld * 4;
    }
#pragma unroll
    for (int i = 0; i < 32; i++) {
      a[0] += bf_lo(v[i].x); a[1] += bf_hi(v[i].x);
      a[2] += bf_lo(v[i].y); a[3] += bf_hi(v[i].y);
      a[4] += bf_lo(v[i].z); a[5] += bf_hi(v[i].z);
      a[6] += bf_lo(v[i].w); a[7] += bf_hi(v[i].w);
      yield_slot();
    }
  }
#pragma unroll
  for (int e = 0; e < 8; e++) {
    a[e] += shfl_xor(a[e], 4);
    a[e] += shfl_xor(a[e], 8);
    a[e] += shfl_xor(a[e], 16);
  }
  float* red = reinterpret_cast<float*>(sm + kSmRed);
  if (lane < 4) {
#pragma unroll
    for (int e = 0; e < 8; e++) red[w * 32 + lane * 8 + e] = a[e];
  }
  wg_bar(wg);
  if (w == 0)
    st_relaxed(out + col0 + lane, tag_value((red[lane] + red[32 + lane]) + (red[64 + lane] + red[96 + lane]), epoch));
}

constexpr float kGelu0 = 2.f * 0.7978845608028654f;
constexpr float kGelu1 = 8.f * 0.7978845608028654f * 0.044715f;

template <int CH>
__device__ __forceinline__ void gelu_chunk(const float (&acc)[2][96], const float2 (&st)[4], const float4* vec,
                                           uint32_t stg, int lane, uint8_t* dst) {
  uint32_t pk[8][4];
#pragma unroll
  for (int jj = 0; jj < 8; jj++) {
    const int J = CH * 8 + jj;
    const float4 v = vec[J * 4];
    float u[8], z[8];
#pragma unroll
    for (int c = 0; c < 4; c++) {
      u[2 * c] = fmaf(acc[c & 1][4 * J + (c & 2)], st[c].x, fmaf(st[c].y, v.x, v.z));
      u[2 * c + 1] = fmaf(acc[c & 1][4 * J + (c & 2) + 1], st[c].x, fmaf(st[c].y, v.y, v.w));
    }
    yield_slot();
#pragma unroll
    for (int e = 0; e < 8; e++) z[e] = fmaf(u[e] * u[e], kGelu1, kGelu0);
    yield_slot();
#pragma unroll
    for (int e = 0; e < 8; e++) z[e] = tanh_fast(u[e] * z[e]);
    yield_slot();
#pragma unroll
    for (int c = 0; c < 4; c++)
      pk[jj][c] = pack2(fmaf(u[2 * c], z[2 * c], u[2 * c]), fmaf(u[2 * c + 1], z[2 * c + 1], u[2 * c + 1]));
    yield_slot();
  }
  if (CH > 0) {
    if (elect()) bulk_wait_read();
    __syncwarp();
  }
#pragma unroll
  for (int jj = 0; jj < 8; jj++)
    stsm4(stg + lane * 128 + ((jj ^ (lane & 7)) << 4), pk[jj][0], pk[jj][1], pk[jj][2], pk[jj][3]);
  fence_async_smem();
  __syncwarp();
  if (elect()) {
    bulk_store(dst + CH * kTileBytes, stg, 4096);
    bulk_commit();
  }
}

__device__ __forceinline__ void epilogue_gelu(const float (&acc)[2][96], uint8_t* sm, uint32_t sb, bool wide,
                                              int vcol0, uint8_t* dst, unsigned* flag, unsigned epoch, int tile,
                                              int w) {
  const int lane = threadIdx.x & 31, t = lane & 3, g = lane >> 2;
  float2 st[4];
#pragma unroll
  for (int c = 0; c < 4; c++) {
    const float2 v = reinterpret_cast<const float2*>(sm + kSmStat)[32 * w + 8 * c + g];
    st[c].x = 0.5f * v.x;
    st[c].y = st[c].x * v.y;
  }
  const float4* vec = reinterpret_cast<const float4*>(sm + kSmV1) + vcol0 / 2 + t;
  const uint32_t stg = sb + kSmStg + w * 4096;
  TRACE_AT(tile, 8);
  gelu_chunk<0>(acc, st, vec, stg, lane, dst);
  TRACE_AT(tile, 9);
  gelu_chunk<1>(acc, st, vec, stg, lane, dst);
  TRACE_AT(tile, 10);
  if (wide) gelu_chunk<2>(acc, st, vec, stg, lane, dst);
  TRACE_AT(tile, 11);
  if (elect()) {
    bulk_wait();
    TRACE_AT(tile, 12);
    mbar_arrive(sb + kBarEpi + tile * 8);
    st_relaxed(flag, epoch);
  }
  __syncwarp();
}

__device__ __forceinline__ void add_mean_term(float (&acc)[2][96], uint8_t* sm, int tq, int w, int lane) {
  const int t = lane & 3, g = lane >> 2;
  float nm[4];
#pragma unroll
  for (int c = 0; c < 4; c++) nm[c] = reinterpret_cast<const float2*>(sm + kSmStat)[32 * w + 8 * c + g].y;
  const float2* cs = reinterpret_cast<const float2*>(sm + kSmCsQ) + tq * 96 + t;
#pragma unroll
  for (int J = 0; J < 24; J++) {
    const float2 v = cs[J * 4];
#pragma unroll
    for (int c = 0; c < 4; c++) {
      acc[c & 1][4 * J + (c & 2)] = fmaf(nm[c], v.x, acc[c & 1][4 * J + (c & 2)]);
      acc[c & 1][4 * J + (c & 2) + 1] = fmaf(nm[c], v.y, acc[c & 1][4 * J + (c & 2) + 1]);
    }
    if (J & 1) yield_slot();
  }
}

__device__ __forceinline__ void epilogue_attn(const float (&acc)[2][96], uint8_t* sm, uint32_t sb, int layer, int tq,
                                              int b, int j, unsigned epoch, int tile, int wg, int w) {
  const int lane = threadIdx.x & 31, t = lane & 3, g = lane >> 2;
  const int hp = j + 8 * tq, att = 2 * layer + tq;
  float rs[4];
#pragma unroll
  for (int c = 0; c < 4; c++) rs[c] = reinterpret_cast<const float2*>(sm + kSmStat)[32 * w + 8 * c + g].x;
  uint32_t q[4][8], k[5][8], vt[5][8];
#define SCALED(c, J) pack2(acc[(c) & 1][4 * (J) + ((c) & 2)] * rs[c], acc[(c) & 1][4 * (J) + ((c) & 2) + 1] * rs[c])
#pragma unroll
  for (int J = 0; J < 8; J++) {
    k[4][J] = SCALED(3, 8 + J);
    vt[4][J] = transpose8(SCALED(3, 16 + J));
    if (J & 1) yield_slot();
  }
  if (w < 3) {
    uint4* hs = reinterpret_cast<uint4*>(sm + kSmHalo + w * 2048) + lane;
    hs[0] = make_uint4(k[4][0], k[4][1], k[4][2], k[4][3]);
    hs[32] = make_uint4(k[4][4], k[4][5], k[4][6], k[4][7]);
    hs[64] = make_uint4(vt[4][0], vt[4][1], vt[4][2], vt[4][3]);
    hs[96] = make_uint4(vt[4][4], vt[4][5], vt[4][6], vt[4][7]);
  } else if ((b & 7) != 7) {
    uint4* gh = g_halo + ((layer * 16 + b) * 16 + hp) * 256 + lane;
#pragma unroll
    for (int i = 0; i < 8; i++)
      asm volatile("{\n.reg .b64 x, y;\nmov.b64 x, {%1, %3};\nmov.b64 y, {%2, %3};\n"
                   "st.relaxed.gpu.global.v2.b64 [%0], {x, y};\n}" ::"l"(gh + i * 32),
                   "r"(k[4][i]), "r"(vt[4][i]), "r"(epoch) : "memory");
  }
#pragma unroll
  for (int c = 0; c < 3; c++)
#pragma unroll
    for (int J = 0; J < 8; J++) {
      k[c + 1][J] = SCALED(c, 8 + J);
      vt[c + 1][J] = transpose8(SCALED(c, 16 + J));
      if (J & 1) yield_slot();
    }
#pragma unroll
  for (int c = 0; c < 4; c++)
#pragma unroll
    for (int J = 0; J < 8; J++) {
      q[c][J] = SCALED(c, J);
      if ((J & 3) == 3) yield_slot();
    }
#undef SCALED
  TRACE_AT(tile, 8);
  wg_bar(wg);
  const bool first = w == 0 && (b & 7) == 0;
  if (w > 0) {
    const uint4* hs = reinterpret_cast<const uint4*>(sm + kSmHalo + (w - 1) * 2048) + lane;
    const uint4 a0 = hs[0], a1 = hs[32], a2 = hs[64], a3 = hs[96];
    k[0][0] = a0.x; k[0][1] = a0.y; k[0][2] = a0.z; k[0][3] = a0.w;
    k[0][4] = a1.x; k[0][5] = a1.y; k[0][6] = a1.z; k[0][7] = a1.w;
    vt[0][0] = a2.x; vt[0][1] = a2.y; vt[0][2] = a2.z; vt[0][3] = a2.w;
    vt[0][4] = a3.x; vt[0][5] = a3.y; vt[0][6] = a3.z; vt[0][7] = a3.w;
  } else if (first) {
#pragma unroll
    for (int i = 0; i < 8; i++) k[0][i] = vt[0][i] = 0u;
  } else {
    const uint4* gh = g_halo + ((layer * 16 + b - 1) * 16 + hp) * 256 + lane;
    unsigned spins = 0;
    while (true) {
      unsigned diff = 0;
#pragma unroll
      for (int i = 0; i < 8; i++) {
        unsigned t0, t1;
        asm volatile("{\n.reg .b64 x, y;\nld.relaxed.gpu.global.v2.b64 {x, y}, [%4];\n"
                     "mov.b64 {%0, %1}, x;\nmov.b64 {%2, %3}, y;\n}"
                     : "=r"(k[0][i]), "=r"(t0), "=r"(vt[0][i]), "=r"(t1) : "l"(gh + i * 32) : "memory");
        diff |= (t0 ^ epoch) | (t1 ^ epoch);
      }
      if (__all_sync(0xffffffffu, diff == 0)) break;
      if (++spins > kSpinLimit) __trap();
    }
  }
  TRACE_AT(tile, 9);
  mbar_wait(sb + kBarPause + att * 8, 0);
  TRACE_AT(tile, 10);

  float s[2][5][4];
#pragma unroll
  for (int hd = 0; hd < 2; hd++)
#pragma unroll
    for (int kg = 0; kg < 5; kg++) {
      const int ca = kg > 0 ? kg - 1 : 0, cb = kg < 4 ? kg : 3;
#pragma unroll
      for (int e = 0; e < 4; e++) s[hd][kg][e] = 0.f;
#pragma unroll
      for (int ks = 0; ks < 2; ks++) {
        const int J = 4 * hd + 2 * ks;
        mma16816(s[hd][kg], q[ca][J], q[cb][J], q[ca][J + 1], q[cb][J + 1], k[kg][J], k[kg][J + 1]);
      }
    }
  constexpr float kScale = 0.17677669529663687f * 1.4426950408889634f;
  const bool own0 = 2 * t <= g, own1 = 2 * t + 1 <= g;
  const uint32_t own_mask = (own0 ? 0xffffu : 0u) | (own1 ? 0xffff0000u : 0u);
  float o[2][4][2][4];
#pragma unroll
  for (int hd = 0; hd < 2; hd++) {
    float v0[4], v1[4], m[4];
#pragma unroll
    for (int c = 0; c < 4; c++) {
      float p0 = s[hd][c][2], p1 = s[hd][c][3];
      if (c == 0 && first) p0 = p1 = -INFINITY;
      v0[c] = own0 ? s[hd][c + 1][0] : p0;
      v1[c] = own1 ? s[hd][c + 1][1] : p1;
      m[c] = fmaxf(v0[c], v1[c]);
    }
#pragma unroll
    for (int c = 0; c < 4; c++) m[c] = fmaxf(m[c], shfl_xor(m[c], 1));
#pragma unroll
    for (int c = 0; c < 4; c++) m[c] = fmaxf(m[c], shfl_xor(m[c], 2));
#pragma unroll
    for (int c = 0; c < 4; c++) {
      const float nm = -m[c] * kScale;
      v0[c] = ex2(fmaf(v0[c], kScale, nm));
      v1[c] = ex2(fmaf(v1[c], kScale, nm));
      m[c] = v0[c] + v1[c];
    }
#pragma unroll
    for (int c = 0; c < 4; c++) m[c] += shfl_xor(m[c], 1);
#pragma unroll
    for (int c = 0; c < 4; c++) m[c] += shfl_xor(m[c], 2);
#pragma unroll
    for (int c = 0; c < 4; c++) {
      const float inv = rcp(m[c]);
      const uint32_t p = pack2(v0[c] * inv, v1[c] * inv);
#pragma unroll
      for (int ds = 0; ds < 2; ds++) {
        const int J = 4 * hd + 2 * ds;
#pragma unroll
        for (int e = 0; e < 4; e++) o[hd][c][ds][e] = 0.f;
        mma16816(o[hd][c][ds], vt[c][J], vt[c][J + 1], vt[c + 1][J], vt[c + 1][J + 1], p & ~own_mask, p & own_mask);
      }
    }
  }
  TRACE_AT(tile, 11);
  const uint32_t stg = sb + kSmStg + w * 4096;
#pragma unroll
  for (int J = 0; J < 8; J++) {
    const int hd = J >> 2, ds = (J >> 1) & 1, e = 2 * (J & 1);
    stsm4_t(stg + lane * 128 + ((J ^ (lane & 7)) << 4), pack2(o[hd][0][ds][e], o[hd][0][ds][e + 1]),
            pack2(o[hd][1][ds][e], o[hd][1][ds][e + 1]), pack2(o[hd][2][ds][e], o[hd][2][ds][e + 1]),
            pack2(o[hd][3][ds][e], o[hd][3][ds][e + 1]));
  }
  if (elect()) mbar_arrive(sb + kBarResume + att * 8);
  fence_async_smem();
  __syncwarp();
  TRACE_AT(tile, 12);
  if (elect()) {
    bulk_store(g_o + (b * 16 + hp) * kTileBytes + w * 4096, stg, 4096);
    bulk_commit();
    bulk_wait();
    TRACE_AT(tile, 13);
    st_relaxed(&g_flag[(tile * 16 + b) * 32 + j * 4 + w], epoch);
    mbar_arrive(sb + kBarEpi + tile * 8);
  }
  __syncwarp();
}

__device__ __forceinline__ void gather_stats(uint8_t* sm, const uint2* stat, unsigned epoch) {
  const int r = threadIdx.x & 127;
  uint2 a[8];
  unsigned spins = 0;
  while (true) {
    unsigned diff = 0;
#pragma unroll
    for (int i = 0; i < 8; i++) {
      a[i] = ld_relaxed2(stat + i * 128 + r);
      diff |= (a[i].x ^ epoch) | (a[i].y ^ epoch);
    }
    if (__all_sync(0xffffffffu, (diff & 7u) == 0)) break;
    if (++spins > kSpinLimit) __trap();
    __nanosleep(200);
  }
  float s = 0.f, q = 0.f;
#pragma unroll
  for (int i = 0; i < 8; i++) {
    s += untag_value(a[i].x);
    q += untag_value(a[i].y);
  }
  const float mean = s * (1.f / 1024.f);
  const float var = fmaxf(fmaf(-mean, mean, q * (1.f / 1024.f)), 0.f);
  reinterpret_cast<float2*>(sm + kSmStat)[r] = make_float2(rsqrtf(var + 1e-5f), -mean);
}

__device__ __forceinline__ void gather_colsums(uint8_t* sm, int which, int j, unsigned epoch) {
  const int tid = threadIdx.x & 127;
  int src[4];
#pragma unroll
  for (int i = 0; i < 4; i++) {
    const int li = i * 128 + tid, blk = li >> 6;
    const int col0 = (blk % 3) * kD + (j + 8 * (blk / 3)) * 64 + (li & 63);
    const int col1 = 3 * kD + (li < 192 ? 192 * j + li : li < 320 ? 1344 + 128 * j + li : 2240 + 128 * j + li);
    src[i] = which ? col1 : col0;
  }
  const bool last = which && tid < 64;
  unsigned v[4], spins = 0;
  while (true) {
    v[0] = ld_relaxed(g_cs + src[0]);
    v[1] = ld_relaxed(g_cs + src[1]);
    v[2] = ld_relaxed(g_cs + src[2]);
    v[3] = last ? ld_relaxed(g_cs + src[3]) : epoch;
    const unsigned diff = (v[0] ^ epoch) | (v[1] ^ epoch) | (v[2] ^ epoch) | (v[3] ^ epoch);
    if (__all_sync(0xffffffffu, (diff & 7u) == 0)) break;
    if (++spins > kSpinLimit) __trap();
    __nanosleep(200);
  }
#pragma unroll
  for (int i = 0; i < 4; i++) {
    const int li = i * 128 + tid;
    float* dst = which ? reinterpret_cast<float*>(sm + kSmV1) + (li >> 1) * 4 + (li & 1)
                       : reinterpret_cast<float*>(sm + kSmCsQ) + li;
    if (i < 3 || last) *dst = untag_value(v[i]);
  }
}

#define PAUSE_QKV2 5
#define PAUSE_WO 3

__global__ void __cluster_dims__(2, 1, 1) __launch_bounds__(384, 1)
fused_layers_kernel(const __grid_constant__ CUtensorMap map_x, const __grid_constant__ CUtensorMap map_out,
                    const __grid_constant__ CUtensorMap map_qkv, const __grid_constant__ CUtensorMap map_wo,
                    const __grid_constant__ CUtensorMap map_w1a, const __grid_constant__ CUtensorMap map_w1b,
                    const __grid_constant__ CUtensorMap map_w2, const __grid_constant__ Params prm) {
  extern __shared__ __align__(1024) uint8_t sm[];
  const uint32_t sb = smem_u32(sm);
  const int warp = __shfl_sync(0xffffffffu, threadIdx.x >> 5, 0), lane = threadIdx.x & 31;
  const int cta = blockIdx.x, rank = cta & 1, cl = cta >> 1;
  const int grp = cl < 4 ? 0 : cl < 36 ? (cl - 4) & 7 : 1 + (cl - 36) % 7;
  const int j = cl < 4 ? 4 + cl : cl < 36 ? (cl - 4) >> 3 : 4 + (cl - 36) / 7;
  const int b = 2 * grp + rank;
  const int xcol = (b >> 3) * kD, xrow = (b & 7) * 128;

  if (warp == 9) {
    if (sb & 1023) __trap();
    for (int o = kSmBar + lane * 8; o < kSmEpoch; o += 256) mbar_init(sb + o, o < kBarEmpty ? 1 : o < kBarEpi ? 2 : 4);
    asm volatile("fence.mbarrier_init.release.cluster;" ::: "memory");
    fence_async_smem();
    __syncwarp();
  } else if (warp == 8 && lane < 4) {
    asm volatile("cp.async.bulk.prefetch.tensor.3d.L2.global [%0, {%1, %2, 0}];" ::"l"(&map_qkv), "r"(j * 64),
                 "r"(lane * 64 + rank * 32) : "memory");
  }
  __syncwarp();
  asm volatile("barrier.cluster.arrive.relaxed.aligned;" ::: "memory");

  if (warp >= 8) {
    asm volatile("setmaxnreg.dec.sync.aligned.u32 40;");
    if (warp < 10) {
      if (warp == 8) asm volatile("barrier.cluster.wait.aligned;" ::: "memory");
      int nb = 0, mb = 0, kb = 0;
      uint32_t off = 0;
#pragma unroll 1
      for (int sg = 0; sg < kSegs; sg++) {
        const uint32_t e = prm.seg[sg];
        const int ty = e & 7, mode = (e >> 15) & 3, reset = (e >> 24) & 3;
        const int nend = nb + (e & 0x1f8);
        const uint32_t step = (e >> 17) & 1 ? 40960 : 32768;
        const int depth = (e >> 18) & 1 ? 40 : 32;
        if (reset) off = reset == 1 ? 0 : reset == 2 ? 40960 : 131072;
        if (mode != kModeContinue) kb = ((e >> 9) & 63) + (mode == kModeHead ? 2 * j : 0);
        const int inc = mode >= kModeSkip ? 2 : 1, skip = mode >= kModeSkip ? j : -1;
        if (warp == 8) {
          const CUtensorMap* map = ty < 2 ? &map_qkv : ty == 2 ? &map_wo : ty == 3 ? &map_w1a : ty < 6 ? &map_w1b : &map_w2;
          const int c0 = ty < 2 ? (j + 8 * ty) * 64 : 0;
          const int c2 = ty < 2 ? 0 : ty == 3 ? 3 * j : ty == 4 ? 24 + 2 * j : ty == 5 ? 40 + 2 * j : 2 * j;
          const uint32_t half = (ty < 2 || ty == 3) ? 12288 : 8192;
          const uint32_t bytes = 2 * half + (mode == kModeHead ? 0 : kTileBytes);
          const uint32_t dst = sb + kSmRing + kTileBytes + rank * half;
#pragma unroll 1
          for (; nb < nend; nb += 8) {
            for (; mb <= nb - depth; mb += 8) mbar_wait(sb + kBarEmpty + (mb & 56), (mb >> 6) & 1);
            if (kb >> 1 == skip) kb += 2;
            if (elect()) {
              const uint32_t full = sb + kBarFull + (nb & 56);
              mbar_expect_tx(full, bytes);
              tma3d_mc(dst + off, map, full, c0, kb * 64 + rank * 32, c2);
            }
            kb += inc;
            off += step;
            if (off == 163840) off = 0;
          }
        } else if (mode == kModeHead) {
          nb = nend;
          off += 2 * step;
          if (off >= 163840) off -= 163840;
          for (; mb <= nb - 56; mb += 8) mbar_wait(sb + kBarEmpty + (mb & 56), (mb >> 6) & 1);
        } else {
          const uint8_t* src = ty == 6 ? g_h + b * 56 * kTileBytes : (ty == 2 ? g_o : g_x) + b * 16 * kTileBytes;
          const int dep = (e >> 19) & 31;
          if (dep != 31) mbar_wait(sb + kBarReady + dep * 8, 0);
#pragma unroll 1
          for (; nb < nend; nb += 8) {
            for (; mb <= nb - depth; mb += 8) mbar_wait(sb + kBarEmpty + (mb & 56), (mb >> 6) & 1);
            if (kb >> 1 == skip) kb += 2;
            const uint32_t dst = sb + kSmRing + off, full = sb + kBarFull + (nb & 56);
            if (sg < 2) {
              if (elect()) tma2d(dst, &map_x, full, xcol + kb * 64, xrow);
            } else {
              if (elect()) bulk_load(dst, src + kb * kTileBytes, kTileBytes, full);
            }
            kb += inc;
            off += step;
            if (off == 163840) off = 0;
          }
        }
      }
      if (warp == 9) asm volatile("barrier.cluster.wait.aligned;" ::: "memory");
    } else if (warp == 10) {
      unsigned epoch = 0;
      if (lane == 0) epoch = atomicAdd(&g_ticket, 1u) / kCtas + 1;
      float* v1 = reinterpret_cast<float*>(sm + kSmV1);
#pragma unroll 1
      for (int i = lane; i < 224; i += 32) {
        const int col = i < 96 ? 96 * j + i : i < 160 ? 672 + 64 * j + i : 1120 + 64 * j + i;
        const uint32_t v = reinterpret_cast<const uint32_t*>(prm.b1)[col];
        *reinterpret_cast<float2*>(v1 + i * 4 + 2) = make_float2(0.5f * bf_lo(v), 0.5f * bf_hi(v));
      }
      {
        const uint2 v = reinterpret_cast<const uint2*>(prm.b2)[32 * j + lane];
        reinterpret_cast<float4*>(sm + kSmB2)[lane] = make_float4(bf_lo(v.x), bf_hi(v.x), bf_lo(v.y), bf_hi(v.y));
      }
      epoch = __shfl_sync(0xffffffffu, epoch, 0);
      *reinterpret_cast<unsigned*>(sm + kSmEpoch) = epoch;
      asm volatile("barrier.cluster.wait.aligned;" ::: "memory");
      if (elect()) mbar_arrive(sb + kBarEpoch);
#pragma unroll 1
      for (int i = 0; i < kTiles - 1; i++) {
        const bool xt = i == 2 || i == 6 || i == 9;
        const unsigned* line = g_flag + (i * 16 + b) * 32;
        mbar_wait(sb + kBarTurn + i * 8, 0);
        wait_flags(line + (xt ? lane & 7 : lane), epoch);
        if (elect()) mbar_arrive(sb + kBarReady + i * 8);
        if (xt) {
          wait_flags(line + 8 + (lane & 7), epoch);
          if (elect()) mbar_arrive(sb + kBarReady + (14 + (i >> 2)) * 8);
        }
      }
    } else {
      asm volatile("barrier.cluster.wait.aligned;" ::: "memory");
      if (elect()) {
        mbar_expect_tx(sb + kBarInit, 32768);
        tma2d(sb + kSmX, &map_x, sb + kBarInit, xcol + j * 128, xrow);
        tma2d(sb + kSmX + kTileBytes, &map_x, sb + kBarInit, xcol + j * 128 + 64, xrow);
      }
      mbar_wait(sb + kBarEpoch, 0);
      const unsigned epoch = *reinterpret_cast<volatile unsigned*>(sm + kSmEpoch);
#pragma unroll 1
      for (int i = 0; i < 11; i++) {
        const int ty = i >= 7 ? i - 7 : i;
        if (ty == 2 || ty == 6) {
#pragma unroll 1
          for (int h = 0; h < 2; h++) {
            mbar_wait(sb + kBarX + ((i >> 2) * 2 + h) * 8, 0);
            if (elect()) {
              bulk_store(g_x + (b * 16 + 2 * j + h) * kTileBytes, sb + kSmX + h * kTileBytes, kTileBytes);
              bulk_commit();
              bulk_wait();
              st_relaxed(&g_flag[(i * 16 + b) * 32 + h * 8 + j], epoch);
            }
            __syncwarp();
          }
        } else if (ty == 0 || ty == 3 || ty == 5) {
          mbar_wait(sb + kBarTurn + i * 8, 0);
          const int chunks = ty == 5 ? 6 : 7;
          const void* base = ty == 0 ? prm.w1 : ty == 3 ? prm.w2 : prm.wqkv;
          if (ty == 0 && lane < 2) l2_prefetch(reinterpret_cast<const uint8_t*>(prm.wo) + (cta * 2 + lane) * 8192, 8192);
          if (lane < chunks) l2_prefetch(reinterpret_cast<const uint8_t*>(base) + (cta * chunks + lane) * 8192, 8192);
          __syncwarp();
        }
      }
    }
    __syncwarp();
    asm volatile("barrier.cluster.arrive.relaxed.aligned;\nbarrier.cluster.wait.aligned;" ::: "memory");
  } else {
    asm volatile("setmaxnreg.inc.sync.aligned.u32 232;");
    asm volatile("barrier.cluster.wait.aligned;" ::: "memory");
    const int wg = warp >> 2, w = warp & 3;
    const bool rel = (threadIdx.x & 95) == 0;
    const uint32_t rel_addr = mapa(sb + kBarEmpty, w & 1);
    if (wg == 1) TRACE_AT(15, 0);
#define EPOCH (*reinterpret_cast<volatile unsigned*>(sm + kSmEpoch))

#pragma unroll 1
    for (int i = wg; i < kTiles; i += 2) {
      const int layer = i >= 7, ty = i - 7 * layer;
      if (i == 1) {
        mbar_wait(sb + kBarEpoch, 0);
        mbar_wait(sb + kBarInit, 0);
      }
      if ((i == 1 && cta < 96) || (i == 2 && cta < 112))
        colsum_slab(i == 1 ? prm.wqkv : prm.w1, i == 1 ? 3 * kD : kF, cta * 32, g_cs + (i == 1 ? 0 : 3 * kD), EPOCH,
                    sm, wg, w);
      TRACE_AT(i, 15);
      float acc[2][96];
      if (ty == 2 || ty == 6) {
        const uint32_t xrow_addr = sb + kSmX + (32 * w + lane) * 128;
        const float2* b2 = reinterpret_cast<const float2*>(sm + kSmB2) + (lane & 3);
#pragma unroll
        for (int J = 0; J < 16; J++) {
          uint32_t r[4];
          ldsm4(xrow_addr + (J >> 3) * kTileBytes + (((J & 7) ^ (lane & 7)) << 4), r);
          float2 bias = make_float2(0.f, 0.f);
          if (ty == 6) bias = b2[J * 4];
#pragma unroll
          for (int c = 0; c < 4; c++) {
            acc[c & 1][4 * J + (c & 2)] = bf_lo(r[c]) + bias.x;
            acc[c & 1][4 * J + (c & 2) + 1] = bf_hi(r[c]) + bias.y;
            asm volatile("" : "+f"(acc[c & 1][4 * J + (c & 2)]), "+f"(acc[c & 1][4 * J + (c & 2) + 1]));
          }
          yield_slot();
        }
        mainloop<128>(acc, sb, i, layer * 152 + ty * 16, ty == 6 ? 4 : 0, ty == 6 ? 56 : 16, ty == 2 ? PAUSE_WO : -1,
                      2 * layer + 1, rel_addr, rel);
        TRACE_AT(i, 2);
#pragma unroll
        for (int h = 0; h < 2; h++) {
#pragma unroll
          for (int J = 8 * h; J < 8 * h + 8; J++)
            stsm4(xrow_addr + h * kTileBytes + (((J & 7) ^ (lane & 7)) << 4), pack2(acc[0][4 * J], acc[0][4 * J + 1]),
                  pack2(acc[1][4 * J], acc[1][4 * J + 1]), pack2(acc[0][4 * J + 2], acc[0][4 * J + 3]),
                  pack2(acc[1][4 * J + 2], acc[1][4 * J + 3]));
          fence_async_smem();
          __syncwarp();
          if (i < kTiles - 1) {
            if (elect()) mbar_arrive(sb + kBarX + ((i >> 2) * 2 + h) * 8);
          } else if (elect()) {
            tma2d_store(&map_out, sb + kSmX + h * kTileBytes + w * 4096, xcol + j * 128 + h * 64, xrow + 32 * w);
            bulk_commit();
            if (h == 1) bulk_wait_read();
          }
          yield_slot();
          TRACE_AT(i, 8 + h);
        }
      } else {
        const int xver = 2 * layer + (ty >= 3);
        const bool wide = ty < 4, split = i > 1 && ty != 5;
        zero_acc<192>(acc);
        if (split) {
          const int n0 = layer * 152 + (ty < 2 ? 2 * ty : 42 + 2 * ty), slot = ty < 2 ? 2 * ty : 2 * ty - 5;
          if (wide) head_blocks<192>(acc, sb, n0, slot, sb + kBarX + (xver - 1) * 16, rel_addr, rel);
          else head_blocks<128>(acc, sb, n0, slot, sb + kBarX + (xver - 1) * 16, rel_addr, rel);
        }
        if (ty == 1 || ty == 4) {
          uint2* stat = g_stat + (xver * 16 + b) * 1024;
          publish_stats(sb, stat + j * 128, w, lane, EPOCH);
          if (layer == 0) gather_colsums(sm, xver, j, EPOCH);
          gather_stats(sm, stat, EPOCH);
          __syncwarp();
          if (elect()) mbar_arrive(sb + kBarStat + xver * 8);
          TRACE_AT(i, 14);
          if (ty == 1) {
            mbar_wait(sb + kBarStat + xver * 8, 0);
            add_mean_term(acc, sm, 1, w, lane);
          }
        }
        const int n0 = layer * 152 + (!split ? 16 * ty : ty < 2 ? 4 + 14 * ty : 10 + 14 * ty);
        const int slot = ty < 2 ? (split ? 2 * ty : 0) : ty == 3 ? 1 : 8 - ty;
        if (wide) mainloop<192>(acc, sb, i, n0, slot, split ? 14 : 16, ty == 1 ? PAUSE_QKV2 : -1, xver, rel_addr, rel);
        else mainloop<128>(acc, sb, i, n0, slot, split ? 14 : 16, -1, 0, rel_addr, rel);
        TRACE_AT(i, 2);
        mbar_wait(sb + kBarStat + xver * 8, 0);
        if (ty != 0 && ty != 3) mbar_wait(sb + kBarEpi + (i - 1) * 8, 0);
        if (ty < 2) {
          if (ty == 0) add_mean_term(acc, sm, 0, w, lane);
          epilogue_attn(acc, sm, sb, layer, ty, b, j, EPOCH, i, wg, w);
        } else {
          const int blk = ty == 3 ? 3 * j : 16 * ty - 40 + 2 * j;
          epilogue_gelu(acc, sm, sb, wide, wide ? 0 : 128 * ty - 320, g_h + (b * 56 + blk) * kTileBytes + w * 4096,
                        &g_flag[(i * 16 + b) * 32 + j * 4 + w], EPOCH, i, w);
        }
      }
      TRACE_AT(i, 3);
    }
#undef EPOCH
    asm volatile("barrier.cluster.arrive.relaxed.aligned;\nbarrier.cluster.wait.aligned;" ::: "memory");
  }
}

void build_segments(uint32_t* seg) {
  int n = 0;
  auto add = [&](int ty, int cnt, int kb0, int mode, int wide, int depth5, int dep, int reset) {
    seg[n++] = ty | cnt << 3 | kb0 << 9 | mode << 15 | wide << 17 | depth5 << 18 | dep << 19 | reset << 24;
  };
  for (int l = 0; l < 2; l++) {
    const int t = 7 * l;
    if (l == 0) {
      add(0, 16, 0, kModePlain, 1, 0, 31, 1);
      add(1, 16, 0, kModePlain, 1, 0, 31, 0);
    } else {
      add(0, 2, 0, kModeHead, 1, 0, 31, 1);
      add(1, 2, 0, kModeHead, 1, 0, 31, 0);
      add(0, 7, 0, kModeSkip, 1, 0, 6, 0);
      add(0, 7, 1, kModeSkip, 1, 0, 15, 0);
      add(1, 7, 0, kModeSkip, 1, 0, 31, 0);
      add(1, 7, 1, kModeSkip, 1, 0, 31, 0);
    }
    add(2, 4, 0, kModePlain, 0, 0, t, 1);
    add(2, 4, 4, kModePlain, 0, 1, 31, 0);
    add(2, 8, 8, kModePlain, 0, 1, t + 1, 0);
    add(3, 2, 0, kModeHead, 1, 0, 31, 2);
    add(4, 2, 0, kModeHead, 1, 0, 31, 0);
    add(3, 7, 0, kModeSkip, 1, 0, t + 2, 0);
    add(3, 7, 1, kModeSkip, 1, 0, 14 + 2 * l, 0);
    add(4, 4, 0, kModeSkip, 0, 0, 31, 3);
    add(4, 3, 0, kModeContinue, 0, 1, 31, 0);
    add(4, 7, 1, kModeSkip, 0, 1, 31, 0);
    add(5, 16, 0, kModePlain, 0, 1, 31, 0);
    add(6, 24, 0, kModePlain, 0, 1, t + 3, 0);
    add(6, 16, 24, kModePlain, 0, 1, t + 4, 0);
    add(6, 16, 40, kModePlain, 0, 1, t + 5, 0);
  }
}

typedef CUresult (*EncodeTiledFn)(CUtensorMap*, CUtensorMapDataType, cuuint32_t, void*, const cuuint64_t*,
                                  const cuuint64_t*, const cuuint32_t*, const cuuint32_t*, CUtensorMapInterleave,
                                  CUtensorMapSwizzle, CUtensorMapL2promotion, CUtensorMapFloatOOBfill);

CUtensorMap make_map(EncodeTiledFn enc, const void* p, int rank, const cuuint64_t* dims, const cuuint64_t* strides,
                     const cuuint32_t* box) {
  CUtensorMap m;
  const cuuint32_t es[5] = {1, 1, 1, 1, 1};
  enc(&m, CU_TENSOR_MAP_DATA_TYPE_BFLOAT16, rank, const_cast<void*>(p), dims, strides, box, es,
      CU_TENSOR_MAP_INTERLEAVE_NONE, CU_TENSOR_MAP_SWIZZLE_128B, CU_TENSOR_MAP_L2_PROMOTION_L2_128B,
      CU_TENSOR_MAP_FLOAT_OOB_FILL_NONE);
  return m;
}

CUtensorMap weight_map(EncodeTiledFn enc, const void* p, int k, int n, int blocks) {
  const cuuint64_t dims[3] = {64, (cuuint64_t)k, (cuuint64_t)n / 64};
  const cuuint64_t strides[2] = {(cuuint64_t)n * 2, 128};
  const cuuint32_t box[3] = {64, 32, (cuuint32_t)blocks};
  return make_map(enc, p, 3, dims, strides, box);
}

CUtensorMap token_map(EncodeTiledFn enc, const void* p, int rows) {
  const cuuint64_t dims[2] = {2 * kD, 1024};
  const cuuint64_t strides[1] = {4 * kD};
  const cuuint32_t box[2] = {64, (cuuint32_t)rows};
  return make_map(enc, p, 2, dims, strides, box);
}

}

extern "C" void kernel_launch(void* const* d_in, const int* in_sizes, int n_in, void* d_out, int out_size) {
  (void)in_sizes; (void)n_in; (void)out_size;
  static EncodeTiledFn enc = nullptr;
  if (!enc) {
    void* fn = nullptr;
    cudaDriverEntryPointQueryResult q;
    cudaGetDriverEntryPoint("cuTensorMapEncodeTiled", &fn, cudaEnableDefault, &q);
    enc = (EncodeTiledFn)fn;
    cudaFuncSetAttribute(fused_layers_kernel, cudaFuncAttributeMaxDynamicSharedMemorySize, kSmBytes);
  }
  Params prm;
  prm.wqkv = (const __nv_bfloat16*)d_in[1];
  prm.wo = (const __nv_bfloat16*)d_in[2];
  prm.w1 = (const __nv_bfloat16*)d_in[4];
  prm.b1 = (const __nv_bfloat16*)d_in[5];
  prm.w2 = (const __nv_bfloat16*)d_in[6];
  prm.b2 = (const __nv_bfloat16*)d_in[7];
  build_segments(prm.seg);
  const cuuint64_t qd[3] = {kD, kD, 3}, qs[2] = {3 * kD * 2, kD * 2};
  const cuuint32_t qb[3] = {64, 32, 3};
  const CUtensorMap map_x = token_map(enc, d_in[0], 128);
  const CUtensorMap map_out = token_map(enc, d_out, 32);
  const CUtensorMap map_qkv = make_map(enc, prm.wqkv, 3, qd, qs, qb);
  const CUtensorMap map_wo = weight_map(enc, prm.wo, kD, kD, 2);
  const CUtensorMap map_w1a = weight_map(enc, prm.w1, kD, kF, 3);
  const CUtensorMap map_w1b = weight_map(enc, prm.w1, kD, kF, 2);
  const CUtensorMap map_w2 = weight_map(enc, prm.w2, kF, kD, 2);
  fused_layers_kernel<<<kCtas, 384, kSmBytes>>>(map_x, map_out, map_qkv, map_wo, map_w1a, map_w1b, map_w2, prm);
}
```

```cpp
#include <cuda.h>
#include <cuda_bf16.h>
#include <cuda_runtime.h>
#include <stdint.h>

namespace {

constexpr int kD = 1024;
constexpr int kF = 3584;
constexpr int kCtas = 128;
constexpr int kGrid = 132;
constexpr int kTiles = 14;
constexpr int kTileBytes = 16384;

constexpr int kSmRing = 0;
constexpr int kSmX = 163840;
constexpr int kSmStg = kSmX + 32768;
constexpr int kSmHalo = kSmStg + 16384;
constexpr int kSmCsQ = kSmHalo + 6144;
constexpr int kSmV1 = kSmCsQ + 384 * 4;
constexpr int kSmB2 = kSmV1 + 448 * 8;
constexpr int kSmStat = kSmB2 + 128 * 4;
constexpr int kSmBar = kSmStat + 128 * 8;
constexpr int kBarFull = kSmBar;
constexpr int kBarTurn = kBarFull + 8 * 8;
constexpr int kBarReady = kBarTurn + 14 * 8;
constexpr int kBarPause = kBarReady + 17 * 8;
constexpr int kBarCs = kBarPause + 4 * 8;
constexpr int kBarInit = kBarCs + 3 * 8;
constexpr int kBarEpoch = kBarInit + 8;
constexpr int kBarEmpty = kBarEpoch + 8;
constexpr int kBarEpi = kBarEmpty + 8 * 8;
constexpr int kBarX = kBarEpi + 14 * 8;
constexpr int kBarStat = kBarX + 6 * 8;
constexpr int kBarResume = kBarStat + 4 * 8;
constexpr int kSmEpoch = kBarResume + 4 * 8;
constexpr int kSmBytes = kSmEpoch + 16;
constexpr int kSegs = 36;

constexpr int kFlagLines = kTiles * 16;

constexpr unsigned kSpinLimit = 1u << 24;

__device__ __align__(1024) uint8_t g_x[16 * 16 * kTileBytes];
__device__ __align__(1024) uint8_t g_o[16 * 16 * kTileBytes];
__device__ __align__(1024) uint8_t g_h[16 * 56 * kTileBytes];
__device__ __align__(128) uint2 g_stat[4 * 16 * 128 * 8];
__device__ __align__(128) unsigned g_cs[3 * kD + kF];
__device__ __align__(128) uint4 g_halo[2 * 16 * 16 * 256];
__device__ __align__(128) unsigned g_flag[kFlagLines * 32];
__device__ unsigned g_ticket;

#define TRACE_AT(tile, k)

struct Params {
  const __nv_bfloat16* x;
  const __nv_bfloat16* wqkv;
  const __nv_bfloat16* wo;
  const __nv_bfloat16* w1;
  const __nv_bfloat16* b1;
  const __nv_bfloat16* w2;
  const __nv_bfloat16* b2;
  uint32_t seg[kSegs];
};

__device__ __forceinline__ uint32_t smem_u32(const void* p) {
  return (uint32_t)__cvta_generic_to_shared(p);
}
__device__ __forceinline__ uint32_t mapa(uint32_t a, uint32_t cta) {
  uint32_t r;
  asm("mapa.shared::cluster.u32 %0, %1, %2;" : "=r"(r) : "r"(a), "r"(cta));
  return r;
}
__device__ __forceinline__ void mbar_init(uint32_t bar, int cnt) {
  asm volatile("mbarrier.init.shared::cta.b64 [%0], %1;" ::"r"(bar), "r"(cnt) : "memory");
}
__device__ __forceinline__ void mbar_expect_tx(uint32_t bar, uint32_t bytes) {
  asm volatile("mbarrier.arrive.expect_tx.shared::cta.b64 _, [%0], %1;" ::"r"(bar), "r"(bytes) : "memory");
}
__device__ __forceinline__ void mbar_arrive(uint32_t bar) {
  asm volatile("mbarrier.arrive.shared::cta.b64 _, [%0];" ::"r"(bar) : "memory");
}
__device__ __forceinline__ void mbar_arrive_cluster(uint32_t cluster_addr) {
  asm volatile("mbarrier.arrive.shared::cluster.b64 _, [%0];" ::"r"(cluster_addr) : "memory");
}
__device__ __forceinline__ void mbar_wait(uint32_t bar, uint32_t parity) {
  asm volatile(
      "{\n.reg .pred p;\n.reg .u32 c;\n"
      "mbarrier.try_wait.parity.shared::cta.b64 p, [%0], %1;\n"
      "@p bra.uni DONE;\n"
      "mov.u32 c, 0;\n"
      "RETRY:\n"
      "mbarrier.try_wait.parity.shared::cta.b64 p, [%0], %1;\n"
      "@p bra.uni DONE;\n"
      "add.u32 c, c, 1;\n"
      "setp.lt.u32 p, c, %2;\n"
      "@p bra.uni RETRY;\n"
      "trap;\n"
      "DONE:\n}" ::"r"(bar), "r"(parity), "n"(kSpinLimit)
      : "memory");
}
__device__ __forceinline__ void tma3d(uint32_t dst, const CUtensorMap* m, uint32_t bar, int c0, int c1, int c2) {
  asm volatile(
      "cp.async.bulk.tensor.3d.shared::cluster.global.mbarrier::complete_tx::bytes [%0], [%1, {%3, %4, %5}], [%2];"
      ::"r"(dst), "l"(m), "r"(bar), "r"(c0), "r"(c1), "r"(c2) : "memory");
}
__device__ __forceinline__ void tma3d_mc(uint32_t dst, const CUtensorMap* m, uint32_t bar, int c0, int c1, int c2) {
  asm volatile(
      "cp.async.bulk.tensor.3d.shared::cluster.global.mbarrier::complete_tx::bytes.multicast::cluster"
      " [%0], [%1, {%3, %4, %5}], [%2], %6;"
      ::"r"(dst), "l"(m), "r"(bar), "r"(c0), "r"(c1), "r"(c2), "h"((uint16_t)3) : "memory");
}
__device__ __forceinline__ void tma2d(uint32_t dst, const CUtensorMap* m, uint32_t bar, int c0, int c1) {
  asm volatile(
      "cp.async.bulk.tensor.2d.shared::cluster.global.mbarrier::complete_tx::bytes [%0], [%1, {%3, %4}], [%2];"
      ::"r"(dst), "l"(m), "r"(bar), "r"(c0), "r"(c1) : "memory");
}
__device__ __forceinline__ void tma2d_store(const CUtensorMap* m, uint32_t src, int c0, int c1) {
  asm volatile("cp.async.bulk.tensor.2d.global.shared::cta.bulk_group [%0, {%2, %3}], [%1];"
               ::"l"(m), "r"(src), "r"(c0), "r"(c1) : "memory");
}
__device__ __forceinline__ bool elect() {
  uint32_t p;
  asm volatile("{\n.reg .pred p;\nelect.sync _|p, 0xffffffff;\nselp.b32 %0, 1, 0, p;\n}" : "=r"(p));
  return p;
}
__device__ __forceinline__ void bulk_load(uint32_t dst, const void* src, uint32_t bytes, uint32_t bar) {
  asm volatile("cp.async.bulk.shared::cluster.global.mbarrier::complete_tx::bytes [%0], [%1], %2, [%3];"
               ::"r"(dst), "l"(src), "r"(bytes), "r"(bar) : "memory");
}
__device__ __forceinline__ void bulk_store(void* dst, uint32_t src, uint32_t bytes) {
  asm volatile("cp.async.bulk.global.shared::cta.bulk_group [%0], [%1], %2;" ::"l"(dst), "r"(src), "r"(bytes)
               : "memory");
}
__device__ __forceinline__ void bulk_commit() { asm volatile("cp.async.bulk.commit_group;" ::: "memory"); }
__device__ __forceinline__ void bulk_wait_read() { asm volatile("cp.async.bulk.wait_group.read 0;" ::: "memory"); }
__device__ __forceinline__ void bulk_wait() { asm volatile("cp.async.bulk.wait_group 0;" ::: "memory"); }
__device__ __forceinline__ void l2_prefetch(const void* p, uint32_t bytes) {
  asm volatile("cp.async.bulk.prefetch.L2.global [%0], %1;" ::"l"(p), "r"(bytes) : "memory");
}
__device__ __forceinline__ void fence_async_smem() { asm volatile("fence.proxy.async.shared::cta;" ::: "memory"); }
__device__ __forceinline__ unsigned ld_relaxed(const unsigned* p) {
  unsigned v;
  asm volatile("ld.relaxed.gpu.global.u32 %0, [%1];" : "=r"(v) : "l"(p) : "memory");
  return v;
}
__device__ __forceinline__ uint2 ld_relaxed2(const uint2* p) {
  uint2 v;
  asm volatile("ld.relaxed.gpu.global.v2.u32 {%0, %1}, [%2];" : "=r"(v.x), "=r"(v.y) : "l"(p) : "memory");
  return v;
}
__device__ __forceinline__ void st_relaxed(unsigned* p, unsigned v) {
  asm volatile("st.relaxed.gpu.global.u32 [%0], %1;" ::"l"(p), "r"(v) : "memory");
}
__device__ __forceinline__ void st_release(unsigned* p, unsigned v) {
  asm volatile("st.release.gpu.global.u32 [%0], %1;" ::"l"(p), "r"(v) : "memory");
}
#define ACQ_MODE 1
__device__ __forceinline__ void wait_flags(const unsigned* p, unsigned epoch) {
  unsigned spins = 0;
  while (true) {
    unsigned v;
    if (ACQ_MODE) asm volatile("ld.acquire.gpu.global.u32 %0, [%1];" : "=r"(v) : "l"(p) : "memory");
    else v = ld_relaxed(p);
    if (__all_sync(0xffffffffu, v == epoch)) break;
    if (++spins > kSpinLimit) __trap();
  }
  if (ACQ_MODE) asm volatile("fence.proxy.async.global;" ::: "memory");
  __syncwarp();
}
__device__ __forceinline__ unsigned tag_value(float v, unsigned epoch) {
  return (__float_as_uint(v) & ~7u) | (epoch & 7u);
}
__device__ __forceinline__ float untag_value(unsigned v) { return __uint_as_float(v & ~7u); }
__device__ __forceinline__ void stsm4(uint32_t a, uint32_t r0, uint32_t r1, uint32_t r2, uint32_t r3) {
  asm volatile("stmatrix.sync.aligned.m8n8.x4.shared.b16 [%0], {%1, %2, %3, %4};" ::"r"(a), "r"(r0), "r"(r1),
               "r"(r2), "r"(r3) : "memory");
}
__device__ __forceinline__ void stsm4_t(uint32_t a, uint32_t r0, uint32_t r1, uint32_t r2, uint32_t r3) {
  asm volatile("stmatrix.sync.aligned.m8n8.x4.trans.shared.b16 [%0], {%1, %2, %3, %4};" ::"r"(a), "r"(r0),
               "r"(r1), "r"(r2), "r"(r3) : "memory");
}
__device__ __forceinline__ uint32_t transpose8(uint32_t a) {
  uint32_t d;
  asm volatile("movmatrix.sync.aligned.m8n8.trans.b16 %0, %1;" : "=r"(d) : "r"(a));
  return d;
}
__device__ __forceinline__ void mma16816(float (&c)[4], uint32_t a0, uint32_t a1, uint32_t a2, uint32_t a3,
                                         uint32_t b0, uint32_t b1) {
  asm volatile("mma.sync.aligned.m16n8k16.row.col.f32.bf16.bf16.f32 {%0, %1, %2, %3}, {%4, %5, %6, %7}, {%8, %9}, "
               "{%0, %1, %2, %3};"
               : "+f"(c[0]), "+f"(c[1]), "+f"(c[2]), "+f"(c[3])
               : "r"(a0), "r"(a1), "r"(a2), "r"(a3), "r"(b0), "r"(b1));
}
__device__ __forceinline__ float shfl_xor(float v, int m) {
  float r;
  asm volatile("shfl.sync.bfly.b32 %0, %1, %2, 31, 0xffffffff;" : "=f"(r) : "f"(v), "r"(m));
  return r;
}
__device__ __forceinline__ float tanh_fast(float x) {
  float r;
  asm("tanh.approx.f32 %0, %1;" : "=f"(r) : "f"(x));
  return r;
}
__device__ __forceinline__ void ldsm4(uint32_t a, uint32_t (&r)[4]) {
  asm volatile("ldmatrix.sync.aligned.m8n8.x4.shared.b16 {%0, %1, %2, %3}, [%4];"
               : "=r"(r[0]), "=r"(r[1]), "=r"(r[2]), "=r"(r[3]) : "r"(a) : "memory");
}
__device__ __forceinline__ uint32_t pack2(float lo, float hi) {
  uint32_t r;
  asm("cvt.rn.bf16x2.f32 %0, %1, %2;" : "=r"(r) : "f"(hi), "f"(lo));
  return r;
}
__device__ __forceinline__ float bf_lo(uint32_t r) { return __uint_as_float(r << 16); }
__device__ __forceinline__ float bf_hi(uint32_t r) { return __uint_as_float(r & 0xffff0000u); }
__device__ __forceinline__ float ex2(float x) {
  float r;
  asm("ex2.approx.ftz.f32 %0, %1;" : "=f"(r) : "f"(x));
  return r;
}
__device__ __forceinline__ float rcp(float x) {
  float r;
  asm("rcp.approx.ftz.f32 %0, %1;" : "=f"(r) : "f"(x));
  return r;
}
template <int N>
__device__ __forceinline__ void wg_wait() {
  asm volatile("wgmma.wait_group.sync.aligned %0;" ::"n"(N) : "memory");
}
__device__ __forceinline__ void yield_slot() { asm volatile("pmevent 0;"); }
__device__ __forceinline__ void wg_bar(int wg) { asm volatile("bar.sync %0, 128;" ::"r"(wg + 1) : "memory"); }

template <int N>
__device__ __forceinline__ void mma_kblock(float (&acc)[2][96], uint32_t a, uint32_t b);

#define F8(d, i) \
  "+f"(d[i]), "+f"(d[i + 1]), "+f"(d[i + 2]), "+f"(d[i + 3]), "+f"(d[i + 4]), "+f"(d[i + 5]), "+f"(d[i + 6]), "+f"(d[i + 7])
#define KSTEP(N, A, B, oa0, oa1, ob)                                                       \
  "add.u32 t, " B ", " #ob ";\nmov.b64 db, {t, hb};\n"                                      \
  "add.u32 t, " A ", " #oa0 ";\nmov.b64 da, {t, ha};\n"                                     \
  "wgmma.mma_async.sync.aligned.m64n" #N "k16.f32.bf16.bf16 {" ACC##N##_0 "}, da, db, 1, 1, 1, 0, 1;\n" \
  "add.u32 t, " A ", " #oa1 ";\nmov.b64 da, {t, ha};\n"                                     \
  "wgmma.mma_async.sync.aligned.m64n" #N "k16.f32.bf16.bf16 {" ACC##N##_1 "}, da, db, 1, 1, 1, 0, 1;\n"

#define ACC128_0 \
  "%0, %1, %2, %3, %4, %5, %6, %7, %8, %9, %10, %11, %12, %13, %14, %15, " \
  "%16, %17, %18, %19, %20, %21, %22, %23, %24, %25, %26, %27, %28, %29, %30, %31, " \
  "%32, %33, %34, %35, %36, %37, %38, %39, %40, %41, %42, %43, %44, %45, %46, %47, " \
  "%48, %49, %50, %51, %52, %53, %54, %55, %56, %57, %58, %59, %60, %61, %62, %63"
#define ACC128_1 \
  "%64, %65, %66, %67, %68, %69, %70, %71, %72, %73, %74, %75, %76, %77, %78, %79, " \
  "%80, %81, %82, %83, %84, %85, %86, %87, %88, %89, %90, %91, %92, %93, %94, %95, " \
  "%96, %97, %98, %99, %100, %101, %102, %103, %104, %105, %106, %107, %108, %109, %110, %111, " \
  "%112, %113, %114, %115, %116, %117, %118, %119, %120, %121, %122, %123, %124, %125, %126, %127"
template <>
__device__ __forceinline__ void mma_kblock<128>(float (&acc)[2][96], uint32_t a, uint32_t b) {
  asm volatile("{\n.reg .b32 t, ha, hb;\n.reg .b64 da, db;\n"
               "mov.b32 ha, 0x40000080;\nmov.b32 hb, 0x40000040;\n"
               "wgmma.fence.sync.aligned;\n"
               KSTEP(128, "%128", "%129", 0, 64, 0) KSTEP(128, "%128", "%129", 2, 66, 128)
               KSTEP(128, "%128", "%129", 4, 68, 512) KSTEP(128, "%128", "%129", 6, 70, 640)
               "wgmma.commit_group.sync.aligned;\n}\n"
      : F8(acc[0], 0), F8(acc[0], 8), F8(acc[0], 16), F8(acc[0], 24), F8(acc[0], 32), F8(acc[0], 40), F8(acc[0], 48), F8(acc[0], 56),
        F8(acc[1], 0), F8(acc[1], 8), F8(acc[1], 16), F8(acc[1], 24), F8(acc[1], 32), F8(acc[1], 40), F8(acc[1], 48), F8(acc[1], 56)
      : "r"(a), "r"(b)
      : "memory");
}

#define ACC192_0 \
  "%0, %1, %2, %3, %4, %5, %6, %7, %8, %9, %10, %11, %12, %13, %14, %15, " \
  "%16, %17, %18, %19, %20, %21, %22, %23, %24, %25, %26, %27, %28, %29, %30, %31, " \
  "%32, %33, %34, %35, %36, %37, %38, %39, %40, %41, %42, %43, %44, %45, %46, %47, " \
  "%48, %49, %50, %51, %52, %53, %54, %55, %56, %57, %58, %59, %60, %61, %62, %63, " \
  "%64, %65, %66, %67, %68, %69, %70, %71, %72, %73, %74, %75, %76, %77, %78, %79, " \
  "%80, %81, %82, %83, %84, %85, %86, %87, %88, %89, %90, %91, %92, %93, %94, %95"
#define ACC192_1 \
  "%96, %97, %98, %99, %100, %101, %102, %103, %104, %105, %106, %107, %108, %109, %110, %111, " \
  "%112, %113, %114, %115, %116, %117, %118, %119, %120, %121, %122, %123, %124, %125, %126, %127, " \
  "%128, %129, %130, %131, %132, %133, %134, %135, %136, %137, %138, %139, %140, %141, %142, %143, " \
  "%144, %145, %146, %147, %148, %149, %150, %151, %152, %153, %154, %155, %156, %157, %158, %159, " \
  "%160, %161, %162, %163, %164, %165, %166, %167, %168, %169, %170, %171, %172, %173, %174, %175, " \
  "%176, %177, %178, %179, %180, %181, %182, %183, %184, %185, %186, %187, %188, %189, %190, %191"
template <>
__device__ __forceinline__ void mma_kblock<192>(float (&acc)[2][96], uint32_t a, uint32_t b) {
  asm volatile("{\n.reg .b32 t, ha, hb;\n.reg .b64 da, db;\n"
               "mov.b32 ha, 0x40000080;\nmov.b32 hb, 0x40000040;\n"
               "wgmma.fence.sync.aligned;\n"
               KSTEP(192, "%192", "%193", 0, 64, 0) KSTEP(192, "%192", "%193", 2, 66, 128)
               KSTEP(192, "%192", "%193", 4, 68, 768) KSTEP(192, "%192", "%193", 6, 70, 896)
               "wgmma.commit_group.sync.aligned;\n}\n"
      : F8(acc[0], 0), F8(acc[0], 8), F8(acc[0], 16), F8(acc[0], 24), F8(acc[0], 32), F8(acc[0], 40), F8(acc[0], 48), F8(acc[0], 56), F8(acc[0], 64), F8(acc[0], 72), F8(acc[0], 80), F8(acc[0], 88),
        F8(acc[1], 0), F8(acc[1], 8), F8(acc[1], 16), F8(acc[1], 24), F8(acc[1], 32), F8(acc[1], 40), F8(acc[1], 48), F8(acc[1], 56), F8(acc[1], 64), F8(acc[1], 72), F8(acc[1], 80), F8(acc[1], 88)
      : "r"(a), "r"(b)
      : "memory");
}

enum { kModePlain = 0, kModeHead = 1, kModeSkip = 2, kModeContinue = 3 };

template <int N>
__device__ __forceinline__ void fence_acc(float (&acc)[2][96]) {
#pragma unroll
  for (int h = 0; h < 2; h++)
#pragma unroll
    for (int i = 0; i < N / 2; i++) asm volatile("" : "+f"(acc[h][i])::"memory");
}

template <int N>
__device__ __forceinline__ void zero_acc(float (&acc)[2][96]) {
#pragma unroll
  for (int h = 0; h < 2; h++)
#pragma unroll
    for (int i = 0; i < N / 2; i++) acc[h][i] = 0.f;
}

constexpr uint32_t kToB = (kTileBytes >> 4) + ((4096u >> 4) << 16) - (1u << 16);

#define TRACE_KB(nb)

template <int N>
__device__ __forceinline__ void head_blocks(float (&acc)[2][96], uint32_t sb, int n0, int slot, uint32_t xbar,
                                            uint32_t rel_addr, bool rel) {
  const uint32_t ring = (((sb & 0x3FFFF) + kSmRing) >> 4) | (1u << 16);
  const uint32_t xdesc = (((sb & 0x3FFFF) + kSmX) >> 4) | (1u << 16);
  const uint32_t nb = n0 * 8;
  fence_acc<N>(acc);
  mbar_wait(xbar, 0);
  mbar_wait(sb + kBarFull + (nb & 56), (nb >> 6) & 1);
  TRACE_KB(nb);
  mma_kblock<N>(acc, xdesc, ring + slot * 2560 + kToB);
  mbar_wait(xbar + 8, 0);
  mbar_wait(sb + kBarFull + (nb & 56) + 8, (nb >> 6) & 1);
  TRACE_KB(nb + 8);
  mma_kblock<N>(acc, xdesc + (kTileBytes >> 4), ring + ((slot + 1) & 3) * 2560 + kToB);
  wg_wait<1>();
  if (rel) mbar_arrive_cluster(rel_addr + (nb & 56));
  wg_wait<0>();
  if (rel) mbar_arrive_cluster(rel_addr + (nb & 56) + 8);
  fence_acc<N>(acc);
}

template <int N>
__device__ __forceinline__ void mainloop(float (&acc)[2][96], uint32_t sb, int tile, int n0, int slot, int nkb,
                                         int pause_kk, int att, uint32_t rel_addr, bool rel) {
  constexpr uint32_t kStep = (N == 192 ? 5 : 4) * 512;
  const uint32_t ring = (((sb & 0x3FFFF) + kSmRing) >> 4) | (1u << 16);
  uint32_t st = ring + slot * kStep;
  uint32_t nb = n0 * 8;
  const bool signal = (threadIdx.x & 127) == 64;
  fence_acc<N>(acc);
  if (tile > 0) mbar_wait(sb + kBarTurn + (tile - 1) * 8, 0);
  TRACE_AT(tile, 0);
  int kk = 0;
#pragma unroll 1
  do {
    if (kk == pause_kk) {
      if (signal) mbar_arrive(sb + kBarPause + att * 8);
      mbar_wait(sb + kBarResume + att * 8, 0);
    }
    mbar_wait(sb + kBarFull + (nb & 56), (nb >> 6) & 1);
    if (kk == 0) TRACE_AT(tile, 1);
    TRACE_KB(nb);
    mma_kblock<N>(acc, st, st + kToB);
    if (kk == nkb - 1 && signal) mbar_arrive(sb + kBarTurn + tile * 8);
    wg_wait<1>();
    if (rel && kk > 0) mbar_arrive_cluster(rel_addr + ((nb - 8) & 56));
    st += kStep;
    if (st == ring + 10240) st = ring;
    nb += 8;
  } while (++kk < nkb);
  wg_wait<0>();
  if (rel) mbar_arrive_cluster(rel_addr + ((nb - 8) & 56));
  fence_acc<N>(acc);
}

__device__ __forceinline__ void publish_stats(uint32_t sb, uint2* stat, int w, int lane, unsigned epoch) {
  const uint32_t row = sb + kSmX + (32 * w + lane) * 128;
  float s[4], q[4];
#pragma unroll
  for (int c = 0; c < 4; c++) s[c] = q[c] = 0.f;
#pragma unroll 1
  for (int J = 0; J < 16; J++) {
    uint32_t r[4];
    ldsm4(row + (J >> 3) * kTileBytes + (((J ^ lane) & 7) << 4), r);
#pragma unroll
    for (int c = 0; c < 4; c++) {
      const float lo = bf_lo(r[c]);
      s[c] += lo;
      q[c] = fmaf(lo, lo, q[c]);
    }
    yield_slot();
#pragma unroll
    for (int c = 0; c < 4; c++) {
      const float hi = bf_hi(r[c]);
      s[c] += hi;
      q[c] = fmaf(hi, hi, q[c]);
    }
  }
#pragma unroll
  for (int c = 0; c < 4; c++) {
    s[c] += shfl_xor(s[c], 1);
    q[c] += shfl_xor(q[c], 1);
    s[c] += shfl_xor(s[c], 2);
    q[c] += shfl_xor(q[c], 2);
  }
  const int t = lane & 3, g = lane >> 2;
  const float so = t == 0 ? s[0] : t == 1 ? s[1] : t == 2 ? s[2] : s[3];
  const float qo = t == 0 ? q[0] : t == 1 ? q[1] : t == 2 ? q[2] : q[3];
  asm volatile("st.relaxed.gpu.global.v2.u32 [%0], {%1, %2};" ::"l"(stat + 32 * w + 8 * t + g),
               "r"(tag_value(so, epoch)), "r"(tag_value(qo, epoch)) : "memory");
}

__device__ __forceinline__ void add_chunk(float (&a)[8], const uint4& v) {
  a[0] += bf_lo(v.x); a[1] += bf_hi(v.x);
  a[2] += bf_lo(v.y); a[3] += bf_hi(v.y);
  a[4] += bf_lo(v.z); a[5] += bf_hi(v.z);
  a[6] += bf_lo(v.w); a[7] += bf_hi(v.w);
}

__device__ __forceinline__ int helper_col(int id, int slab) {
  return slab < 6 ? (slab % 3) * kD + (slab / 3) * 512 + id * 128 : (slab - 6) * 512 + id * 128;
}
__device__ __forceinline__ void helper_cta(const CUtensorMap* map_q, const CUtensorMap* map_1, uint8_t* sm,
                                           uint32_t sb, int id, int warp) {
  constexpr int kRed = 6 * 32768, kBar = kRed + 2 * 4096;
  const int tid = threadIdx.x;
  if (warp == 8 && elect()) {
#pragma unroll
    for (int s = 0; s < 6; s++) {
      mbar_init(sb + kBar + s * 8, 1);
      mbar_init(sb + kBar + 64 + s * 8, 8);
    }
    fence_async_smem();
  }
  __syncthreads();
  if (warp == 8) {
    int slot = 0, ph = 1;
#pragma unroll 1
    for (int n = 0; n < 104; n++) {
      mbar_wait(sb + kBar + 64 + slot * 8, ph);
      if (elect()) {
        mbar_expect_tx(sb + kBar + slot * 8, 32768);
        tma2d(sb + slot * 32768, n < 48 ? map_q : map_1, sb + kBar + slot * 8, helper_col(id, n >> 3), (n & 7) * 128);
      }
      if (++slot == 6) slot = 0, ph ^= 1;
    }
  } else if (warp < 8) {
    if (tid == 0) *reinterpret_cast<unsigned*>(sm + kBar + 128) = atomicAdd(&g_ticket, 1u) / kGrid + 1;
    int slot = 0, ph = 0;
#pragma unroll 1
    for (int slab = 0; slab < 13; slab++) {
      float a[8];
#pragma unroll
      for (int e = 0; e < 8; e++) a[e] = 0.f;
#pragma unroll 1
      for (int box = 0; box < 8; box++) {
        mbar_wait(sb + kBar + slot * 8, ph);
        const uint4* p = reinterpret_cast<const uint4*>(sm + slot * 32768) + tid;
        uint4 v[8];
#pragma unroll
        for (int i = 0; i < 8; i++) v[i] = p[i * 256];
        __syncwarp();
        if (elect()) mbar_arrive(sb + kBar + 64 + slot * 8);
#pragma unroll
        for (int i = 0; i < 8; i++) add_chunk(a, v[i]);
        if (++slot == 6) slot = 0, ph ^= 1;
      }
      float* red = reinterpret_cast<float*>(sm + kRed + (slab & 1) * 4096);
#pragma unroll
      for (int e = 0; e < 8; e++) a[e] += shfl_xor(a[e], 16);
      if ((tid & 16) == 0) {
        float4* d = reinterpret_cast<float4*>(red + warp * 128 + (tid & 15) * 8);
        d[0] = make_float4(a[0], a[1], a[2], a[3]);
        d[1] = make_float4(a[4], a[5], a[6], a[7]);
      }
      asm volatile("bar.sync 1, 256;" ::: "memory");
      if (warp < 4) {
        float t = 0.f;
#pragma unroll
        for (int q = 0; q < 8; q++) t += red[q * 128 + tid];
        st_relaxed(g_cs + (slab < 6 ? 0 : 3 * kD) + helper_col(id, slab) + tid,
                   tag_value(t, *reinterpret_cast<volatile unsigned*>(sm + kBar + 128)));
      }
    }
  }
}

constexpr float kGelu0 = 2.f * 0.7978845608028654f;
constexpr float kGelu1 = 8.f * 0.7978845608028654f * 0.044715f;

template <int CH>
__device__ __forceinline__ void gelu_chunk(const float (&acc)[2][96], const float2 (&st)[4], const float4* vec,
                                           uint32_t stg, int lane, uint8_t* dst) {
  uint32_t pk[8][4];
#pragma unroll
  for (int jj = 0; jj < 8; jj++) {
    const int J = CH * 8 + jj;
    const float4 v = vec[J * 4];
    float u[8], z[8];
#pragma unroll
    for (int c = 0; c < 4; c++) {
      u[2 * c] = fmaf(acc[c & 1][4 * J + (c & 2)], st[c].x, fmaf(st[c].y, v.x, v.z));
      u[2 * c + 1] = fmaf(acc[c & 1][4 * J + (c & 2) + 1], st[c].x, fmaf(st[c].y, v.y, v.w));
    }
    yield_slot();
#pragma unroll
    for (int e = 0; e < 8; e++) z[e] = fmaf(u[e] * u[e], kGelu1, kGelu0);
    yield_slot();
#pragma unroll
    for (int e = 0; e < 8; e++) z[e] = tanh_fast(u[e] * z[e]);
    yield_slot();
#pragma unroll
    for (int c = 0; c < 4; c++)
      pk[jj][c] = pack2(fmaf(u[2 * c], z[2 * c], u[2 * c]), fmaf(u[2 * c + 1], z[2 * c + 1], u[2 * c + 1]));
    yield_slot();
  }
  if (CH > 0) {
    if (elect()) bulk_wait_read();
    __syncwarp();
  }
#pragma unroll
  for (int jj = 0; jj < 8; jj++)
    stsm4(stg + lane * 128 + ((jj ^ (lane & 7)) << 4), pk[jj][0], pk[jj][1], pk[jj][2], pk[jj][3]);
  fence_async_smem();
  __syncwarp();
  if (elect()) {
    bulk_store(dst + CH * kTileBytes, stg, 4096);
    bulk_commit();
  }
}

__device__ __forceinline__ void epilogue_gelu(const float (&acc)[2][96], uint8_t* sm, uint32_t sb, bool wide,
                                              int vcol0, uint8_t* dst, int tile, int w) {
  const int lane = threadIdx.x & 31, t = lane & 3, g = lane >> 2;
  float2 st[4];
#pragma unroll
  for (int c = 0; c < 4; c++) {
    const float2 v = reinterpret_cast<const float2*>(sm + kSmStat)[32 * w + 8 * c + g];
    st[c].x = 0.5f * v.x;
    st[c].y = st[c].x * v.y;
  }
  const float4* vec = reinterpret_cast<const float4*>(sm + kSmV1) + vcol0 / 2 + t;
  const uint32_t stg = sb + kSmStg + w * 4096;
  TRACE_AT(tile, 8);
  gelu_chunk<0>(acc, st, vec, stg, lane, dst);
  TRACE_AT(tile, 9);
  gelu_chunk<1>(acc, st, vec, stg, lane, dst);
  TRACE_AT(tile, 10);
  if (wide) gelu_chunk<2>(acc, st, vec, stg, lane, dst);
  TRACE_AT(tile, 11);
  if (elect()) {
    bulk_wait();
    TRACE_AT(tile, 12);
    mbar_arrive(sb + kBarEpi + tile * 8);
  }
  __syncwarp();
}

__device__ __forceinline__ void add_mean_term(float (&acc)[2][96], uint8_t* sm, int tq, int w, int lane) {
  const int t = lane & 3, g = lane >> 2;
  float nm[4];
#pragma unroll
  for (int c = 0; c < 4; c++) nm[c] = reinterpret_cast<const float2*>(sm + kSmStat)[32 * w + 8 * c + g].y;
  const float2* cs = reinterpret_cast<const float2*>(sm + kSmCsQ) + tq * 96 + t;
#pragma unroll
  for (int J = 0; J < 24; J++) {
    const float2 v = cs[J * 4];
#pragma unroll
    for (int c = 0; c < 4; c++) {
      acc[c & 1][4 * J + (c & 2)] = fmaf(nm[c], v.x, acc[c & 1][4 * J + (c & 2)]);
      acc[c & 1][4 * J + (c & 2) + 1] = fmaf(nm[c], v.y, acc[c & 1][4 * J + (c & 2) + 1]);
    }
    if (J & 1) yield_slot();
  }
}

__device__ __forceinline__ void epilogue_attn(const float (&acc)[2][96], uint8_t* sm, uint32_t sb, int layer, int tq,
                                              int b, int j, unsigned epoch, int tile, int wg, int w) {
  const int lane = threadIdx.x & 31, t = lane & 3, g = lane >> 2;
  const int hp = j + 8 * tq, att = 2 * layer + tq;
  float rs[4];
#pragma unroll
  for (int c = 0; c < 4; c++) rs[c] = reinterpret_cast<const float2*>(sm + kSmStat)[32 * w + 8 * c + g].x;
  uint32_t q[4][8], k[5][8], vt[5][8];
#define SCALED(c, J) pack2(acc[(c) & 1][4 * (J) + ((c) & 2)] * rs[c], acc[(c) & 1][4 * (J) + ((c) & 2) + 1] * rs[c])
#pragma unroll
  for (int J = 0; J < 8; J++) {
    k[4][J] = SCALED(3, 8 + J);
    vt[4][J] = transpose8(SCALED(3, 16 + J));
    if (J & 1) yield_slot();
  }
  if (w < 3) {
    uint4* hs = reinterpret_cast<uint4*>(sm + kSmHalo + w * 2048) + lane;
    hs[0] = make_uint4(k[4][0], k[4][1], k[4][2], k[4][3]);
    hs[32] = make_uint4(k[4][4], k[4][5], k[4][6], k[4][7]);
    hs[64] = make_uint4(vt[4][0], vt[4][1], vt[4][2], vt[4][3]);
    hs[96] = make_uint4(vt[4][4], vt[4][5], vt[4][6], vt[4][7]);
  } else if ((b & 7) != 7) {
    uint4* gh = g_halo + ((layer * 16 + b) * 16 + hp) * 256 + lane;
#pragma unroll
    for (int i = 0; i < 8; i++)
      asm volatile("{\n.reg .b64 x, y;\nmov.b64 x, {%1, %3};\nmov.b64 y, {%2, %3};\n"
                   "st.relaxed.gpu.global.v2.b64 [%0], {x, y};\n}" ::"l"(gh + i * 32),
                   "r"(k[4][i]), "r"(vt[4][i]), "r"(epoch) : "memory");
  }
#pragma unroll
  for (int c = 0; c < 3; c++)
#pragma unroll
    for (int J = 0; J < 8; J++) {
      k[c + 1][J] = SCALED(c, 8 + J);
      vt[c + 1][J] = transpose8(SCALED(c, 16 + J));
      if (J & 1) yield_slot();
    }
#pragma unroll
  for (int c = 0; c < 4; c++)
#pragma unroll
    for (int J = 0; J < 8; J++) {
      q[c][J] = SCALED(c, J);
      if ((J & 3) == 3) yield_slot();
    }
#undef SCALED
  TRACE_AT(tile, 8);
  wg_bar(wg);
  const bool first = w == 0 && (b & 7) == 0;
  if (w > 0) {
    const uint4* hs = reinterpret_cast<const uint4*>(sm + kSmHalo + (w - 1) * 2048) + lane;
    const uint4 a0 = hs[0], a1 = hs[32], a2 = hs[64], a3 = hs[96];
    k[0][0] = a0.x; k[0][1] = a0.y; k[0][2] = a0.z; k[0][3] = a0.w;
    k[0][4] = a1.x; k[0][5] = a1.y; k[0][6] = a1.z; k[0][7] = a1.w;
    vt[0][0] = a2.x; vt[0][1] = a2.y; vt[0][2] = a2.z; vt[0][3] = a2.w;
    vt[0][4] = a3.x; vt[0][5] = a3.y; vt[0][6] = a3.z; vt[0][7] = a3.w;
  } else if (first) {
#pragma unroll
    for (int i = 0; i < 8; i++) k[0][i] = vt[0][i] = 0u;
  } else {
    const uint4* gh = g_halo + ((layer * 16 + b - 1) * 16 + hp) * 256 + lane;
    unsigned spins = 0;
    while (true) {
      unsigned diff = 0;
#pragma unroll
      for (int i = 0; i < 8; i++) {
        unsigned t0, t1;
        asm volatile("{\n.reg .b64 x, y;\nld.relaxed.gpu.global.v2.b64 {x, y}, [%4];\n"
                     "mov.b64 {%0, %1}, x;\nmov.b64 {%2, %3}, y;\n}"
                     : "=r"(k[0][i]), "=r"(t0), "=r"(vt[0][i]), "=r"(t1) : "l"(gh + i * 32) : "memory");
        diff |= (t0 ^ epoch) | (t1 ^ epoch);
      }
      if (__all_sync(0xffffffffu, diff == 0)) break;
      if (++spins > kSpinLimit) __trap();
    }
  }
  TRACE_AT(tile, 9);
  mbar_wait(sb + kBarPause + att * 8, 0);
  TRACE_AT(tile, 10);

  float s[2][5][4];
#pragma unroll
  for (int hd = 0; hd < 2; hd++)
#pragma unroll
    for (int kg = 0; kg < 5; kg++) {
      const int ca = kg > 0 ? kg - 1 : 0, cb = kg < 4 ? kg : 3;
#pragma unroll
      for (int e = 0; e < 4; e++) s[hd][kg][e] = 0.f;
#pragma unroll
      for (int ks = 0; ks < 2; ks++) {
        const int J = 4 * hd + 2 * ks;
        mma16816(s[hd][kg], q[ca][J], q[cb][J], q[ca][J + 1], q[cb][J + 1], k[kg][J], k[kg][J + 1]);
      }
    }
  constexpr float kScale = 0.17677669529663687f * 1.4426950408889634f;
  const bool own0 = 2 * t <= g, own1 = 2 * t + 1 <= g;
  const uint32_t own_mask = (own0 ? 0xffffu : 0u) | (own1 ? 0xffff0000u : 0u);
  float o[2][4][2][4];
#pragma unroll
  for (int hd = 0; hd < 2; hd++) {
    float v0[4], v1[4], m[4];
#pragma unroll
    for (int c = 0; c < 4; c++) {
      float p0 = s[hd][c][2], p1 = s[hd][c][3];
      if (c == 0 && first) p0 = p1 = -INFINITY;
      v0[c] = own0 ? s[hd][c + 1][0] : p0;
      v1[c] = own1 ? s[hd][c + 1][1] : p1;
      m[c] = fmaxf(v0[c], v1[c]);
    }
#pragma unroll
    for (int c = 0; c < 4; c++) m[c] = fmaxf(m[c], shfl_xor(m[c], 1));
#pragma unroll
    for (int c = 0; c < 4; c++) m[c] = fmaxf(m[c], shfl_xor(m[c], 2));
#pragma unroll
    for (int c = 0; c < 4; c++) {
      const float nm = -m[c] * kScale;
      v0[c] = ex2(fmaf(v0[c], kScale, nm));
      v1[c] = ex2(fmaf(v1[c], kScale, nm));
      m[c] = v0[c] + v1[c];
    }
#pragma unroll
    for (int c = 0; c < 4; c++) m[c] += shfl_xor(m[c], 1);
#pragma unroll
    for (int c = 0; c < 4; c++) m[c] += shfl_xor(m[c], 2);
#pragma unroll
    for (int c = 0; c < 4; c++) {
      const float inv = rcp(m[c]);
      const uint32_t p = pack2(v0[c] * inv, v1[c] * inv);
#pragma unroll
      for (int ds = 0; ds < 2; ds++) {
        const int J = 4 * hd + 2 * ds;
#pragma unroll
        for (int e = 0; e < 4; e++) o[hd][c][ds][e] = 0.f;
        mma16816(o[hd][c][ds], vt[c][J], vt[c][J + 1], vt[c + 1][J], vt[c + 1][J + 1], p & ~own_mask, p & own_mask);
      }
    }
  }
  TRACE_AT(tile, 11);
  const uint32_t stg = sb + kSmStg + w * 4096;
#pragma unroll
  for (int J = 0; J < 8; J++) {
    const int hd = J >> 2, ds = (J >> 1) & 1, e = 2 * (J & 1);
    stsm4_t(stg + lane * 128 + ((J ^ (lane & 7)) << 4), pack2(o[hd][0][ds][e], o[hd][0][ds][e + 1]),
            pack2(o[hd][1][ds][e], o[hd][1][ds][e + 1]), pack2(o[hd][2][ds][e], o[hd][2][ds][e + 1]),
            pack2(o[hd][3][ds][e], o[hd][3][ds][e + 1]));
  }
  if (elect()) mbar_arrive(sb + kBarResume + att * 8);
  fence_async_smem();
  __syncwarp();
  TRACE_AT(tile, 12);
  if (elect()) {
    bulk_store(g_o + (b * 16 + hp) * kTileBytes + w * 4096, stg, 4096);
    bulk_commit();
    bulk_wait();
    TRACE_AT(tile, 13);
    mbar_arrive(sb + kBarEpi + tile * 8);
  }
  __syncwarp();
}

__device__ __forceinline__ void gather_stats(uint8_t* sm, const uint2* stat, unsigned epoch) {
  const int r = threadIdx.x & 127;
  uint2 a[8];
  unsigned spins = 0;
  while (true) {
    unsigned diff = 0;
#pragma unroll
    for (int i = 0; i < 8; i++) {
      a[i] = ld_relaxed2(stat + i * 128 + r);
      diff |= (a[i].x ^ epoch) | (a[i].y ^ epoch);
    }
    if (__all_sync(0xffffffffu, (diff & 7u) == 0)) break;
    if (++spins > kSpinLimit) __trap();
    __nanosleep(200);
  }
  float s = 0.f, q = 0.f;
#pragma unroll
  for (int i = 0; i < 8; i++) {
    s += untag_value(a[i].x);
    q += untag_value(a[i].y);
  }
  const float mean = s * (1.f / 1024.f);
  const float var = fmaxf(fmaf(-mean, mean, q * (1.f / 1024.f)), 0.f);
  reinterpret_cast<float2*>(sm + kSmStat)[r] = make_float2(rsqrtf(var + 1e-5f), -mean);
}

__device__ __forceinline__ void gather_colsums(uint8_t* sm, int part, int j, int lane, unsigned epoch) {
#pragma unroll 1
  for (int blk = 0; blk < (part < 2 ? 3 : 7); blk++) {
    const int col = part < 2 ? blk * kD + (j + 8 * part) * 64
                             : 3 * kD + 64 * (blk + (blk < 3 ? 3 * j : blk < 5 ? 21 + 2 * j : 35 + 2 * j));
    uint2 v;
    unsigned spins = 0;
    while (true) {
      v = ld_relaxed2(reinterpret_cast<const uint2*>(g_cs + col) + lane);
      if (__all_sync(0xffffffffu, (((v.x ^ epoch) | (v.y ^ epoch)) & 7u) == 0)) break;
      if (++spins > kSpinLimit) __trap();
      __nanosleep(100);
    }
    uint8_t* dst = part < 2 ? sm + kSmCsQ + (part * 96 + blk * 32 + lane) * 8 : sm + kSmV1 + (blk * 32 + lane) * 16;
    *reinterpret_cast<float2*>(dst) = make_float2(untag_value(v.x), untag_value(v.y));
  }
}

#define PF_START 0
#define PAUSE_QKV2 5
#define PAUSE_WO 3

__global__ void __cluster_dims__(2, 1, 1) __launch_bounds__(384, 1)
fused_layers_kernel(const __grid_constant__ CUtensorMap map_x, const __grid_constant__ CUtensorMap map_out,
                    const __grid_constant__ CUtensorMap map_qkv, const __grid_constant__ CUtensorMap map_wo,
                    const __grid_constant__ CUtensorMap map_w1a, const __grid_constant__ CUtensorMap map_w1b,
                    const __grid_constant__ CUtensorMap map_w2, const __grid_constant__ CUtensorMap map_csq,
                    const __grid_constant__ CUtensorMap map_cs1, const __grid_constant__ Params prm) {
  extern __shared__ __align__(1024) uint8_t sm[];
  if (threadIdx.x < 128 && blockIdx.x < kCtas) TRACE_AT(15, 1);
  const uint32_t sb = smem_u32(sm);
  const int warp = __shfl_sync(0xffffffffu, threadIdx.x >> 5, 0), lane = threadIdx.x & 31;
  const int cta = blockIdx.x, rank = cta & 1, cl = cta >> 1;
  const int grp = cl < 4 ? 0 : cl < 36 ? (cl - 4) & 7 : 1 + (cl - 36) % 7;
  const int j = cl < 4 ? 4 + cl : cl < 36 ? (cl - 4) >> 3 : 4 + (cl - 36) / 7;
  const int b = 2 * grp + rank;
  const int xcol = (b >> 3) * kD, xrow = (b & 7) * 128;

  if (cta >= kCtas) {
    helper_cta(&map_csq, &map_cs1, sm, sb, cta - kCtas, warp);
    return;
  }
  if (warp >= 8 && elect()) {
    if (warp == 9) {
#pragma unroll
      for (int s = 0; s < 8; s++) mbar_init(sb + kBarFull + s * 8, 1);
      fence_async_smem();
#pragma unroll
      for (int s = 0; s < 4; s++) {
        const uint32_t full = sb + kBarFull + s * 8, dst = sb + kSmRing + s * 40960;
        mbar_expect_tx(full, 40960);
        tma2d(dst, &map_x, full, xcol + s * 64, xrow);
        tma3d(dst + kTileBytes, &map_qkv, full, j * 64, s * 64, 0);
        tma3d(dst + kTileBytes + 12288, &map_qkv, full, j * 64, s * 64 + 32, 0);
      }
      if (PF_START & 1) l2_prefetch(reinterpret_cast<const uint8_t*>(prm.x) + cta * 32768, 32768);
      if (PF_START & 2) l2_prefetch(reinterpret_cast<const uint8_t*>(prm.wqkv) + cta * 49152, 49152);
    } else if (warp == 8) {
      if (sb & 1023) __trap();
#pragma unroll
      for (int o = kBarTurn; o < kBarInit; o += 8) mbar_init(sb + o, 1);
    } else if (warp == 10) {
#pragma unroll
      for (int o = kBarEpoch; o < kSmEpoch; o += 8) mbar_init(sb + o, o < kBarEmpty ? 1 : o < kBarEpi ? 2 : 4);
    } else {
      mbar_init(sb + kBarInit, 1);
      fence_async_smem();
      mbar_expect_tx(sb + kBarInit, 32768);
      tma2d(sb + kSmX, &map_x, sb + kBarInit, xcol + j * 128, xrow);
      tma2d(sb + kSmX + kTileBytes, &map_x, sb + kBarInit, xcol + j * 128 + 64, xrow);
    }
    asm volatile("fence.mbarrier_init.release.cluster;" ::: "memory");
  }
  __syncwarp();
  asm volatile("barrier.cluster.arrive.relaxed.aligned;" ::: "memory");

  if (warp >= 8) {
    asm volatile("setmaxnreg.dec.sync.aligned.u32 40;");
    if (warp < 10) {
      asm volatile("barrier.cluster.wait.aligned;" ::: "memory");
      int nb = 32, mb = 0, kb = 0;
      uint32_t off = 0;
#pragma unroll 1
      for (int sg = 0; sg < kSegs; sg++) {
        const uint32_t e = prm.seg[sg];
        const int ty = e & 7, mode = (e >> 15) & 3, reset = (e >> 24) & 3;
        const int nend = nb + (e & 0x1f8);
        const uint32_t step = (e >> 17) & 1 ? 40960 : 32768;
        const int depth = (e >> 18) & 1 ? 40 : 32;
        if (reset) off = reset == 1 ? 0 : reset == 2 ? 40960 : 131072;
        if (mode != kModeContinue) kb = ((e >> 9) & 63) + (mode == kModeHead ? 2 * j : 0);
        const int inc = mode >= kModeSkip ? 2 : 1, skip = mode >= kModeSkip ? j : -1;
        if (warp == 8) {
          const CUtensorMap* map = ty < 2 ? &map_qkv : ty == 2 ? &map_wo : ty == 3 ? &map_w1a : ty < 6 ? &map_w1b : &map_w2;
          const int c0 = ty < 2 ? (j + 8 * ty) * 64 : 0;
          const int c2 = ty < 2 ? 0 : ty == 3 ? 3 * j : ty == 4 ? 24 + 2 * j : ty == 5 ? 40 + 2 * j : 2 * j;
          const uint32_t half = (ty < 2 || ty == 3) ? 12288 : 8192;
          const uint32_t bytes = 2 * half + (mode == kModeHead ? 0 : kTileBytes);
          const uint32_t dst = sb + kSmRing + kTileBytes + rank * half;
#pragma unroll 1
          for (; nb < nend; nb += 8) {
            for (; mb <= nb - depth; mb += 8) mbar_wait(sb + kBarEmpty + (mb & 56), (mb >> 6) & 1);
            if (kb >> 1 == skip) kb += 2;
            if (elect()) {
              const uint32_t full = sb + kBarFull + (nb & 56);
              mbar_expect_tx(full, bytes);
              tma3d_mc(dst + off, map, full, c0, kb * 64 + rank * 32, c2);
            }
            kb += inc;
            off += step;
            if (off == 163840) off = 0;
          }
        } else if (mode == kModeHead) {
          nb = nend;
          off += 2 * step;
          if (off >= 163840) off -= 163840;
          for (; mb <= nb - 56; mb += 8) mbar_wait(sb + kBarEmpty + (mb & 56), (mb >> 6) & 1);
        } else {
          const uint8_t* src = ty == 6 ? g_h + b * 56 * kTileBytes : (ty == 2 ? g_o : g_x) + b * 16 * kTileBytes;
          const int dep = (e >> 19) & 31;
          if (dep != 31) mbar_wait(sb + kBarReady + dep * 8, 0);
#pragma unroll 1
          for (; nb < nend; nb += 8) {
            for (; mb <= nb - depth; mb += 8) mbar_wait(sb + kBarEmpty + (mb & 56), (mb >> 6) & 1);
            if (kb >> 1 == skip) kb += 2;
            const uint32_t dst = sb + kSmRing + off, full = sb + kBarFull + (nb & 56);
            if (sg < 2) {
              if (elect()) tma2d(dst, &map_x, full, xcol + kb * 64, xrow);
            } else {
              if (elect()) bulk_load(dst, src + kb * kTileBytes, kTileBytes, full);
            }
            kb += inc;
            off += step;
            if (off == 163840) off = 0;
          }
        }
      }
    } else if (warp == 10) {
      unsigned epoch = 0;
      if (lane == 0) epoch = atomicAdd(&g_ticket, 1u) / kGrid + 1;
      float* v1 = reinterpret_cast<float*>(sm + kSmV1);
#pragma unroll 1
      for (int i = lane; i < 224; i += 32) {
        const int col = i < 96 ? 96 * j + i : i < 160 ? 672 + 64 * j + i : 1120 + 64 * j + i;
        const uint32_t v = reinterpret_cast<const uint32_t*>(prm.b1)[col];
        *reinterpret_cast<float2*>(v1 + i * 4 + 2) = make_float2(0.5f * bf_lo(v), 0.5f * bf_hi(v));
      }
      {
        const uint2 v = reinterpret_cast<const uint2*>(prm.b2)[32 * j + lane];
        reinterpret_cast<float4*>(sm + kSmB2)[lane] = make_float4(bf_lo(v.x), bf_hi(v.x), bf_lo(v.y), bf_hi(v.y));
      }
      epoch = __shfl_sync(0xffffffffu, epoch, 0);
      *reinterpret_cast<unsigned*>(sm + kSmEpoch) = epoch;
      asm volatile("barrier.cluster.wait.aligned;" ::: "memory");
      if (elect()) mbar_arrive(sb + kBarEpoch);
#pragma unroll 1
      for (int i = 0; i < kTiles - 1; i++) {
        const bool xt = i == 2 || i == 6 || i == 9;
        const unsigned* line = g_flag + (i * 16 + b) * 32;
        mbar_wait(sb + kBarTurn + i * 8, 0);
        wait_flags(line + (lane & 7), epoch);
        if (elect()) mbar_arrive(sb + kBarReady + i * 8);
        if (xt) {
          wait_flags(line + 8 + (lane & 7), epoch);
          if (elect()) mbar_arrive(sb + kBarReady + (14 + (i >> 2)) * 8);
        }
      }
    } else {
      asm volatile("barrier.cluster.wait.aligned;" ::: "memory");
      mbar_wait(sb + kBarEpoch, 0);
      const unsigned epoch = *reinterpret_cast<volatile unsigned*>(sm + kSmEpoch);
#pragma unroll 1
      for (int i = 0; i < kTiles - 1; i++) {
#pragma unroll 1
        for (int part = i == 0 ? 0 : 2; part < (i == 0 ? 2 : i == 3 ? 3 : 0); part++) {
          gather_colsums(sm, part, j, lane, epoch);
          __syncwarp();
          if (elect()) mbar_arrive(sb + kBarCs + part * 8);
        }
        if (i == 2 || i == 6 || i == 9) {
#pragma unroll 1
          for (int h = 0; h < 2; h++) {
            mbar_wait(sb + kBarX + ((i >> 2) * 2 + h) * 8, 0);
            if (elect()) {
              bulk_store(g_x + (b * 16 + 2 * j + h) * kTileBytes, sb + kSmX + h * kTileBytes, kTileBytes);
              bulk_commit();
              bulk_wait();
              st_release(&g_flag[(i * 16 + b) * 32 + h * 8 + j], epoch);
            }
            __syncwarp();
          }
        } else {
          mbar_wait(sb + kBarEpi + i * 8, 0);
          if (elect()) st_release(&g_flag[(i * 16 + b) * 32 + j], epoch);
          __syncwarp();
        }
      }
    }
    __syncwarp();
    asm volatile("barrier.cluster.arrive.relaxed.aligned;\nbarrier.cluster.wait.aligned;" ::: "memory");
  } else {
    asm volatile("setmaxnreg.inc.sync.aligned.u32 232;");
    asm volatile("barrier.cluster.wait.aligned;" ::: "memory");
    const int wg = warp >> 2, w = warp & 3;
    const bool rel = (threadIdx.x & 95) == 0;
    const uint32_t rel_addr = mapa(sb + kBarEmpty, w & 1);
    if (wg == 1) TRACE_AT(15, 0);
#define EPOCH (*reinterpret_cast<volatile unsigned*>(sm + kSmEpoch))

    if (wg == 1) {
      mbar_wait(sb + kBarEpoch, 0);
      mbar_wait(sb + kBarInit, 0);
    }

#pragma unroll 1
    for (int i = wg; i < kTiles; i += 2) {
      const int layer = i >= 7, ty = i - 7 * layer;
      TRACE_AT(i, 15);
      float acc[2][96];
      if (ty == 2 || ty == 6) {
        const uint32_t xrow_addr = sb + kSmX + (32 * w + lane) * 128;
        const float2* b2 = reinterpret_cast<const float2*>(sm + kSmB2) + (lane & 3);
#pragma unroll
        for (int J = 0; J < 16; J++) {
          uint32_t r[4];
          ldsm4(xrow_addr + (J >> 3) * kTileBytes + (((J & 7) ^ (lane & 7)) << 4), r);
          float2 bias = make_float2(0.f, 0.f);
          if (ty == 6) bias = b2[J * 4];
#pragma unroll
          for (int c = 0; c < 4; c++) {
            acc[c & 1][4 * J + (c & 2)] = bf_lo(r[c]) + bias.x;
            acc[c & 1][4 * J + (c & 2) + 1] = bf_hi(r[c]) + bias.y;
            asm volatile("" : "+f"(acc[c & 1][4 * J + (c & 2)]), "+f"(acc[c & 1][4 * J + (c & 2) + 1]));
          }
          yield_slot();
        }
        mainloop<128>(acc, sb, i, layer * 152 + ty * 16, ty == 6 ? 4 : 0, ty == 6 ? 56 : 16, ty == 2 ? PAUSE_WO : -1,
                      2 * layer + 1, rel_addr, rel);
        TRACE_AT(i, 2);
#pragma unroll
        for (int h = 0; h < 2; h++) {
#pragma unroll
          for (int J = 8 * h; J < 8 * h + 8; J++)
            stsm4(xrow_addr + h * kTileBytes + (((J & 7) ^ (lane & 7)) << 4), pack2(acc[0][4 * J], acc[0][4 * J + 1]),
                  pack2(acc[1][4 * J], acc[1][4 * J + 1]), pack2(acc[0][4 * J + 2], acc[0][4 * J + 3]),
                  pack2(acc[1][4 * J + 2], acc[1][4 * J + 3]));
          fence_async_smem();
          __syncwarp();
          if (i < kTiles - 1) {
            if (elect()) mbar_arrive(sb + kBarX + ((i >> 2) * 2 + h) * 8);
          } else if (elect()) {
            tma2d_store(&map_out, sb + kSmX + h * kTileBytes + w * 4096, xcol + j * 128 + h * 64, xrow + 32 * w);
            bulk_commit();
            if (h == 1) bulk_wait_read();
          }
          yield_slot();
          TRACE_AT(i, 8 + h);
        }
      } else {
        const int xver = 2 * layer + (ty >= 3);
        const bool wide = ty < 4, split = i > 1 && ty != 5;
        zero_acc<192>(acc);
        if (split) {
          const int n0 = layer * 152 + (ty < 2 ? 2 * ty : 42 + 2 * ty), slot = ty < 2 ? 2 * ty : 2 * ty - 5;
          if (wide) head_blocks<192>(acc, sb, n0, slot, sb + kBarX + (xver - 1) * 16, rel_addr, rel);
          else head_blocks<128>(acc, sb, n0, slot, sb + kBarX + (xver - 1) * 16, rel_addr, rel);
        }
        if (ty == 1 || ty == 4) {
          uint2* stat = g_stat + (xver * 16 + b) * 1024;
          publish_stats(sb, stat + j * 128, w, lane, EPOCH);
          gather_stats(sm, stat, EPOCH);
          __syncwarp();
          if (elect()) mbar_arrive(sb + kBarStat + xver * 8);
          TRACE_AT(i, 14);
          if (i == 8) {
            mbar_wait(sb + kBarStat + xver * 8, 0);
            add_mean_term(acc, sm, 1, w, lane);
          }
        }
        const int n0 = layer * 152 + (!split ? 16 * ty : ty < 2 ? 4 + 14 * ty : 10 + 14 * ty);
        const int slot = ty < 2 ? (split ? 2 * ty : 0) : ty == 3 ? 1 : 8 - ty;
        if (wide) mainloop<192>(acc, sb, i, n0, slot, split ? 14 : 16, ty == 1 ? PAUSE_QKV2 : -1, xver, rel_addr, rel);
        else mainloop<128>(acc, sb, i, n0, slot, split ? 14 : 16, -1, 0, rel_addr, rel);
        TRACE_AT(i, 2);
        mbar_wait(sb + kBarStat + xver * 8, 0);
        mbar_wait(sb + kBarCs + (ty < 2 ? ty : 2) * 8, 0);
        if (ty != 0 && ty != 3) mbar_wait(sb + kBarEpi + (i - 1) * 8, 0);
        if (ty < 2) {
          if (i != 8) add_mean_term(acc, sm, ty, w, lane);
          epilogue_attn(acc, sm, sb, layer, ty, b, j, EPOCH, i, wg, w);
        } else {
          const int blk = ty == 3 ? 3 * j : 16 * ty - 40 + 2 * j;
          epilogue_gelu(acc, sm, sb, wide, wide ? 0 : 128 * ty - 320, g_h + (b * 56 + blk) * kTileBytes + w * 4096,
                        i, w);
        }
      }
      TRACE_AT(i, 3);
    }
#undef EPOCH
    asm volatile("barrier.cluster.arrive.relaxed.aligned;\nbarrier.cluster.wait.aligned;" ::: "memory");
    if (wg == 1) TRACE_AT(15, 2);
  }
}

void build_segments(uint32_t* seg) {
  int n = 0;
  auto add = [&](int ty, int cnt, int kb0, int mode, int wide, int depth5, int dep, int reset) {
    seg[n++] = ty | cnt << 3 | kb0 << 9 | mode << 15 | wide << 17 | depth5 << 18 | dep << 19 | reset << 24;
  };
  for (int l = 0; l < 2; l++) {
    const int t = 7 * l;
    if (l == 0) {
      add(0, 12, 4, kModePlain, 1, 0, 31, 1);
      add(1, 16, 0, kModePlain, 1, 0, 31, 0);
    } else {
      add(0, 2, 0, kModeHead, 1, 0, 31, 1);
      add(1, 2, 0, kModeHead, 1, 0, 31, 0);
      add(0, 7, 0, kModeSkip, 1, 0, 6, 0);
      add(0, 7, 1, kModeSkip, 1, 0, 15, 0);
      add(1, 7, 0, kModeSkip, 1, 0, 31, 0);
      add(1, 7, 1, kModeSkip, 1, 0, 31, 0);
    }
    add(2, 4, 0, kModePlain, 0, 0, t, 1);
    add(2, 4, 4, kModePlain, 0, 1, 31, 0);
    add(2, 8, 8, kModePlain, 0, 1, t + 1, 0);
    add(3, 2, 0, kModeHead, 1, 0, 31, 2);
    add(4, 2, 0, kModeHead, 1, 0, 31, 0);
    add(3, 7, 0, kModeSkip, 1, 0, t + 2, 0);
    add(3, 7, 1, kModeSkip, 1, 0, 14 + 2 * l, 0);
    add(4, 4, 0, kModeSkip, 0, 0, 31, 3);
    add(4, 3, 0, kModeContinue, 0, 1, 31, 0);
    add(4, 7, 1, kModeSkip, 0, 1, 31, 0);
    add(5, 16, 0, kModePlain, 0, 1, 31, 0);
    add(6, 24, 0, kModePlain, 0, 1, t + 3, 0);
    add(6, 16, 24, kModePlain, 0, 1, t + 4, 0);
    add(6, 16, 40, kModePlain, 0, 1, t + 5, 0);
  }
}

typedef CUresult (*EncodeTiledFn)(CUtensorMap*, CUtensorMapDataType, cuuint32_t, void*, const cuuint64_t*,
                                  const cuuint64_t*, const cuuint32_t*, const cuuint32_t*, CUtensorMapInterleave,
                                  CUtensorMapSwizzle, CUtensorMapL2promotion, CUtensorMapFloatOOBfill);

CUtensorMap make_map(EncodeTiledFn enc, const void* p, int rank, const cuuint64_t* dims, const cuuint64_t* strides,
                     const cuuint32_t* box, CUtensorMapSwizzle swizzle = CU_TENSOR_MAP_SWIZZLE_128B) {
  CUtensorMap m;
  const cuuint32_t es[5] = {1, 1, 1, 1, 1};
  enc(&m, CU_TENSOR_MAP_DATA_TYPE_BFLOAT16, rank, const_cast<void*>(p), dims, strides, box, es,
      CU_TENSOR_MAP_INTERLEAVE_NONE, swizzle, CU_TENSOR_MAP_L2_PROMOTION_L2_128B,
      CU_TENSOR_MAP_FLOAT_OOB_FILL_NONE);
  return m;
}

CUtensorMap weight_map(EncodeTiledFn enc, const void* p, int k, int n, int blocks) {
  const cuuint64_t dims[3] = {64, (cuuint64_t)k, (cuuint64_t)n / 64};
  const cuuint64_t strides[2] = {(cuuint64_t)n * 2, 128};
  const cuuint32_t box[3] = {64, 32, (cuuint32_t)blocks};
  return make_map(enc, p, 3, dims, strides, box);
}

CUtensorMap slab_map(EncodeTiledFn enc, const void* p, int n) {
  const cuuint64_t dims[2] = {(cuuint64_t)n, kD};
  const cuuint64_t strides[1] = {(cuuint64_t)n * 2};
  const cuuint32_t box[2] = {128, 128};
  return make_map(enc, p, 2, dims, strides, box, CU_TENSOR_MAP_SWIZZLE_NONE);
}

CUtensorMap token_map(EncodeTiledFn enc, const void* p, int rows) {
  const cuuint64_t dims[2] = {2 * kD, 1024};
  const cuuint64_t strides[1] = {4 * kD};
  const cuuint32_t box[2] = {64, (cuuint32_t)rows};
  return make_map(enc, p, 2, dims, strides, box);
}

}

extern "C" void kernel_launch(void* const* d_in, const int* in_sizes, int n_in, void* d_out, int out_size) {
  (void)in_sizes; (void)n_in; (void)out_size;
  static EncodeTiledFn enc = nullptr;
  if (!enc) {
    void* fn = nullptr;
    cudaDriverEntryPointQueryResult q;
    cudaGetDriverEntryPoint("cuTensorMapEncodeTiled", &fn, cudaEnableDefault, &q);
    enc = (EncodeTiledFn)fn;
    cudaFuncSetAttribute(fused_layers_kernel, cudaFuncAttributeMaxDynamicSharedMemorySize, kSmBytes);
  }
  Params prm;
  prm.x = (const __nv_bfloat16*)d_in[0];
  prm.wqkv = (const __nv_bfloat16*)d_in[1];
  prm.wo = (const __nv_bfloat16*)d_in[2];
  prm.w1 = (const __nv_bfloat16*)d_in[4];
  prm.b1 = (const __nv_bfloat16*)d_in[5];
  prm.w2 = (const __nv_bfloat16*)d_in[6];
  prm.b2 = (const __nv_bfloat16*)d_in[7];
  build_segments(prm.seg);
  const cuuint64_t qd[3] = {kD, kD, 3}, qs[2] = {3 * kD * 2, kD * 2};
  const cuuint32_t qb[3] = {64, 32, 3};
  const CUtensorMap map_x = token_map(enc, d_in[0], 128);
  const CUtensorMap map_out = token_map(enc, d_out, 32);
  const CUtensorMap map_qkv = make_map(enc, prm.wqkv, 3, qd, qs, qb);
  const CUtensorMap map_wo = weight_map(enc, prm.wo, kD, kD, 2);
  const CUtensorMap map_w1a = weight_map(enc, prm.w1, kD, kF, 3);
  const CUtensorMap map_w1b = weight_map(enc, prm.w1, kD, kF, 2);
  const CUtensorMap map_w2 = weight_map(enc, prm.w2, kF, kD, 2);
  fused_layers_kernel<<<kGrid, 384, kSmBytes>>>(map_x, map_out, map_qkv, map_wo, map_w1a, map_w1b, map_w2,
                                                slab_map(enc, prm.wqkv, 3 * kD), slab_map(enc, prm.w1, kF), prm);
}
```

```cpp
#include <cuda.h>
#include <cuda_bf16.h>
#include <cuda_runtime.h>
#include <stdint.h>

namespace {

constexpr int kD = 1024;
constexpr int kF = 3584;
constexpr int kCtas = 128;
constexpr int kGrid = 132;
constexpr int kTiles = 14;
constexpr int kTileBytes = 16384;

constexpr int kSmRing = 0;
constexpr int kSmX = 163840;
constexpr int kSmStg = kSmX + 32768;
constexpr int kSmHalo = kSmStg + 16384;
constexpr int kSmCsQ = kSmHalo + 6144;
constexpr int kSmV1 = kSmCsQ + 384 * 4;
constexpr int kSmB2 = kSmV1 + 448 * 8;
constexpr int kSmStat = kSmB2 + 128 * 4;
constexpr int kSmBar = kSmStat + 128 * 8;
constexpr int kBarFull = kSmBar;
constexpr int kBarTurn = kBarFull + 8 * 8;
constexpr int kBarReady = kBarTurn + 14 * 8;
constexpr int kBarPause = kBarReady + 17 * 8;
constexpr int kBarCs = kBarPause + 4 * 8;
constexpr int kBarInit = kBarCs + 3 * 8;
constexpr int kBarEpoch = kBarInit + 8;
constexpr int kBarEmpty = kBarEpoch + 8;
constexpr int kBarEpi = kBarEmpty + 9 * 8;
constexpr int kBarX = kBarEpi + 14 * 8;
constexpr int kBarStat = kBarX + 6 * 8;
constexpr int kBarResume = kBarStat + 4 * 8;
constexpr int kSmEpoch = kBarResume + 4 * 8;
constexpr int kSmBytes = kSmEpoch + 16;
constexpr int kSegs = 36;

constexpr int kFlagLines = kTiles * 16;

constexpr unsigned kSpinLimit = 1u << 24;

__device__ __align__(1024) uint8_t g_x[16 * 16 * kTileBytes];
__device__ __align__(1024) uint8_t g_o[16 * 16 * kTileBytes];
__device__ __align__(1024) uint8_t g_h[16 * 56 * kTileBytes];
__device__ __align__(128) uint2 g_stat[4 * 16 * 128 * 8];
__device__ __align__(128) unsigned g_cs[3 * kD + kF];
__device__ __align__(128) uint4 g_halo[2 * 16 * 16 * 256];
__device__ __align__(128) unsigned g_flag[kFlagLines * 32];
__device__ unsigned g_ticket;

#define TRACE_AT(tile, k)

struct Params {
  const __nv_bfloat16* x;
  const __nv_bfloat16* wqkv;
  const __nv_bfloat16* wo;
  const __nv_bfloat16* w1;
  const __nv_bfloat16* b1;
  const __nv_bfloat16* w2;
  const __nv_bfloat16* b2;
  uint32_t seg[kSegs];
};

__device__ __forceinline__ uint32_t smem_u32(const void* p) {
  return (uint32_t)__cvta_generic_to_shared(p);
}
__device__ __forceinline__ uint32_t mapa(uint32_t a, uint32_t cta) {
  uint32_t r;
  asm("mapa.shared::cluster.u32 %0, %1, %2;" : "=r"(r) : "r"(a), "r"(cta));
  return r;
}
__device__ __forceinline__ void mbar_init(uint32_t bar, int cnt) {
  asm volatile("mbarrier.init.shared::cta.b64 [%0], %1;" ::"r"(bar), "r"(cnt) : "memory");
}
__device__ __forceinline__ void mbar_expect_tx(uint32_t bar, uint32_t bytes) {
  asm volatile("mbarrier.arrive.expect_tx.shared::cta.b64 _, [%0], %1;" ::"r"(bar), "r"(bytes) : "memory");
}
__device__ __forceinline__ void mbar_arrive(uint32_t bar) {
  asm volatile("mbarrier.arrive.shared::cta.b64 _, [%0];" ::"r"(bar) : "memory");
}
__device__ __forceinline__ void mbar_arrive_cluster(uint32_t cluster_addr) {
  asm volatile("mbarrier.arrive.shared::cluster.b64 _, [%0];" ::"r"(cluster_addr) : "memory");
}
__device__ __forceinline__ void mbar_wait(uint32_t bar, uint32_t parity) {
  asm volatile(
      "{\n.reg .pred p;\n.reg .u32 c;\n"
      "mbarrier.try_wait.parity.shared::cta.b64 p, [%0], %1;\n"
      "@p bra.uni DONE;\n"
      "mov.u32 c, 0;\n"
      "RETRY:\n"
      "mbarrier.try_wait.parity.shared::cta.b64 p, [%0], %1;\n"
      "@p bra.uni DONE;\n"
      "add.u32 c, c, 1;\n"
      "setp.lt.u32 p, c, %2;\n"
      "@p bra.uni RETRY;\n"
      "trap;\n"
      "DONE:\n}" ::"r"(bar), "r"(parity), "n"(kSpinLimit)
      : "memory");
}
__device__ __forceinline__ void tma3d(uint32_t dst, const CUtensorMap* m, uint32_t bar, int c0, int c1, int c2) {
  asm volatile(
      "cp.async.bulk.tensor.3d.shared::cluster.global.mbarrier::complete_tx::bytes [%0], [%1, {%3, %4, %5}], [%2];"
      ::"r"(dst), "l"(m), "r"(bar), "r"(c0), "r"(c1), "r"(c2) : "memory");
}
__device__ __forceinline__ void tma3d_mc(uint32_t dst, const CUtensorMap* m, uint32_t bar, int c0, int c1, int c2) {
  asm volatile(
      "cp.async.bulk.tensor.3d.shared::cluster.global.mbarrier::complete_tx::bytes.multicast::cluster"
      " [%0], [%1, {%3, %4, %5}], [%2], %6;"
      ::"r"(dst), "l"(m), "r"(bar), "r"(c0), "r"(c1), "r"(c2), "h"((uint16_t)3) : "memory");
}
__device__ __forceinline__ void tma2d(uint32_t dst, const CUtensorMap* m, uint32_t bar, int c0, int c1) {
  asm volatile(
      "cp.async.bulk.tensor.2d.shared::cluster.global.mbarrier::complete_tx::bytes [%0], [%1, {%3, %4}], [%2];"
      ::"r"(dst), "l"(m), "r"(bar), "r"(c0), "r"(c1) : "memory");
}
__device__ __forceinline__ void tma2d_store(const CUtensorMap* m, uint32_t src, int c0, int c1) {
  asm volatile("cp.async.bulk.tensor.2d.global.shared::cta.bulk_group [%0, {%2, %3}], [%1];"
               ::"l"(m), "r"(src), "r"(c0), "r"(c1) : "memory");
}
__device__ __forceinline__ bool elect() {
  uint32_t p;
  asm volatile("{\n.reg .pred p;\nelect.sync _|p, 0xffffffff;\nselp.b32 %0, 1, 0, p;\n}" : "=r"(p));
  return p;
}
__device__ __forceinline__ void bulk_load(uint32_t dst, const void* src, uint32_t bytes, uint32_t bar) {
  asm volatile("cp.async.bulk.shared::cluster.global.mbarrier::complete_tx::bytes [%0], [%1], %2, [%3];"
               ::"r"(dst), "l"(src), "r"(bytes), "r"(bar) : "memory");
}
__device__ __forceinline__ void bulk_store(void* dst, uint32_t src, uint32_t bytes) {
  asm volatile("cp.async.bulk.global.shared::cta.bulk_group [%0], [%1], %2;" ::"l"(dst), "r"(src), "r"(bytes)
               : "memory");
}
__device__ __forceinline__ void bulk_commit() { asm volatile("cp.async.bulk.commit_group;" ::: "memory"); }
__device__ __forceinline__ void bulk_wait_read() { asm volatile("cp.async.bulk.wait_group.read 0;" ::: "memory"); }
__device__ __forceinline__ void bulk_wait() { asm volatile("cp.async.bulk.wait_group 0;" ::: "memory"); }
__device__ __forceinline__ void l2_prefetch(const void* p, uint32_t bytes) {
  asm volatile("cp.async.bulk.prefetch.L2.global [%0], %1;" ::"l"(p), "r"(bytes) : "memory");
}
__device__ __forceinline__ void fence_async_smem() { asm volatile("fence.proxy.async.shared::cta;" ::: "memory"); }
__device__ __forceinline__ unsigned ld_relaxed(const unsigned* p) {
  unsigned v;
  asm volatile("ld.relaxed.gpu.global.u32 %0, [%1];" : "=r"(v) : "l"(p) : "memory");
  return v;
}
__device__ __forceinline__ uint2 ld_relaxed2(const uint2* p) {
  uint2 v;
  asm volatile("ld.relaxed.gpu.global.v2.u32 {%0, %1}, [%2];" : "=r"(v.x), "=r"(v.y) : "l"(p) : "memory");
  return v;
}
__device__ __forceinline__ void st_relaxed(unsigned* p, unsigned v) {
  asm volatile("st.relaxed.gpu.global.u32 [%0], %1;" ::"l"(p), "r"(v) : "memory");
}
__device__ __forceinline__ void st_release(unsigned* p, unsigned v) {
  asm volatile("st.release.gpu.global.u32 [%0], %1;" ::"l"(p), "r"(v) : "memory");
}
#define ACQ_MODE 1
__device__ __forceinline__ void wait_flags(const unsigned* p, unsigned epoch) {
  unsigned spins = 0;
  while (true) {
    const unsigned v = ld_relaxed(p);
    if (__all_sync(0xffffffffu, v == epoch)) break;
    if (++spins > kSpinLimit) __trap();
  }
  if (ACQ_MODE) asm volatile("fence.acquire.gpu;\nfence.proxy.async.global;" ::: "memory");
  __syncwarp();
}
__device__ __forceinline__ unsigned tag_value(float v, unsigned epoch) {
  return (__float_as_uint(v) & ~7u) | (epoch & 7u);
}
__device__ __forceinline__ float untag_value(unsigned v) { return __uint_as_float(v & ~7u); }
__device__ __forceinline__ void stsm4(uint32_t a, uint32_t r0, uint32_t r1, uint32_t r2, uint32_t r3) {
  asm volatile("stmatrix.sync.aligned.m8n8.x4.shared.b16 [%0], {%1, %2, %3, %4};" ::"r"(a), "r"(r0), "r"(r1),
               "r"(r2), "r"(r3) : "memory");
}
__device__ __forceinline__ void stsm4_t(uint32_t a, uint32_t r0, uint32_t r1, uint32_t r2, uint32_t r3) {
  asm volatile("stmatrix.sync.aligned.m8n8.x4.trans.shared.b16 [%0], {%1, %2, %3, %4};" ::"r"(a), "r"(r0),
               "r"(r1), "r"(r2), "r"(r3) : "memory");
}
__device__ __forceinline__ uint32_t transpose8(uint32_t a) {
  uint32_t d;
  asm volatile("movmatrix.sync.aligned.m8n8.trans.b16 %0, %1;" : "=r"(d) : "r"(a));
  return d;
}
__device__ __forceinline__ void mma16816(float (&c)[4], uint32_t a0, uint32_t a1, uint32_t a2, uint32_t a3,
                                         uint32_t b0, uint32_t b1) {
  asm volatile("mma.sync.aligned.m16n8k16.row.col.f32.bf16.bf16.f32 {%0, %1, %2, %3}, {%4, %5, %6, %7}, {%8, %9}, "
               "{%0, %1, %2, %3};"
               : "+f"(c[0]), "+f"(c[1]), "+f"(c[2]), "+f"(c[3])
               : "r"(a0), "r"(a1), "r"(a2), "r"(a3), "r"(b0), "r"(b1));
}
__device__ __forceinline__ float shfl_xor(float v, int m) {
  float r;
  asm volatile("shfl.sync.bfly.b32 %0, %1, %2, 31, 0xffffffff;" : "=f"(r) : "f"(v), "r"(m));
  return r;
}
__device__ __forceinline__ float tanh_fast(float x) {
  float r;
  asm volatile("tanh.approx.f32 %0, %1;" : "=f"(r) : "f"(x));
  return r;
}
__device__ __forceinline__ void ldsm4(uint32_t a, uint32_t (&r)[4]) {
  asm volatile("ldmatrix.sync.aligned.m8n8.x4.shared.b16 {%0, %1, %2, %3}, [%4];"
               : "=r"(r[0]), "=r"(r[1]), "=r"(r[2]), "=r"(r[3]) : "r"(a) : "memory");
}
__device__ __forceinline__ uint32_t pack2(float lo, float hi) {
  uint32_t r;
  asm volatile("cvt.rn.bf16x2.f32 %0, %1, %2;" : "=r"(r) : "f"(hi), "f"(lo));
  return r;
}
__device__ __forceinline__ float bf_lo(uint32_t r) { return __uint_as_float(r << 16); }
__device__ __forceinline__ float bf_hi(uint32_t r) { return __uint_as_float(r & 0xffff0000u); }
__device__ __forceinline__ float ex2(float x) {
  float r;
  asm("ex2.approx.ftz.f32 %0, %1;" : "=f"(r) : "f"(x));
  return r;
}
__device__ __forceinline__ float rcp(float x) {
  float r;
  asm("rcp.approx.ftz.f32 %0, %1;" : "=f"(r) : "f"(x));
  return r;
}
template <int N>
__device__ __forceinline__ void wg_wait() {
  asm volatile("wgmma.wait_group.sync.aligned %0;" ::"n"(N) : "memory");
}
__device__ __forceinline__ void yield_slot() { asm volatile("pmevent 0;"); }
__device__ __forceinline__ void wg_bar(int wg) { asm volatile("bar.sync %0, 128;" ::"r"(wg + 1) : "memory"); }

template <int N, bool SPLIT>
__device__ __forceinline__ void mma_kblock(float (&acc)[2][96], uint32_t a, uint32_t b);

#define F8(d, i) \
  "+f"(d[i]), "+f"(d[i + 1]), "+f"(d[i + 2]), "+f"(d[i + 3]), "+f"(d[i + 4]), "+f"(d[i + 5]), "+f"(d[i + 6]), "+f"(d[i + 7])
#define KSTEP(N, A, B, oa0, oa1, ob)                                                       \
  "add.u32 t, " B ", " #ob ";\nmov.b64 db, {t, hb};\n"                                      \
  "add.u32 t, " A ", " #oa0 ";\nmov.b64 da, {t, ha};\n"                                     \
  "wgmma.mma_async.sync.aligned.m64n" #N "k16.f32.bf16.bf16 {" ACC##N##_0 "}, da, db, 1, 1, 1, 0, 1;\n" \
  "add.u32 t, " A ", " #oa1 ";\nmov.b64 da, {t, ha};\n"                                     \
  "wgmma.mma_async.sync.aligned.m64n" #N "k16.f32.bf16.bf16 {" ACC##N##_1 "}, da, db, 1, 1, 1, 0, 1;\n"

#define MMA_KBLOCK(N, SPLIT, A, B, ob2, ob3, MID)                                          \
  template <>                                                                              \
  __device__ __forceinline__ void mma_kblock<N, SPLIT>(float (&acc)[2][96], uint32_t a, uint32_t b) { \
    asm volatile("{\n.reg .b32 t, ha, hb;\n.reg .b64 da, db;\n"                            \
                 "mov.b32 ha, 0x40000080;\nmov.b32 hb, 0x40000040;\n"                       \
                 "wgmma.fence.sync.aligned;\n"                                             \
                 KSTEP(N, A, B, 0, 64, 0) KSTEP(N, A, B, 2, 66, 128) KSTEP(N, A, B, 4, 68, ob2) \
                 MID KSTEP(N, A, B, 6, 70, ob3) "wgmma.commit_group.sync.aligned;\n}\n"     \
                 : OPS##N : "r"(a), "r"(b) : "memory");                                    \
  }

#define ACC128_0 \
  "%0, %1, %2, %3, %4, %5, %6, %7, %8, %9, %10, %11, %12, %13, %14, %15, " \
  "%16, %17, %18, %19, %20, %21, %22, %23, %24, %25, %26, %27, %28, %29, %30, %31, " \
  "%32, %33, %34, %35, %36, %37, %38, %39, %40, %41, %42, %43, %44, %45, %46, %47, " \
  "%48, %49, %50, %51, %52, %53, %54, %55, %56, %57, %58, %59, %60, %61, %62, %63"
#define ACC128_1 \
  "%64, %65, %66, %67, %68, %69, %70, %71, %72, %73, %74, %75, %76, %77, %78, %79, " \
  "%80, %81, %82, %83, %84, %85, %86, %87, %88, %89, %90, %91, %92, %93, %94, %95, " \
  "%96, %97, %98, %99, %100, %101, %102, %103, %104, %105, %106, %107, %108, %109, %110, %111, " \
  "%112, %113, %114, %115, %116, %117, %118, %119, %120, %121, %122, %123, %124, %125, %126, %127"
#define OPS128 \
  F8(acc[0], 0), F8(acc[0], 8), F8(acc[0], 16), F8(acc[0], 24), F8(acc[0], 32), F8(acc[0], 40), F8(acc[0], 48), F8(acc[0], 56), \
        F8(acc[1], 0), F8(acc[1], 8), F8(acc[1], 16), F8(acc[1], 24), F8(acc[1], 32), F8(acc[1], 40), F8(acc[1], 48), F8(acc[1], 56)
MMA_KBLOCK(128, false, "%128", "%129", 512, 640, "")
MMA_KBLOCK(128, true, "%128", "%129", 512, 640, "wgmma.commit_group.sync.aligned;\n")

#define ACC192_0 \
  "%0, %1, %2, %3, %4, %5, %6, %7, %8, %9, %10, %11, %12, %13, %14, %15, " \
  "%16, %17, %18, %19, %20, %21, %22, %23, %24, %25, %26, %27, %28, %29, %30, %31, " \
  "%32, %33, %34, %35, %36, %37, %38, %39, %40, %41, %42, %43, %44, %45, %46, %47, " \
  "%48, %49, %50, %51, %52, %53, %54, %55, %56, %57, %58, %59, %60, %61, %62, %63, " \
  "%64, %65, %66, %67, %68, %69, %70, %71, %72, %73, %74, %75, %76, %77, %78, %79, " \
  "%80, %81, %82, %83, %84, %85, %86, %87, %88, %89, %90, %91, %92, %93, %94, %95"
#define ACC192_1 \
  "%96, %97, %98, %99, %100, %101, %102, %103, %104, %105, %106, %107, %108, %109, %110, %111, " \
  "%112, %113, %114, %115, %116, %117, %118, %119, %120, %121, %122, %123, %124, %125, %126, %127, " \
  "%128, %129, %130, %131, %132, %133, %134, %135, %136, %137, %138, %139, %140, %141, %142, %143, " \
  "%144, %145, %146, %147, %148, %149, %150, %151, %152, %153, %154, %155, %156, %157, %158, %159, " \
  "%160, %161, %162, %163, %164, %165, %166, %167, %168, %169, %170, %171, %172, %173, %174, %175, " \
  "%176, %177, %178, %179, %180, %181, %182, %183, %184, %185, %186, %187, %188, %189, %190, %191"
#define OPS192 \
  F8(acc[0], 0), F8(acc[0], 8), F8(acc[0], 16), F8(acc[0], 24), F8(acc[0], 32), F8(acc[0], 40), F8(acc[0], 48), F8(acc[0], 56), F8(acc[0], 64), F8(acc[0], 72), F8(acc[0], 80), F8(acc[0], 88), \
        F8(acc[1], 0), F8(acc[1], 8), F8(acc[1], 16), F8(acc[1], 24), F8(acc[1], 32), F8(acc[1], 40), F8(acc[1], 48), F8(acc[1], 56), F8(acc[1], 64), F8(acc[1], 72), F8(acc[1], 80), F8(acc[1], 88)
MMA_KBLOCK(192, false, "%192", "%193", 768, 896, "")
MMA_KBLOCK(192, true, "%192", "%193", 768, 896, "wgmma.commit_group.sync.aligned;\n")

enum { kModePlain = 0, kModeHead = 1, kModeSkip = 2, kModeContinue = 3 };

template <int N>
__device__ __forceinline__ void fence_acc(float (&acc)[2][96]) {
#pragma unroll
  for (int h = 0; h < 2; h++)
#pragma unroll
    for (int i = 0; i < N / 2; i++) asm volatile("" : "+f"(acc[h][i])::"memory");
}

template <int N>
__device__ __forceinline__ void zero_acc(float (&acc)[2][96]) {
#pragma unroll
  for (int h = 0; h < 2; h++)
#pragma unroll
    for (int i = 0; i < N / 2; i++) acc[h][i] = 0.f;
}

#define TURN_EARLY 0
constexpr uint32_t kToB = (kTileBytes >> 4) + ((4096u >> 4) << 16) - (1u << 16);

#define TRACE_KB(nb)

template <int N>
__device__ __forceinline__ void head_blocks(float (&acc)[2][96], uint32_t sb, int n0, int slot, uint32_t xbar,
                                            uint32_t rel_addr, bool rel) {
  const uint32_t ring = (((sb & 0x3FFFF) + kSmRing) >> 4) | (1u << 16);
  const uint32_t xdesc = (((sb & 0x3FFFF) + kSmX) >> 4) | (1u << 16);
  const uint32_t nb = n0 * 8;
  fence_acc<N>(acc);
  mbar_wait(xbar, 0);
  mbar_wait(sb + kBarFull + (nb & 56), (nb >> 6) & 1);
  TRACE_KB(nb);
  mma_kblock<N, false>(acc, xdesc, ring + slot * 2560 + kToB);
  mbar_wait(xbar + 8, 0);
  mbar_wait(sb + kBarFull + (nb & 56) + 8, (nb >> 6) & 1);
  TRACE_KB(nb + 8);
  mma_kblock<N, false>(acc, xdesc + (kTileBytes >> 4), ring + ((slot + 1) & 3) * 2560 + kToB);
  wg_wait<1>();
  if (rel) mbar_arrive_cluster(rel_addr + (nb & 56));
  wg_wait<0>();
  if (rel) mbar_arrive_cluster(rel_addr + (nb & 56) + 8);
  fence_acc<N>(acc);
}

template <int N>
__device__ __forceinline__ void mainloop(float (&acc)[2][96], uint32_t sb, int tile, int n0, int slot, int nkb,
                                         int pause_kk, int att, uint32_t rel_addr, bool rel) {
  constexpr uint32_t kStep = (N == 192 ? 5 : 4) * 512;
  const uint32_t ring = (((sb & 0x3FFFF) + kSmRing) >> 4) | (1u << 16);
  uint32_t st = ring + slot * kStep;
  uint32_t nb = n0 * 8, prev = 64;
  const uint32_t last = nb + 8 * (nkb - 1);
  uint32_t stop = pause_kk >= 0 ? nb + 8 * pause_kk : last;
  const bool signal = (threadIdx.x & 127) == 64;
  fence_acc<N>(acc);
  if (tile > 0) mbar_wait(sb + kBarTurn + (tile - 1) * 8, 0);
  TRACE_AT(tile, 0);
#pragma unroll 1
  while (true) {
#pragma unroll 1
    do {
      mbar_wait(sb + kBarFull + (nb & 56), (nb >> 6) & 1);
      if (nb == n0 * 8) TRACE_AT(tile, 1);
      TRACE_KB(nb);
      mma_kblock<N, false>(acc, st, st + kToB);
      wg_wait<1>();
      if (rel) mbar_arrive_cluster(rel_addr + prev);
      prev = nb & 56;
      st += kStep;
      if (st == ring + 10240) st = ring;
      nb += 8;
    } while (nb != stop);
    if (stop == last) break;
    stop = last;
    if (signal) mbar_arrive(sb + kBarPause + att * 8);
    mbar_wait(sb + kBarResume + att * 8, 0);
  }
  mbar_wait(sb + kBarFull + (nb & 56), (nb >> 6) & 1);
  TRACE_KB(nb);
  mma_kblock<N, true>(acc, st, st + kToB);
  wg_wait<2>();
  if (rel) mbar_arrive_cluster(rel_addr + prev);
  if (TURN_EARLY && signal) mbar_arrive(sb + kBarTurn + tile * 8);
  wg_wait<1>();
  if (!TURN_EARLY && signal) mbar_arrive(sb + kBarTurn + tile * 8);
  wg_wait<0>();
  if (rel) mbar_arrive_cluster(rel_addr + (nb & 56));
  fence_acc<N>(acc);
}

__device__ __forceinline__ void publish_stats(uint32_t sb, uint2* stat, int w, int lane, unsigned epoch) {
  const uint32_t row = sb + kSmX + (32 * w + lane) * 128;
  float s[4], q[4];
#pragma unroll
  for (int c = 0; c < 4; c++) s[c] = q[c] = 0.f;
  uint32_t nx[4];
  ldsm4(row + ((lane & 7) << 4), nx);
#pragma unroll 1
  for (int J = 1; J <= 16; J++) {
    const uint32_t r[4] = {nx[0], nx[1], nx[2], nx[3]};
    ldsm4(row + ((J >> 3) & 1) * kTileBytes + (((J ^ lane) & 7) << 4), nx);
#pragma unroll
    for (int c = 0; c < 4; c++) {
      const float lo = bf_lo(r[c]);
      s[c] += lo;
      q[c] = fmaf(lo, lo, q[c]);
      if (c & 1) yield_slot();
    }
#pragma unroll
    for (int c = 0; c < 4; c++) {
      const float hi = bf_hi(r[c]);
      s[c] += hi;
      q[c] = fmaf(hi, hi, q[c]);
      if (c & 1) yield_slot();
    }
  }
#pragma unroll
  for (int c = 0; c < 4; c++) {
    s[c] += shfl_xor(s[c], 1);
    q[c] += shfl_xor(q[c], 1);
    s[c] += shfl_xor(s[c], 2);
    q[c] += shfl_xor(q[c], 2);
  }
  const int t = lane & 3, g = lane >> 2;
  const float so = t == 0 ? s[0] : t == 1 ? s[1] : t == 2 ? s[2] : s[3];
  const float qo = t == 0 ? q[0] : t == 1 ? q[1] : t == 2 ? q[2] : q[3];
  asm volatile("st.relaxed.gpu.global.v2.u32 [%0], {%1, %2};" ::"l"(stat + 32 * w + 8 * t + g),
               "r"(tag_value(so, epoch)), "r"(tag_value(qo, epoch)) : "memory");
}

__device__ __forceinline__ void add_chunk(float (&a)[8], const uint4& v) {
  a[0] += bf_lo(v.x); a[1] += bf_hi(v.x);
  a[2] += bf_lo(v.y); a[3] += bf_hi(v.y);
  a[4] += bf_lo(v.z); a[5] += bf_hi(v.z);
  a[6] += bf_lo(v.w); a[7] += bf_hi(v.w);
}

__device__ __forceinline__ int helper_col(int id, int slab) {
  return slab < 6 ? (slab % 3) * kD + (slab / 3) * 512 + id * 128 : (slab - 6) * 512 + id * 128;
}
__device__ __forceinline__ void helper_cta(const CUtensorMap* map_q, const CUtensorMap* map_1, uint8_t* sm,
                                           uint32_t sb, int id, int warp) {
  constexpr int kRed = 6 * 32768, kBar = kRed + 2 * 4096;
  const int tid = threadIdx.x;
  if (warp == 8 && elect()) {
#pragma unroll
    for (int s = 0; s < 6; s++) {
      mbar_init(sb + kBar + s * 8, 1);
      mbar_init(sb + kBar + 64 + s * 8, 4);
    }
    fence_async_smem();
  }
  __syncthreads();
  if (warp == 8) {
    int slot = 0, ph = 1;
#pragma unroll 1
    for (int n = 0; n < 104; n++) {
      mbar_wait(sb + kBar + 64 + slot * 8, ph);
      if (elect()) {
        mbar_expect_tx(sb + kBar + slot * 8, 32768);
        tma2d(sb + slot * 32768, n < 48 ? map_q : map_1, sb + kBar + slot * 8, helper_col(id, n >> 3), (n & 7) * 128);
      }
      if (++slot == 6) slot = 0, ph ^= 1;
    }
  } else if (warp < 8) {
    if (tid == 0) *reinterpret_cast<unsigned*>(sm + kBar + 128) = atomicAdd(&g_ticket, 1u) / kGrid + 1;
    int slot = warp >> 2, ph = 0;
#pragma unroll 1
    for (int slab = 0; slab < 13; slab++) {
      float a[8];
#pragma unroll
      for (int e = 0; e < 8; e++) a[e] = 0.f;
#pragma unroll 1
      for (int box = 0; box < 4; box++) {
        mbar_wait(sb + kBar + slot * 8, ph);
        const uint4* p = reinterpret_cast<const uint4*>(sm + slot * 32768) + (tid & 127);
        uint4 v[16];
#pragma unroll
        for (int i = 0; i < 16; i++) v[i] = p[i * 128];
        __syncwarp();
        if (elect()) mbar_arrive(sb + kBar + 64 + slot * 8);
#pragma unroll
        for (int i = 0; i < 16; i++) add_chunk(a, v[i]);
        slot += 2;
        if (slot >= 6) slot -= 6, ph ^= 1;
      }
      float* red = reinterpret_cast<float*>(sm + kRed + (slab & 1) * 4096);
#pragma unroll
      for (int e = 0; e < 8; e++) a[e] += shfl_xor(a[e], 16);
      if ((tid & 16) == 0) {
        float4* d = reinterpret_cast<float4*>(red + warp * 128 + (tid & 15) * 8);
        d[0] = make_float4(a[0], a[1], a[2], a[3]);
        d[1] = make_float4(a[4], a[5], a[6], a[7]);
      }
      asm volatile("bar.sync 1, 256;" ::: "memory");
      if (warp < 4) {
        float t = 0.f;
#pragma unroll
        for (int q = 0; q < 8; q++) t += red[q * 128 + tid];
        st_relaxed(g_cs + (slab < 6 ? 0 : 3 * kD) + helper_col(id, slab) + tid,
                   tag_value(t, *reinterpret_cast<volatile unsigned*>(sm + kBar + 128)));
      }
    }
  }
}

constexpr float kGelu0 = 2.f * 0.7978845608028654f;
constexpr float kGelu1 = 8.f * 0.7978845608028654f * 0.044715f;

__device__ __forceinline__ void store_staged(uint8_t* dst, uint32_t stg) {
  fence_async_smem();
  __syncwarp();
  if (elect()) {
    bulk_store(dst, stg, 4096);
    bulk_commit();
  }
}

#define GY_MASK 0x3F
#define GY(k) if ((GY_MASK >> k) & 1) yield_slot()
template <int CH>
__device__ __forceinline__ void gelu_chunk(const float (&acc)[2][96], const float2 (&st)[4], const float4* vec,
                                           uint32_t stg, int lane, uint8_t* prev) {
  uint32_t pk[8][4];
  float u[3][4], z[3][4];
  float4 v = vec[CH * 32], vn = v;
#pragma unroll
  for (int s = 0; s < 18; s++) {
    const int J = CH * 8 + (s >> 1), c0 = 2 * (s & 1), cur = s % 3, p1 = (s + 2) % 3, p2 = (s + 1) % 3;
    if (s < 16) {
      if (c0 == 0 && s < 14) vn = vec[(J + 1) * 4];
#pragma unroll
      for (int e = 0; e < 4; e++) {
        const int c = c0 + (e >> 1);
        z[cur][e] = fmaf(st[c].y, e & 1 ? v.y : v.x, e & 1 ? v.w : v.z);
      }
      if (c0 == 2) v = vn;
    }
    if (s >= 1 && s < 17) z[p1][0] = tanh_fast(z[p1][0]);
    GY(0);
    if (s < 16) {
#pragma unroll
      for (int e = 0; e < 4; e++) {
        const int c = c0 + (e >> 1);
        u[cur][e] = fmaf(acc[c & 1][4 * J + c0 + (e & 1)], st[c].x, z[cur][e]);
      }
    }
    if (s >= 11) {
      const int jj = s - 11;
      stsm4(stg + lane * 128 + ((jj ^ (lane & 7)) << 4), pk[jj][0], pk[jj][1], pk[jj][2], pk[jj][3]);
    }
    GY(1);
    if (s < 16) {
#pragma unroll
      for (int e = 0; e < 4; e++) z[cur][e] = u[cur][e] * u[cur][e];
    }
    if (s >= 1 && s < 17) z[p1][1] = tanh_fast(z[p1][1]);
    GY(2);
    if (s < 16) {
#pragma unroll
      for (int e = 0; e < 4; e++) z[cur][e] = fmaf(z[cur][e], kGelu1, kGelu0);
    }
    if (s >= 1 && s < 17) z[p1][2] = tanh_fast(z[p1][2]);
    GY(3);
    if (s >= 2) {
      pk[(s - 2) >> 1][c0] = pack2(fmaf(u[p2][0], z[p2][0], u[p2][0]), fmaf(u[p2][1], z[p2][1], u[p2][1]));
      pk[(s - 2) >> 1][c0 + 1] = pack2(fmaf(u[p2][2], z[p2][2], u[p2][2]), fmaf(u[p2][3], z[p2][3], u[p2][3]));
    }
    GY(4);
    if (s < 16) {
#pragma unroll
      for (int e = 0; e < 4; e++) z[cur][e] = u[cur][e] * z[cur][e];
    }
    if (s >= 1 && s < 17) z[p1][3] = tanh_fast(z[p1][3]);
    GY(5);
    if (CH > 0 && s == 1) store_staged(prev, stg);
    if (CH > 0 && s == 10) {
      if (elect()) bulk_wait_read();
      __syncwarp();
    }
  }
  stsm4(stg + lane * 128 + ((7 ^ (lane & 7)) << 4), pk[7][0], pk[7][1], pk[7][2], pk[7][3]);
}

__device__ __forceinline__ void epilogue_gelu(const float (&acc)[2][96], uint8_t* sm, uint32_t sb, bool wide,
                                              int vcol0, uint8_t* dst, int tile, int w) {
  const int lane = threadIdx.x & 31, t = lane & 3, g = lane >> 2;
  float2 st[4];
#pragma unroll
  for (int c = 0; c < 4; c++) {
    const float2 v = reinterpret_cast<const float2*>(sm + kSmStat)[32 * w + 8 * c + g];
    st[c].x = 0.5f * v.x;
    st[c].y = st[c].x * v.y;
  }
  const float4* vec = reinterpret_cast<const float4*>(sm + kSmV1) + vcol0 / 2 + t;
  const uint32_t stg = sb + kSmStg + w * 4096;
  TRACE_AT(tile, 8);
  gelu_chunk<0>(acc, st, vec, stg, lane, dst);
  TRACE_AT(tile, 9);
  gelu_chunk<1>(acc, st, vec, stg, lane, dst);
  TRACE_AT(tile, 10);
  if (wide) gelu_chunk<2>(acc, st, vec, stg, lane, dst + kTileBytes);
  store_staged(dst + (wide ? 2 : 1) * kTileBytes, stg);
  TRACE_AT(tile, 11);
  if (elect()) {
    bulk_wait();
    TRACE_AT(tile, 12);
    mbar_arrive(sb + kBarEpi + tile * 8);
  }
  __syncwarp();
}

__device__ __forceinline__ void add_mean_term(float (&acc)[2][96], uint8_t* sm, int tq, int w, int lane) {
  const int t = lane & 3, g = lane >> 2;
  float nm[4];
#pragma unroll
  for (int c = 0; c < 4; c++) nm[c] = reinterpret_cast<const float2*>(sm + kSmStat)[32 * w + 8 * c + g].y;
  const float2* cs = reinterpret_cast<const float2*>(sm + kSmCsQ) + tq * 96 + t;
#pragma unroll
  for (int J = 0; J < 24; J++) {
    const float2 v = cs[J * 4];
#pragma unroll
    for (int c = 0; c < 4; c++) {
      acc[c & 1][4 * J + (c & 2)] = fmaf(nm[c], v.x, acc[c & 1][4 * J + (c & 2)]);
      acc[c & 1][4 * J + (c & 2) + 1] = fmaf(nm[c], v.y, acc[c & 1][4 * J + (c & 2) + 1]);
    }
    yield_slot();
  }
}

__device__ __forceinline__ void epilogue_attn(const float (&acc)[2][96], uint8_t* sm, uint32_t sb, int layer, int tq,
                                              int b, int j, unsigned epoch, int tile, int wg, int w) {
  const int lane = threadIdx.x & 31, t = lane & 3, g = lane >> 2;
  const int hp = j + 8 * tq, att = 2 * layer + tq;
  float rs[4];
#pragma unroll
  for (int c = 0; c < 4; c++) rs[c] = reinterpret_cast<const float2*>(sm + kSmStat)[32 * w + 8 * c + g].x;
  uint32_t q[4][8], k[5][8], vt[5][8];
#define SCALED(c, J) pack2(acc[(c) & 1][4 * (J) + ((c) & 2)] * rs[c], acc[(c) & 1][4 * (J) + ((c) & 2) + 1] * rs[c])
#pragma unroll
  for (int J = 0; J < 8; J++) {
    k[4][J] = SCALED(3, 8 + J);
    vt[4][J] = transpose8(SCALED(3, 16 + J));
    yield_slot();
  }
  if (w < 3) {
    uint4* hs = reinterpret_cast<uint4*>(sm + kSmHalo + w * 2048) + lane;
    hs[0] = make_uint4(k[4][0], k[4][1], k[4][2], k[4][3]);
    hs[32] = make_uint4(k[4][4], k[4][5], k[4][6], k[4][7]);
    hs[64] = make_uint4(vt[4][0], vt[4][1], vt[4][2], vt[4][3]);
    hs[96] = make_uint4(vt[4][4], vt[4][5], vt[4][6], vt[4][7]);
  } else if ((b & 7) != 7) {
    uint4* gh = g_halo + ((layer * 16 + b) * 16 + hp) * 256 + lane;
#pragma unroll
    for (int i = 0; i < 8; i++)
      asm volatile("{\n.reg .b64 x, y;\nmov.b64 x, {%1, %3};\nmov.b64 y, {%2, %3};\n"
                   "st.relaxed.gpu.global.v2.b64 [%0], {x, y};\n}" ::"l"(gh + i * 32),
                   "r"(k[4][i]), "r"(vt[4][i]), "r"(epoch) : "memory");
  }
#pragma unroll
  for (int c = 0; c < 3; c++)
#pragma unroll
    for (int J = 0; J < 8; J++) {
      k[c + 1][J] = SCALED(c, 8 + J);
      vt[c + 1][J] = transpose8(SCALED(c, 16 + J));
      yield_slot();
    }
#pragma unroll
  for (int c = 0; c < 4; c++)
#pragma unroll
    for (int J = 0; J < 8; J++) {
      q[c][J] = SCALED(c, J);
      if (J & 1) yield_slot();
    }
#undef SCALED
  TRACE_AT(tile, 8);
  wg_bar(wg);
  const bool first = w == 0 && (b & 7) == 0;
  if (w > 0) {
    const uint4* hs = reinterpret_cast<const uint4*>(sm + kSmHalo + (w - 1) * 2048) + lane;
    const uint4 a0 = hs[0], a1 = hs[32], a2 = hs[64], a3 = hs[96];
    k[0][0] = a0.x; k[0][1] = a0.y; k[0][2] = a0.z; k[0][3] = a0.w;
    k[0][4] = a1.x; k[0][5] = a1.y; k[0][6] = a1.z; k[0][7] = a1.w;
    vt[0][0] = a2.x; vt[0][1] = a2.y; vt[0][2] = a2.z; vt[0][3] = a2.w;
    vt[0][4] = a3.x; vt[0][5] = a3.y; vt[0][6] = a3.z; vt[0][7] = a3.w;
  } else if (first) {
#pragma unroll
    for (int i = 0; i < 8; i++) k[0][i] = vt[0][i] = 0u;
  } else {
    const uint4* gh = g_halo + ((layer * 16 + b - 1) * 16 + hp) * 256 + lane;
    unsigned spins = 0;
    while (true) {
      unsigned diff = 0;
#pragma unroll
      for (int i = 0; i < 8; i++) {
        unsigned t0, t1;
        asm volatile("{\n.reg .b64 x, y;\nld.relaxed.gpu.global.v2.b64 {x, y}, [%4];\n"
                     "mov.b64 {%0, %1}, x;\nmov.b64 {%2, %3}, y;\n}"
                     : "=r"(k[0][i]), "=r"(t0), "=r"(vt[0][i]), "=r"(t1) : "l"(gh + i * 32) : "memory");
        diff |= (t0 ^ epoch) | (t1 ^ epoch);
      }
      if (__all_sync(0xffffffffu, diff == 0)) break;
      if (++spins > kSpinLimit) __trap();
    }
  }
  TRACE_AT(tile, 9);
  mbar_wait(sb + kBarPause + att * 8, 0);
  TRACE_AT(tile, 10);

  float s[2][5][4];
#pragma unroll
  for (int hd = 0; hd < 2; hd++)
#pragma unroll
    for (int kg = 0; kg < 5; kg++) {
      const int ca = kg > 0 ? kg - 1 : 0, cb = kg < 4 ? kg : 3;
#pragma unroll
      for (int e = 0; e < 4; e++) s[hd][kg][e] = 0.f;
#pragma unroll
      for (int ks = 0; ks < 2; ks++) {
        const int J = 4 * hd + 2 * ks;
        mma16816(s[hd][kg], q[ca][J], q[cb][J], q[ca][J + 1], q[cb][J + 1], k[kg][J], k[kg][J + 1]);
      }
    }
  constexpr float kScale = 0.17677669529663687f * 1.4426950408889634f;
  const bool own0 = 2 * t <= g, own1 = 2 * t + 1 <= g;
  const uint32_t own_mask = (own0 ? 0xffffu : 0u) | (own1 ? 0xffff0000u : 0u);
  float o[2][4][2][4];
#pragma unroll
  for (int hd = 0; hd < 2; hd++) {
    float v0[4], v1[4], m[4];
#pragma unroll
    for (int c = 0; c < 4; c++) {
      float p0 = s[hd][c][2], p1 = s[hd][c][3];
      if (c == 0 && first) p0 = p1 = -INFINITY;
      v0[c] = own0 ? s[hd][c + 1][0] : p0;
      v1[c] = own1 ? s[hd][c + 1][1] : p1;
      m[c] = fmaxf(v0[c], v1[c]);
    }
#pragma unroll
    for (int c = 0; c < 4; c++) m[c] = fmaxf(m[c], shfl_xor(m[c], 1));
#pragma unroll
    for (int c = 0; c < 4; c++) m[c] = fmaxf(m[c], shfl_xor(m[c], 2));
#pragma unroll
    for (int c = 0; c < 4; c++) {
      const float nm = -m[c] * kScale;
      v0[c] = ex2(fmaf(v0[c], kScale, nm));
      v1[c] = ex2(fmaf(v1[c], kScale, nm));
      m[c] = v0[c] + v1[c];
    }
#pragma unroll
    for (int c = 0; c < 4; c++) m[c] += shfl_xor(m[c], 1);
#pragma unroll
    for (int c = 0; c < 4; c++) m[c] += shfl_xor(m[c], 2);
#pragma unroll
    for (int c = 0; c < 4; c++) {
      const float inv = rcp(m[c]);
      const uint32_t p = pack2(v0[c] * inv, v1[c] * inv);
#pragma unroll
      for (int ds = 0; ds < 2; ds++) {
        const int J = 4 * hd + 2 * ds;
#pragma unroll
        for (int e = 0; e < 4; e++) o[hd][c][ds][e] = 0.f;
        mma16816(o[hd][c][ds], vt[c][J], vt[c][J + 1], vt[c + 1][J], vt[c + 1][J + 1], p & ~own_mask, p & own_mask);
      }
    }
  }
  TRACE_AT(tile, 11);
  const uint32_t stg = sb + kSmStg + w * 4096;
#pragma unroll
  for (int J = 0; J < 8; J++) {
    const int hd = J >> 2, ds = (J >> 1) & 1, e = 2 * (J & 1);
    stsm4_t(stg + lane * 128 + ((J ^ (lane & 7)) << 4), pack2(o[hd][0][ds][e], o[hd][0][ds][e + 1]),
            pack2(o[hd][1][ds][e], o[hd][1][ds][e + 1]), pack2(o[hd][2][ds][e], o[hd][2][ds][e + 1]),
            pack2(o[hd][3][ds][e], o[hd][3][ds][e + 1]));
  }
  if (elect()) mbar_arrive(sb + kBarResume + att * 8);
  fence_async_smem();
  __syncwarp();
  TRACE_AT(tile, 12);
  if (elect()) {
    bulk_store(g_o + (b * 16 + hp) * kTileBytes + w * 4096, stg, 4096);
    bulk_commit();
    bulk_wait();
    TRACE_AT(tile, 13);
    mbar_arrive(sb + kBarEpi + tile * 8);
  }
  __syncwarp();
}

__device__ __forceinline__ void gather_stats(uint8_t* sm, const uint2* stat, unsigned epoch) {
  const int r = threadIdx.x & 127;
  uint2 a[8];
  unsigned spins = 0;
  while (true) {
    unsigned diff = 0;
#pragma unroll
    for (int i = 0; i < 8; i++) {
      a[i] = ld_relaxed2(stat + i * 128 + r);
      diff |= (a[i].x ^ epoch) | (a[i].y ^ epoch);
    }
    if (__all_sync(0xffffffffu, (diff & 7u) == 0)) break;
    if (++spins > kSpinLimit) __trap();
    __nanosleep(200);
  }
  float s = 0.f, q = 0.f;
#pragma unroll
  for (int i = 0; i < 8; i++) {
    s += untag_value(a[i].x);
    q += untag_value(a[i].y);
  }
  const float mean = s * (1.f / 1024.f);
  const float var = fmaxf(fmaf(-mean, mean, q * (1.f / 1024.f)), 0.f);
  reinterpret_cast<float2*>(sm + kSmStat)[r] = make_float2(rsqrtf(var + 1e-5f), -mean);
}

__device__ __forceinline__ void gather_colsums(uint8_t* sm, int part, int j, int lane, unsigned epoch) {
#pragma unroll 1
  for (int blk = 0; blk < (part < 2 ? 3 : 7); blk++) {
    const int col = part < 2 ? blk * kD + (j + 8 * part) * 64
                             : 3 * kD + 64 * (blk + (blk < 3 ? 3 * j : blk < 5 ? 21 + 2 * j : 35 + 2 * j));
    uint2 v;
    unsigned spins = 0;
    while (true) {
      v = ld_relaxed2(reinterpret_cast<const uint2*>(g_cs + col) + lane);
      if (__all_sync(0xffffffffu, (((v.x ^ epoch) | (v.y ^ epoch)) & 7u) == 0)) break;
      if (++spins > kSpinLimit) __trap();
      __nanosleep(100);
    }
    uint8_t* dst = part < 2 ? sm + kSmCsQ + (part * 96 + blk * 32 + lane) * 8 : sm + kSmV1 + (blk * 32 + lane) * 16;
    *reinterpret_cast<float2*>(dst) = make_float2(untag_value(v.x), untag_value(v.y));
  }
}

#define PF_START 0
#define PAUSE_QKV2 5
#define PAUSE_WO 3

__global__ void __cluster_dims__(2, 1, 1) __launch_bounds__(384, 1)
fused_layers_kernel(const __grid_constant__ CUtensorMap map_x, const __grid_constant__ CUtensorMap map_out,
                    const __grid_constant__ CUtensorMap map_qkv, const __grid_constant__ CUtensorMap map_wo,
                    const __grid_constant__ CUtensorMap map_w1a, const __grid_constant__ CUtensorMap map_w1b,
                    const __grid_constant__ CUtensorMap map_w2, const __grid_constant__ CUtensorMap map_csq,
                    const __grid_constant__ CUtensorMap map_cs1, const __grid_constant__ Params prm) {
  extern __shared__ __align__(1024) uint8_t sm[];
  if (threadIdx.x < 128 && blockIdx.x < kCtas) TRACE_AT(15, 1);
  const uint32_t sb = smem_u32(sm);
  const int warp = __shfl_sync(0xffffffffu, threadIdx.x >> 5, 0), lane = threadIdx.x & 31;
  const int cta = blockIdx.x, rank = cta & 1, cl = cta >> 1;
  const int grp = cl < 4 ? 0 : cl < 36 ? (cl - 4) & 7 : 1 + (cl - 36) % 7;
  const int j = cl < 4 ? 4 + cl : cl < 36 ? (cl - 4) >> 3 : 4 + (cl - 36) / 7;
  const int b = 2 * grp + rank;
  const int xcol = (b >> 3) * kD, xrow = (b & 7) * 128;

  if (cta >= kCtas) {
    helper_cta(&map_csq, &map_cs1, sm, sb, cta - kCtas, warp);
    return;
  }
  if (warp >= 8 && elect()) {
    if (warp == 9) {
#pragma unroll
      for (int s = 0; s < 8; s++) mbar_init(sb + kBarFull + s * 8, 1);
      fence_async_smem();
#pragma unroll
      for (int s = 0; s < 4; s++) {
        const uint32_t full = sb + kBarFull + s * 8, dst = sb + kSmRing + s * 40960;
        mbar_expect_tx(full, 40960);
        tma2d(dst, &map_x, full, xcol + s * 64, xrow);
        tma3d(dst + kTileBytes, &map_qkv, full, j * 64, s * 64, 0);
        tma3d(dst + kTileBytes + 12288, &map_qkv, full, j * 64, s * 64 + 32, 0);
      }
      if (PF_START & 1) l2_prefetch(reinterpret_cast<const uint8_t*>(prm.x) + cta * 32768, 32768);
      if (PF_START & 2) l2_prefetch(reinterpret_cast<const uint8_t*>(prm.wqkv) + cta * 49152, 49152);
    } else if (warp == 8) {
      if (sb & 1023) __trap();
#pragma unroll
      for (int o = kBarTurn; o < kBarInit; o += 8) mbar_init(sb + o, 1);
    } else if (warp == 10) {
#pragma unroll
      for (int o = kBarEpoch; o < kSmEpoch; o += 8) mbar_init(sb + o, o < kBarEmpty ? 1 : o < kBarEpi ? 2 : 4);
    } else {
      mbar_init(sb + kBarInit, 1);
      fence_async_smem();
      mbar_expect_tx(sb + kBarInit, 32768);
      tma2d(sb + kSmX, &map_x, sb + kBarInit, xcol + j * 128, xrow);
      tma2d(sb + kSmX + kTileBytes, &map_x, sb + kBarInit, xcol + j * 128 + 64, xrow);
    }
    asm volatile("fence.mbarrier_init.release.cluster;" ::: "memory");
  }
  __syncwarp();
  asm volatile("barrier.cluster.arrive.relaxed.aligned;" ::: "memory");

  if (warp >= 8) {
    asm volatile("setmaxnreg.dec.sync.aligned.u32 40;");
    if (warp < 10) {
      asm volatile("barrier.cluster.wait.aligned;" ::: "memory");
      int nb = 32, mb = 0, kb = 0;
      uint32_t off = 0;
#pragma unroll 1
      for (int sg = 0; sg < kSegs; sg++) {
        const uint32_t e = prm.seg[sg];
        const int ty = e & 7, mode = (e >> 15) & 3, reset = (e >> 24) & 3;
        const int nend = nb + (e & 0x1f8);
        const uint32_t step = (e >> 17) & 1 ? 40960 : 32768;
        const int depth = (e >> 18) & 1 ? 40 : 32;
        if (reset) off = reset == 1 ? 0 : reset == 2 ? 40960 : 131072;
        if (mode != kModeContinue) kb = ((e >> 9) & 63) + (mode == kModeHead ? 2 * j : 0);
        const int inc = mode >= kModeSkip ? 2 : 1, skip = mode >= kModeSkip ? j : -1;
        if (warp == 8) {
          const CUtensorMap* map = ty < 2 ? &map_qkv : ty == 2 ? &map_wo : ty == 3 ? &map_w1a : ty < 6 ? &map_w1b : &map_w2;
          const int c0 = ty < 2 ? (j + 8 * ty) * 64 : 0;
          const int c2 = ty < 2 ? 0 : ty == 3 ? 3 * j : ty == 4 ? 24 + 2 * j : ty == 5 ? 40 + 2 * j : 2 * j;
          const uint32_t half = (ty < 2 || ty == 3) ? 12288 : 8192;
          const uint32_t bytes = 2 * half + (mode == kModeHead ? 0 : kTileBytes);
          const uint32_t dst = sb + kSmRing + kTileBytes + rank * half;
#pragma unroll 1
          for (; nb < nend; nb += 8) {
            for (; mb <= nb - depth; mb += 8) mbar_wait(sb + kBarEmpty + (mb & 56), (mb >> 6) & 1);
            if (kb >> 1 == skip) kb += 2;
            if (elect()) {
              const uint32_t full = sb + kBarFull + (nb & 56);
              mbar_expect_tx(full, bytes);
              tma3d_mc(dst + off, map, full, c0, kb * 64 + rank * 32, c2);
            }
            kb += inc;
            off += step;
            if (off == 163840) off = 0;
          }
        } else if (mode == kModeHead) {
          nb = nend;
          off += 2 * step;
          if (off >= 163840) off -= 163840;
          for (; mb <= nb - 56; mb += 8) mbar_wait(sb + kBarEmpty + (mb & 56), (mb >> 6) & 1);
        } else {
          const uint8_t* src = ty == 6 ? g_h + b * 56 * kTileBytes : (ty == 2 ? g_o : g_x) + b * 16 * kTileBytes;
          const int dep = (e >> 19) & 31;
          if (dep != 31) mbar_wait(sb + kBarReady + dep * 8, 0);
#pragma unroll 1
          for (; nb < nend; nb += 8) {
            for (; mb <= nb - depth; mb += 8) mbar_wait(sb + kBarEmpty + (mb & 56), (mb >> 6) & 1);
            if (kb >> 1 == skip) kb += 2;
            const uint32_t dst = sb + kSmRing + off, full = sb + kBarFull + (nb & 56);
            if (sg < 2) {
              if (elect()) tma2d(dst, &map_x, full, xcol + kb * 64, xrow);
            } else {
              if (elect()) bulk_load(dst, src + kb * kTileBytes, kTileBytes, full);
            }
            kb += inc;
            off += step;
            if (off == 163840) off = 0;
          }
        }
      }
    } else if (warp == 10) {
      unsigned epoch = 0;
      if (lane == 0) epoch = atomicAdd(&g_ticket, 1u) / kGrid + 1;
      epoch = __shfl_sync(0xffffffffu, epoch, 0);
      *reinterpret_cast<unsigned*>(sm + kSmEpoch) = epoch;
      asm volatile("barrier.cluster.wait.aligned;" ::: "memory");
      if (elect()) mbar_arrive(sb + kBarEpoch);
#pragma unroll 1
      for (int i = 0; i < kTiles - 1; i++) {
        const bool xt = i == 2 || i == 6 || i == 9;
        const unsigned* line = g_flag + (i * 16 + b) * 32;
        mbar_wait(sb + (xt ? kBarX + (i >> 2) * 16 : kBarEpi + i * 8), 0);
        wait_flags(line + (lane & 7), epoch);
        if (elect()) mbar_arrive(sb + kBarReady + i * 8);
        if (xt) {
          wait_flags(line + 8 + (lane & 7), epoch);
          if (elect()) mbar_arrive(sb + kBarReady + (14 + (i >> 2)) * 8);
        }
      }
    } else {
      {
        uint32_t v[7];
#pragma unroll
        for (int q = 0; q < 7; q++)
          v[q] = reinterpret_cast<const uint32_t*>(prm.b1)[32 * (q + (q < 3 ? 3 * j : q < 5 ? 21 + 2 * j : 35 + 2 * j)) + lane];
        const uint2 u = reinterpret_cast<const uint2*>(prm.b2)[32 * j + lane];
#pragma unroll
        for (int q = 0; q < 7; q++)
          *reinterpret_cast<float2*>(sm + kSmV1 + (q * 32 + lane) * 16 + 8) = make_float2(0.5f * bf_lo(v[q]), 0.5f * bf_hi(v[q]));
        reinterpret_cast<float4*>(sm + kSmB2)[lane] = make_float4(bf_lo(u.x), bf_hi(u.x), bf_lo(u.y), bf_hi(u.y));
      }
      asm volatile("barrier.cluster.wait.aligned;" ::: "memory");
      mbar_wait(sb + kBarEpoch, 0);
      const unsigned epoch = *reinterpret_cast<volatile unsigned*>(sm + kSmEpoch);
#pragma unroll 1
      for (int i = 0; i < kTiles - 1; i++) {
#pragma unroll 1
        for (int part = i == 0 ? 0 : 2; part < (i == 0 ? 2 : i == 3 ? 3 : 0); part++) {
          gather_colsums(sm, part, j, lane, epoch);
          __syncwarp();
          if (elect()) mbar_arrive(sb + kBarCs + part * 8);
        }
        if (i == 2 || i == 6 || i == 9) {
#pragma unroll 1
          for (int h = 0; h < 2; h++) {
            mbar_wait(sb + kBarX + ((i >> 2) * 2 + h) * 8, 0);
            if (elect()) {
              bulk_store(g_x + (b * 16 + 2 * j + h) * kTileBytes, sb + kSmX + h * kTileBytes, kTileBytes);
              bulk_commit();
              bulk_wait();
              st_release(&g_flag[(i * 16 + b) * 32 + h * 8 + j], epoch);
            }
            __syncwarp();
          }
        } else {
          mbar_wait(sb + kBarEpi + i * 8, 0);
          if (elect()) st_release(&g_flag[(i * 16 + b) * 32 + j], epoch);
          __syncwarp();
        }
      }
    }
    __syncwarp();
    asm volatile("barrier.cluster.arrive.relaxed.aligned;\nbarrier.cluster.wait.aligned;" ::: "memory");
  } else {
    asm volatile("setmaxnreg.inc.sync.aligned.u32 232;");
    asm volatile("barrier.cluster.wait.aligned;" ::: "memory");
    const int wg = warp >> 2, w = warp & 3;
    const bool rel = (threadIdx.x & 95) == 0;
    const uint32_t rel_addr = mapa(sb + kBarEmpty, w & 1);
    if (wg == 1) TRACE_AT(15, 0);
#define EPOCH (*reinterpret_cast<volatile unsigned*>(sm + kSmEpoch))

    if (wg == 1) {
      mbar_wait(sb + kBarEpoch, 0);
      mbar_wait(sb + kBarInit, 0);
    }

#pragma unroll 1
    for (int i = wg; i < kTiles; i += 2) {
      const int layer = i >= 7, ty = i - 7 * layer;
      TRACE_AT(i, 15);
      float acc[2][96];
      if (ty == 2 || ty == 6) {
        const uint32_t xrow_addr = sb + kSmX + (32 * w + lane) * 128;
        const float2* b2 = reinterpret_cast<const float2*>(sm + kSmB2) + (lane & 3);
#pragma unroll
        for (int J = 0; J < 16; J++) {
          uint32_t r[4];
          ldsm4(xrow_addr + (J >> 3) * kTileBytes + (((J & 7) ^ (lane & 7)) << 4), r);
          float2 bias = make_float2(0.f, 0.f);
          if (ty == 6) bias = b2[J * 4];
#pragma unroll
          for (int c = 0; c < 4; c++) {
            acc[c & 1][4 * J + (c & 2)] = bf_lo(r[c]) + bias.x;
            acc[c & 1][4 * J + (c & 2) + 1] = bf_hi(r[c]) + bias.y;
            asm volatile("" : "+f"(acc[c & 1][4 * J + (c & 2)]), "+f"(acc[c & 1][4 * J + (c & 2) + 1]));
            if (c & 1) yield_slot();
          }
        }
        mainloop<128>(acc, sb, i, layer * 152 + ty * 16, ty == 6 ? 4 : 0, ty == 6 ? 56 : 16, ty == 2 ? PAUSE_WO : -1,
                      2 * layer + 1, rel_addr, rel);
        TRACE_AT(i, 2);
#pragma unroll
        for (int h = 0; h < 2; h++) {
#pragma unroll
          for (int J = 8 * h; J < 8 * h + 8; J++)
            stsm4(xrow_addr + h * kTileBytes + (((J & 7) ^ (lane & 7)) << 4), pack2(acc[0][4 * J], acc[0][4 * J + 1]),
                  pack2(acc[1][4 * J], acc[1][4 * J + 1]), pack2(acc[0][4 * J + 2], acc[0][4 * J + 3]),
                  pack2(acc[1][4 * J + 2], acc[1][4 * J + 3]));
          fence_async_smem();
          __syncwarp();
          if (i < kTiles - 1) {
            if (elect()) mbar_arrive(sb + kBarX + ((i >> 2) * 2 + h) * 8);
          } else if (elect()) {
            tma2d_store(&map_out, sb + kSmX + h * kTileBytes + w * 4096, xcol + j * 128 + h * 64, xrow + 32 * w);
            bulk_commit();
            if (h == 1) bulk_wait_read();
          }
          yield_slot();
          TRACE_AT(i, 8 + h);
        }
      } else {
        const int xver = 2 * layer + (ty >= 3);
        const bool wide = ty < 4, split = i > 1 && ty != 5;
        zero_acc<192>(acc);
        if (split) {
          const int n0 = layer * 152 + (ty < 2 ? 2 * ty : 42 + 2 * ty), slot = ty < 2 ? 2 * ty : 2 * ty - 5;
          if (wide) head_blocks<192>(acc, sb, n0, slot, sb + kBarX + (xver - 1) * 16, rel_addr, rel);
          else head_blocks<128>(acc, sb, n0, slot, sb + kBarX + (xver - 1) * 16, rel_addr, rel);
        }
        if (ty == 1 || ty == 4) {
          uint2* stat = g_stat + (xver * 16 + b) * 1024;
          publish_stats(sb, stat + j * 128, w, lane, EPOCH);
          if (ty == 4) TRACE_AT(i, 13);
          gather_stats(sm, stat, EPOCH);
          __syncwarp();
          if (elect()) mbar_arrive(sb + kBarStat + xver * 8);
          TRACE_AT(i, 14);
          if (i == 8) {
            mbar_wait(sb + kBarStat + xver * 8, 0);
            add_mean_term(acc, sm, 1, w, lane);
          }
        }
        const int n0 = layer * 152 + (!split ? 16 * ty : ty < 2 ? 4 + 14 * ty : 10 + 14 * ty);
        const int slot = ty < 2 ? (split ? 2 * ty : 0) : ty == 3 ? 1 : 8 - ty;
        if (wide) mainloop<192>(acc, sb, i, n0, slot, split ? 14 : 16, ty == 1 ? PAUSE_QKV2 : -1, xver, rel_addr, rel);
        else mainloop<128>(acc, sb, i, n0, slot, split ? 14 : 16, -1, 0, rel_addr, rel);
        TRACE_AT(i, 2);
        mbar_wait(sb + kBarStat + xver * 8, 0);
        mbar_wait(sb + kBarCs + (ty < 2 ? ty : 2) * 8, 0);
        if (ty != 0 && ty != 3) mbar_wait(sb + kBarEpi + (i - 1) * 8, 0);
        if (ty < 2) {
          if (i != 8) add_mean_term(acc, sm, ty, w, lane);
          epilogue_attn(acc, sm, sb, layer, ty, b, j, EPOCH, i, wg, w);
        } else {
          const int blk = ty == 3 ? 3 * j : 16 * ty - 40 + 2 * j;
          epilogue_gelu(acc, sm, sb, wide, wide ? 0 : 128 * ty - 320, g_h + (b * 56 + blk) * kTileBytes + w * 4096,
                        i, w);
        }
      }
      TRACE_AT(i, 3);
    }
#undef EPOCH
    asm volatile("barrier.cluster.arrive.relaxed.aligned;\nbarrier.cluster.wait.aligned;" ::: "memory");
    if (wg == 1) TRACE_AT(15, 2);
  }
}

void build_segments(uint32_t* seg) {
  int n = 0;
  auto add = [&](int ty, int cnt, int kb0, int mode, int wide, int depth5, int dep, int reset) {
    seg[n++] = ty | cnt << 3 | kb0 << 9 | mode << 15 | wide << 17 | depth5 << 18 | dep << 19 | reset << 24;
  };
  for (int l = 0; l < 2; l++) {
    const int t = 7 * l;
    if (l == 0) {
      add(0, 12, 4, kModePlain, 1, 0, 31, 1);
      add(1, 16, 0, kModePlain, 1, 0, 31, 0);
    } else {
      add(0, 2, 0, kModeHead, 1, 0, 31, 1);
      add(1, 2, 0, kModeHead, 1, 0, 31, 0);
      add(0, 7, 0, kModeSkip, 1, 0, 6, 0);
      add(0, 7, 1, kModeSkip, 1, 0, 15, 0);
      add(1, 7, 0, kModeSkip, 1, 0, 31, 0);
      add(1, 7, 1, kModeSkip, 1, 0, 31, 0);
    }
    add(2, 4, 0, kModePlain, 0, 0, t, 1);
    add(2, 4, 4, kModePlain, 0, 1, 31, 0);
    add(2, 8, 8, kModePlain, 0, 1, t + 1, 0);
    add(3, 2, 0, kModeHead, 1, 0, 31, 2);
    add(4, 2, 0, kModeHead, 1, 0, 31, 0);
    add(3, 7, 0, kModeSkip, 1, 0, t + 2, 0);
    add(3, 7, 1, kModeSkip, 1, 0, 14 + 2 * l, 0);
    add(4, 4, 0, kModeSkip, 0, 0, 31, 3);
    add(4, 3, 0, kModeContinue, 0, 1, 31, 0);
    add(4, 7, 1, kModeSkip, 0, 1, 31, 0);
    add(5, 16, 0, kModePlain, 0, 1, 31, 0);
    add(6, 24, 0, kModePlain, 0, 1, t + 3, 0);
    add(6, 16, 24, kModePlain, 0, 1, t + 4, 0);
    add(6, 16, 40, kModePlain, 0, 1, t + 5, 0);
  }
}

typedef CUresult (*EncodeTiledFn)(CUtensorMap*, CUtensorMapDataType, cuuint32_t, void*, const cuuint64_t*,
                                  const cuuint64_t*, const cuuint32_t*, const cuuint32_t*, CUtensorMapInterleave,
                                  CUtensorMapSwizzle, CUtensorMapL2promotion, CUtensorMapFloatOOBfill);

CUtensorMap make_map(EncodeTiledFn enc, const void* p, int rank, const cuuint64_t* dims, const cuuint64_t* strides,
                     const cuuint32_t* box, CUtensorMapSwizzle swizzle = CU_TENSOR_MAP_SWIZZLE_128B) {
  CUtensorMap m;
  const cuuint32_t es[5] = {1, 1, 1, 1, 1};
  enc(&m, CU_TENSOR_MAP_DATA_TYPE_BFLOAT16, rank, const_cast<void*>(p), dims, strides, box, es,
      CU_TENSOR_MAP_INTERLEAVE_NONE, swizzle, CU_TENSOR_MAP_L2_PROMOTION_L2_128B,
      CU_TENSOR_MAP_FLOAT_OOB_FILL_NONE);
  return m;
}

CUtensorMap weight_map(EncodeTiledFn enc, const void* p, int k, int n, int blocks) {
  const cuuint64_t dims[3] = {64, (cuuint64_t)k, (cuuint64_t)n / 64};
  const cuuint64_t strides[2] = {(cuuint64_t)n * 2, 128};
  const cuuint32_t box[3] = {64, 32, (cuuint32_t)blocks};
  return make_map(enc, p, 3, dims, strides, box);
}

CUtensorMap slab_map(EncodeTiledFn enc, const void* p, int n) {
  const cuuint64_t dims[2] = {(cuuint64_t)n, kD};
  const cuuint64_t strides[1] = {(cuuint64_t)n * 2};
  const cuuint32_t box[2] = {128, 128};
  return make_map(enc, p, 2, dims, strides, box, CU_TENSOR_MAP_SWIZZLE_NONE);
}

CUtensorMap token_map(EncodeTiledFn enc, const void* p, int rows) {
  const cuuint64_t dims[2] = {2 * kD, 1024};
  const cuuint64_t strides[1] = {4 * kD};
  const cuuint32_t box[2] = {64, (cuuint32_t)rows};
  return make_map(enc, p, 2, dims, strides, box);
}

}

extern "C" void kernel_launch(void* const* d_in, const int* in_sizes, int n_in, void* d_out, int out_size) {
  (void)in_sizes; (void)n_in; (void)out_size;
  static EncodeTiledFn enc = nullptr;
  if (!enc) {
    void* fn = nullptr;
    cudaDriverEntryPointQueryResult q;
    cudaGetDriverEntryPoint("cuTensorMapEncodeTiled", &fn, cudaEnableDefault, &q);
    enc = (EncodeTiledFn)fn;
    cudaFuncSetAttribute(fused_layers_kernel, cudaFuncAttributeMaxDynamicSharedMemorySize, kSmBytes);
  }
  Params prm;
  prm.x = (const __nv_bfloat16*)d_in[0];
  prm.wqkv = (const __nv_bfloat16*)d_in[1];
  prm.wo = (const __nv_bfloat16*)d_in[2];
  prm.w1 = (const __nv_bfloat16*)d_in[4];
  prm.b1 = (const __nv_bfloat16*)d_in[5];
  prm.w2 = (const __nv_bfloat16*)d_in[6];
  prm.b2 = (const __nv_bfloat16*)d_in[7];
  build_segments(prm.seg);
  const cuuint64_t qd[3] = {kD, kD, 3}, qs[2] = {3 * kD * 2, kD * 2};
  const cuuint32_t qb[3] = {64, 32, 3};
  const CUtensorMap map_x = token_map(enc, d_in[0], 128);
  const CUtensorMap map_out = token_map(enc, d_out, 32);
  const CUtensorMap map_qkv = make_map(enc, prm.wqkv, 3, qd, qs, qb);
  const CUtensorMap map_wo = weight_map(enc, prm.wo, kD, kD, 2);
  const CUtensorMap map_w1a = weight_map(enc, prm.w1, kD, kF, 3);
  const CUtensorMap map_w1b = weight_map(enc, prm.w1, kD, kF, 2);
  const CUtensorMap map_w2 = weight_map(enc, prm.w2, kF, kD, 2);
  fused_layers_kernel<<<kGrid, 384, kSmBytes>>>(map_x, map_out, map_qkv, map_wo, map_w1a, map_w1b, map_w2,
                                                slab_map(enc, prm.wqkv, 3 * kD), slab_map(enc, prm.w1, kF), prm);
}
```

```cpp
#include <cuda.h>
#include <cuda_bf16.h>
#include <cuda_runtime.h>
#include <stdint.h>

namespace {

constexpr int kD = 1024;
constexpr int kF = 3584;
constexpr int kCtas = 128;
constexpr int kGrid = 132;
constexpr int kTiles = 14;
constexpr int kTileBytes = 16384;

constexpr int kSmRing = 0;
constexpr int kSmX = 163840;
constexpr int kSmStg = kSmX + 32768;
constexpr int kSmHalo = kSmStg + 16384;
constexpr int kSmCsQ = kSmHalo + 6144;
constexpr int kSmV1 = kSmCsQ + 384 * 4;
constexpr int kSmB2 = kSmV1 + 448 * 8;
constexpr int kSmStat = kSmB2 + 128 * 4;
constexpr int kSmBar = kSmStat + 128 * 8;
constexpr int kBarFull = kSmBar;
constexpr int kBarTurn = kBarFull + 8 * 8;
constexpr int kBarReady = kBarTurn + 14 * 8;
constexpr int kBarPause = kBarReady + 17 * 8;
constexpr int kBarCs = kBarPause + 4 * 8;
constexpr int kBarInit = kBarCs + 6 * 8;
constexpr int kBarEpoch = kBarInit + 8;
constexpr int kBarEmpty = kBarEpoch + 8;
constexpr int kBarEpi = kBarEmpty + 9 * 8;
constexpr int kBarX = kBarEpi + 14 * 8;
constexpr int kBarStat = kBarX + 6 * 8;
constexpr int kBarResume = kBarStat + 4 * 8;
constexpr int kSmEpoch = kBarResume + 4 * 8;
constexpr int kSmBytes = kSmEpoch + 16;
constexpr int kSegs = 36;

constexpr int kFlagLines = kTiles * 16;

constexpr unsigned kSpinLimit = 1u << 24;

__device__ __align__(1024) uint8_t g_x[16 * 16 * kTileBytes];
__device__ __align__(1024) uint8_t g_o[16 * 16 * kTileBytes];
__device__ __align__(1024) uint8_t g_h[16 * 56 * kTileBytes];
__device__ __align__(128) uint2 g_stat[4 * 16 * 128 * 8];
__device__ __align__(128) unsigned g_cs[3 * kD + kF];
__device__ __align__(128) uint4 g_halo[2 * 16 * 16 * 256];
__device__ __align__(128) unsigned g_flag[kFlagLines * 32];
__device__ unsigned g_ticket;

#define TRACE_AT(tile, k)
#define TRACE_PUB(i, k, c)

struct Params {
  const __nv_bfloat16* x;
  const __nv_bfloat16* wqkv;
  const __nv_bfloat16* wo;
  const __nv_bfloat16* w1;
  const __nv_bfloat16* b1;
  const __nv_bfloat16* w2;
  const __nv_bfloat16* b2;
  uint32_t seg[kSegs];
};

__device__ __forceinline__ uint32_t smem_u32(const void* p) {
  return (uint32_t)__cvta_generic_to_shared(p);
}
__device__ __forceinline__ uint32_t mapa(uint32_t a, uint32_t cta) {
  uint32_t r;
  asm("mapa.shared::cluster.u32 %0, %1, %2;" : "=r"(r) : "r"(a), "r"(cta));
  return r;
}
__device__ __forceinline__ void mbar_init(uint32_t bar, int cnt) {
  asm volatile("mbarrier.init.shared::cta.b64 [%0], %1;" ::"r"(bar), "r"(cnt) : "memory");
}
__device__ __forceinline__ void mbar_expect_tx(uint32_t bar, uint32_t bytes) {
  asm volatile("mbarrier.arrive.expect_tx.shared::cta.b64 _, [%0], %1;" ::"r"(bar), "r"(bytes) : "memory");
}
__device__ __forceinline__ void mbar_arrive(uint32_t bar) {
  asm volatile("mbarrier.arrive.shared::cta.b64 _, [%0];" ::"r"(bar) : "memory");
}
__device__ __forceinline__ void mbar_arrive_cluster(uint32_t cluster_addr) {
  asm volatile("mbarrier.arrive.shared::cluster.b64 _, [%0];" ::"r"(cluster_addr) : "memory");
}
__device__ __forceinline__ void mbar_wait(uint32_t bar, uint32_t parity) {
  asm volatile(
      "{\n.reg .pred p;\n.reg .u32 c;\n"
      "mbarrier.try_wait.parity.shared::cta.b64 p, [%0], %1;\n"
      "@p bra.uni DONE;\n"
      "mov.u32 c, 0;\n"
      "RETRY:\n"
      "mbarrier.try_wait.parity.shared::cta.b64 p, [%0], %1;\n"
      "@p bra.uni DONE;\n"
      "add.u32 c, c, 1;\n"
      "setp.lt.u32 p, c, %2;\n"
      "@p bra.uni RETRY;\n"
      "trap;\n"
      "DONE:\n}" ::"r"(bar), "r"(parity), "n"(kSpinLimit)
      : "memory");
}
__device__ __forceinline__ void tma3d(uint32_t dst, const CUtensorMap* m, uint32_t bar, int c0, int c1, int c2) {
  asm volatile(
      "cp.async.bulk.tensor.3d.shared::cluster.global.mbarrier::complete_tx::bytes [%0], [%1, {%3, %4, %5}], [%2];"
      ::"r"(dst), "l"(m), "r"(bar), "r"(c0), "r"(c1), "r"(c2) : "memory");
}
__device__ __forceinline__ void tma3d_mc(uint32_t dst, const CUtensorMap* m, uint32_t bar, int c0, int c1, int c2) {
  asm volatile(
      "cp.async.bulk.tensor.3d.shared::cluster.global.mbarrier::complete_tx::bytes.multicast::cluster"
      " [%0], [%1, {%3, %4, %5}], [%2], %6;"
      ::"r"(dst), "l"(m), "r"(bar), "r"(c0), "r"(c1), "r"(c2), "h"((uint16_t)3) : "memory");
}
__device__ __forceinline__ void tma2d(uint32_t dst, const CUtensorMap* m, uint32_t bar, int c0, int c1) {
  asm volatile(
      "cp.async.bulk.tensor.2d.shared::cluster.global.mbarrier::complete_tx::bytes [%0], [%1, {%3, %4}], [%2];"
      ::"r"(dst), "l"(m), "r"(bar), "r"(c0), "r"(c1) : "memory");
}
__device__ __forceinline__ void tma2d_store(const CUtensorMap* m, uint32_t src, int c0, int c1) {
  asm volatile("cp.async.bulk.tensor.2d.global.shared::cta.bulk_group [%0, {%2, %3}], [%1];"
               ::"l"(m), "r"(src), "r"(c0), "r"(c1) : "memory");
}
__device__ __forceinline__ bool elect() {
  uint32_t p;
  asm volatile("{\n.reg .pred p;\nelect.sync _|p, 0xffffffff;\nselp.b32 %0, 1, 0, p;\n}" : "=r"(p));
  return p;
}
__device__ __forceinline__ void bulk_load(uint32_t dst, const void* src, uint32_t bytes, uint32_t bar) {
  asm volatile("cp.async.bulk.shared::cluster.global.mbarrier::complete_tx::bytes [%0], [%1], %2, [%3];"
               ::"r"(dst), "l"(src), "r"(bytes), "r"(bar) : "memory");
}
__device__ __forceinline__ void bulk_store(void* dst, uint32_t src, uint32_t bytes) {
  asm volatile("cp.async.bulk.global.shared::cta.bulk_group [%0], [%1], %2;" ::"l"(dst), "r"(src), "r"(bytes)
               : "memory");
}
__device__ __forceinline__ void bulk_commit() { asm volatile("cp.async.bulk.commit_group;" ::: "memory"); }
__device__ __forceinline__ void bulk_wait_read() { asm volatile("cp.async.bulk.wait_group.read 0;" ::: "memory"); }
__device__ __forceinline__ void bulk_wait() { asm volatile("cp.async.bulk.wait_group 0;" ::: "memory"); }
__device__ __forceinline__ void l2_prefetch(const void* p, uint32_t bytes) {
  asm volatile("cp.async.bulk.prefetch.L2.global [%0], %1;" ::"l"(p), "r"(bytes) : "memory");
}
__device__ __forceinline__ void fence_async_smem() { asm volatile("fence.proxy.async.shared::cta;" ::: "memory"); }
__device__ __forceinline__ unsigned ld_relaxed(const unsigned* p) {
  unsigned v;
  asm volatile("ld.relaxed.gpu.global.u32 %0, [%1];" : "=r"(v) : "l"(p) : "memory");
  return v;
}
__device__ __forceinline__ uint2 ld_relaxed2(const uint2* p) {
  uint2 v;
  asm volatile("ld.relaxed.gpu.global.v2.u32 {%0, %1}, [%2];" : "=r"(v.x), "=r"(v.y) : "l"(p) : "memory");
  return v;
}
__device__ __forceinline__ void st_relaxed(unsigned* p, unsigned v) {
  asm volatile("st.relaxed.gpu.global.u32 [%0], %1;" ::"l"(p), "r"(v) : "memory");
}
__device__ __forceinline__ void st_release(unsigned* p, unsigned v) {
  asm volatile("st.release.gpu.global.u32 [%0], %1;" ::"l"(p), "r"(v) : "memory");
}
#define ACQ_MODE 1
__device__ __forceinline__ void wait_flags(const unsigned* p, unsigned epoch) {
  unsigned spins = 0;
  while (true) {
    const unsigned v = ld_relaxed(p);
    if (__all_sync(0xffffffffu, v == epoch)) break;
    if (++spins > kSpinLimit) __trap();
  }
  if (ACQ_MODE) asm volatile("fence.acquire.gpu;\nfence.proxy.async.global;" ::: "memory");
  __syncwarp();
}
__device__ __forceinline__ unsigned tag_value(float v, unsigned epoch) {
  return (__float_as_uint(v) & ~7u) | (epoch & 7u);
}
__device__ __forceinline__ float untag_value(unsigned v) { return __uint_as_float(v & ~7u); }
__device__ __forceinline__ void stsm4(uint32_t a, uint32_t r0, uint32_t r1, uint32_t r2, uint32_t r3) {
  asm volatile("stmatrix.sync.aligned.m8n8.x4.shared.b16 [%0], {%1, %2, %3, %4};" ::"r"(a), "r"(r0), "r"(r1),
               "r"(r2), "r"(r3) : "memory");
}
__device__ __forceinline__ void stsm4_t(uint32_t a, uint32_t r0, uint32_t r1, uint32_t r2, uint32_t r3) {
  asm volatile("stmatrix.sync.aligned.m8n8.x4.trans.shared.b16 [%0], {%1, %2, %3, %4};" ::"r"(a), "r"(r0),
               "r"(r1), "r"(r2), "r"(r3) : "memory");
}
__device__ __forceinline__ uint32_t transpose8(uint32_t a) {
  uint32_t d;
  asm volatile("movmatrix.sync.aligned.m8n8.trans.b16 %0, %1;" : "=r"(d) : "r"(a));
  return d;
}
__device__ __forceinline__ void mma16816(float (&c)[4], uint32_t a0, uint32_t a1, uint32_t a2, uint32_t a3,
                                         uint32_t b0, uint32_t b1) {
  asm volatile("mma.sync.aligned.m16n8k16.row.col.f32.bf16.bf16.f32 {%0, %1, %2, %3}, {%4, %5, %6, %7}, {%8, %9}, "
               "{%0, %1, %2, %3};"
               : "+f"(c[0]), "+f"(c[1]), "+f"(c[2]), "+f"(c[3])
               : "r"(a0), "r"(a1), "r"(a2), "r"(a3), "r"(b0), "r"(b1));
}
__device__ __forceinline__ float shfl_xor(float v, int m) {
  float r;
  asm volatile("shfl.sync.bfly.b32 %0, %1, %2, 31, 0xffffffff;" : "=f"(r) : "f"(v), "r"(m));
  return r;
}
__device__ __forceinline__ float tanh_fast(float x) {
  float r;
  asm volatile("tanh.approx.f32 %0, %1;" : "=f"(r) : "f"(x));
  return r;
}
__device__ __forceinline__ void ldsm4(uint32_t a, uint32_t (&r)[4]) {
  asm volatile("ldmatrix.sync.aligned.m8n8.x4.shared.b16 {%0, %1, %2, %3}, [%4];"
               : "=r"(r[0]), "=r"(r[1]), "=r"(r[2]), "=r"(r[3]) : "r"(a) : "memory");
}
__device__ __forceinline__ uint32_t pack2(float lo, float hi) {
  uint32_t r;
  asm volatile("cvt.rn.bf16x2.f32 %0, %1, %2;" : "=r"(r) : "f"(hi), "f"(lo));
  return r;
}
__device__ __forceinline__ float bf_lo(uint32_t r) { return __uint_as_float(r << 16); }
__device__ __forceinline__ float bf_hi(uint32_t r) { return __uint_as_float(r & 0xffff0000u); }
__device__ __forceinline__ float ex2(float x) {
  float r;
  asm("ex2.approx.ftz.f32 %0, %1;" : "=f"(r) : "f"(x));
  return r;
}
__device__ __forceinline__ float rcp(float x) {
  float r;
  asm("rcp.approx.ftz.f32 %0, %1;" : "=f"(r) : "f"(x));
  return r;
}
template <int N>
__device__ __forceinline__ void wg_wait() {
  asm volatile("wgmma.wait_group.sync.aligned %0;" ::"n"(N) : "memory");
}
__device__ __forceinline__ void yield_slot() { asm volatile("pmevent 0;"); }
__device__ __forceinline__ void wg_bar(int wg) { asm volatile("bar.sync %0, 128;" ::"r"(wg + 1) : "memory"); }

template <int N, bool SPLIT>
__device__ __forceinline__ void mma_kblock(float (&acc)[2][96], uint32_t a, uint32_t b);

#define F8(d, i) \
  "+f"(d[i]), "+f"(d[i + 1]), "+f"(d[i + 2]), "+f"(d[i + 3]), "+f"(d[i + 4]), "+f"(d[i + 5]), "+f"(d[i + 6]), "+f"(d[i + 7])
#define KSTEP(N, A, B, oa0, oa1, ob)                                                       \
  "add.u32 t, " B ", " #ob ";\nmov.b64 db, {t, hb};\n"                                      \
  "add.u32 t, " A ", " #oa0 ";\nmov.b64 da, {t, ha};\n"                                     \
  "wgmma.mma_async.sync.aligned.m64n" #N "k16.f32.bf16.bf16 {" ACC##N##_0 "}, da, db, 1, 1, 1, 0, 1;\n" \
  "add.u32 t, " A ", " #oa1 ";\nmov.b64 da, {t, ha};\n"                                     \
  "wgmma.mma_async.sync.aligned.m64n" #N "k16.f32.bf16.bf16 {" ACC##N##_1 "}, da, db, 1, 1, 1, 0, 1;\n"

#define MMA_KBLOCK(N, SPLIT, A, B, ob2, ob3, MID)                                          \
  template <>                                                                              \
  __device__ __forceinline__ void mma_kblock<N, SPLIT>(float (&acc)[2][96], uint32_t a, uint32_t b) { \
    asm volatile("{\n.reg .b32 t, ha, hb;\n.reg .b64 da, db;\n"                            \
                 "mov.b32 ha, 0x40000080;\nmov.b32 hb, 0x40000040;\n"                       \
                 "wgmma.fence.sync.aligned;\n"                                             \
                 KSTEP(N, A, B, 0, 64, 0) KSTEP(N, A, B, 2, 66, 128) KSTEP(N, A, B, 4, 68, ob2) \
                 MID KSTEP(N, A, B, 6, 70, ob3) "wgmma.commit_group.sync.aligned;\n}\n"     \
                 : OPS##N : "r"(a), "r"(b) : "memory");                                    \
  }

#define ACC128_0 \
  "%0, %1, %2, %3, %4, %5, %6, %7, %8, %9, %10, %11, %12, %13, %14, %15, " \
  "%16, %17, %18, %19, %20, %21, %22, %23, %24, %25, %26, %27, %28, %29, %30, %31, " \
  "%32, %33, %34, %35, %36, %37, %38, %39, %40, %41, %42, %43, %44, %45, %46, %47, " \
  "%48, %49, %50, %51, %52, %53, %54, %55, %56, %57, %58, %59, %60, %61, %62, %63"
#define ACC128_1 \
  "%64, %65, %66, %67, %68, %69, %70, %71, %72, %73, %74, %75, %76, %77, %78, %79, " \
  "%80, %81, %82, %83, %84, %85, %86, %87, %88, %89, %90, %91, %92, %93, %94, %95, " \
  "%96, %97, %98, %99, %100, %101, %102, %103, %104, %105, %106, %107, %108, %109, %110, %111, " \
  "%112, %113, %114, %115, %116, %117, %118, %119, %120, %121, %122, %123, %124, %125, %126, %127"
#define OPS128 \
  F8(acc[0], 0), F8(acc[0], 8), F8(acc[0], 16), F8(acc[0], 24), F8(acc[0], 32), F8(acc[0], 40), F8(acc[0], 48), F8(acc[0], 56), \
        F8(acc[1], 0), F8(acc[1], 8), F8(acc[1], 16), F8(acc[1], 24), F8(acc[1], 32), F8(acc[1], 40), F8(acc[1], 48), F8(acc[1], 56)
MMA_KBLOCK(128, false, "%128", "%129", 512, 640, "")
MMA_KBLOCK(128, true, "%128", "%129", 512, 640, "wgmma.commit_group.sync.aligned;\n")

#define ACC192_0 \
  "%0, %1, %2, %3, %4, %5, %6, %7, %8, %9, %10, %11, %12, %13, %14, %15, " \
  "%16, %17, %18, %19, %20, %21, %22, %23, %24, %25, %26, %27, %28, %29, %30, %31, " \
  "%32, %33, %34, %35, %36, %37, %38, %39, %40, %41, %42, %43, %44, %45, %46, %47, " \
  "%48, %49, %50, %51, %52, %53, %54, %55, %56, %57, %58, %59, %60, %61, %62, %63, " \
  "%64, %65, %66, %67, %68, %69, %70, %71, %72, %73, %74, %75, %76, %77, %78, %79, " \
  "%80, %81, %82, %83, %84, %85, %86, %87, %88, %89, %90, %91, %92, %93, %94, %95"
#define ACC192_1 \
  "%96, %97, %98, %99, %100, %101, %102, %103, %104, %105, %106, %107, %108, %109, %110, %111, " \
  "%112, %113, %114, %115, %116, %117, %118, %119, %120, %121, %122, %123, %124, %125, %126, %127, " \
  "%128, %129, %130, %131, %132, %133, %134, %135, %136, %137, %138, %139, %140, %141, %142, %143, " \
  "%144, %145, %146, %147, %148, %149, %150, %151, %152, %153, %154, %155, %156, %157, %158, %159, " \
  "%160, %161, %162, %163, %164, %165, %166, %167, %168, %169, %170, %171, %172, %173, %174, %175, " \
  "%176, %177, %178, %179, %180, %181, %182, %183, %184, %185, %186, %187, %188, %189, %190, %191"
#define OPS192 \
  F8(acc[0], 0), F8(acc[0], 8), F8(acc[0], 16), F8(acc[0], 24), F8(acc[0], 32), F8(acc[0], 40), F8(acc[0], 48), F8(acc[0], 56), F8(acc[0], 64), F8(acc[0], 72), F8(acc[0], 80), F8(acc[0], 88), \
        F8(acc[1], 0), F8(acc[1], 8), F8(acc[1], 16), F8(acc[1], 24), F8(acc[1], 32), F8(acc[1], 40), F8(acc[1], 48), F8(acc[1], 56), F8(acc[1], 64), F8(acc[1], 72), F8(acc[1], 80), F8(acc[1], 88)
MMA_KBLOCK(192, false, "%192", "%193", 768, 896, "")
MMA_KBLOCK(192, true, "%192", "%193", 768, 896, "wgmma.commit_group.sync.aligned;\n")

enum { kModePlain = 0, kModeHead = 1, kModeSkip = 2, kModeContinue = 3 };

template <int N>
__device__ __forceinline__ void fence_acc(float (&acc)[2][96]) {
#pragma unroll
  for (int h = 0; h < 2; h++)
#pragma unroll
    for (int i = 0; i < N / 2; i++) asm volatile("" : "+f"(acc[h][i])::"memory");
}

template <int N>
__device__ __forceinline__ void zero_acc(float (&acc)[2][96]) {
#pragma unroll
  for (int h = 0; h < 2; h++)
#pragma unroll
    for (int i = 0; i < N / 2; i++) acc[h][i] = 0.f;
}

constexpr uint32_t kToB = (kTileBytes >> 4) + ((4096u >> 4) << 16) - (1u << 16);

#define TRACE_KB(nb)

template <int N>
__device__ __forceinline__ void head_blocks(float (&acc)[2][96], uint32_t sb, int n0, int slot, uint32_t xbar,
                                            uint32_t rel_addr, bool rel) {
  const uint32_t ring = (((sb & 0x3FFFF) + kSmRing) >> 4) | (1u << 16);
  const uint32_t xdesc = (((sb & 0x3FFFF) + kSmX) >> 4) | (1u << 16);
  const uint32_t nb = n0 * 8;
  fence_acc<N>(acc);
  mbar_wait(xbar, 0);
  mbar_wait(sb + kBarFull + (nb & 56), (nb >> 6) & 1);
  TRACE_KB(nb);
  mma_kblock<N, false>(acc, xdesc, ring + slot * 2560 + kToB);
  mbar_wait(xbar + 8, 0);
  mbar_wait(sb + kBarFull + (nb & 56) + 8, (nb >> 6) & 1);
  TRACE_KB(nb + 8);
  mma_kblock<N, false>(acc, xdesc + (kTileBytes >> 4), ring + ((slot + 1) & 3) * 2560 + kToB);
  wg_wait<1>();
  if (rel) mbar_arrive_cluster(rel_addr + (nb & 56));
  wg_wait<0>();
  if (rel) mbar_arrive_cluster(rel_addr + (nb & 56) + 8);
  fence_acc<N>(acc);
}

template <int N, class Pre>
__device__ __forceinline__ void mainloop(float (&acc)[2][96], uint32_t sb, int tile, int n0, int slot, int nkb,
                                         int pause_kk, int att, uint32_t rel_addr, bool rel, Pre pre) {
  constexpr uint32_t kStep = (N == 192 ? 5 : 4) * 512;
  const uint32_t ring = (((sb & 0x3FFFF) + kSmRing) >> 4) | (1u << 16);
  uint32_t st = ring + slot * kStep;
  uint32_t nb = n0 * 8, prev = 64;
  const uint32_t last = nb + 8 * (nkb - 1);
  uint32_t stop = pause_kk >= 0 ? nb + 8 * pause_kk : last;
  const bool signal = (threadIdx.x & 127) == 64;
  fence_acc<N>(acc);
  if (tile > 0) mbar_wait(sb + kBarTurn + (tile - 1) * 8, 0);
  TRACE_AT(tile, 0);
#pragma unroll 1
  while (true) {
#pragma unroll 1
    do {
      mbar_wait(sb + kBarFull + (nb & 56), (nb >> 6) & 1);
      if (nb == n0 * 8) TRACE_AT(tile, 1);
      TRACE_KB(nb);
      mma_kblock<N, false>(acc, st, st + kToB);
      wg_wait<1>();
      if (rel) mbar_arrive_cluster(rel_addr + prev);
      prev = nb & 56;
      st += kStep;
      if (st == ring + 10240) st = ring;
      nb += 8;
    } while (nb != stop);
    if (stop == last) break;
    stop = last;
    if (signal) mbar_arrive(sb + kBarPause + att * 8);
    wg_wait<0>();
    if (rel) mbar_arrive_cluster(rel_addr + prev);
    prev = 64;
    mbar_wait(sb + kBarResume + att * 8, 0);
  }
  mbar_wait(sb + kBarFull + (nb & 56), (nb >> 6) & 1);
  TRACE_KB(nb);
  mma_kblock<N, true>(acc, st, st + kToB);
  wg_wait<2>();
  if (rel) mbar_arrive_cluster(rel_addr + prev);
  pre();
  wg_wait<1>();
  if (signal) mbar_arrive(sb + kBarTurn + tile * 8);
  wg_wait<0>();
  if (rel) mbar_arrive_cluster(rel_addr + (nb & 56));
  fence_acc<N>(acc);
}

__device__ __forceinline__ void publish_stats(uint32_t sb, uint2* stat, int w, int lane, unsigned epoch) {
  const uint32_t row = sb + kSmX + (32 * w + lane) * 128;
  float s[4], q[4];
#pragma unroll
  for (int c = 0; c < 4; c++) s[c] = q[c] = 0.f;
  uint32_t nx[4];
  ldsm4(row + ((lane & 7) << 4), nx);
#pragma unroll 1
  for (int J = 1; J <= 16; J++) {
    const uint32_t r[4] = {nx[0], nx[1], nx[2], nx[3]};
    ldsm4(row + ((J >> 3) & 1) * kTileBytes + (((J ^ lane) & 7) << 4), nx);
#pragma unroll
    for (int c = 0; c < 4; c++) {
      const float lo = bf_lo(r[c]);
      s[c] += lo;
      q[c] = fmaf(lo, lo, q[c]);
      if (c & 1) yield_slot();
    }
#pragma unroll
    for (int c = 0; c < 4; c++) {
      const float hi = bf_hi(r[c]);
      s[c] += hi;
      q[c] = fmaf(hi, hi, q[c]);
      if (c & 1) yield_slot();
    }
  }
#pragma unroll
  for (int c = 0; c < 4; c++) {
    s[c] += shfl_xor(s[c], 1);
    q[c] += shfl_xor(q[c], 1);
    s[c] += shfl_xor(s[c], 2);
    q[c] += shfl_xor(q[c], 2);
  }
  const int t = lane & 3, g = lane >> 2;
  const float so = t == 0 ? s[0] : t == 1 ? s[1] : t == 2 ? s[2] : s[3];
  const float qo = t == 0 ? q[0] : t == 1 ? q[1] : t == 2 ? q[2] : q[3];
  asm volatile("st.relaxed.gpu.global.v2.u32 [%0], {%1, %2};" ::"l"(stat + 32 * w + 8 * t + g),
               "r"(tag_value(so, epoch)), "r"(tag_value(qo, epoch)) : "memory");
}

__device__ __forceinline__ void add_chunk(float (&a)[8], const uint4& v) {
  a[0] += bf_lo(v.x); a[1] += bf_hi(v.x);
  a[2] += bf_lo(v.y); a[3] += bf_hi(v.y);
  a[4] += bf_lo(v.z); a[5] += bf_hi(v.z);
  a[6] += bf_lo(v.w); a[7] += bf_hi(v.w);
}

__device__ __forceinline__ int helper_col(int id, int slab) {
  return slab < 6 ? (slab % 3) * kD + (slab / 3) * 512 + id * 128 : (slab - 6) * 512 + id * 128;
}
__device__ __forceinline__ void helper_cta(const CUtensorMap* map_q, const CUtensorMap* map_1, uint8_t* sm,
                                           uint32_t sb, int id, int warp) {
  constexpr int kRed = 6 * 32768, kBar = kRed + 2 * 4096;
  const int tid = threadIdx.x;
  if (warp == 8 && elect()) {
#pragma unroll
    for (int s = 0; s < 6; s++) {
      mbar_init(sb + kBar + s * 8, 1);
      mbar_init(sb + kBar + 64 + s * 8, 4);
    }
    fence_async_smem();
#pragma unroll
    for (int s = 0; s < 6; s++) {
      mbar_expect_tx(sb + kBar + s * 8, 32768);
      tma2d(sb + s * 32768, map_q, sb + kBar + s * 8, id * 128, s * 128);
    }
  }
  __syncthreads();
  if (warp == 8) {
    int slot = 0, ph = 0;
#pragma unroll 1
    for (int n = 6; n < 104; n++) {
      mbar_wait(sb + kBar + 64 + slot * 8, ph);
      if (elect()) {
        mbar_expect_tx(sb + kBar + slot * 8, 32768);
        tma2d(sb + slot * 32768, n < 48 ? map_q : map_1, sb + kBar + slot * 8, helper_col(id, n >> 3), (n & 7) * 128);
      }
      if (++slot == 6) slot = 0, ph ^= 1;
    }
  } else if (warp < 8) {
    if (tid == 0) *reinterpret_cast<unsigned*>(sm + kBar + 128) = atomicAdd(&g_ticket, 1u) / kGrid + 1;
    int slot = warp >> 2, ph = 0;
#pragma unroll 1
    for (int slab = 0; slab < 13; slab++) {
      float a[8];
#pragma unroll
      for (int e = 0; e < 8; e++) a[e] = 0.f;
#pragma unroll 1
      for (int box = 0; box < 4; box++) {
        mbar_wait(sb + kBar + slot * 8, ph);
        const uint4* p = reinterpret_cast<const uint4*>(sm + slot * 32768) + (tid & 127);
        uint4 v[16];
#pragma unroll
        for (int i = 0; i < 16; i++) v[i] = p[i * 128];
        __syncwarp();
        if (elect()) mbar_arrive(sb + kBar + 64 + slot * 8);
#pragma unroll
        for (int i = 0; i < 16; i++) add_chunk(a, v[i]);
        slot += 2;
        if (slot >= 6) slot -= 6, ph ^= 1;
      }
      float* red = reinterpret_cast<float*>(sm + kRed + (slab & 1) * 4096);
#pragma unroll
      for (int e = 0; e < 8; e++) a[e] += shfl_xor(a[e], 16);
      if ((tid & 16) == 0) {
        float4* d = reinterpret_cast<float4*>(red + warp * 128 + (tid & 15) * 8);
        d[0] = make_float4(a[0], a[1], a[2], a[3]);
        d[1] = make_float4(a[4], a[5], a[6], a[7]);
      }
      asm volatile("bar.sync 1, 256;" ::: "memory");
      if (warp < 4) {
        float t = 0.f;
#pragma unroll
        for (int q = 0; q < 8; q++) t += red[q * 128 + tid];
        st_relaxed(g_cs + (slab < 6 ? 0 : 3 * kD) + helper_col(id, slab) + tid,
                   tag_value(t, *reinterpret_cast<volatile unsigned*>(sm + kBar + 128)));
      }
    }
  }
}

constexpr float kGelu0 = 2.f * 0.7978845608028654f;
constexpr float kGelu1 = 8.f * 0.7978845608028654f * 0.044715f;

__device__ __forceinline__ void store_staged(uint8_t* dst, uint32_t stg) {
  fence_async_smem();
  __syncwarp();
  if (elect()) {
    bulk_store(dst, stg, 4096);
    bulk_commit();
  }
}

#define GY_MASK 0x3F
#define GY_MASK2 0
#define GY(k) if (((CH == 2 ? GY_MASK2 : GY_MASK) >> k) & 1) yield_slot()
template <int CH>
__device__ __forceinline__ void gelu_chunk(const float (&acc)[2][96], const float2 (&st)[4], const float4* vec,
                                           uint32_t stg, int lane, uint8_t* prev) {
  uint32_t pk[8][4];
  float u[3][4], z[3][4];
  float4 v = vec[CH * 32], vn = v;
#pragma unroll
  for (int s = 0; s < 18; s++) {
    const int J = CH * 8 + (s >> 1), c0 = 2 * (s & 1), cur = s % 3, p1 = (s + 2) % 3, p2 = (s + 1) % 3;
    if (s < 16) {
      if (c0 == 0 && s < 14) vn = vec[(J + 1) * 4];
#pragma unroll
      for (int e = 0; e < 4; e++) {
        const int c = c0 + (e >> 1);
        z[cur][e] = fmaf(st[c].y, e & 1 ? v.y : v.x, e & 1 ? v.w : v.z);
      }
      if (c0 == 2) v = vn;
    }
    if (s >= 1 && s < 17) z[p1][0] = tanh_fast(z[p1][0]);
    GY(0);
    if (s < 16) {
#pragma unroll
      for (int e = 0; e < 4; e++) {
        const int c = c0 + (e >> 1);
        u[cur][e] = fmaf(acc[c & 1][4 * J + c0 + (e & 1)], st[c].x, z[cur][e]);
      }
    }
    if (s >= 11) {
      const int jj = s - 11;
      stsm4(stg + lane * 128 + ((jj ^ (lane & 7)) << 4), pk[jj][0], pk[jj][1], pk[jj][2], pk[jj][3]);
    }
    GY(1);
    if (s < 16) {
#pragma unroll
      for (int e = 0; e < 4; e++) z[cur][e] = u[cur][e] * u[cur][e];
    }
    if (s >= 1 && s < 17) z[p1][1] = tanh_fast(z[p1][1]);
    GY(2);
    if (s < 16) {
#pragma unroll
      for (int e = 0; e < 4; e++) z[cur][e] = fmaf(z[cur][e], kGelu1, kGelu0);
    }
    if (s >= 1 && s < 17) z[p1][2] = tanh_fast(z[p1][2]);
    GY(3);
    if (s >= 2) {
      pk[(s - 2) >> 1][c0] = pack2(fmaf(u[p2][0], z[p2][0], u[p2][0]), fmaf(u[p2][1], z[p2][1], u[p2][1]));
      pk[(s - 2) >> 1][c0 + 1] = pack2(fmaf(u[p2][2], z[p2][2], u[p2][2]), fmaf(u[p2][3], z[p2][3], u[p2][3]));
    }
    GY(4);
    if (s < 16) {
#pragma unroll
      for (int e = 0; e < 4; e++) z[cur][e] = u[cur][e] * z[cur][e];
    }
    if (s >= 1 && s < 17) z[p1][3] = tanh_fast(z[p1][3]);
    GY(5);
    if (CH > 0 && s == 1) store_staged(prev, stg);
    if (CH > 0 && s == 10) {
      if (elect()) bulk_wait_read();
      __syncwarp();
    }
  }
  stsm4(stg + lane * 128 + ((7 ^ (lane & 7)) << 4), pk[7][0], pk[7][1], pk[7][2], pk[7][3]);
}

__device__ __forceinline__ void epilogue_gelu(const float (&acc)[2][96], float2 (&st)[4], uint8_t* sm, uint32_t sb,
                                              bool wide, int vcol0, uint8_t* dst, int tile, int w) {
  const int lane = threadIdx.x & 31, t = lane & 3;
#pragma unroll
  for (int c = 0; c < 4; c++) {
    st[c].x *= 0.5f;
    st[c].y *= st[c].x;
  }
  const float4* vec = reinterpret_cast<const float4*>(sm + kSmV1) + vcol0 / 2 + t;
  const uint32_t stg = sb + kSmStg + w * 4096;
  TRACE_AT(tile, 8);
  gelu_chunk<0>(acc, st, vec, stg, lane, dst);
  TRACE_AT(tile, 9);
  gelu_chunk<1>(acc, st, vec, stg, lane, dst);
  TRACE_AT(tile, 10);
  if (wide) gelu_chunk<2>(acc, st, vec, stg, lane, dst + kTileBytes);
  store_staged(dst + (wide ? 2 : 1) * kTileBytes, stg);
  TRACE_AT(tile, 11);
  if (elect()) {
    bulk_wait();
    TRACE_AT(tile, 12);
    mbar_arrive(sb + kBarEpi + tile * 8);
  }
  __syncwarp();
}

__device__ __forceinline__ void add_mean_term(float (&acc)[2][96], const float2 (&st)[4], uint8_t* sm, int tq,
                                              int lane) {
  const float2* cs = reinterpret_cast<const float2*>(sm + kSmCsQ) + tq * 96 + (lane & 3);
  float2 vn = cs[0];
#pragma unroll
  for (int J = 0; J < 24; J++) {
    const float2 v = vn;
    if (J < 23) vn = cs[J * 4 + 4];
#pragma unroll
    for (int c = 0; c < 4; c++) {
      acc[c & 1][4 * J + (c & 2)] = fmaf(st[c].y, v.x, acc[c & 1][4 * J + (c & 2)]);
      acc[c & 1][4 * J + (c & 2) + 1] = fmaf(st[c].y, v.y, acc[c & 1][4 * J + (c & 2) + 1]);
    }
    yield_slot();
  }
}

#define HALO_AT 0
__device__ __forceinline__ void epilogue_attn(const float (&acc)[2][96], const float2 (&st)[4], uint8_t* sm,
                                              uint32_t sb, int layer, int tq, int b, int j, unsigned epoch, int tile,
                                              int wg, int w) {
  const int lane = threadIdx.x & 31, t = lane & 3, g = lane >> 2;
  const int hp = j + 8 * tq, att = 2 * layer + tq;
  uint32_t q[4][8], k[5][8], vt[5][8];
#define SCALED(c, J) pack2(acc[(c) & 1][4 * (J) + ((c) & 2)] * st[c].x, acc[(c) & 1][4 * (J) + ((c) & 2) + 1] * st[c].x)
#pragma unroll
  for (int J = 0; J < 8; J++) vt[4][J] = transpose8(SCALED(3, 16 + J));
#pragma unroll
  for (int J = 0; J < 8; J++) k[4][J] = SCALED(3, 8 + J);
  if (w < 3) {
    uint4* hs = reinterpret_cast<uint4*>(sm + kSmHalo + w * 2048) + lane;
    hs[0] = make_uint4(k[4][0], k[4][1], k[4][2], k[4][3]);
    hs[32] = make_uint4(k[4][4], k[4][5], k[4][6], k[4][7]);
    hs[64] = make_uint4(vt[4][0], vt[4][1], vt[4][2], vt[4][3]);
    hs[96] = make_uint4(vt[4][4], vt[4][5], vt[4][6], vt[4][7]);
  } else if ((b & 7) != 7) {
    uint4* gh = g_halo + ((layer * 16 + b) * 16 + hp) * 256 + lane;
#pragma unroll
    for (int i = 0; i < 8; i++)
      asm volatile("{\n.reg .b64 x, y;\nmov.b64 x, {%1, %3};\nmov.b64 y, {%2, %3};\n"
                   "st.relaxed.gpu.global.v2.b64 [%0], {x, y};\n}" ::"l"(gh + i * 32),
                   "r"(k[4][i]), "r"(vt[4][i]), "r"(epoch) : "memory");
  }
#pragma unroll
  for (int c = 0; c < 3; c++)
#pragma unroll
    for (int J = 0; J < 8; J++) {
      k[c + 1][J] = SCALED(c, 8 + J);
      vt[c + 1][J] = transpose8(SCALED(c, 16 + J));
      yield_slot();
    }
  const bool first = w == 0 && (b & 7) == 0;
  const uint4* gh = g_halo + ((layer * 16 + b - 1) * 16 + hp) * 256 + lane;
  uint32_t tag[16];
#define LOAD_HALO(i)                                                                         \
  asm volatile("{\n.reg .b64 x, y;\nld.relaxed.gpu.global.v2.b64 {x, y}, [%4];\n"            \
               "mov.b64 {%0, %1}, x;\nmov.b64 {%2, %3}, y;\n}"                               \
               : "=r"(k[0][i]), "=r"(tag[2 * i]), "=r"(vt[0][i]), "=r"(tag[2 * i + 1])        \
               : "l"(gh + i * 32) : "memory")
#pragma unroll
  for (int c = 0; c <= 4; c++) {
    if (c == HALO_AT) {
      if (w == 0 && !first) {
#pragma unroll
        for (int i = 0; i < 8; i++) LOAD_HALO(i);
      } else {
#pragma unroll
        for (int i = 0; i < 8; i++) k[0][i] = vt[0][i] = tag[2 * i] = tag[2 * i + 1] = 0u;
      }
    }
#pragma unroll
    for (int J = 0; J < 8 && c < 4; J++) {
      q[c & 3][J] = SCALED(c & 3, J);
      if (J & 1) yield_slot();
    }
  }
#undef SCALED
  TRACE_AT(tile, 8);
  wg_bar(wg);
  if (w > 0) {
    const uint4* hs = reinterpret_cast<const uint4*>(sm + kSmHalo + (w - 1) * 2048) + lane;
    const uint4 a0 = hs[0], a1 = hs[32], a2 = hs[64], a3 = hs[96];
    k[0][0] = a0.x; k[0][1] = a0.y; k[0][2] = a0.z; k[0][3] = a0.w;
    k[0][4] = a1.x; k[0][5] = a1.y; k[0][6] = a1.z; k[0][7] = a1.w;
    vt[0][0] = a2.x; vt[0][1] = a2.y; vt[0][2] = a2.z; vt[0][3] = a2.w;
    vt[0][4] = a3.x; vt[0][5] = a3.y; vt[0][6] = a3.z; vt[0][7] = a3.w;
  } else if (!first) {
    unsigned spins = 0;
    while (true) {
      unsigned d0 = 0, d1 = 0, d2 = 0, d3 = 0;
#pragma unroll
      for (int i = 0; i < 4; i++) {
        d0 |= tag[i] ^ epoch;
        d1 |= tag[4 + i] ^ epoch;
        d2 |= tag[8 + i] ^ epoch;
        d3 |= tag[12 + i] ^ epoch;
      }
      if (__all_sync(0xffffffffu, (d0 | d1 | d2 | d3) == 0)) break;
      if (++spins > kSpinLimit) __trap();
#pragma unroll
      for (int i = 0; i < 8; i++) LOAD_HALO(i);
    }
  }
#undef LOAD_HALO
  TRACE_AT(tile, 9);
  mbar_wait(sb + kBarPause + att * 8, 0);
  TRACE_AT(tile, 10);

  float s[2][5][4];
#pragma unroll
  for (int hd = 0; hd < 2; hd++)
#pragma unroll
    for (int kg = 0; kg < 5; kg++) {
      const int ca = kg > 0 ? kg - 1 : 0, cb = kg < 4 ? kg : 3;
#pragma unroll
      for (int e = 0; e < 4; e++) s[hd][kg][e] = 0.f;
#pragma unroll
      for (int ks = 0; ks < 2; ks++) {
        const int J = 4 * hd + 2 * ks;
        mma16816(s[hd][kg], q[ca][J], q[cb][J], q[ca][J + 1], q[cb][J + 1], k[kg][J], k[kg][J + 1]);
      }
    }
  constexpr float kScale = 0.17677669529663687f * 1.4426950408889634f;
  const bool own0 = 2 * t <= g, own1 = 2 * t + 1 <= g;
  const uint32_t own_mask = (own0 ? 0xffffu : 0u) | (own1 ? 0xffff0000u : 0u);
  float o[2][4][2][4];
#pragma unroll
  for (int hd = 0; hd < 2; hd++) {
    float v0[4], v1[4], m[4];
#pragma unroll
    for (int c = 0; c < 4; c++) {
      float p0 = s[hd][c][2], p1 = s[hd][c][3];
      if (c == 0 && first) p0 = p1 = -INFINITY;
      v0[c] = own0 ? s[hd][c + 1][0] : p0;
      v1[c] = own1 ? s[hd][c + 1][1] : p1;
      m[c] = fmaxf(v0[c], v1[c]);
    }
#pragma unroll
    for (int c = 0; c < 4; c++) m[c] = fmaxf(m[c], shfl_xor(m[c], 1));
#pragma unroll
    for (int c = 0; c < 4; c++) m[c] = fmaxf(m[c], shfl_xor(m[c], 2));
#pragma unroll
    for (int c = 0; c < 4; c++) {
      const float nm = -m[c] * kScale;
      v0[c] = ex2(fmaf(v0[c], kScale, nm));
      v1[c] = ex2(fmaf(v1[c], kScale, nm));
      m[c] = v0[c] + v1[c];
    }
#pragma unroll
    for (int c = 0; c < 4; c++) m[c] += shfl_xor(m[c], 1);
#pragma unroll
    for (int c = 0; c < 4; c++) m[c] += shfl_xor(m[c], 2);
#pragma unroll
    for (int c = 0; c < 4; c++) {
      const float inv = rcp(m[c]);
      const uint32_t p = pack2(v0[c] * inv, v1[c] * inv);
#pragma unroll
      for (int ds = 0; ds < 2; ds++) {
        const int J = 4 * hd + 2 * ds;
#pragma unroll
        for (int e = 0; e < 4; e++) o[hd][c][ds][e] = 0.f;
        mma16816(o[hd][c][ds], vt[c][J], vt[c][J + 1], vt[c + 1][J], vt[c + 1][J + 1], p & ~own_mask, p & own_mask);
      }
    }
  }
  TRACE_AT(tile, 11);
  const uint32_t stg = sb + kSmStg + w * 4096;
#pragma unroll
  for (int J = 0; J < 8; J++) {
    const int hd = J >> 2, ds = (J >> 1) & 1, e = 2 * (J & 1);
    stsm4_t(stg + lane * 128 + ((J ^ (lane & 7)) << 4), pack2(o[hd][0][ds][e], o[hd][0][ds][e + 1]),
            pack2(o[hd][1][ds][e], o[hd][1][ds][e + 1]), pack2(o[hd][2][ds][e], o[hd][2][ds][e + 1]),
            pack2(o[hd][3][ds][e], o[hd][3][ds][e + 1]));
  }
  if (elect()) mbar_arrive(sb + kBarResume + att * 8);
  fence_async_smem();
  __syncwarp();
  TRACE_AT(tile, 12);
  if (elect()) {
    bulk_store(g_o + (b * 16 + hp) * kTileBytes + w * 4096, stg, 4096);
    bulk_commit();
    bulk_wait();
    TRACE_AT(tile, 13);
    mbar_arrive(sb + kBarEpi + tile * 8);
  }
  __syncwarp();
}

__device__ __forceinline__ void gather_stats(uint8_t* sm, const uint2* stat, unsigned epoch) {
  const int r = threadIdx.x & 127;
  uint2 a[8];
  unsigned spins = 0;
  while (true) {
    unsigned diff = 0;
#pragma unroll
    for (int i = 0; i < 8; i++) {
      a[i] = ld_relaxed2(stat + i * 128 + r);
      diff |= (a[i].x ^ epoch) | (a[i].y ^ epoch);
    }
    if (__all_sync(0xffffffffu, (diff & 7u) == 0)) break;
    if (++spins > kSpinLimit) __trap();
    __nanosleep(200);
  }
  float s = 0.f, q = 0.f;
#pragma unroll
  for (int i = 0; i < 8; i++) {
    s += untag_value(a[i].x);
    q += untag_value(a[i].y);
  }
  const float mean = s * (1.f / 1024.f);
  const float var = fmaxf(fmaf(-mean, mean, q * (1.f / 1024.f)), 0.f);
  reinterpret_cast<float2*>(sm + kSmStat)[r] = make_float2(rsqrtf(var + 1e-5f), -mean);
}

__device__ __forceinline__ void gather_colsums(uint8_t* sm, int part, int j, int lane, unsigned epoch) {
#pragma unroll 1
  for (int blk = part < 4 ? 0 : 2 * part - 5; blk < (part < 4 ? 3 : 2 * part - 3); blk++) {
    const int col = part < 2 ? blk * kD + (j + 8 * part) * 64
                             : 3 * kD + 64 * (blk + (blk < 3 ? 3 * j : blk < 5 ? 21 + 2 * j : 35 + 2 * j));
    uint2 v;
    unsigned spins = 0;
    while (true) {
      v = ld_relaxed2(reinterpret_cast<const uint2*>(g_cs + col) + lane);
      if (__all_sync(0xffffffffu, (((v.x ^ epoch) | (v.y ^ epoch)) & 7u) == 0)) break;
      if (++spins > kSpinLimit) __trap();
      __nanosleep(100);
    }
    uint8_t* dst = part < 2 ? sm + kSmCsQ + (part * 96 + blk * 32 + lane) * 8 : sm + kSmV1 + (blk * 32 + lane) * 16;
    *reinterpret_cast<float2*>(dst) = make_float2(untag_value(v.x), untag_value(v.y));
  }
}

#define READBACK 0
#define XSPLIT 1
#define PF_START 0
#define PAUSE_QKV2 7
#define PAUSE_WO 3

__global__ void __cluster_dims__(2, 1, 1) __launch_bounds__(384, 1)
fused_layers_kernel(const __grid_constant__ CUtensorMap map_x, const __grid_constant__ CUtensorMap map_out,
                    const __grid_constant__ CUtensorMap map_qkv, const __grid_constant__ CUtensorMap map_wo,
                    const __grid_constant__ CUtensorMap map_w1a, const __grid_constant__ CUtensorMap map_w1b,
                    const __grid_constant__ CUtensorMap map_w2, const __grid_constant__ CUtensorMap map_csq,
                    const __grid_constant__ CUtensorMap map_cs1, const __grid_constant__ Params prm) {
  extern __shared__ __align__(1024) uint8_t sm[];
  if (threadIdx.x < 128 && blockIdx.x < kCtas) TRACE_AT(15, 1);
  const uint32_t sb = smem_u32(sm);
  const int warp = __shfl_sync(0xffffffffu, threadIdx.x >> 5, 0), lane = threadIdx.x & 31;
  const int cta = blockIdx.x, rank = cta & 1, cl = cta >> 1;
  const int grp = cl < 4 ? 0 : cl < 36 ? (cl - 4) & 7 : 1 + (cl - 36) % 7;
  const int j = cl < 4 ? 4 + cl : cl < 36 ? (cl - 4) >> 3 : 4 + (cl - 36) / 7;
  const int b = 2 * grp + rank;
  const int xcol = (b >> 3) * kD, xrow = (b & 7) * 128;

  if (cta >= kCtas) {
    helper_cta(&map_csq, &map_cs1, sm, sb, cta - kCtas, warp);
    return;
  }
  if (warp >= 8 && elect()) {
    if (warp == 9) {
#pragma unroll
      for (int s = 0; s < 8; s++) mbar_init(sb + kBarFull + s * 8, 1);
      fence_async_smem();
#pragma unroll
      for (int s = 0; s < 4; s++) {
        const uint32_t full = sb + kBarFull + s * 8, dst = sb + kSmRing + s * 40960;
        mbar_expect_tx(full, 40960);
        tma2d(dst, &map_x, full, xcol + s * 64, xrow);
        tma3d(dst + kTileBytes, &map_qkv, full, j * 64, s * 64, 0);
        tma3d(dst + kTileBytes + 12288, &map_qkv, full, j * 64, s * 64 + 32, 0);
      }
      if (PF_START & 1) l2_prefetch(reinterpret_cast<const uint8_t*>(prm.x) + cta * 32768, 32768);
      if (PF_START & 2) l2_prefetch(reinterpret_cast<const uint8_t*>(prm.wqkv) + cta * 49152, 49152);
    } else if (warp == 8) {
      if (sb & 1023) __trap();
#pragma unroll
      for (int o = kBarTurn; o < kBarInit; o += 8) mbar_init(sb + o, 1);
    } else if (warp == 10) {
#pragma unroll
      for (int o = kBarEpoch; o < kSmEpoch; o += 8) mbar_init(sb + o, o < kBarEmpty ? 1 : o < kBarEpi ? 2 : 4);
    } else {
      mbar_init(sb + kBarInit, 1);
      fence_async_smem();
      mbar_expect_tx(sb + kBarInit, 32768);
      tma2d(sb + kSmX, &map_x, sb + kBarInit, xcol + j * 128, xrow);
      tma2d(sb + kSmX + kTileBytes, &map_x, sb + kBarInit, xcol + j * 128 + 64, xrow);
    }
    asm volatile("fence.mbarrier_init.release.cluster;" ::: "memory");
  }
  __syncwarp();
  asm volatile("barrier.cluster.arrive.relaxed.aligned;" ::: "memory");

  if (warp >= 8) {
    asm volatile("setmaxnreg.dec.sync.aligned.u32 40;");
    if (warp < 10) {
      asm volatile("barrier.cluster.wait.aligned;" ::: "memory");
      int nb = 32, mb = 0, kb = 0;
      uint32_t off = 0;
#pragma unroll 1
      for (int sg = 0; sg < kSegs; sg++) {
        const uint32_t e = prm.seg[sg];
        const int ty = e & 7, mode = (e >> 15) & 3, reset = (e >> 24) & 3;
        const int nend = nb + (e & 0x1f8);
        const uint32_t step = (e >> 17) & 1 ? 40960 : 32768;
        const int depth = (e >> 18) & 1 ? 40 : 32;
        if (reset) off = reset == 1 ? 0 : reset == 2 ? 40960 : 131072;
        if (mode != kModeContinue) kb = ((e >> 9) & 63) + (mode == kModeHead ? 2 * j : 0);
        const int inc = mode >= kModeSkip ? 2 : 1, skip = mode >= kModeSkip ? j : -1;
        if (warp == 8) {
          const CUtensorMap* map = ty < 2 ? &map_qkv : ty == 2 ? &map_wo : ty == 3 ? &map_w1a : ty < 6 ? &map_w1b : &map_w2;
          const int c0 = ty < 2 ? (j + 8 * ty) * 64 : 0;
          const int c2 = ty < 2 ? 0 : ty == 3 ? 3 * j : ty == 4 ? 24 + 2 * j : ty == 5 ? 40 + 2 * j : 2 * j;
          const uint32_t half = (ty < 2 || ty == 3) ? 12288 : 8192;
          const uint32_t bytes = 2 * half + (mode == kModeHead ? 0 : kTileBytes);
          const uint32_t dst = sb + kSmRing + kTileBytes + rank * half;
#pragma unroll 1
          for (; nb < nend; nb += 8) {
            for (; mb <= nb - depth; mb += 8) mbar_wait(sb + kBarEmpty + (mb & 56), (mb >> 6) & 1);
            if (kb >> 1 == skip) kb += 2;
            if (elect()) {
              const uint32_t full = sb + kBarFull + (nb & 56);
              mbar_expect_tx(full, bytes);
              tma3d_mc(dst + off, map, full, c0, kb * 64 + rank * 32, c2);
            }
            kb += inc;
            off += step;
            if (off == 163840) off = 0;
          }
        } else if (mode == kModeHead) {
          nb = nend;
          off += 2 * step;
          if (off >= 163840) off -= 163840;
          for (; mb <= nb - 56; mb += 8) mbar_wait(sb + kBarEmpty + (mb & 56), (mb >> 6) & 1);
        } else {
          const uint8_t* src = ty == 6 ? g_h + b * 56 * kTileBytes : (ty == 2 ? g_o : g_x) + b * 16 * kTileBytes;
          const int dep = (e >> 19) & 31;
          if (dep != 31) mbar_wait(sb + kBarReady + dep * 8, 0);
#pragma unroll 1
          for (; nb < nend; nb += 8) {
            for (; mb <= nb - depth; mb += 8) mbar_wait(sb + kBarEmpty + (mb & 56), (mb >> 6) & 1);
            if (kb >> 1 == skip) kb += 2;
            const uint32_t dst = sb + kSmRing + off, full = sb + kBarFull + (nb & 56);
            if (sg < 2) {
              if (elect()) tma2d(dst, &map_x, full, xcol + kb * 64, xrow);
            } else {
              if (elect()) bulk_load(dst, src + kb * kTileBytes, kTileBytes, full);
            }
            kb += inc;
            off += step;
            if (off == 163840) off = 0;
          }
        }
      }
    } else if (warp == 10) {
      unsigned epoch = 0;
      if (lane == 0) epoch = atomicAdd(&g_ticket, 1u) / kGrid + 1;
      epoch = __shfl_sync(0xffffffffu, epoch, 0);
      *reinterpret_cast<unsigned*>(sm + kSmEpoch) = epoch;
      asm volatile("barrier.cluster.wait.aligned;" ::: "memory");
      if (elect()) mbar_arrive(sb + kBarEpoch);
#pragma unroll 1
      for (int i = 0; i < kTiles - 1; i++) {
        const bool xt = i == 2 || i == 6 || i == 9;
        const unsigned* line = g_flag + (i * 16 + b) * 32;
        mbar_wait(sb + (xt ? kBarX + (i >> 2) * 16 : kBarEpi + i * 8), 0);
        wait_flags(line + (lane & 7), epoch);
        if (elect()) mbar_arrive(sb + kBarReady + i * 8);
        if (xt) {
          wait_flags(line + 8 + (lane & 7), epoch);
          if (elect()) mbar_arrive(sb + kBarReady + (14 + (i >> 2)) * 8);
        }
      }
    } else {
      {
        uint32_t v[7];
#pragma unroll
        for (int q = 0; q < 7; q++)
          v[q] = reinterpret_cast<const uint32_t*>(prm.b1)[32 * (q + (q < 3 ? 3 * j : q < 5 ? 21 + 2 * j : 35 + 2 * j)) + lane];
        const uint2 u = reinterpret_cast<const uint2*>(prm.b2)[32 * j + lane];
#pragma unroll
        for (int q = 0; q < 7; q++)
          *reinterpret_cast<float2*>(sm + kSmV1 + (q * 32 + lane) * 16 + 8) = make_float2(0.5f * bf_lo(v[q]), 0.5f * bf_hi(v[q]));
        reinterpret_cast<float4*>(sm + kSmB2)[lane] = make_float4(bf_lo(u.x), bf_hi(u.x), bf_lo(u.y), bf_hi(u.y));
      }
      asm volatile("barrier.cluster.wait.aligned;" ::: "memory");
      mbar_wait(sb + kBarEpoch, 0);
      const unsigned epoch = *reinterpret_cast<volatile unsigned*>(sm + kSmEpoch);
#pragma unroll 1
      for (int i = 0; i < kTiles - 1; i++) {
#pragma unroll 1
        for (int part = i == 4 ? 5 : i; part < (i < 2 ? i + 1 : i == 3 || i == 4 ? i + 2 : 0); part++) {
          gather_colsums(sm, part, j, lane, epoch);
          __syncwarp();
          if (elect()) mbar_arrive(sb + kBarCs + part * 8);
        }
        const bool xt = i == 2 || i == 6 || i == 9;
#pragma unroll 1
        for (int h = 0; h < (xt ? 2 : 1); h++) {
          mbar_wait(sb + (xt ? kBarX + ((i >> 2) * 2 + h) * 8 : kBarEpi + i * 8), 0);
          if (xt && elect()) {
#pragma unroll
            for (int q = 0; q < XSPLIT; q++)
              bulk_store(g_x + (b * 16 + 2 * j + h) * kTileBytes + q * (kTileBytes / XSPLIT),
                         sb + kSmX + h * kTileBytes + q * (kTileBytes / XSPLIT), kTileBytes / XSPLIT);
            bulk_commit();
            bulk_wait();
          }
          __syncwarp();
          if (elect()) st_release(&g_flag[(i * 16 + b) * 32 + h * 8 + j], epoch);
          __syncwarp();
        }
      }
    }
    __syncwarp();
    asm volatile("barrier.cluster.arrive.relaxed.aligned;\nbarrier.cluster.wait.aligned;" ::: "memory");
  } else {
    asm volatile("setmaxnreg.inc.sync.aligned.u32 232;");
    asm volatile("barrier.cluster.wait.aligned;" ::: "memory");
    const int wg = warp >> 2, w = warp & 3;
    const bool rel = (threadIdx.x & 95) == 0;
    const uint32_t rel_addr = mapa(sb + kBarEmpty, w & 1);
    if (wg == 1) TRACE_AT(15, 0);
#define EPOCH (*reinterpret_cast<volatile unsigned*>(sm + kSmEpoch))

    if (wg == 1) {
      mbar_wait(sb + kBarEpoch, 0);
      mbar_wait(sb + kBarInit, 0);
    }

#pragma unroll 1
    for (int i = wg; i < kTiles; i += 2) {
      const int layer = i >= 7, ty = i - 7 * layer;
      TRACE_AT(i, 15);
      float acc[2][96];
      if (ty == 2 || ty == 6) {
        const uint32_t xrow_addr = sb + kSmX + (32 * w + lane) * 128;
        const float2* b2 = reinterpret_cast<const float2*>(sm + kSmB2) + (lane & 3);
#pragma unroll
        for (int J = 0; J < 16; J++) {
          uint32_t r[4];
          ldsm4(xrow_addr + (J >> 3) * kTileBytes + (((J & 7) ^ (lane & 7)) << 4), r);
          float2 bias = make_float2(0.f, 0.f);
          if (ty == 6) bias = b2[J * 4];
#pragma unroll
          for (int c = 0; c < 4; c++) {
            acc[c & 1][4 * J + (c & 2)] = bf_lo(r[c]) + bias.x;
            acc[c & 1][4 * J + (c & 2) + 1] = bf_hi(r[c]) + bias.y;
            asm volatile("" : "+f"(acc[c & 1][4 * J + (c & 2)]), "+f"(acc[c & 1][4 * J + (c & 2) + 1]));
            if (c & 1) yield_slot();
          }
        }
        mainloop<128>(acc, sb, i, layer * 152 + ty * 16, ty == 6 ? 4 : 0, ty == 6 ? 56 : 16, ty == 2 ? PAUSE_WO : -1,
                      2 * layer + 1, rel_addr, rel, [] {});
        TRACE_AT(i, 2);
#pragma unroll
        for (int h = 0; h < 2; h++) {
#pragma unroll
          for (int J = 8 * h; J < 8 * h + 8; J++)
            stsm4(xrow_addr + h * kTileBytes + (((J & 7) ^ (lane & 7)) << 4), pack2(acc[0][4 * J], acc[0][4 * J + 1]),
                  pack2(acc[1][4 * J], acc[1][4 * J + 1]), pack2(acc[0][4 * J + 2], acc[0][4 * J + 3]),
                  pack2(acc[1][4 * J + 2], acc[1][4 * J + 3]));
          fence_async_smem();
          __syncwarp();
          if (i < kTiles - 1) {
            if (elect()) mbar_arrive(sb + kBarX + ((i >> 2) * 2 + h) * 8);
          } else if (elect()) {
            tma2d_store(&map_out, sb + kSmX + h * kTileBytes + w * 4096, xcol + j * 128 + h * 64, xrow + 32 * w);
            bulk_commit();
            if (h == 1) bulk_wait_read();
          }
          yield_slot();
          TRACE_AT(i, 8 + h);
        }
      } else {
        const int xver = 2 * layer + (ty >= 3);
        const bool wide = ty < 4, split = i > 1 && ty != 5;
        zero_acc<192>(acc);
        if (split) {
          const int n0 = layer * 152 + (ty < 2 ? 2 * ty : 42 + 2 * ty), slot = ty < 2 ? 2 * ty : 2 * ty - 5;
          if (wide) head_blocks<192>(acc, sb, n0, slot, sb + kBarX + (xver - 1) * 16, rel_addr, rel);
          else head_blocks<128>(acc, sb, n0, slot, sb + kBarX + (xver - 1) * 16, rel_addr, rel);
        }
        if (ty == 1 || ty == 4) {
          uint2* stat = g_stat + (xver * 16 + b) * 1024;
          publish_stats(sb, stat + j * 128, w, lane, EPOCH);
          if (ty == 4) TRACE_AT(i, 13);
          gather_stats(sm, stat, EPOCH);
          __syncwarp();
          if (elect()) mbar_arrive(sb + kBarStat + xver * 8);
          TRACE_AT(i, 14);
          if (i == 8) {
            float2 st[4];
#pragma unroll
            for (int c = 0; c < 4; c++) st[c] = reinterpret_cast<const float2*>(sm + kSmStat)[32 * w + 8 * c + (lane >> 2)];
            add_mean_term(acc, st, sm, 1, lane);
          }
        }
        const int n0 = layer * 152 + (!split ? 16 * ty : ty < 2 ? 4 + 14 * ty : 10 + 14 * ty);
        const int slot = ty < 2 ? (split ? 2 * ty : 0) : ty == 3 ? 1 : 8 - ty;
        float2 st[4];
        unsigned epoch;
        auto pre = [&] {
          mbar_wait(sb + (ty == 0 || ty == 3 ? kBarStat + xver * 8 : kBarEpi + (i - 1) * 8), 0);
#pragma unroll
          for (int c = 0; c < 4; c++) st[c] = reinterpret_cast<const float2*>(sm + kSmStat)[32 * w + 8 * c + (lane >> 2)];
          epoch = EPOCH;
        };
        if (wide) mainloop<192>(acc, sb, i, n0, slot, split ? 14 : 16, ty == 1 ? PAUSE_QKV2 : -1, xver, rel_addr, rel, pre);
        else mainloop<128>(acc, sb, i, n0, slot, split ? 14 : 16, -1, 0, rel_addr, rel, pre);
        TRACE_AT(i, 2);
        if (layer == 0) mbar_wait(sb + kBarCs + ty * 8, 0);
        if (ty < 2) {
          if (i != 8) add_mean_term(acc, st, sm, ty, lane);
          epilogue_attn(acc, st, sm, sb, layer, ty, b, j, epoch, i, wg, w);
        } else {
          const int blk = ty == 3 ? 3 * j : 16 * ty - 40 + 2 * j;
          epilogue_gelu(acc, st, sm, sb, wide, wide ? 0 : 128 * ty - 320, g_h + (b * 56 + blk) * kTileBytes + w * 4096,
                        i, w);
        }
      }
      TRACE_AT(i, 3);
    }
#undef EPOCH
    asm volatile("barrier.cluster.arrive.relaxed.aligned;\nbarrier.cluster.wait.aligned;" ::: "memory");
    if (wg == 1) TRACE_AT(15, 2);
  }
}

void build_segments(uint32_t* seg) {
  int n = 0;
  auto add = [&](int ty, int cnt, int kb0, int mode, int wide, int depth5, int dep, int reset) {
    seg[n++] = ty | cnt << 3 | kb0 << 9 | mode << 15 | wide << 17 | depth5 << 18 | dep << 19 | reset << 24;
  };
  for (int l = 0; l < 2; l++) {
    const int t = 7 * l;
    if (l == 0) {
      add(0, 12, 4, kModePlain, 1, 0, 31, 1);
      add(1, 16, 0, kModePlain, 1, 0, 31, 0);
    } else {
      add(0, 2, 0, kModeHead, 1, 0, 31, 1);
      add(1, 2, 0, kModeHead, 1, 0, 31, 0);
      add(0, 7, 0, kModeSkip, 1, 0, 6, 0);
      add(0, 7, 1, kModeSkip, 1, 0, 15, 0);
      add(1, 7, 0, kModeSkip, 1, 0, 31, 0);
      add(1, 7, 1, kModeSkip, 1, 0, 31, 0);
    }
    add(2, 4, 0, kModePlain, 0, 0, t, 1);
    add(2, 4, 4, kModePlain, 0, 1, 31, 0);
    add(2, 8, 8, kModePlain, 0, 1, t + 1, 0);
    add(3, 2, 0, kModeHead, 1, 0, 31, 2);
    add(4, 2, 0, kModeHead, 1, 0, 31, 0);
    add(3, 7, 0, kModeSkip, 1, 0, t + 2, 0);
    add(3, 7, 1, kModeSkip, 1, 0, 14 + 2 * l, 0);
    add(4, 4, 0, kModeSkip, 0, 0, 31, 3);
    add(4, 3, 0, kModeContinue, 0, 1, 31, 0);
    add(4, 7, 1, kModeSkip, 0, 1, 31, 0);
    add(5, 16, 0, kModePlain, 0, 1, 31, 0);
    add(6, 24, 0, kModePlain, 0, 1, t + 3, 0);
    add(6, 16, 24, kModePlain, 0, 1, t + 4, 0);
    add(6, 16, 40, kModePlain, 0, 1, t + 5, 0);
  }
}

typedef CUresult (*EncodeTiledFn)(CUtensorMap*, CUtensorMapDataType, cuuint32_t, void*, const cuuint64_t*,
                                  const cuuint64_t*, const cuuint32_t*, const cuuint32_t*, CUtensorMapInterleave,
                                  CUtensorMapSwizzle, CUtensorMapL2promotion, CUtensorMapFloatOOBfill);

CUtensorMap make_map(EncodeTiledFn enc, const void* p, int rank, const cuuint64_t* dims, const cuuint64_t* strides,
                     const cuuint32_t* box, CUtensorMapSwizzle swizzle = CU_TENSOR_MAP_SWIZZLE_128B) {
  CUtensorMap m;
  const cuuint32_t es[5] = {1, 1, 1, 1, 1};
  enc(&m, CU_TENSOR_MAP_DATA_TYPE_BFLOAT16, rank, const_cast<void*>(p), dims, strides, box, es,
      CU_TENSOR_MAP_INTERLEAVE_NONE, swizzle, CU_TENSOR_MAP_L2_PROMOTION_L2_128B,
      CU_TENSOR_MAP_FLOAT_OOB_FILL_NONE);
  return m;
}

CUtensorMap weight_map(EncodeTiledFn enc, const void* p, int k, int n, int blocks) {
  const cuuint64_t dims[3] = {64, (cuuint64_t)k, (cuuint64_t)n / 64};
  const cuuint64_t strides[2] = {(cuuint64_t)n * 2, 128};
  const cuuint32_t box[3] = {64, 32, (cuuint32_t)blocks};
  return make_map(enc, p, 3, dims, strides, box);
}

CUtensorMap slab_map(EncodeTiledFn enc, const void* p, int n) {
  const cuuint64_t dims[2] = {(cuuint64_t)n, kD};
  const cuuint64_t strides[1] = {(cuuint64_t)n * 2};
  const cuuint32_t box[2] = {128, 128};
  return make_map(enc, p, 2, dims, strides, box, CU_TENSOR_MAP_SWIZZLE_NONE);
}

CUtensorMap token_map(EncodeTiledFn enc, const void* p, int rows) {
  const cuuint64_t dims[2] = {2 * kD, 1024};
  const cuuint64_t strides[1] = {4 * kD};
  const cuuint32_t box[2] = {64, (cuuint32_t)rows};
  return make_map(enc, p, 2, dims, strides, box);
}

}

extern "C" void kernel_launch(void* const* d_in, const int* in_sizes, int n_in, void* d_out, int out_size) {
  (void)in_sizes; (void)n_in; (void)out_size;
  static EncodeTiledFn enc = nullptr;
  if (!enc) {
    void* fn = nullptr;
    cudaDriverEntryPointQueryResult q;
    cudaGetDriverEntryPoint("cuTensorMapEncodeTiled", &fn, cudaEnableDefault, &q);
    enc = (EncodeTiledFn)fn;
    cudaFuncSetAttribute(fused_layers_kernel, cudaFuncAttributeMaxDynamicSharedMemorySize, kSmBytes);
  }
  Params prm;
  prm.x = (const __nv_bfloat16*)d_in[0];
  prm.wqkv = (const __nv_bfloat16*)d_in[1];
  prm.wo = (const __nv_bfloat16*)d_in[2];
  prm.w1 = (const __nv_bfloat16*)d_in[4];
  prm.b1 = (const __nv_bfloat16*)d_in[5];
  prm.w2 = (const __nv_bfloat16*)d_in[6];
  prm.b2 = (const __nv_bfloat16*)d_in[7];
  build_segments(prm.seg);
  const cuuint64_t qd[3] = {kD, kD, 3}, qs[2] = {3 * kD * 2, kD * 2};
  const cuuint32_t qb[3] = {64, 32, 3};
  const CUtensorMap map_x = token_map(enc, d_in[0], 128);
  const CUtensorMap map_out = token_map(enc, d_out, 32);
  const CUtensorMap map_qkv = make_map(enc, prm.wqkv, 3, qd, qs, qb);
  const CUtensorMap map_wo = weight_map(enc, prm.wo, kD, kD, 2);
  const CUtensorMap map_w1a = weight_map(enc, prm.w1, kD, kF, 3);
  const CUtensorMap map_w1b = weight_map(enc, prm.w1, kD, kF, 2);
  const CUtensorMap map_w2 = weight_map(enc, prm.w2, kF, kD, 2);
  fused_layers_kernel<<<kGrid, 384, kSmBytes>>>(map_x, map_out, map_qkv, map_wo, map_w1a, map_w1b, map_w2,
                                                slab_map(enc, prm.wqkv, 3 * kD), slab_map(enc, prm.w1, kF), prm);
}
```

```cpp
#include <cuda.h>
#include <cuda_bf16.h>
#include <cuda_runtime.h>
#include <stdint.h>

namespace {

constexpr int kD = 1024;
constexpr int kF = 3584;
constexpr int kCtas = 128;
constexpr int kGrid = 132;
constexpr int kTiles = 14;
constexpr int kTileBytes = 16384;

constexpr int kSmRing = 0;
constexpr int kSmX = 163840;
constexpr int kSmStg = kSmX + 32768;
constexpr int kSmHalo = kSmStg + 16384;
constexpr int kSmCsQ = kSmHalo + 6144;
constexpr int kSmV1 = kSmCsQ + 384 * 4;
constexpr int kSmB2 = kSmV1 + 448 * 8;
constexpr int kSmStat = kSmB2 + 128 * 4;
constexpr int kSmBar = kSmStat + 128 * 8;
constexpr int kBarFull = kSmBar;
constexpr int kBarTurn = kBarFull + 8 * 8;
constexpr int kBarReady = kBarTurn + 14 * 8;
constexpr int kBarPause = kBarReady + 17 * 8;
constexpr int kBarCs = kBarPause + 4 * 8;
constexpr int kBarInit = kBarCs + 6 * 8;
constexpr int kBarEpoch = kBarInit + 8;
constexpr int kBarEmpty = kBarEpoch + 8;
constexpr int kBarEpi = kBarEmpty + 9 * 8;
constexpr int kBarX = kBarEpi + 14 * 8;
constexpr int kBarStat = kBarX + 6 * 8;
constexpr int kBarResume = kBarStat + 4 * 8;
constexpr int kSmEpoch = kBarResume + 4 * 8;
constexpr int kSmBytes = kSmEpoch + 16;
constexpr int kSegs = 36;

constexpr int kFlagLines = kTiles * 16;

constexpr unsigned kSpinLimit = 1u << 24;

__device__ __align__(1024) uint8_t g_x[16 * 16 * kTileBytes];
__device__ __align__(1024) uint8_t g_o[16 * 16 * kTileBytes];
__device__ __align__(1024) uint8_t g_h[16 * 56 * kTileBytes];
__device__ __align__(128) uint2 g_stat[4 * 16 * 128 * 8];
__device__ __align__(128) unsigned g_cs[3 * kD + kF];
__device__ __align__(128) uint4 g_halo[2 * 16 * 16 * 256];
__device__ __align__(128) unsigned g_flag[kFlagLines * 32];
__device__ unsigned g_ticket;

#define TRACE_AT(tile, k)
#define TRACE_PUB(i, k, c)
#define TRACE_ISSUE(which, nb)

struct Params {
  const __nv_bfloat16* x;
  const __nv_bfloat16* wqkv;
  const __nv_bfloat16* wo;
  const __nv_bfloat16* w1;
  const __nv_bfloat16* b1;
  const __nv_bfloat16* w2;
  const __nv_bfloat16* b2;
  uint32_t seg[kSegs];
};

__device__ __forceinline__ uint32_t smem_u32(const void* p) {
  return (uint32_t)__cvta_generic_to_shared(p);
}
__device__ __forceinline__ uint32_t mapa(uint32_t a, uint32_t cta) {
  uint32_t r;
  asm("mapa.shared::cluster.u32 %0, %1, %2;" : "=r"(r) : "r"(a), "r"(cta));
  return r;
}
__device__ __forceinline__ void mbar_init(uint32_t bar, int cnt) {
  asm volatile("mbarrier.init.shared::cta.b64 [%0], %1;" ::"r"(bar), "r"(cnt) : "memory");
}
__device__ __forceinline__ void mbar_expect_tx(uint32_t bar, uint32_t bytes) {
  asm volatile("mbarrier.arrive.expect_tx.shared::cta.b64 _, [%0], %1;" ::"r"(bar), "r"(bytes) : "memory");
}
__device__ __forceinline__ void mbar_arrive(uint32_t bar) {
  asm volatile("mbarrier.arrive.shared::cta.b64 _, [%0];" ::"r"(bar) : "memory");
}
__device__ __forceinline__ void mbar_arrive_cluster(uint32_t cluster_addr) {
  asm volatile("mbarrier.arrive.shared::cluster.b64 _, [%0];" ::"r"(cluster_addr) : "memory");
}
__device__ __forceinline__ void mbar_wait(uint32_t bar, uint32_t parity) {
  asm volatile(
      "{\n.reg .pred p;\n.reg .u32 c;\n"
      "mbarrier.try_wait.parity.shared::cta.b64 p, [%0], %1;\n"
      "@p bra.uni DONE;\n"
      "mov.u32 c, 0;\n"
      "RETRY:\n"
      "mbarrier.try_wait.parity.shared::cta.b64 p, [%0], %1;\n"
      "@p bra.uni DONE;\n"
      "add.u32 c, c, 1;\n"
      "setp.lt.u32 p, c, %2;\n"
      "@p bra.uni RETRY;\n"
      "trap;\n"
      "DONE:\n}" ::"r"(bar), "r"(parity), "n"(kSpinLimit)
      : "memory");
}
__device__ __forceinline__ void tma3d(uint32_t dst, const CUtensorMap* m, uint32_t bar, int c0, int c1, int c2) {
  asm volatile(
      "cp.async.bulk.tensor.3d.shared::cluster.global.mbarrier::complete_tx::bytes [%0], [%1, {%3, %4, %5}], [%2];"
      ::"r"(dst), "l"(m), "r"(bar), "r"(c0), "r"(c1), "r"(c2) : "memory");
}
__device__ __forceinline__ void tma3d_mc(uint32_t dst, const CUtensorMap* m, uint32_t bar, int c0, int c1, int c2) {
  asm volatile(
      "cp.async.bulk.tensor.3d.shared::cluster.global.mbarrier::complete_tx::bytes.multicast::cluster"
      " [%0], [%1, {%3, %4, %5}], [%2], %6;"
      ::"r"(dst), "l"(m), "r"(bar), "r"(c0), "r"(c1), "r"(c2), "h"((uint16_t)3) : "memory");
}
__device__ __forceinline__ void tma2d(uint32_t dst, const CUtensorMap* m, uint32_t bar, int c0, int c1) {
  asm volatile(
      "cp.async.bulk.tensor.2d.shared::cluster.global.mbarrier::complete_tx::bytes [%0], [%1, {%3, %4}], [%2];"
      ::"r"(dst), "l"(m), "r"(bar), "r"(c0), "r"(c1) : "memory");
}
__device__ __forceinline__ void tma2d_store(const CUtensorMap* m, uint32_t src, int c0, int c1) {
  asm volatile("cp.async.bulk.tensor.2d.global.shared::cta.bulk_group [%0, {%2, %3}], [%1];"
               ::"l"(m), "r"(src), "r"(c0), "r"(c1) : "memory");
}
__device__ __forceinline__ bool elect() {
  uint32_t p;
  asm volatile("{\n.reg .pred p;\nelect.sync _|p, 0xffffffff;\nselp.b32 %0, 1, 0, p;\n}" : "=r"(p));
  return p;
}
__device__ __forceinline__ void bulk_load(uint32_t dst, const void* src, uint32_t bytes, uint32_t bar) {
  asm volatile("cp.async.bulk.shared::cluster.global.mbarrier::complete_tx::bytes [%0], [%1], %2, [%3];"
               ::"r"(dst), "l"(src), "r"(bytes), "r"(bar) : "memory");
}
__device__ __forceinline__ void bulk_store(void* dst, uint32_t src, uint32_t bytes) {
  asm volatile("cp.async.bulk.global.shared::cta.bulk_group [%0], [%1], %2;" ::"l"(dst), "r"(src), "r"(bytes)
               : "memory");
}
__device__ __forceinline__ void bulk_commit() { asm volatile("cp.async.bulk.commit_group;" ::: "memory"); }
__device__ __forceinline__ void bulk_wait_read() { asm volatile("cp.async.bulk.wait_group.read 0;" ::: "memory"); }
__device__ __forceinline__ void bulk_wait() { asm volatile("cp.async.bulk.wait_group 0;" ::: "memory"); }
__device__ __forceinline__ void l2_prefetch(const void* p, uint32_t bytes) {
  asm volatile("cp.async.bulk.prefetch.L2.global [%0], %1;" ::"l"(p), "r"(bytes) : "memory");
}
__device__ __forceinline__ void fence_async_smem() { asm volatile("fence.proxy.async.shared::cta;" ::: "memory"); }
__device__ __forceinline__ unsigned ld_relaxed(const unsigned* p) {
  unsigned v;
  asm volatile("ld.relaxed.gpu.global.u32 %0, [%1];" : "=r"(v) : "l"(p) : "memory");
  return v;
}
__device__ __forceinline__ uint2 ld_relaxed2(const uint2* p) {
  uint2 v;
  asm volatile("ld.relaxed.gpu.global.v2.u32 {%0, %1}, [%2];" : "=r"(v.x), "=r"(v.y) : "l"(p) : "memory");
  return v;
}
__device__ __forceinline__ void st_relaxed(unsigned* p, unsigned v) {
  asm volatile("st.relaxed.gpu.global.u32 [%0], %1;" ::"l"(p), "r"(v) : "memory");
}
__device__ __forceinline__ void st_release(unsigned* p, unsigned v) {
  asm volatile("st.release.gpu.global.u32 [%0], %1;" ::"l"(p), "r"(v) : "memory");
}
#define ACQ_MODE 1
__device__ __forceinline__ void wait_flags(const unsigned* p, unsigned epoch) {
  unsigned spins = 0;
  while (true) {
    const unsigned v = ld_relaxed(p);
    if (__all_sync(0xffffffffu, v == epoch)) break;
    if (++spins > kSpinLimit) __trap();
  }
  if (ACQ_MODE) asm volatile("fence.acquire.gpu;\nfence.proxy.async.global;" ::: "memory");
  __syncwarp();
}
__device__ __forceinline__ unsigned tag_value(float v, unsigned epoch) {
  return (__float_as_uint(v) & ~7u) | (epoch & 7u);
}
__device__ __forceinline__ float untag_value(unsigned v) { return __uint_as_float(v & ~7u); }
__device__ __forceinline__ void stsm4(uint32_t a, uint32_t r0, uint32_t r1, uint32_t r2, uint32_t r3) {
  asm volatile("stmatrix.sync.aligned.m8n8.x4.shared.b16 [%0], {%1, %2, %3, %4};" ::"r"(a), "r"(r0), "r"(r1),
               "r"(r2), "r"(r3) : "memory");
}
__device__ __forceinline__ void stsm4_t(uint32_t a, uint32_t r0, uint32_t r1, uint32_t r2, uint32_t r3) {
  asm volatile("stmatrix.sync.aligned.m8n8.x4.trans.shared.b16 [%0], {%1, %2, %3, %4};" ::"r"(a), "r"(r0),
               "r"(r1), "r"(r2), "r"(r3) : "memory");
}
__device__ __forceinline__ uint32_t transpose8(uint32_t a) {
  uint32_t d;
  asm volatile("movmatrix.sync.aligned.m8n8.trans.b16 %0, %1;" : "=r"(d) : "r"(a));
  return d;
}
__device__ __forceinline__ void mma16816(float (&c)[4], uint32_t a0, uint32_t a1, uint32_t a2, uint32_t a3,
                                         uint32_t b0, uint32_t b1) {
  asm volatile("mma.sync.aligned.m16n8k16.row.col.f32.bf16.bf16.f32 {%0, %1, %2, %3}, {%4, %5, %6, %7}, {%8, %9}, "
               "{%0, %1, %2, %3};"
               : "+f"(c[0]), "+f"(c[1]), "+f"(c[2]), "+f"(c[3])
               : "r"(a0), "r"(a1), "r"(a2), "r"(a3), "r"(b0), "r"(b1));
}
__device__ __forceinline__ float shfl_xor(float v, int m) {
  float r;
  asm volatile("shfl.sync.bfly.b32 %0, %1, %2, 31, 0xffffffff;" : "=f"(r) : "f"(v), "r"(m));
  return r;
}
__device__ __forceinline__ float tanh_fast(float x) {
  float r;
  asm volatile("tanh.approx.f32 %0, %1;" : "=f"(r) : "f"(x));
  return r;
}
__device__ __forceinline__ void ldsm4(uint32_t a, uint32_t (&r)[4]) {
  asm volatile("ldmatrix.sync.aligned.m8n8.x4.shared.b16 {%0, %1, %2, %3}, [%4];"
               : "=r"(r[0]), "=r"(r[1]), "=r"(r[2]), "=r"(r[3]) : "r"(a) : "memory");
}
__device__ __forceinline__ uint32_t pack2(float lo, float hi) {
  uint32_t r;
  asm volatile("cvt.rn.bf16x2.f32 %0, %1, %2;" : "=r"(r) : "f"(hi), "f"(lo));
  return r;
}
__device__ __forceinline__ float bf_lo(uint32_t r) { return __uint_as_float(r << 16); }
__device__ __forceinline__ float bf_hi(uint32_t r) { return __uint_as_float(r & 0xffff0000u); }
__device__ __forceinline__ float ex2(float x) {
  float r;
  asm("ex2.approx.ftz.f32 %0, %1;" : "=f"(r) : "f"(x));
  return r;
}
__device__ __forceinline__ float rcp(float x) {
  float r;
  asm("rcp.approx.ftz.f32 %0, %1;" : "=f"(r) : "f"(x));
  return r;
}
template <int N>
__device__ __forceinline__ void wg_wait() {
  asm volatile("wgmma.wait_group.sync.aligned %0;" ::"n"(N) : "memory");
}
__device__ __forceinline__ void yield_slot() { asm volatile("pmevent 0;"); }
__device__ __forceinline__ void wg_bar(int wg) { asm volatile("bar.sync %0, 128;" ::"r"(wg + 1) : "memory"); }

template <int N, bool SPLIT>
__device__ __forceinline__ void mma_kblock(float (&acc)[2][96], uint32_t a, uint32_t b);

#define F8(d, i) \
  "+f"(d[i]), "+f"(d[i + 1]), "+f"(d[i + 2]), "+f"(d[i + 3]), "+f"(d[i + 4]), "+f"(d[i + 5]), "+f"(d[i + 6]), "+f"(d[i + 7])
#define KSTEP(N, A, B, oa0, oa1, ob)                                                       \
  "add.u32 t, " B ", " #ob ";\nmov.b64 db, {t, hb};\n"                                      \
  "add.u32 t, " A ", " #oa0 ";\nmov.b64 da, {t, ha};\n"                                     \
  "wgmma.mma_async.sync.aligned.m64n" #N "k16.f32.bf16.bf16 {" ACC##N##_0 "}, da, db, 1, 1, 1, 0, 1;\n" \
  "add.u32 t, " A ", " #oa1 ";\nmov.b64 da, {t, ha};\n"                                     \
  "wgmma.mma_async.sync.aligned.m64n" #N "k16.f32.bf16.bf16 {" ACC##N##_1 "}, da, db, 1, 1, 1, 0, 1;\n"

#define MMA_KBLOCK(N, SPLIT, A, B, ob2, ob3, MID)                                          \
  template <>                                                                              \
  __device__ __forceinline__ void mma_kblock<N, SPLIT>(float (&acc)[2][96], uint32_t a, uint32_t b) { \
    asm volatile("{\n.reg .b32 t, ha, hb;\n.reg .b64 da, db;\n"                            \
                 "mov.b32 ha, 0x40000080;\nmov.b32 hb, 0x40000040;\n"                       \
                 "wgmma.fence.sync.aligned;\n"                                             \
                 KSTEP(N, A, B, 0, 64, 0) KSTEP(N, A, B, 2, 66, 128) KSTEP(N, A, B, 4, 68, ob2) \
                 MID KSTEP(N, A, B, 6, 70, ob3) "wgmma.commit_group.sync.aligned;\n}\n"     \
                 : OPS##N : "r"(a), "r"(b) : "memory");                                    \
  }

#define ACC128_0 \
  "%0, %1, %2, %3, %4, %5, %6, %7, %8, %9, %10, %11, %12, %13, %14, %15, " \
  "%16, %17, %18, %19, %20, %21, %22, %23, %24, %25, %26, %27, %28, %29, %30, %31, " \
  "%32, %33, %34, %35, %36, %37, %38, %39, %40, %41, %42, %43, %44, %45, %46, %47, " \
  "%48, %49, %50, %51, %52, %53, %54, %55, %56, %57, %58, %59, %60, %61, %62, %63"
#define ACC128_1 \
  "%64, %65, %66, %67, %68, %69, %70, %71, %72, %73, %74, %75, %76, %77, %78, %79, " \
  "%80, %81, %82, %83, %84, %85, %86, %87, %88, %89, %90, %91, %92, %93, %94, %95, " \
  "%96, %97, %98, %99, %100, %101, %102, %103, %104, %105, %106, %107, %108, %109, %110, %111, " \
  "%112, %113, %114, %115, %116, %117, %118, %119, %120, %121, %122, %123, %124, %125, %126, %127"
#define OPS128 \
  F8(acc[0], 0), F8(acc[0], 8), F8(acc[0], 16), F8(acc[0], 24), F8(acc[0], 32), F8(acc[0], 40), F8(acc[0], 48), F8(acc[0], 56), \
        F8(acc[1], 0), F8(acc[1], 8), F8(acc[1], 16), F8(acc[1], 24), F8(acc[1], 32), F8(acc[1], 40), F8(acc[1], 48), F8(acc[1], 56)
MMA_KBLOCK(128, false, "%128", "%129", 512, 640, "")
MMA_KBLOCK(128, true, "%128", "%129", 512, 640, "wgmma.commit_group.sync.aligned;\n")

#define ACC192_0 \
  "%0, %1, %2, %3, %4, %5, %6, %7, %8, %9, %10, %11, %12, %13, %14, %15, " \
  "%16, %17, %18, %19, %20, %21, %22, %23, %24, %25, %26, %27, %28, %29, %30, %31, " \
  "%32, %33, %34, %35, %36, %37, %38, %39, %40, %41, %42, %43, %44, %45, %46, %47, " \
  "%48, %49, %50, %51, %52, %53, %54, %55, %56, %57, %58, %59, %60, %61, %62, %63, " \
  "%64, %65, %66, %67, %68, %69, %70, %71, %72, %73, %74, %75, %76, %77, %78, %79, " \
  "%80, %81, %82, %83, %84, %85, %86, %87, %88, %89, %90, %91, %92, %93, %94, %95"
#define ACC192_1 \
  "%96, %97, %98, %99, %100, %101, %102, %103, %104, %105, %106, %107, %108, %109, %110, %111, " \
  "%112, %113, %114, %115, %116, %117, %118, %119, %120, %121, %122, %123, %124, %125, %126, %127, " \
  "%128, %129, %130, %131, %132, %133, %134, %135, %136, %137, %138, %139, %140, %141, %142, %143, " \
  "%144, %145, %146, %147, %148, %149, %150, %151, %152, %153, %154, %155, %156, %157, %158, %159, " \
  "%160, %161, %162, %163, %164, %165, %166, %167, %168, %169, %170, %171, %172, %173, %174, %175, " \
  "%176, %177, %178, %179, %180, %181, %182, %183, %184, %185, %186, %187, %188, %189, %190, %191"
#define OPS192 \
  F8(acc[0], 0), F8(acc[0], 8), F8(acc[0], 16), F8(acc[0], 24), F8(acc[0], 32), F8(acc[0], 40), F8(acc[0], 48), F8(acc[0], 56), F8(acc[0], 64), F8(acc[0], 72), F8(acc[0], 80), F8(acc[0], 88), \
        F8(acc[1], 0), F8(acc[1], 8), F8(acc[1], 16), F8(acc[1], 24), F8(acc[1], 32), F8(acc[1], 40), F8(acc[1], 48), F8(acc[1], 56), F8(acc[1], 64), F8(acc[1], 72), F8(acc[1], 80), F8(acc[1], 88)
MMA_KBLOCK(192, false, "%192", "%193", 768, 896, "")
MMA_KBLOCK(192, true, "%192", "%193", 768, 896, "wgmma.commit_group.sync.aligned;\n")

enum { kModePlain = 0, kModeHead = 1, kModeSkip = 2, kModeContinue = 3 };

template <int N>
__device__ __forceinline__ void fence_acc(float (&acc)[2][96]) {
#pragma unroll
  for (int h = 0; h < 2; h++)
#pragma unroll
    for (int i = 0; i < N / 2; i++) asm volatile("" : "+f"(acc[h][i])::"memory");
}

template <int N>
__device__ __forceinline__ void zero_acc(float (&acc)[2][96]) {
#pragma unroll
  for (int h = 0; h < 2; h++)
#pragma unroll
    for (int i = 0; i < N / 2; i++) acc[h][i] = 0.f;
}

constexpr uint32_t kToB = (kTileBytes >> 4) + ((4096u >> 4) << 16) - (1u << 16);

#define TRACE_KB(nb)

#define HEAD_BOTH 0
template <int N>
__device__ __forceinline__ void head_blocks(float (&acc)[2][96], uint32_t sb, int n0, int slot, uint32_t xbar,
                                            uint32_t rel_addr, bool rel) {
  const uint32_t ring = (((sb & 0x3FFFF) + kSmRing) >> 4) | (1u << 16);
  const uint32_t xdesc = (((sb & 0x3FFFF) + kSmX) >> 4) | (1u << 16);
  const uint32_t nb = n0 * 8;
  fence_acc<N>(acc);
  mbar_wait(xbar + 8 * HEAD_BOTH, 0);
  mbar_wait(sb + kBarFull + (nb & 56), nb >> 6);
  TRACE_KB(nb);
  mma_kblock<N, false>(acc, xdesc, ring + slot * 2560 + kToB);
  mbar_wait(xbar + 8, 0);
  mbar_wait(sb + kBarFull + (nb & 56) + 8, nb >> 6);
  TRACE_KB(nb + 8);
  mma_kblock<N, false>(acc, xdesc + (kTileBytes >> 4), ring + ((slot + 1) & 3) * 2560 + kToB);
  wg_wait<1>();
  if (rel) mbar_arrive_cluster(rel_addr + (nb & 56));
  wg_wait<0>();
  if (rel) mbar_arrive_cluster(rel_addr + (nb & 56) + 8);
  fence_acc<N>(acc);
}

template <int N, class Pre>
__device__ __forceinline__ void mainloop(float (&acc)[2][96], uint32_t sb, int tile, int n0, int slot, int nkb,
                                         int pause_kk, int att, uint32_t rel_addr, bool rel, Pre pre) {
  constexpr uint32_t kStep = (N == 192 ? 5 : 4) * 512;
  const uint32_t ring = (((sb & 0x3FFFF) + kSmRing) >> 4) | (1u << 16);
  uint32_t st = ring + slot * kStep;
  uint32_t nb = n0 * 8, prev = 64;
  const uint32_t last = nb + 8 * (nkb - 1);
  uint32_t stop = pause_kk >= 0 ? nb + 8 * pause_kk : last;
  const bool signal = (threadIdx.x & 127) == 64;
  fence_acc<N>(acc);
  if (tile > 0) mbar_wait(sb + kBarTurn + (tile - 1) * 8, 0);
  TRACE_AT(tile, 0);
#pragma unroll 1
  while (true) {
#pragma unroll 1
    do {
      mbar_wait(sb + kBarFull + (nb & 56), nb >> 6);
      if (nb == n0 * 8) TRACE_AT(tile, 1);
      TRACE_KB(nb);
      mma_kblock<N, false>(acc, st, st + kToB);
      wg_wait<1>();
      if (rel) mbar_arrive_cluster(rel_addr + prev);
      prev = nb & 56;
      st += kStep;
      if (st == ring + 10240) st = ring;
      nb += 8;
    } while (nb != stop);
    if (stop == last) break;
    stop = last;
    if (signal) mbar_arrive(sb + kBarPause + att * 8);
    wg_wait<0>();
    if (rel) mbar_arrive_cluster(rel_addr + prev);
    prev = 64;
    mbar_wait(sb + kBarResume + att * 8, 0);
  }
  mbar_wait(sb + kBarFull + (nb & 56), nb >> 6);
  TRACE_KB(nb);
  mma_kblock<N, true>(acc, st, st + kToB);
  wg_wait<2>();
  if (rel) mbar_arrive_cluster(rel_addr + prev);
  pre();
  wg_wait<1>();
  if (signal) mbar_arrive(sb + kBarTurn + tile * 8);
  wg_wait<0>();
  if (rel) mbar_arrive_cluster(rel_addr + (nb & 56));
  fence_acc<N>(acc);
}

__device__ __forceinline__ void publish_stats(uint32_t sb, uint2* stat, int w, int lane, unsigned epoch) {
  const uint32_t row = sb + kSmX + (32 * w + lane) * 128;
  float s[4], q[4];
#pragma unroll
  for (int c = 0; c < 4; c++) s[c] = q[c] = 0.f;
  uint32_t nx[4];
  ldsm4(row + ((lane & 7) << 4), nx);
#pragma unroll 1
  for (int J = 1; J <= 16; J++) {
    const uint32_t r[4] = {nx[0], nx[1], nx[2], nx[3]};
    ldsm4(row + ((J >> 3) & 1) * kTileBytes + (((J ^ lane) & 7) << 4), nx);
#pragma unroll
    for (int c = 0; c < 4; c++) {
      const float lo = bf_lo(r[c]);
      s[c] += lo;
      q[c] = fmaf(lo, lo, q[c]);
      if (c & 1) yield_slot();
    }
#pragma unroll
    for (int c = 0; c < 4; c++) {
      const float hi = bf_hi(r[c]);
      s[c] += hi;
      q[c] = fmaf(hi, hi, q[c]);
      if (c & 1) yield_slot();
    }
  }
#pragma unroll
  for (int c = 0; c < 4; c++) {
    s[c] += shfl_xor(s[c], 1);
    q[c] += shfl_xor(q[c], 1);
    s[c] += shfl_xor(s[c], 2);
    q[c] += shfl_xor(q[c], 2);
  }
  const int t = lane & 3, g = lane >> 2;
  const float so = t == 0 ? s[0] : t == 1 ? s[1] : t == 2 ? s[2] : s[3];
  const float qo = t == 0 ? q[0] : t == 1 ? q[1] : t == 2 ? q[2] : q[3];
  asm volatile("st.relaxed.gpu.global.v2.u32 [%0], {%1, %2};" ::"l"(stat + 32 * w + 8 * t + g),
               "r"(tag_value(so, epoch)), "r"(tag_value(qo, epoch)) : "memory");
}

__device__ __forceinline__ void add_chunk(float (&a)[8], const uint4& v) {
  a[0] += bf_lo(v.x); a[1] += bf_hi(v.x);
  a[2] += bf_lo(v.y); a[3] += bf_hi(v.y);
  a[4] += bf_lo(v.z); a[5] += bf_hi(v.z);
  a[6] += bf_lo(v.w); a[7] += bf_hi(v.w);
}

__device__ __forceinline__ int helper_col(int id, int slab) {
  return slab < 6 ? (slab % 3) * kD + (slab / 3) * 512 + id * 128 : (slab - 6) * 512 + id * 128;
}
__device__ __forceinline__ void helper_cta(const CUtensorMap* map_q, const CUtensorMap* map_1, uint8_t* sm,
                                           uint32_t sb, int id, int warp) {
  constexpr int kRed = 6 * 32768, kBar = kRed + 2 * 4096;
  const int tid = threadIdx.x;
  if (warp == 8 && elect()) {
#pragma unroll
    for (int s = 0; s < 6; s++) {
      mbar_init(sb + kBar + s * 8, 1);
      mbar_init(sb + kBar + 64 + s * 8, 4);
    }
    fence_async_smem();
#pragma unroll
    for (int s = 0; s < 6; s++) {
      mbar_expect_tx(sb + kBar + s * 8, 32768);
      tma2d(sb + s * 32768, map_q, sb + kBar + s * 8, id * 128, s * 128);
    }
  }
  __syncthreads();
  if (warp == 8) {
    int slot = 0, ph = 0;
#pragma unroll 1
    for (int n = 6; n < 104; n++) {
      mbar_wait(sb + kBar + 64 + slot * 8, ph);
      if (elect()) {
        mbar_expect_tx(sb + kBar + slot * 8, 32768);
        tma2d(sb + slot * 32768, n < 48 ? map_q : map_1, sb + kBar + slot * 8, helper_col(id, n >> 3), (n & 7) * 128);
      }
      if (++slot == 6) slot = 0, ph ^= 1;
    }
  } else if (warp < 8) {
    if (tid == 0) *reinterpret_cast<unsigned*>(sm + kBar + 128) = atomicAdd(&g_ticket, 1u) / kGrid + 1;
    int slot = warp >> 2, ph = 0;
#pragma unroll 1
    for (int slab = 0; slab < 13; slab++) {
      float a[8];
#pragma unroll
      for (int e = 0; e < 8; e++) a[e] = 0.f;
#pragma unroll 1
      for (int box = 0; box < 4; box++) {
        mbar_wait(sb + kBar + slot * 8, ph);
        const uint4* p = reinterpret_cast<const uint4*>(sm + slot * 32768) + (tid & 127);
        uint4 v[16];
#pragma unroll
        for (int i = 0; i < 16; i++) v[i] = p[i * 128];
        __syncwarp();
        if (elect()) mbar_arrive(sb + kBar + 64 + slot * 8);
#pragma unroll
        for (int i = 0; i < 16; i++) add_chunk(a, v[i]);
        slot += 2;
        if (slot >= 6) slot -= 6, ph ^= 1;
      }
      float* red = reinterpret_cast<float*>(sm + kRed + (slab & 1) * 4096);
#pragma unroll
      for (int e = 0; e < 8; e++) a[e] += shfl_xor(a[e], 16);
      if ((tid & 16) == 0) {
        float4* d = reinterpret_cast<float4*>(red + warp * 128 + (tid & 15) * 8);
        d[0] = make_float4(a[0], a[1], a[2], a[3]);
        d[1] = make_float4(a[4], a[5], a[6], a[7]);
      }
      asm volatile("bar.sync 1, 256;" ::: "memory");
      if (warp < 4) {
        float t = 0.f;
#pragma unroll
        for (int q = 0; q < 8; q++) t += red[q * 128 + tid];
        st_relaxed(g_cs + (slab < 6 ? 0 : 3 * kD) + helper_col(id, slab) + tid,
                   tag_value(t, *reinterpret_cast<volatile unsigned*>(sm + kBar + 128)));
      }
    }
  }
}

constexpr float kGelu0 = 2.f * 0.7978845608028654f;
constexpr float kGelu1 = 8.f * 0.7978845608028654f * 0.044715f;

__device__ __forceinline__ void store_staged(uint8_t* dst, uint32_t stg) {
  fence_async_smem();
  __syncwarp();
  if (elect()) {
    bulk_store(dst, stg, 4096);
    bulk_commit();
  }
}

#define GY_MASK 0x3F
#define GY_MASK2 0
#define GY(k) if (((CH == 2 ? GY_MASK2 : GY_MASK) >> k) & 1) yield_slot()
template <int CH>
__device__ __forceinline__ void gelu_chunk(const float (&acc)[2][96], const float2 (&st)[4], const float4* vec,
                                           uint32_t stg, int lane, uint8_t* prev) {
  uint32_t pk[8][4];
  float u[3][4], z[3][4];
  float4 v = vec[CH * 32], vn = v;
#pragma unroll
  for (int s = 0; s < 18; s++) {
    const int J = CH * 8 + (s >> 1), c0 = 2 * (s & 1), cur = s % 3, p1 = (s + 2) % 3, p2 = (s + 1) % 3;
    if (s < 16) {
      if (c0 == 0 && s < 14) vn = vec[(J + 1) * 4];
#pragma unroll
      for (int e = 0; e < 4; e++) {
        const int c = c0 + (e >> 1);
        z[cur][e] = fmaf(st[c].y, e & 1 ? v.y : v.x, e & 1 ? v.w : v.z);
      }
      if (c0 == 2) v = vn;
    }
    if (s >= 1 && s < 17) z[p1][0] = tanh_fast(z[p1][0]);
    GY(0);
    if (s < 16) {
#pragma unroll
      for (int e = 0; e < 4; e++) {
        const int c = c0 + (e >> 1);
        u[cur][e] = fmaf(acc[c & 1][4 * J + c0 + (e & 1)], st[c].x, z[cur][e]);
      }
    }
    if (s >= 11) {
      const int jj = s - 11;
      stsm4(stg + lane * 128 + ((jj ^ (lane & 7)) << 4), pk[jj][0], pk[jj][1], pk[jj][2], pk[jj][3]);
    }
    GY(1);
    if (s < 16) {
#pragma unroll
      for (int e = 0; e < 4; e++) z[cur][e] = u[cur][e] * u[cur][e];
    }
    if (s >= 1 && s < 17) z[p1][1] = tanh_fast(z[p1][1]);
    GY(2);
    if (s < 16) {
#pragma unroll
      for (int e = 0; e < 4; e++) z[cur][e] = fmaf(z[cur][e], kGelu1, kGelu0);
    }
    if (s >= 1 && s < 17) z[p1][2] = tanh_fast(z[p1][2]);
    GY(3);
    if (s >= 2) {
      pk[(s - 2) >> 1][c0] = pack2(fmaf(u[p2][0], z[p2][0], u[p2][0]), fmaf(u[p2][1], z[p2][1], u[p2][1]));
      pk[(s - 2) >> 1][c0 + 1] = pack2(fmaf(u[p2][2], z[p2][2], u[p2][2]), fmaf(u[p2][3], z[p2][3], u[p2][3]));
    }
    GY(4);
    if (s < 16) {
#pragma unroll
      for (int e = 0; e < 4; e++) z[cur][e] = u[cur][e] * z[cur][e];
    }
    if (s >= 1 && s < 17) z[p1][3] = tanh_fast(z[p1][3]);
    GY(5);
    if (CH > 0 && s == 1) store_staged(prev, stg);
    if (CH > 0 && s == 10) {
      if (elect()) bulk_wait_read();
      __syncwarp();
    }
  }
  stsm4(stg + lane * 128 + ((7 ^ (lane & 7)) << 4), pk[7][0], pk[7][1], pk[7][2], pk[7][3]);
}

__device__ __forceinline__ void epilogue_gelu(const float (&acc)[2][96], float2 (&st)[4], uint8_t* sm, uint32_t sb,
                                              bool wide, int vcol0, uint8_t* dst, int tile, int w) {
  const int lane = threadIdx.x & 31, t = lane & 3;
#pragma unroll
  for (int c = 0; c < 4; c++) {
    st[c].x *= 0.5f;
    st[c].y *= st[c].x;
  }
  const float4* vec = reinterpret_cast<const float4*>(sm + kSmV1) + vcol0 / 2 + t;
  const uint32_t stg = sb + kSmStg + w * 4096;
  TRACE_AT(tile, 8);
  gelu_chunk<0>(acc, st, vec, stg, lane, dst);
  TRACE_AT(tile, 9);
  gelu_chunk<1>(acc, st, vec, stg, lane, dst);
  TRACE_AT(tile, 10);
  if (wide) gelu_chunk<2>(acc, st, vec, stg, lane, dst + kTileBytes);
  store_staged(dst + (wide ? 2 : 1) * kTileBytes, stg);
  TRACE_AT(tile, 11);
  if (elect()) {
    bulk_wait();
    TRACE_AT(tile, 12);
    mbar_arrive(sb + kBarEpi + tile * 8);
  }
  __syncwarp();
}

__device__ __forceinline__ void add_mean_term(float (&acc)[2][96], const float2 (&st)[4], uint8_t* sm, int tq,
                                              int lane) {
  const float2* cs = reinterpret_cast<const float2*>(sm + kSmCsQ) + tq * 96 + (lane & 3);
  float2 vn = cs[0];
#pragma unroll
  for (int J = 0; J < 24; J++) {
    const float2 v = vn;
    if (J < 23) vn = cs[J * 4 + 4];
#pragma unroll
    for (int c = 0; c < 4; c++) {
      acc[c & 1][4 * J + (c & 2)] = fmaf(st[c].y, v.x, acc[c & 1][4 * J + (c & 2)]);
      acc[c & 1][4 * J + (c & 2) + 1] = fmaf(st[c].y, v.y, acc[c & 1][4 * J + (c & 2) + 1]);
    }
    yield_slot();
  }
}

#define HALO_AT 2
__device__ __forceinline__ void epilogue_attn(const float (&acc)[2][96], const float2 (&st)[4], uint8_t* sm,
                                              uint32_t sb, int layer, int tq, int b, int j, unsigned epoch, int tile,
                                              int wg, int w) {
  const int lane = threadIdx.x & 31, t = lane & 3, g = lane >> 2;
  const int hp = j + 8 * tq, att = 2 * layer + tq;
  uint32_t q[4][8], k[5][8], vt[5][8];
#define SCALED(c, J) pack2(acc[(c) & 1][4 * (J) + ((c) & 2)] * st[c].x, acc[(c) & 1][4 * (J) + ((c) & 2) + 1] * st[c].x)
#pragma unroll
  for (int J = 0; J < 8; J++) vt[4][J] = transpose8(SCALED(3, 16 + J));
#pragma unroll
  for (int J = 0; J < 8; J++) k[4][J] = SCALED(3, 8 + J);
  if (w < 3) {
    uint4* hs = reinterpret_cast<uint4*>(sm + kSmHalo + w * 2048) + lane;
    hs[0] = make_uint4(k[4][0], k[4][1], k[4][2], k[4][3]);
    hs[32] = make_uint4(k[4][4], k[4][5], k[4][6], k[4][7]);
    hs[64] = make_uint4(vt[4][0], vt[4][1], vt[4][2], vt[4][3]);
    hs[96] = make_uint4(vt[4][4], vt[4][5], vt[4][6], vt[4][7]);
  } else if ((b & 7) != 7) {
    uint4* gh = g_halo + ((layer * 16 + b) * 16 + hp) * 256 + lane;
#pragma unroll
    for (int i = 0; i < 8; i++)
      asm volatile("{\n.reg .b64 x, y;\nmov.b64 x, {%1, %3};\nmov.b64 y, {%2, %3};\n"
                   "st.relaxed.gpu.global.v2.b64 [%0], {x, y};\n}" ::"l"(gh + i * 32),
                   "r"(k[4][i]), "r"(vt[4][i]), "r"(epoch) : "memory");
  }
#pragma unroll
  for (int c = 0; c < 3; c++)
#pragma unroll
    for (int J = 0; J < 8; J++) {
      k[c + 1][J] = SCALED(c, 8 + J);
      vt[c + 1][J] = transpose8(SCALED(c, 16 + J));
      yield_slot();
    }
  const bool first = w == 0 && (b & 7) == 0;
  const uint4* gh = g_halo + ((layer * 16 + b - 1) * 16 + hp) * 256 + lane;
  uint32_t tag[16];
#define LOAD_HALO(i)                                                                         \
  asm volatile("{\n.reg .b64 x, y;\nld.relaxed.gpu.global.v2.b64 {x, y}, [%4];\n"            \
               "mov.b64 {%0, %1}, x;\nmov.b64 {%2, %3}, y;\n}"                               \
               : "=r"(k[0][i]), "=r"(tag[2 * i]), "=r"(vt[0][i]), "=r"(tag[2 * i + 1])        \
               : "l"(gh + i * 32) : "memory")
#pragma unroll
  for (int c = 0; c <= 4; c++) {
    if (c == HALO_AT) {
      if (w == 0 && !first) {
#pragma unroll
        for (int i = 0; i < 8; i++) LOAD_HALO(i);
      } else {
#pragma unroll
        for (int i = 0; i < 8; i++) k[0][i] = vt[0][i] = tag[2 * i] = tag[2 * i + 1] = 0u;
      }
    }
#pragma unroll
    for (int J = 0; J < 8 && c < 4; J++) {
      q[c & 3][J] = SCALED(c & 3, J);
      if (J & 1) yield_slot();
    }
  }
#undef SCALED
  TRACE_AT(tile, 8);
  wg_bar(wg);
  if (w > 0) {
    const uint4* hs = reinterpret_cast<const uint4*>(sm + kSmHalo + (w - 1) * 2048) + lane;
    const uint4 a0 = hs[0], a1 = hs[32], a2 = hs[64], a3 = hs[96];
    k[0][0] = a0.x; k[0][1] = a0.y; k[0][2] = a0.z; k[0][3] = a0.w;
    k[0][4] = a1.x; k[0][5] = a1.y; k[0][6] = a1.z; k[0][7] = a1.w;
    vt[0][0] = a2.x; vt[0][1] = a2.y; vt[0][2] = a2.z; vt[0][3] = a2.w;
    vt[0][4] = a3.x; vt[0][5] = a3.y; vt[0][6] = a3.z; vt[0][7] = a3.w;
  } else if (!first) {
    unsigned spins = 0;
    while (true) {
      unsigned d0 = 0, d1 = 0, d2 = 0, d3 = 0;
#pragma unroll
      for (int i = 0; i < 4; i++) {
        d0 |= tag[i] ^ epoch;
        d1 |= tag[4 + i] ^ epoch;
        d2 |= tag[8 + i] ^ epoch;
        d3 |= tag[12 + i] ^ epoch;
      }
      if (__all_sync(0xffffffffu, (d0 | d1 | d2 | d3) == 0)) break;
      if (++spins > kSpinLimit) __trap();
#pragma unroll
      for (int i = 0; i < 8; i++) LOAD_HALO(i);
    }
  }
#undef LOAD_HALO
  TRACE_AT(tile, 9);
  mbar_wait(sb + kBarPause + att * 8, 0);
  TRACE_AT(tile, 10);

  float s[2][5][4];
#pragma unroll
  for (int hd = 0; hd < 2; hd++)
#pragma unroll
    for (int kg = 0; kg < 5; kg++) {
      const int ca = kg > 0 ? kg - 1 : 0, cb = kg < 4 ? kg : 3;
#pragma unroll
      for (int e = 0; e < 4; e++) s[hd][kg][e] = 0.f;
#pragma unroll
      for (int ks = 0; ks < 2; ks++) {
        const int J = 4 * hd + 2 * ks;
        mma16816(s[hd][kg], q[ca][J], q[cb][J], q[ca][J + 1], q[cb][J + 1], k[kg][J], k[kg][J + 1]);
      }
    }
  constexpr float kScale = 0.17677669529663687f * 1.4426950408889634f;
  const bool own0 = 2 * t <= g, own1 = 2 * t + 1 <= g;
  const uint32_t own_mask = (own0 ? 0xffffu : 0u) | (own1 ? 0xffff0000u : 0u);
  float o[2][4][2][4];
#pragma unroll
  for (int hd = 0; hd < 2; hd++) {
    float v0[4], v1[4], m[4];
#pragma unroll
    for (int c = 0; c < 4; c++) {
      float p0 = s[hd][c][2], p1 = s[hd][c][3];
      if (c == 0 && first) p0 = p1 = -INFINITY;
      v0[c] = own0 ? s[hd][c + 1][0] : p0;
      v1[c] = own1 ? s[hd][c + 1][1] : p1;
      m[c] = fmaxf(v0[c], v1[c]);
    }
#pragma unroll
    for (int c = 0; c < 4; c++) m[c] = fmaxf(m[c], shfl_xor(m[c], 1));
#pragma unroll
    for (int c = 0; c < 4; c++) m[c] = fmaxf(m[c], shfl_xor(m[c], 2));
#pragma unroll
    for (int c = 0; c < 4; c++) {
      const float nm = -m[c] * kScale;
      v0[c] = ex2(fmaf(v0[c], kScale, nm));
      v1[c] = ex2(fmaf(v1[c], kScale, nm));
      m[c] = v0[c] + v1[c];
    }
#pragma unroll
    for (int c = 0; c < 4; c++) m[c] += shfl_xor(m[c], 1);
#pragma unroll
    for (int c = 0; c < 4; c++) m[c] += shfl_xor(m[c], 2);
#pragma unroll
    for (int c = 0; c < 4; c++) {
      const float inv = rcp(m[c]);
      const uint32_t p = pack2(v0[c] * inv, v1[c] * inv);
#pragma unroll
      for (int ds = 0; ds < 2; ds++) {
        const int J = 4 * hd + 2 * ds;
#pragma unroll
        for (int e = 0; e < 4; e++) o[hd][c][ds][e] = 0.f;
        mma16816(o[hd][c][ds], vt[c][J], vt[c][J + 1], vt[c + 1][J], vt[c + 1][J + 1], p & ~own_mask, p & own_mask);
      }
    }
  }
  TRACE_AT(tile, 11);
  const uint32_t stg = sb + kSmStg + w * 4096;
#pragma unroll
  for (int J = 0; J < 8; J++) {
    const int hd = J >> 2, ds = (J >> 1) & 1, e = 2 * (J & 1);
    stsm4_t(stg + lane * 128 + ((J ^ (lane & 7)) << 4), pack2(o[hd][0][ds][e], o[hd][0][ds][e + 1]),
            pack2(o[hd][1][ds][e], o[hd][1][ds][e + 1]), pack2(o[hd][2][ds][e], o[hd][2][ds][e + 1]),
            pack2(o[hd][3][ds][e], o[hd][3][ds][e + 1]));
  }
  if (elect()) mbar_arrive(sb + kBarResume + att * 8);
  fence_async_smem();
  __syncwarp();
  TRACE_AT(tile, 12);
  if (elect()) {
    bulk_store(g_o + (b * 16 + hp) * kTileBytes + w * 4096, stg, 4096);
    bulk_commit();
    bulk_wait();
    TRACE_AT(tile, 13);
    mbar_arrive(sb + kBarEpi + tile * 8);
  }
  __syncwarp();
}

__device__ __forceinline__ void gather_stats(uint8_t* sm, const uint2* stat, unsigned epoch) {
  const int r = threadIdx.x & 127;
  uint2 a[8];
  unsigned spins = 0;
  while (true) {
    unsigned diff = 0;
#pragma unroll
    for (int i = 0; i < 8; i++) {
      a[i] = ld_relaxed2(stat + i * 128 + r);
      diff |= (a[i].x ^ epoch) | (a[i].y ^ epoch);
    }
    if (__all_sync(0xffffffffu, (diff & 7u) == 0)) break;
    if (++spins > kSpinLimit) __trap();
    __nanosleep(200);
  }
  float s = 0.f, q = 0.f;
#pragma unroll
  for (int i = 0; i < 8; i++) {
    s += untag_value(a[i].x);
    q += untag_value(a[i].y);
  }
  const float mean = s * (1.f / 1024.f);
  const float var = fmaxf(fmaf(-mean, mean, q * (1.f / 1024.f)), 0.f);
  reinterpret_cast<float2*>(sm + kSmStat)[r] = make_float2(rsqrtf(var + 1e-5f), -mean);
}

__device__ __forceinline__ void gather_colsums(uint8_t* sm, int part, int j, int lane, unsigned epoch) {
#pragma unroll 1
  for (int blk = part < 4 ? 0 : 2 * part - 5; blk < (part < 4 ? 3 : 2 * part - 3); blk++) {
    const int col = part < 2 ? blk * kD + (j + 8 * part) * 64
                             : 3 * kD + 64 * (blk + (blk < 3 ? 3 * j : blk < 5 ? 21 + 2 * j : 35 + 2 * j));
    uint2 v;
    unsigned spins = 0;
    while (true) {
      v = ld_relaxed2(reinterpret_cast<const uint2*>(g_cs + col) + lane);
      if (__all_sync(0xffffffffu, (((v.x ^ epoch) | (v.y ^ epoch)) & 7u) == 0)) break;
      if (++spins > kSpinLimit) __trap();
      __nanosleep(100);
    }
    uint8_t* dst = part < 2 ? sm + kSmCsQ + (part * 96 + blk * 32 + lane) * 8 : sm + kSmV1 + (blk * 32 + lane) * 16;
    *reinterpret_cast<float2*>(dst) = make_float2(untag_value(v.x), untag_value(v.y));
  }
}

#define READBACK 0
#define PF_START 0
#define PAUSE_QKV2 7
#define PAUSE_WO 1

__global__ void __cluster_dims__(2, 1, 1) __launch_bounds__(384, 1)
fused_layers_kernel(const __grid_constant__ CUtensorMap map_x, const __grid_constant__ CUtensorMap map_out,
                    const __grid_constant__ CUtensorMap map_qkv, const __grid_constant__ CUtensorMap map_wo,
                    const __grid_constant__ CUtensorMap map_w1a, const __grid_constant__ CUtensorMap map_w1b,
                    const __grid_constant__ CUtensorMap map_w2, const __grid_constant__ CUtensorMap map_csq,
                    const __grid_constant__ CUtensorMap map_cs1, const __grid_constant__ Params prm) {
  extern __shared__ __align__(1024) uint8_t sm[];
  if (threadIdx.x < 128 && blockIdx.x < kCtas) TRACE_AT(15, 1);
  const uint32_t sb = __shfl_sync(0xffffffffu, smem_u32(sm), 0);
  const int warp = __shfl_sync(0xffffffffu, threadIdx.x >> 5, 0), lane = threadIdx.x & 31;
  const int cta = blockIdx.x, rank = cta & 1, cl = cta >> 1;
  const int grp = cl < 4 ? 0 : cl < 36 ? (cl - 4) & 7 : 1 + (cl - 36) % 7;
  const int j = cl < 4 ? 4 + cl : cl < 36 ? (cl - 4) >> 3 : 4 + (cl - 36) / 7;
  const int b = 2 * grp + rank;
  const int xcol = (b >> 3) * kD, xrow = (b & 7) * 128;

  if (cta >= kCtas) {
    helper_cta(&map_csq, &map_cs1, sm, sb, cta - kCtas, warp);
    return;
  }
  if (warp >= 8 && elect()) {
    if (warp == 9) {
#pragma unroll
      for (int s = 0; s < 8; s++) mbar_init(sb + kBarFull + s * 8, 1);
      fence_async_smem();
#pragma unroll
      for (int s = 0; s < 4; s++) {
        const uint32_t full = sb + kBarFull + s * 8, dst = sb + kSmRing + s * 40960;
        mbar_expect_tx(full, 40960);
        tma2d(dst, &map_x, full, xcol + s * 64, xrow);
        tma3d(dst + kTileBytes, &map_qkv, full, j * 64, s * 64, 0);
        tma3d(dst + kTileBytes + 12288, &map_qkv, full, j * 64, s * 64 + 32, 0);
      }
      if (PF_START & 1) l2_prefetch(reinterpret_cast<const uint8_t*>(prm.x) + cta * 32768, 32768);
      if (PF_START & 2) l2_prefetch(reinterpret_cast<const uint8_t*>(prm.wqkv) + cta * 49152, 49152);
    } else if (warp == 8) {
      if (sb & 1023) __trap();
#pragma unroll
      for (int o = kBarTurn; o < kBarInit; o += 8) mbar_init(sb + o, 1);
    } else if (warp == 10) {
#pragma unroll
      for (int o = kBarEpoch; o < kSmEpoch; o += 8) mbar_init(sb + o, o < kBarEmpty ? 1 : o < kBarEpi ? 2 : 4);
    } else {
      mbar_init(sb + kBarInit, 1);
      fence_async_smem();
      mbar_expect_tx(sb + kBarInit, 32768);
      tma2d(sb + kSmX, &map_x, sb + kBarInit, xcol + j * 128, xrow);
      tma2d(sb + kSmX + kTileBytes, &map_x, sb + kBarInit, xcol + j * 128 + 64, xrow);
    }
    asm volatile("fence.mbarrier_init.release.cluster;" ::: "memory");
  }
  __syncwarp();
  asm volatile("barrier.cluster.arrive.relaxed.aligned;" ::: "memory");

  if (warp >= 8) {
    asm volatile("setmaxnreg.dec.sync.aligned.u32 40;");
    if (warp < 10) {
      asm volatile("barrier.cluster.wait.aligned;" ::: "memory");
      uint32_t nb = 32, off = 0, kb = 0;
#define RING_STEP(ISSUE)                                                  \
  do {                                                                    \
    const uint32_t mb = nb - depth, full = sb + kBarFull + (nb & 56);     \
    if (kb == skip) kb += 2;                                              \
    mbar_wait(sb + kBarEmpty + (mb & 56), mb >> 6);                       \
    if (elect()) { ISSUE; }                                               \
    TRACE_ISSUE(9 - warp, nb);                                            \
    kb += inc;                                                            \
    off = off == wrap ? 0 : off + step;                                   \
    nb += 8;                                                              \
  } while (nb != nend)
#pragma unroll 1
      for (int sg = 0; sg < kSegs; sg++) {
        const uint32_t e = prm.seg[sg];
        const int ty = e & 7, mode = (e >> 15) & 3, reset = (e >> 24) & 3;
        const uint32_t nend = nb + (e & 0x1f8);
        const uint32_t step = (e >> 17) & 1 ? 40960 : 32768, wrap = 163840 - step;
        const uint32_t depth = (e >> 18) & 1 ? 40 : 32;
        if (reset) off = reset == 1 ? 0 : reset == 2 ? 40960 : 131072;
        if (mode != kModeContinue) kb = ((e >> 9) & 63) + (mode == kModeHead ? 2 * j : 0);
        const uint32_t inc = mode >= kModeSkip ? 2 : 1, skip = mode >= kModeSkip ? 2 * j + (kb & 1) : 255;
        if (warp == 8) {
          const CUtensorMap* map = ty < 2 ? &map_qkv : ty == 2 ? &map_wo : ty == 3 ? &map_w1a : ty < 6 ? &map_w1b : &map_w2;
          const int c0 = ty < 2 ? (j + 8 * ty) * 64 : 0;
          const int c2 = ty < 2 ? 0 : ty == 3 ? 3 * j : ty == 4 ? 24 + 2 * j : ty == 5 ? 40 + 2 * j : 2 * j;
          const uint32_t half = (ty < 2 || ty == 3) ? 12288 : 8192;
          const uint32_t bytes = 2 * half + (mode == kModeHead ? 0 : kTileBytes);
          const uint32_t dst = sb + kSmRing + kTileBytes + rank * half;
#pragma unroll 1
          RING_STEP(mbar_expect_tx(full, bytes); tma3d_mc(dst + off, map, full, c0, kb * 64 + rank * 32, c2));
        } else if (mode == kModeHead) {
          nb = nend;
          off += 2 * step;
          if (off >= 163840) off -= 163840;
        } else if (sg < 2) {
#pragma unroll 1
          RING_STEP(tma2d(sb + kSmRing + off, &map_x, full, xcol + kb * 64, xrow));
        } else {
          const uint8_t* src = ty == 6 ? g_h + b * 56 * kTileBytes : (ty == 2 ? g_o : g_x) + b * 16 * kTileBytes;
          const int dep = (e >> 19) & 31;
          if (dep != 31) mbar_wait(sb + kBarReady + dep * 8, 0);
#pragma unroll 1
          RING_STEP(bulk_load(sb + kSmRing + off, src + kb * kTileBytes, kTileBytes, full));
        }
      }
#undef RING_STEP
    } else if (warp == 10) {
      unsigned epoch = 0;
      if (lane == 0) epoch = atomicAdd(&g_ticket, 1u) / kGrid + 1;
      epoch = __shfl_sync(0xffffffffu, epoch, 0);
      *reinterpret_cast<unsigned*>(sm + kSmEpoch) = epoch;
      asm volatile("barrier.cluster.wait.aligned;" ::: "memory");
      if (elect()) mbar_arrive(sb + kBarEpoch);
#pragma unroll 1
      for (int i = 0; i < kTiles - 1; i++) {
        const bool xt = i == 2 || i == 6 || i == 9;
        const unsigned* line = g_flag + (i * 16 + b) * 32;
        mbar_wait(sb + kBarEpi + i * 8, 0);
        wait_flags(line + (lane & 7), epoch);
        if (elect()) mbar_arrive(sb + kBarReady + i * 8);
        if (xt) {
          wait_flags(line + 8 + (lane & 7), epoch);
          if (elect()) mbar_arrive(sb + kBarReady + (14 + (i >> 2)) * 8);
        }
      }
    } else {
      {
        uint32_t v[7];
#pragma unroll
        for (int q = 0; q < 7; q++)
          v[q] = reinterpret_cast<const uint32_t*>(prm.b1)[32 * (q + (q < 3 ? 3 * j : q < 5 ? 21 + 2 * j : 35 + 2 * j)) + lane];
        const uint2 u = reinterpret_cast<const uint2*>(prm.b2)[32 * j + lane];
#pragma unroll
        for (int q = 0; q < 7; q++)
          *reinterpret_cast<float2*>(sm + kSmV1 + (q * 32 + lane) * 16 + 8) = make_float2(0.5f * bf_lo(v[q]), 0.5f * bf_hi(v[q]));
        reinterpret_cast<float4*>(sm + kSmB2)[lane] = make_float4(bf_lo(u.x), bf_hi(u.x), bf_lo(u.y), bf_hi(u.y));
      }
      asm volatile("barrier.cluster.wait.aligned;" ::: "memory");
      mbar_wait(sb + kBarEpoch, 0);
      const unsigned epoch = *reinterpret_cast<volatile unsigned*>(sm + kSmEpoch);
#pragma unroll 1
      for (int i = 0; i < kTiles - 1; i++) {
#pragma unroll 1
        for (int part = i == 4 ? 5 : i; part < (i < 2 ? i + 1 : i == 3 || i == 4 ? i + 2 : 0); part++) {
          gather_colsums(sm, part, j, lane, epoch);
          __syncwarp();
          if (elect()) mbar_arrive(sb + kBarCs + part * 8);
        }
        const bool xt = i == 2 || i == 6 || i == 9;
#pragma unroll 1
        for (int h = 0; h < (xt ? 2 : 1); h++) {
          if (h == 0) mbar_wait(sb + kBarEpi + i * 8, 0);
          if (h == 1 && elect()) {
            bulk_store(g_x + (b * 16 + 2 * j + 1) * kTileBytes, sb + kSmX + kTileBytes, kTileBytes);
            bulk_commit();
            bulk_wait();
          }
          __syncwarp();
          if (elect()) st_release(&g_flag[(i * 16 + b) * 32 + h * 8 + j], epoch);
          __syncwarp();
        }
      }
    }
    __syncwarp();
    asm volatile("barrier.cluster.arrive.relaxed.aligned;\nbarrier.cluster.wait.aligned;" ::: "memory");
  } else {
    asm volatile("setmaxnreg.inc.sync.aligned.u32 232;");
    asm volatile("barrier.cluster.wait.aligned;" ::: "memory");
    const int wg = warp >> 2, w = warp & 3;
    const bool rel = (threadIdx.x & 95) == 0;
    const uint32_t rel_addr = mapa(sb + kBarEmpty, w & 1);
    if (wg == 1) TRACE_AT(15, 0);
#define EPOCH (*reinterpret_cast<volatile unsigned*>(sm + kSmEpoch))

    if (wg == 1) {
      mbar_wait(sb + kBarEpoch, 0);
      mbar_wait(sb + kBarInit, 0);
    }

#pragma unroll 1
    for (int i = wg; i < kTiles; i += 2) {
      const int layer = i >= 7, ty = i - 7 * layer;
      TRACE_AT(i, 15);
      float acc[2][96];
      if (ty == 2 || ty == 6) {
        const uint32_t xrow_addr = sb + kSmX + (32 * w + lane) * 128;
        const float2* b2 = reinterpret_cast<const float2*>(sm + kSmB2) + (lane & 3);
#pragma unroll
        for (int J = 0; J < 16; J++) {
          uint32_t r[4];
          ldsm4(xrow_addr + (J >> 3) * kTileBytes + (((J & 7) ^ (lane & 7)) << 4), r);
          float2 bias = make_float2(0.f, 0.f);
          if (ty == 6) bias = b2[J * 4];
#pragma unroll
          for (int c = 0; c < 4; c++) {
            acc[c & 1][4 * J + (c & 2)] = bf_lo(r[c]) + bias.x;
            acc[c & 1][4 * J + (c & 2) + 1] = bf_hi(r[c]) + bias.y;
            asm volatile("" : "+f"(acc[c & 1][4 * J + (c & 2)]), "+f"(acc[c & 1][4 * J + (c & 2) + 1]));
            if (c & 1) yield_slot();
          }
        }
        mainloop<128>(acc, sb, i, layer * 152 + ty * 16, ty == 6 ? 4 : 0, ty == 6 ? 56 : 16, ty == 2 ? PAUSE_WO : -1,
                      2 * layer + 1, rel_addr, rel, [] {});
        TRACE_AT(i, 2);
#pragma unroll
        for (int h = 0; h < 2; h++) {
#pragma unroll
          for (int J = 8 * h; J < 8 * h + 8; J++)
            stsm4(xrow_addr + h * kTileBytes + (((J & 7) ^ (lane & 7)) << 4), pack2(acc[0][4 * J], acc[0][4 * J + 1]),
                  pack2(acc[1][4 * J], acc[1][4 * J + 1]), pack2(acc[0][4 * J + 2], acc[0][4 * J + 3]),
                  pack2(acc[1][4 * J + 2], acc[1][4 * J + 3]));
          fence_async_smem();
          __syncwarp();
          if (elect()) {
            const uint32_t src = sb + kSmX + h * kTileBytes + w * 4096;
            if (i == kTiles - 1) {
              tma2d_store(&map_out, src, xcol + j * 128 + h * 64, xrow + 32 * w);
              bulk_commit();
              if (h == 1) bulk_wait_read();
            } else if (h == 0) {
              bulk_store(g_x + (b * 16 + 2 * j) * kTileBytes + w * 4096, src, 4096);
              bulk_commit();
              mbar_arrive(sb + kBarX + (i >> 2) * 16);
            } else {
              mbar_arrive(sb + kBarX + (i >> 2) * 16 + 8);
              bulk_wait();
              mbar_arrive(sb + kBarEpi + i * 8);
            }
          }
          __syncwarp();
          yield_slot();
          TRACE_AT(i, 8 + h);
        }
      } else {
        const int xver = 2 * layer + (ty >= 3);
        const bool wide = ty < 4, split = i > 1 && ty != 5;
        zero_acc<192>(acc);
        if (split) {
          const int n0 = layer * 152 + (ty < 2 ? 2 * ty : 42 + 2 * ty), slot = ty < 2 ? 2 * ty : 2 * ty - 5;
          if (wide) head_blocks<192>(acc, sb, n0, slot, sb + kBarX + (xver - 1) * 16, rel_addr, rel);
          else head_blocks<128>(acc, sb, n0, slot, sb + kBarX + (xver - 1) * 16, rel_addr, rel);
        }
        if (ty == 1 || ty == 4) {
          uint2* stat = g_stat + (xver * 16 + b) * 1024;
          publish_stats(sb, stat + j * 128, w, lane, EPOCH);
          if (ty == 4) TRACE_AT(i, 13);
          gather_stats(sm, stat, EPOCH);
          __syncwarp();
          if (elect()) mbar_arrive(sb + kBarStat + xver * 8);
          TRACE_AT(i, 14);
          if (i == 8) {
            float2 st[4];
#pragma unroll
            for (int c = 0; c < 4; c++) st[c] = reinterpret_cast<const float2*>(sm + kSmStat)[32 * w + 8 * c + (lane >> 2)];
            add_mean_term(acc, st, sm, 1, lane);
          }
        }
        const int n0 = layer * 152 + (!split ? 16 * ty : ty < 2 ? 4 + 14 * ty : 10 + 14 * ty);
        const int slot = ty < 2 ? (split ? 2 * ty : 0) : ty == 3 ? 1 : 8 - ty;
        float2 st[4];
        unsigned epoch;
        auto pre = [&] {
          mbar_wait(sb + (ty == 0 || ty == 3 ? kBarStat + xver * 8 : kBarEpi + (i - 1) * 8), 0);
#pragma unroll
          for (int c = 0; c < 4; c++) st[c] = reinterpret_cast<const float2*>(sm + kSmStat)[32 * w + 8 * c + (lane >> 2)];
          epoch = EPOCH;
        };
        if (wide) mainloop<192>(acc, sb, i, n0, slot, split ? 14 : 16, ty == 1 ? PAUSE_QKV2 : -1, xver, rel_addr, rel, pre);
        else mainloop<128>(acc, sb, i, n0, slot, split ? 14 : 16, -1, 0, rel_addr, rel, pre);
        TRACE_AT(i, 2);
        if (layer == 0) mbar_wait(sb + kBarCs + ty * 8, 0);
        if (ty < 2) {
          if (i != 8) add_mean_term(acc, st, sm, ty, lane);
          epilogue_attn(acc, st, sm, sb, layer, ty, b, j, epoch, i, wg, w);
        } else {
          const int blk = ty == 3 ? 3 * j : 16 * ty - 40 + 2 * j;
          epilogue_gelu(acc, st, sm, sb, wide, wide ? 0 : 128 * ty - 320, g_h + (b * 56 + blk) * kTileBytes + w * 4096,
                        i, w);
        }
      }
      TRACE_AT(i, 3);
    }
#undef EPOCH
    asm volatile("barrier.cluster.arrive.relaxed.aligned;\nbarrier.cluster.wait.aligned;" ::: "memory");
    if (wg == 1) TRACE_AT(15, 2);
  }
}

void build_segments(uint32_t* seg) {
  int n = 0;
  auto add = [&](int ty, int cnt, int kb0, int mode, int wide, int depth5, int dep, int reset) {
    seg[n++] = ty | cnt << 3 | kb0 << 9 | mode << 15 | wide << 17 | depth5 << 18 | dep << 19 | reset << 24;
  };
  for (int l = 0; l < 2; l++) {
    const int t = 7 * l;
    if (l == 0) {
      add(0, 12, 4, kModePlain, 1, 0, 31, 1);
      add(1, 16, 0, kModePlain, 1, 0, 31, 0);
    } else {
      add(0, 2, 0, kModeHead, 1, 0, 31, 1);
      add(1, 2, 0, kModeHead, 1, 0, 31, 0);
      add(0, 7, 0, kModeSkip, 1, 0, 6, 0);
      add(0, 7, 1, kModeSkip, 1, 0, 15, 0);
      add(1, 7, 0, kModeSkip, 1, 0, 31, 0);
      add(1, 7, 1, kModeSkip, 1, 0, 31, 0);
    }
    add(2, 4, 0, kModePlain, 0, 0, t, 1);
    add(2, 4, 4, kModePlain, 0, 1, 31, 0);
    add(2, 8, 8, kModePlain, 0, 1, t + 1, 0);
    add(3, 2, 0, kModeHead, 1, 0, 31, 2);
    add(4, 2, 0, kModeHead, 1, 0, 31, 0);
    add(3, 7, 0, kModeSkip, 1, 0, t + 2, 0);
    add(3, 7, 1, kModeSkip, 1, 0, 14 + 2 * l, 0);
    add(4, 4, 0, kModeSkip, 0, 0, 31, 3);
    add(4, 3, 0, kModeContinue, 0, 1, 31, 0);
    add(4, 7, 1, kModeSkip, 0, 1, 31, 0);
    add(5, 16, 0, kModePlain, 0, 1, 31, 0);
    add(6, 24, 0, kModePlain, 0, 1, t + 3, 0);
    add(6, 16, 24, kModePlain, 0, 1, t + 4, 0);
    add(6, 16, 40, kModePlain, 0, 1, t + 5, 0);
  }
}

typedef CUresult (*EncodeTiledFn)(CUtensorMap*, CUtensorMapDataType, cuuint32_t, void*, const cuuint64_t*,
                                  const cuuint64_t*, const cuuint32_t*, const cuuint32_t*, CUtensorMapInterleave,
                                  CUtensorMapSwizzle, CUtensorMapL2promotion, CUtensorMapFloatOOBfill);

CUtensorMap make_map(EncodeTiledFn enc, const void* p, int rank, const cuuint64_t* dims, const cuuint64_t* strides,
                     const cuuint32_t* box, CUtensorMapSwizzle swizzle = CU_TENSOR_MAP_SWIZZLE_128B) {
  CUtensorMap m;
  const cuuint32_t es[5] = {1, 1, 1, 1, 1};
  enc(&m, CU_TENSOR_MAP_DATA_TYPE_BFLOAT16, rank, const_cast<void*>(p), dims, strides, box, es,
      CU_TENSOR_MAP_INTERLEAVE_NONE, swizzle, CU_TENSOR_MAP_L2_PROMOTION_L2_128B,
      CU_TENSOR_MAP_FLOAT_OOB_FILL_NONE);
  return m;
}

CUtensorMap weight_map(EncodeTiledFn enc, const void* p, int k, int n, int blocks) {
  const cuuint64_t dims[3] = {64, (cuuint64_t)k, (cuuint64_t)n / 64};
  const cuuint64_t strides[2] = {(cuuint64_t)n * 2, 128};
  const cuuint32_t box[3] = {64, 32, (cuuint32_t)blocks};
  return make_map(enc, p, 3, dims, strides, box);
}

CUtensorMap slab_map(EncodeTiledFn enc, const void* p, int n) {
  const cuuint64_t dims[2] = {(cuuint64_t)n, kD};
  const cuuint64_t strides[1] = {(cuuint64_t)n * 2};
  const cuuint32_t box[2] = {128, 128};
  return make_map(enc, p, 2, dims, strides, box, CU_TENSOR_MAP_SWIZZLE_NONE);
}

CUtensorMap token_map(EncodeTiledFn enc, const void* p, int rows) {
  const cuuint64_t dims[2] = {2 * kD, 1024};
  const cuuint64_t strides[1] = {4 * kD};
  const cuuint32_t box[2] = {64, (cuuint32_t)rows};
  return make_map(enc, p, 2, dims, strides, box);
}

}

extern "C" void kernel_launch(void* const* d_in, const int* in_sizes, int n_in, void* d_out, int out_size) {
  (void)in_sizes; (void)n_in; (void)out_size;
  static EncodeTiledFn enc = nullptr;
  if (!enc) {
    void* fn = nullptr;
    cudaDriverEntryPointQueryResult q;
    cudaGetDriverEntryPoint("cuTensorMapEncodeTiled", &fn, cudaEnableDefault, &q);
    enc = (EncodeTiledFn)fn;
    cudaFuncSetAttribute(fused_layers_kernel, cudaFuncAttributeMaxDynamicSharedMemorySize, kSmBytes);
  }
  Params prm;
  prm.x = (const __nv_bfloat16*)d_in[0];
  prm.wqkv = (const __nv_bfloat16*)d_in[1];
  prm.wo = (const __nv_bfloat16*)d_in[2];
  prm.w1 = (const __nv_bfloat16*)d_in[4];
  prm.b1 = (const __nv_bfloat16*)d_in[5];
  prm.w2 = (const __nv_bfloat16*)d_in[6];
  prm.b2 = (const __nv_bfloat16*)d_in[7];
  build_segments(prm.seg);
  const cuuint64_t qd[3] = {kD, kD, 3}, qs[2] = {3 * kD * 2, kD * 2};
  const cuuint32_t qb[3] = {64, 32, 3};
  const CUtensorMap map_x = token_map(enc, d_in[0], 128);
  const CUtensorMap map_out = token_map(enc, d_out, 32);
  const CUtensorMap map_qkv = make_map(enc, prm.wqkv, 3, qd, qs, qb);
  const CUtensorMap map_wo = weight_map(enc, prm.wo, kD, kD, 2);
  const CUtensorMap map_w1a = weight_map(enc, prm.w1, kD, kF, 3);
  const CUtensorMap map_w1b = weight_map(enc, prm.w1, kD, kF, 2);
  const CUtensorMap map_w2 = weight_map(enc, prm.w2, kF, kD, 2);
  fused_layers_kernel<<<kGrid, 384, kSmBytes>>>(map_x, map_out, map_qkv, map_wo, map_w1a, map_w1b, map_w2,
                                                slab_map(enc, prm.wqkv, 3 * kD), slab_map(enc, prm.w1, kF), prm);
}
```

```cpp
#include <cuda.h>
#include <cuda_bf16.h>
#include <cuda_runtime.h>
#include <stdint.h>

namespace {

constexpr int kD = 1024;
constexpr int kF = 3584;
constexpr int kCtas = 128;
constexpr int kGrid = 132;
constexpr int kTiles = 14;
constexpr int kTileBytes = 16384;

constexpr int kSmRing = 0;
constexpr int kSmX = 163840;
constexpr int kSmStg = kSmX + 32768;
constexpr int kSmHalo = kSmStg + 16384;
constexpr int kSmCsQ = kSmHalo + 6144;
constexpr int kSmV1 = kSmCsQ + 384 * 4;
constexpr int kSmB2 = kSmV1 + 448 * 8;
constexpr int kSmStat = kSmB2 + 128 * 4;
constexpr int kSmBar = kSmStat + 128 * 8;
constexpr int kBarFull = kSmBar;
constexpr int kBarTurn = kBarFull + 8 * 8;
constexpr int kBarReady = kBarTurn + 14 * 8;
constexpr int kBarPause = kBarReady + 17 * 8;
constexpr int kBarFree = kBarPause + 4 * 8;
constexpr int kBarCs = kBarFree + 14 * 8;
constexpr int kBarInit = kBarCs + 6 * 8;
constexpr int kBarEpoch = kBarInit + 8;
constexpr int kBarEmpty = kBarEpoch + 8;
constexpr int kBarEpi = kBarEmpty + 9 * 8;
constexpr int kBarX = kBarEpi + 14 * 8;
constexpr int kBarStat = kBarX + 6 * 8;
constexpr int kBarResume = kBarStat + 4 * 8;
constexpr int kSmEpoch = kBarResume + 4 * 8;
constexpr int kSmBytes = kSmEpoch + 16;
constexpr int kSegs = 36;

constexpr int kFlagLines = kTiles * 16;

constexpr unsigned kSpinLimit = 1u << 22;

__device__ __align__(1024) uint8_t g_x[16 * 16 * kTileBytes];
__device__ __align__(1024) uint8_t g_o[16 * 16 * kTileBytes];
__device__ __align__(1024) uint8_t g_h[16 * 56 * kTileBytes];
__device__ __align__(128) uint2 g_stat[4 * 16 * 128 * 8];
__device__ __align__(128) unsigned g_cs[3 * kD + kF];
__device__ __align__(128) uint4 g_halo[2 * 16 * 16 * 256];
__device__ __align__(128) unsigned g_flag[kFlagLines * 32];
__device__ unsigned g_ticket;

#define TRACE_AT(tile, k)
#define TRACE_PUB(i, k, c)
#define TRACE_ISSUE(which, nb)

struct Params {
  const __nv_bfloat16* x;
  const __nv_bfloat16* wqkv;
  const __nv_bfloat16* wo;
  const __nv_bfloat16* w1;
  const __nv_bfloat16* b1;
  const __nv_bfloat16* w2;
  const __nv_bfloat16* b2;
  uint32_t seg[kSegs];
};

__device__ __forceinline__ uint32_t smem_u32(const void* p) {
  return (uint32_t)__cvta_generic_to_shared(p);
}
__device__ __forceinline__ uint32_t mapa(uint32_t a, uint32_t cta) {
  uint32_t r;
  asm("mapa.shared::cluster.u32 %0, %1, %2;" : "=r"(r) : "r"(a), "r"(cta));
  return r;
}
__device__ __forceinline__ void mbar_init(uint32_t bar, int cnt) {
  asm volatile("mbarrier.init.shared::cta.b64 [%0], %1;" ::"r"(bar), "r"(cnt) : "memory");
}
__device__ __forceinline__ void mbar_expect_tx(uint32_t bar, uint32_t bytes) {
  asm volatile("mbarrier.arrive.expect_tx.shared::cta.b64 _, [%0], %1;" ::"r"(bar), "r"(bytes) : "memory");
}
__device__ __forceinline__ void mbar_arrive(uint32_t bar) {
  asm volatile("mbarrier.arrive.shared::cta.b64 _, [%0];" ::"r"(bar) : "memory");
}
__device__ __forceinline__ void mbar_arrive_cluster(uint32_t cluster_addr) {
  asm volatile("mbarrier.arrive.shared::cluster.b64 _, [%0];" ::"r"(cluster_addr) : "memory");
}
__device__ __forceinline__ void mbar_wait(uint32_t bar, uint32_t parity) {
  asm volatile(
      "{\n.reg .pred p;\n.reg .u32 c;\n"
      "mbarrier.try_wait.parity.shared::cta.b64 p, [%0], %1;\n"
      "@p bra.uni DONE;\n"
      "mov.u32 c, 0;\n"
      "RETRY:\n"
      "mbarrier.try_wait.parity.shared::cta.b64 p, [%0], %1;\n"
      "@p bra.uni DONE;\n"
      "add.u32 c, c, 1;\n"
      "setp.lt.u32 p, c, %2;\n"
      "@p bra.uni RETRY;\n"
      "trap;\n"
      "DONE:\n}" ::"r"(bar), "r"(parity), "n"(1u << 19)
      : "memory");
}
__device__ __forceinline__ void tma3d(uint32_t dst, const CUtensorMap* m, uint32_t bar, int c0, int c1, int c2) {
  asm volatile(
      "cp.async.bulk.tensor.3d.shared::cluster.global.mbarrier::complete_tx::bytes [%0], [%1, {%3, %4, %5}], [%2];"
      ::"r"(dst), "l"(m), "r"(bar), "r"(c0), "r"(c1), "r"(c2) : "memory");
}
__device__ __forceinline__ void tma3d_mc(uint32_t dst, const CUtensorMap* m, uint32_t bar, int c0, int c1, int c2) {
  asm volatile(
      "cp.async.bulk.tensor.3d.shared::cluster.global.mbarrier::complete_tx::bytes.multicast::cluster"
      " [%0], [%1, {%3, %4, %5}], [%2], %6;"
      ::"r"(dst), "l"(m), "r"(bar), "r"(c0), "r"(c1), "r"(c2), "h"((uint16_t)3) : "memory");
}
__device__ __forceinline__ void tma2d(uint32_t dst, const CUtensorMap* m, uint32_t bar, int c0, int c1) {
  asm volatile(
      "cp.async.bulk.tensor.2d.shared::cluster.global.mbarrier::complete_tx::bytes [%0], [%1, {%3, %4}], [%2];"
      ::"r"(dst), "l"(m), "r"(bar), "r"(c0), "r"(c1) : "memory");
}
__device__ __forceinline__ void tma2d_store(const CUtensorMap* m, uint32_t src, int c0, int c1) {
  asm volatile("cp.async.bulk.tensor.2d.global.shared::cta.bulk_group [%0, {%2, %3}], [%1];"
               ::"l"(m), "r"(src), "r"(c0), "r"(c1) : "memory");
}
__device__ __forceinline__ bool elect() {
  uint32_t p;
  asm volatile("{\n.reg .pred p;\nelect.sync _|p, 0xffffffff;\nselp.b32 %0, 1, 0, p;\n}" : "=r"(p));
  return p;
}
__device__ __forceinline__ void bulk_load(uint32_t dst, const void* src, uint32_t bytes, uint32_t bar) {
  asm volatile("cp.async.bulk.shared::cluster.global.mbarrier::complete_tx::bytes [%0], [%1], %2, [%3];"
               ::"r"(dst), "l"(src), "r"(bytes), "r"(bar) : "memory");
}
__device__ __forceinline__ void bulk_store(void* dst, uint32_t src, uint32_t bytes) {
  asm volatile("cp.async.bulk.global.shared::cta.bulk_group [%0], [%1], %2;" ::"l"(dst), "r"(src), "r"(bytes)
               : "memory");
}
__device__ __forceinline__ void bulk_commit() { asm volatile("cp.async.bulk.commit_group;" ::: "memory"); }
__device__ __forceinline__ void bulk_wait_read() { asm volatile("cp.async.bulk.wait_group.read 0;" ::: "memory"); }
__device__ __forceinline__ void bulk_wait() { asm volatile("cp.async.bulk.wait_group 0;" ::: "memory"); }
__device__ __forceinline__ void l2_prefetch(const void* p, uint32_t bytes) {
  asm volatile("cp.async.bulk.prefetch.L2.global [%0], %1;" ::"l"(p), "r"(bytes) : "memory");
}
__device__ __forceinline__ void fence_async_smem() { asm volatile("fence.proxy.async.shared::cta;" ::: "memory"); }
__device__ __forceinline__ unsigned ld_relaxed(const unsigned* p) {
  unsigned v;
  asm volatile("ld.relaxed.gpu.global.u32 %0, [%1];" : "=r"(v) : "l"(p) : "memory");
  return v;
}
__device__ __forceinline__ uint2 ld_relaxed2(const uint2* p) {
  uint2 v;
  asm volatile("ld.relaxed.gpu.global.v2.u32 {%0, %1}, [%2];" : "=r"(v.x), "=r"(v.y) : "l"(p) : "memory");
  return v;
}
__device__ __forceinline__ void st_relaxed(unsigned* p, unsigned v) {
  asm volatile("st.relaxed.gpu.global.u32 [%0], %1;" ::"l"(p), "r"(v) : "memory");
}
__device__ __forceinline__ void st_release(unsigned* p, unsigned v) {
  asm volatile("st.release.gpu.global.u32 [%0], %1;" ::"l"(p), "r"(v) : "memory");
}
#define ACQ_MODE 1
__device__ __forceinline__ void wait_flags(const unsigned* p, unsigned epoch) {
  unsigned spins = 0;
  while (true) {
    const unsigned v = ld_relaxed(p);
    if (__all_sync(0xffffffffu, v == epoch)) break;
    if (++spins > kSpinLimit) __trap();
  }
  if (ACQ_MODE) asm volatile("fence.acquire.gpu;\nfence.proxy.async.global;" ::: "memory");
  __syncwarp();
}
__device__ __forceinline__ unsigned tag_value(float v, unsigned epoch) {
  return (__float_as_uint(v) & ~7u) | (epoch & 7u);
}
__device__ __forceinline__ float untag_value(unsigned v) { return __uint_as_float(v & ~7u); }
__device__ __forceinline__ void stsm4(uint32_t a, uint32_t r0, uint32_t r1, uint32_t r2, uint32_t r3) {
  asm volatile("stmatrix.sync.aligned.m8n8.x4.shared.b16 [%0], {%1, %2, %3, %4};" ::"r"(a), "r"(r0), "r"(r1),
               "r"(r2), "r"(r3) : "memory");
}
__device__ __forceinline__ void stsm4_t(uint32_t a, uint32_t r0, uint32_t r1, uint32_t r2, uint32_t r3) {
  asm volatile("stmatrix.sync.aligned.m8n8.x4.trans.shared.b16 [%0], {%1, %2, %3, %4};" ::"r"(a), "r"(r0),
               "r"(r1), "r"(r2), "r"(r3) : "memory");
}
__device__ __forceinline__ uint32_t transpose8(uint32_t a) {
  uint32_t d;
  asm volatile("movmatrix.sync.aligned.m8n8.trans.b16 %0, %1;" : "=r"(d) : "r"(a));
  return d;
}
__device__ __forceinline__ void mma16816(float (&c)[4], uint32_t a0, uint32_t a1, uint32_t a2, uint32_t a3,
                                         uint32_t b0, uint32_t b1) {
  asm volatile("mma.sync.aligned.m16n8k16.row.col.f32.bf16.bf16.f32 {%0, %1, %2, %3}, {%4, %5, %6, %7}, {%8, %9}, "
               "{%0, %1, %2, %3};"
               : "+f"(c[0]), "+f"(c[1]), "+f"(c[2]), "+f"(c[3])
               : "r"(a0), "r"(a1), "r"(a2), "r"(a3), "r"(b0), "r"(b1));
}
__device__ __forceinline__ float shfl_xor(float v, int m) {
  float r;
  asm volatile("shfl.sync.bfly.b32 %0, %1, %2, 31, 0xffffffff;" : "=f"(r) : "f"(v), "r"(m));
  return r;
}
__device__ __forceinline__ float tanh_fast(float x) {
  float r;
  asm volatile("tanh.approx.f32 %0, %1;" : "=f"(r) : "f"(x));
  return r;
}
__device__ __forceinline__ void ldsm4(uint32_t a, uint32_t (&r)[4]) {
  asm volatile("ldmatrix.sync.aligned.m8n8.x4.shared.b16 {%0, %1, %2, %3}, [%4];"
               : "=r"(r[0]), "=r"(r[1]), "=r"(r[2]), "=r"(r[3]) : "r"(a) : "memory");
}
__device__ __forceinline__ uint32_t pack2(float lo, float hi) {
  uint32_t r;
  asm volatile("cvt.rn.bf16x2.f32 %0, %1, %2;" : "=r"(r) : "f"(hi), "f"(lo));
  return r;
}
__device__ __forceinline__ float bf_lo(uint32_t r) { return __uint_as_float(r << 16); }
__device__ __forceinline__ float bf_hi(uint32_t r) { return __uint_as_float(r & 0xffff0000u); }
__device__ __forceinline__ float ex2(float x) {
  float r;
  asm("ex2.approx.ftz.f32 %0, %1;" : "=f"(r) : "f"(x));
  return r;
}
__device__ __forceinline__ float rcp(float x) {
  float r;
  asm("rcp.approx.ftz.f32 %0, %1;" : "=f"(r) : "f"(x));
  return r;
}
template <int N>
__device__ __forceinline__ void wg_wait() {
  asm volatile("wgmma.wait_group.sync.aligned %0;" ::"n"(N) : "memory");
}
__device__ __forceinline__ void yield_slot() { asm volatile("pmevent 0;"); }
__device__ __forceinline__ void wg_bar(int wg) { asm volatile("bar.sync %0, 128;" ::"r"(wg + 1) : "memory"); }

template <int N, int KIND>
__device__ __forceinline__ void mma_kblock(float (&acc)[2][96], uint32_t a, uint32_t b);

#define F8(m, d, i) m(d[i]), m(d[i + 1]), m(d[i + 2]), m(d[i + 3]), m(d[i + 4]), m(d[i + 5]), m(d[i + 6]), m(d[i + 7])
#define KSTEP(N, A, B, oa0, oa1, ob, sd)                                                   \
  "add.u32 t, " B ", " #ob ";\nmov.b64 db, {t, hb};\n"                                      \
  "add.u32 t, " A ", " #oa0 ";\nmov.b64 da, {t, ha};\n"                                     \
  "wgmma.mma_async.sync.aligned.m64n" #N "k16.f32.bf16.bf16 {" ACC##N##_0 "}, da, db, " #sd ", 1, 1, 0, 1;\n" \
  "add.u32 t, " A ", " #oa1 ";\nmov.b64 da, {t, ha};\n"                                     \
  "wgmma.mma_async.sync.aligned.m64n" #N "k16.f32.bf16.bf16 {" ACC##N##_1 "}, da, db, " #sd ", 1, 1, 0, 1;\n"

#define MMA_KBLOCK(N, KIND, A, B, ob2, ob3, sd, MID, MODE)                                 \
  template <>                                                                              \
  __device__ __forceinline__ void mma_kblock<N, KIND>(float (&acc)[2][96], uint32_t a, uint32_t b) { \
    asm volatile("{\n.reg .b32 t, ha, hb;\n.reg .b64 da, db;\n"                            \
                 "mov.b32 ha, 0x40000080;\nmov.b32 hb, 0x40000040;\n"                       \
                 "wgmma.fence.sync.aligned;\n"                                             \
                 KSTEP(N, A, B, 0, 64, 0, sd) KSTEP(N, A, B, 2, 66, 128, 1) KSTEP(N, A, B, 4, 68, ob2, 1) \
                 MID KSTEP(N, A, B, 6, 70, ob3, 1) "wgmma.commit_group.sync.aligned;\n}\n"  \
                 : OPS##N(MODE) : "r"(a), "r"(b) : "memory");                              \
  }
#define MMA_KBLOCKS(N, A, B, ob2, ob3)                                                     \
  MMA_KBLOCK(N, 0, A, B, ob2, ob3, 1, "", "+f")                                            \
  MMA_KBLOCK(N, 1, A, B, ob2, ob3, 1, "wgmma.commit_group.sync.aligned;\n", "+f")          \
  MMA_KBLOCK(N, 2, A, B, ob2, ob3, 0, "", "=f")

#define ACC128_0 \
  "%0, %1, %2, %3, %4, %5, %6, %7, %8, %9, %10, %11, %12, %13, %14, %15, " \
  "%16, %17, %18, %19, %20, %21, %22, %23, %24, %25, %26, %27, %28, %29, %30, %31, " \
  "%32, %33, %34, %35, %36, %37, %38, %39, %40, %41, %42, %43, %44, %45, %46, %47, " \
  "%48, %49, %50, %51, %52, %53, %54, %55, %56, %57, %58, %59, %60, %61, %62, %63"
#define ACC128_1 \
  "%64, %65, %66, %67, %68, %69, %70, %71, %72, %73, %74, %75, %76, %77, %78, %79, " \
  "%80, %81, %82, %83, %84, %85, %86, %87, %88, %89, %90, %91, %92, %93, %94, %95, " \
  "%96, %97, %98, %99, %100, %101, %102, %103, %104, %105, %106, %107, %108, %109, %110, %111, " \
  "%112, %113, %114, %115, %116, %117, %118, %119, %120, %121, %122, %123, %124, %125, %126, %127"
#define OPS128(m) \
  F8(m, acc[0], 0), F8(m, acc[0], 8), F8(m, acc[0], 16), F8(m, acc[0], 24), F8(m, acc[0], 32), F8(m, acc[0], 40), F8(m, acc[0], 48), F8(m, acc[0], 56), \
        F8(m, acc[1], 0), F8(m, acc[1], 8), F8(m, acc[1], 16), F8(m, acc[1], 24), F8(m, acc[1], 32), F8(m, acc[1], 40), F8(m, acc[1], 48), F8(m, acc[1], 56)
MMA_KBLOCKS(128, "%128", "%129", 512, 640)

#define ACC192_0 \
  "%0, %1, %2, %3, %4, %5, %6, %7, %8, %9, %10, %11, %12, %13, %14, %15, " \
  "%16, %17, %18, %19, %20, %21, %22, %23, %24, %25, %26, %27, %28, %29, %30, %31, " \
  "%32, %33, %34, %35, %36, %37, %38, %39, %40, %41, %42, %43, %44, %45, %46, %47, " \
  "%48, %49, %50, %51, %52, %53, %54, %55, %56, %57, %58, %59, %60, %61, %62, %63, " \
  "%64, %65, %66, %67, %68, %69, %70, %71, %72, %73, %74, %75, %76, %77, %78, %79, " \
  "%80, %81, %82, %83, %84, %85, %86, %87, %88, %89, %90, %91, %92, %93, %94, %95"
#define ACC192_1 \
  "%96, %97, %98, %99, %100, %101, %102, %103, %104, %105, %106, %107, %108, %109, %110, %111, " \
  "%112, %113, %114, %115, %116, %117, %118, %119, %120, %121, %122, %123, %124, %125, %126, %127, " \
  "%128, %129, %130, %131, %132, %133, %134, %135, %136, %137, %138, %139, %140, %141, %142, %143, " \
  "%144, %145, %146, %147, %148, %149, %150, %151, %152, %153, %154, %155, %156, %157, %158, %159, " \
  "%160, %161, %162, %163, %164, %165, %166, %167, %168, %169, %170, %171, %172, %173, %174, %175, " \
  "%176, %177, %178, %179, %180, %181, %182, %183, %184, %185, %186, %187, %188, %189, %190, %191"
#define OPS192(m) \
  F8(m, acc[0], 0), F8(m, acc[0], 8), F8(m, acc[0], 16), F8(m, acc[0], 24), F8(m, acc[0], 32), F8(m, acc[0], 40), F8(m, acc[0], 48), F8(m, acc[0], 56), F8(m, acc[0], 64), F8(m, acc[0], 72), F8(m, acc[0], 80), F8(m, acc[0], 88), \
        F8(m, acc[1], 0), F8(m, acc[1], 8), F8(m, acc[1], 16), F8(m, acc[1], 24), F8(m, acc[1], 32), F8(m, acc[1], 40), F8(m, acc[1], 48), F8(m, acc[1], 56), F8(m, acc[1], 64), F8(m, acc[1], 72), F8(m, acc[1], 80), F8(m, acc[1], 88)
MMA_KBLOCKS(192, "%192", "%193", 768, 896)

enum { kModePlain = 0, kModeHead = 1, kModeSkip = 2, kModeContinue = 3 };

template <int N>
__device__ __forceinline__ void fence_acc(float (&acc)[2][96]) {
#pragma unroll
  for (int h = 0; h < 2; h++)
#pragma unroll
    for (int i = 0; i < N / 2; i++) asm volatile("" : "+f"(acc[h][i])::"memory");
}

template <int N>
__device__ __forceinline__ void zero_acc(float (&acc)[2][96]) {
#pragma unroll
  for (int h = 0; h < 2; h++)
#pragma unroll
    for (int i = 0; i < N / 2; i++) acc[h][i] = 0.f;
}

constexpr uint32_t kToB = (kTileBytes >> 4) + ((4096u >> 4) << 16) - (1u << 16);

#define TRACE_KB(nb)

#define HEAD_BOTH 0
template <int N>
__device__ __forceinline__ void head_blocks(float (&acc)[2][96], uint32_t sb, int n0, int slot, uint32_t xbar,
                                            uint32_t rel_addr, bool rel) {
  const uint32_t ring = (((sb & 0x3FFFF) + kSmRing) >> 4) | (1u << 16);
  const uint32_t xdesc = (((sb & 0x3FFFF) + kSmX) >> 4) | (1u << 16);
  const uint32_t nb = n0 * 8;
  mbar_wait(xbar + 8 * HEAD_BOTH, 0);
  mbar_wait(sb + kBarFull + (nb & 56), nb >> 6);
  TRACE_KB(nb);
  mma_kblock<N, 2>(acc, xdesc, ring + slot * 2560 + kToB);
  mbar_wait(xbar + 8, 0);
  mbar_wait(sb + kBarFull + (nb & 56) + 8, nb >> 6);
  TRACE_KB(nb + 8);
  mma_kblock<N, 0>(acc, xdesc + (kTileBytes >> 4), ring + ((slot + 1) & 3) * 2560 + kToB);
  wg_wait<1>();
  if (rel) mbar_arrive_cluster(rel_addr + (nb & 56));
  wg_wait<0>();
  if (rel) mbar_arrive_cluster(rel_addr + (nb & 56) + 8);
  fence_acc<N>(acc);
}

template <int N, class Pre>
__device__ __forceinline__ void mainloop(float (&acc)[2][96], uint32_t sb, int tile, int n0, int slot, int nkb,
                                         int pause_kk, int att, uint32_t rel_addr, bool rel, uint32_t prev, Pre pre) {
  constexpr uint32_t kStep = (N == 192 ? 5 : 4) * 512;
  const uint32_t ring = (((sb & 0x3FFFF) + kSmRing) >> 4) | (1u << 16);
  uint32_t st = ring + slot * kStep;
  uint32_t nb = n0 * 8;
  const uint32_t last = nb + 8 * (nkb - 1);
  uint32_t stop = pause_kk >= 0 ? nb + 8 * pause_kk : last;
  const bool signal = (threadIdx.x & 127) == 64;
  fence_acc<N>(acc);
  if (tile > 0) mbar_wait(sb + kBarTurn + (tile - 1) * 8, 0);
  TRACE_AT(tile, 0);
#pragma unroll 1
  while (true) {
#pragma unroll 1
    do {
      mbar_wait(sb + kBarFull + (nb & 56), nb >> 6);
      if (nb == n0 * 8) TRACE_AT(tile, 1);
      TRACE_KB(nb);
      mma_kblock<N, 0>(acc, st, st + kToB);
      wg_wait<1>();
      if (rel) mbar_arrive_cluster(rel_addr + prev);
      prev = nb & 56;
      st += kStep;
      if (st == ring + 10240) st = ring;
      nb += 8;
    } while (nb != stop);
    if (stop == last) break;
    stop = last;
    if (signal) mbar_arrive(sb + kBarPause + att * 8);
    wg_wait<0>();
    if (rel) mbar_arrive_cluster(rel_addr + prev);
    prev = 64;
    mbar_wait(sb + kBarResume + att * 8, 0);
  }
  mbar_wait(sb + kBarFull + (nb & 56), nb >> 6);
  TRACE_KB(nb);
  mma_kblock<N, 1>(acc, st, st + kToB);
  wg_wait<2>();
  if (rel) mbar_arrive_cluster(rel_addr + prev);
  pre();
  wg_wait<1>();
  if (signal) mbar_arrive(sb + kBarTurn + tile * 8);
  wg_wait<0>();
  if (rel) mbar_arrive_cluster(rel_addr + (nb & 56));
  fence_acc<N>(acc);
}

__device__ __forceinline__ void publish_stats(uint32_t sb, uint2* stat, int w, int lane, unsigned epoch) {
  const uint32_t row = sb + kSmX + (32 * w + lane) * 128;
  float s[4], q[4];
#pragma unroll
  for (int c = 0; c < 4; c++) s[c] = q[c] = 0.f;
  uint32_t nx[4];
  ldsm4(row + ((lane & 7) << 4), nx);
#pragma unroll 1
  for (int J = 1; J <= 16; J++) {
    const uint32_t r[4] = {nx[0], nx[1], nx[2], nx[3]};
    ldsm4(row + ((J >> 3) & 1) * kTileBytes + (((J ^ lane) & 7) << 4), nx);
#pragma unroll
    for (int c = 0; c < 4; c++) {
      const float lo = bf_lo(r[c]);
      s[c] += lo;
      q[c] = fmaf(lo, lo, q[c]);
      if (c & 1) yield_slot();
    }
#pragma unroll
    for (int c = 0; c < 4; c++) {
      const float hi = bf_hi(r[c]);
      s[c] += hi;
      q[c] = fmaf(hi, hi, q[c]);
      if (c & 1) yield_slot();
    }
  }
#pragma unroll
  for (int c = 0; c < 4; c++) {
    s[c] += shfl_xor(s[c], 1);
    q[c] += shfl_xor(q[c], 1);
    s[c] += shfl_xor(s[c], 2);
    q[c] += shfl_xor(q[c], 2);
  }
  const int t = lane & 3, g = lane >> 2;
  const float so = t == 0 ? s[0] : t == 1 ? s[1] : t == 2 ? s[2] : s[3];
  const float qo = t == 0 ? q[0] : t == 1 ? q[1] : t == 2 ? q[2] : q[3];
  asm volatile("st.relaxed.gpu.global.v2.u32 [%0], {%1, %2};" ::"l"(stat + 32 * w + 8 * t + g),
               "r"(tag_value(so, epoch)), "r"(tag_value(qo, epoch)) : "memory");
}

__device__ __forceinline__ void add_chunk(float (&a)[8], const uint4& v) {
  a[0] += bf_lo(v.x); a[1] += bf_hi(v.x);
  a[2] += bf_lo(v.y); a[3] += bf_hi(v.y);
  a[4] += bf_lo(v.z); a[5] += bf_hi(v.z);
  a[6] += bf_lo(v.w); a[7] += bf_hi(v.w);
}

__device__ __forceinline__ int helper_col(int id, int slab) {
  return slab < 6 ? (slab % 3) * kD + (slab / 3) * 512 + id * 128 : (slab - 6) * 512 + id * 128;
}
__device__ __forceinline__ void helper_cta(const CUtensorMap* map_q, const CUtensorMap* map_1, uint8_t* sm,
                                           uint32_t sb, int id, int warp) {
  constexpr int kRed = 6 * 32768, kBar = kRed + 2 * 4096;
  const int tid = threadIdx.x;
  if (warp == 8 && elect()) {
#pragma unroll
    for (int s = 0; s < 6; s++) {
      mbar_init(sb + kBar + s * 8, 1);
      mbar_init(sb + kBar + 64 + s * 8, 4);
    }
    fence_async_smem();
#pragma unroll
    for (int s = 0; s < 6; s++) {
      mbar_expect_tx(sb + kBar + s * 8, 32768);
      tma2d(sb + s * 32768, map_q, sb + kBar + s * 8, id * 128, s * 128);
    }
  }
  __syncthreads();
  if (warp == 8) {
    int slot = 0, ph = 0;
#pragma unroll 1
    for (int n = 6; n < 104; n++) {
      mbar_wait(sb + kBar + 64 + slot * 8, ph);
      if (elect()) {
        mbar_expect_tx(sb + kBar + slot * 8, 32768);
        tma2d(sb + slot * 32768, n < 48 ? map_q : map_1, sb + kBar + slot * 8, helper_col(id, n >> 3), (n & 7) * 128);
      }
      if (++slot == 6) slot = 0, ph ^= 1;
    }
  } else if (warp < 8) {
    if (tid == 0) *reinterpret_cast<unsigned*>(sm + kBar + 128) = atomicAdd(&g_ticket, 1u) / kGrid + 1;
    int slot = warp >> 2, ph = 0;
#pragma unroll 1
    for (int slab = 0; slab < 13; slab++) {
      float a[8];
#pragma unroll
      for (int e = 0; e < 8; e++) a[e] = 0.f;
#pragma unroll 1
      for (int box = 0; box < 4; box++) {
        mbar_wait(sb + kBar + slot * 8, ph);
        const uint4* p = reinterpret_cast<const uint4*>(sm + slot * 32768) + (tid & 127);
        uint4 v[16];
#pragma unroll
        for (int i = 0; i < 16; i++) v[i] = p[i * 128];
        __syncwarp();
        if (elect()) mbar_arrive(sb + kBar + 64 + slot * 8);
#pragma unroll
        for (int i = 0; i < 16; i++) add_chunk(a, v[i]);
        slot += 2;
        if (slot >= 6) slot -= 6, ph ^= 1;
      }
      float* red = reinterpret_cast<float*>(sm + kRed + (slab & 1) * 4096);
#pragma unroll
      for (int e = 0; e < 8; e++) a[e] += shfl_xor(a[e], 16);
      if ((tid & 16) == 0) {
        float4* d = reinterpret_cast<float4*>(red + warp * 128 + (tid & 15) * 8);
        d[0] = make_float4(a[0], a[1], a[2], a[3]);
        d[1] = make_float4(a[4], a[5], a[6], a[7]);
      }
      asm volatile("bar.sync 1, 256;" ::: "memory");
      if (warp < 4) {
        float t = 0.f;
#pragma unroll
        for (int q = 0; q < 8; q++) t += red[q * 128 + tid];
        st_relaxed(g_cs + (slab < 6 ? 0 : 3 * kD) + helper_col(id, slab) + tid,
                   tag_value(t, *reinterpret_cast<volatile unsigned*>(sm + kBar + 128)));
      }
    }
  }
}

constexpr float kGelu0 = 2.f * 0.7978845608028654f;
constexpr float kGelu1 = 8.f * 0.7978845608028654f * 0.044715f;

__device__ __forceinline__ void store_staged(uint8_t* dst, uint32_t stg) {
  fence_async_smem();
  __syncwarp();
  if (elect()) {
    bulk_store(dst, stg, 4096);
    bulk_commit();
  }
}

#define GY_MASK 0x3F
#define GY_MASK2 0x2a
#define GY(k) if (((CH == 2 ? GY_MASK2 : GY_MASK) >> k) & 1) yield_slot()
template <int CH>
__device__ __forceinline__ void gelu_chunk(const float (&acc)[2][96], const float2 (&st)[4], const float4* vec,
                                           uint32_t stg, int lane, bool chained, uint8_t* prev, uint32_t free_bar) {
  uint32_t pk[8][4];
  float u[3][4], z[3][4];
  float4 v = vec[CH * 32], vn = v;
#pragma unroll
  for (int s = 0; s < 18; s++) {
    const int J = CH * 8 + (s >> 1), c0 = 2 * (s & 1), cur = s % 3, p1 = (s + 2) % 3, p2 = (s + 1) % 3;
    if (s < 16) {
      if (c0 == 0 && s < 14) vn = vec[(J + 1) * 4];
#pragma unroll
      for (int e = 0; e < 4; e++) {
        const int c = c0 + (e >> 1);
        z[cur][e] = fmaf(st[c].y, e & 1 ? v.y : v.x, e & 1 ? v.w : v.z);
      }
      if (c0 == 2) v = vn;
    }
    if (s >= 1 && s < 17) z[p1][0] = tanh_fast(z[p1][0]);
    GY(0);
    if (s < 16) {
#pragma unroll
      for (int e = 0; e < 4; e++) {
        const int c = c0 + (e >> 1);
        u[cur][e] = fmaf(acc[c & 1][4 * J + c0 + (e & 1)], st[c].x, z[cur][e]);
      }
    }
    if (s >= 11) {
      const int jj = s - 11;
      stsm4(stg + lane * 128 + ((jj ^ (lane & 7)) << 4), pk[jj][0], pk[jj][1], pk[jj][2], pk[jj][3]);
    }
    GY(1);
    if (s < 16) {
#pragma unroll
      for (int e = 0; e < 4; e++) z[cur][e] = u[cur][e] * u[cur][e];
    }
    if (s >= 1 && s < 17) z[p1][1] = tanh_fast(z[p1][1]);
    GY(2);
    if (s < 16) {
#pragma unroll
      for (int e = 0; e < 4; e++) z[cur][e] = fmaf(z[cur][e], kGelu1, kGelu0);
    }
    if (s >= 1 && s < 17) z[p1][2] = tanh_fast(z[p1][2]);
    GY(3);
    if (s >= 2) {
      pk[(s - 2) >> 1][c0] = pack2(fmaf(u[p2][0], z[p2][0], u[p2][0]), fmaf(u[p2][1], z[p2][1], u[p2][1]));
      pk[(s - 2) >> 1][c0 + 1] = pack2(fmaf(u[p2][2], z[p2][2], u[p2][2]), fmaf(u[p2][3], z[p2][3], u[p2][3]));
    }
    GY(4);
    if (s < 16) {
#pragma unroll
      for (int e = 0; e < 4; e++) z[cur][e] = u[cur][e] * z[cur][e];
    }
    if (s >= 1 && s < 17) z[p1][3] = tanh_fast(z[p1][3]);
    GY(5);
    if (CH < 2 && s == 1 && chained) store_staged(prev, stg);
    if (CH < 2 && s == 10) {
      if (chained) {
        if (elect()) bulk_wait();
        __syncwarp();
      } else {
        mbar_wait(free_bar, 0);
      }
    }
  }
  stsm4(stg + lane * 128 + ((7 ^ (lane & 7)) << 4), pk[7][0], pk[7][1], pk[7][2], pk[7][3]);
}

__device__ __forceinline__ void halve_stats(float2 (&st)[4]) {
#pragma unroll
  for (int c = 0; c < 4; c++) {
    st[c].x *= 0.5f;
    st[c].y *= st[c].x;
  }
}

__device__ __forceinline__ void add_mean_term(float (&acc)[2][96], const float2 (&st)[4], uint8_t* sm, int tq,
                                              int lane) {
  const float2* cs = reinterpret_cast<const float2*>(sm + kSmCsQ) + tq * 96 + (lane & 3);
  float2 vn = cs[0];
#pragma unroll
  for (int J = 0; J < 24; J++) {
    const float2 v = vn;
    if (J < 23) vn = cs[J * 4 + 4];
#pragma unroll
    for (int c = 0; c < 4; c++) {
      acc[c & 1][4 * J + (c & 2)] = fmaf(st[c].y, v.x, acc[c & 1][4 * J + (c & 2)]);
      acc[c & 1][4 * J + (c & 2) + 1] = fmaf(st[c].y, v.y, acc[c & 1][4 * J + (c & 2) + 1]);
    }
    yield_slot();
  }
}

#define HALO_AT 2
__device__ __forceinline__ void epilogue_attn(const float (&acc)[2][96], const float2 (&st)[4], uint8_t* sm,
                                              uint32_t sb, int layer, int tq, int b, int j, unsigned epoch, int tile,
                                              int wg, int w) {
  const int lane = threadIdx.x & 31, t = lane & 3, g = lane >> 2;
  const int hp = j + 8 * tq, att = 2 * layer + tq;
  uint32_t q[4][8], k[5][8], vt[5][8];
#define SCALED(c, J) pack2(acc[(c) & 1][4 * (J) + ((c) & 2)] * st[c].x, acc[(c) & 1][4 * (J) + ((c) & 2) + 1] * st[c].x)
#pragma unroll
  for (int J = 0; J < 8; J++) vt[4][J] = transpose8(SCALED(3, 16 + J));
#pragma unroll
  for (int J = 0; J < 8; J++) k[4][J] = SCALED(3, 8 + J);
  if (w < 3) {
    uint4* hs = reinterpret_cast<uint4*>(sm + kSmHalo + w * 2048) + lane;
    hs[0] = make_uint4(k[4][0], k[4][1], k[4][2], k[4][3]);
    hs[32] = make_uint4(k[4][4], k[4][5], k[4][6], k[4][7]);
    hs[64] = make_uint4(vt[4][0], vt[4][1], vt[4][2], vt[4][3]);
    hs[96] = make_uint4(vt[4][4], vt[4][5], vt[4][6], vt[4][7]);
  } else if ((b & 7) != 7) {
    uint4* gh = g_halo + ((layer * 16 + b) * 16 + hp) * 256 + lane;
#pragma unroll
    for (int i = 0; i < 8; i++)
      asm volatile("{\n.reg .b64 x, y;\nmov.b64 x, {%1, %3};\nmov.b64 y, {%2, %3};\n"
                   "st.relaxed.gpu.global.v2.b64 [%0], {x, y};\n}" ::"l"(gh + i * 32),
                   "r"(k[4][i]), "r"(vt[4][i]), "r"(epoch) : "memory");
  }
#pragma unroll
  for (int c = 0; c < 3; c++)
#pragma unroll
    for (int J = 0; J < 8; J++) {
      k[c + 1][J] = SCALED(c, 8 + J);
      vt[c + 1][J] = transpose8(SCALED(c, 16 + J));
      yield_slot();
    }
  const bool first = w == 0 && (b & 7) == 0;
  const uint4* gh = g_halo + ((layer * 16 + b - 1) * 16 + hp) * 256 + lane;
  uint32_t tag[16];
#define LOAD_HALO(i)                                                                         \
  asm volatile("{\n.reg .b64 x, y;\nld.relaxed.gpu.global.v2.b64 {x, y}, [%4];\n"            \
               "mov.b64 {%0, %1}, x;\nmov.b64 {%2, %3}, y;\n}"                               \
               : "=r"(k[0][i]), "=r"(tag[2 * i]), "=r"(vt[0][i]), "=r"(tag[2 * i + 1])        \
               : "l"(gh + i * 32) : "memory")
#pragma unroll
  for (int c = 0; c <= 4; c++) {
    if (c == HALO_AT) {
      if (w == 0 && !first) {
#pragma unroll
        for (int i = 0; i < 8; i++) LOAD_HALO(i);
      } else {
#pragma unroll
        for (int i = 0; i < 8; i++) k[0][i] = vt[0][i] = tag[2 * i] = tag[2 * i + 1] = 0u;
      }
    }
#pragma unroll
    for (int J = 0; J < 8 && c < 4; J++) {
      q[c & 3][J] = SCALED(c & 3, J);
      if (J & 1) yield_slot();
    }
  }
#undef SCALED
  TRACE_AT(tile, 8);
  wg_bar(wg);
  if (w > 0) {
    const uint4* hs = reinterpret_cast<const uint4*>(sm + kSmHalo + (w - 1) * 2048) + lane;
    const uint4 a0 = hs[0], a1 = hs[32], a2 = hs[64], a3 = hs[96];
    k[0][0] = a0.x; k[0][1] = a0.y; k[0][2] = a0.z; k[0][3] = a0.w;
    k[0][4] = a1.x; k[0][5] = a1.y; k[0][6] = a1.z; k[0][7] = a1.w;
    vt[0][0] = a2.x; vt[0][1] = a2.y; vt[0][2] = a2.z; vt[0][3] = a2.w;
    vt[0][4] = a3.x; vt[0][5] = a3.y; vt[0][6] = a3.z; vt[0][7] = a3.w;
  } else if (!first) {
    unsigned spins = 0;
    while (true) {
      unsigned d0 = 0, d1 = 0, d2 = 0, d3 = 0;
#pragma unroll
      for (int i = 0; i < 4; i++) {
        d0 |= tag[i] ^ epoch;
        d1 |= tag[4 + i] ^ epoch;
        d2 |= tag[8 + i] ^ epoch;
        d3 |= tag[12 + i] ^ epoch;
      }
      if (__all_sync(0xffffffffu, (d0 | d1 | d2 | d3) == 0)) break;
      if (++spins > kSpinLimit) __trap();
#pragma unroll
      for (int i = 0; i < 8; i++) LOAD_HALO(i);
    }
  }
#undef LOAD_HALO
  TRACE_AT(tile, 9);
  mbar_wait(sb + kBarPause + att * 8, 0);
  TRACE_AT(tile, 10);

  float s[2][5][4];
#pragma unroll
  for (int hd = 0; hd < 2; hd++)
#pragma unroll
    for (int kg = 0; kg < 5; kg++) {
      const int ca = kg > 0 ? kg - 1 : 0, cb = kg < 4 ? kg : 3;
#pragma unroll
      for (int e = 0; e < 4; e++) s[hd][kg][e] = 0.f;
#pragma unroll
      for (int ks = 0; ks < 2; ks++) {
        const int J = 4 * hd + 2 * ks;
        mma16816(s[hd][kg], q[ca][J], q[cb][J], q[ca][J + 1], q[cb][J + 1], k[kg][J], k[kg][J + 1]);
      }
    }
  constexpr float kScale = 0.17677669529663687f * 1.4426950408889634f;
  const bool own0 = 2 * t <= g, own1 = 2 * t + 1 <= g;
  const uint32_t own_mask = (own0 ? 0xffffu : 0u) | (own1 ? 0xffff0000u : 0u);
  float o[2][4][2][4];
#pragma unroll
  for (int hd = 0; hd < 2; hd++) {
    float v0[4], v1[4], m[4];
#pragma unroll
    for (int c = 0; c < 4; c++) {
      float p0 = s[hd][c][2], p1 = s[hd][c][3];
      if (c == 0 && first) p0 = p1 = -INFINITY;
      v0[c] = own0 ? s[hd][c + 1][0] : p0;
      v1[c] = own1 ? s[hd][c + 1][1] : p1;
      m[c] = fmaxf(v0[c], v1[c]);
    }
#pragma unroll
    for (int c = 0; c < 4; c++) m[c] = fmaxf(m[c], shfl_xor(m[c], 1));
#pragma unroll
    for (int c = 0; c < 4; c++) m[c] = fmaxf(m[c], shfl_xor(m[c], 2));
#pragma unroll
    for (int c = 0; c < 4; c++) {
      const float nm = -m[c] * kScale;
      v0[c] = ex2(fmaf(v0[c], kScale, nm));
      v1[c] = ex2(fmaf(v1[c], kScale, nm));
      m[c] = v0[c] + v1[c];
    }
#pragma unroll
    for (int c = 0; c < 4; c++) m[c] += shfl_xor(m[c], 1);
#pragma unroll
    for (int c = 0; c < 4; c++) m[c] += shfl_xor(m[c], 2);
#pragma unroll
    for (int c = 0; c < 4; c++) {
      const float inv = rcp(m[c]);
      const uint32_t p = pack2(v0[c] * inv, v1[c] * inv);
#pragma unroll
      for (int ds = 0; ds < 2; ds++) {
        const int J = 4 * hd + 2 * ds;
#pragma unroll
        for (int e = 0; e < 4; e++) o[hd][c][ds][e] = 0.f;
        mma16816(o[hd][c][ds], vt[c][J], vt[c][J + 1], vt[c + 1][J], vt[c + 1][J + 1], p & ~own_mask, p & own_mask);
      }
    }
  }
  TRACE_AT(tile, 11);
  const uint32_t stg = sb + kSmStg + w * 4096;
#pragma unroll
  for (int J = 0; J < 8; J++) {
    const int hd = J >> 2, ds = (J >> 1) & 1, e = 2 * (J & 1);
    stsm4_t(stg + lane * 128 + ((J ^ (lane & 7)) << 4), pack2(o[hd][0][ds][e], o[hd][0][ds][e + 1]),
            pack2(o[hd][1][ds][e], o[hd][1][ds][e + 1]), pack2(o[hd][2][ds][e], o[hd][2][ds][e + 1]),
            pack2(o[hd][3][ds][e], o[hd][3][ds][e + 1]));
  }
  if (elect()) mbar_arrive(sb + kBarResume + att * 8);
  fence_async_smem();
  __syncwarp();
  TRACE_AT(tile, 12);
  if (elect()) {
    bulk_store(g_o + (b * 16 + hp) * kTileBytes + w * 4096, stg, 4096);
    bulk_commit();
    bulk_wait();
    TRACE_AT(tile, 13);
    mbar_arrive(sb + kBarEpi + tile * 8);
  }
  __syncwarp();
}

__device__ __forceinline__ void gather_stats(uint8_t* sm, const uint2* stat, unsigned epoch) {
  const int r = threadIdx.x & 127;
  uint2 a[8];
  unsigned spins = 0;
  while (true) {
    unsigned diff = 0;
#pragma unroll
    for (int i = 0; i < 8; i++) {
      a[i] = ld_relaxed2(stat + i * 128 + r);
      diff |= (a[i].x ^ epoch) | (a[i].y ^ epoch);
    }
    if (__all_sync(0xffffffffu, (diff & 7u) == 0)) break;
    if (++spins > kSpinLimit) __trap();
    __nanosleep(200);
  }
  float s = 0.f, q = 0.f;
#pragma unroll
  for (int i = 0; i < 8; i++) {
    s += untag_value(a[i].x);
    q += untag_value(a[i].y);
  }
  const float mean = s * (1.f / 1024.f);
  const float var = fmaxf(fmaf(-mean, mean, q * (1.f / 1024.f)), 0.f);
  reinterpret_cast<float2*>(sm + kSmStat)[r] = make_float2(rsqrtf(var + 1e-5f), -mean);
}

__device__ __forceinline__ void gather_colsums(uint8_t* sm, int part, int j, int lane, unsigned epoch) {
#pragma unroll 1
  for (int blk = part < 4 ? 0 : 2 * part - 5; blk < (part < 4 ? 3 : 2 * part - 3); blk++) {
    const int col = part < 2 ? blk * kD + (j + 8 * part) * 64
                             : 3 * kD + 64 * (blk + (blk < 3 ? 3 * j : blk < 5 ? 21 + 2 * j : 35 + 2 * j));
    uint2 v;
    unsigned spins = 0;
    while (true) {
      v = ld_relaxed2(reinterpret_cast<const uint2*>(g_cs + col) + lane);
      if (__all_sync(0xffffffffu, (((v.x ^ epoch) | (v.y ^ epoch)) & 7u) == 0)) break;
      if (++spins > kSpinLimit) __trap();
      __nanosleep(100);
    }
    uint8_t* dst = part < 2 ? sm + kSmCsQ + (part * 96 + blk * 32 + lane) * 8 : sm + kSmV1 + (blk * 32 + lane) * 16;
    *reinterpret_cast<float2*>(dst) = make_float2(untag_value(v.x), untag_value(v.y));
  }
}

#define READBACK 0
#define PF_START 0
#define PAUSE_QKV2 7
#define PAUSE_WO 1

__global__ void __cluster_dims__(2, 1, 1) __launch_bounds__(384, 1)
fused_layers_kernel(const __grid_constant__ CUtensorMap map_x, const __grid_constant__ CUtensorMap map_out,
                    const __grid_constant__ CUtensorMap map_qkv, const __grid_constant__ CUtensorMap map_wo,
                    const __grid_constant__ CUtensorMap map_w1a, const __grid_constant__ CUtensorMap map_w1b,
                    const __grid_constant__ CUtensorMap map_w2, const __grid_constant__ CUtensorMap map_csq,
                    const __grid_constant__ CUtensorMap map_cs1, const __grid_constant__ Params prm) {
  extern __shared__ __align__(1024) uint8_t sm[];
  if (threadIdx.x < 128 && blockIdx.x < kCtas) TRACE_AT(15, 1);
  const uint32_t sb = __shfl_sync(0xffffffffu, smem_u32(sm), 0);
  const int warp = __shfl_sync(0xffffffffu, threadIdx.x >> 5, 0), lane = threadIdx.x & 31;
  const int cta = blockIdx.x, rank = cta & 1, cl = cta >> 1;
  const int grp = cl < 4 ? 0 : cl < 36 ? (cl - 4) & 7 : 1 + (cl - 36) % 7;
  const int j = cl < 4 ? 4 + cl : cl < 36 ? (cl - 4) >> 3 : 4 + (cl - 36) / 7;
  const int b = 2 * grp + rank;
  const int xcol = (b >> 3) * kD, xrow = (b & 7) * 128;

  if (cta >= kCtas) {
    helper_cta(&map_csq, &map_cs1, sm, sb, cta - kCtas, warp);
    return;
  }
  if (warp >= 8 && elect()) {
    if (warp == 9) {
#pragma unroll
      for (int s = 0; s < 8; s++) mbar_init(sb + kBarFull + s * 8, 1);
      fence_async_smem();
#pragma unroll
      for (int s = 0; s < 4; s++) {
        const uint32_t full = sb + kBarFull + s * 8, dst = sb + kSmRing + s * 40960;
        mbar_expect_tx(full, 40960);
        tma2d(dst, &map_x, full, xcol + s * 64, xrow);
        tma3d(dst + kTileBytes, &map_qkv, full, j * 64, s * 64, 0);
        tma3d(dst + kTileBytes + 12288, &map_qkv, full, j * 64, s * 64 + 32, 0);
      }
      if (PF_START & 1) l2_prefetch(reinterpret_cast<const uint8_t*>(prm.x) + cta * 32768, 32768);
      if (PF_START & 2) l2_prefetch(reinterpret_cast<const uint8_t*>(prm.wqkv) + cta * 49152, 49152);
    } else if (warp == 8) {
      if (sb & 1023) __trap();
#pragma unroll
      for (int o = kBarTurn; o < kBarInit; o += 8) mbar_init(sb + o, 1);
    } else if (warp == 10) {
#pragma unroll
      for (int o = kBarEpoch; o < kSmEpoch; o += 8) mbar_init(sb + o, o < kBarEmpty ? 1 : o < kBarEpi ? 2 : 4);
    } else {
      mbar_init(sb + kBarInit, 1);
      fence_async_smem();
      mbar_expect_tx(sb + kBarInit, 32768);
      tma2d(sb + kSmX, &map_x, sb + kBarInit, xcol + j * 128, xrow);
      tma2d(sb + kSmX + kTileBytes, &map_x, sb + kBarInit, xcol + j * 128 + 64, xrow);
    }
    asm volatile("fence.mbarrier_init.release.cluster;" ::: "memory");
  }
  __syncwarp();
  asm volatile("barrier.cluster.arrive.relaxed.aligned;" ::: "memory");

  if (warp >= 8) {
    asm volatile("setmaxnreg.dec.sync.aligned.u32 40;");
    if (warp < 10) {
      asm volatile("barrier.cluster.wait.aligned;" ::: "memory");
      uint32_t nb = 32, off = 0, kb = 0;
#define RING_STEP(ISSUE)                                                  \
  do {                                                                    \
    const uint32_t mb = nb - depth, full = sb + kBarFull + (nb & 56);     \
    if (kb == skip) kb += 2;                                              \
    mbar_wait(sb + kBarEmpty + (mb & 56), mb >> 6);                       \
    if (elect()) { ISSUE; }                                               \
    TRACE_ISSUE(9 - warp, nb);                                            \
    kb += inc;                                                            \
    off = off == wrap ? 0 : off + step;                                   \
    nb += 8;                                                              \
  } while (nb != nend)
#pragma unroll 1
      for (int sg = 0; sg < kSegs; sg++) {
        const uint32_t e = prm.seg[sg];
        const int ty = e & 7, mode = (e >> 15) & 3, reset = (e >> 24) & 3;
        const uint32_t nend = nb + (e & 0x1f8);
        const uint32_t step = (e >> 17) & 1 ? 40960 : 32768, wrap = 163840 - step;
        const uint32_t depth = (e >> 18) & 1 ? 40 : 32;
        if (reset) off = reset == 1 ? 0 : reset == 2 ? 40960 : 131072;
        if (mode != kModeContinue) kb = ((e >> 9) & 63) + (mode == kModeHead ? 2 * j : 0);
        const uint32_t inc = mode >= kModeSkip ? 2 : 1, skip = mode >= kModeSkip ? 2 * j + (kb & 1) : 255;
        if (warp == 8) {
          const CUtensorMap* map = ty < 2 ? &map_qkv : ty == 2 ? &map_wo : ty == 3 ? &map_w1a : ty < 6 ? &map_w1b : &map_w2;
          const int c0 = ty < 2 ? (j + 8 * ty) * 64 : 0;
          const int c2 = ty < 2 ? 0 : ty == 3 ? 3 * j : ty == 4 ? 24 + 2 * j : ty == 5 ? 40 + 2 * j : 2 * j;
          const uint32_t half = (ty < 2 || ty == 3) ? 12288 : 8192;
          const uint32_t bytes = 2 * half + (mode == kModeHead ? 0 : kTileBytes);
          const uint32_t dst = sb + kSmRing + kTileBytes + rank * half;
#pragma unroll 1
          RING_STEP(mbar_expect_tx(full, bytes); tma3d_mc(dst + off, map, full, c0, kb * 64 + rank * 32, c2));
        } else if (mode == kModeHead) {
          nb = nend;
          off += 2 * step;
          if (off >= 163840) off -= 163840;
        } else if (sg < 2) {
#pragma unroll 1
          RING_STEP(tma2d(sb + kSmRing + off, &map_x, full, xcol + kb * 64, xrow));
        } else {
          const uint8_t* src = ty == 6 ? g_h + b * 56 * kTileBytes : (ty == 2 ? g_o : g_x) + b * 16 * kTileBytes;
          const int dep = (e >> 19) & 31;
          if (dep != 31) mbar_wait(sb + kBarReady + dep * 8, 0);
#pragma unroll 1
          RING_STEP(bulk_load(sb + kSmRing + off, src + kb * kTileBytes, kTileBytes, full));
        }
      }
#undef RING_STEP
    } else if (warp == 10) {
      unsigned epoch = 0;
      if (lane == 0) epoch = atomicAdd(&g_ticket, 1u) / kGrid + 1;
      epoch = __shfl_sync(0xffffffffu, epoch, 0);
      *reinterpret_cast<unsigned*>(sm + kSmEpoch) = epoch;
      asm volatile("barrier.cluster.wait.aligned;" ::: "memory");
      if (elect()) mbar_arrive(sb + kBarEpoch);
#pragma unroll 1
      for (int i = 0; i < kTiles - 1; i++) {
        const bool xt = i == 2 || i == 6 || i == 9;
        const unsigned* line = g_flag + (i * 16 + b) * 32;
        mbar_wait(sb + kBarEpi + i * 8, 0);
        wait_flags(line + (lane & 7), epoch);
        if (elect()) mbar_arrive(sb + kBarReady + i * 8);
        if (xt) {
          wait_flags(line + 8 + (lane & 7), epoch);
          if (elect()) mbar_arrive(sb + kBarReady + (14 + (i >> 2)) * 8);
        }
      }
    } else {
      {
        uint32_t v[7];
#pragma unroll
        for (int q = 0; q < 7; q++)
          v[q] = reinterpret_cast<const uint32_t*>(prm.b1)[32 * (q + (q < 3 ? 3 * j : q < 5 ? 21 + 2 * j : 35 + 2 * j)) + lane];
        const uint2 u = reinterpret_cast<const uint2*>(prm.b2)[32 * j + lane];
#pragma unroll
        for (int q = 0; q < 7; q++)
          *reinterpret_cast<float2*>(sm + kSmV1 + (q * 32 + lane) * 16 + 8) = make_float2(0.5f * bf_lo(v[q]), 0.5f * bf_hi(v[q]));
        reinterpret_cast<float4*>(sm + kSmB2)[lane] = make_float4(bf_lo(u.x), bf_hi(u.x), bf_lo(u.y), bf_hi(u.y));
      }
      asm volatile("barrier.cluster.wait.aligned;" ::: "memory");
      mbar_wait(sb + kBarEpoch, 0);
      const unsigned epoch = *reinterpret_cast<volatile unsigned*>(sm + kSmEpoch);
#pragma unroll 1
      for (int i = 0; i < kTiles - 1; i++) {
#pragma unroll 1
        for (int part = i == 4 ? 5 : i; part < (i < 2 ? i + 1 : i == 3 || i == 4 ? i + 2 : 0); part++) {
          gather_colsums(sm, part, j, lane, epoch);
          __syncwarp();
          if (elect()) mbar_arrive(sb + kBarCs + part * 8);
        }
        const bool xt = i == 2 || i == 6 || i == 9;
#pragma unroll 1
        for (int h = 0; h < (xt ? 2 : 1); h++) {
          if (h == 0) mbar_wait(sb + kBarEpi + i * 8, 0);
          const int ty = i >= 7 ? i - 7 : i;
          if ((h == 1 || (ty >= 3 && !xt)) && elect()) {
            uint8_t* dst = xt ? g_x + (b * 16 + 2 * j + 1) * kTileBytes
                              : g_h + (b * 56 + 1 + (ty == 3 ? 3 * j : 16 * ty - 40 + 2 * j)) * kTileBytes;
            bulk_store(dst, sb + (xt ? kSmX + kTileBytes : kSmStg), kTileBytes);
            bulk_commit();
            bulk_wait();
            mbar_arrive(sb + kBarFree + i * 8);
          }
          __syncwarp();
          if (elect()) st_release(&g_flag[(i * 16 + b) * 32 + h * 8 + j], epoch);
          __syncwarp();
        }
      }
    }
    __syncwarp();
    asm volatile("barrier.cluster.arrive.relaxed.aligned;\nbarrier.cluster.wait.aligned;" ::: "memory");
  } else {
    asm volatile("setmaxnreg.inc.sync.aligned.u32 232;");
    asm volatile("barrier.cluster.wait.aligned;" ::: "memory");
    const int wg = warp >> 2, w = warp & 3;
    const bool rel = (threadIdx.x & 95) == 0;
    const uint32_t rel_addr = mapa(sb + kBarEmpty, w & 1);
    if (wg == 1) TRACE_AT(15, 0);
#define EPOCH (*reinterpret_cast<volatile unsigned*>(sm + kSmEpoch))

    if (wg == 1) {
      mbar_wait(sb + kBarEpoch, 0);
      mbar_wait(sb + kBarInit, 0);
    }

#pragma unroll 1
    for (int i = wg; i < kTiles; i += 2) {
      const int layer = i >= 7, ty = i - 7 * layer;
      TRACE_AT(i, 15);
      float acc[2][96];
      if (ty == 2 || ty == 6) {
        const uint32_t xrow_addr = sb + kSmX + (32 * w + lane) * 128;
        const float2* b2 = reinterpret_cast<const float2*>(sm + kSmB2) + (lane & 3);
#pragma unroll
        for (int J = 0; J < 16; J++) {
          uint32_t r[4];
          ldsm4(xrow_addr + (J >> 3) * kTileBytes + (((J & 7) ^ (lane & 7)) << 4), r);
          float2 bias = make_float2(0.f, 0.f);
          if (ty == 6) bias = b2[J * 4];
#pragma unroll
          for (int c = 0; c < 4; c++) {
            acc[c & 1][4 * J + (c & 2)] = bf_lo(r[c]) + bias.x;
            acc[c & 1][4 * J + (c & 2) + 1] = bf_hi(r[c]) + bias.y;
            asm volatile("" : "+f"(acc[c & 1][4 * J + (c & 2)]), "+f"(acc[c & 1][4 * J + (c & 2) + 1]));
            if (c & 1) yield_slot();
          }
        }
        mainloop<128>(acc, sb, i, layer * 152 + ty * 16, ty == 6 ? 4 : 0, ty == 6 ? 56 : 16, ty == 2 ? PAUSE_WO : -1,
                      2 * layer + 1, rel_addr, rel, 64, [] {});
        TRACE_AT(i, 2);
#pragma unroll
        for (int h = 0; h < 2; h++) {
#pragma unroll
          for (int J = 8 * h; J < 8 * h + 8; J++)
            stsm4(xrow_addr + h * kTileBytes + (((J & 7) ^ (lane & 7)) << 4), pack2(acc[0][4 * J], acc[0][4 * J + 1]),
                  pack2(acc[1][4 * J], acc[1][4 * J + 1]), pack2(acc[0][4 * J + 2], acc[0][4 * J + 3]),
                  pack2(acc[1][4 * J + 2], acc[1][4 * J + 3]));
          fence_async_smem();
          __syncwarp();
          if (elect()) {
            const uint32_t src = sb + kSmX + h * kTileBytes + w * 4096;
            if (i == kTiles - 1) {
              tma2d_store(&map_out, src, xcol + j * 128 + h * 64, xrow + 32 * w);
              bulk_commit();
              if (h == 1) bulk_wait_read();
            } else if (h == 0) {
              bulk_store(g_x + (b * 16 + 2 * j) * kTileBytes + w * 4096, src, 4096);
              bulk_commit();
              mbar_arrive(sb + kBarX + (i >> 2) * 16);
            } else {
              mbar_arrive(sb + kBarX + (i >> 2) * 16 + 8);
              bulk_wait();
              mbar_arrive(sb + kBarEpi + i * 8);
            }
          }
          __syncwarp();
          yield_slot();
          TRACE_AT(i, 8 + h);
        }
      } else {
        const int xver = 2 * layer + (ty >= 3);
        const uint32_t stg = sb + kSmStg + w * 4096;
        const float4* vec = reinterpret_cast<const float4*>(sm + kSmV1) + (ty == 3 ? 0 : 64 * ty - 160) + (lane & 3);
        uint8_t* hdst = g_h + (b * 56 + (ty == 3 ? 3 * j : 16 * ty - 40 + 2 * j)) * kTileBytes + w * 4096;
        float2 st[4];
        unsigned epoch;
        auto pre = [&] {
          if (ty < 4) mbar_wait(sb + (ty == 1 ? kBarEpi + (i - 1) * 8 : kBarStat + xver * 8), 0);
#pragma unroll
          for (int c = 0; c < 4; c++) st[c] = reinterpret_cast<const float2*>(sm + kSmStat)[32 * w + 8 * c + (lane >> 2)];
          epoch = EPOCH;
        };
        if (ty == 5) {
          const uint32_t nb = (layer * 152 + 80) * 8, s0 = ((((sb & 0x3FFFF) + kSmRing) >> 4) | (1u << 16)) + 3 * 2048;
          mbar_wait(sb + kBarTurn + (i - 1) * 8, 0);
          mbar_wait(sb + kBarFull, nb >> 6);
          TRACE_KB(nb);
          mma_kblock<128, 2>(acc, s0, s0 + kToB);
        } else {
          if (i < 2) {
            zero_acc<192>(acc);
          } else {
            const int n0 = layer * 152 + (ty < 2 ? 2 * ty : 42 + 2 * ty), slot = ty < 2 ? 2 * ty : 2 * ty - 5;
            if (ty < 4) {
              head_blocks<192>(acc, sb, n0, slot, sb + kBarX + (xver - 1) * 16, rel_addr, rel);
            } else {
              head_blocks<128>(acc, sb, n0, slot, sb + kBarX + (xver - 1) * 16, rel_addr, rel);
#pragma unroll
              for (int q = 64; q < 96; q++) acc[0][q] = acc[1][q] = 0.f;
            }
          }
          if (ty == 1 || ty == 4) {
            uint2* stat = g_stat + (xver * 16 + b) * 1024;
            publish_stats(sb, stat + j * 128, w, lane, EPOCH);
            gather_stats(sm, stat, EPOCH);
            __syncwarp();
            if (elect()) mbar_arrive(sb + kBarStat + xver * 8);
            TRACE_AT(i, 14);
            if (i == 8) {
#pragma unroll
              for (int c = 0; c < 4; c++) st[c] = reinterpret_cast<const float2*>(sm + kSmStat)[32 * w + 8 * c + (lane >> 2)];
              add_mean_term(acc, st, sm, 1, lane);
            }
          }
          if (ty < 4) {
            mainloop<192>(acc, sb, i, i < 2 ? 16 * i : layer * 152 + (ty < 2 ? 4 + 14 * ty : 52), i == 8 ? 2 : ty == 3,
                          i < 2 ? 16 : 14, ty == 1 ? PAUSE_QKV2 : -1, xver, rel_addr, rel, 64, pre);
            TRACE_AT(i, 2);
            if (layer == 0) mbar_wait(sb + kBarCs + ty * 8, 0);
            if (ty < 2) {
              if (i != 8) add_mean_term(acc, st, sm, ty, lane);
              epilogue_attn(acc, st, sm, sb, layer, ty, b, j, epoch, i, wg, w);
              TRACE_AT(i, 3);
              continue;
            }
            halve_stats(st);
            gelu_chunk<2>(acc, st, vec, stg, lane, false, nullptr, 0);
            goto common_chunks;
          }
        }
        mainloop<128>(acc, sb, i, layer * 152 + 6 + 15 * ty, 4, ty + 10, -1, 0, rel_addr, rel, ty == 5 ? 0 : 64, pre);
        TRACE_AT(i, 2);
        if (layer == 0) mbar_wait(sb + kBarCs + ty * 8, 0);
        halve_stats(st);
      common_chunks:
        TRACE_AT(i, 8);
        gelu_chunk<0>(acc, st, vec, stg, lane, ty == 3, hdst + 2 * kTileBytes, sb + kBarFree + (i - 1) * 8);
        TRACE_AT(i, 9);
        gelu_chunk<1>(acc, st, vec, stg, lane, true, hdst, 0);
        TRACE_AT(i, 10);
        fence_async_smem();
        __syncwarp();
        if (elect()) mbar_arrive(sb + kBarEpi + i * 8);
      }
      TRACE_AT(i, 3);
    }
#undef EPOCH
    asm volatile("barrier.cluster.arrive.relaxed.aligned;\nbarrier.cluster.wait.aligned;" ::: "memory");
    if (wg == 1) TRACE_AT(15, 2);
  }
}

void build_segments(uint32_t* seg) {
  int n = 0;
  auto add = [&](int ty, int cnt, int kb0, int mode, int wide, int depth5, int dep, int reset) {
    seg[n++] = ty | cnt << 3 | kb0 << 9 | mode << 15 | wide << 17 | depth5 << 18 | dep << 19 | reset << 24;
  };
  for (int l = 0; l < 2; l++) {
    const int t = 7 * l;
    if (l == 0) {
      add(0, 12, 4, kModePlain, 1, 0, 31, 1);
      add(1, 16, 0, kModePlain, 1, 0, 31, 0);
    } else {
      add(0, 2, 0, kModeHead, 1, 0, 31, 1);
      add(1, 2, 0, kModeHead, 1, 0, 31, 0);
      add(0, 7, 0, kModeSkip, 1, 0, 6, 0);
      add(0, 7, 1, kModeSkip, 1, 0, 15, 0);
      add(1, 7, 0, kModeSkip, 1, 0, 31, 0);
      add(1, 7, 1, kModeSkip, 1, 0, 31, 0);
    }
    add(2, 4, 0, kModePlain, 0, 0, t, 1);
    add(2, 4, 4, kModePlain, 0, 1, 31, 0);
    add(2, 8, 8, kModePlain, 0, 1, t + 1, 0);
    add(3, 2, 0, kModeHead, 1, 0, 31, 2);
    add(4, 2, 0, kModeHead, 1, 0, 31, 0);
    add(3, 7, 0, kModeSkip, 1, 0, t + 2, 0);
    add(3, 7, 1, kModeSkip, 1, 0, 14 + 2 * l, 0);
    add(4, 4, 0, kModeSkip, 0, 0, 31, 3);
    add(4, 3, 0, kModeContinue, 0, 1, 31, 0);
    add(4, 7, 1, kModeSkip, 0, 1, 31, 0);
    add(5, 16, 0, kModePlain, 0, 1, 31, 0);
    add(6, 24, 0, kModePlain, 0, 1, t + 3, 0);
    add(6, 16, 24, kModePlain, 0, 1, t + 4, 0);
    add(6, 16, 40, kModePlain, 0, 1, t + 5, 0);
  }
}

typedef CUresult (*EncodeTiledFn)(CUtensorMap*, CUtensorMapDataType, cuuint32_t, void*, const cuuint64_t*,
                                  const cuuint64_t*, const cuuint32_t*, const cuuint32_t*, CUtensorMapInterleave,
                                  CUtensorMapSwizzle, CUtensorMapL2promotion, CUtensorMapFloatOOBfill);

CUtensorMap make_map(EncodeTiledFn enc, const void* p, int rank, const cuuint64_t* dims, const cuuint64_t* strides,
                     const cuuint32_t* box, CUtensorMapSwizzle swizzle = CU_TENSOR_MAP_SWIZZLE_128B) {
  CUtensorMap m;
  const cuuint32_t es[5] = {1, 1, 1, 1, 1};
  enc(&m, CU_TENSOR_MAP_DATA_TYPE_BFLOAT16, rank, const_cast<void*>(p), dims, strides, box, es,
      CU_TENSOR_MAP_INTERLEAVE_NONE, swizzle, CU_TENSOR_MAP_L2_PROMOTION_L2_128B,
      CU_TENSOR_MAP_FLOAT_OOB_FILL_NONE);
  return m;
}

CUtensorMap weight_map(EncodeTiledFn enc, const void* p, int k, int n, int blocks) {
  const cuuint64_t dims[3] = {64, (cuuint64_t)k, (cuuint64_t)n / 64};
  const cuuint64_t strides[2] = {(cuuint64_t)n * 2, 128};
  const cuuint32_t box[3] = {64, 32, (cuuint32_t)blocks};
  return make_map(enc, p, 3, dims, strides, box);
}

CUtensorMap slab_map(EncodeTiledFn enc, const void* p, int n) {
  const cuuint64_t dims[2] = {(cuuint64_t)n, kD};
  const cuuint64_t strides[1] = {(cuuint64_t)n * 2};
  const cuuint32_t box[2] = {128, 128};
  return make_map(enc, p, 2, dims, strides, box, CU_TENSOR_MAP_SWIZZLE_NONE);
}

CUtensorMap token_map(EncodeTiledFn enc, const void* p, int rows) {
  const cuuint64_t dims[2] = {2 * kD, 1024};
  const cuuint64_t strides[1] = {4 * kD};
  const cuuint32_t box[2] = {64, (cuuint32_t)rows};
  return make_map(enc, p, 2, dims, strides, box);
}

}

extern "C" void kernel_launch(void* const* d_in, const int* in_sizes, int n_in, void* d_out, int out_size) {
  (void)in_sizes; (void)n_in; (void)out_size;
  static EncodeTiledFn enc = nullptr;
  if (!enc) {
    void* fn = nullptr;
    cudaDriverEntryPointQueryResult q;
    cudaGetDriverEntryPoint("cuTensorMapEncodeTiled", &fn, cudaEnableDefault, &q);
    enc = (EncodeTiledFn)fn;
    cudaFuncSetAttribute(fused_layers_kernel, cudaFuncAttributeMaxDynamicSharedMemorySize, kSmBytes);
  }
  Params prm;
  prm.x = (const __nv_bfloat16*)d_in[0];
  prm.wqkv = (const __nv_bfloat16*)d_in[1];
  prm.wo = (const __nv_bfloat16*)d_in[2];
  prm.w1 = (const __nv_bfloat16*)d_in[4];
  prm.b1 = (const __nv_bfloat16*)d_in[5];
  prm.w2 = (const __nv_bfloat16*)d_in[6];
  prm.b2 = (const __nv_bfloat16*)d_in[7];
  build_segments(prm.seg);
  const cuuint64_t qd[3] = {kD, kD, 3}, qs[2] = {3 * kD * 2, kD * 2};
  const cuuint32_t qb[3] = {64, 32, 3};
  const CUtensorMap map_x = token_map(enc, d_in[0], 128);
  const CUtensorMap map_out = token_map(enc, d_out, 32);
  const CUtensorMap map_qkv = make_map(enc, prm.wqkv, 3, qd, qs, qb);
  const CUtensorMap map_wo = weight_map(enc, prm.wo, kD, kD, 2);
  const CUtensorMap map_w1a = weight_map(enc, prm.w1, kD, kF, 3);
  const CUtensorMap map_w1b = weight_map(enc, prm.w1, kD, kF, 2);
  const CUtensorMap map_w2 = weight_map(enc, prm.w2, kF, kD, 2);
  fused_layers_kernel<<<kGrid, 384, kSmBytes>>>(map_x, map_out, map_qkv, map_wo, map_w1a, map_w1b, map_w2,
                                                slab_map(enc, prm.wqkv, 3 * kD), slab_map(enc, prm.w1, kF), prm);
}
```

```cpp
#include <cuda.h>
#include <cuda_bf16.h>
#include <cuda_runtime.h>
#include <stdint.h>

namespace {

constexpr int kD = 1024;
constexpr int kF = 3584;
constexpr int kCtas = 128;
constexpr int kGrid = 132;
constexpr int kTiles = 14;
constexpr int kTileBytes = 16384;

constexpr int kSmRing = 0;
constexpr int kSmX = 163840;
constexpr int kSmStg = kSmX + 32768;
constexpr int kSmHalo = kSmStg + 16384;
constexpr int kSmCsQ = kSmHalo + 6144;
constexpr int kSmV1 = kSmCsQ + 384 * 4;
constexpr int kSmB2 = kSmV1 + 448 * 8;
constexpr int kSmStat = kSmB2 + 128 * 4;
constexpr int kSmBar = kSmStat + 128 * 8;
constexpr int kBarFull = kSmBar;
constexpr int kBarTurn = kBarFull + 8 * 8;
constexpr int kBarReady = kBarTurn + 14 * 8;
constexpr int kBarPause = kBarReady + 17 * 8;
constexpr int kBarFree = kBarPause + 4 * 8;
constexpr int kBarCs = kBarFree + 14 * 8;
constexpr int kBarInit = kBarCs + 6 * 8;
constexpr int kBarEpoch = kBarInit + 8;
constexpr int kBarEmpty = kBarEpoch + 8;
constexpr int kBarEpi = kBarEmpty + 9 * 8;
constexpr int kBarX = kBarEpi + 14 * 8;
constexpr int kBarStat = kBarX + 6 * 8;
constexpr int kBarResume = kBarStat + 4 * 8;
constexpr int kSmEpoch = kBarResume + 4 * 8;
constexpr int kSmBytes = kSmEpoch + 16;
constexpr int kSegs = 36;

constexpr int kFlagLines = kTiles * 16;

constexpr unsigned kSpinLimit = 1u << 22;

__device__ __align__(1024) uint8_t g_x[16 * 16 * kTileBytes];
__device__ __align__(1024) uint8_t g_o[16 * 16 * kTileBytes];
__device__ __align__(1024) uint8_t g_h[16 * 56 * kTileBytes];
__device__ __align__(128) uint2 g_stat[4 * 16 * 128 * 8];
__device__ __align__(128) unsigned g_cs[3 * kD + kF];
__device__ __align__(128) uint4 g_halo[2 * 16 * 16 * 256];
__device__ __align__(128) unsigned g_flag[kFlagLines * 32];
__device__ unsigned g_ticket;

#define TRACE_AT(tile, k)
#define TRACE_PUB(i, k, c)
#define TRACE_ISSUE(which, nb)

struct Params {
  const __nv_bfloat16* x;
  const __nv_bfloat16* wqkv;
  const __nv_bfloat16* wo;
  const __nv_bfloat16* w1;
  const __nv_bfloat16* b1;
  const __nv_bfloat16* w2;
  const __nv_bfloat16* b2;
  uint32_t seg[kSegs];
};

__device__ __forceinline__ uint32_t smem_u32(const void* p) {
  return (uint32_t)__cvta_generic_to_shared(p);
}
__device__ __forceinline__ uint32_t mapa(uint32_t a, uint32_t cta) {
  uint32_t r;
  asm("mapa.shared::cluster.u32 %0, %1, %2;" : "=r"(r) : "r"(a), "r"(cta));
  return r;
}
__device__ __forceinline__ void mbar_init(uint32_t bar, int cnt) {
  asm volatile("mbarrier.init.shared::cta.b64 [%0], %1;" ::"r"(bar), "r"(cnt) : "memory");
}
__device__ __forceinline__ void mbar_expect_tx(uint32_t bar, uint32_t bytes) {
  asm volatile("mbarrier.arrive.expect_tx.shared::cta.b64 _, [%0], %1;" ::"r"(bar), "r"(bytes) : "memory");
}
__device__ __forceinline__ void mbar_arrive(uint32_t bar) {
  asm volatile("mbarrier.arrive.shared::cta.b64 _, [%0];" ::"r"(bar) : "memory");
}
__device__ __forceinline__ void mbar_arrive_cluster(uint32_t cluster_addr) {
  asm volatile("mbarrier.arrive.shared::cluster.b64 _, [%0];" ::"r"(cluster_addr) : "memory");
}
__device__ __forceinline__ void mbar_wait(uint32_t bar, uint32_t parity) {
  asm volatile(
      "{\n.reg .pred p;\n.reg .u32 c;\n"
      "mbarrier.try_wait.parity.shared::cta.b64 p, [%0], %1;\n"
      "@p bra.uni DONE;\n"
      "mov.u32 c, 0;\n"
      "RETRY:\n"
      "mbarrier.try_wait.parity.shared::cta.b64 p, [%0], %1;\n"
      "@p bra.uni DONE;\n"
      "add.u32 c, c, 1;\n"
      "setp.lt.u32 p, c, %2;\n"
      "@p bra.uni RETRY;\n"
      "trap;\n"
      "DONE:\n}" ::"r"(bar), "r"(parity), "n"(1u << 19)
      : "memory");
}
__device__ __forceinline__ void tma3d(uint32_t dst, const CUtensorMap* m, uint32_t bar, int c0, int c1, int c2) {
  asm volatile(
      "cp.async.bulk.tensor.3d.shared::cluster.global.mbarrier::complete_tx::bytes [%0], [%1, {%3, %4, %5}], [%2];"
      ::"r"(dst), "l"(m), "r"(bar), "r"(c0), "r"(c1), "r"(c2) : "memory");
}
__device__ __forceinline__ void tma3d_mc(uint32_t dst, const CUtensorMap* m, uint32_t bar, int c0, int c1, int c2) {
  asm volatile(
      "cp.async.bulk.tensor.3d.shared::cluster.global.mbarrier::complete_tx::bytes.multicast::cluster"
      " [%0], [%1, {%3, %4, %5}], [%2], %6;"
      ::"r"(dst), "l"(m), "r"(bar), "r"(c0), "r"(c1), "r"(c2), "h"((uint16_t)3) : "memory");
}
__device__ __forceinline__ void tma2d(uint32_t dst, const CUtensorMap* m, uint32_t bar, int c0, int c1) {
  asm volatile(
      "cp.async.bulk.tensor.2d.shared::cluster.global.mbarrier::complete_tx::bytes [%0], [%1, {%3, %4}], [%2];"
      ::"r"(dst), "l"(m), "r"(bar), "r"(c0), "r"(c1) : "memory");
}
__device__ __forceinline__ void tma2d_store(const CUtensorMap* m, uint32_t src, int c0, int c1) {
  asm volatile("cp.async.bulk.tensor.2d.global.shared::cta.bulk_group [%0, {%2, %3}], [%1];"
               ::"l"(m), "r"(src), "r"(c0), "r"(c1) : "memory");
}
__device__ __forceinline__ bool elect() {
  uint32_t p;
  asm volatile("{\n.reg .pred p;\nelect.sync _|p, 0xffffffff;\nselp.b32 %0, 1, 0, p;\n}" : "=r"(p));
  return p;
}
__device__ __forceinline__ void bulk_load(uint32_t dst, const void* src, uint32_t bytes, uint32_t bar) {
  asm volatile("cp.async.bulk.shared::cluster.global.mbarrier::complete_tx::bytes [%0], [%1], %2, [%3];"
               ::"r"(dst), "l"(src), "r"(bytes), "r"(bar) : "memory");
}
__device__ __forceinline__ void bulk_store(void* dst, uint32_t src, uint32_t bytes) {
  asm volatile("cp.async.bulk.global.shared::cta.bulk_group [%0], [%1], %2;" ::"l"(dst), "r"(src), "r"(bytes)
               : "memory");
}
__device__ __forceinline__ void bulk_commit() { asm volatile("cp.async.bulk.commit_group;" ::: "memory"); }
__device__ __forceinline__ void bulk_wait_read() { asm volatile("cp.async.bulk.wait_group.read 0;" ::: "memory"); }
__device__ __forceinline__ void bulk_wait() { asm volatile("cp.async.bulk.wait_group 0;" ::: "memory"); }
__device__ __forceinline__ void l2_prefetch(const void* p, uint32_t bytes) {
  asm volatile("cp.async.bulk.prefetch.L2.global [%0], %1;" ::"l"(p), "r"(bytes) : "memory");
}
__device__ __forceinline__ void fence_async_smem() { asm volatile("fence.proxy.async.shared::cta;" ::: "memory"); }
__device__ __forceinline__ unsigned ld_relaxed(const unsigned* p) {
  unsigned v;
  asm volatile("ld.relaxed.gpu.global.u32 %0, [%1];" : "=r"(v) : "l"(p) : "memory");
  return v;
}
__device__ __forceinline__ uint2 ld_relaxed2(const uint2* p) {
  uint2 v;
  asm volatile("ld.relaxed.gpu.global.v2.u32 {%0, %1}, [%2];" : "=r"(v.x), "=r"(v.y) : "l"(p) : "memory");
  return v;
}
__device__ __forceinline__ void st_relaxed(unsigned* p, unsigned v) {
  asm volatile("st.relaxed.gpu.global.u32 [%0], %1;" ::"l"(p), "r"(v) : "memory");
}
__device__ __forceinline__ void st_release(unsigned* p, unsigned v) {
  asm volatile("st.release.gpu.global.u32 [%0], %1;" ::"l"(p), "r"(v) : "memory");
}
#define ACQ_MODE 1
__device__ __forceinline__ void wait_flags(const unsigned* p, unsigned epoch) {
  unsigned spins = 0;
  while (true) {
    const unsigned v = ld_relaxed(p);
    if (__all_sync(0xffffffffu, v == epoch)) break;
    if (++spins > kSpinLimit) __trap();
  }
  if (ACQ_MODE) asm volatile("fence.acquire.gpu;\nfence.proxy.async.global;" ::: "memory");
  __syncwarp();
}
__device__ __forceinline__ unsigned tag_value(float v, unsigned epoch) {
  return (__float_as_uint(v) & ~7u) | (epoch & 7u);
}
__device__ __forceinline__ float untag_value(unsigned v) { return __uint_as_float(v & ~7u); }
__device__ __forceinline__ void stsm4(uint32_t a, uint32_t r0, uint32_t r1, uint32_t r2, uint32_t r3) {
  asm volatile("stmatrix.sync.aligned.m8n8.x4.shared.b16 [%0], {%1, %2, %3, %4};" ::"r"(a), "r"(r0), "r"(r1),
               "r"(r2), "r"(r3) : "memory");
}
__device__ __forceinline__ void stsm4_if(bool on, uint32_t a, uint32_t r0, uint32_t r1, uint32_t r2, uint32_t r3) {
  asm volatile("{\n.reg .pred p;\nsetp.ne.u32 p, %5, 0;\n"
               "@p stmatrix.sync.aligned.m8n8.x4.shared.b16 [%0], {%1, %2, %3, %4};\n}" ::"r"(a), "r"(r0), "r"(r1),
               "r"(r2), "r"(r3), "r"((uint32_t)on) : "memory");
}
__device__ __forceinline__ void stsm4_t(uint32_t a, uint32_t r0, uint32_t r1, uint32_t r2, uint32_t r3) {
  asm volatile("stmatrix.sync.aligned.m8n8.x4.trans.shared.b16 [%0], {%1, %2, %3, %4};" ::"r"(a), "r"(r0),
               "r"(r1), "r"(r2), "r"(r3) : "memory");
}
__device__ __forceinline__ uint32_t transpose8(uint32_t a) {
  uint32_t d;
  asm volatile("movmatrix.sync.aligned.m8n8.trans.b16 %0, %1;" : "=r"(d) : "r"(a));
  return d;
}
__device__ __forceinline__ void mma16816(float (&c)[4], uint32_t a0, uint32_t a1, uint32_t a2, uint32_t a3,
                                         uint32_t b0, uint32_t b1) {
  asm volatile("mma.sync.aligned.m16n8k16.row.col.f32.bf16.bf16.f32 {%0, %1, %2, %3}, {%4, %5, %6, %7}, {%8, %9}, "
               "{%0, %1, %2, %3};"
               : "+f"(c[0]), "+f"(c[1]), "+f"(c[2]), "+f"(c[3])
               : "r"(a0), "r"(a1), "r"(a2), "r"(a3), "r"(b0), "r"(b1));
}
__device__ __forceinline__ float shfl_xor(float v, int m) {
  float r;
  asm volatile("shfl.sync.bfly.b32 %0, %1, %2, 31, 0xffffffff;" : "=f"(r) : "f"(v), "r"(m));
  return r;
}
__device__ __forceinline__ float tanh_fast(float x) {
  float r;
  asm volatile("tanh.approx.f32 %0, %1;" : "=f"(r) : "f"(x));
  return r;
}
__device__ __forceinline__ void ldsm4(uint32_t a, uint32_t (&r)[4]) {
  asm volatile("ldmatrix.sync.aligned.m8n8.x4.shared.b16 {%0, %1, %2, %3}, [%4];"
               : "=r"(r[0]), "=r"(r[1]), "=r"(r[2]), "=r"(r[3]) : "r"(a) : "memory");
}
__device__ __forceinline__ uint32_t pack2(float lo, float hi) {
  uint32_t r;
  asm volatile("cvt.rn.bf16x2.f32 %0, %1, %2;" : "=r"(r) : "f"(hi), "f"(lo));
  return r;
}
__device__ __forceinline__ float bf_lo(uint32_t r) { return __uint_as_float(r << 16); }
__device__ __forceinline__ float bf_hi(uint32_t r) { return __uint_as_float(r & 0xffff0000u); }
__device__ __forceinline__ float ex2(float x) {
  float r;
  asm("ex2.approx.ftz.f32 %0, %1;" : "=f"(r) : "f"(x));
  return r;
}
__device__ __forceinline__ float rcp(float x) {
  float r;
  asm("rcp.approx.ftz.f32 %0, %1;" : "=f"(r) : "f"(x));
  return r;
}
template <int N>
__device__ __forceinline__ void wg_wait() {
  asm volatile("wgmma.wait_group.sync.aligned %0;" ::"n"(N) : "memory");
}
__device__ __forceinline__ void yield_slot() { asm volatile("pmevent 0;"); }
__device__ __forceinline__ void wg_bar(int wg) { asm volatile("bar.sync %0, 128;" ::"r"(wg + 1) : "memory"); }

template <int N, int KIND>
__device__ __forceinline__ void mma_kblock(float (&acc)[2][96], uint32_t a, uint32_t b);

#define F8(m, d, i) m(d[i]), m(d[i + 1]), m(d[i + 2]), m(d[i + 3]), m(d[i + 4]), m(d[i + 5]), m(d[i + 6]), m(d[i + 7])
#define KSTEP(N, A, B, oa0, oa1, ob, sd)                                                   \
  "add.u32 t, " B ", " #ob ";\nmov.b64 db, {t, hb};\n"                                      \
  "add.u32 t, " A ", " #oa0 ";\nmov.b64 da, {t, ha};\n"                                     \
  "wgmma.mma_async.sync.aligned.m64n" #N "k16.f32.bf16.bf16 {" ACC##N##_0 "}, da, db, " #sd ", 1, 1, 0, 1;\n" \
  "add.u32 t, " A ", " #oa1 ";\nmov.b64 da, {t, ha};\n"                                     \
  "wgmma.mma_async.sync.aligned.m64n" #N "k16.f32.bf16.bf16 {" ACC##N##_1 "}, da, db, " #sd ", 1, 1, 0, 1;\n"

#define MMA_KBLOCK(N, KIND, A, B, ob2, ob3, sd, MID, MODE)                                 \
  template <>                                                                              \
  __device__ __forceinline__ void mma_kblock<N, KIND>(float (&acc)[2][96], uint32_t a, uint32_t b) { \
    asm volatile("{\n.reg .b32 t, ha, hb;\n.reg .b64 da, db;\n"                            \
                 "mov.b32 ha, 0x40000080;\nmov.b32 hb, 0x40000040;\n"                       \
                 "wgmma.fence.sync.aligned;\n"                                             \
                 KSTEP(N, A, B, 0, 64, 0, sd) KSTEP(N, A, B, 2, 66, 128, 1) KSTEP(N, A, B, 4, 68, ob2, 1) \
                 MID KSTEP(N, A, B, 6, 70, ob3, 1) "wgmma.commit_group.sync.aligned;\n}\n"  \
                 : OPS##N(MODE) : "r"(a), "r"(b) : "memory");                              \
  }
#define MMA_KBLOCKS(N, A, B, ob2, ob3)                                                     \
  MMA_KBLOCK(N, 0, A, B, ob2, ob3, 1, "", "+f")                                            \
  MMA_KBLOCK(N, 1, A, B, ob2, ob3, 1, "wgmma.commit_group.sync.aligned;\n", "+f")          \
  MMA_KBLOCK(N, 2, A, B, ob2, ob3, 0, "", "=f")

#define ACC128_0 \
  "%0, %1, %2, %3, %4, %5, %6, %7, %8, %9, %10, %11, %12, %13, %14, %15, " \
  "%16, %17, %18, %19, %20, %21, %22, %23, %24, %25, %26, %27, %28, %29, %30, %31, " \
  "%32, %33, %34, %35, %36, %37, %38, %39, %40, %41, %42, %43, %44, %45, %46, %47, " \
  "%48, %49, %50, %51, %52, %53, %54, %55, %56, %57, %58, %59, %60, %61, %62, %63"
#define ACC128_1 \
  "%64, %65, %66, %67, %68, %69, %70, %71, %72, %73, %74, %75, %76, %77, %78, %79, " \
  "%80, %81, %82, %83, %84, %85, %86, %87, %88, %89, %90, %91, %92, %93, %94, %95, " \
  "%96, %97, %98, %99, %100, %101, %102, %103, %104, %105, %106, %107, %108, %109, %110, %111, " \
  "%112, %113, %114, %115, %116, %117, %118, %119, %120, %121, %122, %123, %124, %125, %126, %127"
#define OPS128(m) \
  F8(m, acc[0], 0), F8(m, acc[0], 8), F8(m, acc[0], 16), F8(m, acc[0], 24), F8(m, acc[0], 32), F8(m, acc[0], 40), F8(m, acc[0], 48), F8(m, acc[0], 56), \
        F8(m, acc[1], 0), F8(m, acc[1], 8), F8(m, acc[1], 16), F8(m, acc[1], 24), F8(m, acc[1], 32), F8(m, acc[1], 40), F8(m, acc[1], 48), F8(m, acc[1], 56)
MMA_KBLOCKS(128, "%128", "%129", 512, 640)

#define ACC192_0 \
  "%0, %1, %2, %3, %4, %5, %6, %7, %8, %9, %10, %11, %12, %13, %14, %15, " \
  "%16, %17, %18, %19, %20, %21, %22, %23, %24, %25, %26, %27, %28, %29, %30, %31, " \
  "%32, %33, %34, %35, %36, %37, %38, %39, %40, %41, %42, %43, %44, %45, %46, %47, " \
  "%48, %49, %50, %51, %52, %53, %54, %55, %56, %57, %58, %59, %60, %61, %62, %63, " \
  "%64, %65, %66, %67, %68, %69, %70, %71, %72, %73, %74, %75, %76, %77, %78, %79, " \
  "%80, %81, %82, %83, %84, %85, %86, %87, %88, %89, %90, %91, %92, %93, %94, %95"
#define ACC192_1 \
  "%96, %97, %98, %99, %100, %101, %102, %103, %104, %105, %106, %107, %108, %109, %110, %111, " \
  "%112, %113, %114, %115, %116, %117, %118, %119, %120, %121, %122, %123, %124, %125, %126, %127, " \
  "%128, %129, %130, %131, %132, %133, %134, %135, %136, %137, %138, %139, %140, %141, %142, %143, " \
  "%144, %145, %146, %147, %148, %149, %150, %151, %152, %153, %154, %155, %156, %157, %158, %159, " \
  "%160, %161, %162, %163, %164, %165, %166, %167, %168, %169, %170, %171, %172, %173, %174, %175, " \
  "%176, %177, %178, %179, %180, %181, %182, %183, %184, %185, %186, %187, %188, %189, %190, %191"
#define OPS192(m) \
  F8(m, acc[0], 0), F8(m, acc[0], 8), F8(m, acc[0], 16), F8(m, acc[0], 24), F8(m, acc[0], 32), F8(m, acc[0], 40), F8(m, acc[0], 48), F8(m, acc[0], 56), F8(m, acc[0], 64), F8(m, acc[0], 72), F8(m, acc[0], 80), F8(m, acc[0], 88), \
        F8(m, acc[1], 0), F8(m, acc[1], 8), F8(m, acc[1], 16), F8(m, acc[1], 24), F8(m, acc[1], 32), F8(m, acc[1], 40), F8(m, acc[1], 48), F8(m, acc[1], 56), F8(m, acc[1], 64), F8(m, acc[1], 72), F8(m, acc[1], 80), F8(m, acc[1], 88)
MMA_KBLOCKS(192, "%192", "%193", 768, 896)

enum { kModePlain = 0, kModeHead = 1, kModeSkip = 2, kModeContinue = 3 };

template <int N>
__device__ __forceinline__ void fence_acc(float (&acc)[2][96]) {
#pragma unroll
  for (int h = 0; h < 2; h++)
#pragma unroll
    for (int i = 0; i < N / 2; i++) asm volatile("" : "+f"(acc[h][i])::"memory");
}

template <int N>
__device__ __forceinline__ void zero_acc(float (&acc)[2][96]) {
#pragma unroll
  for (int h = 0; h < 2; h++)
#pragma unroll
    for (int i = 0; i < N / 2; i++) acc[h][i] = 0.f;
}

constexpr uint32_t kToB = (kTileBytes >> 4) + ((4096u >> 4) << 16) - (1u << 16);

#define TRACE_KB(nb)

#define HEAD_BOTH 1
template <int N>
__device__ __forceinline__ void head_blocks(float (&acc)[2][96], uint32_t sb, int n0, int slot, uint32_t xbar, uint32_t ebar,
                                            uint32_t rel_addr, bool rel) {
  const uint32_t ring = (((sb & 0x3FFFF) + kSmRing) >> 4) | (1u << 16);
  const uint32_t xdesc = (((sb & 0x3FFFF) + kSmX) >> 4) | (1u << 16);
  const uint32_t nb = n0 * 8;
  mbar_wait(HEAD_BOTH == 2 ? ebar : xbar + 8 * HEAD_BOTH, 0);
  mbar_wait(sb + kBarFull + (nb & 56), nb >> 6);
  TRACE_KB(nb);
  mma_kblock<N, 2>(acc, xdesc, ring + slot * 2560 + kToB);
  mbar_wait(xbar + 8, 0);
  mbar_wait(sb + kBarFull + (nb & 56) + 8, nb >> 6);
  TRACE_KB(nb + 8);
  mma_kblock<N, 0>(acc, xdesc + (kTileBytes >> 4), ring + ((slot + 1) & 3) * 2560 + kToB);
  wg_wait<1>();
  if (rel) mbar_arrive_cluster(rel_addr + (nb & 56));
  wg_wait<0>();
  if (rel) mbar_arrive_cluster(rel_addr + (nb & 56) + 8);
  fence_acc<N>(acc);
}

template <int N, class Pre>
__device__ __forceinline__ void mainloop(float (&acc)[2][96], uint32_t sb, int tile, int n0, int slot, int nkb,
                                         int pause_kk, int att, uint32_t rel_addr, bool rel, uint32_t prev, Pre pre) {
  constexpr uint32_t kStep = (N == 192 ? 5 : 4) * 512;
  const uint32_t ring = (((sb & 0x3FFFF) + kSmRing) >> 4) | (1u << 16);
  uint32_t st = ring + slot * kStep;
  uint32_t nb = n0 * 8;
  const uint32_t last = nb + 8 * (nkb - 1);
  uint32_t stop = pause_kk >= 0 ? nb + 8 * pause_kk : last;
  const bool signal = (threadIdx.x & 127) == 64;
  fence_acc<N>(acc);
  if (tile > 0) mbar_wait(sb + kBarTurn + (tile - 1) * 8, 0);
  TRACE_AT(tile, 0);
#pragma unroll 1
  while (true) {
#pragma unroll 1
    do {
      mbar_wait(sb + kBarFull + (nb & 56), nb >> 6);
      if (nb == n0 * 8) TRACE_AT(tile, 1);
      TRACE_KB(nb);
      mma_kblock<N, 0>(acc, st, st + kToB);
      wg_wait<1>();
      if (rel) mbar_arrive_cluster(rel_addr + prev);
      prev = nb & 56;
      st += kStep;
      if (st == ring + 10240) st = ring;
      nb += 8;
    } while (nb != stop);
    if (stop == last) break;
    stop = last;
    if (signal) mbar_arrive(sb + kBarPause + att * 8);
    wg_wait<0>();
    if (rel) mbar_arrive_cluster(rel_addr + prev);
    prev = 64;
    mbar_wait(sb + kBarResume + att * 8, 0);
  }
  mbar_wait(sb + kBarFull + (nb & 56), nb >> 6);
  TRACE_KB(nb);
  mma_kblock<N, 1>(acc, st, st + kToB);
  wg_wait<2>();
  if (rel) mbar_arrive_cluster(rel_addr + prev);
  pre();
  wg_wait<1>();
  if (signal) mbar_arrive(sb + kBarTurn + tile * 8);
  wg_wait<0>();
  if (rel) mbar_arrive_cluster(rel_addr + (nb & 56));
  fence_acc<N>(acc);
}

__device__ __forceinline__ void publish_stats(uint32_t sb, uint2* stat, int w, int lane, unsigned epoch) {
  const uint32_t row = sb + kSmX + (32 * w + lane) * 128;
  float s[4], q[4];
#pragma unroll
  for (int c = 0; c < 4; c++) s[c] = q[c] = 0.f;
  uint32_t nx[4];
  ldsm4(row + ((lane & 7) << 4), nx);
#pragma unroll 1
  for (int J = 1; J <= 16; J++) {
    const uint32_t r[4] = {nx[0], nx[1], nx[2], nx[3]};
    ldsm4(row + ((J >> 3) & 1) * kTileBytes + (((J ^ lane) & 7) << 4), nx);
#pragma unroll
    for (int c = 0; c < 4; c++) {
      const float lo = bf_lo(r[c]);
      s[c] += lo;
      q[c] = fmaf(lo, lo, q[c]);
      if (c & 1) yield_slot();
    }
#pragma unroll
    for (int c = 0; c < 4; c++) {
      const float hi = bf_hi(r[c]);
      s[c] += hi;
      q[c] = fmaf(hi, hi, q[c]);
      if (c & 1) yield_slot();
    }
  }
#pragma unroll
  for (int c = 0; c < 4; c++) {
    s[c] += shfl_xor(s[c], 1);
    q[c] += shfl_xor(q[c], 1);
    s[c] += shfl_xor(s[c], 2);
    q[c] += shfl_xor(q[c], 2);
  }
  const int t = lane & 3, g = lane >> 2;
  const float so = t == 0 ? s[0] : t == 1 ? s[1] : t == 2 ? s[2] : s[3];
  const float qo = t == 0 ? q[0] : t == 1 ? q[1] : t == 2 ? q[2] : q[3];
  asm volatile("st.relaxed.gpu.global.v2.u32 [%0], {%1, %2};" ::"l"(stat + 32 * w + 8 * t + g),
               "r"(tag_value(so, epoch)), "r"(tag_value(qo, epoch)) : "memory");
}

__device__ __forceinline__ void add_chunk(float (&a)[8], const uint4& v) {
  a[0] += bf_lo(v.x); a[1] += bf_hi(v.x);
  a[2] += bf_lo(v.y); a[3] += bf_hi(v.y);
  a[4] += bf_lo(v.z); a[5] += bf_hi(v.z);
  a[6] += bf_lo(v.w); a[7] += bf_hi(v.w);
}

__device__ __forceinline__ int helper_col(int id, int slab) {
  return slab < 6 ? (slab % 3) * kD + (slab / 3) * 512 + id * 128 : (slab - 6) * 512 + id * 128;
}
__device__ __forceinline__ void helper_cta(const CUtensorMap* map_q, const CUtensorMap* map_1, uint8_t* sm,
                                           uint32_t sb, int id, int warp) {
  constexpr int kRed = 6 * 32768, kBar = kRed + 2 * 4096;
  const int tid = threadIdx.x;
  if (warp == 8 && elect()) {
#pragma unroll
    for (int s = 0; s < 6; s++) {
      mbar_init(sb + kBar + s * 8, 1);
      mbar_init(sb + kBar + 64 + s * 8, 4);
    }
    fence_async_smem();
#pragma unroll
    for (int s = 0; s < 6; s++) {
      mbar_expect_tx(sb + kBar + s * 8, 32768);
      tma2d(sb + s * 32768, map_q, sb + kBar + s * 8, id * 128, s * 128);
    }
  }
  __syncthreads();
  if (warp == 8) {
    int slot = 0, ph = 0;
#pragma unroll 1
    for (int n = 6; n < 104; n++) {
      mbar_wait(sb + kBar + 64 + slot * 8, ph);
      if (elect()) {
        mbar_expect_tx(sb + kBar + slot * 8, 32768);
        tma2d(sb + slot * 32768, n < 48 ? map_q : map_1, sb + kBar + slot * 8, helper_col(id, n >> 3), (n & 7) * 128);
      }
      if (++slot == 6) slot = 0, ph ^= 1;
    }
  } else if (warp < 8) {
    if (tid == 0) *reinterpret_cast<unsigned*>(sm + kBar + 128) = atomicAdd(&g_ticket, 1u) / kGrid + 1;
    int slot = warp >> 2, ph = 0;
#pragma unroll 1
    for (int slab = 0; slab < 13; slab++) {
      float a[8];
#pragma unroll
      for (int e = 0; e < 8; e++) a[e] = 0.f;
#pragma unroll 1
      for (int box = 0; box < 4; box++) {
        mbar_wait(sb + kBar + slot * 8, ph);
        const uint4* p = reinterpret_cast<const uint4*>(sm + slot * 32768) + (tid & 127);
        uint4 v[16];
#pragma unroll
        for (int i = 0; i < 16; i++) v[i] = p[i * 128];
        __syncwarp();
        if (elect()) mbar_arrive(sb + kBar + 64 + slot * 8);
#pragma unroll
        for (int i = 0; i < 16; i++) add_chunk(a, v[i]);
        slot += 2;
        if (slot >= 6) slot -= 6, ph ^= 1;
      }
      float* red = reinterpret_cast<float*>(sm + kRed + (slab & 1) * 4096);
#pragma unroll
      for (int e = 0; e < 8; e++) a[e] += shfl_xor(a[e], 16);
      if ((tid & 16) == 0) {
        float4* d = reinterpret_cast<float4*>(red + warp * 128 + (tid & 15) * 8);
        d[0] = make_float4(a[0], a[1], a[2], a[3]);
        d[1] = make_float4(a[4], a[5], a[6], a[7]);
      }
      asm volatile("bar.sync 1, 256;" ::: "memory");
      if (warp < 4) {
        float t = 0.f;
#pragma unroll
        for (int q = 0; q < 8; q++) t += red[q * 128 + tid];
        st_relaxed(g_cs + (slab < 6 ? 0 : 3 * kD) + helper_col(id, slab) + tid,
                   tag_value(t, *reinterpret_cast<volatile unsigned*>(sm + kBar + 128)));
      }
    }
  }
}

constexpr float kGeluBeta = 0.3292034911525734f;
constexpr float kGeluK = 2.423681954311584f;

__device__ __forceinline__ void store_staged(uint8_t* dst, uint32_t stg) {
  fence_async_smem();
  __syncwarp();
  if (elect()) {
    bulk_store(dst, stg, 4096);
    bulk_commit();
  }
}

#define GY_MASK 0x3F
#define GY_MASK2 0x3f
#define GY(k) if (((CH == 2 ? GY_MASK2 : GY_MASK) >> k) & 1) yield_slot()
template <int CH>
__device__ __forceinline__ void gelu_chunk(const float (&acc)[2][96], const float2 (&st)[4], const float4* vec,
                                           uint32_t stg, int lane, bool chained, uint8_t* prev, uint32_t free_bar) {
  uint32_t pk[8][4];
  float u[3][4], z[3][4];
  float4 v = vec[CH * 32], vn = v;
#pragma unroll
  for (int s = 0; s < 18; s++) {
    const int J = CH * 8 + (s >> 1), c0 = 2 * (s & 1), cur = s % 3, p1 = (s + 2) % 3, p2 = (s + 1) % 3;
    if (s < 16) {
      if (c0 == 0 && s < 14) vn = vec[(J + 1) * 4];
#pragma unroll
      for (int e = 0; e < 4; e++) {
        const int c = c0 + (e >> 1);
        z[cur][e] = fmaf(st[c].y, e & 1 ? v.y : v.x, e & 1 ? v.w : v.z);
      }
      if (c0 == 2) v = vn;
    }
    if (s >= 1 && s < 17) z[p1][0] = tanh_fast(z[p1][0]);
    GY(0);
    if (s < 16) {
#pragma unroll
      for (int e = 0; e < 4; e++) {
        const int c = c0 + (e >> 1);
        u[cur][e] = fmaf(acc[c & 1][4 * J + c0 + (e & 1)], st[c].x, z[cur][e]);
      }
    }
    if (s >= 1 && s < 17) z[p1][1] = tanh_fast(z[p1][1]);
    GY(1);
    if (s >= 11) {
      const int jj = s - 11;
      stsm4(stg + lane * 128 + ((jj ^ (lane & 7)) << 4), pk[jj][0], pk[jj][1], pk[jj][2], pk[jj][3]);
    }
    if (s < 16) {
#pragma unroll
      for (int e = 0; e < 4; e++) z[cur][e] = fmaf(u[cur][e], u[cur][e], kGeluK);
    }
    if (s >= 1 && s < 17) z[p1][2] = tanh_fast(z[p1][2]);
    GY(3);
    if (s >= 2) {
      pk[(s - 2) >> 1][c0] = pack2(fmaf(u[p2][0], z[p2][0], u[p2][0]), fmaf(u[p2][1], z[p2][1], u[p2][1]));
      pk[(s - 2) >> 1][c0 + 1] = pack2(fmaf(u[p2][2], z[p2][2], u[p2][2]), fmaf(u[p2][3], z[p2][3], u[p2][3]));
    }
    GY(4);
    if (s < 16) {
#pragma unroll
      for (int e = 0; e < 4; e++) z[cur][e] = u[cur][e] * z[cur][e];
    }
    if (s >= 1 && s < 17) z[p1][3] = tanh_fast(z[p1][3]);
    GY(5);
    if (CH < 2 && s == 1 && chained) store_staged(prev, stg);
    if (CH < 2 && s == 10) {
      if (chained) {
        if (elect()) bulk_wait();
        __syncwarp();
      } else {
        mbar_wait(free_bar, 0);
      }
    }
  }
  stsm4(stg + lane * 128 + ((7 ^ (lane & 7)) << 4), pk[7][0], pk[7][1], pk[7][2], pk[7][3]);
}

__device__ __forceinline__ void scale_stats(float2 (&st)[4]) {
#pragma unroll
  for (int c = 0; c < 4; c++) {
    st[c].x *= kGeluBeta;
    st[c].y *= st[c].x;
  }
}

__device__ __forceinline__ void add_mean_term(float (&acc)[2][96], const float2 (&st)[4], uint8_t* sm, int tq,
                                              int lane) {
  const float2* cs = reinterpret_cast<const float2*>(sm + kSmCsQ) + tq * 96 + (lane & 3);
  float2 vn = cs[0];
#pragma unroll
  for (int J = 0; J < 24; J++) {
    const float2 v = vn;
    if (J < 23) vn = cs[J * 4 + 4];
#pragma unroll
    for (int c = 0; c < 4; c++) {
      acc[c & 1][4 * J + (c & 2)] = fmaf(st[c].y, v.x, acc[c & 1][4 * J + (c & 2)]);
      acc[c & 1][4 * J + (c & 2) + 1] = fmaf(st[c].y, v.y, acc[c & 1][4 * J + (c & 2) + 1]);
    }
    yield_slot();
  }
}

#define HALO_AT 2
__device__ __forceinline__ void epilogue_attn(const float (&acc)[2][96], const float2 (&st)[4], uint8_t* sm,
                                              uint32_t sb, int layer, int tq, int b, int j, unsigned epoch, int tile,
                                              int wg, int w) {
  const int lane = threadIdx.x & 31, t = lane & 3, g = lane >> 2;
  const int hp = j + 8 * tq, att = 2 * layer + tq;
  uint32_t q[4][8], k[5][8], vt[5][8];
#define SCALED(c, J) pack2(acc[(c) & 1][4 * (J) + ((c) & 2)] * st[c].x, acc[(c) & 1][4 * (J) + ((c) & 2) + 1] * st[c].x)
#pragma unroll
  for (int J = 0; J < 8; J++) vt[4][J] = transpose8(SCALED(3, 16 + J));
#pragma unroll
  for (int J = 0; J < 8; J++) k[4][J] = SCALED(3, 8 + J);
  if (w < 3) {
    uint4* hs = reinterpret_cast<uint4*>(sm + kSmHalo + w * 2048) + lane;
    hs[0] = make_uint4(k[4][0], k[4][1], k[4][2], k[4][3]);
    hs[32] = make_uint4(k[4][4], k[4][5], k[4][6], k[4][7]);
    hs[64] = make_uint4(vt[4][0], vt[4][1], vt[4][2], vt[4][3]);
    hs[96] = make_uint4(vt[4][4], vt[4][5], vt[4][6], vt[4][7]);
  } else if ((b & 7) != 7) {
    uint4* gh = g_halo + ((layer * 16 + b) * 16 + hp) * 256 + lane;
#pragma unroll
    for (int i = 0; i < 8; i++)
      asm volatile("{\n.reg .b64 x, y;\nmov.b64 x, {%1, %3};\nmov.b64 y, {%2, %3};\n"
                   "st.relaxed.gpu.global.v2.b64 [%0], {x, y};\n}" ::"l"(gh + i * 32),
                   "r"(k[4][i]), "r"(vt[4][i]), "r"(epoch) : "memory");
  }
#pragma unroll
  for (int c = 0; c < 3; c++)
#pragma unroll
    for (int J = 0; J < 8; J++) {
      k[c + 1][J] = SCALED(c, 8 + J);
      vt[c + 1][J] = transpose8(SCALED(c, 16 + J));
      yield_slot();
    }
  const bool first = w == 0 && (b & 7) == 0;
  const uint4* gh = g_halo + ((layer * 16 + b - 1) * 16 + hp) * 256 + lane;
  uint32_t tag[16];
#define LOAD_HALO(i)                                                                         \
  asm volatile("{\n.reg .b64 x, y;\nld.relaxed.gpu.global.v2.b64 {x, y}, [%4];\n"            \
               "mov.b64 {%0, %1}, x;\nmov.b64 {%2, %3}, y;\n}"                               \
               : "=r"(k[0][i]), "=r"(tag[2 * i]), "=r"(vt[0][i]), "=r"(tag[2 * i + 1])        \
               : "l"(gh + i * 32) : "memory")
#pragma unroll
  for (int c = 0; c <= 4; c++) {
    if (c == HALO_AT) {
      if (w == 0 && !first) {
#pragma unroll
        for (int i = 0; i < 8; i++) LOAD_HALO(i);
      } else {
#pragma unroll
        for (int i = 0; i < 8; i++) k[0][i] = vt[0][i] = tag[2 * i] = tag[2 * i + 1] = 0u;
      }
    }
#pragma unroll
    for (int J = 0; J < 8 && c < 4; J++) {
      q[c & 3][J] = SCALED(c & 3, J);
      if (J & 1) yield_slot();
    }
  }
#undef SCALED
  TRACE_AT(tile, 8);
  wg_bar(wg);
  if (w > 0) {
    const uint4* hs = reinterpret_cast<const uint4*>(sm + kSmHalo + (w - 1) * 2048) + lane;
    const uint4 a0 = hs[0], a1 = hs[32], a2 = hs[64], a3 = hs[96];
    k[0][0] = a0.x; k[0][1] = a0.y; k[0][2] = a0.z; k[0][3] = a0.w;
    k[0][4] = a1.x; k[0][5] = a1.y; k[0][6] = a1.z; k[0][7] = a1.w;
    vt[0][0] = a2.x; vt[0][1] = a2.y; vt[0][2] = a2.z; vt[0][3] = a2.w;
    vt[0][4] = a3.x; vt[0][5] = a3.y; vt[0][6] = a3.z; vt[0][7] = a3.w;
  } else if (!first) {
    unsigned spins = 0;
    while (true) {
      unsigned d0 = 0, d1 = 0, d2 = 0, d3 = 0;
#pragma unroll
      for (int i = 0; i < 4; i++) {
        d0 |= tag[i] ^ epoch;
        d1 |= tag[4 + i] ^ epoch;
        d2 |= tag[8 + i] ^ epoch;
        d3 |= tag[12 + i] ^ epoch;
      }
      if (__all_sync(0xffffffffu, (d0 | d1 | d2 | d3) == 0)) break;
      if (++spins > kSpinLimit) __trap();
#pragma unroll
      for (int i = 0; i < 8; i++) LOAD_HALO(i);
    }
  }
#undef LOAD_HALO
  TRACE_AT(tile, 9);
  mbar_wait(sb + kBarPause + att * 8, 0);
  TRACE_AT(tile, 10);

  float s[2][5][4];
#pragma unroll
  for (int hd = 0; hd < 2; hd++)
#pragma unroll
    for (int kg = 0; kg < 5; kg++) {
      const int ca = kg > 0 ? kg - 1 : 0, cb = kg < 4 ? kg : 3;
#pragma unroll
      for (int e = 0; e < 4; e++) s[hd][kg][e] = 0.f;
#pragma unroll
      for (int ks = 0; ks < 2; ks++) {
        const int J = 4 * hd + 2 * ks;
        mma16816(s[hd][kg], q[ca][J], q[cb][J], q[ca][J + 1], q[cb][J + 1], k[kg][J], k[kg][J + 1]);
      }
    }
  constexpr float kScale = 0.17677669529663687f * 1.4426950408889634f;
  const bool own0 = 2 * t <= g, own1 = 2 * t + 1 <= g;
  const uint32_t own_mask = (own0 ? 0xffffu : 0u) | (own1 ? 0xffff0000u : 0u);
  float o[2][4][2][4];
#pragma unroll
  for (int hd = 0; hd < 2; hd++) {
    float v0[4], v1[4], m[4];
#pragma unroll
    for (int c = 0; c < 4; c++) {
      float p0 = s[hd][c][2], p1 = s[hd][c][3];
      if (c == 0 && first) p0 = p1 = -INFINITY;
      v0[c] = own0 ? s[hd][c + 1][0] : p0;
      v1[c] = own1 ? s[hd][c + 1][1] : p1;
      m[c] = fmaxf(v0[c], v1[c]);
    }
#pragma unroll
    for (int c = 0; c < 4; c++) m[c] = fmaxf(m[c], shfl_xor(m[c], 1));
#pragma unroll
    for (int c = 0; c < 4; c++) m[c] = fmaxf(m[c], shfl_xor(m[c], 2));
#pragma unroll
    for (int c = 0; c < 4; c++) {
      const float nm = -m[c] * kScale;
      v0[c] = ex2(fmaf(v0[c], kScale, nm));
      v1[c] = ex2(fmaf(v1[c], kScale, nm));
      m[c] = v0[c] + v1[c];
    }
#pragma unroll
    for (int c = 0; c < 4; c++) m[c] += shfl_xor(m[c], 1);
#pragma unroll
    for (int c = 0; c < 4; c++) m[c] += shfl_xor(m[c], 2);
#pragma unroll
    for (int c = 0; c < 4; c++) {
      const float inv = rcp(m[c]);
      const uint32_t p = pack2(v0[c] * inv, v1[c] * inv);
#pragma unroll
      for (int ds = 0; ds < 2; ds++) {
        const int J = 4 * hd + 2 * ds;
#pragma unroll
        for (int e = 0; e < 4; e++) o[hd][c][ds][e] = 0.f;
        mma16816(o[hd][c][ds], vt[c][J], vt[c][J + 1], vt[c + 1][J], vt[c + 1][J + 1], p & ~own_mask, p & own_mask);
      }
    }
  }
  TRACE_AT(tile, 11);
  const uint32_t stg = sb + kSmStg + w * 4096;
#pragma unroll
  for (int J = 0; J < 8; J++) {
    const int hd = J >> 2, ds = (J >> 1) & 1, e = 2 * (J & 1);
    stsm4_t(stg + lane * 128 + ((J ^ (lane & 7)) << 4), pack2(o[hd][0][ds][e], o[hd][0][ds][e + 1]),
            pack2(o[hd][1][ds][e], o[hd][1][ds][e + 1]), pack2(o[hd][2][ds][e], o[hd][2][ds][e + 1]),
            pack2(o[hd][3][ds][e], o[hd][3][ds][e + 1]));
  }
  if (elect()) mbar_arrive(sb + kBarResume + att * 8);
  fence_async_smem();
  __syncwarp();
  TRACE_AT(tile, 12);
  if (elect()) {
    bulk_store(g_o + (b * 16 + hp) * kTileBytes + w * 4096, stg, 4096);
    bulk_commit();
    bulk_wait();
    TRACE_AT(tile, 13);
    mbar_arrive(sb + kBarEpi + tile * 8);
  }
  __syncwarp();
}

__device__ __forceinline__ void gather_stats(uint8_t* sm, const uint2* stat, unsigned epoch) {
  const int r = threadIdx.x & 127;
  uint2 a[8];
  unsigned spins = 0;
  while (true) {
    unsigned diff = 0;
#pragma unroll
    for (int i = 0; i < 8; i++) {
      a[i] = ld_relaxed2(stat + i * 128 + r);
      diff |= (a[i].x ^ epoch) | (a[i].y ^ epoch);
    }
    if (__all_sync(0xffffffffu, (diff & 7u) == 0)) break;
    if (++spins > kSpinLimit) __trap();
    __nanosleep(200);
  }
  float s = 0.f, q = 0.f;
#pragma unroll
  for (int i = 0; i < 8; i++) {
    s += untag_value(a[i].x);
    q += untag_value(a[i].y);
  }
  const float mean = s * (1.f / 1024.f);
  const float var = fmaxf(fmaf(-mean, mean, q * (1.f / 1024.f)), 0.f);
  reinterpret_cast<float2*>(sm + kSmStat)[r] = make_float2(rsqrtf(var + 1e-5f), -mean);
}

__device__ __forceinline__ void gather_colsums(uint8_t* sm, int part, int j, int lane, unsigned epoch) {
#pragma unroll 1
  for (int blk = part < 4 ? 0 : 2 * part - 5; blk < (part < 4 ? 3 : 2 * part - 3); blk++) {
    const int col = part < 2 ? blk * kD + (j + 8 * part) * 64
                             : 3 * kD + 64 * (blk + (blk < 3 ? 3 * j : blk < 5 ? 21 + 2 * j : 35 + 2 * j));
    uint2 v;
    unsigned spins = 0;
    while (true) {
      v = ld_relaxed2(reinterpret_cast<const uint2*>(g_cs + col) + lane);
      if (__all_sync(0xffffffffu, (((v.x ^ epoch) | (v.y ^ epoch)) & 7u) == 0)) break;
      if (++spins > kSpinLimit) __trap();
      __nanosleep(100);
    }
    uint8_t* dst = part < 2 ? sm + kSmCsQ + (part * 96 + blk * 32 + lane) * 8 : sm + kSmV1 + (blk * 32 + lane) * 16;
    *reinterpret_cast<float2*>(dst) = make_float2(untag_value(v.x), untag_value(v.y));
  }
}

#define READBACK 0
#define DRY_X 0
#define EARLY_EPI 1
#define PF_START 0
#define PAUSE_QKV2 7
#define PAUSE_WO 1

__global__ void __cluster_dims__(2, 1, 1) __launch_bounds__(384, 1)
fused_layers_kernel(const __grid_constant__ CUtensorMap map_x, const __grid_constant__ CUtensorMap map_out,
                    const __grid_constant__ CUtensorMap map_qkv, const __grid_constant__ CUtensorMap map_wo,
                    const __grid_constant__ CUtensorMap map_w1a, const __grid_constant__ CUtensorMap map_w1b,
                    const __grid_constant__ CUtensorMap map_w2, const __grid_constant__ CUtensorMap map_csq,
                    const __grid_constant__ CUtensorMap map_cs1, const __grid_constant__ Params prm) {
  extern __shared__ __align__(1024) uint8_t sm[];
  if (threadIdx.x < 128 && blockIdx.x < kCtas) TRACE_AT(15, 1);
  const uint32_t sb = __shfl_sync(0xffffffffu, smem_u32(sm), 0);
  const int warp = __shfl_sync(0xffffffffu, threadIdx.x >> 5, 0), lane = threadIdx.x & 31;
  const int cta = blockIdx.x, rank = cta & 1, cl = cta >> 1;
  const int grp = cl < 4 ? 0 : cl < 36 ? (cl - 4) & 7 : 1 + (cl - 36) % 7;
  const int j = cl < 4 ? 4 + cl : cl < 36 ? (cl - 4) >> 3 : 4 + (cl - 36) / 7;
  const int b = 2 * grp + rank;
  const int xcol = (b >> 3) * kD, xrow = (b & 7) * 128;

  if (cta >= kCtas) {
    helper_cta(&map_csq, &map_cs1, sm, sb, cta - kCtas, warp);
    return;
  }
  if (warp >= 8 && elect()) {
    if (warp == 9) {
#pragma unroll
      for (int s = 0; s < 8; s++) mbar_init(sb + kBarFull + s * 8, 1);
      fence_async_smem();
#pragma unroll
      for (int s = 0; s < 4; s++) {
        const uint32_t full = sb + kBarFull + s * 8, dst = sb + kSmRing + s * 40960;
        mbar_expect_tx(full, 40960);
        tma2d(dst, &map_x, full, xcol + s * 64, xrow);
        tma3d(dst + kTileBytes, &map_qkv, full, j * 64, s * 64, 0);
        tma3d(dst + kTileBytes + 12288, &map_qkv, full, j * 64, s * 64 + 32, 0);
      }
      if (PF_START & 1) l2_prefetch(reinterpret_cast<const uint8_t*>(prm.x) + cta * 32768, 32768);
      if (PF_START & 2) l2_prefetch(reinterpret_cast<const uint8_t*>(prm.wqkv) + cta * 49152, 49152);
    } else if (warp == 8) {
      if (sb & 1023) __trap();
#pragma unroll
      for (int o = kBarTurn; o < kBarInit; o += 8) mbar_init(sb + o, 1);
    } else if (warp == 10) {
#pragma unroll
      for (int o = kBarEpoch; o < kSmEpoch; o += 8) mbar_init(sb + o, o < kBarEmpty ? 1 : o < kBarEpi ? 2 : 4);
    } else {
      mbar_init(sb + kBarInit, 1);
      fence_async_smem();
      mbar_expect_tx(sb + kBarInit, 32768);
      tma2d(sb + kSmX, &map_x, sb + kBarInit, xcol + j * 128, xrow);
      tma2d(sb + kSmX + kTileBytes, &map_x, sb + kBarInit, xcol + j * 128 + 64, xrow);
    }
    asm volatile("fence.mbarrier_init.release.cluster;" ::: "memory");
  }
  __syncwarp();
  asm volatile("barrier.cluster.arrive.relaxed.aligned;" ::: "memory");

  if (warp >= 8) {
    asm volatile("setmaxnreg.dec.sync.aligned.u32 40;");
    if (warp < 10) {
      asm volatile("barrier.cluster.wait.aligned;" ::: "memory");
      uint32_t nb = 32, off = 0, kb = 0;
#define RING_STEP(ISSUE)                                                  \
  do {                                                                    \
    const uint32_t mb = nb - depth, full = sb + kBarFull + (nb & 56);     \
    if (kb == skip) kb += 2;                                              \
    mbar_wait(sb + kBarEmpty + (mb & 56), mb >> 6);                       \
    if (elect()) { ISSUE; }                                               \
    TRACE_ISSUE(9 - warp, nb);                                            \
    kb += inc;                                                            \
    off = off == wrap ? 0 : off + step;                                   \
    nb += 8;                                                              \
  } while (nb != nend)
#pragma unroll 1
      for (int sg = 0; sg < kSegs; sg++) {
        const uint32_t e = prm.seg[sg];
        const int ty = e & 7, mode = (e >> 15) & 3, reset = (e >> 24) & 3;
        const uint32_t nend = nb + (e & 0x1f8);
        const uint32_t step = (e >> 17) & 1 ? 40960 : 32768, wrap = 163840 - step;
        const uint32_t depth = (e >> 18) & 1 ? 40 : 32;
        if (reset) off = reset == 1 ? 0 : reset == 2 ? 40960 : 131072;
        if (mode != kModeContinue) kb = ((e >> 9) & 63) + (mode == kModeHead ? 2 * j : 0);
        const uint32_t inc = mode >= kModeSkip ? 2 : 1, skip = mode >= kModeSkip ? 2 * j + (kb & 1) : 255;
        if (warp == 8) {
          const CUtensorMap* map = ty < 2 ? &map_qkv : ty == 2 ? &map_wo : ty == 3 ? &map_w1a : ty < 6 ? &map_w1b : &map_w2;
          const int c0 = ty < 2 ? (j + 8 * ty) * 64 : 0;
          const int c2 = ty < 2 ? 0 : ty == 3 ? 3 * j : ty == 4 ? 24 + 2 * j : ty == 5 ? 40 + 2 * j : 2 * j;
          const uint32_t half = (ty < 2 || ty == 3) ? 12288 : 8192;
          const uint32_t bytes = 2 * half + (mode == kModeHead ? 0 : kTileBytes);
          const uint32_t dst = sb + kSmRing + kTileBytes + rank * half;
#pragma unroll 1
          RING_STEP(mbar_expect_tx(full, bytes); tma3d_mc(dst + off, map, full, c0, kb * 64 + rank * 32, c2));
        } else if (mode == kModeHead) {
          nb = nend;
          off += 2 * step;
          if (off >= 163840) off -= 163840;
        } else if (sg < 2) {
#pragma unroll 1
          RING_STEP(tma2d(sb + kSmRing + off, &map_x, full, xcol + kb * 64, xrow));
        } else {
          const uint8_t* src = ty == 6 ? g_h + b * 56 * kTileBytes : (ty == 2 ? g_o : g_x) + b * 16 * kTileBytes;
          const int dep = (e >> 19) & 31;
          if (dep != 31) mbar_wait(sb + kBarReady + dep * 8, 0);
#pragma unroll 1
          RING_STEP(bulk_load(sb + kSmRing + off, src + kb * kTileBytes, kTileBytes, full));
        }
      }
#undef RING_STEP
    } else if (warp == 10) {
      unsigned epoch = 0;
      if (lane == 0) epoch = atomicAdd(&g_ticket, 1u) / kGrid + 1;
      epoch = __shfl_sync(0xffffffffu, epoch, 0);
      *reinterpret_cast<unsigned*>(sm + kSmEpoch) = epoch;
      asm volatile("barrier.cluster.wait.aligned;" ::: "memory");
      if (elect()) mbar_arrive(sb + kBarEpoch);
#pragma unroll 1
      for (int i = 0; i < kTiles - 1; i++) {
        const bool xt = i == 2 || i == 6 || i == 9;
        const unsigned* line = g_flag + (i * 16 + b) * 32;
        mbar_wait(sb + kBarEpi + i * 8, 0);
        wait_flags(line + (lane & 7), epoch);
        if (elect()) mbar_arrive(sb + kBarReady + i * 8);
        if (xt) {
          wait_flags(line + 8 + (lane & 7), epoch);
          if (elect()) mbar_arrive(sb + kBarReady + (14 + (i >> 2)) * 8);
        }
      }
    } else {
      {
        uint32_t v[7];
#pragma unroll
        for (int q = 0; q < 7; q++)
          v[q] = reinterpret_cast<const uint32_t*>(prm.b1)[32 * (q + (q < 3 ? 3 * j : q < 5 ? 21 + 2 * j : 35 + 2 * j)) + lane];
        const uint2 u = reinterpret_cast<const uint2*>(prm.b2)[32 * j + lane];
#pragma unroll
        for (int q = 0; q < 7; q++)
          *reinterpret_cast<float2*>(sm + kSmV1 + (q * 32 + lane) * 16 + 8) = make_float2(kGeluBeta * bf_lo(v[q]), kGeluBeta * bf_hi(v[q]));
        reinterpret_cast<float4*>(sm + kSmB2)[lane] = make_float4(
            2.f * kGeluBeta * bf_lo(u.x), 2.f * kGeluBeta * bf_hi(u.x), 2.f * kGeluBeta * bf_lo(u.y), 2.f * kGeluBeta * bf_hi(u.y));
      }
      asm volatile("barrier.cluster.wait.aligned;" ::: "memory");
      mbar_wait(sb + kBarEpoch, 0);
      const unsigned epoch = *reinterpret_cast<volatile unsigned*>(sm + kSmEpoch);
#pragma unroll 1
      for (int i = 0; i < kTiles - 1; i++) {
#pragma unroll 1
        for (int part = i == 4 ? 5 : i; part < (i < 2 ? i + 1 : i == 3 || i == 4 ? i + 2 : 0); part++) {
          gather_colsums(sm, part, j, lane, epoch);
          __syncwarp();
          if (elect()) mbar_arrive(sb + kBarCs + part * 8);
        }
        const bool xt = i == 2 || i == 6 || i == 9;
#pragma unroll 1
        for (int h = 0; h < (xt ? 2 : 1); h++) {
          mbar_wait(sb + (h == 0 ? kBarEpi + i * 8 : kBarX + (i >> 2) * 16 + 8), 0);
          const int ty = i >= 7 ? i - 7 : i;
          if ((h == 1 || (ty >= 3 && !xt)) && elect()) {
            uint8_t* dst = xt ? g_x + (b * 16 + 2 * j + 1) * kTileBytes
                              : g_h + (b * 56 + 1 + (ty == 3 ? 3 * j : 16 * ty - 40 + 2 * j)) * kTileBytes;
            bulk_store(dst, sb + (xt ? kSmX + kTileBytes : kSmStg), kTileBytes);
            bulk_commit();
            bulk_wait();
            mbar_arrive(sb + kBarFree + i * 8);
          }
          __syncwarp();
          if (elect()) st_release(&g_flag[(i * 16 + b) * 32 + h * 8 + j], epoch);
          __syncwarp();
        }
      }
    }
    __syncwarp();
    asm volatile("barrier.cluster.arrive.relaxed.aligned;\nbarrier.cluster.wait.aligned;" ::: "memory");
  } else {
    asm volatile("setmaxnreg.inc.sync.aligned.u32 232;");
    asm volatile("barrier.cluster.wait.aligned;" ::: "memory");
    const int wg = warp >> 2, w = warp & 3;
    const bool rel = (threadIdx.x & 95) == 0;
    const uint32_t rel_addr = mapa(sb + kBarEmpty, w & 1);
    if (wg == 1) TRACE_AT(15, 0);
#define EPOCH (*reinterpret_cast<volatile unsigned*>(sm + kSmEpoch))

    if (wg == 1) {
      mbar_wait(sb + kBarEpoch, 0);
      mbar_wait(sb + kBarInit, 0);
    }

#pragma unroll 1
    for (int i = wg; i < kTiles; i += 2) {
      const int layer = i >= 7, ty = i - 7 * layer;
      TRACE_AT(i, 15);
      float acc[2][96];
      if (ty == 2 || ty == 6) {
        const uint32_t xrow_addr = sb + kSmX + (32 * w + lane) * 128;
        const float2* b2 = reinterpret_cast<const float2*>(sm + kSmB2) + (lane & 3);
        const float up = ty == 6 ? 2.f * kGeluBeta : 1.f;
#pragma unroll
        for (int J = 0; J < 16; J++) {
          uint32_t r[4];
          ldsm4(xrow_addr + (J >> 3) * kTileBytes + (((J & 7) ^ (lane & 7)) << 4), r);
          float2 bias = make_float2(0.f, 0.f);
          if (ty == 6) bias = b2[J * 4];
#pragma unroll
          for (int c = 0; c < 4; c++) {
            acc[c & 1][4 * J + (c & 2)] = fmaf(bf_lo(r[c]), up, bias.x);
            acc[c & 1][4 * J + (c & 2) + 1] = fmaf(bf_hi(r[c]), up, bias.y);
            asm volatile("" : "+f"(acc[c & 1][4 * J + (c & 2)]), "+f"(acc[c & 1][4 * J + (c & 2) + 1]));
            if (c & 1) yield_slot();
          }
        }
        mainloop<128>(acc, sb, i, layer * 152 + ty * 16, ty == 6 ? 4 : 0, ty == 6 ? 56 : 16, ty == 2 ? PAUSE_WO : -1,
                      2 * layer + 1, rel_addr, rel, 64, [] {});
        TRACE_AT(i, 2);
      } else {
        const int xver = 2 * layer + (ty >= 3);
        const uint32_t stg = sb + kSmStg + w * 4096;
        const float4* vec = reinterpret_cast<const float4*>(sm + kSmV1) + (ty == 3 ? 0 : 64 * ty - 160) + (lane & 3);
        uint8_t* hdst = g_h + (b * 56 + (ty == 3 ? 3 * j : 16 * ty - 40 + 2 * j)) * kTileBytes + w * 4096;
        float2 st[4];
        unsigned epoch;
        auto pre = [&] {
          if (ty < 4) mbar_wait(sb + (ty == 1 ? kBarEpi + (i - 1) * 8 : kBarStat + xver * 8), 0);
#pragma unroll
          for (int c = 0; c < 4; c++) st[c] = reinterpret_cast<const float2*>(sm + kSmStat)[32 * w + 8 * c + (lane >> 2)];
          epoch = EPOCH;
        };
        if (ty == 5) {
          const uint32_t nb = (layer * 152 + 80) * 8, s0 = ((((sb & 0x3FFFF) + kSmRing) >> 4) | (1u << 16)) + 3 * 2048;
          mbar_wait(sb + kBarTurn + (i - 1) * 8, 0);
          mbar_wait(sb + kBarFull, nb >> 6);
          TRACE_KB(nb);
          mma_kblock<128, 2>(acc, s0, s0 + kToB);
        } else {
          if (i < 2) {
            zero_acc<192>(acc);
          } else {
            const int n0 = layer * 152 + (ty < 2 ? 2 * ty : 42 + 2 * ty), slot = ty < 2 ? 2 * ty : 2 * ty - 5;
            if (ty < 4) {
              head_blocks<192>(acc, sb, n0, slot, sb + kBarX + (xver - 1) * 16,
                               sb + kBarEpi + (xver == 1 ? 2 : 3 * xver) * 8, rel_addr, rel);
            } else {
              head_blocks<128>(acc, sb, n0, slot, sb + kBarX + (xver - 1) * 16,
                               sb + kBarEpi + (xver == 1 ? 2 : 3 * xver) * 8, rel_addr, rel);
#pragma unroll
              for (int q = 64; q < 96; q++) acc[0][q] = acc[1][q] = 0.f;
            }
          }
          if (ty == 1 || ty == 4) {
            uint2* stat = g_stat + (xver * 16 + b) * 1024;
            publish_stats(sb, stat + j * 128, w, lane, EPOCH);
            gather_stats(sm, stat, EPOCH);
            __syncwarp();
            if (elect()) mbar_arrive(sb + kBarStat + xver * 8);
            TRACE_AT(i, 14);
            if (i == 8) {
#pragma unroll
              for (int c = 0; c < 4; c++) st[c] = reinterpret_cast<const float2*>(sm + kSmStat)[32 * w + 8 * c + (lane >> 2)];
              add_mean_term(acc, st, sm, 1, lane);
            }
          }
          if (ty < 4) {
            mainloop<192>(acc, sb, i, i < 2 ? 16 * i : layer * 152 + (ty < 2 ? 4 + 14 * ty : 52), i == 8 ? 2 : ty == 3,
                          i < 2 ? 16 : 14, ty == 1 ? PAUSE_QKV2 : -1, xver, rel_addr, rel, 64, pre);
            TRACE_AT(i, 2);
            if (layer == 0) mbar_wait(sb + kBarCs + ty * 8, 0);
            if (ty < 2) {
              if (i != 8) add_mean_term(acc, st, sm, ty, lane);
              epilogue_attn(acc, st, sm, sb, layer, ty, b, j, epoch, i, wg, w);
              goto tile_done;
            }
            scale_stats(st);
            gelu_chunk<2>(acc, st, vec, stg, lane, false, nullptr, 0);
            goto common_chunks;
          }
        }
        mainloop<128>(acc, sb, i, layer * 152 + 6 + 15 * ty, 4, ty + 10, -1, 0, rel_addr, rel, ty == 5 ? 0 : 64, pre);
        TRACE_AT(i, 2);
        if (layer == 0) mbar_wait(sb + kBarCs + ty * 8, 0);
        scale_stats(st);
      common_chunks:
        TRACE_AT(i, 8);
        gelu_chunk<0>(acc, st, vec, stg, lane, ty == 3, hdst + 2 * kTileBytes, sb + kBarFree + (i - 1) * 8);
        TRACE_AT(i, 9);
        gelu_chunk<1>(acc, st, vec, stg, lane, true, hdst, 0);
        TRACE_AT(i, 10);
        fence_async_smem();
        __syncwarp();
        if (elect()) mbar_arrive(sb + kBarEpi + i * 8);
      tile_done:
        TRACE_AT(i, 3);
        if (!DRY_X || (ty != 1 && ty != 5)) continue;
        zero_acc<128>(acc);
        fence_acc<128>(acc);
      }
      const bool live = ty == 2 || ty == 6;
#pragma unroll
      for (int h = 0; h < 2; h++) {
        if (ty >= 5) {
#pragma unroll
          for (int q = 32 * h; q < 32 * h + 32; q++) {
            acc[0][q] *= 0.5f / kGeluBeta;
            acc[1][q] *= 0.5f / kGeluBeta;
          }
        }
#pragma unroll
        for (int J = 8 * h; J < 8 * h + 8; J++)
          stsm4_if(live, sb + kSmX + (32 * w + lane) * 128 + h * kTileBytes + (((J & 7) ^ (lane & 7)) << 4),
                   pack2(acc[0][4 * J], acc[0][4 * J + 1]), pack2(acc[1][4 * J], acc[1][4 * J + 1]),
                   pack2(acc[0][4 * J + 2], acc[0][4 * J + 3]), pack2(acc[1][4 * J + 2], acc[1][4 * J + 3]));
        fence_async_smem();
        __syncwarp();
        if (live && elect()) {
          const uint32_t src = sb + kSmX + h * kTileBytes + w * 4096;
          if (i == kTiles - 1) {
            tma2d_store(&map_out, src, xcol + j * 128 + h * 64, xrow + 32 * w);
            bulk_commit();
            if (h == 1) bulk_wait_read();
          } else if (h == 0) {
            bulk_store(g_x + (b * 16 + 2 * j) * kTileBytes + w * 4096, src, 4096);
            bulk_commit();
            mbar_arrive(sb + kBarX + (i >> 2) * 16);
            if (EARLY_EPI) {
              bulk_wait();
              mbar_arrive(sb + kBarEpi + i * 8);
            }
          } else {
            mbar_arrive(sb + kBarX + (i >> 2) * 16 + 8);
            if (!EARLY_EPI) {
              bulk_wait();
              mbar_arrive(sb + kBarEpi + i * 8);
            }
          }
        }
        __syncwarp();
        yield_slot();
        if (live) TRACE_AT(i, 8 + h);
      }
      if (live) TRACE_AT(i, 3);
    }
#undef EPOCH
    asm volatile("barrier.cluster.arrive.relaxed.aligned;\nbarrier.cluster.wait.aligned;" ::: "memory");
    if (wg == 1) TRACE_AT(15, 2);
  }
}

void build_segments(uint32_t* seg) {
  int n = 0;
  auto add = [&](int ty, int cnt, int kb0, int mode, int wide, int depth5, int dep, int reset) {
    seg[n++] = ty | cnt << 3 | kb0 << 9 | mode << 15 | wide << 17 | depth5 << 18 | dep << 19 | reset << 24;
  };
  for (int l = 0; l < 2; l++) {
    const int t = 7 * l;
    if (l == 0) {
      add(0, 12, 4, kModePlain, 1, 0, 31, 1);
      add(1, 16, 0, kModePlain, 1, 0, 31, 0);
    } else {
      add(0, 2, 0, kModeHead, 1, 0, 31, 1);
      add(1, 2, 0, kModeHead, 1, 0, 31, 0);
      add(0, 7, 0, kModeSkip, 1, 0, 6, 0);
      add(0, 7, 1, kModeSkip, 1, 0, 15, 0);
      add(1, 7, 0, kModeSkip, 1, 0, 31, 0);
      add(1, 7, 1, kModeSkip, 1, 0, 31, 0);
    }
    add(2, 4, 0, kModePlain, 0, 0, t, 1);
    add(2, 4, 4, kModePlain, 0, 1, 31, 0);
    add(2, 8, 8, kModePlain, 0, 1, t + 1, 0);
    add(3, 2, 0, kModeHead, 1, 0, 31, 2);
    add(4, 2, 0, kModeHead, 1, 0, 31, 0);
    add(3, 7, 0, kModeSkip, 1, 0, t + 2, 0);
    add(3, 7, 1, kModeSkip, 1, 0, 14 + 2 * l, 0);
    add(4, 4, 0, kModeSkip, 0, 0, 31, 3);
    add(4, 3, 0, kModeContinue, 0, 1, 31, 0);
    add(4, 7, 1, kModeSkip, 0, 1, 31, 0);
    add(5, 16, 0, kModePlain, 0, 1, 31, 0);
    add(6, 24, 0, kModePlain, 0, 1, t + 3, 0);
    add(6, 16, 24, kModePlain, 0, 1, t + 4, 0);
    add(6, 16, 40, kModePlain, 0, 1, t + 5, 0);
  }
}

typedef CUresult (*EncodeTiledFn)(CUtensorMap*, CUtensorMapDataType, cuuint32_t, void*, const cuuint64_t*,
                                  const cuuint64_t*, const cuuint32_t*, const cuuint32_t*, CUtensorMapInterleave,
                                  CUtensorMapSwizzle, CUtensorMapL2promotion, CUtensorMapFloatOOBfill);

CUtensorMap make_map(EncodeTiledFn enc, const void* p, int rank, const cuuint64_t* dims, const cuuint64_t* strides,
                     const cuuint32_t* box, CUtensorMapSwizzle swizzle = CU_TENSOR_MAP_SWIZZLE_128B) {
  CUtensorMap m;
  const cuuint32_t es[5] = {1, 1, 1, 1, 1};
  enc(&m, CU_TENSOR_MAP_DATA_TYPE_BFLOAT16, rank, const_cast<void*>(p), dims, strides, box, es,
      CU_TENSOR_MAP_INTERLEAVE_NONE, swizzle, CU_TENSOR_MAP_L2_PROMOTION_L2_128B,
      CU_TENSOR_MAP_FLOAT_OOB_FILL_NONE);
  return m;
}

CUtensorMap weight_map(EncodeTiledFn enc, const void* p, int k, int n, int blocks) {
  const cuuint64_t dims[3] = {64, (cuuint64_t)k, (cuuint64_t)n / 64};
  const cuuint64_t strides[2] = {(cuuint64_t)n * 2, 128};
  const cuuint32_t box[3] = {64, 32, (cuuint32_t)blocks};
  return make_map(enc, p, 3, dims, strides, box);
}

CUtensorMap slab_map(EncodeTiledFn enc, const void* p, int n) {
  const cuuint64_t dims[2] = {(cuuint64_t)n, kD};
  const cuuint64_t strides[1] = {(cuuint64_t)n * 2};
  const cuuint32_t box[2] = {128, 128};
  return make_map(enc, p, 2, dims, strides, box, CU_TENSOR_MAP_SWIZZLE_NONE);
}

CUtensorMap token_map(EncodeTiledFn enc, const void* p, int rows) {
  const cuuint64_t dims[2] = {2 * kD, 1024};
  const cuuint64_t strides[1] = {4 * kD};
  const cuuint32_t box[2] = {64, (cuuint32_t)rows};
  return make_map(enc, p, 2, dims, strides, box);
}

}

extern "C" void kernel_launch(void* const* d_in, const int* in_sizes, int n_in, void* d_out, int out_size) {
  (void)in_sizes; (void)n_in; (void)out_size;
  static EncodeTiledFn enc = nullptr;
  if (!enc) {
    void* fn = nullptr;
    cudaDriverEntryPointQueryResult q;
    cudaGetDriverEntryPoint("cuTensorMapEncodeTiled", &fn, cudaEnableDefault, &q);
    enc = (EncodeTiledFn)fn;
    cudaFuncSetAttribute(fused_layers_kernel, cudaFuncAttributeMaxDynamicSharedMemorySize, kSmBytes);
  }
  Params prm;
  prm.x = (const __nv_bfloat16*)d_in[0];
  prm.wqkv = (const __nv_bfloat16*)d_in[1];
  prm.wo = (const __nv_bfloat16*)d_in[2];
  prm.w1 = (const __nv_bfloat16*)d_in[4];
  prm.b1 = (const __nv_bfloat16*)d_in[5];
  prm.w2 = (const __nv_bfloat16*)d_in[6];
  prm.b2 = (const __nv_bfloat16*)d_in[7];
  build_segments(prm.seg);
  const cuuint64_t qd[3] = {kD, kD, 3}, qs[2] = {3 * kD * 2, kD * 2};
  const cuuint32_t qb[3] = {64, 32, 3};
  const CUtensorMap map_x = token_map(enc, d_in[0], 128);
  const CUtensorMap map_out = token_map(enc, d_out, 32);
  const CUtensorMap map_qkv = make_map(enc, prm.wqkv, 3, qd, qs, qb);
  const CUtensorMap map_wo = weight_map(enc, prm.wo, kD, kD, 2);
  const CUtensorMap map_w1a = weight_map(enc, prm.w1, kD, kF, 3);
  const CUtensorMap map_w1b = weight_map(enc, prm.w1, kD, kF, 2);
  const CUtensorMap map_w2 = weight_map(enc, prm.w2, kF, kD, 2);
  fused_layers_kernel<<<kGrid, 384, kSmBytes>>>(map_x, map_out, map_qkv, map_wo, map_w1a, map_w1b, map_w2,
                                                slab_map(enc, prm.wqkv, 3 * kD), slab_map(enc, prm.w1, kF), prm);
}
```

```cpp
#include <cuda.h>
#include <cuda_bf16.h>
#include <cuda_runtime.h>
#include <stdint.h>

namespace {

constexpr int kD = 1024;
constexpr int kF = 3584;
constexpr int kCtas = 128;
constexpr int kGrid = 132;
constexpr int kTiles = 14;
constexpr int kTileBytes = 16384;

constexpr int kSmRing = 0;
constexpr int kSmX = 163840;
constexpr int kSmStg = kSmX + 32768;
constexpr int kSmHalo = kSmStg + 16384;
constexpr int kSmCsQ = kSmHalo + 6144;
constexpr int kSmV1 = kSmCsQ + 384 * 4;
constexpr int kSmB2 = kSmV1 + 448 * 8;
constexpr int kSmStat = kSmB2 + 128 * 4;
constexpr int kSmBar = kSmStat + 128 * 8;
constexpr int kBarFull = kSmBar;
constexpr int kBarTurn = kBarFull + 8 * 8;
constexpr int kBarReady = kBarTurn + 14 * 8;
constexpr int kBarPause = kBarReady + 17 * 8;
constexpr int kBarFree = kBarPause + 4 * 8;
constexpr int kBarCs = kBarFree + 14 * 8;
constexpr int kBarInit = kBarCs + 6 * 8;
constexpr int kBarEpoch = kBarInit + 8;
constexpr int kBarEmpty = kBarEpoch + 8;
constexpr int kBarEpi = kBarEmpty + 9 * 8;
constexpr int kBarX = kBarEpi + 14 * 8;
constexpr int kBarStat = kBarX + 6 * 8;
constexpr int kBarResume = kBarStat + 4 * 8;
constexpr int kSmEpoch = kBarResume + 4 * 8;
constexpr int kSmBytes = kSmEpoch + 16;
constexpr int kSegs = 38;

constexpr int kFlagLines = kTiles * 16;

constexpr unsigned kSpinLimit = 1u << 22;

__device__ __align__(1024) uint8_t g_x[16 * 16 * kTileBytes];
__device__ __align__(1024) uint8_t g_o[16 * 16 * kTileBytes];
__device__ __align__(1024) uint8_t g_h[16 * 56 * kTileBytes];
__device__ __align__(128) uint2 g_stat[4 * 16 * 128 * 8];
__device__ __align__(128) unsigned g_cs[3 * kD + kF];
__device__ __align__(128) uint4 g_halo[2 * 16 * 16 * 256];
__device__ __align__(128) unsigned g_flag[kFlagLines * 32];
__device__ unsigned g_ticket;

#define TRACE_AT(tile, k)
#define TRACE_PUB(i, k, c)
#define TRACE_ISSUE(which, nb)

struct Params {
  const __nv_bfloat16* x;
  const __nv_bfloat16* wqkv;
  const __nv_bfloat16* wo;
  const __nv_bfloat16* w1;
  const __nv_bfloat16* b1;
  const __nv_bfloat16* w2;
  const __nv_bfloat16* b2;
  uint32_t seg[kSegs];
};

__device__ __forceinline__ uint32_t smem_u32(const void* p) {
  return (uint32_t)__cvta_generic_to_shared(p);
}
__device__ __forceinline__ uint32_t mapa(uint32_t a, uint32_t cta) {
  uint32_t r;
  asm("mapa.shared::cluster.u32 %0, %1, %2;" : "=r"(r) : "r"(a), "r"(cta));
  return r;
}
__device__ __forceinline__ void mbar_init(uint32_t bar, int cnt) {
  asm volatile("mbarrier.init.shared::cta.b64 [%0], %1;" ::"r"(bar), "r"(cnt) : "memory");
}
__device__ __forceinline__ void mbar_expect_tx(uint32_t bar, uint32_t bytes) {
  asm volatile("mbarrier.arrive.expect_tx.shared::cta.b64 _, [%0], %1;" ::"r"(bar), "r"(bytes) : "memory");
}
__device__ __forceinline__ void mbar_arrive(uint32_t bar) {
  asm volatile("mbarrier.arrive.shared::cta.b64 _, [%0];" ::"r"(bar) : "memory");
}
__device__ __forceinline__ void mbar_arrive_cluster(uint32_t cluster_addr) {
  asm volatile("mbarrier.arrive.shared::cluster.b64 _, [%0];" ::"r"(cluster_addr) : "memory");
}
__device__ __forceinline__ void mbar_wait(uint32_t bar, uint32_t parity) {
  asm volatile(
      "{\n.reg .pred p;\n.reg .u32 c;\n"
      "mbarrier.try_wait.parity.shared::cta.b64 p, [%0], %1;\n"
      "@p bra.uni DONE;\n"
      "mov.u32 c, 0;\n"
      "RETRY:\n"
      "mbarrier.try_wait.parity.shared::cta.b64 p, [%0], %1;\n"
      "@p bra.uni DONE;\n"
      "add.u32 c, c, 1;\n"
      "setp.lt.u32 p, c, %2;\n"
      "@p bra.uni RETRY;\n"
      "trap;\n"
      "DONE:\n}" ::"r"(bar), "r"(parity), "n"(1u << 19)
      : "memory");
}
__device__ __forceinline__ void tma3d(uint32_t dst, const CUtensorMap* m, uint32_t bar, int c0, int c1, int c2) {
  asm volatile(
      "cp.async.bulk.tensor.3d.shared::cluster.global.mbarrier::complete_tx::bytes [%0], [%1, {%3, %4, %5}], [%2];"
      ::"r"(dst), "l"(m), "r"(bar), "r"(c0), "r"(c1), "r"(c2) : "memory");
}
__device__ __forceinline__ void tma3d_mc(uint32_t dst, const CUtensorMap* m, uint32_t bar, int c0, int c1, int c2) {
  asm volatile(
      "cp.async.bulk.tensor.3d.shared::cluster.global.mbarrier::complete_tx::bytes.multicast::cluster"
      " [%0], [%1, {%3, %4, %5}], [%2], %6;"
      ::"r"(dst), "l"(m), "r"(bar), "r"(c0), "r"(c1), "r"(c2), "h"((uint16_t)3) : "memory");
}
__device__ __forceinline__ void tma2d(uint32_t dst, const CUtensorMap* m, uint32_t bar, int c0, int c1) {
  asm volatile(
      "cp.async.bulk.tensor.2d.shared::cluster.global.mbarrier::complete_tx::bytes [%0], [%1, {%3, %4}], [%2];"
      ::"r"(dst), "l"(m), "r"(bar), "r"(c0), "r"(c1) : "memory");
}
__device__ __forceinline__ void tma2d_store(const CUtensorMap* m, uint32_t src, int c0, int c1) {
  asm volatile("cp.async.bulk.tensor.2d.global.shared::cta.bulk_group [%0, {%2, %3}], [%1];"
               ::"l"(m), "r"(src), "r"(c0), "r"(c1) : "memory");
}
__device__ __forceinline__ bool elect() {
  uint32_t p;
  asm volatile("{\n.reg .pred p;\nelect.sync _|p, 0xffffffff;\nselp.b32 %0, 1, 0, p;\n}" : "=r"(p));
  return p;
}
__device__ __forceinline__ void bulk_load(uint32_t dst, const void* src, uint32_t bytes, uint32_t bar) {
  asm volatile("cp.async.bulk.shared::cluster.global.mbarrier::complete_tx::bytes [%0], [%1], %2, [%3];"
               ::"r"(dst), "l"(src), "r"(bytes), "r"(bar) : "memory");
}
__device__ __forceinline__ void bulk_store(void* dst, uint32_t src, uint32_t bytes) {
  asm volatile("cp.async.bulk.global.shared::cta.bulk_group [%0], [%1], %2;" ::"l"(dst), "r"(src), "r"(bytes)
               : "memory");
}
__device__ __forceinline__ void bulk_commit() { asm volatile("cp.async.bulk.commit_group;" ::: "memory"); }
__device__ __forceinline__ void bulk_wait_read() { asm volatile("cp.async.bulk.wait_group.read 0;" ::: "memory"); }
__device__ __forceinline__ void bulk_wait() { asm volatile("cp.async.bulk.wait_group 0;" ::: "memory"); }
__device__ __forceinline__ void l2_prefetch(const void* p, uint32_t bytes) {
  asm volatile("cp.async.bulk.prefetch.L2.global [%0], %1;" ::"l"(p), "r"(bytes) : "memory");
}
__device__ __forceinline__ void fence_async_smem() { asm volatile("fence.proxy.async.shared::cta;" ::: "memory"); }
__device__ __forceinline__ unsigned ld_relaxed(const unsigned* p) {
  unsigned v;
  asm volatile("ld.relaxed.gpu.global.u32 %0, [%1];" : "=r"(v) : "l"(p) : "memory");
  return v;
}
__device__ __forceinline__ uint2 ld_relaxed2(const uint2* p) {
  uint2 v;
  asm volatile("ld.relaxed.gpu.global.v2.u32 {%0, %1}, [%2];" : "=r"(v.x), "=r"(v.y) : "l"(p) : "memory");
  return v;
}
__device__ __forceinline__ void st_relaxed(unsigned* p, unsigned v) {
  asm volatile("st.relaxed.gpu.global.u32 [%0], %1;" ::"l"(p), "r"(v) : "memory");
}
__device__ __forceinline__ void st_release(unsigned* p, unsigned v) {
  asm volatile("st.release.gpu.global.u32 [%0], %1;" ::"l"(p), "r"(v) : "memory");
}
#define ACQ_MODE 1
__device__ __forceinline__ void wait_flags(const unsigned* p, unsigned epoch) {
  unsigned spins = 0;
  while (true) {
    const unsigned v = ld_relaxed(p);
    if (__all_sync(0xffffffffu, v == epoch)) break;
    if (++spins > kSpinLimit) __trap();
  }
  if (ACQ_MODE) asm volatile("fence.acquire.gpu;\nfence.proxy.async.global;" ::: "memory");
  __syncwarp();
}
__device__ __forceinline__ void st_packet(uint4* p, uint32_t d0, uint32_t d1, uint32_t tag) {
  asm volatile("{\n.reg .b128 v;\n.reg .b64 x, y;\nmov.b64 x, {%1, %2};\nmov.b64 y, {%3, %3};\nmov.b128 v, {x, y};\n"
               "st.relaxed.gpu.global.b128 [%0], v;\n}" ::"l"(p), "r"(d0), "r"(d1), "r"(tag) : "memory");
}
__device__ __forceinline__ void ld_packet(const uint4* p, uint32_t& d0, uint32_t& d1, uint32_t& tag) {
  asm volatile("{\n.reg .b128 v;\n.reg .b64 x, y;\n.reg .b32 u;\nld.relaxed.gpu.global.b128 v, [%3];\n"
               "mov.b128 {x, y}, v;\nmov.b64 {%0, %1}, x;\nmov.b64 {%2, u}, y;\n}"
               : "=r"(d0), "=r"(d1), "=r"(tag) : "l"(p) : "memory");
}
__device__ __forceinline__ unsigned tag_value(float v, unsigned epoch) {
  return (__float_as_uint(v) & ~7u) | (epoch & 7u);
}
__device__ __forceinline__ float untag_value(unsigned v) { return __uint_as_float(v & ~7u); }
__device__ __forceinline__ void stsm4(uint32_t a, uint32_t r0, uint32_t r1, uint32_t r2, uint32_t r3) {
  asm volatile("stmatrix.sync.aligned.m8n8.x4.shared.b16 [%0], {%1, %2, %3, %4};" ::"r"(a), "r"(r0), "r"(r1),
               "r"(r2), "r"(r3) : "memory");
}
__device__ __forceinline__ void stsm4_if(bool on, uint32_t a, uint32_t r0, uint32_t r1, uint32_t r2, uint32_t r3) {
  asm volatile("{\n.reg .pred p;\nsetp.ne.u32 p, %5, 0;\n"
               "@p stmatrix.sync.aligned.m8n8.x4.shared.b16 [%0], {%1, %2, %3, %4};\n}" ::"r"(a), "r"(r0), "r"(r1),
               "r"(r2), "r"(r3), "r"((uint32_t)on) : "memory");
}
__device__ __forceinline__ void stsm4_t(uint32_t a, uint32_t r0, uint32_t r1, uint32_t r2, uint32_t r3) {
  asm volatile("stmatrix.sync.aligned.m8n8.x4.trans.shared.b16 [%0], {%1, %2, %3, %4};" ::"r"(a), "r"(r0),
               "r"(r1), "r"(r2), "r"(r3) : "memory");
}
__device__ __forceinline__ uint32_t transpose8(uint32_t a) {
  uint32_t d;
  asm volatile("movmatrix.sync.aligned.m8n8.trans.b16 %0, %1;" : "=r"(d) : "r"(a));
  return d;
}
__device__ __forceinline__ void mma16816(float (&c)[4], uint32_t a0, uint32_t a1, uint32_t a2, uint32_t a3,
                                         uint32_t b0, uint32_t b1) {
  asm volatile("mma.sync.aligned.m16n8k16.row.col.f32.bf16.bf16.f32 {%0, %1, %2, %3}, {%4, %5, %6, %7}, {%8, %9}, "
               "{%0, %1, %2, %3};"
               : "+f"(c[0]), "+f"(c[1]), "+f"(c[2]), "+f"(c[3])
               : "r"(a0), "r"(a1), "r"(a2), "r"(a3), "r"(b0), "r"(b1));
}
__device__ __forceinline__ void mma1688(float (&c)[4], uint32_t a0, uint32_t a1, uint32_t b0) {
  asm volatile("mma.sync.aligned.m16n8k8.row.col.f32.bf16.bf16.f32 {%0, %1, %2, %3}, {%4, %5}, {%6}, {%0, %1, %2, %3};"
               : "+f"(c[0]), "+f"(c[1]), "+f"(c[2]), "+f"(c[3]) : "r"(a0), "r"(a1), "r"(b0));
}
__device__ __forceinline__ float shfl_xor(float v, int m) {
  float r;
  asm volatile("shfl.sync.bfly.b32 %0, %1, %2, 31, 0xffffffff;" : "=f"(r) : "f"(v), "r"(m));
  return r;
}
__device__ __forceinline__ float tanh_fast(float x) {
  float r;
  asm volatile("tanh.approx.f32 %0, %1;" : "=f"(r) : "f"(x));
  return r;
}
__device__ __forceinline__ void ldsm4(uint32_t a, uint32_t (&r)[4]) {
  asm volatile("ldmatrix.sync.aligned.m8n8.x4.shared.b16 {%0, %1, %2, %3}, [%4];"
               : "=r"(r[0]), "=r"(r[1]), "=r"(r[2]), "=r"(r[3]) : "r"(a) : "memory");
}
__device__ __forceinline__ uint32_t pack2(float lo, float hi) {
  uint32_t r;
  asm volatile("cvt.rn.bf16x2.f32 %0, %1, %2;" : "=r"(r) : "f"(hi), "f"(lo));
  return r;
}
__device__ __forceinline__ float bf_lo(uint32_t r) { return __uint_as_float(r << 16); }
__device__ __forceinline__ float bf_hi(uint32_t r) { return __uint_as_float(r & 0xffff0000u); }
__device__ __forceinline__ float ex2(float x) {
  float r;
  asm("ex2.approx.ftz.f32 %0, %1;" : "=f"(r) : "f"(x));
  return r;
}
__device__ __forceinline__ float rcp(float x) {
  float r;
  asm("rcp.approx.ftz.f32 %0, %1;" : "=f"(r) : "f"(x));
  return r;
}
template <int N>
__device__ __forceinline__ void wg_wait() {
  asm volatile("wgmma.wait_group.sync.aligned %0;" ::"n"(N) : "memory");
}
__device__ __forceinline__ void yield_slot() { asm volatile("pmevent 0;"); }
__device__ __forceinline__ void wg_bar(int wg) { asm volatile("bar.sync %0, 128;" ::"r"(wg + 1) : "memory"); }

template <int N, int KIND>
__device__ __forceinline__ void mma_kblock(float (&acc)[2][96], uint32_t a, uint32_t b);

#define F8(m, d, i) m(d[i]), m(d[i + 1]), m(d[i + 2]), m(d[i + 3]), m(d[i + 4]), m(d[i + 5]), m(d[i + 6]), m(d[i + 7])
#define KSTEP(N, A, B, oa0, oa1, ob, sd)                                                   \
  "add.u32 t, " B ", " #ob ";\nmov.b64 db, {t, hb};\n"                                      \
  "add.u32 t, " A ", " #oa0 ";\nmov.b64 da, {t, ha};\n"                                     \
  "wgmma.mma_async.sync.aligned.m64n" #N "k16.f32.bf16.bf16 {" ACC##N##_0 "}, da, db, " #sd ", 1, 1, 0, 1;\n" \
  "add.u32 t, " A ", " #oa1 ";\nmov.b64 da, {t, ha};\n"                                     \
  "wgmma.mma_async.sync.aligned.m64n" #N "k16.f32.bf16.bf16 {" ACC##N##_1 "}, da, db, " #sd ", 1, 1, 0, 1;\n"

#define MMA_KBLOCK(N, KIND, A, B, ob2, ob3, sd, MID, MODE)                                 \
  template <>                                                                              \
  __device__ __forceinline__ void mma_kblock<N, KIND>(float (&acc)[2][96], uint32_t a, uint32_t b) { \
    asm volatile("{\n.reg .b32 t, ha, hb;\n.reg .b64 da, db;\n"                            \
                 "mov.b32 ha, 0x40000080;\nmov.b32 hb, 0x40000040;\n"                       \
                 "wgmma.fence.sync.aligned;\n"                                             \
                 KSTEP(N, A, B, 0, 64, 0, sd) KSTEP(N, A, B, 2, 66, 128, 1) KSTEP(N, A, B, 4, 68, ob2, 1) \
                 MID KSTEP(N, A, B, 6, 70, ob3, 1) "wgmma.commit_group.sync.aligned;\n}\n"  \
                 : OPS##N(MODE) : "r"(a), "r"(b) : "memory");                              \
  }
#define MMA_KBLOCKS(N, A, B, ob2, ob3)                                                     \
  MMA_KBLOCK(N, 0, A, B, ob2, ob3, 1, "", "+f")                                            \
  MMA_KBLOCK(N, 1, A, B, ob2, ob3, 1, "wgmma.commit_group.sync.aligned;\n", "+f")          \
  MMA_KBLOCK(N, 2, A, B, ob2, ob3, 0, "", "=f")

#define ACC128_0 \
  "%0, %1, %2, %3, %4, %5, %6, %7, %8, %9, %10, %11, %12, %13, %14, %15, " \
  "%16, %17, %18, %19, %20, %21, %22, %23, %24, %25, %26, %27, %28, %29, %30, %31, " \
  "%32, %33, %34, %35, %36, %37, %38, %39, %40, %41, %42, %43, %44, %45, %46, %47, " \
  "%48, %49, %50, %51, %52, %53, %54, %55, %56, %57, %58, %59, %60, %61, %62, %63"
#define ACC128_1 \
  "%64, %65, %66, %67, %68, %69, %70, %71, %72, %73, %74, %75, %76, %77, %78, %79, " \
  "%80, %81, %82, %83, %84, %85, %86, %87, %88, %89, %90, %91, %92, %93, %94, %95, " \
  "%96, %97, %98, %99, %100, %101, %102, %103, %104, %105, %106, %107, %108, %109, %110, %111, " \
  "%112, %113, %114, %115, %116, %117, %118, %119, %120, %121, %122, %123, %124, %125, %126, %127"
#define OPS128(m) \
  F8(m, acc[0], 0), F8(m, acc[0], 8), F8(m, acc[0], 16), F8(m, acc[0], 24), F8(m, acc[0], 32), F8(m, acc[0], 40), F8(m, acc[0], 48), F8(m, acc[0], 56), \
        F8(m, acc[1], 0), F8(m, acc[1], 8), F8(m, acc[1], 16), F8(m, acc[1], 24), F8(m, acc[1], 32), F8(m, acc[1], 40), F8(m, acc[1], 48), F8(m, acc[1], 56)
MMA_KBLOCKS(128, "%128", "%129", 512, 640)

#define ACC192_0 \
  "%0, %1, %2, %3, %4, %5, %6, %7, %8, %9, %10, %11, %12, %13, %14, %15, " \
  "%16, %17, %18, %19, %20, %21, %22, %23, %24, %25, %26, %27, %28, %29, %30, %31, " \
  "%32, %33, %34, %35, %36, %37, %38, %39, %40, %41, %42, %43, %44, %45, %46, %47, " \
  "%48, %49, %50, %51, %52, %53, %54, %55, %56, %57, %58, %59, %60, %61, %62, %63, " \
  "%64, %65, %66, %67, %68, %69, %70, %71, %72, %73, %74, %75, %76, %77, %78, %79, " \
  "%80, %81, %82, %83, %84, %85, %86, %87, %88, %89, %90, %91, %92, %93, %94, %95"
#define ACC192_1 \
  "%96, %97, %98, %99, %100, %101, %102, %103, %104, %105, %106, %107, %108, %109, %110, %111, " \
  "%112, %113, %114, %115, %116, %117, %118, %119, %120, %121, %122, %123, %124, %125, %126, %127, " \
  "%128, %129, %130, %131, %132, %133, %134, %135, %136, %137, %138, %139, %140, %141, %142, %143, " \
  "%144, %145, %146, %147, %148, %149, %150, %151, %152, %153, %154, %155, %156, %157, %158, %159, " \
  "%160, %161, %162, %163, %164, %165, %166, %167, %168, %169, %170, %171, %172, %173, %174, %175, " \
  "%176, %177, %178, %179, %180, %181, %182, %183, %184, %185, %186, %187, %188, %189, %190, %191"
#define OPS192(m) \
  F8(m, acc[0], 0), F8(m, acc[0], 8), F8(m, acc[0], 16), F8(m, acc[0], 24), F8(m, acc[0], 32), F8(m, acc[0], 40), F8(m, acc[0], 48), F8(m, acc[0], 56), F8(m, acc[0], 64), F8(m, acc[0], 72), F8(m, acc[0], 80), F8(m, acc[0], 88), \
        F8(m, acc[1], 0), F8(m, acc[1], 8), F8(m, acc[1], 16), F8(m, acc[1], 24), F8(m, acc[1], 32), F8(m, acc[1], 40), F8(m, acc[1], 48), F8(m, acc[1], 56), F8(m, acc[1], 64), F8(m, acc[1], 72), F8(m, acc[1], 80), F8(m, acc[1], 88)
MMA_KBLOCKS(192, "%192", "%193", 768, 896)

enum { kModePlain = 0, kModeHead = 1, kModeSkip = 2, kModeContinue = 3 };

template <int N>
__device__ __forceinline__ void fence_acc(float (&acc)[2][96]) {
#pragma unroll
  for (int h = 0; h < 2; h++)
#pragma unroll
    for (int i = 0; i < N / 2; i++) asm volatile("" : "+f"(acc[h][i])::"memory");
}

template <int N>
__device__ __forceinline__ void zero_acc(float (&acc)[2][96]) {
#pragma unroll
  for (int h = 0; h < 2; h++)
#pragma unroll
    for (int i = 0; i < N / 2; i++) acc[h][i] = 0.f;
}

constexpr uint32_t kToB = (kTileBytes >> 4) + ((4096u >> 4) << 16) - (1u << 16);

#define TRACE_KB(nb)

#define HEAD_BOTH 1
template <int N>
__device__ __forceinline__ void head_blocks(float (&acc)[2][96], uint32_t sb, int n0, int slot, uint32_t xbar, uint32_t ebar,
                                            uint32_t rel_addr, bool rel) {
  const uint32_t ring = (((sb & 0x3FFFF) + kSmRing) >> 4) | (1u << 16);
  const uint32_t xdesc = (((sb & 0x3FFFF) + kSmX) >> 4) | (1u << 16);
  const uint32_t nb = n0 * 8;
  mbar_wait(HEAD_BOTH == 2 ? ebar : xbar + 8 * HEAD_BOTH, 0);
  mbar_wait(sb + kBarFull + (nb & 56), nb >> 6);
  TRACE_KB(nb);
  mma_kblock<N, 2>(acc, xdesc, ring + slot * 2560 + kToB);
  mbar_wait(xbar + 8, 0);
  mbar_wait(sb + kBarFull + (nb & 56) + 8, nb >> 6);
  TRACE_KB(nb + 8);
  mma_kblock<N, 0>(acc, xdesc + (kTileBytes >> 4), ring + ((slot + 1) & 3) * 2560 + kToB);
  wg_wait<1>();
  if (rel) mbar_arrive_cluster(rel_addr + (nb & 56));
  wg_wait<0>();
  if (rel) mbar_arrive_cluster(rel_addr + (nb & 56) + 8);
  fence_acc<N>(acc);
}

template <int N, bool OWN, class Pre>
__device__ __forceinline__ void mainloop(float (&acc)[2][96], uint32_t sb, int tile, int n0, int slot, int nkb,
                                         int pause_kk, int att, uint32_t rel_addr, bool rel, uint32_t prev, int own_kk,
                                         Pre pre) {
  constexpr uint32_t kStep = (N == 192 ? 5 : 4) * 512;
  const uint32_t ring = (((sb & 0x3FFFF) + kSmRing) >> 4) | (1u << 16);
  uint32_t st = ring + slot * kStep;
  uint32_t nb = n0 * 8;
  const uint32_t last = nb + 8 * (nkb - 1), own = nb + 8 * own_kk;
  const uint32_t stg = (((sb & 0x3FFFF) + kSmStg) >> 4) | (1u << 16);
  uint32_t stop = pause_kk >= 0 ? nb + 8 * pause_kk : last;
  const bool signal = (threadIdx.x & 127) == 64;
  fence_acc<N>(acc);
  if (tile > 0) mbar_wait(sb + kBarTurn + (tile - 1) * 8, 0);
  TRACE_AT(tile, 0);
#pragma unroll 1
  while (true) {
#pragma unroll 1
    do {
      mbar_wait(sb + kBarFull + (nb & 56), nb >> 6);
      if (nb == n0 * 8) TRACE_AT(tile, 1);
      TRACE_KB(nb);
      mma_kblock<N, 0>(acc, OWN && nb == own ? stg : st, st + kToB);
      wg_wait<1>();
      if (rel) mbar_arrive_cluster(rel_addr + prev);
      prev = nb & 56;
      st += kStep;
      if (st == ring + 10240) st = ring;
      nb += 8;
    } while (nb != stop);
    if (stop == last) break;
    stop = last;
    if (signal) mbar_arrive(sb + kBarPause + att * 8);
    wg_wait<0>();
    if (rel) mbar_arrive_cluster(rel_addr + prev);
    prev = 64;
    mbar_wait(sb + kBarResume + att * 8, 0);
  }
  mbar_wait(sb + kBarFull + (nb & 56), nb >> 6);
  TRACE_KB(nb);
  mma_kblock<N, 1>(acc, st, st + kToB);
  wg_wait<2>();
  if (rel) mbar_arrive_cluster(rel_addr + prev);
  pre();
  wg_wait<1>();
  if (signal) mbar_arrive(sb + kBarTurn + tile * 8);
  wg_wait<0>();
  if (rel) mbar_arrive_cluster(rel_addr + (nb & 56));
  fence_acc<N>(acc);
}

__device__ __forceinline__ void publish_stats(uint32_t sb, uint2* stat, int w, int lane, unsigned epoch) {
  const uint32_t row = sb + kSmX + (32 * w + lane) * 128;
  float s[4], q[4];
#pragma unroll
  for (int c = 0; c < 4; c++) s[c] = q[c] = 0.f;
  uint32_t nx[4];
  ldsm4(row + ((lane & 7) << 4), nx);
#pragma unroll 1
  for (int J = 1; J <= 16; J++) {
    const uint32_t r[4] = {nx[0], nx[1], nx[2], nx[3]};
    ldsm4(row + ((J >> 3) & 1) * kTileBytes + (((J ^ lane) & 7) << 4), nx);
#pragma unroll
    for (int c = 0; c < 4; c++) {
      const float lo = bf_lo(r[c]);
      s[c] += lo;
      q[c] = fmaf(lo, lo, q[c]);
      if (c & 1) yield_slot();
    }
#pragma unroll
    for (int c = 0; c < 4; c++) {
      const float hi = bf_hi(r[c]);
      s[c] += hi;
      q[c] = fmaf(hi, hi, q[c]);
      if (c & 1) yield_slot();
    }
  }
#pragma unroll
  for (int c = 0; c < 4; c++) {
    s[c] += shfl_xor(s[c], 1);
    q[c] += shfl_xor(q[c], 1);
    s[c] += shfl_xor(s[c], 2);
    q[c] += shfl_xor(q[c], 2);
  }
  const int t = lane & 3, g = lane >> 2;
  const float so = t == 0 ? s[0] : t == 1 ? s[1] : t == 2 ? s[2] : s[3];
  const float qo = t == 0 ? q[0] : t == 1 ? q[1] : t == 2 ? q[2] : q[3];
  asm volatile("st.relaxed.gpu.global.v2.u32 [%0], {%1, %2};" ::"l"(stat + 32 * w + 8 * t + g),
               "r"(tag_value(so, epoch)), "r"(tag_value(qo, epoch)) : "memory");
}

__device__ __forceinline__ void add_chunk(float (&a)[8], const uint4& v) {
  a[0] += bf_lo(v.x); a[1] += bf_hi(v.x);
  a[2] += bf_lo(v.y); a[3] += bf_hi(v.y);
  a[4] += bf_lo(v.z); a[5] += bf_hi(v.z);
  a[6] += bf_lo(v.w); a[7] += bf_hi(v.w);
}

__device__ __forceinline__ int helper_col(int id, int slab) {
  return slab < 6 ? (slab % 3) * kD + (slab / 3) * 512 + id * 128 : (slab - 6) * 512 + id * 128;
}
__device__ __forceinline__ void helper_cta(const CUtensorMap* map_q, const CUtensorMap* map_1, uint8_t* sm,
                                           uint32_t sb, int id, int warp) {
  constexpr int kRed = 6 * 32768, kBar = kRed + 2 * 4096;
  const int tid = threadIdx.x;
  if (warp == 8 && elect()) {
#pragma unroll
    for (int s = 0; s < 6; s++) {
      mbar_init(sb + kBar + s * 8, 1);
      mbar_init(sb + kBar + 64 + s * 8, 4);
    }
    fence_async_smem();
#pragma unroll
    for (int s = 0; s < 6; s++) {
      mbar_expect_tx(sb + kBar + s * 8, 32768);
      tma2d(sb + s * 32768, map_q, sb + kBar + s * 8, id * 128, s * 128);
    }
  }
  __syncthreads();
  if (warp == 8) {
    int slot = 0, ph = 0;
#pragma unroll 1
    for (int n = 6; n < 104; n++) {
      mbar_wait(sb + kBar + 64 + slot * 8, ph);
      if (elect()) {
        mbar_expect_tx(sb + kBar + slot * 8, 32768);
        tma2d(sb + slot * 32768, n < 48 ? map_q : map_1, sb + kBar + slot * 8, helper_col(id, n >> 3), (n & 7) * 128);
      }
      if (++slot == 6) slot = 0, ph ^= 1;
    }
  } else if (warp < 8) {
    if (tid == 0) *reinterpret_cast<unsigned*>(sm + kBar + 128) = atomicAdd(&g_ticket, 1u) / kGrid + 1;
    int slot = warp >> 2, ph = 0;
#pragma unroll 1
    for (int slab = 0; slab < 13; slab++) {
      float a[8];
#pragma unroll
      for (int e = 0; e < 8; e++) a[e] = 0.f;
#pragma unroll 1
      for (int box = 0; box < 4; box++) {
        mbar_wait(sb + kBar + slot * 8, ph);
        const uint4* p = reinterpret_cast<const uint4*>(sm + slot * 32768) + (tid & 127);
        uint4 v[16];
#pragma unroll
        for (int i = 0; i < 16; i++) v[i] = p[i * 128];
        __syncwarp();
        if (elect()) mbar_arrive(sb + kBar + 64 + slot * 8);
#pragma unroll
        for (int i = 0; i < 16; i++) add_chunk(a, v[i]);
        slot += 2;
        if (slot >= 6) slot -= 6, ph ^= 1;
      }
      float* red = reinterpret_cast<float*>(sm + kRed + (slab & 1) * 4096);
#pragma unroll
      for (int e = 0; e < 8; e++) a[e] += shfl_xor(a[e], 16);
      if ((tid & 16) == 0) {
        float4* d = reinterpret_cast<float4*>(red + warp * 128 + (tid & 15) * 8);
        d[0] = make_float4(a[0], a[1], a[2], a[3]);
        d[1] = make_float4(a[4], a[5], a[6], a[7]);
      }
      asm volatile("bar.sync 1, 256;" ::: "memory");
      if (warp < 4) {
        float t = 0.f;
#pragma unroll
        for (int q = 0; q < 8; q++) t += red[q * 128 + tid];
        st_relaxed(g_cs + (slab < 6 ? 0 : 3 * kD) + helper_col(id, slab) + tid,
                   tag_value(t, *reinterpret_cast<volatile unsigned*>(sm + kBar + 128)));
      }
    }
  }
}

constexpr float kGeluBeta = 0.3292034911525734f;
constexpr float kGeluK = 2.423681954311584f;

__device__ __forceinline__ void store_staged(uint8_t* dst, uint32_t stg) {
  fence_async_smem();
  __syncwarp();
  if (elect()) {
    bulk_store(dst, stg, 4096);
    bulk_commit();
  }
}

#define GY_MASK 0x3F
#define GY_MASK2 0x3f
#define GY(k) if (((CH == 2 ? GY_MASK2 : GY_MASK) >> k) & 1) yield_slot()
template <int CH>
__device__ __forceinline__ void gelu_chunk(const float (&acc)[2][96], const float2 (&st)[4], const float4* vec,
                                           uint32_t stg, int lane, bool chained, uint8_t* prev, uint32_t free_bar) {
  uint32_t pk[8][4];
  float u[3][4], z[3][4];
  float4 v = vec[CH * 32], vn = v;
#pragma unroll
  for (int s = 0; s < 18; s++) {
    const int J = CH * 8 + (s >> 1), c0 = 2 * (s & 1), cur = s % 3, p1 = (s + 2) % 3, p2 = (s + 1) % 3;
    if (s < 16) {
      if (c0 == 0 && s < 14) vn = vec[(J + 1) * 4];
#pragma unroll
      for (int e = 0; e < 4; e++) {
        const int c = c0 + (e >> 1);
        z[cur][e] = fmaf(st[c].y, e & 1 ? v.y : v.x, e & 1 ? v.w : v.z);
      }
      if (c0 == 2) v = vn;
    }
    if (s >= 1 && s < 17) z[p1][0] = tanh_fast(z[p1][0]);
    GY(0);
    if (s < 16) {
#pragma unroll
      for (int e = 0; e < 4; e++) {
        const int c = c0 + (e >> 1);
        u[cur][e] = fmaf(acc[c & 1][4 * J + c0 + (e & 1)], st[c].x, z[cur][e]);
      }
    }
    if (s >= 1 && s < 17) z[p1][1] = tanh_fast(z[p1][1]);
    GY(1);
    if (s >= 11) {
      const int jj = s - 11;
      stsm4(stg + lane * 128 + ((jj ^ (lane & 7)) << 4), pk[jj][0], pk[jj][1], pk[jj][2], pk[jj][3]);
    }
    if (s < 16) {
#pragma unroll
      for (int e = 0; e < 4; e++) z[cur][e] = fmaf(u[cur][e], u[cur][e], kGeluK);
    }
    if (s >= 1 && s < 17) z[p1][2] = tanh_fast(z[p1][2]);
    GY(3);
    if (s >= 2) {
      pk[(s - 2) >> 1][c0] = pack2(fmaf(u[p2][0], z[p2][0], u[p2][0]), fmaf(u[p2][1], z[p2][1], u[p2][1]));
      pk[(s - 2) >> 1][c0 + 1] = pack2(fmaf(u[p2][2], z[p2][2], u[p2][2]), fmaf(u[p2][3], z[p2][3], u[p2][3]));
    }
    GY(4);
    if (s < 16) {
#pragma unroll
      for (int e = 0; e < 4; e++) z[cur][e] = u[cur][e] * z[cur][e];
    }
    if (s >= 1 && s < 17) z[p1][3] = tanh_fast(z[p1][3]);
    GY(5);
    if (CH < 2 && s == 1 && chained) store_staged(prev, stg);
    if (CH < 2 && s == 10) {
      if (chained) {
        if (elect()) bulk_wait();
        __syncwarp();
      } else {
        mbar_wait(free_bar, 0);
      }
    }
  }
  stsm4(stg + lane * 128 + ((7 ^ (lane & 7)) << 4), pk[7][0], pk[7][1], pk[7][2], pk[7][3]);
}

__device__ __forceinline__ void scale_stats(float2 (&st)[4]) {
#pragma unroll
  for (int c = 0; c < 4; c++) {
    st[c].x *= kGeluBeta;
    st[c].y *= st[c].x;
  }
}

__device__ __forceinline__ void add_mean_term(float (&acc)[2][96], const float2 (&st)[4], uint8_t* sm, int tq,
                                              int lane) {
  const float2* cs = reinterpret_cast<const float2*>(sm + kSmCsQ) + tq * 96 + (lane & 3);
  float2 vn = cs[0];
#pragma unroll
  for (int J = 0; J < 24; J++) {
    const float2 v = vn;
    if (J < 23) vn = cs[J * 4 + 4];
#pragma unroll
    for (int c = 0; c < 4; c++) {
      acc[c & 1][4 * J + (c & 2)] = fmaf(st[c].y, v.x, acc[c & 1][4 * J + (c & 2)]);
      acc[c & 1][4 * J + (c & 2) + 1] = fmaf(st[c].y, v.y, acc[c & 1][4 * J + (c & 2) + 1]);
    }
    yield_slot();
  }
}

#define TWO_PART 0
#define RESUME_LATE 0
#define HALO_AT 2
__device__ __forceinline__ void epilogue_attn(const float (&acc)[2][96], const float2 (&st)[4], uint8_t* sm,
                                              uint32_t sb, int layer, int tq, int b, int j, unsigned epoch, int tile,
                                              int wg, int w) {
  const int lane = threadIdx.x & 31, t = lane & 3, g = lane >> 2;
  const int hp = j + 8 * tq, att = 2 * layer + tq;
  uint32_t q[4][8], k[5][8], vt[5][8];
#define SCALED(c, J) pack2(acc[(c) & 1][4 * (J) + ((c) & 2)] * st[c].x, acc[(c) & 1][4 * (J) + ((c) & 2) + 1] * st[c].x)
#pragma unroll
  for (int J = 0; J < 8; J++) vt[4][J] = transpose8(SCALED(3, 16 + J));
#pragma unroll
  for (int J = 0; J < 8; J++) k[4][J] = SCALED(3, 8 + J);
  if (w < 3) {
    uint2* hs = reinterpret_cast<uint2*>(sm + kSmHalo + w * 2048) + lane;
#pragma unroll
    for (int i = 0; i < 4; i++) {
      hs[i * 32] = make_uint2(k[4][2 * i], k[4][2 * i + 1]);
      hs[128 + i * 32] = make_uint2(vt[4][2 * i], vt[4][2 * i + 1]);
    }
  } else if ((b & 7) != 7) {
    uint4* gh = g_halo + ((layer * 16 + b) * 16 + hp) * 256 + lane;
#pragma unroll
    for (int i = 0; i < 4; i++) {
      st_packet(gh + i * 32, k[4][2 * i], k[4][2 * i + 1], epoch);
      st_packet(gh + 128 + i * 32, vt[4][2 * i], vt[4][2 * i + 1], epoch);
    }
  }
#pragma unroll
  for (int c = 0; c < 3; c++)
#pragma unroll
    for (int J = 0; J < 8; J++) {
      k[c + 1][J] = SCALED(c, 8 + J);
      vt[c + 1][J] = transpose8(SCALED(c, 16 + J));
      yield_slot();
    }
  const bool first = w == 0 && (b & 7) == 0;
  const uint4* gh = g_halo + ((layer * 16 + b - 1) * 16 + hp) * 256 + lane;
  uint32_t tag[8];
#define LOAD_HALO()                                                                                    \
  _Pragma("unroll") for (int i = 0; i < 4; i++) {                                                      \
    ld_packet(gh + i * 32, k[0][2 * i], k[0][2 * i + 1], tag[i]);                                      \
    ld_packet(gh + 128 + i * 32, vt[0][2 * i], vt[0][2 * i + 1], tag[4 + i]);                          \
  }
#define AWAIT_HALO()                                                                                   \
  for (unsigned spins = 0;; spins++) {                                                                 \
    const unsigned d0 = (tag[0] ^ epoch) | (tag[1] ^ epoch) | (tag[2] ^ epoch) | (tag[3] ^ epoch);     \
    const unsigned d1 = (tag[4] ^ epoch) | (tag[5] ^ epoch) | (tag[6] ^ epoch) | (tag[7] ^ epoch);     \
    if (__all_sync(0xffffffffu, (d0 | d1) == 0)) break;                                                \
    if (spins > kSpinLimit) __trap();                                                                  \
    LOAD_HALO();                                                                                       \
  }
#pragma unroll
  for (int c = 0; c <= 4; c++) {
    if (c == HALO_AT) {
      if (w == 0 && !first) {
        LOAD_HALO();
      } else {
#pragma unroll
        for (int i = 0; i < 8; i++) k[0][i] = vt[0][i] = tag[i] = 0u;
      }
    }
#pragma unroll
    for (int J = 0; J < 8 && c < 4; J++) {
      q[c & 3][J] = SCALED(c & 3, J);
      if (J & 1) yield_slot();
    }
  }
#undef SCALED
  TRACE_AT(tile, 8);
  wg_bar(wg);
  if (w > 0) {
    const uint2* hs = reinterpret_cast<const uint2*>(sm + kSmHalo + (w - 1) * 2048) + lane;
#pragma unroll
    for (int i = 0; i < 4; i++) {
      const uint2 a = hs[i * 32], c = hs[128 + i * 32];
      k[0][2 * i] = a.x; k[0][2 * i + 1] = a.y;
      vt[0][2 * i] = c.x; vt[0][2 * i + 1] = c.y;
    }
  } else if (!first && tq == 0) {
    AWAIT_HALO();
  }
  constexpr float kScale = 0.17677669529663687f * 1.4426950408889634f;
  const bool own0 = 2 * t <= g, own1 = 2 * t + 1 <= g;
  const uint32_t own_mask = (own0 ? 0xffffu : 0u) | (own1 ? 0xffff0000u : 0u);
  const uint32_t stg = sb + kSmStg + w * 4096;
  const uint32_t orow = stg + (lane & 7) * 128, ochunk = (lane >> 3) ^ (lane & 7);
  TRACE_AT(tile, 9);
  mbar_wait(sb + kBarPause + att * 8, 0);
  TRACE_AT(tile, 10);

  float s[2][6][4], o[2][4][2][4];
  auto scores = [&](int hd, int m) {
    const int ca = 2 * (m / 3), kg = ca + m % 3;
#pragma unroll
    for (int e = 0; e < 4; e++) s[hd][m][e] = 0.f;
#pragma unroll
    for (int J = 4 * hd; J < 4 * hd + 4; J += 2)
      mma16816(s[hd][m], q[ca][J], q[ca + 1][J], q[ca][J + 1], q[ca + 1][J + 1], k[kg][J], k[kg][J + 1]);
  };
  auto attend = [&](int c0, int c1) {
    float v0[2][4], v1[2][4], m[2][4];
#define UNITS _Pragma("unroll") for (int hd = 0; hd < 2; hd++) _Pragma("unroll") for (int c = c0; c < c1; c++)
    UNITS {
      const int mp = 3 * (c >> 1) + (c & 1), r = 2 * (c & 1);
      float p0 = s[hd][mp][r], p1 = s[hd][mp][r + 1];
      if (c == 0 && first) p0 = p1 = -INFINITY;
      v0[hd][c] = own0 ? s[hd][mp + 1][r] : p0;
      v1[hd][c] = own1 ? s[hd][mp + 1][r + 1] : p1;
      m[hd][c] = fmaxf(v0[hd][c], v1[hd][c]);
    }
    UNITS m[hd][c] = fmaxf(m[hd][c], shfl_xor(m[hd][c], 1));
    UNITS m[hd][c] = fmaxf(m[hd][c], shfl_xor(m[hd][c], 2));
    UNITS {
      const float nm = -m[hd][c] * kScale;
      v0[hd][c] = ex2(fmaf(v0[hd][c], kScale, nm));
      v1[hd][c] = ex2(fmaf(v1[hd][c], kScale, nm));
      m[hd][c] = v0[hd][c] + v1[hd][c];
    }
    UNITS m[hd][c] += shfl_xor(m[hd][c], 1);
    UNITS m[hd][c] += shfl_xor(m[hd][c], 2);
    UNITS {
      const float inv = rcp(m[hd][c]);
      const uint32_t p = pack2(v0[hd][c] * inv, v1[hd][c] * inv);
#pragma unroll
      for (int ds = 0; ds < 2; ds++) {
        const int J = 4 * hd + 2 * ds;
#pragma unroll
        for (int e = 0; e < 4; e++) o[hd][c][ds][e] = 0.f;
        if (c & 1) {
          mma16816(o[hd][c][ds], vt[c][J], vt[c][J + 1], vt[c + 1][J], vt[c + 1][J + 1], p & ~own_mask, p & own_mask);
        } else {
          mma1688(o[hd][c][ds], vt[c + 1][J], vt[c + 1][J + 1], p & own_mask);
          mma1688(o[hd][c][ds], vt[c][J], vt[c][J + 1], p & ~own_mask);
        }
      }
    }
  };
  auto stage = [&](int c0, int c1) {
    UNITS stsm4_t(orow + c * 1024 + ((ochunk ^ (4 * hd)) << 4), pack2(o[hd][c][0][0], o[hd][c][0][1]),
                  pack2(o[hd][c][0][2], o[hd][c][0][3]), pack2(o[hd][c][1][0], o[hd][c][1][1]),
                  pack2(o[hd][c][1][2], o[hd][c][1][3]));
#undef UNITS
  };
  if (w == 0 && !first) AWAIT_HALO();
#pragma unroll
  for (int hd = 0; hd < 2; hd++)
#pragma unroll
    for (int m = 0; m < 6; m++) scores(hd, m);
  attend(0, 4);
  yield_slot();
  if (tq == 0 && elect()) mbar_arrive(sb + kBarResume + att * 8);
  TRACE_AT(tile, 11);
  stage(0, 4);
#undef AWAIT_HALO
#undef LOAD_HALO
  fence_async_smem();
  __syncwarp();
  TRACE_AT(tile, 12);
  if (elect()) {
    bulk_store(g_o + (b * 16 + hp) * kTileBytes + w * 4096, stg, 4096);
    bulk_commit();
    if (tq == 1 && !RESUME_LATE) mbar_arrive(sb + kBarResume + att * 8);
    bulk_wait();
    if (tq == 1 && RESUME_LATE) mbar_arrive(sb + kBarResume + att * 8);
    TRACE_AT(tile, 13);
    mbar_arrive(sb + kBarEpi + tile * 8);
  }
  __syncwarp();
}

__device__ __forceinline__ void gather_stats(uint8_t* sm, const uint2* stat, unsigned epoch) {
  const int r = threadIdx.x & 127;
  uint2 a[8];
  unsigned spins = 0;
  while (true) {
    unsigned diff = 0;
#pragma unroll
    for (int i = 0; i < 8; i++) {
      a[i] = ld_relaxed2(stat + i * 128 + r);
      diff |= (a[i].x ^ epoch) | (a[i].y ^ epoch);
    }
    if (__all_sync(0xffffffffu, (diff & 7u) == 0)) break;
    if (++spins > kSpinLimit) __trap();
    __nanosleep(200);
  }
  float s = 0.f, q = 0.f;
#pragma unroll
  for (int i = 0; i < 8; i++) {
    s += untag_value(a[i].x);
    q += untag_value(a[i].y);
  }
  const float mean = s * (1.f / 1024.f);
  const float var = fmaxf(fmaf(-mean, mean, q * (1.f / 1024.f)), 0.f);
  reinterpret_cast<float2*>(sm + kSmStat)[r] = make_float2(rsqrtf(var + 1e-5f), -mean);
}

__device__ __forceinline__ void gather_colsums(uint8_t* sm, int part, int j, int lane, unsigned epoch) {
#pragma unroll 1
  for (int blk = part < 4 ? 0 : 2 * part - 5; blk < (part < 4 ? 3 : 2 * part - 3); blk++) {
    const int col = part < 2 ? blk * kD + (j + 8 * part) * 64
                             : 3 * kD + 64 * (blk + (blk < 3 ? 3 * j : blk < 5 ? 21 + 2 * j : 35 + 2 * j));
    uint2 v;
    unsigned spins = 0;
    while (true) {
      v = ld_relaxed2(reinterpret_cast<const uint2*>(g_cs + col) + lane);
      if (__all_sync(0xffffffffu, (((v.x ^ epoch) | (v.y ^ epoch)) & 7u) == 0)) break;
      if (++spins > kSpinLimit) __trap();
      __nanosleep(100);
    }
    uint8_t* dst = part < 2 ? sm + kSmCsQ + (part * 96 + blk * 32 + lane) * 8 : sm + kSmV1 + (blk * 32 + lane) * 16;
    *reinterpret_cast<float2*>(dst) = make_float2(untag_value(v.x), untag_value(v.y));
  }
}

#define READBACK 0
#define DRY_X 0
#define EARLY_EPI 1
#define PF_START 0
#define PAUSE_QKV2 7
#define PAUSE_WO 1

__global__ void __cluster_dims__(2, 1, 1) __launch_bounds__(384, 1)
fused_layers_kernel(const __grid_constant__ CUtensorMap map_x, const __grid_constant__ CUtensorMap map_out,
                    const __grid_constant__ CUtensorMap map_qkv, const __grid_constant__ CUtensorMap map_wo,
                    const __grid_constant__ CUtensorMap map_w1a, const __grid_constant__ CUtensorMap map_w1b,
                    const __grid_constant__ CUtensorMap map_w2, const __grid_constant__ CUtensorMap map_csq,
                    const __grid_constant__ CUtensorMap map_cs1, const __grid_constant__ Params prm) {
  extern __shared__ __align__(1024) uint8_t sm[];
  if (threadIdx.x < 128 && blockIdx.x < kCtas) TRACE_AT(15, 1);
  const uint32_t sb = __shfl_sync(0xffffffffu, smem_u32(sm), 0);
  const int warp = __shfl_sync(0xffffffffu, threadIdx.x >> 5, 0), lane = threadIdx.x & 31;
  const int cta = blockIdx.x, rank = cta & 1, cl = cta >> 1;
  const int grp = cl < 4 ? 0 : cl < 36 ? (cl - 4) & 7 : 1 + (cl - 36) % 7;
  const int j = cl < 4 ? 4 + cl : cl < 36 ? (cl - 4) >> 3 : 4 + (cl - 36) / 7;
  const int b = 2 * grp + rank;
  const int xcol = (b >> 3) * kD, xrow = (b & 7) * 128;

  if (cta >= kCtas) {
    helper_cta(&map_csq, &map_cs1, sm, sb, cta - kCtas, warp);
    return;
  }
  if (warp >= 8 && elect()) {
    if (warp == 9) {
#pragma unroll
      for (int s = 0; s < 8; s++) mbar_init(sb + kBarFull + s * 8, 1);
      fence_async_smem();
#pragma unroll
      for (int s = 0; s < 4; s++) {
        const uint32_t full = sb + kBarFull + s * 8, dst = sb + kSmRing + s * 40960;
        mbar_expect_tx(full, 40960);
        tma2d(dst, &map_x, full, xcol + s * 64, xrow);
        tma3d(dst + kTileBytes, &map_qkv, full, j * 64, s * 64, 0);
        tma3d(dst + kTileBytes + 12288, &map_qkv, full, j * 64, s * 64 + 32, 0);
      }
      if (PF_START & 1) l2_prefetch(reinterpret_cast<const uint8_t*>(prm.x) + cta * 32768, 32768);
      if (PF_START & 2) l2_prefetch(reinterpret_cast<const uint8_t*>(prm.wqkv) + cta * 49152, 49152);
    } else if (warp == 8) {
      if (sb & 1023) __trap();
#pragma unroll
      for (int o = kBarTurn; o < kBarInit; o += 8) mbar_init(sb + o, 1);
    } else if (warp == 10) {
#pragma unroll
      for (int o = kBarEpoch; o < kSmEpoch; o += 8) mbar_init(sb + o, o < kBarEmpty ? 1 : o < kBarEpi ? 2 : 4);
    } else {
      mbar_init(sb + kBarInit, 1);
      fence_async_smem();
      mbar_expect_tx(sb + kBarInit, 32768);
      tma2d(sb + kSmX, &map_x, sb + kBarInit, xcol + j * 128, xrow);
      tma2d(sb + kSmX + kTileBytes, &map_x, sb + kBarInit, xcol + j * 128 + 64, xrow);
    }
    asm volatile("fence.mbarrier_init.release.cluster;" ::: "memory");
  }
  __syncwarp();
  asm volatile("barrier.cluster.arrive.relaxed.aligned;" ::: "memory");

  if (warp >= 8) {
    asm volatile("setmaxnreg.dec.sync.aligned.u32 40;");
    if (warp < 10) {
      asm volatile("barrier.cluster.wait.aligned;" ::: "memory");
      uint32_t nb = 32, off = 0, kb = 0;
#define RING_STEP(ISSUE)                                                  \
  do {                                                                    \
    const uint32_t mb = nb - depth, full = sb + kBarFull + (nb & 56);     \
    if (kb == skip) kb += inc;                                            \
    mbar_wait(sb + kBarEmpty + (mb & 56), mb >> 6);                       \
    if (elect()) { ISSUE; }                                               \
    TRACE_ISSUE(9 - warp, nb);                                            \
    kb += inc;                                                            \
    off = off == wrap ? 0 : off + step;                                   \
    nb += 8;                                                              \
  } while (nb != nend)
#pragma unroll 1
      for (int sg = 0; sg < kSegs; sg++) {
        const uint32_t e = prm.seg[sg];
        const int ty = e & 7, mode = (e >> 15) & 3, reset = (e >> 24) & 3;
        const uint32_t nend = nb + (e & 0x1f8);
        const uint32_t step = (e >> 17) & 1 ? 40960 : 32768, wrap = 163840 - step;
        const uint32_t depth = (e >> 18) & 1 ? 40 : 32;
        if (reset) off = reset == 1 ? 0 : reset == 2 ? 40960 : 131072;
        const uint32_t own = ty == 2 ? 8 + j : 2 * j;
        if (mode != kModeContinue) kb = mode == kModeHead ? own : (e >> 9) & 63;
        const uint32_t inc = mode >= kModeSkip && ty != 2 ? 2 : 1, skip = mode >= kModeSkip ? own + (kb & 1) : 255;
        if (warp == 8) {
          const CUtensorMap* map = ty < 2 ? &map_qkv : ty == 2 ? &map_wo : ty == 3 ? &map_w1a : ty < 6 ? &map_w1b : &map_w2;
          const int c0 = ty < 2 ? (j + 8 * ty) * 64 : 0;
          const int c2 = ty < 2 ? 0 : ty == 3 ? 3 * j : ty == 4 ? 24 + 2 * j : ty == 5 ? 40 + 2 * j : 2 * j;
          const uint32_t half = (ty < 2 || ty == 3) ? 12288 : 8192;
          const uint32_t bytes = 2 * half + (mode == kModeHead ? 0 : kTileBytes);
          const uint32_t dst = sb + kSmRing + kTileBytes + rank * half;
#pragma unroll 1
          RING_STEP(mbar_expect_tx(full, bytes); tma3d_mc(dst + off, map, full, c0, kb * 64 + rank * 32, c2));
        } else if (mode == kModeHead) {
          off += ((nend - nb) >> 3) * step;
          nb = nend;
          if (off >= 163840) off -= 163840;
        } else if (sg < 2) {
#pragma unroll 1
          RING_STEP(tma2d(sb + kSmRing + off, &map_x, full, xcol + kb * 64, xrow));
        } else {
          const uint8_t* src = ty == 6 ? g_h + b * 56 * kTileBytes : (ty == 2 ? g_o : g_x) + b * 16 * kTileBytes;
          const int dep = (e >> 19) & 31;
          if (dep != 31) mbar_wait(sb + kBarReady + dep * 8, 0);
#pragma unroll 1
          RING_STEP(bulk_load(sb + kSmRing + off, src + kb * kTileBytes, kTileBytes, full));
        }
      }
#undef RING_STEP
    } else if (warp == 10) {
      unsigned epoch = 0;
      if (lane == 0) epoch = atomicAdd(&g_ticket, 1u) / kGrid + 1;
      epoch = __shfl_sync(0xffffffffu, epoch, 0);
      *reinterpret_cast<unsigned*>(sm + kSmEpoch) = epoch;
      asm volatile("barrier.cluster.wait.aligned;" ::: "memory");
      if (elect()) mbar_arrive(sb + kBarEpoch);
#pragma unroll 1
      for (int i = 0; i < kTiles - 1; i++) {
        const bool xt = i == 2 || i == 6 || i == 9;
        const unsigned* line = g_flag + (i * 16 + b) * 32;
        mbar_wait(sb + kBarEpi + i * 8, 0);
        wait_flags(line + (lane & 7), epoch);
        if (elect()) mbar_arrive(sb + kBarReady + i * 8);
        if (xt) {
          wait_flags(line + 8 + (lane & 7), epoch);
          if (elect()) mbar_arrive(sb + kBarReady + (14 + (i >> 2)) * 8);
        }
      }
    } else {
      {
        uint32_t v[7];
#pragma unroll
        for (int q = 0; q < 7; q++)
          v[q] = reinterpret_cast<const uint32_t*>(prm.b1)[32 * (q + (q < 3 ? 3 * j : q < 5 ? 21 + 2 * j : 35 + 2 * j)) + lane];
        const uint2 u = reinterpret_cast<const uint2*>(prm.b2)[32 * j + lane];
#pragma unroll
        for (int q = 0; q < 7; q++)
          *reinterpret_cast<float2*>(sm + kSmV1 + (q * 32 + lane) * 16 + 8) = make_float2(kGeluBeta * bf_lo(v[q]), kGeluBeta * bf_hi(v[q]));
        reinterpret_cast<float4*>(sm + kSmB2)[lane] = make_float4(
            2.f * kGeluBeta * bf_lo(u.x), 2.f * kGeluBeta * bf_hi(u.x), 2.f * kGeluBeta * bf_lo(u.y), 2.f * kGeluBeta * bf_hi(u.y));
      }
      asm volatile("barrier.cluster.wait.aligned;" ::: "memory");
      mbar_wait(sb + kBarEpoch, 0);
      const unsigned epoch = *reinterpret_cast<volatile unsigned*>(sm + kSmEpoch);
#pragma unroll 1
      for (int i = 0; i < kTiles - 1; i++) {
#pragma unroll 1
        for (int part = i == 4 ? 5 : i; part < (i < 2 ? i + 1 : i == 3 || i == 4 ? i + 2 : 0); part++) {
          gather_colsums(sm, part, j, lane, epoch);
          __syncwarp();
          if (elect()) mbar_arrive(sb + kBarCs + part * 8);
        }
        const bool xt = i == 2 || i == 6 || i == 9;
#pragma unroll 1
        for (int h = 0; h < (xt ? 2 : 1); h++) {
          mbar_wait(sb + (h == 0 ? kBarEpi + i * 8 : kBarX + (i >> 2) * 16 + 8), 0);
          const int ty = i >= 7 ? i - 7 : i;
          if ((h == 1 || (ty >= 3 && !xt)) && elect()) {
            uint8_t* dst = xt ? g_x + (b * 16 + 2 * j + 1) * kTileBytes
                              : g_h + (b * 56 + 1 + (ty == 3 ? 3 * j : 16 * ty - 40 + 2 * j)) * kTileBytes;
            bulk_store(dst, sb + (xt ? kSmX + kTileBytes : kSmStg), kTileBytes);
            bulk_commit();
            bulk_wait();
            mbar_arrive(sb + kBarFree + i * 8);
          }
          __syncwarp();
          if (elect()) st_release(&g_flag[(i * 16 + b) * 32 + h * 8 + j], epoch);
          __syncwarp();
        }
      }
    }
    __syncwarp();
    asm volatile("barrier.cluster.arrive.relaxed.aligned;\nbarrier.cluster.wait.aligned;" ::: "memory");
  } else {
    asm volatile("setmaxnreg.inc.sync.aligned.u32 232;");
    asm volatile("barrier.cluster.wait.aligned;" ::: "memory");
    const int wg = warp >> 2, w = warp & 3;
    const bool rel = (threadIdx.x & 95) == 0;
    const uint32_t rel_addr = mapa(sb + kBarEmpty, w & 1);
    if (wg == 1) TRACE_AT(15, 0);
#define EPOCH (*reinterpret_cast<volatile unsigned*>(sm + kSmEpoch))

    if (wg == 1) {
      mbar_wait(sb + kBarEpoch, 0);
      mbar_wait(sb + kBarInit, 0);
    }

#pragma unroll 1
    for (int i = wg; i < kTiles; i += 2) {
      const int layer = i >= 7, ty = i - 7 * layer;
      TRACE_AT(i, 15);
      float acc[2][96];
      if (ty == 2 || ty == 6) {
        const uint32_t xrow_addr = sb + kSmX + (32 * w + lane) * 128;
        const float2* b2 = reinterpret_cast<const float2*>(sm + kSmB2) + (lane & 3);
        const float up = ty == 6 ? 2.f * kGeluBeta : 1.f;
#pragma unroll
        for (int J = 0; J < 16; J++) {
          uint32_t r[4];
          ldsm4(xrow_addr + (J >> 3) * kTileBytes + (((J & 7) ^ (lane & 7)) << 4), r);
          float2 bias = make_float2(0.f, 0.f);
          if (ty == 6) bias = b2[J * 4];
#pragma unroll
          for (int c = 0; c < 4; c++) {
            acc[c & 1][4 * J + (c & 2)] = fmaf(bf_lo(r[c]), up, bias.x);
            acc[c & 1][4 * J + (c & 2) + 1] = fmaf(bf_hi(r[c]), up, bias.y);
            asm volatile("" : "+f"(acc[c & 1][4 * J + (c & 2)]), "+f"(acc[c & 1][4 * J + (c & 2) + 1]));
            if (c & 1) yield_slot();
          }
        }
        mainloop<128, true>(acc, sb, i, layer * 152 + ty * 16, ty == 6 ? 4 : 0, ty == 6 ? 56 : 16, ty == 2 ? PAUSE_WO : -1,
                      2 * layer + 1, rel_addr, rel, 64, ty == 2 ? 8 : -1, [] {});
        TRACE_AT(i, 2);
      } else {
        const int xver = 2 * layer + (ty >= 3);
        const uint32_t stg = sb + kSmStg + w * 4096;
        const float4* vec = reinterpret_cast<const float4*>(sm + kSmV1) + (ty == 3 ? 0 : 64 * ty - 160) + (lane & 3);
        uint8_t* hdst = g_h + (b * 56 + (ty == 3 ? 3 * j : 16 * ty - 40 + 2 * j)) * kTileBytes + w * 4096;
        float2 st[4];
        unsigned epoch;
        auto pre = [&] {
          if (ty < 4) mbar_wait(sb + (ty == 1 ? kBarEpi + (i - 1) * 8 : kBarStat + xver * 8), 0);
#pragma unroll
          for (int c = 0; c < 4; c++) st[c] = reinterpret_cast<const float2*>(sm + kSmStat)[32 * w + 8 * c + (lane >> 2)];
          epoch = EPOCH;
        };
        if (ty == 5) {
          const uint32_t nb = (layer * 152 + 80) * 8, s0 = ((((sb & 0x3FFFF) + kSmRing) >> 4) | (1u << 16)) + 3 * 2048;
          mbar_wait(sb + kBarTurn + (i - 1) * 8, 0);
          mbar_wait(sb + kBarFull, nb >> 6);
          TRACE_KB(nb);
          mma_kblock<128, 2>(acc, s0, s0 + kToB);
        } else {
          if (i < 2) {
            zero_acc<192>(acc);
          } else {
            const int n0 = layer * 152 + (ty < 2 ? 2 * ty : 42 + 2 * ty), slot = ty < 2 ? 2 * ty : 2 * ty - 5;
            if (ty < 4) {
              head_blocks<192>(acc, sb, n0, slot, sb + kBarX + (xver - 1) * 16,
                               sb + kBarEpi + (xver == 1 ? 2 : 3 * xver) * 8, rel_addr, rel);
            } else {
              head_blocks<128>(acc, sb, n0, slot, sb + kBarX + (xver - 1) * 16,
                               sb + kBarEpi + (xver == 1 ? 2 : 3 * xver) * 8, rel_addr, rel);
#pragma unroll
              for (int q = 64; q < 96; q++) acc[0][q] = acc[1][q] = 0.f;
            }
          }
          if (ty == 1 || ty == 4) {
            uint2* stat = g_stat + (xver * 16 + b) * 1024;
            publish_stats(sb, stat + j * 128, w, lane, EPOCH);
            gather_stats(sm, stat, EPOCH);
            __syncwarp();
            if (elect()) mbar_arrive(sb + kBarStat + xver * 8);
            TRACE_AT(i, 14);
            if (i == 8) {
#pragma unroll
              for (int c = 0; c < 4; c++) st[c] = reinterpret_cast<const float2*>(sm + kSmStat)[32 * w + 8 * c + (lane >> 2)];
              add_mean_term(acc, st, sm, 1, lane);
            }
          }
          if (ty < 4) {
            mainloop<192, false>(acc, sb, i, i < 2 ? 16 * i : layer * 152 + (ty < 2 ? 4 + 14 * ty : 52), i == 8 ? 2 : ty == 3,
                          i < 2 ? 16 : 14, ty == 1 ? PAUSE_QKV2 : -1, xver, rel_addr, rel, 64, 0, pre);
            TRACE_AT(i, 2);
            if (layer == 0) mbar_wait(sb + kBarCs + ty * 8, 0);
            if (ty < 2) {
              if (i != 8) add_mean_term(acc, st, sm, ty, lane);
              epilogue_attn(acc, st, sm, sb, layer, ty, b, j, epoch, i, wg, w);
              goto tile_done;
            }
            scale_stats(st);
            gelu_chunk<2>(acc, st, vec, stg, lane, false, nullptr, 0);
            goto common_chunks;
          }
        }
        mainloop<128, false>(acc, sb, i, layer * 152 + 6 + 15 * ty, 4, ty + 10, -1, 0, rel_addr, rel, ty == 5 ? 0 : 64, 0, pre);
        TRACE_AT(i, 2);
        if (layer == 0) mbar_wait(sb + kBarCs + ty * 8, 0);
        scale_stats(st);
      common_chunks:
        TRACE_AT(i, 8);
        gelu_chunk<0>(acc, st, vec, stg, lane, ty == 3, hdst + 2 * kTileBytes, sb + kBarFree + (i - 1) * 8);
        TRACE_AT(i, 9);
        gelu_chunk<1>(acc, st, vec, stg, lane, true, hdst, 0);
        TRACE_AT(i, 10);
        fence_async_smem();
        __syncwarp();
        if (elect()) mbar_arrive(sb + kBarEpi + i * 8);
      tile_done:
        TRACE_AT(i, 3);
        if (!DRY_X || (ty != 1 && ty != 5)) continue;
        zero_acc<128>(acc);
        fence_acc<128>(acc);
      }
      const bool live = ty == 2 || ty == 6;
#pragma unroll
      for (int h = 0; h < 2; h++) {
        if (ty >= 5) {
#pragma unroll
          for (int q = 32 * h; q < 32 * h + 32; q++) {
            acc[0][q] *= 0.5f / kGeluBeta;
            acc[1][q] *= 0.5f / kGeluBeta;
          }
        }
#pragma unroll
        for (int J = 8 * h; J < 8 * h + 8; J++)
          stsm4_if(live, sb + kSmX + (32 * w + lane) * 128 + h * kTileBytes + (((J & 7) ^ (lane & 7)) << 4),
                   pack2(acc[0][4 * J], acc[0][4 * J + 1]), pack2(acc[1][4 * J], acc[1][4 * J + 1]),
                   pack2(acc[0][4 * J + 2], acc[0][4 * J + 3]), pack2(acc[1][4 * J + 2], acc[1][4 * J + 3]));
        fence_async_smem();
        __syncwarp();
        if (live && elect()) {
          const uint32_t src = sb + kSmX + h * kTileBytes + w * 4096;
          if (i == kTiles - 1) {
            tma2d_store(&map_out, src, xcol + j * 128 + h * 64, xrow + 32 * w);
            bulk_commit();
            if (h == 1) bulk_wait_read();
          } else if (h == 0) {
            bulk_store(g_x + (b * 16 + 2 * j) * kTileBytes + w * 4096, src, 4096);
            bulk_commit();
            mbar_arrive(sb + kBarX + (i >> 2) * 16);
            if (EARLY_EPI) {
              bulk_wait();
              mbar_arrive(sb + kBarEpi + i * 8);
            }
          } else {
            mbar_arrive(sb + kBarX + (i >> 2) * 16 + 8);
            if (!EARLY_EPI) {
              bulk_wait();
              mbar_arrive(sb + kBarEpi + i * 8);
            }
          }
        }
        __syncwarp();
        yield_slot();
        if (live) TRACE_AT(i, 8 + h);
      }
      if (live) TRACE_AT(i, 3);
    }
#undef EPOCH
    asm volatile("barrier.cluster.arrive.relaxed.aligned;\nbarrier.cluster.wait.aligned;" ::: "memory");
    if (wg == 1) TRACE_AT(15, 2);
  }
}

void build_segments(uint32_t* seg) {
  int n = 0;
  auto add = [&](int ty, int cnt, int kb0, int mode, int wide, int depth5, int dep, int reset) {
    seg[n++] = ty | cnt << 3 | kb0 << 9 | mode << 15 | wide << 17 | depth5 << 18 | dep << 19 | reset << 24;
  };
  for (int l = 0; l < 2; l++) {
    const int t = 7 * l;
    if (l == 0) {
      add(0, 12, 4, kModePlain, 1, 0, 31, 1);
      add(1, 16, 0, kModePlain, 1, 0, 31, 0);
    } else {
      add(0, 2, 0, kModeHead, 1, 0, 31, 1);
      add(1, 2, 0, kModeHead, 1, 0, 31, 0);
      add(0, 7, 0, kModeSkip, 1, 0, 6, 0);
      add(0, 7, 1, kModeSkip, 1, 0, 15, 0);
      add(1, 7, 0, kModeSkip, 1, 0, 31, 0);
      add(1, 7, 1, kModeSkip, 1, 0, 31, 0);
    }
    add(2, 4, 0, kModePlain, 0, 0, t, 1);
    add(2, 4, 4, kModePlain, 0, 1, 31, 0);
    add(2, 1, 0, kModeHead, 0, 1, 31, 0);
    add(2, 7, 8, kModeSkip, 0, 1, t + 1, 0);
    add(3, 2, 0, kModeHead, 1, 0, 31, 2);
    add(4, 2, 0, kModeHead, 1, 0, 31, 0);
    add(3, 7, 0, kModeSkip, 1, 0, t + 2, 0);
    add(3, 7, 1, kModeSkip, 1, 0, 14 + 2 * l, 0);
    add(4, 4, 0, kModeSkip, 0, 0, 31, 3);
    add(4, 3, 0, kModeContinue, 0, 1, 31, 0);
    add(4, 7, 1, kModeSkip, 0, 1, 31, 0);
    add(5, 16, 0, kModePlain, 0, 1, 31, 0);
    add(6, 24, 0, kModePlain, 0, 1, t + 3, 0);
    add(6, 16, 24, kModePlain, 0, 1, t + 4, 0);
    add(6, 16, 40, kModePlain, 0, 1, t + 5, 0);
  }
}

typedef CUresult (*EncodeTiledFn)(CUtensorMap*, CUtensorMapDataType, cuuint32_t, void*, const cuuint64_t*,
                                  const cuuint64_t*, const cuuint32_t*, const cuuint32_t*, CUtensorMapInterleave,
                                  CUtensorMapSwizzle, CUtensorMapL2promotion, CUtensorMapFloatOOBfill);

CUtensorMap make_map(EncodeTiledFn enc, const void* p, int rank, const cuuint64_t* dims, const cuuint64_t* strides,
                     const cuuint32_t* box, CUtensorMapSwizzle swizzle = CU_TENSOR_MAP_SWIZZLE_128B) {
  CUtensorMap m;
  const cuuint32_t es[5] = {1, 1, 1, 1, 1};
  enc(&m, CU_TENSOR_MAP_DATA_TYPE_BFLOAT16, rank, const_cast<void*>(p), dims, strides, box, es,
      CU_TENSOR_MAP_INTERLEAVE_NONE, swizzle, CU_TENSOR_MAP_L2_PROMOTION_L2_128B,
      CU_TENSOR_MAP_FLOAT_OOB_FILL_NONE);
  return m;
}

CUtensorMap weight_map(EncodeTiledFn enc, const void* p, int k, int n, int blocks) {
  const cuuint64_t dims[3] = {64, (cuuint64_t)k, (cuuint64_t)n / 64};
  const cuuint64_t strides[2] = {(cuuint64_t)n * 2, 128};
  const cuuint32_t box[3] = {64, 32, (cuuint32_t)blocks};
  return make_map(enc, p, 3, dims, strides, box);
}

CUtensorMap slab_map(EncodeTiledFn enc, const void* p, int n) {
  const cuuint64_t dims[2] = {(cuuint64_t)n, kD};
  const cuuint64_t strides[1] = {(cuuint64_t)n * 2};
  const cuuint32_t box[2] = {128, 128};
  return make_map(enc, p, 2, dims, strides, box, CU_TENSOR_MAP_SWIZZLE_NONE);
}

CUtensorMap token_map(EncodeTiledFn enc, const void* p, int rows) {
  const cuuint64_t dims[2] = {2 * kD, 1024};
  const cuuint64_t strides[1] = {4 * kD};
  const cuuint32_t box[2] = {64, (cuuint32_t)rows};
  return make_map(enc, p, 2, dims, strides, box);
}

}

extern "C" void kernel_launch(void* const* d_in, const int* in_sizes, int n_in, void* d_out, int out_size) {
  (void)in_sizes; (void)n_in; (void)out_size;
  static EncodeTiledFn enc = nullptr;
  if (!enc) {
    void* fn = nullptr;
    cudaDriverEntryPointQueryResult q;
    cudaGetDriverEntryPoint("cuTensorMapEncodeTiled", &fn, cudaEnableDefault, &q);
    enc = (EncodeTiledFn)fn;
    cudaFuncSetAttribute(fused_layers_kernel, cudaFuncAttributeMaxDynamicSharedMemorySize, kSmBytes);
  }
  Params prm;
  prm.x = (const __nv_bfloat16*)d_in[0];
  prm.wqkv = (const __nv_bfloat16*)d_in[1];
  prm.wo = (const __nv_bfloat16*)d_in[2];
  prm.w1 = (const __nv_bfloat16*)d_in[4];
  prm.b1 = (const __nv_bfloat16*)d_in[5];
  prm.w2 = (const __nv_bfloat16*)d_in[6];
  prm.b2 = (const __nv_bfloat16*)d_in[7];
  build_segments(prm.seg);
  const cuuint64_t qd[3] = {kD, kD, 3}, qs[2] = {3 * kD * 2, kD * 2};
  const cuuint32_t qb[3] = {64, 32, 3};
  const CUtensorMap map_x = token_map(enc, d_in[0], 128);
  const CUtensorMap map_out = token_map(enc, d_out, 32);
  const CUtensorMap map_qkv = make_map(enc, prm.wqkv, 3, qd, qs, qb);
  const CUtensorMap map_wo = weight_map(enc, prm.wo, kD, kD, 2);
  const CUtensorMap map_w1a = weight_map(enc, prm.w1, kD, kF, 3);
  const CUtensorMap map_w1b = weight_map(enc, prm.w1, kD, kF, 2);
  const CUtensorMap map_w2 = weight_map(enc, prm.w2, kF, kD, 2);
  fused_layers_kernel<<<kGrid, 384, kSmBytes>>>(map_x, map_out, map_qkv, map_wo, map_w1a, map_w1b, map_w2,
                                                slab_map(enc, prm.wqkv, 3 * kD), slab_map(enc, prm.w1, kF), prm);
}
```

```cpp
#include <cuda.h>
#include <cuda_bf16.h>
#include <cuda_runtime.h>
#include <stdint.h>

namespace {

constexpr int kD = 1024;
constexpr int kF = 3584;
constexpr int kCtas = 128;
constexpr int kGrid = 132;
constexpr int kTiles = 14;
constexpr int kTileBytes = 16384;

constexpr int kSmRing = 0;
constexpr int kSmX = 163840;
constexpr int kSmStg = kSmX + 32768;
constexpr int kSmHalo = kSmStg + 16384;
constexpr int kSmCsQ = kSmHalo + 6144;
constexpr int kSmV1 = kSmCsQ + 384 * 4;
constexpr int kSmB2 = kSmV1 + 448 * 8;
constexpr int kSmStat = kSmB2 + 128 * 4;
constexpr int kSmBar = kSmStat + 128 * 8;
constexpr int kBarFull = kSmBar;
constexpr int kBarTurn = kBarFull + 8 * 8;
constexpr int kBarReady = kBarTurn + 14 * 8;
constexpr int kBarPause = kBarReady + 17 * 8;
constexpr int kBarFree = kBarPause + 4 * 8;
constexpr int kBarCs = kBarFree + 14 * 8;
constexpr int kBarInit = kBarCs + 6 * 8;
constexpr int kBarEpoch = kBarInit + 8;
constexpr int kBarEmpty = kBarEpoch + 8;
constexpr int kBarEpi = kBarEmpty + 9 * 8;
constexpr int kBarX = kBarEpi + 14 * 8;
constexpr int kBarStat = kBarX + 8 * 8;
constexpr int kBarResume = kBarStat + 4 * 8;
constexpr int kSmEpoch = kBarResume + 4 * 8;
constexpr int kSmBytes = kSmEpoch + 16;
constexpr int kSegs = 38;

constexpr int kFlagLines = kTiles * 16;

constexpr unsigned kSpinLimit = 1u << 22;

__device__ __align__(1024) uint8_t g_x[16 * 16 * kTileBytes];
__device__ __align__(1024) uint8_t g_o[16 * 16 * kTileBytes];
__device__ __align__(1024) uint8_t g_h[16 * 56 * kTileBytes];
__device__ __align__(128) uint2 g_stat[4 * 16 * 128 * 8];
__device__ __align__(128) unsigned g_cs[3 * kD + kF];
__device__ __align__(128) uint4 g_halo[2 * 16 * 16 * 256];
__device__ __align__(128) unsigned g_flag[kFlagLines * 32];
__device__ unsigned g_ticket;

#define TRACE_AT(tile, k)
#define TRACE_PUB(i, k, c)
#define TRACE_ISSUE(which, nb)

struct Params {
  const __nv_bfloat16* x;
  const __nv_bfloat16* wqkv;
  const __nv_bfloat16* wo;
  const __nv_bfloat16* w1;
  const __nv_bfloat16* b1;
  const __nv_bfloat16* w2;
  const __nv_bfloat16* b2;
  uint32_t seg[kSegs];
};

__device__ __forceinline__ uint32_t smem_u32(const void* p) {
  return (uint32_t)__cvta_generic_to_shared(p);
}
__device__ __forceinline__ uint32_t mapa(uint32_t a, uint32_t cta) {
  uint32_t r;
  asm("mapa.shared::cluster.u32 %0, %1, %2;" : "=r"(r) : "r"(a), "r"(cta));
  return r;
}
__device__ __forceinline__ void mbar_init(uint32_t bar, int cnt) {
  asm volatile("mbarrier.init.shared::cta.b64 [%0], %1;" ::"r"(bar), "r"(cnt) : "memory");
}
__device__ __forceinline__ void mbar_expect_tx(uint32_t bar, uint32_t bytes) {
  asm volatile("mbarrier.arrive.expect_tx.shared::cta.b64 _, [%0], %1;" ::"r"(bar), "r"(bytes) : "memory");
}
__device__ __forceinline__ void mbar_arrive(uint32_t bar) {
  asm volatile("mbarrier.arrive.shared::cta.b64 _, [%0];" ::"r"(bar) : "memory");
}
__device__ __forceinline__ void mbar_arrive_cluster(uint32_t cluster_addr) {
  asm volatile("mbarrier.arrive.shared::cluster.b64 _, [%0];" ::"r"(cluster_addr) : "memory");
}
__device__ __forceinline__ void mbar_wait(uint32_t bar, uint32_t parity) {
  asm volatile(
      "{\n.reg .pred p;\n.reg .u32 c;\n"
      "mbarrier.try_wait.parity.shared::cta.b64 p, [%0], %1;\n"
      "@p bra.uni DONE;\n"
      "mov.u32 c, 0;\n"
      "RETRY:\n"
      "mbarrier.try_wait.parity.shared::cta.b64 p, [%0], %1;\n"
      "@p bra.uni DONE;\n"
      "add.u32 c, c, 1;\n"
      "setp.lt.u32 p, c, %2;\n"
      "@p bra.uni RETRY;\n"
      "trap;\n"
      "DONE:\n}" ::"r"(bar), "r"(parity), "n"(1u << 19)
      : "memory");
}
__device__ __forceinline__ void tma3d(uint32_t dst, const CUtensorMap* m, uint32_t bar, int c0, int c1, int c2) {
  asm volatile(
      "cp.async.bulk.tensor.3d.shared::cluster.global.mbarrier::complete_tx::bytes [%0], [%1, {%3, %4, %5}], [%2];"
      ::"r"(dst), "l"(m), "r"(bar), "r"(c0), "r"(c1), "r"(c2) : "memory");
}
__device__ __forceinline__ void tma3d_mc(uint32_t dst, const CUtensorMap* m, uint32_t bar, int c0, int c1, int c2) {
  asm volatile(
      "cp.async.bulk.tensor.3d.shared::cluster.global.mbarrier::complete_tx::bytes.multicast::cluster"
      " [%0], [%1, {%3, %4, %5}], [%2], %6;"
      ::"r"(dst), "l"(m), "r"(bar), "r"(c0), "r"(c1), "r"(c2), "h"((uint16_t)3) : "memory");
}
__device__ __forceinline__ void tma2d(uint32_t dst, const CUtensorMap* m, uint32_t bar, int c0, int c1) {
  asm volatile(
      "cp.async.bulk.tensor.2d.shared::cluster.global.mbarrier::complete_tx::bytes [%0], [%1, {%3, %4}], [%2];"
      ::"r"(dst), "l"(m), "r"(bar), "r"(c0), "r"(c1) : "memory");
}
__device__ __forceinline__ void tma2d_store(const CUtensorMap* m, uint32_t src, int c0, int c1) {
  asm volatile("cp.async.bulk.tensor.2d.global.shared::cta.bulk_group [%0, {%2, %3}], [%1];"
               ::"l"(m), "r"(src), "r"(c0), "r"(c1) : "memory");
}
__device__ __forceinline__ bool elect() {
  uint32_t p;
  asm volatile("{\n.reg .pred p;\nelect.sync _|p, 0xffffffff;\nselp.b32 %0, 1, 0, p;\n}" : "=r"(p));
  return p;
}
__device__ __forceinline__ void bulk_load(uint32_t dst, const void* src, uint32_t bytes, uint32_t bar) {
  asm volatile("cp.async.bulk.shared::cluster.global.mbarrier::complete_tx::bytes [%0], [%1], %2, [%3];"
               ::"r"(dst), "l"(src), "r"(bytes), "r"(bar) : "memory");
}
__device__ __forceinline__ void bulk_store(void* dst, uint32_t src, uint32_t bytes) {
  asm volatile("cp.async.bulk.global.shared::cta.bulk_group [%0], [%1], %2;" ::"l"(dst), "r"(src), "r"(bytes)
               : "memory");
}
__device__ __forceinline__ void bulk_commit() { asm volatile("cp.async.bulk.commit_group;" ::: "memory"); }
__device__ __forceinline__ void bulk_wait_read() { asm volatile("cp.async.bulk.wait_group.read 0;" ::: "memory"); }
__device__ __forceinline__ void bulk_wait() { asm volatile("cp.async.bulk.wait_group 0;" ::: "memory"); }
__device__ __forceinline__ void l2_prefetch(const void* p, uint32_t bytes) {
  asm volatile("cp.async.bulk.prefetch.L2.global [%0], %1;" ::"l"(p), "r"(bytes) : "memory");
}
__device__ __forceinline__ void fence_async_smem() { asm volatile("fence.proxy.async.shared::cta;" ::: "memory"); }
__device__ __forceinline__ unsigned ld_relaxed(const unsigned* p) {
  unsigned v;
  asm volatile("ld.relaxed.gpu.global.u32 %0, [%1];" : "=r"(v) : "l"(p) : "memory");
  return v;
}
__device__ __forceinline__ uint2 ld_relaxed2(const uint2* p) {
  uint2 v;
  asm volatile("ld.relaxed.gpu.global.v2.u32 {%0, %1}, [%2];" : "=r"(v.x), "=r"(v.y) : "l"(p) : "memory");
  return v;
}
__device__ __forceinline__ void st_relaxed(unsigned* p, unsigned v) {
  asm volatile("st.relaxed.gpu.global.u32 [%0], %1;" ::"l"(p), "r"(v) : "memory");
}
__device__ __forceinline__ void st_release(unsigned* p, unsigned v) {
  asm volatile("st.release.gpu.global.u32 [%0], %1;" ::"l"(p), "r"(v) : "memory");
}
#define ACQ_MODE 1
__device__ __forceinline__ void wait_flags(const unsigned* p, unsigned epoch) {
  unsigned spins = 0;
  while (true) {
    const unsigned v = ld_relaxed(p);
    if (__all_sync(0xffffffffu, v == epoch)) break;
    if (++spins > kSpinLimit) __trap();
  }
  if (ACQ_MODE) asm volatile("fence.acquire.gpu;\nfence.proxy.async.global;" ::: "memory");
  __syncwarp();
}
__device__ __forceinline__ void st_packet(uint4* p, uint32_t d0, uint32_t d1, uint32_t tag) {
  asm volatile("{\n.reg .b128 v;\n.reg .b64 x, y;\nmov.b64 x, {%1, %2};\nmov.b64 y, {%3, %3};\nmov.b128 v, {x, y};\n"
               "st.relaxed.gpu.global.b128 [%0], v;\n}" ::"l"(p), "r"(d0), "r"(d1), "r"(tag) : "memory");
}
__device__ __forceinline__ void ld_packet(const uint4* p, uint32_t& d0, uint32_t& d1, uint32_t& tag) {
  asm volatile("{\n.reg .b128 v;\n.reg .b64 x, y;\n.reg .b32 u;\nld.relaxed.gpu.global.b128 v, [%3];\n"
               "mov.b128 {x, y}, v;\nmov.b64 {%0, %1}, x;\nmov.b64 {%2, u}, y;\n}"
               : "=r"(d0), "=r"(d1), "=r"(tag) : "l"(p) : "memory");
}
__device__ __forceinline__ unsigned tag_value(float v, unsigned epoch) {
  return (__float_as_uint(v) & ~7u) | (epoch & 7u);
}
__device__ __forceinline__ float untag_value(unsigned v) { return __uint_as_float(v & ~7u); }
__device__ __forceinline__ void stsm4(uint32_t a, uint32_t r0, uint32_t r1, uint32_t r2, uint32_t r3) {
  asm volatile("stmatrix.sync.aligned.m8n8.x4.shared.b16 [%0], {%1, %2, %3, %4};" ::"r"(a), "r"(r0), "r"(r1),
               "r"(r2), "r"(r3) : "memory");
}
__device__ __forceinline__ void stsm4_t(uint32_t a, uint32_t r0, uint32_t r1, uint32_t r2, uint32_t r3) {
  asm volatile("stmatrix.sync.aligned.m8n8.x4.trans.shared.b16 [%0], {%1, %2, %3, %4};" ::"r"(a), "r"(r0),
               "r"(r1), "r"(r2), "r"(r3) : "memory");
}
__device__ __forceinline__ uint32_t transpose8(uint32_t a) {
  uint32_t d;
  asm volatile("movmatrix.sync.aligned.m8n8.trans.b16 %0, %1;" : "=r"(d) : "r"(a));
  return d;
}
__device__ __forceinline__ void mma16816(float (&c)[4], uint32_t a0, uint32_t a1, uint32_t a2, uint32_t a3,
                                         uint32_t b0, uint32_t b1) {
  asm volatile("mma.sync.aligned.m16n8k16.row.col.f32.bf16.bf16.f32 {%0, %1, %2, %3}, {%4, %5, %6, %7}, {%8, %9}, "
               "{%0, %1, %2, %3};"
               : "+f"(c[0]), "+f"(c[1]), "+f"(c[2]), "+f"(c[3])
               : "r"(a0), "r"(a1), "r"(a2), "r"(a3), "r"(b0), "r"(b1));
}
__device__ __forceinline__ void mma1688(float (&c)[4], uint32_t a0, uint32_t a1, uint32_t b0) {
  asm volatile("mma.sync.aligned.m16n8k8.row.col.f32.bf16.bf16.f32 {%0, %1, %2, %3}, {%4, %5}, {%6}, {%0, %1, %2, %3};"
               : "+f"(c[0]), "+f"(c[1]), "+f"(c[2]), "+f"(c[3]) : "r"(a0), "r"(a1), "r"(b0));
}
__device__ __forceinline__ float shfl_xor(float v, int m) {
  float r;
  asm volatile("shfl.sync.bfly.b32 %0, %1, %2, 31, 0xffffffff;" : "=f"(r) : "f"(v), "r"(m));
  return r;
}
__device__ __forceinline__ float tanh_fast(float x) {
  float r;
  asm volatile("tanh.approx.f32 %0, %1;" : "=f"(r) : "f"(x));
  return r;
}
__device__ __forceinline__ void ldsm4(uint32_t a, uint32_t (&r)[4]) {
  asm volatile("ldmatrix.sync.aligned.m8n8.x4.shared.b16 {%0, %1, %2, %3}, [%4];"
               : "=r"(r[0]), "=r"(r[1]), "=r"(r[2]), "=r"(r[3]) : "r"(a) : "memory");
}
__device__ __forceinline__ void ldsm4_t(uint32_t a, uint32_t (&r)[4]) {
  asm volatile("ldmatrix.sync.aligned.m8n8.x4.trans.shared.b16 {%0, %1, %2, %3}, [%4];"
               : "=r"(r[0]), "=r"(r[1]), "=r"(r[2]), "=r"(r[3]) : "r"(a) : "memory");
}
__device__ __forceinline__ uint32_t pack2(float lo, float hi) {
  uint32_t r;
  asm volatile("cvt.rn.bf16x2.f32 %0, %1, %2;" : "=r"(r) : "f"(hi), "f"(lo));
  return r;
}
__device__ __forceinline__ float bf_lo(uint32_t r) { return __uint_as_float(r << 16); }
__device__ __forceinline__ float bf_hi(uint32_t r) { return __uint_as_float(r & 0xffff0000u); }
__device__ __forceinline__ float ex2(float x) {
  float r;
  asm("ex2.approx.ftz.f32 %0, %1;" : "=f"(r) : "f"(x));
  return r;
}
__device__ __forceinline__ float rcp(float x) {
  float r;
  asm("rcp.approx.ftz.f32 %0, %1;" : "=f"(r) : "f"(x));
  return r;
}
template <int N>
__device__ __forceinline__ void wg_wait() {
  asm volatile("wgmma.wait_group.sync.aligned %0;" ::"n"(N) : "memory");
}
__device__ __forceinline__ void yield_slot() { asm volatile("pmevent 0;"); }
__device__ __forceinline__ void wg_bar(int wg) { asm volatile("bar.sync %0, 128;" ::"r"(wg + 1) : "memory"); }

template <int N, int KIND>
__device__ __forceinline__ void mma_kblock(float (&acc)[2][96], uint32_t a, uint32_t b);

#define F8(m, d, i) m(d[i]), m(d[i + 1]), m(d[i + 2]), m(d[i + 3]), m(d[i + 4]), m(d[i + 5]), m(d[i + 6]), m(d[i + 7])
#define KSTEP(N, A, B, oa0, oa1, ob, sd)                                                   \
  "add.u32 t, " B ", " #ob ";\nmov.b64 db, {t, hb};\n"                                      \
  "add.u32 t, " A ", " #oa0 ";\nmov.b64 da, {t, ha};\n"                                     \
  "wgmma.mma_async.sync.aligned.m64n" #N "k16.f32.bf16.bf16 {" ACC##N##_0 "}, da, db, " #sd ", 1, 1, 0, 1;\n" \
  "add.u32 t, " A ", " #oa1 ";\nmov.b64 da, {t, ha};\n"                                     \
  "wgmma.mma_async.sync.aligned.m64n" #N "k16.f32.bf16.bf16 {" ACC##N##_1 "}, da, db, " #sd ", 1, 1, 0, 1;\n"

#define MMA_KBLOCK(N, KIND, A, B, ob2, ob3, sd, MID, MODE)                                 \
  template <>                                                                              \
  __device__ __forceinline__ void mma_kblock<N, KIND>(float (&acc)[2][96], uint32_t a, uint32_t b) { \
    asm volatile("{\n.reg .b32 t, ha, hb;\n.reg .b64 da, db;\n"                            \
                 "mov.b32 ha, 0x40000080;\nmov.b32 hb, 0x40000040;\n"                       \
                 "wgmma.fence.sync.aligned;\n"                                             \
                 KSTEP(N, A, B, 0, 64, 0, sd) KSTEP(N, A, B, 2, 66, 128, 1) KSTEP(N, A, B, 4, 68, ob2, 1) \
                 MID KSTEP(N, A, B, 6, 70, ob3, 1) "wgmma.commit_group.sync.aligned;\n}\n"  \
                 : OPS##N(MODE) : "r"(a), "r"(b) : "memory");                              \
  }
#define MMA_KBLOCKS(N, A, B, ob2, ob3)                                                     \
  MMA_KBLOCK(N, 0, A, B, ob2, ob3, 1, "", "+f")                                            \
  MMA_KBLOCK(N, 1, A, B, ob2, ob3, 1, "wgmma.commit_group.sync.aligned;\n", "+f")          \
  MMA_KBLOCK(N, 2, A, B, ob2, ob3, 0, "", "=f")

#define ACC128_0 \
  "%0, %1, %2, %3, %4, %5, %6, %7, %8, %9, %10, %11, %12, %13, %14, %15, " \
  "%16, %17, %18, %19, %20, %21, %22, %23, %24, %25, %26, %27, %28, %29, %30, %31, " \
  "%32, %33, %34, %35, %36, %37, %38, %39, %40, %41, %42, %43, %44, %45, %46, %47, " \
  "%48, %49, %50, %51, %52, %53, %54, %55, %56, %57, %58, %59, %60, %61, %62, %63"
#define ACC128_1 \
  "%64, %65, %66, %67, %68, %69, %70, %71, %72, %73, %74, %75, %76, %77, %78, %79, " \
  "%80, %81, %82, %83, %84, %85, %86, %87, %88, %89, %90, %91, %92, %93, %94, %95, " \
  "%96, %97, %98, %99, %100, %101, %102, %103, %104, %105, %106, %107, %108, %109, %110, %111, " \
  "%112, %113, %114, %115, %116, %117, %118, %119, %120, %121, %122, %123, %124, %125, %126, %127"
#define OPS128(m) \
  F8(m, acc[0], 0), F8(m, acc[0], 8), F8(m, acc[0], 16), F8(m, acc[0], 24), F8(m, acc[0], 32), F8(m, acc[0], 40), F8(m, acc[0], 48), F8(m, acc[0], 56), \
        F8(m, acc[1], 0), F8(m, acc[1], 8), F8(m, acc[1], 16), F8(m, acc[1], 24), F8(m, acc[1], 32), F8(m, acc[1], 40), F8(m, acc[1], 48), F8(m, acc[1], 56)
MMA_KBLOCKS(128, "%128", "%129", 512, 640)

#define ACC192_0 \
  "%0, %1, %2, %3, %4, %5, %6, %7, %8, %9, %10, %11, %12, %13, %14, %15, " \
  "%16, %17, %18, %19, %20, %21, %22, %23, %24, %25, %26, %27, %28, %29, %30, %31, " \
  "%32, %33, %34, %35, %36, %37, %38, %39, %40, %41, %42, %43, %44, %45, %46, %47, " \
  "%48, %49, %50, %51, %52, %53, %54, %55, %56, %57, %58, %59, %60, %61, %62, %63, " \
  "%64, %65, %66, %67, %68, %69, %70, %71, %72, %73, %74, %75, %76, %77, %78, %79, " \
  "%80, %81, %82, %83, %84, %85, %86, %87, %88, %89, %90, %91, %92, %93, %94, %95"
#define ACC192_1 \
  "%96, %97, %98, %99, %100, %101, %102, %103, %104, %105, %106, %107, %108, %109, %110, %111, " \
  "%112, %113, %114, %115, %116, %117, %118, %119, %120, %121, %122, %123, %124, %125, %126, %127, " \
  "%128, %129, %130, %131, %132, %133, %134, %135, %136, %137, %138, %139, %140, %141, %142, %143, " \
  "%144, %145, %146, %147, %148, %149, %150, %151, %152, %153, %154, %155, %156, %157, %158, %159, " \
  "%160, %161, %162, %163, %164, %165, %166, %167, %168, %169, %170, %171, %172, %173, %174, %175, " \
  "%176, %177, %178, %179, %180, %181, %182, %183, %184, %185, %186, %187, %188, %189, %190, %191"
#define OPS192(m) \
  F8(m, acc[0], 0), F8(m, acc[0], 8), F8(m, acc[0], 16), F8(m, acc[0], 24), F8(m, acc[0], 32), F8(m, acc[0], 40), F8(m, acc[0], 48), F8(m, acc[0], 56), F8(m, acc[0], 64), F8(m, acc[0], 72), F8(m, acc[0], 80), F8(m, acc[0], 88), \
        F8(m, acc[1], 0), F8(m, acc[1], 8), F8(m, acc[1], 16), F8(m, acc[1], 24), F8(m, acc[1], 32), F8(m, acc[1], 40), F8(m, acc[1], 48), F8(m, acc[1], 56), F8(m, acc[1], 64), F8(m, acc[1], 72), F8(m, acc[1], 80), F8(m, acc[1], 88)
MMA_KBLOCKS(192, "%192", "%193", 768, 896)

#define TSTEP(REGS, W, X, ow, ox)                                                           \
  "add.u32 t, " X ", " #ox ";\nmov.b64 db, {t, hi};\nadd.u32 t, " W ", " #ow ";\nmov.b64 da, {t, hi};\n" \
  "wgmma.mma_async.sync.aligned.m64n128k16.f32.bf16.bf16 {" REGS "}, da, db, 1, 1, 1, 1, 0;\n"
#define THEAD "{\n.reg .b32 t, hi;\n.reg .b64 da, db;\nmov.b32 hi, 0x40000040;\nwgmma.fence.sync.aligned;\n"
#define TTAIL "wgmma.commit_group.sync.aligned;\n}\n"
__device__ __forceinline__ void mma_kblock_t(float (&acc)[2][96], uint32_t wd, uint32_t xd) {
  asm volatile(THEAD TSTEP(ACC128_0, "%128", "%129", 0, 0) TSTEP(ACC128_1, "%128", "%129", 256, 0)
               TSTEP(ACC128_0, "%128", "%129", 128, 2) TSTEP(ACC128_1, "%128", "%129", 384, 2)
               TSTEP(ACC128_0, "%128", "%129", 512, 4) TSTEP(ACC128_1, "%128", "%129", 768, 4)
               TSTEP(ACC128_0, "%128", "%129", 640, 6) TSTEP(ACC128_1, "%128", "%129", 896, 6) TTAIL
               : OPS128("+f") : "r"(wd), "r"(xd) : "memory");
}
__device__ __forceinline__ void mma_half_t(float (&d)[96], uint32_t wd, uint32_t xd) {
  asm volatile(THEAD TSTEP(ACC128_0, "%64", "%65", 0, 0) TSTEP(ACC128_0, "%64", "%65", 128, 2)
               TSTEP(ACC128_0, "%64", "%65", 512, 4) TSTEP(ACC128_0, "%64", "%65", 640, 6) TTAIL
               : F8("+f", d, 0), F8("+f", d, 8), F8("+f", d, 16), F8("+f", d, 24), F8("+f", d, 32), F8("+f", d, 40),
                 F8("+f", d, 48), F8("+f", d, 56) : "r"(wd), "r"(xd) : "memory");
}

enum { kModePlain = 0, kModeHead = 1, kModeSkip = 2, kModeContinue = 3 };

template <int N>
__device__ __forceinline__ void fence_acc(float (&acc)[2][96]) {
#pragma unroll
  for (int h = 0; h < 2; h++)
#pragma unroll
    for (int i = 0; i < N / 2; i++) asm volatile("" : "+f"(acc[h][i])::"memory");
}

template <int N>
__device__ __forceinline__ void zero_acc(float (&acc)[2][96]) {
#pragma unroll
  for (int h = 0; h < 2; h++)
#pragma unroll
    for (int i = 0; i < N / 2; i++) acc[h][i] = 0.f;
}

constexpr uint32_t kToB = (kTileBytes >> 4) + ((4096u >> 4) << 16) - (1u << 16);

#define TRACE_KB(nb)

#define HEAD_BOTH 0
template <int N>
__device__ __forceinline__ void head_blocks(float (&acc)[2][96], uint32_t sb, int n0, int slot, uint32_t xbar, uint32_t turn,
                                            uint32_t rel_addr, bool rel) {
  const uint32_t ring = (((sb & 0x3FFFF) + kSmRing) >> 4) | (1u << 16);
  const uint32_t xdesc = (((sb & 0x3FFFF) + kSmX) >> 4) | (1u << 16);
  const uint32_t nb = n0 * 8;
  mbar_wait(xbar + 8 * HEAD_BOTH, 0);
  mbar_wait(turn, 0);
  mbar_wait(sb + kBarFull + (nb & 56), nb >> 6);
  TRACE_KB(nb);
  mma_kblock<N, 2>(acc, xdesc, ring + slot * 2560 + kToB);
  mbar_wait(xbar + 8, 0);
  mbar_wait(sb + kBarFull + (nb & 56) + 8, nb >> 6);
  TRACE_KB(nb + 8);
  mma_kblock<N, 0>(acc, xdesc + (kTileBytes >> 4), ring + ((slot + 1) & 3) * 2560 + kToB);
  wg_wait<1>();
  if (rel) mbar_arrive_cluster(rel_addr + (nb & 56));
  wg_wait<0>();
  if (rel) mbar_arrive_cluster(rel_addr + (nb & 56) + 8);
  fence_acc<N>(acc);
}

template <int N, bool RESID, class Pre>
__device__ __forceinline__ void mainloop(float (&acc)[2][96], uint32_t sb, int tile, int n0, int slot, int nkb,
                                         int pause_kk, int att, uint32_t rel_addr, bool rel, uint32_t prev, int own_kk,
                                         Pre pre) {
  constexpr uint32_t kStep = (N == 192 ? 5 : 4) * 512;
  const uint32_t ring = (((sb & 0x3FFFF) + kSmRing) >> 4) | (1u << 16);
  uint32_t st = ring + slot * kStep;
  uint32_t nb = n0 * 8;
  const uint32_t last = nb + 8 * (nkb - (RESID ? 3 : 1)), own = nb + 8 * own_kk;
  const uint32_t stg = (((sb & 0x3FFFF) + kSmStg) >> 4) | (1u << 16);
  uint32_t stop = pause_kk >= 0 ? nb + 8 * pause_kk : last;
  const bool signal = (threadIdx.x & 127) == 64;
  fence_acc<N>(acc);
  if (tile > 0) mbar_wait(sb + kBarTurn + (tile - 1) * 8, 0);
  TRACE_AT(tile, 0);
#pragma unroll 1
  while (true) {
#pragma unroll 1
    do {
      mbar_wait(sb + kBarFull + (nb & 56), nb >> 6);
      if (nb == n0 * 8) TRACE_AT(tile, 1);
      TRACE_KB(nb);
      if constexpr (RESID) mma_kblock_t(acc, st + kToB, nb == own ? stg : st);
      else mma_kblock<N, 0>(acc, st, st + kToB);
      wg_wait<1>();
      if (rel) mbar_arrive_cluster(rel_addr + prev);
      prev = nb & 56;
      st += kStep;
      if (st == ring + 10240) st = ring;
      nb += 8;
    } while (nb != stop);
    if (stop == last) break;
    stop = last;
    if (signal) mbar_arrive(sb + kBarPause + att * 8);
    wg_wait<0>();
    if (rel) mbar_arrive_cluster(rel_addr + prev);
    prev = 64;
    mbar_wait(sb + kBarResume + att * 8, 0);
  }
  mbar_wait(sb + kBarFull + (nb & 56), nb >> 6);
  TRACE_KB(nb);
  if constexpr (RESID) {
    const uint32_t z = gridDim.y - 1;
    const uint32_t s2 = st + kStep, s3 = s2 == ring + 8192 ? ring : s2 + kStep;
    mma_half_t(acc[0], st + kToB, st);
    wg_wait<1>();
    if (rel) mbar_arrive_cluster(rel_addr + 32);
    mbar_wait(sb + kBarFull + 48, nb >> 6);
    TRACE_KB(nb + 8);
    mma_half_t(acc[0], s2 + kToB, s2);
    mbar_wait(sb + kBarFull + 56, nb >> 6);
    TRACE_KB(nb + 16);
    mma_half_t(acc[0], s3 + kToB, s3);
    mma_half_t(acc[1], st + kToB + 256, st + z);
    mma_half_t(acc[1], s2 + kToB + 256, s2 + z);
    wg_wait<2>();
#pragma unroll
    for (int i = 0; i < 64; i++) asm volatile("" : "+f"(acc[0][i])::"memory");
    pre(0);
    mma_half_t(acc[1], s3 + kToB + 256, s3 + z);
    wg_wait<2>();
    if (rel) mbar_arrive_cluster(rel_addr + 40);
    pre(1);
    wg_wait<1>();
    if (rel) mbar_arrive_cluster(rel_addr + 48);
    if (signal) mbar_arrive(sb + kBarTurn + tile * 8);
    wg_wait<0>();
    if (rel) mbar_arrive_cluster(rel_addr + 56);
#pragma unroll
    for (int i = 0; i < 64; i++) asm volatile("" : "+f"(acc[1][i])::"memory");
  } else {
    mma_kblock<N, 1>(acc, st, st + kToB);
    wg_wait<2>();
    if (rel) mbar_arrive_cluster(rel_addr + prev);
    pre();
    wg_wait<1>();
    if (signal) mbar_arrive(sb + kBarTurn + tile * 8);
    wg_wait<0>();
    if (rel) mbar_arrive_cluster(rel_addr + (nb & 56));
    fence_acc<N>(acc);
  }
}

__device__ __forceinline__ void publish_stats(uint32_t sb, uint2* stat, int w, int lane, unsigned epoch) {
  const uint32_t row = sb + kSmX + (32 * w + lane) * 128;
  float s[4], q[4];
#pragma unroll
  for (int c = 0; c < 4; c++) s[c] = q[c] = 0.f;
  uint32_t nx[4];
  ldsm4(row + ((lane & 7) << 4), nx);
#pragma unroll 1
  for (int J = 1; J <= 16; J++) {
    const uint32_t r[4] = {nx[0], nx[1], nx[2], nx[3]};
    ldsm4(row + ((J >> 3) & 1) * kTileBytes + (((J ^ lane) & 7) << 4), nx);
#pragma unroll
    for (int c = 0; c < 4; c++) {
      const float lo = bf_lo(r[c]);
      s[c] += lo;
      q[c] = fmaf(lo, lo, q[c]);
      if (c & 1) yield_slot();
    }
#pragma unroll
    for (int c = 0; c < 4; c++) {
      const float hi = bf_hi(r[c]);
      s[c] += hi;
      q[c] = fmaf(hi, hi, q[c]);
      if (c & 1) yield_slot();
    }
  }
#pragma unroll
  for (int c = 0; c < 4; c++) {
    s[c] += shfl_xor(s[c], 1);
    q[c] += shfl_xor(q[c], 1);
    s[c] += shfl_xor(s[c], 2);
    q[c] += shfl_xor(q[c], 2);
  }
  const int t = lane & 3, g = lane >> 2;
  const float so = t == 0 ? s[0] : t == 1 ? s[1] : t == 2 ? s[2] : s[3];
  const float qo = t == 0 ? q[0] : t == 1 ? q[1] : t == 2 ? q[2] : q[3];
  asm volatile("st.relaxed.gpu.global.v2.u32 [%0], {%1, %2};" ::"l"(stat + 32 * w + 8 * t + g),
               "r"(tag_value(so, epoch)), "r"(tag_value(qo, epoch)) : "memory");
}

__device__ __forceinline__ void add_chunk(float (&a)[8], const uint4& v) {
  a[0] += bf_lo(v.x); a[1] += bf_hi(v.x);
  a[2] += bf_lo(v.y); a[3] += bf_hi(v.y);
  a[4] += bf_lo(v.z); a[5] += bf_hi(v.z);
  a[6] += bf_lo(v.w); a[7] += bf_hi(v.w);
}

__device__ __forceinline__ int helper_col(int id, int slab) {
  return slab < 6 ? (slab % 3) * kD + (slab / 3) * 512 + id * 128 : (slab - 6) * 512 + id * 128;
}
__device__ __forceinline__ void helper_cta(const CUtensorMap* map_q, const CUtensorMap* map_1, uint8_t* sm,
                                           uint32_t sb, int id, int warp) {
  constexpr int kRed = 6 * 32768, kBar = kRed + 2 * 4096;
  const int tid = threadIdx.x;
  if (warp == 8 && elect()) {
#pragma unroll
    for (int s = 0; s < 6; s++) {
      mbar_init(sb + kBar + s * 8, 1);
      mbar_init(sb + kBar + 64 + s * 8, 4);
    }
    fence_async_smem();
#pragma unroll
    for (int s = 0; s < 6; s++) {
      mbar_expect_tx(sb + kBar + s * 8, 32768);
      tma2d(sb + s * 32768, map_q, sb + kBar + s * 8, id * 128, s * 128);
    }
  }
  __syncthreads();
  if (warp == 8) {
    int slot = 0, ph = 0;
#pragma unroll 1
    for (int n = 6; n < 104; n++) {
      mbar_wait(sb + kBar + 64 + slot * 8, ph);
      if (elect()) {
        mbar_expect_tx(sb + kBar + slot * 8, 32768);
        tma2d(sb + slot * 32768, n < 48 ? map_q : map_1, sb + kBar + slot * 8, helper_col(id, n >> 3), (n & 7) * 128);
      }
      if (++slot == 6) slot = 0, ph ^= 1;
    }
  } else if (warp < 8) {
    if (tid == 0) *reinterpret_cast<unsigned*>(sm + kBar + 128) = atomicAdd(&g_ticket, 1u) / kGrid + 1;
    int slot = warp >> 2, ph = 0;
#pragma unroll 1
    for (int slab = 0; slab < 13; slab++) {
      float a[8];
#pragma unroll
      for (int e = 0; e < 8; e++) a[e] = 0.f;
#pragma unroll 1
      for (int box = 0; box < 4; box++) {
        mbar_wait(sb + kBar + slot * 8, ph);
        const uint4* p = reinterpret_cast<const uint4*>(sm + slot * 32768) + (tid & 127);
        uint4 v[16];
#pragma unroll
        for (int i = 0; i < 16; i++) v[i] = p[i * 128];
        __syncwarp();
        if (elect()) mbar_arrive(sb + kBar + 64 + slot * 8);
#pragma unroll
        for (int i = 0; i < 16; i++) add_chunk(a, v[i]);
        slot += 2;
        if (slot >= 6) slot -= 6, ph ^= 1;
      }
      float* red = reinterpret_cast<float*>(sm + kRed + (slab & 1) * 4096);
#pragma unroll
      for (int e = 0; e < 8; e++) a[e] += shfl_xor(a[e], 16);
      if ((tid & 16) == 0) {
        float4* d = reinterpret_cast<float4*>(red + warp * 128 + (tid & 15) * 8);
        d[0] = make_float4(a[0], a[1], a[2], a[3]);
        d[1] = make_float4(a[4], a[5], a[6], a[7]);
      }
      asm volatile("bar.sync 1, 256;" ::: "memory");
      if (warp < 4) {
        float t = 0.f;
#pragma unroll
        for (int q = 0; q < 8; q++) t += red[q * 128 + tid];
        st_relaxed(g_cs + (slab < 6 ? 0 : 3 * kD) + helper_col(id, slab) + tid,
                   tag_value(t, *reinterpret_cast<volatile unsigned*>(sm + kBar + 128)));
      }
    }
  }
}

constexpr float kGeluBeta = 0.3292034911525734f;
constexpr float kGeluK = 2.423681954311584f;

__device__ __forceinline__ void store_staged(uint8_t* dst, uint32_t stg) {
  fence_async_smem();
  __syncwarp();
  if (elect()) {
    bulk_store(dst, stg, 4096);
    bulk_commit();
  }
}

#define GY_MASK 0x3F
#define GY_MASK2 0x3f
#define GY(k) if (((CH == 2 ? GY_MASK2 : GY_MASK) >> k) & 1) yield_slot()
template <int CH>
__device__ __forceinline__ void gelu_chunk(const float (&acc)[2][96], const float2 (&st)[4], const float4* vec,
                                           uint32_t stg, int lane, bool chained, uint8_t* prev, uint32_t free_bar) {
  uint32_t pk[8][4];
  float u[3][4], z[3][4];
  float4 v = vec[CH * 32], vn = v;
#pragma unroll
  for (int s = 0; s < 18; s++) {
    const int J = CH * 8 + (s >> 1), c0 = 2 * (s & 1), cur = s % 3, p1 = (s + 2) % 3, p2 = (s + 1) % 3;
    if (s < 16) {
      if (c0 == 0 && s < 14) vn = vec[(J + 1) * 4];
#pragma unroll
      for (int e = 0; e < 4; e++) {
        const int c = c0 + (e >> 1);
        z[cur][e] = fmaf(st[c].y, e & 1 ? v.y : v.x, e & 1 ? v.w : v.z);
      }
      if (c0 == 2) v = vn;
    }
    if (s >= 1 && s < 17) z[p1][0] = tanh_fast(z[p1][0]);
    GY(0);
    if (s < 16) {
#pragma unroll
      for (int e = 0; e < 4; e++) {
        const int c = c0 + (e >> 1);
        u[cur][e] = fmaf(acc[c & 1][4 * J + c0 + (e & 1)], st[c].x, z[cur][e]);
      }
    }
    if (s >= 1 && s < 17) z[p1][1] = tanh_fast(z[p1][1]);
    GY(1);
    if (s >= 11) {
      const int jj = s - 11;
      stsm4(stg + lane * 128 + ((jj ^ (lane & 7)) << 4), pk[jj][0], pk[jj][1], pk[jj][2], pk[jj][3]);
    }
    if (s < 16) {
#pragma unroll
      for (int e = 0; e < 4; e++) z[cur][e] = fmaf(u[cur][e], u[cur][e], kGeluK);
    }
    if (s >= 1 && s < 17) z[p1][2] = tanh_fast(z[p1][2]);
    GY(3);
    if (s >= 2) {
      pk[(s - 2) >> 1][c0] = pack2(fmaf(u[p2][0], z[p2][0], u[p2][0]), fmaf(u[p2][1], z[p2][1], u[p2][1]));
      pk[(s - 2) >> 1][c0 + 1] = pack2(fmaf(u[p2][2], z[p2][2], u[p2][2]), fmaf(u[p2][3], z[p2][3], u[p2][3]));
    }
    GY(4);
    if (s < 16) {
#pragma unroll
      for (int e = 0; e < 4; e++) z[cur][e] = u[cur][e] * z[cur][e];
    }
    if (s >= 1 && s < 17) z[p1][3] = tanh_fast(z[p1][3]);
    GY(5);
    if (CH < 2 && s == 1 && chained) store_staged(prev, stg);
    if (CH < 2 && s == 10) {
      if (chained) {
        if (elect()) bulk_wait();
        __syncwarp();
      } else {
        mbar_wait(free_bar, 0);
      }
    }
  }
  stsm4(stg + lane * 128 + ((7 ^ (lane & 7)) << 4), pk[7][0], pk[7][1], pk[7][2], pk[7][3]);
}

__device__ __forceinline__ void scale_stats(float2 (&st)[4]) {
#pragma unroll
  for (int c = 0; c < 4; c++) {
    st[c].x *= kGeluBeta;
    st[c].y *= st[c].x;
  }
}

__device__ __forceinline__ void add_mean_term(float (&acc)[2][96], const float2 (&st)[4], uint8_t* sm, int tq,
                                              int lane) {
  const float2* cs = reinterpret_cast<const float2*>(sm + kSmCsQ) + tq * 96 + (lane & 3);
  float2 vn = cs[0];
#pragma unroll
  for (int J = 0; J < 24; J++) {
    const float2 v = vn;
    if (J < 23) vn = cs[J * 4 + 4];
#pragma unroll
    for (int c = 0; c < 4; c++) {
      acc[c & 1][4 * J + (c & 2)] = fmaf(st[c].y, v.x, acc[c & 1][4 * J + (c & 2)]);
      acc[c & 1][4 * J + (c & 2) + 1] = fmaf(st[c].y, v.y, acc[c & 1][4 * J + (c & 2) + 1]);
    }
    yield_slot();
  }
}

#define TWO_PART 0
#define RESUME_LATE 0
#define HALO_AT 2
__device__ __forceinline__ void epilogue_attn(const float (&acc)[2][96], const float2 (&st)[4], uint8_t* sm,
                                              uint32_t sb, int layer, int tq, int b, int j, unsigned epoch, int tile,
                                              int wg, int w) {
  const int lane = threadIdx.x & 31, t = lane & 3, g = lane >> 2;
  const int hp = j + 8 * tq, att = 2 * layer + tq;
  uint32_t q[4][8], k[5][8], vt[5][8];
#define SCALED(c, J) pack2(acc[(c) & 1][4 * (J) + ((c) & 2)] * st[c].x, acc[(c) & 1][4 * (J) + ((c) & 2) + 1] * st[c].x)
#pragma unroll
  for (int J = 0; J < 8; J++) vt[4][J] = transpose8(SCALED(3, 16 + J));
#pragma unroll
  for (int J = 0; J < 8; J++) k[4][J] = SCALED(3, 8 + J);
  if (w < 3) {
    uint2* hs = reinterpret_cast<uint2*>(sm + kSmHalo + w * 2048) + lane;
#pragma unroll
    for (int i = 0; i < 4; i++) {
      hs[i * 32] = make_uint2(k[4][2 * i], k[4][2 * i + 1]);
      hs[128 + i * 32] = make_uint2(vt[4][2 * i], vt[4][2 * i + 1]);
    }
  } else if ((b & 7) != 7) {
    uint4* gh = g_halo + ((layer * 16 + b) * 16 + hp) * 256 + lane;
#pragma unroll
    for (int i = 0; i < 4; i++) {
      st_packet(gh + i * 32, k[4][2 * i], k[4][2 * i + 1], epoch);
      st_packet(gh + 128 + i * 32, vt[4][2 * i], vt[4][2 * i + 1], epoch);
    }
  }
#pragma unroll
  for (int c = 0; c < 3; c++)
#pragma unroll
    for (int J = 0; J < 8; J++) {
      k[c + 1][J] = SCALED(c, 8 + J);
      vt[c + 1][J] = transpose8(SCALED(c, 16 + J));
      yield_slot();
    }
  const bool first = w == 0 && (b & 7) == 0;
  const uint4* gh = g_halo + ((layer * 16 + b - 1) * 16 + hp) * 256 + lane;
  uint32_t tag[8];
#define LOAD_HALO()                                                                                    \
  _Pragma("unroll") for (int i = 0; i < 4; i++) {                                                      \
    ld_packet(gh + i * 32, k[0][2 * i], k[0][2 * i + 1], tag[i]);                                      \
    ld_packet(gh + 128 + i * 32, vt[0][2 * i], vt[0][2 * i + 1], tag[4 + i]);                          \
  }
#define AWAIT_HALO()                                                                                   \
  for (unsigned spins = 0;; spins++) {                                                                 \
    const unsigned d0 = (tag[0] ^ epoch) | (tag[1] ^ epoch) | (tag[2] ^ epoch) | (tag[3] ^ epoch);     \
    const unsigned d1 = (tag[4] ^ epoch) | (tag[5] ^ epoch) | (tag[6] ^ epoch) | (tag[7] ^ epoch);     \
    if (__all_sync(0xffffffffu, (d0 | d1) == 0)) break;                                                \
    if (spins > kSpinLimit) __trap();                                                                  \
    LOAD_HALO();                                                                                       \
  }
#pragma unroll
  for (int c = 0; c <= 4; c++) {
    if (c == HALO_AT) {
      if (w == 0 && !first) {
        LOAD_HALO();
      } else {
#pragma unroll
        for (int i = 0; i < 8; i++) k[0][i] = vt[0][i] = tag[i] = 0u;
      }
    }
#pragma unroll
    for (int J = 0; J < 8 && c < 4; J++) {
      q[c & 3][J] = SCALED(c & 3, J);
      if (J & 1) yield_slot();
    }
  }
#undef SCALED
  TRACE_AT(tile, 8);
  wg_bar(wg);
  if (w > 0) {
    const uint2* hs = reinterpret_cast<const uint2*>(sm + kSmHalo + (w - 1) * 2048) + lane;
#pragma unroll
    for (int i = 0; i < 4; i++) {
      const uint2 a = hs[i * 32], c = hs[128 + i * 32];
      k[0][2 * i] = a.x; k[0][2 * i + 1] = a.y;
      vt[0][2 * i] = c.x; vt[0][2 * i + 1] = c.y;
    }
  } else if (!first && tq == 0) {
    AWAIT_HALO();
  }
  constexpr float kScale = 0.17677669529663687f * 1.4426950408889634f;
  const bool own0 = 2 * t <= g, own1 = 2 * t + 1 <= g;
  const uint32_t own_mask = (own0 ? 0xffffu : 0u) | (own1 ? 0xffff0000u : 0u);
  const uint32_t stg = sb + kSmStg + w * 4096;
  const uint32_t orow = stg + (lane & 7) * 128, ochunk = (lane >> 3) ^ (lane & 7);
  TRACE_AT(tile, 9);
  mbar_wait(sb + kBarPause + att * 8, 0);
  TRACE_AT(tile, 10);

  float s[2][6][4], o[2][4][2][4];
  auto scores = [&](int hd, int m) {
    const int ca = 2 * (m / 3), kg = ca + m % 3;
#pragma unroll
    for (int e = 0; e < 4; e++) s[hd][m][e] = 0.f;
#pragma unroll
    for (int J = 4 * hd; J < 4 * hd + 4; J += 2)
      mma16816(s[hd][m], q[ca][J], q[ca + 1][J], q[ca][J + 1], q[ca + 1][J + 1], k[kg][J], k[kg][J + 1]);
  };
  auto attend = [&](int c0, int c1) {
    float v0[2][4], v1[2][4], m[2][4];
#define UNITS _Pragma("unroll") for (int hd = 0; hd < 2; hd++) _Pragma("unroll") for (int c = c0; c < c1; c++)
    UNITS {
      const int mp = 3 * (c >> 1) + (c & 1), r = 2 * (c & 1);
      float p0 = s[hd][mp][r], p1 = s[hd][mp][r + 1];
      if (c == 0 && first) p0 = p1 = -INFINITY;
      v0[hd][c] = own0 ? s[hd][mp + 1][r] : p0;
      v1[hd][c] = own1 ? s[hd][mp + 1][r + 1] : p1;
      m[hd][c] = fmaxf(v0[hd][c], v1[hd][c]);
    }
    UNITS m[hd][c] = fmaxf(m[hd][c], shfl_xor(m[hd][c], 1));
    UNITS m[hd][c] = fmaxf(m[hd][c], shfl_xor(m[hd][c], 2));
    UNITS {
      const float nm = -m[hd][c] * kScale;
      v0[hd][c] = ex2(fmaf(v0[hd][c], kScale, nm));
      v1[hd][c] = ex2(fmaf(v1[hd][c], kScale, nm));
      m[hd][c] = v0[hd][c] + v1[hd][c];
    }
    UNITS m[hd][c] += shfl_xor(m[hd][c], 1);
    UNITS m[hd][c] += shfl_xor(m[hd][c], 2);
    UNITS {
      const float inv = rcp(m[hd][c]);
      const uint32_t p = pack2(v0[hd][c] * inv, v1[hd][c] * inv);
#pragma unroll
      for (int ds = 0; ds < 2; ds++) {
        const int J = 4 * hd + 2 * ds;
#pragma unroll
        for (int e = 0; e < 4; e++) o[hd][c][ds][e] = 0.f;
        if (c & 1) {
          mma16816(o[hd][c][ds], vt[c][J], vt[c][J + 1], vt[c + 1][J], vt[c + 1][J + 1], p & ~own_mask, p & own_mask);
        } else {
          mma1688(o[hd][c][ds], vt[c + 1][J], vt[c + 1][J + 1], p & own_mask);
          mma1688(o[hd][c][ds], vt[c][J], vt[c][J + 1], p & ~own_mask);
        }
      }
    }
  };
  auto stage = [&](int c0, int c1) {
    UNITS stsm4_t(orow + c * 1024 + ((ochunk ^ (4 * hd)) << 4), pack2(o[hd][c][0][0], o[hd][c][0][1]),
                  pack2(o[hd][c][0][2], o[hd][c][0][3]), pack2(o[hd][c][1][0], o[hd][c][1][1]),
                  pack2(o[hd][c][1][2], o[hd][c][1][3]));
#undef UNITS
  };
  if (w == 0 && !first) AWAIT_HALO();
#pragma unroll
  for (int hd = 0; hd < 2; hd++)
#pragma unroll
    for (int m = 0; m < 6; m++) scores(hd, m);
  attend(0, 4);
  yield_slot();
  if (tq == 0 && elect()) mbar_arrive(sb + kBarResume + att * 8);
  TRACE_AT(tile, 11);
  stage(0, 4);
#undef AWAIT_HALO
#undef LOAD_HALO
  fence_async_smem();
  __syncwarp();
  TRACE_AT(tile, 12);
  if (elect()) {
    bulk_store(g_o + (b * 16 + hp) * kTileBytes + w * 4096, stg, 4096);
    bulk_commit();
    if (tq == 1 && !RESUME_LATE) mbar_arrive(sb + kBarResume + att * 8);
    bulk_wait();
    if (tq == 1 && RESUME_LATE) mbar_arrive(sb + kBarResume + att * 8);
    TRACE_AT(tile, 13);
    mbar_arrive(sb + kBarEpi + tile * 8);
  }
  __syncwarp();
}

__device__ __forceinline__ void gather_stats(uint8_t* sm, const uint2* stat, unsigned epoch) {
  const int r = threadIdx.x & 127;
  uint2 a[8];
  unsigned spins = 0;
  while (true) {
    unsigned diff = 0;
#pragma unroll
    for (int i = 0; i < 8; i++) {
      a[i] = ld_relaxed2(stat + i * 128 + r);
      diff |= (a[i].x ^ epoch) | (a[i].y ^ epoch);
    }
    if (__all_sync(0xffffffffu, (diff & 7u) == 0)) break;
    if (++spins > kSpinLimit) __trap();
    __nanosleep(200);
  }
  float s = 0.f, q = 0.f;
#pragma unroll
  for (int i = 0; i < 8; i++) {
    s += untag_value(a[i].x);
    q += untag_value(a[i].y);
  }
  const float mean = s * (1.f / 1024.f);
  const float var = fmaxf(fmaf(-mean, mean, q * (1.f / 1024.f)), 0.f);
  reinterpret_cast<float2*>(sm + kSmStat)[r] = make_float2(rsqrtf(var + 1e-5f), -mean);
}

__device__ __forceinline__ void gather_colsums(uint8_t* sm, int part, int j, int lane, unsigned epoch) {
#pragma unroll 1
  for (int blk = part < 4 ? 0 : 2 * part - 5; blk < (part < 4 ? 3 : 2 * part - 3); blk++) {
    const int col = part < 2 ? blk * kD + (j + 8 * part) * 64
                             : 3 * kD + 64 * (blk + (blk < 3 ? 3 * j : blk < 5 ? 21 + 2 * j : 35 + 2 * j));
    uint2 v;
    unsigned spins = 0;
    while (true) {
      v = ld_relaxed2(reinterpret_cast<const uint2*>(g_cs + col) + lane);
      if (__all_sync(0xffffffffu, (((v.x ^ epoch) | (v.y ^ epoch)) & 7u) == 0)) break;
      if (++spins > kSpinLimit) __trap();
      __nanosleep(100);
    }
    uint8_t* dst = part < 2 ? sm + kSmCsQ + (part * 96 + blk * 32 + lane) * 8 : sm + kSmV1 + (blk * 32 + lane) * 16;
    *reinterpret_cast<float2*>(dst) = make_float2(untag_value(v.x), untag_value(v.y));
  }
}

#define READBACK 0
#define PF_START 0
#define PAUSE_QKV2 7
#define PAUSE_WO 1

__global__ void __cluster_dims__(2, 1, 1) __launch_bounds__(384, 1)
fused_layers_kernel(const __grid_constant__ CUtensorMap map_x, const __grid_constant__ CUtensorMap map_out,
                    const __grid_constant__ CUtensorMap map_qkv, const __grid_constant__ CUtensorMap map_wo,
                    const __grid_constant__ CUtensorMap map_w1a, const __grid_constant__ CUtensorMap map_w1b,
                    const __grid_constant__ CUtensorMap map_w2, const __grid_constant__ CUtensorMap map_csq,
                    const __grid_constant__ CUtensorMap map_cs1, const __grid_constant__ Params prm) {
  extern __shared__ __align__(1024) uint8_t sm[];
  if (threadIdx.x < 128 && blockIdx.x < kCtas) TRACE_AT(15, 1);
  const uint32_t sb = __shfl_sync(0xffffffffu, smem_u32(sm), 0);
  const int warp = __shfl_sync(0xffffffffu, threadIdx.x >> 5, 0), lane = threadIdx.x & 31;
  const int cta = blockIdx.x, rank = cta & 1, cl = cta >> 1;
  const int grp = cl < 4 ? 0 : cl < 36 ? (cl - 4) & 7 : 1 + (cl - 36) % 7;
  const int j = cl < 4 ? 4 + cl : cl < 36 ? (cl - 4) >> 3 : 4 + (cl - 36) / 7;
  const int b = 2 * grp + rank;
  const int xcol = (b >> 3) * kD, xrow = (b & 7) * 128;

  if (cta >= kCtas) {
    helper_cta(&map_csq, &map_cs1, sm, sb, cta - kCtas, warp);
    return;
  }
  if (warp >= 8 && elect()) {
    if (warp == 9) {
#pragma unroll
      for (int s = 0; s < 8; s++) mbar_init(sb + kBarFull + s * 8, 1);
      fence_async_smem();
#pragma unroll
      for (int s = 0; s < 4; s++) {
        const uint32_t full = sb + kBarFull + s * 8, dst = sb + kSmRing + s * 40960;
        mbar_expect_tx(full, 40960);
        tma2d(dst, &map_x, full, xcol + s * 64, xrow);
        tma3d(dst + kTileBytes, &map_qkv, full, j * 64, s * 64, 0);
        tma3d(dst + kTileBytes + 12288, &map_qkv, full, j * 64, s * 64 + 32, 0);
      }
      if (PF_START & 1) l2_prefetch(reinterpret_cast<const uint8_t*>(prm.x) + cta * 32768, 32768);
      if (PF_START & 2) l2_prefetch(reinterpret_cast<const uint8_t*>(prm.wqkv) + cta * 49152, 49152);
    } else if (warp == 8) {
      if (sb & 1023) __trap();
#pragma unroll
      for (int o = kBarTurn; o < kBarInit; o += 8) mbar_init(sb + o, 1);
    } else if (warp == 10) {
#pragma unroll
      for (int o = kBarEpoch; o < kSmEpoch; o += 8) mbar_init(sb + o, o < kBarEmpty ? 1 : o < kBarEpi ? 2 : 4);
    } else {
      mbar_init(sb + kBarInit, 1);
      fence_async_smem();
      mbar_expect_tx(sb + kBarInit, 32768);
      tma2d(sb + kSmX, &map_x, sb + kBarInit, xcol + j * 128, xrow);
      tma2d(sb + kSmX + kTileBytes, &map_x, sb + kBarInit, xcol + j * 128 + 64, xrow);
    }
    asm volatile("fence.mbarrier_init.release.cluster;" ::: "memory");
  }
  __syncwarp();
  asm volatile("barrier.cluster.arrive.relaxed.aligned;" ::: "memory");

  if (warp >= 8) {
    asm volatile("setmaxnreg.dec.sync.aligned.u32 40;");
    if (warp < 10) {
      asm volatile("barrier.cluster.wait.aligned;" ::: "memory");
      uint32_t nb = 32, off = 0, kb = 0;
#define RING_STEP(ISSUE)                                                  \
  do {                                                                    \
    const uint32_t mb = nb - depth, full = sb + kBarFull + (nb & 56);     \
    if (kb == skip) kb += inc;                                            \
    mbar_wait(sb + kBarEmpty + (mb & 56), mb >> 6);                       \
    if (elect()) { ISSUE; }                                               \
    TRACE_ISSUE(9 - warp, nb);                                            \
    kb += inc;                                                            \
    off = off == wrap ? 0 : off + step;                                   \
    nb += 8;                                                              \
  } while (nb != nend)
#pragma unroll 1
      for (int sg = 0; sg < kSegs; sg++) {
        const uint32_t e = prm.seg[sg];
        const int ty = e & 7, mode = (e >> 15) & 3, reset = (e >> 24) & 3;
        const uint32_t nend = nb + (e & 0x1f8);
        const uint32_t step = (e >> 17) & 1 ? 40960 : 32768, wrap = 163840 - step;
        const uint32_t depth = (e >> 18) & 1 ? 40 : 32;
        if (reset) off = reset == 1 ? 0 : reset == 2 ? 40960 : 131072;
        const uint32_t own = ty == 2 ? 8 + j : 2 * j;
        if (mode != kModeContinue) kb = mode == kModeHead ? own : (e >> 9) & 63;
        const uint32_t inc = mode >= kModeSkip && ty != 2 ? 2 : 1, skip = mode >= kModeSkip ? own + (kb & 1) : 255;
        if (warp == 8) {
          const CUtensorMap* map = ty < 2 ? &map_qkv : ty == 2 ? &map_wo : ty == 3 ? &map_w1a : ty < 6 ? &map_w1b : &map_w2;
          const int c0 = ty < 2 ? (j + 8 * ty) * 64 : 0;
          const int c2 = ty < 2 ? 0 : ty == 3 ? 3 * j : ty == 4 ? 24 + 2 * j : ty == 5 ? 40 + 2 * j : 2 * j;
          const uint32_t half = (ty < 2 || ty == 3) ? 12288 : 8192;
          const uint32_t bytes = 2 * half + (mode == kModeHead ? 0 : kTileBytes);
          const uint32_t dst = sb + kSmRing + kTileBytes + rank * half;
#pragma unroll 1
          RING_STEP(mbar_expect_tx(full, bytes); tma3d_mc(dst + off, map, full, c0, kb * 64 + rank * 32, c2));
        } else if (mode == kModeHead) {
          off += ((nend - nb) >> 3) * step;
          nb = nend;
          if (off >= 163840) off -= 163840;
        } else if (sg < 2) {
#pragma unroll 1
          RING_STEP(tma2d(sb + kSmRing + off, &map_x, full, xcol + kb * 64, xrow));
        } else {
          const uint8_t* src = ty == 6 ? g_h + b * 56 * kTileBytes : (ty == 2 ? g_o : g_x) + b * 16 * kTileBytes;
          const int dep = (e >> 19) & 31;
          if (dep != 31) mbar_wait(sb + kBarReady + dep * 8, 0);
#pragma unroll 1
          RING_STEP(bulk_load(sb + kSmRing + off, src + kb * kTileBytes, kTileBytes, full));
        }
      }
#undef RING_STEP
    } else if (warp == 10) {
      unsigned epoch = 0;
      if (lane == 0) epoch = atomicAdd(&g_ticket, 1u) / kGrid + 1;
      epoch = __shfl_sync(0xffffffffu, epoch, 0);
      *reinterpret_cast<unsigned*>(sm + kSmEpoch) = epoch;
      asm volatile("barrier.cluster.wait.aligned;" ::: "memory");
      if (elect()) mbar_arrive(sb + kBarEpoch);
#pragma unroll 1
      for (int i = 0; i < kTiles - 1; i++) {
        const bool xt = i == 2 || i == 6 || i == 9;
        const unsigned* line = g_flag + (i * 16 + b) * 32;
        mbar_wait(sb + (xt ? kBarX + (i >> 2) * 16 : kBarEpi + i * 8), 0);
        wait_flags(line + (lane & 7), epoch);
        if (elect()) mbar_arrive(sb + kBarReady + i * 8);
        if (xt) {
          wait_flags(line + 8 + (lane & 7), epoch);
          if (elect()) mbar_arrive(sb + kBarReady + (14 + (i >> 2)) * 8);
        }
      }
    } else {
      {
        uint32_t v[7];
#pragma unroll
        for (int q = 0; q < 7; q++)
          v[q] = reinterpret_cast<const uint32_t*>(prm.b1)[32 * (q + (q < 3 ? 3 * j : q < 5 ? 21 + 2 * j : 35 + 2 * j)) + lane];
        const uint2 u = reinterpret_cast<const uint2*>(prm.b2)[32 * j + lane];
#pragma unroll
        for (int q = 0; q < 7; q++)
          *reinterpret_cast<float2*>(sm + kSmV1 + (q * 32 + lane) * 16 + 8) = make_float2(kGeluBeta * bf_lo(v[q]), kGeluBeta * bf_hi(v[q]));
        reinterpret_cast<float4*>(sm + kSmB2)[lane] = make_float4(
            2.f * kGeluBeta * bf_lo(u.x), 2.f * kGeluBeta * bf_hi(u.x), 2.f * kGeluBeta * bf_lo(u.y), 2.f * kGeluBeta * bf_hi(u.y));
      }
      asm volatile("barrier.cluster.wait.aligned;" ::: "memory");
      mbar_wait(sb + kBarEpoch, 0);
      const unsigned epoch = *reinterpret_cast<volatile unsigned*>(sm + kSmEpoch);
#pragma unroll 1
      for (int i = 0; i < kTiles - 1; i++) {
#pragma unroll 1
        for (int part = i == 4 ? 5 : i; part < (i < 2 ? i + 1 : i == 3 || i == 4 ? i + 2 : 0); part++) {
          gather_colsums(sm, part, j, lane, epoch);
          __syncwarp();
          if (elect()) mbar_arrive(sb + kBarCs + part * 8);
        }
        const bool xt = i == 2 || i == 6 || i == 9;
#pragma unroll 1
        for (int h = 0; h < (xt ? 2 : 1); h++) {
          mbar_wait(sb + (xt ? kBarX + (i >> 2) * 16 + 8 * h : kBarEpi + i * 8), 0);
          const int ty = i >= 7 ? i - 7 : i;
          if (ty >= 2 && elect()) {
            uint8_t* dst = xt ? g_x + (b * 16 + 2 * j + h) * kTileBytes
                              : g_h + (b * 56 + 1 + (ty == 3 ? 3 * j : 16 * ty - 40 + 2 * j)) * kTileBytes;
            bulk_store(dst, sb + (xt ? kSmX + h * kTileBytes : kSmStg), kTileBytes);
            bulk_commit();
            bulk_wait();
            mbar_arrive(sb + kBarFree + i * 8);
          }
          __syncwarp();
          if (elect()) st_release(&g_flag[(i * 16 + b) * 32 + h * 8 + j], epoch);
          __syncwarp();
        }
      }
#pragma unroll 1
      for (int h = 0; h < 2; h++) {
        mbar_wait(sb + kBarX + 48 + 8 * h, 0);
        if (elect()) {
          tma2d_store(&map_out, sb + kSmX + h * kTileBytes, xcol + j * 128 + h * 64, xrow);
          bulk_commit();
          if (h == 1) bulk_wait_read();
        }
      }
    }
    __syncwarp();
    asm volatile("barrier.cluster.arrive.relaxed.aligned;\nbarrier.cluster.wait.aligned;" ::: "memory");
  } else {
    asm volatile("setmaxnreg.inc.sync.aligned.u32 232;");
    asm volatile("barrier.cluster.wait.aligned;" ::: "memory");
    const int wg = warp >> 2, w = warp & 3;
    const bool rel = (threadIdx.x & 95) == 0;
    const uint32_t rel_addr = mapa(sb + kBarEmpty, w & 1);
    if (wg == 1) TRACE_AT(15, 0);
#define EPOCH (*reinterpret_cast<volatile unsigned*>(sm + kSmEpoch))

    if (wg == 1) {
      mbar_wait(sb + kBarEpoch, 0);
      mbar_wait(sb + kBarInit, 0);
    }

#pragma unroll 1
    for (int i = wg; i < kTiles; i += 2) {
      const int layer = i >= 7, ty = i - 7 * layer;
      TRACE_AT(i, 15);
      float acc[2][96];
      if (ty == 2 || ty == 6) {
        const uint32_t xa = sb + kSmX + ((lane >> 4) * 8 + (lane & 7)) * 128 + (((2 * w + ((lane >> 3) & 1)) ^ (lane & 7)) << 4);
        const float up = ty == 6 ? 2.f * kGeluBeta : 1.f, dn = ty == 6 ? 0.5f / kGeluBeta : 1.f;
#pragma unroll
        for (int h = 0; h < 2; h++) {
          const float* b2 = reinterpret_cast<const float*>(sm + kSmB2) + 64 * h + 16 * w + (lane >> 2);
          const float bias[2] = {ty == 6 ? b2[0] : 0.f, ty == 6 ? b2[8] : 0.f};
#pragma unroll
          for (int p = 0; p < 8; p++) {
            uint32_t r[4];
            ldsm4_t(xa + h * kTileBytes + p * 2048, r);
#pragma unroll
            for (int m = 0; m < 4; m++) {
              acc[h][8 * p + 2 * m] = fmaf(bf_lo(r[m]), up, bias[m & 1]);
              acc[h][8 * p + 2 * m + 1] = fmaf(bf_hi(r[m]), up, bias[m & 1]);
              asm volatile("" : "+f"(acc[h][8 * p + 2 * m]), "+f"(acc[h][8 * p + 2 * m + 1]));
              if (m & 1) yield_slot();
            }
          }
        }
        auto stage = [&](int qt) {
          const int h = qt >> 1;
#pragma unroll
          for (int p = 4 * (qt & 1); p < 4 * (qt & 1) + 4; p++) {
            const float* a = &acc[h][8 * p];
            stsm4_t(xa + h * kTileBytes + p * 2048, pack2(a[0] * dn, a[1] * dn), pack2(a[2] * dn, a[3] * dn),
                    pack2(a[4] * dn, a[5] * dn), pack2(a[6] * dn, a[7] * dn));
            yield_slot();
          }
          if (qt & 1) {
            fence_async_smem();
            __syncwarp();
            if (elect()) mbar_arrive(sb + kBarX + (i >> 2) * 16 + 8 * h);
            TRACE_AT(i, 8 + h);
          }
        };
        mainloop<128, true>(acc, sb, i, layer * 152 + ty * 16, ty == 6 ? 4 : 0, ty == 6 ? 56 : 16,
                            ty == 2 ? PAUSE_WO : -1, 2 * layer + 1, rel_addr, rel, 64, ty == 2 ? 8 : -1, stage);
        TRACE_AT(i, 2);
        stage(2);
        stage(3);
      } else {
        const int xver = 2 * layer + (ty >= 3);
        const uint32_t stg = sb + kSmStg + w * 4096;
        const float4* vec = reinterpret_cast<const float4*>(sm + kSmV1) + (ty == 3 ? 0 : 64 * ty - 160) + (lane & 3);
        uint8_t* hdst = g_h + (b * 56 + (ty == 3 ? 3 * j : 16 * ty - 40 + 2 * j)) * kTileBytes + w * 4096;
        float2 st[4];
        unsigned epoch;
        auto pre = [&] {
          if (ty < 4) mbar_wait(sb + (ty == 1 ? kBarEpi + (i - 1) * 8 : kBarStat + xver * 8), 0);
#pragma unroll
          for (int c = 0; c < 4; c++) st[c] = reinterpret_cast<const float2*>(sm + kSmStat)[32 * w + 8 * c + (lane >> 2)];
          epoch = EPOCH;
        };
        if (ty == 5) {
          const uint32_t nb = (layer * 152 + 80) * 8, s0 = ((((sb & 0x3FFFF) + kSmRing) >> 4) | (1u << 16)) + 3 * 2048;
          mbar_wait(sb + kBarTurn + (i - 1) * 8, 0);
          mbar_wait(sb + kBarFull, nb >> 6);
          TRACE_KB(nb);
          mma_kblock<128, 2>(acc, s0, s0 + kToB);
        } else {
          if (i < 2) {
            zero_acc<192>(acc);
          } else {
            const int n0 = layer * 152 + (ty < 2 ? 2 * ty : 42 + 2 * ty), slot = ty < 2 ? 2 * ty : 2 * ty - 5;
            if (ty < 4) {
              head_blocks<192>(acc, sb, n0, slot, sb + kBarX + (xver - 1) * 16,
                               sb + kBarTurn + (xver == 1 ? 2 : 3 * xver) * 8, rel_addr, rel);
            } else {
              head_blocks<128>(acc, sb, n0, slot, sb + kBarX + (xver - 1) * 16,
                               sb + kBarTurn + (xver == 1 ? 2 : 3 * xver) * 8, rel_addr, rel);
#pragma unroll
              for (int q = 64; q < 96; q++) acc[0][q] = acc[1][q] = 0.f;
            }
          }
          if (ty == 1 || ty == 4) {
            uint2* stat = g_stat + (xver * 16 + b) * 1024;
            publish_stats(sb, stat + j * 128, w, lane, EPOCH);
            gather_stats(sm, stat, EPOCH);
            __syncwarp();
            if (elect()) mbar_arrive(sb + kBarStat + xver * 8);
            TRACE_AT(i, 14);
            if (i == 8) {
#pragma unroll
              for (int c = 0; c < 4; c++) st[c] = reinterpret_cast<const float2*>(sm + kSmStat)[32 * w + 8 * c + (lane >> 2)];
              add_mean_term(acc, st, sm, 1, lane);
            }
          }
          if (ty < 4) {
            mainloop<192, false>(acc, sb, i, i < 2 ? 16 * i : layer * 152 + (ty < 2 ? 4 + 14 * ty : 52), i == 8 ? 2 : ty == 3,
                          i < 2 ? 16 : 14, ty == 1 ? PAUSE_QKV2 : -1, xver, rel_addr, rel, 64, 0, pre);
            TRACE_AT(i, 2);
            if (layer == 0) mbar_wait(sb + kBarCs + ty * 8, 0);
            if (ty < 2) {
              if (i != 8) add_mean_term(acc, st, sm, ty, lane);
              epilogue_attn(acc, st, sm, sb, layer, ty, b, j, epoch, i, wg, w);
              goto tile_done;
            }
            scale_stats(st);
            gelu_chunk<2>(acc, st, vec, stg, lane, false, nullptr, 0);
            goto common_chunks;
          }
        }
        mainloop<128, false>(acc, sb, i, layer * 152 + 6 + 15 * ty, 4, ty + 10, -1, 0, rel_addr, rel, ty == 5 ? 0 : 64, 0, pre);
        TRACE_AT(i, 2);
        if (layer == 0) mbar_wait(sb + kBarCs + ty * 8, 0);
        scale_stats(st);
      common_chunks:
        TRACE_AT(i, 8);
        gelu_chunk<0>(acc, st, vec, stg, lane, ty == 3, hdst + 2 * kTileBytes, sb + kBarFree + (i - 1) * 8);
        TRACE_AT(i, 9);
        gelu_chunk<1>(acc, st, vec, stg, lane, true, hdst, 0);
        TRACE_AT(i, 10);
        fence_async_smem();
        __syncwarp();
        if (elect()) mbar_arrive(sb + kBarEpi + i * 8);
      }
    tile_done:
      TRACE_AT(i, 3);
    }
#undef EPOCH
    asm volatile("barrier.cluster.arrive.relaxed.aligned;\nbarrier.cluster.wait.aligned;" ::: "memory");
    if (wg == 1) TRACE_AT(15, 2);
  }
}

void build_segments(uint32_t* seg) {
  int n = 0;
  auto add = [&](int ty, int cnt, int kb0, int mode, int wide, int depth5, int dep, int reset) {
    seg[n++] = ty | cnt << 3 | kb0 << 9 | mode << 15 | wide << 17 | depth5 << 18 | dep << 19 | reset << 24;
  };
  for (int l = 0; l < 2; l++) {
    const int t = 7 * l;
    if (l == 0) {
      add(0, 12, 4, kModePlain, 1, 0, 31, 1);
      add(1, 16, 0, kModePlain, 1, 0, 31, 0);
    } else {
      add(0, 2, 0, kModeHead, 1, 0, 31, 1);
      add(1, 2, 0, kModeHead, 1, 0, 31, 0);
      add(0, 7, 0, kModeSkip, 1, 0, 6, 0);
      add(0, 7, 1, kModeSkip, 1, 0, 15, 0);
      add(1, 7, 0, kModeSkip, 1, 0, 31, 0);
      add(1, 7, 1, kModeSkip, 1, 0, 31, 0);
    }
    add(2, 4, 0, kModePlain, 0, 0, t, 1);
    add(2, 4, 4, kModePlain, 0, 1, 31, 0);
    add(2, 1, 0, kModeHead, 0, 1, 31, 0);
    add(2, 7, 8, kModeSkip, 0, 1, t + 1, 0);
    add(3, 2, 0, kModeHead, 1, 0, 31, 2);
    add(4, 2, 0, kModeHead, 1, 0, 31, 0);
    add(3, 7, 0, kModeSkip, 1, 0, t + 2, 0);
    add(3, 7, 1, kModeSkip, 1, 0, 14 + 2 * l, 0);
    add(4, 4, 0, kModeSkip, 0, 0, 31, 3);
    add(4, 3, 0, kModeContinue, 0, 1, 31, 0);
    add(4, 7, 1, kModeSkip, 0, 1, 31, 0);
    add(5, 16, 0, kModePlain, 0, 1, 31, 0);
    add(6, 24, 0, kModePlain, 0, 1, t + 3, 0);
    add(6, 16, 24, kModePlain, 0, 1, t + 4, 0);
    add(6, 16, 40, kModePlain, 0, 1, t + 5, 0);
  }
}

typedef CUresult (*EncodeTiledFn)(CUtensorMap*, CUtensorMapDataType, cuuint32_t, void*, const cuuint64_t*,
                                  const cuuint64_t*, const cuuint32_t*, const cuuint32_t*, CUtensorMapInterleave,
                                  CUtensorMapSwizzle, CUtensorMapL2promotion, CUtensorMapFloatOOBfill);

CUtensorMap make_map(EncodeTiledFn enc, const void* p, int rank, const cuuint64_t* dims, const cuuint64_t* strides,
                     const cuuint32_t* box, CUtensorMapSwizzle swizzle = CU_TENSOR_MAP_SWIZZLE_128B) {
  CUtensorMap m;
  const cuuint32_t es[5] = {1, 1, 1, 1, 1};
  enc(&m, CU_TENSOR_MAP_DATA_TYPE_BFLOAT16, rank, const_cast<void*>(p), dims, strides, box, es,
      CU_TENSOR_MAP_INTERLEAVE_NONE, swizzle, CU_TENSOR_MAP_L2_PROMOTION_L2_128B,
      CU_TENSOR_MAP_FLOAT_OOB_FILL_NONE);
  return m;
}

CUtensorMap weight_map(EncodeTiledFn enc, const void* p, int k, int n, int blocks) {
  const cuuint64_t dims[3] = {64, (cuuint64_t)k, (cuuint64_t)n / 64};
  const cuuint64_t strides[2] = {(cuuint64_t)n * 2, 128};
  const cuuint32_t box[3] = {64, 32, (cuuint32_t)blocks};
  return make_map(enc, p, 3, dims, strides, box);
}

CUtensorMap slab_map(EncodeTiledFn enc, const void* p, int n) {
  const cuuint64_t dims[2] = {(cuuint64_t)n, kD};
  const cuuint64_t strides[1] = {(cuuint64_t)n * 2};
  const cuuint32_t box[2] = {128, 128};
  return make_map(enc, p, 2, dims, strides, box, CU_TENSOR_MAP_SWIZZLE_NONE);
}

CUtensorMap token_map(EncodeTiledFn enc, const void* p, int rows) {
  const cuuint64_t dims[2] = {2 * kD, 1024};
  const cuuint64_t strides[1] = {4 * kD};
  const cuuint32_t box[2] = {64, (cuuint32_t)rows};
  return make_map(enc, p, 2, dims, strides, box);
}

}

extern "C" void kernel_launch(void* const* d_in, const int* in_sizes, int n_in, void* d_out, int out_size) {
  (void)in_sizes; (void)n_in; (void)out_size;
  static EncodeTiledFn enc = nullptr;
  if (!enc) {
    void* fn = nullptr;
    cudaDriverEntryPointQueryResult q;
    cudaGetDriverEntryPoint("cuTensorMapEncodeTiled", &fn, cudaEnableDefault, &q);
    enc = (EncodeTiledFn)fn;
    cudaFuncSetAttribute(fused_layers_kernel, cudaFuncAttributeMaxDynamicSharedMemorySize, kSmBytes);
  }
  Params prm;
  prm.x = (const __nv_bfloat16*)d_in[0];
  prm.wqkv = (const __nv_bfloat16*)d_in[1];
  prm.wo = (const __nv_bfloat16*)d_in[2];
  prm.w1 = (const __nv_bfloat16*)d_in[4];
  prm.b1 = (const __nv_bfloat16*)d_in[5];
  prm.w2 = (const __nv_bfloat16*)d_in[6];
  prm.b2 = (const __nv_bfloat16*)d_in[7];
  build_segments(prm.seg);
  const cuuint64_t qd[3] = {kD, kD, 3}, qs[2] = {3 * kD * 2, kD * 2};
  const cuuint32_t qb[3] = {64, 32, 3};
  const CUtensorMap map_x = token_map(enc, d_in[0], 128);
  const CUtensorMap map_out = token_map(enc, d_out, 128);
  const CUtensorMap map_qkv = make_map(enc, prm.wqkv, 3, qd, qs, qb);
  const CUtensorMap map_wo = weight_map(enc, prm.wo, kD, kD, 2);
  const CUtensorMap map_w1a = weight_map(enc, prm.w1, kD, kF, 3);
  const CUtensorMap map_w1b = weight_map(enc, prm.w1, kD, kF, 2);
  const CUtensorMap map_w2 = weight_map(enc, prm.w2, kF, kD, 2);
  fused_layers_kernel<<<kGrid, 384, kSmBytes>>>(map_x, map_out, map_qkv, map_wo, map_w1a, map_w1b, map_w2,
                                                slab_map(enc, prm.wqkv, 3 * kD), slab_map(enc, prm.w1, kF), prm);
}
```

```cpp
#include <cuda.h>
#include <cuda_bf16.h>
#include <cuda_runtime.h>
#include <stdint.h>

namespace {

constexpr int kD = 1024;
constexpr int kF = 3584;
constexpr int kCtas = 128;
constexpr int kGrid = 132;
constexpr int kTiles = 14;
constexpr int kTileBytes = 16384;

constexpr int kSmRing = 0;
constexpr int kSmX = 163840;
constexpr int kSmStg = kSmX + 32768;
constexpr int kSmHalo = kSmStg + 16384;
constexpr int kSmCsQ = kSmHalo + 6144;
constexpr int kSmV1 = kSmCsQ + 384 * 4;
constexpr int kSmB2 = kSmV1 + 448 * 8;
constexpr int kSmStat = kSmB2 + 128 * 4;
constexpr int kSmBar = kSmStat + 128 * 8;
constexpr int kBarFull = kSmBar;
constexpr int kBarTurn = kBarFull + 8 * 8;
constexpr int kBarReady = kBarTurn + 14 * 8;
constexpr int kBarPause = kBarReady + 17 * 8;
constexpr int kBarFree = kBarPause + 4 * 8;
constexpr int kBarCs = kBarFree + 14 * 8;
constexpr int kBarInit = kBarCs + 6 * 8;
constexpr int kBarEpoch = kBarInit + 8;
constexpr int kBarEmpty = kBarEpoch + 8;
constexpr int kBarEpi = kBarEmpty + 9 * 8;
constexpr int kBarX = kBarEpi + 14 * 8;
constexpr int kBarStat = kBarX + 8 * 8;
constexpr int kBarResume = kBarStat + 4 * 8;
constexpr int kSmEpoch = kBarResume + 4 * 8;
constexpr int kSmBytes = kSmEpoch + 16;
constexpr int kSegs = 38;

constexpr int kFlagLines = kTiles * 16;

constexpr unsigned kSpinLimit = 1u << 22;

__device__ __align__(1024) uint8_t g_x[16 * 16 * kTileBytes];
__device__ __align__(1024) uint8_t g_o[16 * 16 * kTileBytes];
__device__ __align__(1024) uint8_t g_h[16 * 56 * kTileBytes];
__device__ __align__(128) uint2 g_stat[4 * 16 * 128 * 8];
__device__ __align__(128) unsigned g_cs[3 * kD + kF];
__device__ __align__(128) uint4 g_halo[2 * 16 * 16 * 256];
__device__ __align__(128) unsigned g_flag[kFlagLines * 32];
__device__ unsigned g_ticket;

#define TRACE_AT(tile, k)
#define TRACE_PUB(i, k, c)
#define TRACE_ISSUE(which, nb)

struct Params {
  const __nv_bfloat16* b1;
  const __nv_bfloat16* b2;
  uint32_t seg[kSegs];
};

__device__ __forceinline__ uint32_t smem_u32(const void* p) {
  return (uint32_t)__cvta_generic_to_shared(p);
}
__device__ __forceinline__ uint32_t mapa(uint32_t a, uint32_t cta) {
  uint32_t r;
  asm("mapa.shared::cluster.u32 %0, %1, %2;" : "=r"(r) : "r"(a), "r"(cta));
  return r;
}
__device__ __forceinline__ void mbar_init(uint32_t bar, int cnt) {
  asm volatile("mbarrier.init.shared::cta.b64 [%0], %1;" ::"r"(bar), "r"(cnt) : "memory");
}
__device__ __forceinline__ void mbar_expect_tx(uint32_t bar, uint32_t bytes) {
  asm volatile("mbarrier.arrive.expect_tx.shared::cta.b64 _, [%0], %1;" ::"r"(bar), "r"(bytes) : "memory");
}
__device__ __forceinline__ void mbar_arrive(uint32_t bar) {
  asm volatile("mbarrier.arrive.shared::cta.b64 _, [%0];" ::"r"(bar) : "memory");
}
__device__ __forceinline__ void mbar_arrive_cluster(uint32_t cluster_addr) {
  asm volatile("mbarrier.arrive.shared::cluster.b64 _, [%0];" ::"r"(cluster_addr) : "memory");
}
__device__ __forceinline__ void mbar_wait(uint32_t bar, uint32_t parity) {
  asm volatile(
      "{\n.reg .pred p;\n.reg .u32 c;\n"
      "mbarrier.try_wait.parity.shared::cta.b64 p, [%0], %1;\n"
      "@p bra.uni DONE;\n"
      "mov.u32 c, 0;\n"
      "RETRY:\n"
      "mbarrier.try_wait.parity.shared::cta.b64 p, [%0], %1;\n"
      "@p bra.uni DONE;\n"
      "add.u32 c, c, 1;\n"
      "setp.lt.u32 p, c, %2;\n"
      "@p bra.uni RETRY;\n"
      "trap;\n"
      "DONE:\n}" ::"r"(bar), "r"(parity), "n"(1u << 19)
      : "memory");
}
__device__ __forceinline__ void tma3d(uint32_t dst, const CUtensorMap* m, uint32_t bar, int c0, int c1, int c2) {
  asm volatile(
      "cp.async.bulk.tensor.3d.shared::cluster.global.mbarrier::complete_tx::bytes [%0], [%1, {%3, %4, %5}], [%2];"
      ::"r"(dst), "l"(m), "r"(bar), "r"(c0), "r"(c1), "r"(c2) : "memory");
}
__device__ __forceinline__ void tma3d_mc(uint32_t dst, const CUtensorMap* m, uint32_t bar, int c0, int c1, int c2) {
  asm volatile(
      "cp.async.bulk.tensor.3d.shared::cluster.global.mbarrier::complete_tx::bytes.multicast::cluster"
      " [%0], [%1, {%3, %4, %5}], [%2], %6;"
      ::"r"(dst), "l"(m), "r"(bar), "r"(c0), "r"(c1), "r"(c2), "h"((uint16_t)3) : "memory");
}
__device__ __forceinline__ void tma2d(uint32_t dst, const CUtensorMap* m, uint32_t bar, int c0, int c1) {
  asm volatile(
      "cp.async.bulk.tensor.2d.shared::cluster.global.mbarrier::complete_tx::bytes [%0], [%1, {%3, %4}], [%2];"
      ::"r"(dst), "l"(m), "r"(bar), "r"(c0), "r"(c1) : "memory");
}
__device__ __forceinline__ void tma2d_store(const CUtensorMap* m, uint32_t src, int c0, int c1) {
  asm volatile("cp.async.bulk.tensor.2d.global.shared::cta.bulk_group [%0, {%2, %3}], [%1];"
               ::"l"(m), "r"(src), "r"(c0), "r"(c1) : "memory");
}
__device__ __forceinline__ bool elect() {
  uint32_t p;
  asm volatile("{\n.reg .pred p;\nelect.sync _|p, 0xffffffff;\nselp.b32 %0, 1, 0, p;\n}" : "=r"(p));
  return p;
}
__device__ __forceinline__ void bulk_load(uint32_t dst, const void* src, uint32_t bytes, uint32_t bar) {
  asm volatile("cp.async.bulk.shared::cluster.global.mbarrier::complete_tx::bytes [%0], [%1], %2, [%3];"
               ::"r"(dst), "l"(src), "r"(bytes), "r"(bar) : "memory");
}
__device__ __forceinline__ void bulk_store(void* dst, uint32_t src, uint32_t bytes) {
  asm volatile("cp.async.bulk.global.shared::cta.bulk_group [%0], [%1], %2;" ::"l"(dst), "r"(src), "r"(bytes)
               : "memory");
}
__device__ __forceinline__ void bulk_commit() { asm volatile("cp.async.bulk.commit_group;" ::: "memory"); }
__device__ __forceinline__ void bulk_wait_read() { asm volatile("cp.async.bulk.wait_group.read 0;" ::: "memory"); }
__device__ __forceinline__ void bulk_wait() { asm volatile("cp.async.bulk.wait_group 0;" ::: "memory"); }
__device__ __forceinline__ void fence_async_smem() { asm volatile("fence.proxy.async.shared::cta;" ::: "memory"); }
__device__ __forceinline__ unsigned ld_relaxed(const unsigned* p) {
  unsigned v;
  asm volatile("ld.relaxed.gpu.global.u32 %0, [%1];" : "=r"(v) : "l"(p) : "memory");
  return v;
}
__device__ __forceinline__ uint2 ld_relaxed2(const uint2* p) {
  uint2 v;
  asm volatile("ld.relaxed.gpu.global.v2.u32 {%0, %1}, [%2];" : "=r"(v.x), "=r"(v.y) : "l"(p) : "memory");
  return v;
}
__device__ __forceinline__ void st_relaxed(unsigned* p, unsigned v) {
  asm volatile("st.relaxed.gpu.global.u32 [%0], %1;" ::"l"(p), "r"(v) : "memory");
}
__device__ __forceinline__ void st_release(unsigned* p, unsigned v) {
  asm volatile("st.release.gpu.global.u32 [%0], %1;" ::"l"(p), "r"(v) : "memory");
}
#define ACQ_MODE 1
__device__ __forceinline__ void wait_flags(const unsigned* p, unsigned epoch) {
  unsigned spins = 0;
  while (true) {
    const unsigned v = ld_relaxed(p);
    if (__all_sync(0xffffffffu, v == epoch)) break;
    if (++spins > kSpinLimit) __trap();
  }
  if (ACQ_MODE) asm volatile("fence.acquire.gpu;\nfence.proxy.async.global;" ::: "memory");
  __syncwarp();
}
__device__ __forceinline__ void st_packet(uint4* p, uint32_t d0, uint32_t d1, uint32_t tag) {
  asm volatile("{\n.reg .b128 v;\n.reg .b64 x, y;\nmov.b64 x, {%1, %2};\nmov.b64 y, {%3, %3};\nmov.b128 v, {x, y};\n"
               "st.relaxed.gpu.global.b128 [%0], v;\n}" ::"l"(p), "r"(d0), "r"(d1), "r"(tag) : "memory");
}
__device__ __forceinline__ void ld_packet(const uint4* p, uint32_t& d0, uint32_t& d1, uint32_t& tag) {
  asm volatile("{\n.reg .b128 v;\n.reg .b64 x, y;\n.reg .b32 u;\nld.relaxed.gpu.global.b128 v, [%3];\n"
               "mov.b128 {x, y}, v;\nmov.b64 {%0, %1}, x;\nmov.b64 {%2, u}, y;\n}"
               : "=r"(d0), "=r"(d1), "=r"(tag) : "l"(p) : "memory");
}
__device__ __forceinline__ unsigned tag_value(float v, unsigned epoch) {
  return (__float_as_uint(v) & ~7u) | (epoch & 7u);
}
__device__ __forceinline__ float untag_value(unsigned v) { return __uint_as_float(v & ~7u); }
__device__ __forceinline__ void stsm4(uint32_t a, uint32_t r0, uint32_t r1, uint32_t r2, uint32_t r3) {
  asm volatile("stmatrix.sync.aligned.m8n8.x4.shared.b16 [%0], {%1, %2, %3, %4};" ::"r"(a), "r"(r0), "r"(r1),
               "r"(r2), "r"(r3) : "memory");
}
__device__ __forceinline__ void stsm4_t(uint32_t a, uint32_t r0, uint32_t r1, uint32_t r2, uint32_t r3) {
  asm volatile("stmatrix.sync.aligned.m8n8.x4.trans.shared.b16 [%0], {%1, %2, %3, %4};" ::"r"(a), "r"(r0),
               "r"(r1), "r"(r2), "r"(r3) : "memory");
}
__device__ __forceinline__ uint32_t transpose8(uint32_t a) {
  uint32_t d;
  asm volatile("movmatrix.sync.aligned.m8n8.trans.b16 %0, %1;" : "=r"(d) : "r"(a));
  return d;
}
__device__ __forceinline__ void mma16816(float (&c)[4], uint32_t a0, uint32_t a1, uint32_t a2, uint32_t a3,
                                         uint32_t b0, uint32_t b1) {
  asm volatile("mma.sync.aligned.m16n8k16.row.col.f32.bf16.bf16.f32 {%0, %1, %2, %3}, {%4, %5, %6, %7}, {%8, %9}, "
               "{%0, %1, %2, %3};"
               : "+f"(c[0]), "+f"(c[1]), "+f"(c[2]), "+f"(c[3])
               : "r"(a0), "r"(a1), "r"(a2), "r"(a3), "r"(b0), "r"(b1));
}
__device__ __forceinline__ void mma1688(float (&c)[4], uint32_t a0, uint32_t a1, uint32_t b0) {
  asm volatile("mma.sync.aligned.m16n8k8.row.col.f32.bf16.bf16.f32 {%0, %1, %2, %3}, {%4, %5}, {%6}, {%0, %1, %2, %3};"
               : "+f"(c[0]), "+f"(c[1]), "+f"(c[2]), "+f"(c[3]) : "r"(a0), "r"(a1), "r"(b0));
}
__device__ __forceinline__ float shfl_xor(float v, int m) {
  float r;
  asm volatile("shfl.sync.bfly.b32 %0, %1, %2, 31, 0xffffffff;" : "=f"(r) : "f"(v), "r"(m));
  return r;
}
__device__ __forceinline__ float tanh_fast(float x) {
  float r;
  asm volatile("tanh.approx.f32 %0, %1;" : "=f"(r) : "f"(x));
  return r;
}
__device__ __forceinline__ void ldsm4(uint32_t a, uint32_t (&r)[4]) {
  asm volatile("ldmatrix.sync.aligned.m8n8.x4.shared.b16 {%0, %1, %2, %3}, [%4];"
               : "=r"(r[0]), "=r"(r[1]), "=r"(r[2]), "=r"(r[3]) : "r"(a) : "memory");
}
__device__ __forceinline__ void ldsm4_t(uint32_t a, uint32_t (&r)[4]) {
  asm volatile("ldmatrix.sync.aligned.m8n8.x4.trans.shared.b16 {%0, %1, %2, %3}, [%4];"
               : "=r"(r[0]), "=r"(r[1]), "=r"(r[2]), "=r"(r[3]) : "r"(a) : "memory");
}
__device__ __forceinline__ uint32_t pack2(float lo, float hi) {
  uint32_t r;
  asm volatile("cvt.rn.bf16x2.f32 %0, %1, %2;" : "=r"(r) : "f"(hi), "f"(lo));
  return r;
}
__device__ __forceinline__ float bf_lo(uint32_t r) { return __uint_as_float(r << 16); }
__device__ __forceinline__ float bf_hi(uint32_t r) { return __uint_as_float(r & 0xffff0000u); }
__device__ __forceinline__ float ex2(float x) {
  float r;
  asm("ex2.approx.ftz.f32 %0, %1;" : "=f"(r) : "f"(x));
  return r;
}
__device__ __forceinline__ float rcp(float x) {
  float r;
  asm("rcp.approx.ftz.f32 %0, %1;" : "=f"(r) : "f"(x));
  return r;
}
template <int N>
__device__ __forceinline__ void wg_wait() {
  asm volatile("wgmma.wait_group.sync.aligned %0;" ::"n"(N) : "memory");
}
__device__ __forceinline__ void yield_slot() { asm volatile("pmevent 0;"); }
__device__ __forceinline__ void wg_bar(int wg) { asm volatile("bar.sync %0, 128;" ::"r"(wg + 1) : "memory"); }

template <int N, int KIND>
__device__ __forceinline__ void mma_kblock(float (&acc)[2][96], uint32_t a, uint32_t b);

#define F8(m, d, i) m(d[i]), m(d[i + 1]), m(d[i + 2]), m(d[i + 3]), m(d[i + 4]), m(d[i + 5]), m(d[i + 6]), m(d[i + 7])
#define KSTEP(N, A, B, oa0, oa1, ob, sd)                                                   \
  "add.u32 t, " B ", " #ob ";\nmov.b64 db, {t, hb};\n"                                      \
  "add.u32 t, " A ", " #oa0 ";\nmov.b64 da, {t, ha};\n"                                     \
  "wgmma.mma_async.sync.aligned.m64n" #N "k16.f32.bf16.bf16 {" ACC##N##_0 "}, da, db, " #sd ", 1, 1, 0, 1;\n" \
  "add.u32 t, " A ", " #oa1 ";\nmov.b64 da, {t, ha};\n"                                     \
  "wgmma.mma_async.sync.aligned.m64n" #N "k16.f32.bf16.bf16 {" ACC##N##_1 "}, da, db, " #sd ", 1, 1, 0, 1;\n"

#define MMA_KBLOCK(N, KIND, A, B, ob2, ob3, sd, MID, MODE)                                 \
  template <>                                                                              \
  __device__ __forceinline__ void mma_kblock<N, KIND>(float (&acc)[2][96], uint32_t a, uint32_t b) { \
    asm volatile("{\n.reg .b32 t, ha, hb;\n.reg .b64 da, db;\n"                            \
                 "mov.b32 ha, 0x40000080;\nmov.b32 hb, 0x40000040;\n"                       \
                 "wgmma.fence.sync.aligned;\n"                                             \
                 KSTEP(N, A, B, 0, 64, 0, sd) KSTEP(N, A, B, 2, 66, 128, 1) KSTEP(N, A, B, 4, 68, ob2, 1) \
                 MID KSTEP(N, A, B, 6, 70, ob3, 1) "wgmma.commit_group.sync.aligned;\n}\n"  \
                 : OPS##N(MODE) : "r"(a), "r"(b) : "memory");                              \
  }
#define MMA_KBLOCKS(N, A, B, ob2, ob3)                                                     \
  MMA_KBLOCK(N, 0, A, B, ob2, ob3, 1, "", "+f")                                            \
  MMA_KBLOCK(N, 1, A, B, ob2, ob3, 1, "wgmma.commit_group.sync.aligned;\n", "+f")          \
  MMA_KBLOCK(N, 2, A, B, ob2, ob3, 0, "", "=f")

#define ACC128_0 \
  "%0, %1, %2, %3, %4, %5, %6, %7, %8, %9, %10, %11, %12, %13, %14, %15, " \
  "%16, %17, %18, %19, %20, %21, %22, %23, %24, %25, %26, %27, %28, %29, %30, %31, " \
  "%32, %33, %34, %35, %36, %37, %38, %39, %40, %41, %42, %43, %44, %45, %46, %47, " \
  "%48, %49, %50, %51, %52, %53, %54, %55, %56, %57, %58, %59, %60, %61, %62, %63"
#define ACC128_1 \
  "%64, %65, %66, %67, %68, %69, %70, %71, %72, %73, %74, %75, %76, %77, %78, %79, " \
  "%80, %81, %82, %83, %84, %85, %86, %87, %88, %89, %90, %91, %92, %93, %94, %95, " \
  "%96, %97, %98, %99, %100, %101, %102, %103, %104, %105, %106, %107, %108, %109, %110, %111, " \
  "%112, %113, %114, %115, %116, %117, %118, %119, %120, %121, %122, %123, %124, %125, %126, %127"
#define OPS128(m) \
  F8(m, acc[0], 0), F8(m, acc[0], 8), F8(m, acc[0], 16), F8(m, acc[0], 24), F8(m, acc[0], 32), F8(m, acc[0], 40), F8(m, acc[0], 48), F8(m, acc[0], 56), \
        F8(m, acc[1], 0), F8(m, acc[1], 8), F8(m, acc[1], 16), F8(m, acc[1], 24), F8(m, acc[1], 32), F8(m, acc[1], 40), F8(m, acc[1], 48), F8(m, acc[1], 56)
MMA_KBLOCKS(128, "%128", "%129", 512, 640)

#define ACC192_0 \
  "%0, %1, %2, %3, %4, %5, %6, %7, %8, %9, %10, %11, %12, %13, %14, %15, " \
  "%16, %17, %18, %19, %20, %21, %22, %23, %24, %25, %26, %27, %28, %29, %30, %31, " \
  "%32, %33, %34, %35, %36, %37, %38, %39, %40, %41, %42, %43, %44, %45, %46, %47, " \
  "%48, %49, %50, %51, %52, %53, %54, %55, %56, %57, %58, %59, %60, %61, %62, %63, " \
  "%64, %65, %66, %67, %68, %69, %70, %71, %72, %73, %74, %75, %76, %77, %78, %79, " \
  "%80, %81, %82, %83, %84, %85, %86, %87, %88, %89, %90, %91, %92, %93, %94, %95"
#define ACC192_1 \
  "%96, %97, %98, %99, %100, %101, %102, %103, %104, %105, %106, %107, %108, %109, %110, %111, " \
  "%112, %113, %114, %115, %116, %117, %118, %119, %120, %121, %122, %123, %124, %125, %126, %127, " \
  "%128, %129, %130, %131, %132, %133, %134, %135, %136, %137, %138, %139, %140, %141, %142, %143, " \
  "%144, %145, %146, %147, %148, %149, %150, %151, %152, %153, %154, %155, %156, %157, %158, %159, " \
  "%160, %161, %162, %163, %164, %165, %166, %167, %168, %169, %170, %171, %172, %173, %174, %175, " \
  "%176, %177, %178, %179, %180, %181, %182, %183, %184, %185, %186, %187, %188, %189, %190, %191"
#define OPS192(m) \
  F8(m, acc[0], 0), F8(m, acc[0], 8), F8(m, acc[0], 16), F8(m, acc[0], 24), F8(m, acc[0], 32), F8(m, acc[0], 40), F8(m, acc[0], 48), F8(m, acc[0], 56), F8(m, acc[0], 64), F8(m, acc[0], 72), F8(m, acc[0], 80), F8(m, acc[0], 88), \
        F8(m, acc[1], 0), F8(m, acc[1], 8), F8(m, acc[1], 16), F8(m, acc[1], 24), F8(m, acc[1], 32), F8(m, acc[1], 40), F8(m, acc[1], 48), F8(m, acc[1], 56), F8(m, acc[1], 64), F8(m, acc[1], 72), F8(m, acc[1], 80), F8(m, acc[1], 88)
MMA_KBLOCKS(192, "%192", "%193", 768, 896)

#define TSTEP(REGS, W, X, ow, ox)                                                           \
  "add.u32 t, " X ", " #ox ";\nmov.b64 db, {t, hi};\nadd.u32 t, " W ", " #ow ";\nmov.b64 da, {t, hi};\n" \
  "wgmma.mma_async.sync.aligned.m64n128k16.f32.bf16.bf16 {" REGS "}, da, db, 1, 1, 1, 1, 0;\n"
#define THEAD "{\n.reg .b32 t, hi;\n.reg .b64 da, db;\nmov.b32 hi, 0x40000040;\nwgmma.fence.sync.aligned;\n"
#define TTAIL "wgmma.commit_group.sync.aligned;\n}\n"
__device__ __forceinline__ void mma_kblock_t(float (&acc)[2][96], uint32_t wd, uint32_t xd) {
  asm volatile(THEAD TSTEP(ACC128_0, "%128", "%129", 0, 0) TSTEP(ACC128_1, "%128", "%129", 256, 0)
               TSTEP(ACC128_0, "%128", "%129", 128, 2) TSTEP(ACC128_1, "%128", "%129", 384, 2)
               TSTEP(ACC128_0, "%128", "%129", 512, 4) TSTEP(ACC128_1, "%128", "%129", 768, 4)
               TSTEP(ACC128_0, "%128", "%129", 640, 6) TSTEP(ACC128_1, "%128", "%129", 896, 6) TTAIL
               : OPS128("+f") : "r"(wd), "r"(xd) : "memory");
}
__device__ __forceinline__ void mma_half_t(float (&d)[96], uint32_t wd, uint32_t xd) {
  asm volatile(THEAD TSTEP(ACC128_0, "%64", "%65", 0, 0) TSTEP(ACC128_0, "%64", "%65", 128, 2)
               TSTEP(ACC128_0, "%64", "%65", 512, 4) TSTEP(ACC128_0, "%64", "%65", 640, 6) TTAIL
               : F8("+f", d, 0), F8("+f", d, 8), F8("+f", d, 16), F8("+f", d, 24), F8("+f", d, 32), F8("+f", d, 40),
                 F8("+f", d, 48), F8("+f", d, 56) : "r"(wd), "r"(xd) : "memory");
}

enum { kModePlain = 0, kModeHead = 1, kModeSkip = 2, kModeContinue = 3 };

template <int N>
__device__ __forceinline__ void fence_acc(float (&acc)[2][96]) {
#pragma unroll
  for (int h = 0; h < 2; h++)
#pragma unroll
    for (int i = 0; i < N / 2; i++) asm volatile("" : "+f"(acc[h][i])::"memory");
}

template <int N>
__device__ __forceinline__ void zero_acc(float (&acc)[2][96]) {
#pragma unroll
  for (int h = 0; h < 2; h++)
#pragma unroll
    for (int i = 0; i < N / 2; i++) acc[h][i] = 0.f;
}

constexpr uint32_t kToB = (kTileBytes >> 4) + ((4096u >> 4) << 16) - (1u << 16);

#define TRACE_KB(nb)

#define HEAD_BOTH 0
template <int N>
__device__ __forceinline__ void head_blocks(float (&acc)[2][96], uint32_t sb, int n0, int slot, uint32_t xbar, uint32_t turn,
                                            uint32_t rel_addr, bool rel) {
  const uint32_t ring = (((sb & 0x3FFFF) + kSmRing) >> 4) | (1u << 16);
  const uint32_t xdesc = (((sb & 0x3FFFF) + kSmX) >> 4) | (1u << 16);
  const uint32_t nb = n0 * 8;
  mbar_wait(xbar + 8 * HEAD_BOTH, 0);
  mbar_wait(turn, 0);
  mbar_wait(sb + kBarFull + (nb & 56), nb >> 6);
  TRACE_KB(nb);
  mma_kblock<N, 2>(acc, xdesc, ring + slot * 2560 + kToB);
  mbar_wait(xbar + 8, 0);
  mbar_wait(sb + kBarFull + (nb & 56) + 8, nb >> 6);
  TRACE_KB(nb + 8);
  mma_kblock<N, 0>(acc, xdesc + (kTileBytes >> 4), ring + ((slot + 1) & 3) * 2560 + kToB);
  wg_wait<1>();
  if (rel) mbar_arrive_cluster(rel_addr + (nb & 56));
  wg_wait<0>();
  if (rel) mbar_arrive_cluster(rel_addr + (nb & 56) + 8);
  fence_acc<N>(acc);
}

template <int N, bool RESID, bool FRESH, class Pre>
__device__ __forceinline__ void mainloop(float (&acc)[2][96], uint32_t sb, int tile, int n0, int slot, int nkb,
                                         int pause_kk, int att, uint32_t rel_addr, bool rel, int own_kk, Pre pre) {
  constexpr uint32_t kStep = (N == 192 ? 5 : 4) * 512;
  const uint32_t ring = (((sb & 0x3FFFF) + kSmRing) >> 4) | (1u << 16);
  uint32_t st = ring + slot * kStep;
  uint32_t nb = n0 * 8, prev = 64;
  const uint32_t last = nb + 8 * (nkb - (RESID ? 3 : 1)), own = nb + 8 * own_kk;
  const uint32_t stg = (((sb & 0x3FFFF) + kSmStg) >> 4) | (1u << 16);
  uint32_t stop = pause_kk >= 0 ? nb + 8 * pause_kk : last;
  const bool signal = (threadIdx.x & 127) == 64;
  if (!FRESH) fence_acc<N>(acc);
  if (tile > 0) mbar_wait(sb + kBarTurn + (tile - 1) * 8, 0);
  TRACE_AT(tile, 0);
  if constexpr (FRESH) {
    mbar_wait(sb + kBarFull + (nb & 56), nb >> 6);
    TRACE_KB(nb);
    mma_kblock<N, 2>(acc, st, st + kToB);
    prev = nb & 56;
    st += kStep;
    nb += 8;
  }
#pragma unroll 1
  while (true) {
#pragma unroll 1
    do {
      mbar_wait(sb + kBarFull + (nb & 56), nb >> 6);
      TRACE_KB(nb);
      if constexpr (RESID) mma_kblock_t(acc, st + kToB, nb == own ? stg : st);
      else mma_kblock<N, 0>(acc, st, st + kToB);
      wg_wait<1>();
      if (rel) mbar_arrive_cluster(rel_addr + prev);
      prev = nb & 56;
      st += kStep;
      if (st == ring + 10240) st = ring;
      nb += 8;
    } while (nb != stop);
    if (stop == last) break;
    stop = last;
    if (signal) mbar_arrive(sb + kBarPause + att * 8);
    wg_wait<0>();
    if (rel) mbar_arrive_cluster(rel_addr + prev);
    prev = 64;
    mbar_wait(sb + kBarResume + att * 8, 0);
  }
  mbar_wait(sb + kBarFull + (nb & 56), nb >> 6);
  TRACE_KB(nb);
  if constexpr (RESID) {
    const uint32_t z = gridDim.y - 1;
    const uint32_t s2 = st + kStep, s3 = s2 == ring + 8192 ? ring : s2 + kStep;
    mma_half_t(acc[0], st + kToB, st);
    wg_wait<1>();
    if (rel) mbar_arrive_cluster(rel_addr + 32);
    mbar_wait(sb + kBarFull + 48, nb >> 6);
    TRACE_KB(nb + 8);
    mma_half_t(acc[0], s2 + kToB, s2);
    mbar_wait(sb + kBarFull + 56, nb >> 6);
    TRACE_KB(nb + 16);
    mma_half_t(acc[0], s3 + kToB, s3);
    mma_half_t(acc[1], st + kToB + 256, st + z);
    mma_half_t(acc[1], s2 + kToB + 256, s2 + z);
    wg_wait<2>();
#pragma unroll
    for (int i = 0; i < 64; i++) asm volatile("" : "+f"(acc[0][i])::"memory");
    pre(0);
    mma_half_t(acc[1], s3 + kToB + 256, s3 + z);
    wg_wait<2>();
    if (rel) mbar_arrive_cluster(rel_addr + 40);
    pre(1);
    wg_wait<1>();
    if (rel) mbar_arrive_cluster(rel_addr + 48);
    if (signal) mbar_arrive(sb + kBarTurn + tile * 8);
    wg_wait<0>();
    if (rel) mbar_arrive_cluster(rel_addr + 56);
#pragma unroll
    for (int i = 0; i < 64; i++) asm volatile("" : "+f"(acc[1][i])::"memory");
  } else {
    mma_kblock<N, 1>(acc, st, st + kToB);
    wg_wait<2>();
    if (rel) mbar_arrive_cluster(rel_addr + prev);
    pre();
    wg_wait<1>();
    if (signal) mbar_arrive(sb + kBarTurn + tile * 8);
    wg_wait<0>();
    if (rel) mbar_arrive_cluster(rel_addr + (nb & 56));
    fence_acc<N>(acc);
  }
}

__device__ __forceinline__ void publish_stats(uint32_t sb, uint2* stat, int w, int lane, unsigned epoch) {
  const uint32_t row = sb + kSmX + (32 * w + lane) * 128;
  float s[4], q[4];
#pragma unroll
  for (int c = 0; c < 4; c++) s[c] = q[c] = 0.f;
  uint32_t nx[4];
  ldsm4(row + ((lane & 7) << 4), nx);
#pragma unroll 1
  for (int J = 1; J <= 16; J++) {
    const uint32_t r[4] = {nx[0], nx[1], nx[2], nx[3]};
    ldsm4(row + ((J >> 3) & 1) * kTileBytes + (((J ^ lane) & 7) << 4), nx);
#pragma unroll
    for (int c = 0; c < 4; c++) {
      const float lo = bf_lo(r[c]);
      s[c] += lo;
      q[c] = fmaf(lo, lo, q[c]);
      if (c & 1) yield_slot();
    }
#pragma unroll
    for (int c = 0; c < 4; c++) {
      const float hi = bf_hi(r[c]);
      s[c] += hi;
      q[c] = fmaf(hi, hi, q[c]);
      if (c & 1) yield_slot();
    }
  }
#pragma unroll
  for (int c = 0; c < 4; c++) {
    s[c] += shfl_xor(s[c], 1);
    q[c] += shfl_xor(q[c], 1);
    s[c] += shfl_xor(s[c], 2);
    q[c] += shfl_xor(q[c], 2);
  }
  const int t = lane & 3, g = lane >> 2;
  const float so = t == 0 ? s[0] : t == 1 ? s[1] : t == 2 ? s[2] : s[3];
  const float qo = t == 0 ? q[0] : t == 1 ? q[1] : t == 2 ? q[2] : q[3];
  asm volatile("st.relaxed.gpu.global.v2.u32 [%0], {%1, %2};" ::"l"(stat + 32 * w + 8 * t + g),
               "r"(tag_value(so, epoch)), "r"(tag_value(qo, epoch)) : "memory");
}

__device__ __forceinline__ void add_chunk(float (&a)[8], const uint4& v) {
  a[0] += bf_lo(v.x); a[1] += bf_hi(v.x);
  a[2] += bf_lo(v.y); a[3] += bf_hi(v.y);
  a[4] += bf_lo(v.z); a[5] += bf_hi(v.z);
  a[6] += bf_lo(v.w); a[7] += bf_hi(v.w);
}

__device__ __forceinline__ int helper_col(int id, int slab) {
  return slab < 6 ? (slab % 3) * kD + (slab / 3) * 512 + id * 128 : (slab - 6) * 512 + id * 128;
}
__device__ __forceinline__ void helper_cta(const CUtensorMap* map_q, const CUtensorMap* map_1, uint8_t* sm,
                                           uint32_t sb, int id, int warp) {
  constexpr int kRed = 6 * 32768, kBar = kRed + 2 * 4096;
  const int tid = threadIdx.x;
  if (warp == 8 && elect()) {
#pragma unroll
    for (int s = 0; s < 6; s++) {
      mbar_init(sb + kBar + s * 8, 1);
      mbar_init(sb + kBar + 64 + s * 8, 4);
    }
    fence_async_smem();
#pragma unroll
    for (int s = 0; s < 6; s++) {
      mbar_expect_tx(sb + kBar + s * 8, 32768);
      tma2d(sb + s * 32768, map_q, sb + kBar + s * 8, id * 128, s * 128);
    }
  }
  __syncthreads();
  if (warp == 8) {
    int slot = 0, ph = 0;
#pragma unroll 1
    for (int n = 6; n < 104; n++) {
      mbar_wait(sb + kBar + 64 + slot * 8, ph);
      if (elect()) {
        mbar_expect_tx(sb + kBar + slot * 8, 32768);
        tma2d(sb + slot * 32768, n < 48 ? map_q : map_1, sb + kBar + slot * 8, helper_col(id, n >> 3), (n & 7) * 128);
      }
      if (++slot == 6) slot = 0, ph ^= 1;
    }
  } else if (warp < 8) {
    if (tid == 0) *reinterpret_cast<unsigned*>(sm + kBar + 128) = atomicAdd(&g_ticket, 1u) / kGrid + 1;
    int slot = warp >> 2, ph = 0;
#pragma unroll 1
    for (int slab = 0; slab < 13; slab++) {
      float a[8];
#pragma unroll
      for (int e = 0; e < 8; e++) a[e] = 0.f;
#pragma unroll 1
      for (int box = 0; box < 4; box++) {
        mbar_wait(sb + kBar + slot * 8, ph);
        const uint4* p = reinterpret_cast<const uint4*>(sm + slot * 32768) + (tid & 127);
        uint4 v[16];
#pragma unroll
        for (int i = 0; i < 16; i++) v[i] = p[i * 128];
        __syncwarp();
        if (elect()) mbar_arrive(sb + kBar + 64 + slot * 8);
#pragma unroll
        for (int i = 0; i < 16; i++) add_chunk(a, v[i]);
        slot += 2;
        if (slot >= 6) slot -= 6, ph ^= 1;
      }
      float* red = reinterpret_cast<float*>(sm + kRed + (slab & 1) * 4096);
#pragma unroll
      for (int e = 0; e < 8; e++) a[e] += shfl_xor(a[e], 16);
      if ((tid & 16) == 0) {
        float4* d = reinterpret_cast<float4*>(red + warp * 128 + (tid & 15) * 8);
        d[0] = make_float4(a[0], a[1], a[2], a[3]);
        d[1] = make_float4(a[4], a[5], a[6], a[7]);
      }
      asm volatile("bar.sync 1, 256;" ::: "memory");
      if (warp < 4) {
        float t = 0.f;
#pragma unroll
        for (int q = 0; q < 8; q++) t += red[q * 128 + tid];
        st_relaxed(g_cs + (slab < 6 ? 0 : 3 * kD) + helper_col(id, slab) + tid,
                   tag_value(t, *reinterpret_cast<volatile unsigned*>(sm + kBar + 128)));
      }
    }
  }
}

constexpr float kGeluBeta = 0.3292034911525734f;
constexpr float kGeluK = 2.423681954311584f;

__device__ __forceinline__ void store_staged(uint8_t* dst, uint32_t stg) {
  fence_async_smem();
  __syncwarp();
  if (elect()) {
    bulk_store(dst, stg, 4096);
    bulk_commit();
  }
}

#define GY_MASK 0x3F
#define GY_MASK2 0x3f
#define GY(k) if (((CH == 2 ? GY_MASK2 : GY_MASK) >> k) & 1) yield_slot()
template <int CH>
__device__ __forceinline__ void gelu_chunk(const float (&acc)[2][96], const float2 (&st)[4], const float4* vec,
                                           uint32_t stg, int lane, bool chained, uint8_t* prev, uint32_t free_bar) {
  uint32_t pk[8][4];
  float u[3][4], z[3][4];
  float4 v = vec[CH * 32], vn = v;
#pragma unroll
  for (int s = 0; s < 18; s++) {
    const int J = CH * 8 + (s >> 1), c0 = 2 * (s & 1), cur = s % 3, p1 = (s + 2) % 3, p2 = (s + 1) % 3;
    if (s < 16) {
      if (c0 == 0 && s < 14) vn = vec[(J + 1) * 4];
#pragma unroll
      for (int e = 0; e < 4; e++) {
        const int c = c0 + (e >> 1);
        z[cur][e] = fmaf(st[c].y, e & 1 ? v.y : v.x, e & 1 ? v.w : v.z);
      }
      if (c0 == 2) v = vn;
    }
    if (s >= 1 && s < 17) z[p1][0] = tanh_fast(z[p1][0]);
    GY(0);
    if (s < 16) {
#pragma unroll
      for (int e = 0; e < 4; e++) {
        const int c = c0 + (e >> 1);
        u[cur][e] = fmaf(acc[c & 1][4 * J + c0 + (e & 1)], st[c].x, z[cur][e]);
      }
    }
    if (s >= 1 && s < 17) z[p1][1] = tanh_fast(z[p1][1]);
    GY(1);
    if (s >= 11) {
      const int jj = s - 11;
      stsm4(stg + lane * 128 + ((jj ^ (lane & 7)) << 4), pk[jj][0], pk[jj][1], pk[jj][2], pk[jj][3]);
    }
    if (s < 16) {
#pragma unroll
      for (int e = 0; e < 4; e++) z[cur][e] = fmaf(u[cur][e], u[cur][e], kGeluK);
    }
    if (s >= 1 && s < 17) z[p1][2] = tanh_fast(z[p1][2]);
    GY(3);
    if (s >= 2) {
      pk[(s - 2) >> 1][c0] = pack2(fmaf(u[p2][0], z[p2][0], u[p2][0]), fmaf(u[p2][1], z[p2][1], u[p2][1]));
      pk[(s - 2) >> 1][c0 + 1] = pack2(fmaf(u[p2][2], z[p2][2], u[p2][2]), fmaf(u[p2][3], z[p2][3], u[p2][3]));
    }
    GY(4);
    if (s < 16) {
#pragma unroll
      for (int e = 0; e < 4; e++) z[cur][e] = u[cur][e] * z[cur][e];
    }
    if (s >= 1 && s < 17) z[p1][3] = tanh_fast(z[p1][3]);
    GY(5);
    if (CH < 2 && s == 1 && chained) store_staged(prev, stg);
    if (CH < 2 && s == 10) {
      if (chained) {
        if (elect()) bulk_wait();
        __syncwarp();
      } else {
        mbar_wait(free_bar, 0);
      }
    }
  }
  stsm4(stg + lane * 128 + ((7 ^ (lane & 7)) << 4), pk[7][0], pk[7][1], pk[7][2], pk[7][3]);
}

__device__ __forceinline__ void scale_stats(float2 (&st)[4]) {
#pragma unroll
  for (int c = 0; c < 4; c++) {
    st[c].x *= kGeluBeta;
    st[c].y *= st[c].x;
  }
}

__device__ __forceinline__ void add_mean_term(float (&acc)[2][96], const float2 (&st)[4], uint8_t* sm, int tq,
                                              int lane) {
  const float2* cs = reinterpret_cast<const float2*>(sm + kSmCsQ) + tq * 96 + (lane & 3);
  float2 vn = cs[0];
#pragma unroll
  for (int J = 0; J < 24; J++) {
    const float2 v = vn;
    if (J < 23) vn = cs[J * 4 + 4];
#pragma unroll
    for (int c = 0; c < 4; c++) {
      acc[c & 1][4 * J + (c & 2)] = fmaf(st[c].y, v.x, acc[c & 1][4 * J + (c & 2)]);
      acc[c & 1][4 * J + (c & 2) + 1] = fmaf(st[c].y, v.y, acc[c & 1][4 * J + (c & 2) + 1]);
    }
    yield_slot();
  }
}

#define TWO_PART 0
#define RESUME_LATE 0
#define HALO_AT 2
__device__ __forceinline__ void epilogue_attn(const float (&acc)[2][96], const float2 (&st)[4], uint8_t* sm,
                                              uint32_t sb, int layer, int tq, int b, int j, unsigned epoch, int tile,
                                              int wg, int w) {
  const int lane = threadIdx.x & 31, t = lane & 3, g = lane >> 2;
  const int hp = j + 8 * tq, att = 2 * layer + tq;
  uint32_t q[4][8], k[5][8], vt[5][8];
#define SCALED(c, J) pack2(acc[(c) & 1][4 * (J) + ((c) & 2)] * st[c].x, acc[(c) & 1][4 * (J) + ((c) & 2) + 1] * st[c].x)
#pragma unroll
  for (int J = 0; J < 8; J++) vt[4][J] = transpose8(SCALED(3, 16 + J));
#pragma unroll
  for (int J = 0; J < 8; J++) k[4][J] = SCALED(3, 8 + J);
  if (w < 3) {
    uint2* hs = reinterpret_cast<uint2*>(sm + kSmHalo + w * 2048) + lane;
#pragma unroll
    for (int i = 0; i < 4; i++) {
      hs[i * 32] = make_uint2(k[4][2 * i], k[4][2 * i + 1]);
      hs[128 + i * 32] = make_uint2(vt[4][2 * i], vt[4][2 * i + 1]);
    }
  } else if ((b & 7) != 7) {
    uint4* gh = g_halo + ((layer * 16 + b) * 16 + hp) * 256 + lane;
#pragma unroll
    for (int i = 0; i < 4; i++) {
      st_packet(gh + i * 32, k[4][2 * i], k[4][2 * i + 1], epoch);
      st_packet(gh + 128 + i * 32, vt[4][2 * i], vt[4][2 * i + 1], epoch);
    }
  }
#pragma unroll
  for (int c = 0; c < 3; c++)
#pragma unroll
    for (int J = 0; J < 8; J++) {
      k[c + 1][J] = SCALED(c, 8 + J);
      vt[c + 1][J] = transpose8(SCALED(c, 16 + J));
      yield_slot();
    }
  const bool first = w == 0 && (b & 7) == 0;
  const uint4* gh = g_halo + ((layer * 16 + b - 1) * 16 + hp) * 256 + lane;
  uint32_t tag[8];
#define LOAD_HALO()                                                                                    \
  _Pragma("unroll") for (int i = 0; i < 4; i++) {                                                      \
    ld_packet(gh + i * 32, k[0][2 * i], k[0][2 * i + 1], tag[i]);                                      \
    ld_packet(gh + 128 + i * 32, vt[0][2 * i], vt[0][2 * i + 1], tag[4 + i]);                          \
  }
#define AWAIT_HALO()                                                                                   \
  for (unsigned spins = 0;; spins++) {                                                                 \
    const unsigned d0 = (tag[0] ^ epoch) | (tag[1] ^ epoch) | (tag[2] ^ epoch) | (tag[3] ^ epoch);     \
    const unsigned d1 = (tag[4] ^ epoch) | (tag[5] ^ epoch) | (tag[6] ^ epoch) | (tag[7] ^ epoch);     \
    if (__all_sync(0xffffffffu, (d0 | d1) == 0)) break;                                                \
    if (spins > kSpinLimit) __trap();                                                                  \
    LOAD_HALO();                                                                                       \
  }
#pragma unroll
  for (int c = 0; c <= 4; c++) {
    if (c == HALO_AT) {
      if (w == 0 && !first) {
        LOAD_HALO();
      } else {
#pragma unroll
        for (int i = 0; i < 8; i++) k[0][i] = vt[0][i] = tag[i] = 0u;
      }
    }
#pragma unroll
    for (int J = 0; J < 8 && c < 4; J++) {
      q[c & 3][J] = SCALED(c & 3, J);
      if (J & 1) yield_slot();
    }
  }
#undef SCALED
  TRACE_AT(tile, 8);
  wg_bar(wg);
  if (w > 0) {
    const uint2* hs = reinterpret_cast<const uint2*>(sm + kSmHalo + (w - 1) * 2048) + lane;
#pragma unroll
    for (int i = 0; i < 4; i++) {
      const uint2 a = hs[i * 32], c = hs[128 + i * 32];
      k[0][2 * i] = a.x; k[0][2 * i + 1] = a.y;
      vt[0][2 * i] = c.x; vt[0][2 * i + 1] = c.y;
    }
  } else if (!first && tq == 0) {
    AWAIT_HALO();
  }
  constexpr float kScale = 0.17677669529663687f * 1.4426950408889634f;
  const bool own0 = 2 * t <= g, own1 = 2 * t + 1 <= g;
  const uint32_t own_mask = (own0 ? 0xffffu : 0u) | (own1 ? 0xffff0000u : 0u);
  const uint32_t stg = sb + kSmStg + w * 4096;
  const uint32_t orow = stg + (lane & 7) * 128, ochunk = (lane >> 3) ^ (lane & 7);
  TRACE_AT(tile, 9);
  mbar_wait(sb + kBarPause + att * 8, 0);
  TRACE_AT(tile, 10);

  float s[2][6][4], o[2][4][2][4];
  auto scores = [&](int hd, int m) {
    const int ca = 2 * (m / 3), kg = ca + m % 3;
#pragma unroll
    for (int e = 0; e < 4; e++) s[hd][m][e] = 0.f;
#pragma unroll
    for (int J = 4 * hd; J < 4 * hd + 4; J += 2)
      mma16816(s[hd][m], q[ca][J], q[ca + 1][J], q[ca][J + 1], q[ca + 1][J + 1], k[kg][J], k[kg][J + 1]);
  };
  auto attend = [&](int c0, int c1) {
    float v0[2][4], v1[2][4], m[2][4];
#define UNITS _Pragma("unroll") for (int hd = 0; hd < 2; hd++) _Pragma("unroll") for (int c = c0; c < c1; c++)
    UNITS {
      const int mp = 3 * (c >> 1) + (c & 1), r = 2 * (c & 1);
      float p0 = s[hd][mp][r], p1 = s[hd][mp][r + 1];
      if (c == 0 && first) p0 = p1 = -INFINITY;
      v0[hd][c] = own0 ? s[hd][mp + 1][r] : p0;
      v1[hd][c] = own1 ? s[hd][mp + 1][r + 1] : p1;
      m[hd][c] = fmaxf(v0[hd][c], v1[hd][c]);
    }
    UNITS m[hd][c] = fmaxf(m[hd][c], shfl_xor(m[hd][c], 1));
    UNITS m[hd][c] = fmaxf(m[hd][c], shfl_xor(m[hd][c], 2));
    UNITS {
      const float nm = -m[hd][c] * kScale;
      v0[hd][c] = ex2(fmaf(v0[hd][c], kScale, nm));
      v1[hd][c] = ex2(fmaf(v1[hd][c], kScale, nm));
      m[hd][c] = v0[hd][c] + v1[hd][c];
    }
    UNITS m[hd][c] += shfl_xor(m[hd][c], 1);
    UNITS m[hd][c] += shfl_xor(m[hd][c], 2);
    UNITS {
      const float inv = rcp(m[hd][c]);
      const uint32_t p = pack2(v0[hd][c] * inv, v1[hd][c] * inv);
#pragma unroll
      for (int ds = 0; ds < 2; ds++) {
        const int J = 4 * hd + 2 * ds;
#pragma unroll
        for (int e = 0; e < 4; e++) o[hd][c][ds][e] = 0.f;
        if (c & 1) {
          mma16816(o[hd][c][ds], vt[c][J], vt[c][J + 1], vt[c + 1][J], vt[c + 1][J + 1], p & ~own_mask, p & own_mask);
        } else {
          mma1688(o[hd][c][ds], vt[c + 1][J], vt[c + 1][J + 1], p & own_mask);
          mma1688(o[hd][c][ds], vt[c][J], vt[c][J + 1], p & ~own_mask);
        }
      }
    }
  };
  auto stage = [&](int c0, int c1) {
    UNITS stsm4_t(orow + c * 1024 + ((ochunk ^ (4 * hd)) << 4), pack2(o[hd][c][0][0], o[hd][c][0][1]),
                  pack2(o[hd][c][0][2], o[hd][c][0][3]), pack2(o[hd][c][1][0], o[hd][c][1][1]),
                  pack2(o[hd][c][1][2], o[hd][c][1][3]));
#undef UNITS
  };
  if (w == 0 && !first) AWAIT_HALO();
#pragma unroll
  for (int hd = 0; hd < 2; hd++)
#pragma unroll
    for (int m = 0; m < 6; m++) scores(hd, m);
  attend(0, 4);
  yield_slot();
  if (tq == 0 && elect()) mbar_arrive(sb + kBarResume + att * 8);
  TRACE_AT(tile, 11);
  stage(0, 4);
#undef AWAIT_HALO
#undef LOAD_HALO
  fence_async_smem();
  __syncwarp();
  TRACE_AT(tile, 12);
  if (elect()) {
    bulk_store(g_o + (b * 16 + hp) * kTileBytes + w * 4096, stg, 4096);
    bulk_commit();
    if (tq == 1 && !RESUME_LATE) mbar_arrive(sb + kBarResume + att * 8);
    bulk_wait();
    if (tq == 1 && RESUME_LATE) mbar_arrive(sb + kBarResume + att * 8);
    TRACE_AT(tile, 13);
    mbar_arrive(sb + kBarEpi + tile * 8);
  }
  __syncwarp();
}

__device__ __forceinline__ void gather_stats(uint8_t* sm, const uint2* stat, unsigned epoch) {
  const int r = threadIdx.x & 127;
  uint2 a[8];
  unsigned spins = 0;
  while (true) {
    unsigned diff = 0;
#pragma unroll
    for (int i = 0; i < 8; i++) {
      a[i] = ld_relaxed2(stat + i * 128 + r);
      diff |= (a[i].x ^ epoch) | (a[i].y ^ epoch);
    }
    if (__all_sync(0xffffffffu, (diff & 7u) == 0)) break;
    if (++spins > kSpinLimit) __trap();
    __nanosleep(200);
  }
  float s = 0.f, q = 0.f;
#pragma unroll
  for (int i = 0; i < 8; i++) {
    s += untag_value(a[i].x);
    q += untag_value(a[i].y);
  }
  const float mean = s * (1.f / 1024.f);
  const float var = fmaxf(fmaf(-mean, mean, q * (1.f / 1024.f)), 0.f);
  reinterpret_cast<float2*>(sm + kSmStat)[r] = make_float2(rsqrtf(var + 1e-5f), -mean);
}

__device__ __forceinline__ void gather_colsums(uint8_t* sm, int part, int j, int lane, unsigned epoch) {
#pragma unroll 1
  for (int blk = part < 4 ? 0 : 2 * part - 5; blk < (part < 4 ? 3 : 2 * part - 3); blk++) {
    const int col = part < 2 ? blk * kD + (j + 8 * part) * 64
                             : 3 * kD + 64 * (blk + (blk < 3 ? 3 * j : blk < 5 ? 21 + 2 * j : 35 + 2 * j));
    uint2 v;
    unsigned spins = 0;
    while (true) {
      v = ld_relaxed2(reinterpret_cast<const uint2*>(g_cs + col) + lane);
      if (__all_sync(0xffffffffu, (((v.x ^ epoch) | (v.y ^ epoch)) & 7u) == 0)) break;
      if (++spins > kSpinLimit) __trap();
      __nanosleep(100);
    }
    uint8_t* dst = part < 2 ? sm + kSmCsQ + (part * 96 + blk * 32 + lane) * 8 : sm + kSmV1 + (blk * 32 + lane) * 16;
    *reinterpret_cast<float2*>(dst) = make_float2(untag_value(v.x), untag_value(v.y));
  }
}

#define READBACK 0
#define GATE_B 0
#define LATE_REL2 1
#define XT_LATE 1
#define STAGE_YIELD 1
#define PAUSE_QKV2 7
#define PAUSE_WO 1

__global__ void __cluster_dims__(2, 1, 1) __launch_bounds__(384, 1)
fused_layers_kernel(const __grid_constant__ CUtensorMap map_x, const __grid_constant__ CUtensorMap map_out,
                    const __grid_constant__ CUtensorMap map_qkv, const __grid_constant__ CUtensorMap map_wo,
                    const __grid_constant__ CUtensorMap map_w1a, const __grid_constant__ CUtensorMap map_w1b,
                    const __grid_constant__ CUtensorMap map_w2, const __grid_constant__ CUtensorMap map_csq,
                    const __grid_constant__ CUtensorMap map_cs1, const __grid_constant__ Params prm) {
  extern __shared__ __align__(1024) uint8_t sm[];
  if (threadIdx.x < 128 && blockIdx.x < kCtas) TRACE_AT(15, 1);
  const uint32_t sb = __shfl_sync(0xffffffffu, smem_u32(sm), 0);
  const int warp = __shfl_sync(0xffffffffu, threadIdx.x >> 5, 0), lane = threadIdx.x & 31;
  const int cta = blockIdx.x, rank = cta & 1, cl = cta >> 1;
  const int grp = cl < 4 ? 0 : cl < 36 ? (cl - 4) & 7 : 1 + (cl - 36) % 7;
  const int j = cl < 4 ? 4 + cl : cl < 36 ? (cl - 4) >> 3 : 4 + (cl - 36) / 7;
  const int b = 2 * grp + rank;
  const int xcol = (b >> 3) * kD, xrow = (b & 7) * 128;

  if (cta >= kCtas) {
    helper_cta(&map_csq, &map_cs1, sm, sb, cta - kCtas, warp);
    return;
  }
  if (warp >= 8 && elect()) {
    if (warp == 9) {
#pragma unroll
      for (int s = 0; s < 8; s++) mbar_init(sb + kBarFull + s * 8, 1);
      mbar_init(sb + kBarInit, 1);
      fence_async_smem();
#pragma unroll
      for (int s = 0; s < 4; s++) {
        const uint32_t full = sb + kBarFull + s * 8, dst = sb + kSmRing + s * 40960;
        mbar_expect_tx(full, 40960);
        tma2d(dst, &map_x, full, xcol + s * 64, xrow);
        tma3d(dst + kTileBytes, &map_qkv, full, j * 64, s * 64, 0);
        tma3d(dst + kTileBytes + 12288, &map_qkv, full, j * 64, s * 64 + 32, 0);
      }
      if (!XT_LATE) {
        mbar_expect_tx(sb + kBarInit, 32768);
        tma2d(sb + kSmX, &map_x, sb + kBarInit, xcol + j * 128, xrow);
        tma2d(sb + kSmX + kTileBytes, &map_x, sb + kBarInit, xcol + j * 128 + 64, xrow);
      }
    } else if (warp == 8) {
      if (sb & 1023) __trap();
#pragma unroll
      for (int o = kBarTurn; o < kBarPause; o += 8) mbar_init(sb + o, 1);
    } else if (warp == 10) {
#pragma unroll
      for (int o = kBarEpi; o < kSmEpoch; o += 8) mbar_init(sb + o, 4);
    } else {
#pragma unroll
      for (int o = kBarPause; o < kBarEpi; o += 8)
        if (o != kBarInit) mbar_init(sb + o, o < kBarEmpty ? 1 : 2);
    }
    asm volatile("fence.mbarrier_init.release.cluster;" ::: "memory");
  }
  __syncwarp();
  asm volatile("barrier.cluster.arrive.relaxed.aligned;" ::: "memory");

  if (warp >= 8) {
    asm volatile("setmaxnreg.dec.sync.aligned.u32 40;");
    if (warp < 10) {
      asm volatile("barrier.cluster.wait.aligned;" ::: "memory");
      uint32_t nb = 32, off = 0, kb = 0;
#define RING_STEP(ISSUE)                                                  \
  do {                                                                    \
    const uint32_t mb = nb - depth, full = sb + kBarFull + (nb & 56);     \
    if (kb == skip) kb += inc;                                            \
    mbar_wait(sb + kBarEmpty + (mb & 56), mb >> 6);                       \
    if (elect()) { ISSUE; }                                               \
    TRACE_ISSUE(9 - warp, nb);                                            \
    kb += inc;                                                            \
    off = off == wrap ? 0 : off + step;                                   \
    nb += 8;                                                              \
  } while (nb != nend)
#pragma unroll 1
      for (int sg = 0; sg < kSegs; sg++) {
        const uint32_t e = prm.seg[sg];
        const int ty = e & 7, mode = (e >> 15) & 3, reset = (e >> 24) & 3;
        const uint32_t nend = nb + (e & 0x1f8);
        const uint32_t step = (e >> 17) & 1 ? 40960 : 32768, wrap = 163840 - step;
        const uint32_t depth = (e >> 18) & 1 ? 40 : 32;
        if (reset) off = reset == 1 ? 0 : reset == 2 ? 40960 : 131072;
        const uint32_t own = ty == 2 ? 8 + j : 2 * j;
        if (mode != kModeContinue) kb = mode == kModeHead ? own : (e >> 9) & 63;
        const uint32_t inc = mode >= kModeSkip && ty != 2 ? 2 : 1, skip = mode >= kModeSkip ? own + (kb & 1) : 255;
        if (warp == 8) {
          const CUtensorMap* map = ty < 2 ? &map_qkv : ty == 2 ? &map_wo : ty == 3 ? &map_w1a : ty < 6 ? &map_w1b : &map_w2;
          const int c0 = ty < 2 ? (j + 8 * ty) * 64 : 0;
          const int c2 = ty < 2 ? 0 : ty == 3 ? 3 * j : ty == 4 ? 24 + 2 * j : ty == 5 ? 40 + 2 * j : 2 * j;
          const uint32_t half = (ty < 2 || ty == 3) ? 12288 : 8192;
          const uint32_t bytes = 2 * half + (mode == kModeHead ? 0 : kTileBytes);
          const uint32_t dst = sb + kSmRing + kTileBytes + rank * half;
          if (GATE_B) {
            const int dep = (e >> 19) & 31;
            if (dep == 2 || dep == 6 || dep == 9) mbar_wait(sb + kBarFree + dep * 8, 0);
          }
#pragma unroll 1
          RING_STEP(mbar_expect_tx(full, bytes); tma3d_mc(dst + off, map, full, c0, kb * 64 + rank * 32, c2));
        } else if (mode == kModeHead) {
          off += ((nend - nb) >> 3) * step;
          nb = nend;
          if (off >= 163840) off -= 163840;
        } else if (sg < 2) {
#pragma unroll 1
          RING_STEP(tma2d(sb + kSmRing + off, &map_x, full, xcol + kb * 64, xrow));
        } else {
          const uint8_t* src = ty == 6 ? g_h + b * 56 * kTileBytes : (ty == 2 ? g_o : g_x) + b * 16 * kTileBytes;
          const int dep = (e >> 19) & 31;
          if (dep != 31) mbar_wait(sb + kBarReady + dep * 8, 0);
#pragma unroll 1
          RING_STEP(bulk_load(sb + kSmRing + off, src + kb * kTileBytes, kTileBytes, full));
        }
      }
#undef RING_STEP
    } else if (warp == 10) {
      unsigned epoch = 0;
      if (lane == 0) epoch = atomicAdd(&g_ticket, 1u) / kGrid + 1;
      epoch = __shfl_sync(0xffffffffu, epoch, 0);
      *reinterpret_cast<unsigned*>(sm + kSmEpoch) = epoch;
      asm volatile("barrier.cluster.wait.aligned;" ::: "memory");
      if (elect()) mbar_arrive(sb + kBarEpoch);
#pragma unroll 1
      for (int i = 0; i < kTiles - 1; i++) {
        const bool xt = i == 2 || i == 6 || i == 9;
        const unsigned* line = g_flag + (i * 16 + b) * 32;
        mbar_wait(sb + (xt ? kBarX + (i >> 2) * 16 : kBarEpi + i * 8), 0);
        wait_flags(line + (lane & 7), epoch);
        if (elect()) mbar_arrive(sb + kBarReady + i * 8);
        if (xt) {
          wait_flags(line + 8 + (lane & 7), epoch);
          if (elect()) mbar_arrive(sb + kBarReady + (14 + (i >> 2)) * 8);
        }
      }
    } else {
      asm volatile("barrier.cluster.wait.aligned;" ::: "memory");
      if (XT_LATE) {
        mbar_wait(sb + kBarFull + 8 * (XT_LATE - 1), 0);
        if (elect()) {
          mbar_expect_tx(sb + kBarInit, 32768);
          tma2d(sb + kSmX, &map_x, sb + kBarInit, xcol + j * 128, xrow);
          tma2d(sb + kSmX + kTileBytes, &map_x, sb + kBarInit, xcol + j * 128 + 64, xrow);
        }
      }
      {
        uint32_t v[7];
#pragma unroll
        for (int q = 0; q < 7; q++)
          v[q] = reinterpret_cast<const uint32_t*>(prm.b1)[32 * (q + (q < 3 ? 3 * j : q < 5 ? 21 + 2 * j : 35 + 2 * j)) + lane];
        const uint2 u = reinterpret_cast<const uint2*>(prm.b2)[32 * j + lane];
#pragma unroll
        for (int q = 0; q < 7; q++)
          *reinterpret_cast<float2*>(sm + kSmV1 + (q * 32 + lane) * 16 + 8) = make_float2(kGeluBeta * bf_lo(v[q]), kGeluBeta * bf_hi(v[q]));
        reinterpret_cast<float4*>(sm + kSmB2)[lane] = make_float4(
            2.f * kGeluBeta * bf_lo(u.x), 2.f * kGeluBeta * bf_hi(u.x), 2.f * kGeluBeta * bf_lo(u.y), 2.f * kGeluBeta * bf_hi(u.y));
      }
      mbar_wait(sb + kBarEpoch, 0);
      const unsigned epoch = *reinterpret_cast<volatile unsigned*>(sm + kSmEpoch);
#pragma unroll 1
      for (int i = 0; i < kTiles - 1; i++) {
#pragma unroll 1
        for (int part = i == 4 ? 5 : i; part < (i < 2 ? i + 1 : i == 3 || i == 4 ? i + 2 : 0); part++) {
          gather_colsums(sm, part, j, lane, epoch);
          __syncwarp();
          if (elect()) mbar_arrive(sb + kBarCs + part * 8);
        }
        const bool xt = i == 2 || i == 6 || i == 9;
#pragma unroll 1
        for (int h = 0; h < (xt ? 2 : 1); h++) {
          mbar_wait(sb + (xt ? kBarX + (i >> 2) * 16 + 8 * h : kBarEpi + i * 8), 0);
          const int ty = i >= 7 ? i - 7 : i;
          if (ty >= 2 && elect()) {
            uint8_t* dst = xt ? g_x + (b * 16 + 2 * j + h) * kTileBytes
                              : g_h + (b * 56 + 1 + (ty == 3 ? 3 * j : 16 * ty - 40 + 2 * j)) * kTileBytes;
            bulk_store(dst, sb + (xt ? kSmX + h * kTileBytes : kSmStg), kTileBytes);
            bulk_commit();
            bulk_wait();
            if (!xt) mbar_arrive(sb + kBarFree + i * 8);
          }
          if (LATE_REL2 && h == 1) mbar_wait(sb + kBarFull + 32, i == 2 ? 6 : i == 6 ? 19 : 25);
          __syncwarp();
          if (elect()) st_release(&g_flag[(i * 16 + b) * 32 + h * 8 + j], epoch);
          __syncwarp();
          if (xt && h == 0 && elect()) mbar_arrive(sb + kBarFree + i * 8);
        }
      }
#pragma unroll 1
      for (int h = 0; h < 2; h++) {
        mbar_wait(sb + kBarX + 48 + 8 * h, 0);
        if (elect()) {
          tma2d_store(&map_out, sb + kSmX + h * kTileBytes, xcol + j * 128 + h * 64, xrow);
          bulk_commit();
          if (h == 1) bulk_wait_read();
        }
      }
    }
    __syncwarp();
    asm volatile("barrier.cluster.arrive.relaxed.aligned;\nbarrier.cluster.wait.aligned;" ::: "memory");
  } else {
    asm volatile("setmaxnreg.inc.sync.aligned.u32 232;");
    asm volatile("barrier.cluster.wait.aligned;" ::: "memory");
    const int wg = warp >> 2, w = warp & 3;
    const bool rel = (threadIdx.x & 95) == 0;
    const uint32_t rel_addr = mapa(sb + kBarEmpty, w & 1);
    if (wg == 1) TRACE_AT(15, 0);
#define EPOCH (*reinterpret_cast<volatile unsigned*>(sm + kSmEpoch))

    if (wg == 1) {
      mbar_wait(sb + kBarEpoch, 0);
      mbar_wait(sb + kBarInit, 0);
    }

#pragma unroll 1
    for (int i = wg; i < kTiles; i += 2) {
      const int layer = i >= 7, ty = i - 7 * layer;
      TRACE_AT(i, 15);
      float acc[2][96];
      if (ty == 2 || ty == 6) {
        const uint32_t xa = sb + kSmX + ((lane >> 4) * 8 + (lane & 7)) * 128 + (((2 * w + ((lane >> 3) & 1)) ^ (lane & 7)) << 4);
        const float up = ty == 6 ? 2.f * kGeluBeta : 1.f, dn = ty == 6 ? 0.5f / kGeluBeta : 1.f;
#pragma unroll
        for (int h = 0; h < 2; h++) {
          const float* b2 = reinterpret_cast<const float*>(sm + kSmB2) + 64 * h + 16 * w + (lane >> 2);
          const float bias[2] = {ty == 6 ? b2[0] : 0.f, ty == 6 ? b2[8] : 0.f};
#pragma unroll
          for (int p = 0; p < 8; p++) {
            uint32_t r[4];
            ldsm4_t(xa + h * kTileBytes + p * 2048, r);
#pragma unroll
            for (int m = 0; m < 4; m++) {
              acc[h][8 * p + 2 * m] = fmaf(bf_lo(r[m]), up, bias[m & 1]);
              acc[h][8 * p + 2 * m + 1] = fmaf(bf_hi(r[m]), up, bias[m & 1]);
              asm volatile("" : "+f"(acc[h][8 * p + 2 * m]), "+f"(acc[h][8 * p + 2 * m + 1]));
              if (m & 1) yield_slot();
            }
          }
        }
        auto stage = [&](int qt) {
          const int h = qt >> 1;
#pragma unroll
          for (int p = 4 * (qt & 1); p < 4 * (qt & 1) + 4; p++) {
            const float* a = &acc[h][8 * p];
            stsm4_t(xa + h * kTileBytes + p * 2048, pack2(a[0] * dn, a[1] * dn), pack2(a[2] * dn, a[3] * dn),
                    pack2(a[4] * dn, a[5] * dn), pack2(a[6] * dn, a[7] * dn));
            if (STAGE_YIELD || (p & 3) == 3) yield_slot();
          }
          if (qt & 1) {
            fence_async_smem();
            __syncwarp();
            if (elect()) mbar_arrive(sb + kBarX + (i >> 2) * 16 + 8 * h);
            TRACE_AT(i, 8 + h);
          }
        };
        mainloop<128, true, false>(acc, sb, i, layer * 152 + ty * 16, ty == 6 ? 4 : 0, ty == 6 ? 56 : 16,
                            ty == 2 ? PAUSE_WO : -1, 2 * layer + 1, rel_addr, rel, ty == 2 ? 8 : -1, stage);
        TRACE_AT(i, 2);
        stage(2);
        stage(3);
      } else {
        const int xver = 2 * layer + (ty >= 3);
        const uint32_t stg = sb + kSmStg + w * 4096;
        const float4* vec = reinterpret_cast<const float4*>(sm + kSmV1) + (ty == 3 ? 0 : 64 * ty - 160) + (lane & 3);
        uint8_t* hdst = g_h + (b * 56 + (ty == 3 ? 3 * j : 16 * ty - 40 + 2 * j)) * kTileBytes + w * 4096;
        float2 st[4];
        unsigned epoch;
        auto pre = [&] {
          if (ty < 4) mbar_wait(sb + (ty == 1 ? kBarEpi + (i - 1) * 8 : kBarStat + xver * 8), 0);
#pragma unroll
          for (int c = 0; c < 4; c++) st[c] = reinterpret_cast<const float2*>(sm + kSmStat)[32 * w + 8 * c + (lane >> 2)];
          epoch = EPOCH;
        };
        if (ty == 5) {
          mainloop<128, false, true>(acc, sb, i, layer * 152 + 80, 3, 16, -1, 0, rel_addr, rel, 0, pre);
        } else {
          if (i < 2) {
            zero_acc<192>(acc);
          } else {
            const int n0 = layer * 152 + (ty < 2 ? 2 * ty : 42 + 2 * ty), slot = ty < 2 ? 2 * ty : 2 * ty - 5;
            if (ty < 4) {
              head_blocks<192>(acc, sb, n0, slot, sb + kBarX + (xver - 1) * 16,
                               sb + kBarTurn + (xver == 1 ? 2 : 3 * xver) * 8, rel_addr, rel);
            } else {
              head_blocks<128>(acc, sb, n0, slot, sb + kBarX + (xver - 1) * 16,
                               sb + kBarTurn + (xver == 1 ? 2 : 3 * xver) * 8, rel_addr, rel);
#pragma unroll
              for (int q = 64; q < 96; q++) acc[0][q] = acc[1][q] = 0.f;
            }
          }
          if (ty == 1 || ty == 4) {
            uint2* stat = g_stat + (xver * 16 + b) * 1024;
            publish_stats(sb, stat + j * 128, w, lane, EPOCH);
            gather_stats(sm, stat, EPOCH);
            __syncwarp();
            if (elect()) mbar_arrive(sb + kBarStat + xver * 8);
            TRACE_AT(i, 14);
            if (i == 8) {
#pragma unroll
              for (int c = 0; c < 4; c++) st[c] = reinterpret_cast<const float2*>(sm + kSmStat)[32 * w + 8 * c + (lane >> 2)];
              add_mean_term(acc, st, sm, 1, lane);
            }
          }
          if (ty < 4) {
            mainloop<192, false, false>(acc, sb, i, i < 2 ? 16 * i : layer * 152 + (ty < 2 ? 4 + 14 * ty : 52), i == 8 ? 2 : ty == 3,
                          i < 2 ? 16 : 14, ty == 1 ? PAUSE_QKV2 : -1, xver, rel_addr, rel, 0, pre);
            TRACE_AT(i, 2);
            if (layer == 0) mbar_wait(sb + kBarCs + ty * 8, 0);
            if (ty < 2) {
              if (i != 8) add_mean_term(acc, st, sm, ty, lane);
              epilogue_attn(acc, st, sm, sb, layer, ty, b, j, epoch, i, wg, w);
              goto tile_done;
            }
            scale_stats(st);
            gelu_chunk<2>(acc, st, vec, stg, lane, false, nullptr, 0);
            goto common_chunks;
          }
          mainloop<128, false, false>(acc, sb, i, layer * 152 + 66, 4, 14, -1, 0, rel_addr, rel, 0, pre);
        }
        TRACE_AT(i, 2);
        if (layer == 0) mbar_wait(sb + kBarCs + ty * 8, 0);
        scale_stats(st);
      common_chunks:
        TRACE_AT(i, 8);
        gelu_chunk<0>(acc, st, vec, stg, lane, ty == 3, hdst + 2 * kTileBytes, sb + kBarFree + (i - 1) * 8);
        TRACE_AT(i, 9);
        gelu_chunk<1>(acc, st, vec, stg, lane, true, hdst, 0);
        TRACE_AT(i, 10);
        fence_async_smem();
        __syncwarp();
        if (elect()) mbar_arrive(sb + kBarEpi + i * 8);
      }
    tile_done:
      TRACE_AT(i, 3);
    }
#undef EPOCH
    asm volatile("barrier.cluster.arrive.relaxed.aligned;\nbarrier.cluster.wait.aligned;" ::: "memory");
    if (wg == 1) TRACE_AT(15, 2);
  }
}

void build_segments(uint32_t* seg) {
  int n = 0;
  auto add = [&](int ty, int cnt, int kb0, int mode, int wide, int depth5, int dep, int reset) {
    seg[n++] = ty | cnt << 3 | kb0 << 9 | mode << 15 | wide << 17 | depth5 << 18 | dep << 19 | reset << 24;
  };
  for (int l = 0; l < 2; l++) {
    const int t = 7 * l;
    if (l == 0) {
      add(0, 12, 4, kModePlain, 1, 0, 31, 1);
      add(1, 16, 0, kModePlain, 1, 0, 31, 0);
    } else {
      add(0, 2, 0, kModeHead, 1, 0, 31, 1);
      add(1, 2, 0, kModeHead, 1, 0, 31, 0);
      add(0, 7, 0, kModeSkip, 1, 0, 6, 0);
      add(0, 7, 1, kModeSkip, 1, 0, 15, 0);
      add(1, 7, 0, kModeSkip, 1, 0, 31, 0);
      add(1, 7, 1, kModeSkip, 1, 0, 31, 0);
    }
    add(2, 4, 0, kModePlain, 0, 0, t, 1);
    add(2, 4, 4, kModePlain, 0, 1, 31, 0);
    add(2, 1, 0, kModeHead, 0, 1, 31, 0);
    add(2, 7, 8, kModeSkip, 0, 1, t + 1, 0);
    add(3, 2, 0, kModeHead, 1, 0, 31, 2);
    add(4, 2, 0, kModeHead, 1, 0, 31, 0);
    add(3, 7, 0, kModeSkip, 1, 0, t + 2, 0);
    add(3, 7, 1, kModeSkip, 1, 0, 14 + 2 * l, 0);
    add(4, 4, 0, kModeSkip, 0, 0, 31, 3);
    add(4, 3, 0, kModeContinue, 0, 1, 31, 0);
    add(4, 7, 1, kModeSkip, 0, 1, 31, 0);
    add(5, 16, 0, kModePlain, 0, 1, 31, 0);
    add(6, 24, 0, kModePlain, 0, 1, t + 3, 0);
    add(6, 16, 24, kModePlain, 0, 1, t + 4, 0);
    add(6, 16, 40, kModePlain, 0, 1, t + 5, 0);
  }
}

typedef CUresult (*EncodeTiledFn)(CUtensorMap*, CUtensorMapDataType, cuuint32_t, void*, const cuuint64_t*,
                                  const cuuint64_t*, const cuuint32_t*, const cuuint32_t*, CUtensorMapInterleave,
                                  CUtensorMapSwizzle, CUtensorMapL2promotion, CUtensorMapFloatOOBfill);

CUtensorMap make_map(EncodeTiledFn enc, const void* p, int rank, const cuuint64_t* dims, const cuuint64_t* strides,
                     const cuuint32_t* box, CUtensorMapSwizzle swizzle = CU_TENSOR_MAP_SWIZZLE_128B) {
  CUtensorMap m;
  const cuuint32_t es[5] = {1, 1, 1, 1, 1};
  enc(&m, CU_TENSOR_MAP_DATA_TYPE_BFLOAT16, rank, const_cast<void*>(p), dims, strides, box, es,
      CU_TENSOR_MAP_INTERLEAVE_NONE, swizzle, CU_TENSOR_MAP_L2_PROMOTION_L2_128B,
      CU_TENSOR_MAP_FLOAT_OOB_FILL_NONE);
  return m;
}

CUtensorMap weight_map(EncodeTiledFn enc, const void* p, int k, int n, int blocks) {
  const cuuint64_t dims[3] = {64, (cuuint64_t)k, (cuuint64_t)n / 64};
  const cuuint64_t strides[2] = {(cuuint64_t)n * 2, 128};
  const cuuint32_t box[3] = {64, 32, (cuuint32_t)blocks};
  return make_map(enc, p, 3, dims, strides, box);
}

CUtensorMap slab_map(EncodeTiledFn enc, const void* p, int n) {
  const cuuint64_t dims[2] = {(cuuint64_t)n, kD};
  const cuuint64_t strides[1] = {(cuuint64_t)n * 2};
  const cuuint32_t box[2] = {128, 128};
  return make_map(enc, p, 2, dims, strides, box, CU_TENSOR_MAP_SWIZZLE_NONE);
}

CUtensorMap token_map(EncodeTiledFn enc, const void* p, int rows) {
  const cuuint64_t dims[2] = {2 * kD, 1024};
  const cuuint64_t strides[1] = {4 * kD};
  const cuuint32_t box[2] = {64, (cuuint32_t)rows};
  return make_map(enc, p, 2, dims, strides, box);
}

}

extern "C" void kernel_launch(void* const* d_in, const int* in_sizes, int n_in, void* d_out, int out_size) {
  (void)in_sizes; (void)n_in; (void)out_size;
  static EncodeTiledFn enc = nullptr;
  if (!enc) {
    void* fn = nullptr;
    cudaDriverEntryPointQueryResult q;
    cudaGetDriverEntryPoint("cuTensorMapEncodeTiled", &fn, cudaEnableDefault, &q);
    enc = (EncodeTiledFn)fn;
    cudaFuncSetAttribute(fused_layers_kernel, cudaFuncAttributeMaxDynamicSharedMemorySize, kSmBytes);
  }
  Params prm;
  prm.b1 = (const __nv_bfloat16*)d_in[5];
  prm.b2 = (const __nv_bfloat16*)d_in[7];
  build_segments(prm.seg);
  const cuuint64_t qd[3] = {kD, kD, 3}, qs[2] = {3 * kD * 2, kD * 2};
  const cuuint32_t qb[3] = {64, 32, 3};
  const CUtensorMap map_x = token_map(enc, d_in[0], 128);
  const CUtensorMap map_out = token_map(enc, d_out, 128);
  const CUtensorMap map_qkv = make_map(enc, d_in[1], 3, qd, qs, qb);
  const CUtensorMap map_wo = weight_map(enc, d_in[2], kD, kD, 2);
  const CUtensorMap map_w1a = weight_map(enc, d_in[4], kD, kF, 3);
  const CUtensorMap map_w1b = weight_map(enc, d_in[4], kD, kF, 2);
  const CUtensorMap map_w2 = weight_map(enc, d_in[6], kF, kD, 2);
  fused_layers_kernel<<<kGrid, 384, kSmBytes>>>(map_x, map_out, map_qkv, map_wo, map_w1a, map_w1b, map_w2,
                                                slab_map(enc, d_in[1], 3 * kD), slab_map(enc, d_in[4], kF), prm);
}
```

```cpp
#include <cuda.h>
#include <cuda_bf16.h>
#include <cuda_runtime.h>
#include <stdint.h>

namespace {

constexpr int kD = 1024;
constexpr int kF = 3584;
constexpr int kCtas = 128;
constexpr int kGrid = 132;
constexpr int kTiles = 14;
constexpr int kTileBytes = 16384;

constexpr int kSmRing = 0;
constexpr int kSmX = 163840;
constexpr int kSmStg = kSmX + 32768;
constexpr int kSmHalo = kSmStg + 16384;
constexpr int kSmCsQ = kSmHalo + 6144;
constexpr int kSmV1 = kSmCsQ + 384 * 4;
constexpr int kSmB2 = kSmV1 + 448 * 8;
constexpr int kSmStat = kSmB2 + 128 * 4;
constexpr int kSmBar = kSmStat + 128 * 8;
constexpr int kBarFull = kSmBar;
constexpr int kBarTurn = kBarFull + 8 * 8;
constexpr int kBarReady = kBarTurn + 14 * 8;
constexpr int kBarPause = kBarReady + 17 * 8;
constexpr int kBarFree = kBarPause + 4 * 8;
constexpr int kBarCs = kBarFree + 14 * 8;
constexpr int kBarInit = kBarCs + 6 * 8;
constexpr int kBarEpoch = kBarInit + 8;
constexpr int kBarEmpty = kBarEpoch + 8;
constexpr int kBarEpi = kBarEmpty + 9 * 8;
constexpr int kBarX = kBarEpi + 14 * 8;
constexpr int kBarStat = kBarX + 8 * 8;
constexpr int kBarResume = kBarStat + 4 * 8;
constexpr int kSmEpoch = kBarResume + 4 * 8;
constexpr int kSmBytes = kSmEpoch + 16;
constexpr int kSegs = 38;

constexpr int kFlagLines = kTiles * 16;

constexpr unsigned kSpinLimit = 1u << 22;

__device__ __align__(1024) uint8_t g_x[16 * 16 * kTileBytes];
__device__ __align__(1024) uint8_t g_o[16 * 16 * kTileBytes];
__device__ __align__(1024) uint8_t g_h[16 * 56 * kTileBytes];
__device__ __align__(128) uint2 g_stat[4 * 16 * 128 * 8];
__device__ __align__(128) unsigned g_cs[3 * kD + kF];
__device__ __align__(128) uint4 g_halo[2 * 16 * 16 * 256];
__device__ __align__(128) unsigned g_flag[kFlagLines * 32];
__device__ unsigned g_ticket;

#define TRACE_AT(tile, k)
#define TRACE_PUB(i, k, c)
#define TRACE_ISSUE(which, nb)

struct Params {
  const __nv_bfloat16* b1;
  const __nv_bfloat16* b2;
  uint32_t seg[kSegs];
};

__device__ __forceinline__ uint32_t smem_u32(const void* p) {
  return (uint32_t)__cvta_generic_to_shared(p);
}
__device__ __forceinline__ uint32_t mapa(uint32_t a, uint32_t cta) {
  uint32_t r;
  asm("mapa.shared::cluster.u32 %0, %1, %2;" : "=r"(r) : "r"(a), "r"(cta));
  return r;
}
__device__ __forceinline__ void mbar_init(uint32_t bar, int cnt) {
  asm volatile("mbarrier.init.shared::cta.b64 [%0], %1;" ::"r"(bar), "r"(cnt) : "memory");
}
__device__ __forceinline__ void mbar_expect_tx(uint32_t bar, uint32_t bytes) {
  asm volatile("mbarrier.arrive.expect_tx.shared::cta.b64 _, [%0], %1;" ::"r"(bar), "r"(bytes) : "memory");
}
__device__ __forceinline__ void mbar_arrive(uint32_t bar) {
  asm volatile("mbarrier.arrive.shared::cta.b64 _, [%0];" ::"r"(bar) : "memory");
}
__device__ __forceinline__ void mbar_arrive_cluster(uint32_t cluster_addr) {
  asm volatile("mbarrier.arrive.shared::cluster.b64 _, [%0];" ::"r"(cluster_addr) : "memory");
}
__device__ __forceinline__ void mbar_wait(uint32_t bar, uint32_t parity) {
  asm volatile("{\n.reg .pred p;\nRETRY:\nmbarrier.try_wait.parity.shared::cta.b64 p, [%0], %1;\n"
               "@!p bra.uni RETRY;\n}" ::"r"(bar), "r"(parity) : "memory");
}
__device__ __forceinline__ void mbar_wait_bounded(uint32_t bar, uint32_t parity) {
  asm volatile("{\n.reg .pred p;\n.reg .u32 c;\nmov.u32 c, 0;\nRETRY:\n"
               "mbarrier.try_wait.parity.shared::cta.b64 p, [%0], %1;\n@p bra.uni DONE;\n"
               "add.u32 c, c, 1;\nsetp.lt.u32 p, c, %2;\n@p bra.uni RETRY;\ntrap;\nDONE:\n}"
               ::"r"(bar), "r"(parity), "n"(1u << 19) : "memory");
}
__device__ __forceinline__ void tma3d(uint32_t dst, const CUtensorMap* m, uint32_t bar, int c0, int c1, int c2) {
  asm volatile(
      "cp.async.bulk.tensor.3d.shared::cluster.global.mbarrier::complete_tx::bytes [%0], [%1, {%3, %4, %5}], [%2];"
      ::"r"(dst), "l"(m), "r"(bar), "r"(c0), "r"(c1), "r"(c2) : "memory");
}
__device__ __forceinline__ void tma3d_mc(uint32_t dst, const CUtensorMap* m, uint32_t bar, int c0, int c1, int c2) {
  asm volatile(
      "cp.async.bulk.tensor.3d.shared::cluster.global.mbarrier::complete_tx::bytes.multicast::cluster"
      " [%0], [%1, {%3, %4, %5}], [%2], %6;"
      ::"r"(dst), "l"(m), "r"(bar), "r"(c0), "r"(c1), "r"(c2), "h"((uint16_t)3) : "memory");
}
__device__ __forceinline__ void tma2d(uint32_t dst, const CUtensorMap* m, uint32_t bar, int c0, int c1) {
  asm volatile(
      "cp.async.bulk.tensor.2d.shared::cluster.global.mbarrier::complete_tx::bytes [%0], [%1, {%3, %4}], [%2];"
      ::"r"(dst), "l"(m), "r"(bar), "r"(c0), "r"(c1) : "memory");
}
__device__ __forceinline__ void tma2d_store(const CUtensorMap* m, uint32_t src, int c0, int c1) {
  asm volatile("cp.async.bulk.tensor.2d.global.shared::cta.bulk_group [%0, {%2, %3}], [%1];"
               ::"l"(m), "r"(src), "r"(c0), "r"(c1) : "memory");
}
__device__ __forceinline__ int lane_id() {
  int l;
  asm volatile("mov.u32 %0, %%laneid;" : "=r"(l));
  return l;
}
__device__ __forceinline__ bool elect() {
  uint32_t p;
  asm volatile("{\n.reg .pred p;\nelect.sync _|p, 0xffffffff;\nselp.b32 %0, 1, 0, p;\n}" : "=r"(p));
  return p;
}
__device__ __forceinline__ void bulk_load(uint32_t dst, const void* src, uint32_t bytes, uint32_t bar) {
  asm volatile("cp.async.bulk.shared::cluster.global.mbarrier::complete_tx::bytes [%0], [%1], %2, [%3];"
               ::"r"(dst), "l"(src), "r"(bytes), "r"(bar) : "memory");
}
__device__ __forceinline__ void bulk_store(void* dst, uint32_t src, uint32_t bytes) {
  asm volatile("cp.async.bulk.global.shared::cta.bulk_group [%0], [%1], %2;" ::"l"(dst), "r"(src), "r"(bytes)
               : "memory");
}
__device__ __forceinline__ void bulk_commit() { asm volatile("cp.async.bulk.commit_group;" ::: "memory"); }
__device__ __forceinline__ void bulk_wait_read() { asm volatile("cp.async.bulk.wait_group.read 0;" ::: "memory"); }
__device__ __forceinline__ void bulk_wait() { asm volatile("cp.async.bulk.wait_group 0;" ::: "memory"); }
__device__ __forceinline__ void fence_async_smem() { asm volatile("fence.proxy.async.shared::cta;" ::: "memory"); }
__device__ __forceinline__ unsigned ld_relaxed(const unsigned* p) {
  unsigned v;
  asm volatile("ld.relaxed.gpu.global.u32 %0, [%1];" : "=r"(v) : "l"(p) : "memory");
  return v;
}
__device__ __forceinline__ uint2 ld_relaxed2(const uint2* p) {
  uint2 v;
  asm volatile("ld.relaxed.gpu.global.v2.u32 {%0, %1}, [%2];" : "=r"(v.x), "=r"(v.y) : "l"(p) : "memory");
  return v;
}
__device__ __forceinline__ void st_relaxed(unsigned* p, unsigned v) {
  asm volatile("st.relaxed.gpu.global.u32 [%0], %1;" ::"l"(p), "r"(v) : "memory");
}
__device__ __forceinline__ void st_release(unsigned* p, unsigned v) {
  asm volatile("st.release.gpu.global.u32 [%0], %1;" ::"l"(p), "r"(v) : "memory");
}
#define ACQ_MODE 1
__device__ __forceinline__ void wait_flags(const unsigned* p, unsigned epoch) {
  unsigned spins = 0;
  while (true) {
    const unsigned v = ld_relaxed(p);
    if (__all_sync(0xffffffffu, v == epoch)) break;
    if (++spins > kSpinLimit) __trap();
  }
  if (ACQ_MODE) asm volatile("fence.acquire.gpu;\nfence.proxy.async.global;" ::: "memory");
  __syncwarp();
}
__device__ __forceinline__ void st_packet(uint4* p, uint32_t d0, uint32_t d1, uint32_t tag) {
  asm volatile("{\n.reg .b128 v;\n.reg .b64 x, y;\nmov.b64 x, {%1, %2};\nmov.b64 y, {%3, %3};\nmov.b128 v, {x, y};\n"
               "st.relaxed.gpu.global.b128 [%0], v;\n}" ::"l"(p), "r"(d0), "r"(d1), "r"(tag) : "memory");
}
__device__ __forceinline__ void ld_packet(const uint4* p, uint32_t& d0, uint32_t& d1, uint32_t& tag) {
  asm volatile("{\n.reg .b128 v;\n.reg .b64 x, y;\n.reg .b32 u;\nld.relaxed.gpu.global.b128 v, [%3];\n"
               "mov.b128 {x, y}, v;\nmov.b64 {%0, %1}, x;\nmov.b64 {%2, u}, y;\n}"
               : "=r"(d0), "=r"(d1), "=r"(tag) : "l"(p) : "memory");
}
__device__ __forceinline__ unsigned tag_value(float v, unsigned epoch) {
  return (__float_as_uint(v) & ~7u) | (epoch & 7u);
}
__device__ __forceinline__ float untag_value(unsigned v) { return __uint_as_float(v & ~7u); }
__device__ __forceinline__ void stsm4(uint32_t a, uint32_t r0, uint32_t r1, uint32_t r2, uint32_t r3) {
  asm volatile("stmatrix.sync.aligned.m8n8.x4.shared.b16 [%0], {%1, %2, %3, %4};" ::"r"(a), "r"(r0), "r"(r1),
               "r"(r2), "r"(r3) : "memory");
}
__device__ __forceinline__ void stsm4_t(uint32_t a, uint32_t r0, uint32_t r1, uint32_t r2, uint32_t r3) {
  asm volatile("stmatrix.sync.aligned.m8n8.x4.trans.shared.b16 [%0], {%1, %2, %3, %4};" ::"r"(a), "r"(r0),
               "r"(r1), "r"(r2), "r"(r3) : "memory");
}
__device__ __forceinline__ uint32_t transpose8(uint32_t a) {
  uint32_t d;
  asm volatile("movmatrix.sync.aligned.m8n8.trans.b16 %0, %1;" : "=r"(d) : "r"(a));
  return d;
}
__device__ __forceinline__ void mma16816(float (&c)[4], uint32_t a0, uint32_t a1, uint32_t a2, uint32_t a3,
                                         uint32_t b0, uint32_t b1) {
  asm volatile("mma.sync.aligned.m16n8k16.row.col.f32.bf16.bf16.f32 {%0, %1, %2, %3}, {%4, %5, %6, %7}, {%8, %9}, "
               "{%0, %1, %2, %3};"
               : "+f"(c[0]), "+f"(c[1]), "+f"(c[2]), "+f"(c[3])
               : "r"(a0), "r"(a1), "r"(a2), "r"(a3), "r"(b0), "r"(b1));
}
__device__ __forceinline__ void mma1688(float (&c)[4], uint32_t a0, uint32_t a1, uint32_t b0) {
  asm volatile("mma.sync.aligned.m16n8k8.row.col.f32.bf16.bf16.f32 {%0, %1, %2, %3}, {%4, %5}, {%6}, {%0, %1, %2, %3};"
               : "+f"(c[0]), "+f"(c[1]), "+f"(c[2]), "+f"(c[3]) : "r"(a0), "r"(a1), "r"(b0));
}
__device__ __forceinline__ float shfl_xor(float v, int m) {
  float r;
  asm volatile("shfl.sync.bfly.b32 %0, %1, %2, 31, 0xffffffff;" : "=f"(r) : "f"(v), "r"(m));
  return r;
}
__device__ __forceinline__ float tanh_fast(float x) {
  float r;
  asm volatile("tanh.approx.f32 %0, %1;" : "=f"(r) : "f"(x));
  return r;
}
__device__ __forceinline__ void ldsm4(uint32_t a, uint32_t (&r)[4]) {
  asm volatile("ldmatrix.sync.aligned.m8n8.x4.shared.b16 {%0, %1, %2, %3}, [%4];"
               : "=r"(r[0]), "=r"(r[1]), "=r"(r[2]), "=r"(r[3]) : "r"(a) : "memory");
}
__device__ __forceinline__ void ldsm4_t(uint32_t a, uint32_t (&r)[4]) {
  asm volatile("ldmatrix.sync.aligned.m8n8.x4.trans.shared.b16 {%0, %1, %2, %3}, [%4];"
               : "=r"(r[0]), "=r"(r[1]), "=r"(r[2]), "=r"(r[3]) : "r"(a) : "memory");
}
__device__ __forceinline__ uint32_t pack2(float lo, float hi) {
  uint32_t r;
  asm volatile("cvt.rn.bf16x2.f32 %0, %1, %2;" : "=r"(r) : "f"(hi), "f"(lo));
  return r;
}
__device__ __forceinline__ float bf_lo(uint32_t r) { return __uint_as_float(r << 16); }
__device__ __forceinline__ float bf_hi(uint32_t r) { return __uint_as_float(r & 0xffff0000u); }
__device__ __forceinline__ float ex2(float x) {
  float r;
  asm("ex2.approx.ftz.f32 %0, %1;" : "=f"(r) : "f"(x));
  return r;
}
__device__ __forceinline__ float rcp(float x) {
  float r;
  asm("rcp.approx.ftz.f32 %0, %1;" : "=f"(r) : "f"(x));
  return r;
}
template <int N>
__device__ __forceinline__ void wg_wait() {
  asm volatile("wgmma.wait_group.sync.aligned %0;" ::"n"(N) : "memory");
}
__device__ __forceinline__ void yield_slot() { asm volatile("pmevent 0;"); }
__device__ __forceinline__ void wg_bar(int wg) { asm volatile("bar.sync %0, 128;" ::"r"(wg + 1) : "memory"); }

template <int N, int KIND>
__device__ __forceinline__ void mma_kblock(float (&acc)[2][96], uint32_t a, uint32_t b);

#define F8(m, d, i) m(d[i]), m(d[i + 1]), m(d[i + 2]), m(d[i + 3]), m(d[i + 4]), m(d[i + 5]), m(d[i + 6]), m(d[i + 7])
#define KSTEP(N, A, B, oa0, oa1, ob, sd)                                                   \
  "add.u32 t, " B ", " #ob ";\nmov.b64 db, {t, hb};\n"                                      \
  "add.u32 t, " A ", " #oa0 ";\nmov.b64 da, {t, ha};\n"                                     \
  "wgmma.mma_async.sync.aligned.m64n" #N "k16.f32.bf16.bf16 {" ACC##N##_0 "}, da, db, " #sd ", 1, 1, 0, 1;\n" \
  "add.u32 t, " A ", " #oa1 ";\nmov.b64 da, {t, ha};\n"                                     \
  "wgmma.mma_async.sync.aligned.m64n" #N "k16.f32.bf16.bf16 {" ACC##N##_1 "}, da, db, " #sd ", 1, 1, 0, 1;\n"

#define MMA_KBLOCK(N, KIND, A, B, ob2, ob3, sd, MID, MODE)                                 \
  template <>                                                                              \
  __device__ __forceinline__ void mma_kblock<N, KIND>(float (&acc)[2][96], uint32_t a, uint32_t b) { \
    asm volatile("{\n.reg .b32 t, ha, hb;\n.reg .b64 da, db;\n"                            \
                 "mov.b32 ha, 0x40000080;\nmov.b32 hb, 0x40000040;\n"                       \
                 "wgmma.fence.sync.aligned;\n"                                             \
                 KSTEP(N, A, B, 0, 64, 0, sd) KSTEP(N, A, B, 2, 66, 128, 1) KSTEP(N, A, B, 4, 68, ob2, 1) \
                 MID KSTEP(N, A, B, 6, 70, ob3, 1) "wgmma.commit_group.sync.aligned;\n}\n"  \
                 : OPS##N(MODE) : "r"(a), "r"(b) : "memory");                              \
  }
#define MMA_KBLOCKS(N, A, B, ob2, ob3)                                                     \
  MMA_KBLOCK(N, 0, A, B, ob2, ob3, 1, "", "+f")                                            \
  MMA_KBLOCK(N, 1, A, B, ob2, ob3, 1, "wgmma.commit_group.sync.aligned;\n", "+f")          \
  MMA_KBLOCK(N, 2, A, B, ob2, ob3, 0, "", "=f")

#define ACC128_0 \
  "%0, %1, %2, %3, %4, %5, %6, %7, %8, %9, %10, %11, %12, %13, %14, %15, " \
  "%16, %17, %18, %19, %20, %21, %22, %23, %24, %25, %26, %27, %28, %29, %30, %31, " \
  "%32, %33, %34, %35, %36, %37, %38, %39, %40, %41, %42, %43, %44, %45, %46, %47, " \
  "%48, %49, %50, %51, %52, %53, %54, %55, %56, %57, %58, %59, %60, %61, %62, %63"
#define ACC128_1 \
  "%64, %65, %66, %67, %68, %69, %70, %71, %72, %73, %74, %75, %76, %77, %78, %79, " \
  "%80, %81, %82, %83, %84, %85, %86, %87, %88, %89, %90, %91, %92, %93, %94, %95, " \
  "%96, %97, %98, %99, %100, %101, %102, %103, %104, %105, %106, %107, %108, %109, %110, %111, " \
  "%112, %113, %114, %115, %116, %117, %118, %119, %120, %121, %122, %123, %124, %125, %126, %127"
#define OPS128(m) \
  F8(m, acc[0], 0), F8(m, acc[0], 8), F8(m, acc[0], 16), F8(m, acc[0], 24), F8(m, acc[0], 32), F8(m, acc[0], 40), F8(m, acc[0], 48), F8(m, acc[0], 56), \
        F8(m, acc[1], 0), F8(m, acc[1], 8), F8(m, acc[1], 16), F8(m, acc[1], 24), F8(m, acc[1], 32), F8(m, acc[1], 40), F8(m, acc[1], 48), F8(m, acc[1], 56)
MMA_KBLOCKS(128, "%128", "%129", 512, 640)

#define ACC192_0 \
  "%0, %1, %2, %3, %4, %5, %6, %7, %8, %9, %10, %11, %12, %13, %14, %15, " \
  "%16, %17, %18, %19, %20, %21, %22, %23, %24, %25, %26, %27, %28, %29, %30, %31, " \
  "%32, %33, %34, %35, %36, %37, %38, %39, %40, %41, %42, %43, %44, %45, %46, %47, " \
  "%48, %49, %50, %51, %52, %53, %54, %55, %56, %57, %58, %59, %60, %61, %62, %63, " \
  "%64, %65, %66, %67, %68, %69, %70, %71, %72, %73, %74, %75, %76, %77, %78, %79, " \
  "%80, %81, %82, %83, %84, %85, %86, %87, %88, %89, %90, %91, %92, %93, %94, %95"
#define ACC192_1 \
  "%96, %97, %98, %99, %100, %101, %102, %103, %104, %105, %106, %107, %108, %109, %110, %111, " \
  "%112, %113, %114, %115, %116, %117, %118, %119, %120, %121, %122, %123, %124, %125, %126, %127, " \
  "%128, %129, %130, %131, %132, %133, %134, %135, %136, %137, %138, %139, %140, %141, %142, %143, " \
  "%144, %145, %146, %147, %148, %149, %150, %151, %152, %153, %154, %155, %156, %157, %158, %159, " \
  "%160, %161, %162, %163, %164, %165, %166, %167, %168, %169, %170, %171, %172, %173, %174, %175, " \
  "%176, %177, %178, %179, %180, %181, %182, %183, %184, %185, %186, %187, %188, %189, %190, %191"
#define OPS192(m) \
  F8(m, acc[0], 0), F8(m, acc[0], 8), F8(m, acc[0], 16), F8(m, acc[0], 24), F8(m, acc[0], 32), F8(m, acc[0], 40), F8(m, acc[0], 48), F8(m, acc[0], 56), F8(m, acc[0], 64), F8(m, acc[0], 72), F8(m, acc[0], 80), F8(m, acc[0], 88), \
        F8(m, acc[1], 0), F8(m, acc[1], 8), F8(m, acc[1], 16), F8(m, acc[1], 24), F8(m, acc[1], 32), F8(m, acc[1], 40), F8(m, acc[1], 48), F8(m, acc[1], 56), F8(m, acc[1], 64), F8(m, acc[1], 72), F8(m, acc[1], 80), F8(m, acc[1], 88)
MMA_KBLOCKS(192, "%192", "%193", 768, 896)

#define TSTEP(REGS, W, X, ow, ox)                                                           \
  "add.u32 t, " X ", " #ox ";\nmov.b64 db, {t, hi};\nadd.u32 t, " W ", " #ow ";\nmov.b64 da, {t, hi};\n" \
  "wgmma.mma_async.sync.aligned.m64n128k16.f32.bf16.bf16 {" REGS "}, da, db, 1, 1, 1, 1, 0;\n"
#define THEAD "{\n.reg .b32 t, hi;\n.reg .b64 da, db;\nmov.b32 hi, 0x40000040;\nwgmma.fence.sync.aligned;\n"
#define TTAIL "wgmma.commit_group.sync.aligned;\n}\n"
__device__ __forceinline__ void mma_kblock_t(float (&acc)[2][96], uint32_t wd, uint32_t xd) {
  asm volatile(THEAD TSTEP(ACC128_0, "%128", "%129", 0, 0) TSTEP(ACC128_1, "%128", "%129", 256, 0)
               TSTEP(ACC128_0, "%128", "%129", 128, 2) TSTEP(ACC128_1, "%128", "%129", 384, 2)
               TSTEP(ACC128_0, "%128", "%129", 512, 4) TSTEP(ACC128_1, "%128", "%129", 768, 4)
               TSTEP(ACC128_0, "%128", "%129", 640, 6) TSTEP(ACC128_1, "%128", "%129", 896, 6) TTAIL
               : OPS128("+f") : "r"(wd), "r"(xd) : "memory");
}
__device__ __forceinline__ void mma_half_t(float (&d)[96], uint32_t wd, uint32_t xd) {
  asm volatile(THEAD TSTEP(ACC128_0, "%64", "%65", 0, 0) TSTEP(ACC128_0, "%64", "%65", 128, 2)
               TSTEP(ACC128_0, "%64", "%65", 512, 4) TSTEP(ACC128_0, "%64", "%65", 640, 6) TTAIL
               : F8("+f", d, 0), F8("+f", d, 8), F8("+f", d, 16), F8("+f", d, 24), F8("+f", d, 32), F8("+f", d, 40),
                 F8("+f", d, 48), F8("+f", d, 56) : "r"(wd), "r"(xd) : "memory");
}

enum { kModePlain = 0, kModeHead = 1, kModeSkip = 2, kModeContinue = 3 };

template <int N>
__device__ __forceinline__ void fence_acc(float (&acc)[2][96]) {
#pragma unroll
  for (int h = 0; h < 2; h++)
#pragma unroll
    for (int i = 0; i < N / 2; i++) asm volatile("" : "+f"(acc[h][i])::"memory");
}

constexpr uint32_t kToB = (kTileBytes >> 4) + ((4096u >> 4) << 16) - (1u << 16);

#define TRACE_KB(nb)

#define HEAD_BOTH 0
template <int N>
__device__ __forceinline__ void head_blocks(float (&acc)[2][96], uint32_t sb, int n0, int slot, int xver,
                                            uint32_t rel_addr, bool rel) {
  const uint32_t ring = (((sb & 0x3FFFF) + kSmRing) >> 4) | (1u << 16);
  const uint32_t xdesc = (((sb & 0x3FFFF) + kSmX) >> 4) | (1u << 16);
  const uint32_t s0 = ring + slot * 2560, s1 = ring + ((slot + 1) & 3) * 2560;
  const uint32_t nb = n0 * 8, xbar = sb + kBarX + (xver - 1) * 16;
  if (xver > 0) {
    mbar_wait(xbar + 8 * HEAD_BOTH, 0);
    mbar_wait(sb + kBarTurn + (xver == 1 ? 2 : 3 * xver) * 8, 0);
  }
  mbar_wait(sb + kBarFull + (nb & 56), nb >> 6);
  if (n0 == 0) TRACE_AT(0, 1);
  TRACE_KB(nb);
  mma_kblock<N, 2>(acc, xver > 0 ? xdesc : s0, s0 + kToB);
  if (xver > 0) mbar_wait(xbar + 8, 0);
  mbar_wait(sb + kBarFull + (nb & 56) + 8, nb >> 6);
  TRACE_KB(nb + 8);
  mma_kblock<N, 0>(acc, xver > 0 ? xdesc + (kTileBytes >> 4) : s1, s1 + kToB);
  wg_wait<1>();
  if (rel) mbar_arrive_cluster(rel_addr + (nb & 56));
  wg_wait<0>();
  if (rel) mbar_arrive_cluster(rel_addr + (nb & 56) + 8);
  fence_acc<N>(acc);
}

template <int N, bool RESID, bool FRESH, class Pre>
__device__ __forceinline__ void mainloop(float (&acc)[2][96], uint32_t sb, int tile, int n0, int slot, int nkb,
                                         int pause_kk, int att, uint32_t rel_addr, bool rel, int own_kk, Pre pre) {
  constexpr uint32_t kStep = (N == 192 ? 5 : 4) * 512;
  const uint32_t ring = (((sb & 0x3FFFF) + kSmRing) >> 4) | (1u << 16);
  uint32_t st = ring + slot * kStep;
  uint32_t nb = n0 * 8, prev = 64;
  const uint32_t last = nb + 8 * (nkb - (RESID ? 3 : 1)), own = nb + 8 * own_kk;
  const uint32_t stg = (((sb & 0x3FFFF) + kSmStg) >> 4) | (1u << 16);
  uint32_t stop = pause_kk >= 0 ? nb + 8 * pause_kk : last;
  const bool signal = (threadIdx.x & 127) == 64;
  if (!FRESH) fence_acc<N>(acc);
  if (tile > 0) mbar_wait(sb + kBarTurn + (tile - 1) * 8, 0);
  TRACE_AT(tile, 0);
  if constexpr (FRESH) {
    mbar_wait(sb + kBarFull + (nb & 56), nb >> 6);
    TRACE_KB(nb);
    mma_kblock<N, 2>(acc, st, st + kToB);
    prev = nb & 56;
    st += kStep;
    nb += 8;
  }
#pragma unroll 1
  while (true) {
#pragma unroll 1
    do {
      mbar_wait(sb + kBarFull + (nb & 56), nb >> 6);
      TRACE_KB(nb);
      if constexpr (RESID) mma_kblock_t(acc, st + kToB, nb == own ? stg : st);
      else mma_kblock<N, 0>(acc, st, st + kToB);
      wg_wait<1>();
      if (rel) mbar_arrive_cluster(rel_addr + prev);
      prev = nb & 56;
      st += kStep;
      if (st == ring + 10240) st = ring;
      nb += 8;
    } while (nb != stop);
    if (stop == last) break;
    stop = last;
    if (signal) mbar_arrive(sb + kBarPause + att * 8);
    wg_wait<0>();
    if (rel) mbar_arrive_cluster(rel_addr + prev);
    prev = 64;
    mbar_wait(sb + kBarResume + att * 8, 0);
  }
  mbar_wait(sb + kBarFull + (nb & 56), nb >> 6);
  TRACE_KB(nb);
  if constexpr (RESID) {
    const uint32_t z = gridDim.y - 1;
    const uint32_t s2 = st + kStep, s3 = s2 == ring + 8192 ? ring : s2 + kStep;
    mma_half_t(acc[0], st + kToB, st);
    wg_wait<1>();
    if (rel) mbar_arrive_cluster(rel_addr + 32);
    mbar_wait(sb + kBarFull + 48, nb >> 6);
    TRACE_KB(nb + 8);
    mma_half_t(acc[0], s2 + kToB, s2);
    mbar_wait(sb + kBarFull + 56, nb >> 6);
    TRACE_KB(nb + 16);
    mma_half_t(acc[0], s3 + kToB, s3);
    mma_half_t(acc[1], st + kToB + 256, st + z);
    mma_half_t(acc[1], s2 + kToB + 256, s2 + z);
    wg_wait<2>();
#pragma unroll
    for (int i = 0; i < 64; i++) asm volatile("" : "+f"(acc[0][i])::"memory");
    pre(0);
    mma_half_t(acc[1], s3 + kToB + 256, s3 + z);
    wg_wait<2>();
    if (rel) mbar_arrive_cluster(rel_addr + 40);
    pre(1);
    wg_wait<1>();
    if (rel) mbar_arrive_cluster(rel_addr + 48);
    if (signal) mbar_arrive(sb + kBarTurn + tile * 8);
    wg_wait<0>();
    if (rel) mbar_arrive_cluster(rel_addr + 56);
#pragma unroll
    for (int i = 0; i < 64; i++) asm volatile("" : "+f"(acc[1][i])::"memory");
  } else {
    mma_kblock<N, 1>(acc, st, st + kToB);
    wg_wait<2>();
    if (rel) mbar_arrive_cluster(rel_addr + prev);
    pre();
    wg_wait<1>();
    if (signal) mbar_arrive(sb + kBarTurn + tile * 8);
    wg_wait<0>();
    if (rel) mbar_arrive_cluster(rel_addr + (nb & 56));
    fence_acc<N>(acc);
  }
}

__device__ __forceinline__ void publish_stats(uint32_t sb, uint2* stat, int w, int lane, unsigned epoch) {
  const uint32_t row = sb + kSmX + (32 * w + lane) * 128;
  float s[4], q[4];
#pragma unroll
  for (int c = 0; c < 4; c++) s[c] = q[c] = 0.f;
  uint32_t nx[4];
  ldsm4(row + ((lane & 7) << 4), nx);
#pragma unroll 1
  for (int J = 1; J <= 16; J++) {
    const uint32_t r[4] = {nx[0], nx[1], nx[2], nx[3]};
    ldsm4(row + ((J >> 3) & 1) * kTileBytes + (((J ^ lane) & 7) << 4), nx);
#pragma unroll
    for (int c = 0; c < 4; c++) {
      const float lo = bf_lo(r[c]);
      s[c] += lo;
      q[c] = fmaf(lo, lo, q[c]);
      if (c & 1) yield_slot();
    }
#pragma unroll
    for (int c = 0; c < 4; c++) {
      const float hi = bf_hi(r[c]);
      s[c] += hi;
      q[c] = fmaf(hi, hi, q[c]);
      if (c & 1) yield_slot();
    }
  }
#pragma unroll
  for (int c = 0; c < 4; c++) {
    s[c] += shfl_xor(s[c], 1);
    q[c] += shfl_xor(q[c], 1);
    s[c] += shfl_xor(s[c], 2);
    q[c] += shfl_xor(q[c], 2);
  }
  const int t = lane & 3, g = lane >> 2;
  const float so = t == 0 ? s[0] : t == 1 ? s[1] : t == 2 ? s[2] : s[3];
  const float qo = t == 0 ? q[0] : t == 1 ? q[1] : t == 2 ? q[2] : q[3];
  asm volatile("st.relaxed.gpu.global.v2.u32 [%0], {%1, %2};" ::"l"(stat + 32 * w + 8 * t + g),
               "r"(tag_value(so, epoch)), "r"(tag_value(qo, epoch)) : "memory");
}

__device__ __forceinline__ void add_chunk(float (&a)[8], const uint4& v) {
  a[0] += bf_lo(v.x); a[1] += bf_hi(v.x);
  a[2] += bf_lo(v.y); a[3] += bf_hi(v.y);
  a[4] += bf_lo(v.z); a[5] += bf_hi(v.z);
  a[6] += bf_lo(v.w); a[7] += bf_hi(v.w);
}

__device__ __forceinline__ int helper_col(int id, int slab) {
  return slab < 6 ? (slab % 3) * kD + (slab / 3) * 512 + id * 128 : (slab - 6) * 512 + id * 128;
}
__device__ __forceinline__ void helper_cta(const CUtensorMap* map_q, const CUtensorMap* map_1, uint8_t* sm,
                                           uint32_t sb, int id, int warp) {
  constexpr int kRed = 6 * 32768, kBar = kRed + 2 * 4096;
  const int tid = threadIdx.x;
  if (warp == 8 && elect()) {
#pragma unroll
    for (int s = 0; s < 6; s++) {
      mbar_init(sb + kBar + s * 8, 1);
      mbar_init(sb + kBar + 64 + s * 8, 4);
    }
    fence_async_smem();
#pragma unroll
    for (int s = 0; s < 6; s++) {
      mbar_expect_tx(sb + kBar + s * 8, 32768);
      tma2d(sb + s * 32768, map_q, sb + kBar + s * 8, id * 128, s * 128);
    }
  }
  __syncthreads();
  if (warp == 8) {
    int slot = 0, ph = 0;
#pragma unroll 1
    for (int n = 6; n < 104; n++) {
      mbar_wait(sb + kBar + 64 + slot * 8, ph);
      if (elect()) {
        mbar_expect_tx(sb + kBar + slot * 8, 32768);
        tma2d(sb + slot * 32768, n < 48 ? map_q : map_1, sb + kBar + slot * 8, helper_col(id, n >> 3), (n & 7) * 128);
      }
      if (++slot == 6) slot = 0, ph ^= 1;
    }
  } else if (warp < 8) {
    if (tid == 0) *reinterpret_cast<unsigned*>(sm + kBar + 128) = atomicAdd(&g_ticket, 1u) / kGrid + 1;
    int slot = warp >> 2, ph = 0;
#pragma unroll 1
    for (int slab = 0; slab < 13; slab++) {
      float a[8];
#pragma unroll
      for (int e = 0; e < 8; e++) a[e] = 0.f;
#pragma unroll 1
      for (int box = 0; box < 4; box++) {
        mbar_wait_bounded(sb + kBar + slot * 8, ph);
        const uint4* p = reinterpret_cast<const uint4*>(sm + slot * 32768) + (tid & 127);
        uint4 v[16];
#pragma unroll
        for (int i = 0; i < 16; i++) v[i] = p[i * 128];
        __syncwarp();
        if (elect()) mbar_arrive(sb + kBar + 64 + slot * 8);
#pragma unroll
        for (int i = 0; i < 16; i++) add_chunk(a, v[i]);
        slot += 2;
        if (slot >= 6) slot -= 6, ph ^= 1;
      }
      float* red = reinterpret_cast<float*>(sm + kRed + (slab & 1) * 4096);
#pragma unroll
      for (int e = 0; e < 8; e++) a[e] += shfl_xor(a[e], 16);
      if ((tid & 16) == 0) {
        float4* d = reinterpret_cast<float4*>(red + warp * 128 + (tid & 15) * 8);
        d[0] = make_float4(a[0], a[1], a[2], a[3]);
        d[1] = make_float4(a[4], a[5], a[6], a[7]);
      }
      asm volatile("bar.sync 1, 256;" ::: "memory");
      if (warp < 4) {
        float t = 0.f;
#pragma unroll
        for (int q = 0; q < 8; q++) t += red[q * 128 + tid];
        st_relaxed(g_cs + (slab < 6 ? 0 : 3 * kD) + helper_col(id, slab) + tid,
                   tag_value(t, *reinterpret_cast<volatile unsigned*>(sm + kBar + 128)));
      }
    }
  }
}

constexpr float kGeluBeta = 0.3292034911525734f;
constexpr float kGeluK = 2.423681954311584f;

__device__ __forceinline__ void store_staged(uint8_t* dst, uint32_t stg) {
  fence_async_smem();
  __syncwarp();
  if (elect()) {
    bulk_store(dst, stg, 4096);
    bulk_commit();
  }
}

#define GY_MASK 0x2a
#define GY_MASK2 0x2a
#define GY(k) if (((CH == 2 ? GY_MASK2 : GY_MASK) >> k) & 1) yield_slot()
template <int CH>
__device__ __forceinline__ void gelu_chunk(const float (&acc)[2][96], const float2 (&st)[4], const float4* vec,
                                           uint32_t stg, int lane, bool chained, uint8_t* prev, uint32_t free_bar) {
  uint32_t pk[8][4];
  float u[3][4], z[3][4];
  vec += lane & 3;
  const uint32_t row = (stg + lane * 128) ^ ((lane & 7) << 4);
  float4 v = vec[CH * 32], vn = v;
#pragma unroll
  for (int s = 0; s < 18; s++) {
    const int J = CH * 8 + (s >> 1), c0 = 2 * (s & 1), cur = s % 3, p1 = (s + 2) % 3, p2 = (s + 1) % 3;
    if (s < 16) {
      if (c0 == 0 && s < 14) vn = vec[(J + 1) * 4];
#pragma unroll
      for (int e = 0; e < 4; e++) {
        const int c = c0 + (e >> 1);
        z[cur][e] = fmaf(st[c].y, e & 1 ? v.y : v.x, e & 1 ? v.w : v.z);
      }
      if (c0 == 2) v = vn;
    }
    if (s >= 1 && s < 17) z[p1][0] = tanh_fast(z[p1][0]);
    GY(0);
    if (s < 16) {
#pragma unroll
      for (int e = 0; e < 4; e++) {
        const int c = c0 + (e >> 1);
        u[cur][e] = fmaf(acc[c & 1][4 * J + c0 + (e & 1)], st[c].x, z[cur][e]);
      }
    }
    if (s >= 1 && s < 17) z[p1][1] = tanh_fast(z[p1][1]);
    GY(1);
    if (s >= 11) {
      const int jj = s - 11;
      stsm4(row ^ (jj << 4), pk[jj][0], pk[jj][1], pk[jj][2], pk[jj][3]);
    }
    if (s < 16) {
#pragma unroll
      for (int e = 0; e < 4; e++) z[cur][e] = fmaf(u[cur][e], u[cur][e], kGeluK);
    }
    if (s >= 1 && s < 17) z[p1][2] = tanh_fast(z[p1][2]);
    GY(3);
    if (s >= 2) {
      pk[(s - 2) >> 1][c0] = pack2(fmaf(u[p2][0], z[p2][0], u[p2][0]), fmaf(u[p2][1], z[p2][1], u[p2][1]));
      pk[(s - 2) >> 1][c0 + 1] = pack2(fmaf(u[p2][2], z[p2][2], u[p2][2]), fmaf(u[p2][3], z[p2][3], u[p2][3]));
    }
    GY(4);
    if (s < 16) {
#pragma unroll
      for (int e = 0; e < 4; e++) z[cur][e] = u[cur][e] * z[cur][e];
    }
    if (s >= 1 && s < 17) z[p1][3] = tanh_fast(z[p1][3]);
    GY(5);
    if (CH < 2 && s == 1 && chained) store_staged(prev, stg);
    if (CH < 2 && s == 10) {
      if (chained) {
        if (elect()) bulk_wait();
        __syncwarp();
      } else {
        mbar_wait(free_bar, 0);
      }
    }
  }
  stsm4(row ^ (7 << 4), pk[7][0], pk[7][1], pk[7][2], pk[7][3]);
}

__device__ __forceinline__ void scale_stats(float2 (&st)[4]) {
#pragma unroll
  for (int c = 0; c < 4; c++) {
    st[c].x *= kGeluBeta;
    st[c].y *= st[c].x;
  }
}

__device__ __forceinline__ void add_mean_term(float (&acc)[2][96], const float2 (&st)[4], uint8_t* sm, int tq,
                                              int lane) {
  const float2* cs = reinterpret_cast<const float2*>(sm + kSmCsQ) + tq * 96 + (lane & 3);
  float2 vn = cs[0];
#pragma unroll
  for (int J = 0; J < 24; J++) {
    const float2 v = vn;
    if (J < 23) vn = cs[J * 4 + 4];
#pragma unroll
    for (int c = 0; c < 4; c++) {
      acc[c & 1][4 * J + (c & 2)] = fmaf(st[c].y, v.x, acc[c & 1][4 * J + (c & 2)]);
      acc[c & 1][4 * J + (c & 2) + 1] = fmaf(st[c].y, v.y, acc[c & 1][4 * J + (c & 2) + 1]);
    }
    yield_slot();
  }
}

#define TWO_PART 0
#define RESUME_LATE 0
#define HALO_AT 2
__device__ __forceinline__ void epilogue_attn(const float (&acc)[2][96], const float2 (&st)[4], uint8_t* sm,
                                              uint32_t sb, int layer, int tq, int b, int j, unsigned epoch, int tile,
                                              int wg, int w, int lane) {
  const int t = lane & 3, g = lane >> 2;
  const int hp = j + 8 * tq, att = 2 * layer + tq;
  uint32_t q[4][8], k[5][8], vt[5][8];
#define SCALED(c, J) pack2(acc[(c) & 1][4 * (J) + ((c) & 2)] * st[c].x, acc[(c) & 1][4 * (J) + ((c) & 2) + 1] * st[c].x)
#pragma unroll
  for (int J = 0; J < 8; J++) vt[4][J] = transpose8(SCALED(3, 16 + J));
#pragma unroll
  for (int J = 0; J < 8; J++) k[4][J] = SCALED(3, 8 + J);
  if (w < 3) {
    uint2* hs = reinterpret_cast<uint2*>(sm + kSmHalo + w * 2048) + lane;
#pragma unroll
    for (int i = 0; i < 4; i++) {
      hs[i * 32] = make_uint2(k[4][2 * i], k[4][2 * i + 1]);
      hs[128 + i * 32] = make_uint2(vt[4][2 * i], vt[4][2 * i + 1]);
    }
  } else if ((b & 7) != 7) {
    uint4* gh = g_halo + ((layer * 16 + b) * 16 + hp) * 256 + lane;
#pragma unroll
    for (int i = 0; i < 4; i++) {
      st_packet(gh + i * 32, k[4][2 * i], k[4][2 * i + 1], epoch);
      st_packet(gh + 128 + i * 32, vt[4][2 * i], vt[4][2 * i + 1], epoch);
    }
  }
#pragma unroll
  for (int c = 0; c < 3; c++)
#pragma unroll
    for (int J = 0; J < 8; J++) {
      k[c + 1][J] = SCALED(c, 8 + J);
      vt[c + 1][J] = transpose8(SCALED(c, 16 + J));
      yield_slot();
    }
  const bool first = w == 0 && (b & 7) == 0;
  const uint4* gh = g_halo + ((layer * 16 + b - 1) * 16 + hp) * 256 + lane;
  uint32_t tag[8];
#define LOAD_HALO()                                                                                    \
  _Pragma("unroll") for (int i = 0; i < 4; i++) {                                                      \
    ld_packet(gh + i * 32, k[0][2 * i], k[0][2 * i + 1], tag[i]);                                      \
    ld_packet(gh + 128 + i * 32, vt[0][2 * i], vt[0][2 * i + 1], tag[4 + i]);                          \
  }
#define AWAIT_HALO()                                                                                   \
  for (unsigned spins = 0;; spins++) {                                                                 \
    const unsigned d0 = (tag[0] ^ epoch) | (tag[1] ^ epoch) | (tag[2] ^ epoch) | (tag[3] ^ epoch);     \
    const unsigned d1 = (tag[4] ^ epoch) | (tag[5] ^ epoch) | (tag[6] ^ epoch) | (tag[7] ^ epoch);     \
    if (__all_sync(0xffffffffu, (d0 | d1) == 0)) break;                                                \
    if (spins > kSpinLimit) __trap();                                                                  \
    LOAD_HALO();                                                                                       \
  }
#pragma unroll
  for (int c = 0; c <= 4; c++) {
    if (c == HALO_AT) {
      if (w == 0 && !first) {
        LOAD_HALO();
      } else {
#pragma unroll
        for (int i = 0; i < 8; i++) k[0][i] = vt[0][i] = tag[i] = 0u;
      }
    }
#pragma unroll
    for (int J = 0; J < 8 && c < 4; J++) {
      q[c & 3][J] = SCALED(c & 3, J);
      if (J & 1) yield_slot();
    }
  }
#undef SCALED
  TRACE_AT(tile, 8);
  wg_bar(wg);
  if (w > 0) {
    const uint2* hs = reinterpret_cast<const uint2*>(sm + kSmHalo + (w - 1) * 2048) + lane;
#pragma unroll
    for (int i = 0; i < 4; i++) {
      const uint2 a = hs[i * 32], c = hs[128 + i * 32];
      k[0][2 * i] = a.x; k[0][2 * i + 1] = a.y;
      vt[0][2 * i] = c.x; vt[0][2 * i + 1] = c.y;
    }
  } else if (!first && tq == 0) {
    AWAIT_HALO();
  }
  constexpr float kScale = 0.17677669529663687f * 1.4426950408889634f;
  const bool own0 = 2 * t <= g, own1 = 2 * t + 1 <= g;
  const uint32_t own_mask = (own0 ? 0xffffu : 0u) | (own1 ? 0xffff0000u : 0u);
  const uint32_t stg = sb + kSmStg + w * 4096;
  const uint32_t orow = stg + (lane & 7) * 128, ochunk = (lane >> 3) ^ (lane & 7);
  TRACE_AT(tile, 9);
  mbar_wait(sb + kBarPause + att * 8, 0);
  TRACE_AT(tile, 10);

  float s[2][6][4], o[2][4][2][4];
  auto scores = [&](int hd, int m) {
    const int ca = 2 * (m / 3), kg = ca + m % 3;
#pragma unroll
    for (int e = 0; e < 4; e++) s[hd][m][e] = 0.f;
#pragma unroll
    for (int J = 4 * hd; J < 4 * hd + 4; J += 2)
      mma16816(s[hd][m], q[ca][J], q[ca + 1][J], q[ca][J + 1], q[ca + 1][J + 1], k[kg][J], k[kg][J + 1]);
  };
  auto attend = [&](int c0, int c1) {
    float v0[2][4], v1[2][4], m[2][4];
#define UNITS _Pragma("unroll") for (int hd = 0; hd < 2; hd++) _Pragma("unroll") for (int c = c0; c < c1; c++)
    UNITS {
      const int mp = 3 * (c >> 1) + (c & 1), r = 2 * (c & 1);
      float p0 = s[hd][mp][r], p1 = s[hd][mp][r + 1];
      if (c == 0 && first) p0 = p1 = -INFINITY;
      v0[hd][c] = own0 ? s[hd][mp + 1][r] : p0;
      v1[hd][c] = own1 ? s[hd][mp + 1][r + 1] : p1;
      m[hd][c] = fmaxf(v0[hd][c], v1[hd][c]);
    }
    UNITS m[hd][c] = fmaxf(m[hd][c], shfl_xor(m[hd][c], 1));
    UNITS m[hd][c] = fmaxf(m[hd][c], shfl_xor(m[hd][c], 2));
    UNITS {
      const float nm = -m[hd][c] * kScale;
      v0[hd][c] = ex2(fmaf(v0[hd][c], kScale, nm));
      v1[hd][c] = ex2(fmaf(v1[hd][c], kScale, nm));
      m[hd][c] = v0[hd][c] + v1[hd][c];
    }
    UNITS m[hd][c] += shfl_xor(m[hd][c], 1);
    UNITS m[hd][c] += shfl_xor(m[hd][c], 2);
    UNITS {
      const float inv = rcp(m[hd][c]);
      const uint32_t p = pack2(v0[hd][c] * inv, v1[hd][c] * inv);
#pragma unroll
      for (int ds = 0; ds < 2; ds++) {
        const int J = 4 * hd + 2 * ds;
#pragma unroll
        for (int e = 0; e < 4; e++) o[hd][c][ds][e] = 0.f;
        if (c & 1) {
          mma16816(o[hd][c][ds], vt[c][J], vt[c][J + 1], vt[c + 1][J], vt[c + 1][J + 1], p & ~own_mask, p & own_mask);
        } else {
          mma1688(o[hd][c][ds], vt[c + 1][J], vt[c + 1][J + 1], p & own_mask);
          mma1688(o[hd][c][ds], vt[c][J], vt[c][J + 1], p & ~own_mask);
        }
      }
    }
  };
  auto stage = [&](int c0, int c1) {
    UNITS stsm4_t(orow + c * 1024 + ((ochunk ^ (4 * hd)) << 4), pack2(o[hd][c][0][0], o[hd][c][0][1]),
                  pack2(o[hd][c][0][2], o[hd][c][0][3]), pack2(o[hd][c][1][0], o[hd][c][1][1]),
                  pack2(o[hd][c][1][2], o[hd][c][1][3]));
#undef UNITS
  };
  if (w == 0 && !first) AWAIT_HALO();
#pragma unroll
  for (int hd = 0; hd < 2; hd++)
#pragma unroll
    for (int m = 0; m < 6; m++) scores(hd, m);
  attend(0, 4);
  yield_slot();
  if (tq == 0 && elect()) mbar_arrive(sb + kBarResume + att * 8);
  TRACE_AT(tile, 11);
  stage(0, 4);
#undef AWAIT_HALO
#undef LOAD_HALO
  fence_async_smem();
  __syncwarp();
  TRACE_AT(tile, 12);
  if (elect()) {
    bulk_store(g_o + (b * 16 + hp) * kTileBytes + w * 4096, stg, 4096);
    bulk_commit();
    if (tq == 1 && !RESUME_LATE) mbar_arrive(sb + kBarResume + att * 8);
    bulk_wait();
    if (tq == 1 && RESUME_LATE) mbar_arrive(sb + kBarResume + att * 8);
    TRACE_AT(tile, 13);
    mbar_arrive(sb + kBarEpi + tile * 8);
  }
  __syncwarp();
}

__device__ __forceinline__ void gather_stats(uint8_t* sm, const uint2* stat, int r, unsigned epoch) {
  uint2 a[8];
  unsigned spins = 0;
  while (true) {
    unsigned diff = 0;
#pragma unroll
    for (int i = 0; i < 8; i++) {
      a[i] = ld_relaxed2(stat + i * 128 + r);
      diff |= (a[i].x ^ epoch) | (a[i].y ^ epoch);
    }
    if (__all_sync(0xffffffffu, (diff & 7u) == 0)) break;
    if (++spins > kSpinLimit) __trap();
    __nanosleep(200);
  }
  float s = 0.f, q = 0.f;
#pragma unroll
  for (int i = 0; i < 8; i++) {
    s += untag_value(a[i].x);
    q += untag_value(a[i].y);
  }
  const float mean = s * (1.f / 1024.f);
  const float var = fmaxf(fmaf(-mean, mean, q * (1.f / 1024.f)), 0.f);
  reinterpret_cast<float2*>(sm + kSmStat)[r] = make_float2(rsqrtf(var + 1e-5f), -mean);
}

__device__ __forceinline__ void gather_colsums(uint8_t* sm, int part, int j, int lane, unsigned epoch) {
#pragma unroll 1
  for (int blk = part < 4 ? 0 : 2 * part - 5; blk < (part < 4 ? 3 : 2 * part - 3); blk++) {
    const int col = part < 2 ? blk * kD + (j + 8 * part) * 64
                             : 3 * kD + 64 * (blk + (blk < 3 ? 3 * j : blk < 5 ? 21 + 2 * j : 35 + 2 * j));
    uint2 v;
    unsigned spins = 0;
    while (true) {
      v = ld_relaxed2(reinterpret_cast<const uint2*>(g_cs + col) + lane);
      if (__all_sync(0xffffffffu, (((v.x ^ epoch) | (v.y ^ epoch)) & 7u) == 0)) break;
      if (++spins > kSpinLimit) __trap();
      __nanosleep(100);
    }
    uint8_t* dst = part < 2 ? sm + kSmCsQ + (part * 96 + blk * 32 + lane) * 8 : sm + kSmV1 + (blk * 32 + lane) * 16;
    *reinterpret_cast<float2*>(dst) = make_float2(untag_value(v.x), untag_value(v.y));
  }
}

#define READBACK 0
#define GATE_B 0
#define LATE_REL2 1
#define XT_LATE 1
#define STAGE_YIELD 1
#define PAUSE_QKV2 7
#define PAUSE_WO 1

__global__ void __cluster_dims__(2, 1, 1) __launch_bounds__(384, 1)
fused_layers_kernel(const __grid_constant__ CUtensorMap map_x, const __grid_constant__ CUtensorMap map_out,
                    const __grid_constant__ CUtensorMap map_qkv, const __grid_constant__ CUtensorMap map_wo,
                    const __grid_constant__ CUtensorMap map_w1a, const __grid_constant__ CUtensorMap map_w1b,
                    const __grid_constant__ CUtensorMap map_w2, const __grid_constant__ CUtensorMap map_csq,
                    const __grid_constant__ CUtensorMap map_cs1, const __grid_constant__ Params prm) {
  extern __shared__ __align__(1024) uint8_t sm[];
  if (threadIdx.x < 128 && blockIdx.x < kCtas) TRACE_AT(15, 1);
  const uint32_t sb = __shfl_sync(0xffffffffu, smem_u32(sm), 0);
  const int warp = __shfl_sync(0xffffffffu, threadIdx.x >> 5, 0), lane = threadIdx.x & 31;
  const int cta = blockIdx.x, rank = cta & 1, cl = cta >> 1;
  const int grp = cl < 4 ? 0 : cl < 36 ? (cl - 4) & 7 : 1 + (cl - 36) % 7;
  const int j = cl < 4 ? 4 + cl : cl < 36 ? (cl - 4) >> 3 : 4 + (cl - 36) / 7;
  const int b = 2 * grp + rank;
  const int xcol = (b >> 3) * kD, xrow = (b & 7) * 128;

  if (cta >= kCtas) {
    helper_cta(&map_csq, &map_cs1, sm, sb, cta - kCtas, warp);
    return;
  }
  if (warp >= 8 && elect()) {
    if (warp == 9) {
#pragma unroll
      for (int s = 0; s < 8; s++) mbar_init(sb + kBarFull + s * 8, 1);
      mbar_init(sb + kBarInit, 1);
      fence_async_smem();
#pragma unroll
      for (int s = 0; s < 4; s++) {
        const uint32_t full = sb + kBarFull + s * 8, dst = sb + kSmRing + s * 40960;
        mbar_expect_tx(full, 40960);
        tma2d(dst, &map_x, full, xcol + (s & 1) * 64, xrow);
        tma3d(dst + kTileBytes, &map_qkv, full, (j + 4 * (s & 2)) * 64, (s & 1) * 64, 0);
        tma3d(dst + kTileBytes + 12288, &map_qkv, full, (j + 4 * (s & 2)) * 64, (s & 1) * 64 + 32, 0);
      }
      if (!XT_LATE) {
        mbar_expect_tx(sb + kBarInit, 32768);
        tma2d(sb + kSmX, &map_x, sb + kBarInit, xcol + j * 128, xrow);
        tma2d(sb + kSmX + kTileBytes, &map_x, sb + kBarInit, xcol + j * 128 + 64, xrow);
      }
    } else if (warp == 8) {
      if (sb & 1023) __trap();
#pragma unroll
      for (int o = kBarTurn; o < kBarPause; o += 8) mbar_init(sb + o, 1);
    } else if (warp == 10) {
#pragma unroll
      for (int o = kBarEpi; o < kSmEpoch; o += 8) mbar_init(sb + o, 4);
    } else {
#pragma unroll
      for (int o = kBarPause; o < kBarEpi; o += 8)
        if (o != kBarInit) mbar_init(sb + o, o < kBarEmpty ? 1 : 2);
    }
    asm volatile("fence.mbarrier_init.release.cluster;" ::: "memory");
  }
  __syncwarp();
  asm volatile("barrier.cluster.arrive.relaxed.aligned;" ::: "memory");

  if (warp >= 8) {
    asm volatile("setmaxnreg.dec.sync.aligned.u32 40;");
    if (warp < 10) {
      asm volatile("barrier.cluster.wait.aligned;" ::: "memory");
      uint32_t nb = 32, off = 0, kb = 0;
#define RING_STEP(ISSUE)                                                  \
  do {                                                                    \
    const uint32_t mb = nb - depth, full = sb + kBarFull + (nb & 56);     \
    if (kb == skip) kb += inc;                                            \
    mbar_wait(sb + kBarEmpty + (mb & 56), mb >> 6);                       \
    if (elect()) { ISSUE; }                                               \
    TRACE_ISSUE(9 - warp, nb);                                            \
    kb += inc;                                                            \
    off = off == wrap ? 0 : off + step;                                   \
    nb += 8;                                                              \
  } while (nb != nend)
#pragma unroll 1
      for (int sg = 0; sg < kSegs; sg++) {
        const uint32_t e = prm.seg[sg];
        const int ty = e & 7, mode = (e >> 15) & 3, reset = (e >> 24) & 3;
        const uint32_t nend = nb + (e & 0x1f8);
        const uint32_t step = (e >> 17) & 1 ? 40960 : 32768, wrap = 163840 - step;
        const uint32_t depth = (e >> 18) & 1 ? 40 : 32;
        if (reset) off = reset == 1 ? 0 : reset == 2 ? 40960 : 131072;
        const uint32_t own = ty == 2 ? 8 + j : 2 * j;
        if (mode != kModeContinue) kb = mode == kModeHead ? own : (e >> 9) & 63;
        const uint32_t inc = mode >= kModeSkip && ty != 2 ? 2 : 1, skip = mode >= kModeSkip ? own + (kb & 1) : 255;
        if (warp == 8) {
          const CUtensorMap* map = ty < 2 ? &map_qkv : ty == 2 ? &map_wo : ty == 3 ? &map_w1a : ty < 6 ? &map_w1b : &map_w2;
          const int c0 = ty < 2 ? (j + 8 * ty) * 64 : 0;
          const int c2 = ty < 2 ? 0 : ty == 3 ? 3 * j : ty == 4 ? 24 + 2 * j : ty == 5 ? 40 + 2 * j : 2 * j;
          const uint32_t half = (ty < 2 || ty == 3) ? 12288 : 8192;
          const uint32_t bytes = 2 * half + (mode == kModeHead ? 0 : kTileBytes);
          const uint32_t dst = sb + kSmRing + kTileBytes + rank * half;
          if (GATE_B) {
            const int dep = (e >> 19) & 31;
            if (dep == 2 || dep == 6 || dep == 9) mbar_wait(sb + kBarFree + dep * 8, 0);
          }
#pragma unroll 1
          RING_STEP(mbar_expect_tx(full, bytes); tma3d_mc(dst + off, map, full, c0, kb * 64 + rank * 32, c2));
        } else if (mode == kModeHead) {
          off += ((nend - nb) >> 3) * step;
          nb = nend;
          if (off >= 163840) off -= 163840;
        } else if (sg < 2) {
#pragma unroll 1
          RING_STEP(tma2d(sb + kSmRing + off, &map_x, full, xcol + kb * 64, xrow));
        } else {
          const uint8_t* src = ty == 6 ? g_h + b * 56 * kTileBytes : (ty == 2 ? g_o : g_x) + b * 16 * kTileBytes;
          const int dep = (e >> 19) & 31;
          if (dep != 31) mbar_wait(sb + kBarReady + dep * 8, 0);
#pragma unroll 1
          RING_STEP(bulk_load(sb + kSmRing + off, src + kb * kTileBytes, kTileBytes, full));
        }
      }
#undef RING_STEP
    } else if (warp == 10) {
      unsigned epoch = 0;
      if (lane == 0) epoch = atomicAdd(&g_ticket, 1u) / kGrid + 1;
      epoch = __shfl_sync(0xffffffffu, epoch, 0);
      *reinterpret_cast<unsigned*>(sm + kSmEpoch) = epoch;
      asm volatile("barrier.cluster.wait.aligned;" ::: "memory");
      if (elect()) mbar_arrive(sb + kBarEpoch);
#pragma unroll 1
      for (int i = 0; i < kTiles - 1; i++) {
        const bool xt = i == 2 || i == 6 || i == 9;
        const unsigned* line = g_flag + (i * 16 + b) * 32;
        mbar_wait(sb + (xt ? kBarX + (i >> 2) * 16 : kBarEpi + i * 8), 0);
        wait_flags(line + (lane & 7), epoch);
        if (elect()) mbar_arrive(sb + kBarReady + i * 8);
        if (xt) {
          wait_flags(line + 8 + (lane & 7), epoch);
          if (elect()) mbar_arrive(sb + kBarReady + (14 + (i >> 2)) * 8);
        }
      }
    } else {
      asm volatile("barrier.cluster.wait.aligned;" ::: "memory");
      if (XT_LATE) {
        mbar_wait_bounded(sb + kBarFull + 8 * (XT_LATE - 1), 0);
        if (elect()) {
          mbar_expect_tx(sb + kBarInit, 32768);
          tma2d(sb + kSmX, &map_x, sb + kBarInit, xcol + j * 128, xrow);
          tma2d(sb + kSmX + kTileBytes, &map_x, sb + kBarInit, xcol + j * 128 + 64, xrow);
        }
      }
      {
        uint32_t v[7];
#pragma unroll
        for (int q = 0; q < 7; q++)
          v[q] = reinterpret_cast<const uint32_t*>(prm.b1)[32 * (q + (q < 3 ? 3 * j : q < 5 ? 21 + 2 * j : 35 + 2 * j)) + lane];
        const uint2 u = reinterpret_cast<const uint2*>(prm.b2)[32 * j + lane];
#pragma unroll
        for (int q = 0; q < 7; q++)
          *reinterpret_cast<float2*>(sm + kSmV1 + (q * 32 + lane) * 16 + 8) = make_float2(kGeluBeta * bf_lo(v[q]), kGeluBeta * bf_hi(v[q]));
        reinterpret_cast<float4*>(sm + kSmB2)[lane] = make_float4(
            2.f * kGeluBeta * bf_lo(u.x), 2.f * kGeluBeta * bf_hi(u.x), 2.f * kGeluBeta * bf_lo(u.y), 2.f * kGeluBeta * bf_hi(u.y));
      }
      mbar_wait_bounded(sb + kBarEpoch, 0);
      const unsigned epoch = *reinterpret_cast<volatile unsigned*>(sm + kSmEpoch);
#pragma unroll 1
      for (int i = 0; i < kTiles - 1; i++) {
#pragma unroll 1
        for (int part = i == 4 ? 5 : i; part < (i < 2 ? i + 1 : i == 3 || i == 4 ? i + 2 : 0); part++) {
          gather_colsums(sm, part, j, lane, epoch);
          __syncwarp();
          if (elect()) mbar_arrive(sb + kBarCs + part * 8);
        }
        const bool xt = i == 2 || i == 6 || i == 9;
#pragma unroll 1
        for (int h = 0; h < (xt ? 2 : 1); h++) {
          mbar_wait_bounded(sb + (xt ? kBarX + (i >> 2) * 16 + 8 * h : kBarEpi + i * 8), 0);
          const int ty = i >= 7 ? i - 7 : i;
          if (ty >= 2 && elect()) {
            uint8_t* dst = xt ? g_x + (b * 16 + 2 * j + h) * kTileBytes
                              : g_h + (b * 56 + 1 + (ty == 3 ? 3 * j : 16 * ty - 40 + 2 * j)) * kTileBytes;
            bulk_store(dst, sb + (xt ? kSmX + h * kTileBytes : kSmStg), kTileBytes);
            bulk_commit();
            bulk_wait();
            if (!xt) mbar_arrive(sb + kBarFree + i * 8);
          }
          if (LATE_REL2 && h == 1) mbar_wait_bounded(sb + kBarFull + 32, i == 2 ? 6 : i == 6 ? 19 : 25);
          __syncwarp();
          if (elect()) st_release(&g_flag[(i * 16 + b) * 32 + h * 8 + j], epoch);
          __syncwarp();
          if (xt && h == 0 && elect()) mbar_arrive(sb + kBarFree + i * 8);
        }
      }
#pragma unroll 1
      for (int h = 0; h < 2; h++) {
        mbar_wait_bounded(sb + kBarX + 48 + 8 * h, 0);
        if (elect()) {
          tma2d_store(&map_out, sb + kSmX + h * kTileBytes, xcol + j * 128 + h * 64, xrow);
          bulk_commit();
          if (h == 1) bulk_wait_read();
        }
      }
    }
    __syncwarp();
    asm volatile("barrier.cluster.arrive.relaxed.aligned;\nbarrier.cluster.wait.aligned;" ::: "memory");
  } else {
    asm volatile("setmaxnreg.inc.sync.aligned.u32 232;");
    asm volatile("barrier.cluster.wait.aligned;" ::: "memory");
    const int wg = warp >> 2, w = warp & 3;
    const bool rel = (threadIdx.x & 95) == 0;
    const uint32_t rel_addr = mapa(sb + kBarEmpty, w & 1);
    if (wg == 1) TRACE_AT(15, 0);
#define EPOCH (*reinterpret_cast<volatile unsigned*>(sm + kSmEpoch))

#pragma unroll 1
    for (int i = wg; i < kTiles; i += 2) {
      const int layer = i >= 7, ty = i - 7 * layer;
      TRACE_AT(i, 15);
      float acc[2][96];
      if (ty == 2 || ty == 6) {
        const int lane = lane_id();
        const uint32_t xa = sb + kSmX + ((lane >> 4) * 8 + (lane & 7)) * 128 + (((2 * w + ((lane >> 3) & 1)) ^ (lane & 7)) << 4);
        const float up = ty == 6 ? 2.f * kGeluBeta : 1.f, dn = ty == 6 ? 0.5f / kGeluBeta : 1.f;
#pragma unroll
        for (int h = 0; h < 2; h++) {
          const float* b2 = reinterpret_cast<const float*>(sm + kSmB2) + 64 * h + 16 * w + (lane >> 2);
          const float bias[2] = {ty == 6 ? b2[0] : 0.f, ty == 6 ? b2[8] : 0.f};
#pragma unroll
          for (int p = 0; p < 8; p++) {
            uint32_t r[4];
            ldsm4_t(xa + h * kTileBytes + p * 2048, r);
#pragma unroll
            for (int m = 0; m < 4; m++) {
              acc[h][8 * p + 2 * m] = fmaf(bf_lo(r[m]), up, bias[m & 1]);
              acc[h][8 * p + 2 * m + 1] = fmaf(bf_hi(r[m]), up, bias[m & 1]);
              asm volatile("" : "+f"(acc[h][8 * p + 2 * m]), "+f"(acc[h][8 * p + 2 * m + 1]));
              if (m & 1) yield_slot();
            }
          }
        }
        auto stage = [&](int qt) {
          const int h = qt >> 1;
#pragma unroll
          for (int p = 4 * (qt & 1); p < 4 * (qt & 1) + 4; p++) {
            const float* a = &acc[h][8 * p];
            stsm4_t(xa + h * kTileBytes + p * 2048, pack2(a[0] * dn, a[1] * dn), pack2(a[2] * dn, a[3] * dn),
                    pack2(a[4] * dn, a[5] * dn), pack2(a[6] * dn, a[7] * dn));
            if (STAGE_YIELD || (p & 3) == 3) yield_slot();
          }
          if (qt & 1) {
            fence_async_smem();
            __syncwarp();
            if (elect()) mbar_arrive(sb + kBarX + (i >> 2) * 16 + 8 * h);
            TRACE_AT(i, 8 + h);
          }
        };
        mainloop<128, true, false>(acc, sb, i, layer * 152 + ty * 16, ty == 6 ? 4 : 0, ty == 6 ? 56 : 16,
                            ty == 2 ? PAUSE_WO : -1, 2 * layer + 1, rel_addr, rel, ty == 2 ? 8 : -1, stage);
        TRACE_AT(i, 2);
        stage(2);
        stage(3);
      } else {
        const int xver = 2 * layer + (ty >= 3);
        const uint32_t stg = sb + kSmStg + w * 4096;
        const float4* vec = reinterpret_cast<const float4*>(sm + kSmV1) + (ty == 3 ? 0 : 64 * ty - 160);
        int lane;
        uint8_t* hdst = g_h + (b * 56 + (ty == 3 ? 3 * j : 16 * ty - 40 + 2 * j)) * kTileBytes + w * 4096;
        float2 st[4];
        unsigned epoch;
        auto pre = [&] {
          lane = lane_id();
          if (ty < 4) mbar_wait(sb + (ty == 1 ? kBarEpi + (i - 1) * 8 : kBarStat + xver * 8), 0);
#pragma unroll
          for (int c = 0; c < 4; c++) st[c] = reinterpret_cast<const float2*>(sm + kSmStat)[32 * w + 8 * c + (lane >> 2)];
          epoch = EPOCH;
        };
        auto team_stats = [&] {
          uint2* stat = g_stat + (xver * 16 + b) * 1024;
          lane = lane_id();
          publish_stats(sb, stat + j * 128, w, lane, EPOCH);
          gather_stats(sm, stat, 32 * w + lane, EPOCH);
          __syncwarp();
          if (elect()) mbar_arrive(sb + kBarStat + xver * 8);
          TRACE_AT(i, 14);
        };
        if (ty < 4) {
          head_blocks<192>(acc, sb, layer * 152 + (ty < 2 ? 2 * ty : 48), ty < 2 ? 2 * ty : 1, xver, rel_addr, rel);
          if (ty == 1) {
            if (i == 1) {
              mbar_wait(sb + kBarEpoch, 0);
              mbar_wait(sb + kBarInit, 0);
            }
            team_stats();
            if (i == 8) {
#pragma unroll
              for (int c = 0; c < 4; c++) st[c] = reinterpret_cast<const float2*>(sm + kSmStat)[32 * w + 8 * c + (lane >> 2)];
              add_mean_term(acc, st, sm, 1, lane);
            }
          }
          mainloop<192, false, false>(acc, sb, i, layer * 152 + (ty < 2 ? 4 + 14 * ty : 52), ty < 2 ? 2 * ty : 1, 14,
                                      ty == 1 ? PAUSE_QKV2 : -1, xver, rel_addr, rel, 0, pre);
          TRACE_AT(i, 2);
          if (layer == 0) mbar_wait(sb + kBarCs + ty * 8, 0);
          if (ty < 2) {
            if (i != 8) add_mean_term(acc, st, sm, ty, lane);
            epilogue_attn(acc, st, sm, sb, layer, ty, b, j, epoch, i, wg, w, lane);
            TRACE_AT(i, 3);
            continue;
          }
          scale_stats(st);
          gelu_chunk<2>(acc, st, vec, stg, lane, false, nullptr, 0);
        } else {
          if (ty == 4) {
            head_blocks<128>(acc, sb, layer * 152 + 50, 3, xver, rel_addr, rel);
            team_stats();
            mainloop<128, false, false>(acc, sb, i, layer * 152 + 66, 4, 14, -1, 0, rel_addr, rel, 0, pre);
          } else {
            mainloop<128, false, true>(acc, sb, i, layer * 152 + 80, 3, 16, -1, 0, rel_addr, rel, 0, pre);
          }
          TRACE_AT(i, 2);
          if (layer == 0) mbar_wait(sb + kBarCs + ty * 8, 0);
          scale_stats(st);
        }
        TRACE_AT(i, 8);
        gelu_chunk<0>(acc, st, vec, stg, lane, ty == 3, hdst + 2 * kTileBytes, sb + kBarFree + (i - 1) * 8);
        TRACE_AT(i, 9);
        gelu_chunk<1>(acc, st, vec, stg, lane, true, hdst, 0);
        TRACE_AT(i, 10);
        fence_async_smem();
        __syncwarp();
        if (elect()) mbar_arrive(sb + kBarEpi + i * 8);
      }
      TRACE_AT(i, 3);
    }
#undef EPOCH
    asm volatile("barrier.cluster.arrive.relaxed.aligned;\nbarrier.cluster.wait.aligned;" ::: "memory");
    if (wg == 1) TRACE_AT(15, 2);
  }
}

void build_segments(uint32_t* seg) {
  int n = 0;
  auto add = [&](int ty, int cnt, int kb0, int mode, int wide, int depth5, int dep, int reset) {
    seg[n++] = ty | cnt << 3 | kb0 << 9 | mode << 15 | wide << 17 | depth5 << 18 | dep << 19 | reset << 24;
  };
  for (int l = 0; l < 2; l++) {
    const int t = 7 * l;
    if (l == 0) {
      add(0, 14, 2, kModePlain, 1, 0, 31, 1);
      add(1, 14, 2, kModePlain, 1, 0, 31, 0);
    } else {
      add(0, 2, 0, kModeHead, 1, 0, 31, 1);
      add(1, 2, 0, kModeHead, 1, 0, 31, 0);
      add(0, 7, 0, kModeSkip, 1, 0, 6, 0);
      add(0, 7, 1, kModeSkip, 1, 0, 15, 0);
      add(1, 7, 0, kModeSkip, 1, 0, 31, 0);
      add(1, 7, 1, kModeSkip, 1, 0, 31, 0);
    }
    add(2, 4, 0, kModePlain, 0, 0, t, 1);
    add(2, 4, 4, kModePlain, 0, 1, 31, 0);
    add(2, 1, 0, kModeHead, 0, 1, 31, 0);
    add(2, 7, 8, kModeSkip, 0, 1, t + 1, 0);
    add(3, 2, 0, kModeHead, 1, 0, 31, 2);
    add(4, 2, 0, kModeHead, 1, 0, 31, 0);
    add(3, 7, 0, kModeSkip, 1, 0, t + 2, 0);
    add(3, 7, 1, kModeSkip, 1, 0, 14 + 2 * l, 0);
    add(4, 4, 0, kModeSkip, 0, 0, 31, 3);
    add(4, 3, 0, kModeContinue, 0, 1, 31, 0);
    add(4, 7, 1, kModeSkip, 0, 1, 31, 0);
    add(5, 16, 0, kModePlain, 0, 1, 31, 0);
    add(6, 24, 0, kModePlain, 0, 1, t + 3, 0);
    add(6, 16, 24, kModePlain, 0, 1, t + 4, 0);
    add(6, 16, 40, kModePlain, 0, 1, t + 5, 0);
  }
}

typedef CUresult (*EncodeTiledFn)(CUtensorMap*, CUtensorMapDataType, cuuint32_t, void*, const cuuint64_t*,
                                  const cuuint64_t*, const cuuint32_t*, const cuuint32_t*, CUtensorMapInterleave,
                                  CUtensorMapSwizzle, CUtensorMapL2promotion, CUtensorMapFloatOOBfill);

CUtensorMap make_map(EncodeTiledFn enc, const void* p, int rank, const cuuint64_t* dims, const cuuint64_t* strides,
                     const cuuint32_t* box, CUtensorMapSwizzle swizzle = CU_TENSOR_MAP_SWIZZLE_128B) {
  CUtensorMap m;
  const cuuint32_t es[5] = {1, 1, 1, 1, 1};
  enc(&m, CU_TENSOR_MAP_DATA_TYPE_BFLOAT16, rank, const_cast<void*>(p), dims, strides, box, es,
      CU_TENSOR_MAP_INTERLEAVE_NONE, swizzle, CU_TENSOR_MAP_L2_PROMOTION_L2_128B,
      CU_TENSOR_MAP_FLOAT_OOB_FILL_NONE);
  return m;
}

CUtensorMap weight_map(EncodeTiledFn enc, const void* p, int k, int n, int blocks) {
  const cuuint64_t dims[3] = {64, (cuuint64_t)k, (cuuint64_t)n / 64};
  const cuuint64_t strides[2] = {(cuuint64_t)n * 2, 128};
  const cuuint32_t box[3] = {64, 32, (cuuint32_t)blocks};
  return make_map(enc, p, 3, dims, strides, box);
}

CUtensorMap slab_map(EncodeTiledFn enc, const void* p, int n) {
  const cuuint64_t dims[2] = {(cuuint64_t)n, kD};
  const cuuint64_t strides[1] = {(cuuint64_t)n * 2};
  const cuuint32_t box[2] = {128, 128};
  return make_map(enc, p, 2, dims, strides, box, CU_TENSOR_MAP_SWIZZLE_NONE);
}

CUtensorMap token_map(EncodeTiledFn enc, const void* p, int rows) {
  const cuuint64_t dims[2] = {2 * kD, 1024};
  const cuuint64_t strides[1] = {4 * kD};
  const cuuint32_t box[2] = {64, (cuuint32_t)rows};
  return make_map(enc, p, 2, dims, strides, box);
}

}

extern "C" void kernel_launch(void* const* d_in, const int* in_sizes, int n_in, void* d_out, int out_size) {
  (void)in_sizes; (void)n_in; (void)out_size;
  static EncodeTiledFn enc = nullptr;
  if (!enc) {
    void* fn = nullptr;
    cudaDriverEntryPointQueryResult q;
    cudaGetDriverEntryPoint("cuTensorMapEncodeTiled", &fn, cudaEnableDefault, &q);
    enc = (EncodeTiledFn)fn;
    cudaFuncSetAttribute(fused_layers_kernel, cudaFuncAttributeMaxDynamicSharedMemorySize, kSmBytes);
  }
  Params prm;
  prm.b1 = (const __nv_bfloat16*)d_in[5];
  prm.b2 = (const __nv_bfloat16*)d_in[7];
  build_segments(prm.seg);
  const cuuint64_t qd[3] = {kD, kD, 3}, qs[2] = {3 * kD * 2, kD * 2};
  const cuuint32_t qb[3] = {64, 32, 3};
  const CUtensorMap map_x = token_map(enc, d_in[0], 128);
  const CUtensorMap map_out = token_map(enc, d_out, 128);
  const CUtensorMap map_qkv = make_map(enc, d_in[1], 3, qd, qs, qb);
  const CUtensorMap map_wo = weight_map(enc, d_in[2], kD, kD, 2);
  const CUtensorMap map_w1a = weight_map(enc, d_in[4], kD, kF, 3);
  const CUtensorMap map_w1b = weight_map(enc, d_in[4], kD, kF, 2);
  const CUtensorMap map_w2 = weight_map(enc, d_in[6], kF, kD, 2);
  fused_layers_kernel<<<kGrid, 384, kSmBytes>>>(map_x, map_out, map_qkv, map_wo, map_w1a, map_w1b, map_w2,
                                                slab_map(enc, d_in[1], 3 * kD), slab_map(enc, d_in[4], kF), prm);
}
```

```cpp
#include <cuda.h>
#include <cuda_bf16.h>
#include <cuda_runtime.h>
#include <stdint.h>

namespace {

constexpr int kD = 1024;
constexpr int kF = 3584;
constexpr int kCtas = 128;
constexpr int kGrid = 132;
constexpr int kTiles = 14;
constexpr int kTileBytes = 16384;

constexpr int kSmRing = 0;
constexpr int kSmX = 163840;
constexpr int kSmStg = kSmX + 32768;
constexpr int kSmHalo = kSmStg + 16384;
constexpr int kSmCsQ = kSmHalo + 6144;
constexpr int kSmV1 = kSmCsQ + 384 * 4;
constexpr int kSmB2 = kSmV1 + 448 * 8;
constexpr int kSmStat = kSmB2 + 128 * 4;
constexpr int kSmBar = kSmStat + 128 * 8;
constexpr int kBarFull = kSmBar;
constexpr int kBarTurn = kBarFull + 8 * 8;
constexpr int kBarReady = kBarTurn + 14 * 8;
constexpr int kBarSrc = kBarReady + 17 * 8;
constexpr int kBarPause = kBarSrc + 8 * 8;
constexpr int kBarFree = kBarPause + 4 * 8;
constexpr int kBarCs = kBarFree + 14 * 8;
constexpr int kBarInit = kBarCs + 6 * 8;
constexpr int kBarEpoch = kBarInit + 8;
constexpr int kBarEmpty = kBarEpoch + 8;
constexpr int kBarEpi = kBarEmpty + 9 * 8;
constexpr int kBarX = kBarEpi + 14 * 8;
constexpr int kBarStat = kBarX + 8 * 8;
constexpr int kBarResume = kBarStat + 4 * 8;
constexpr int kSmEpoch = kBarResume + 4 * 8;
constexpr int kSmBytes = kSmEpoch + 16;
constexpr int kSegs = 38;

constexpr int kFlagLines = kTiles * 16;

constexpr unsigned kSpinLimit = 1u << 22;

__device__ __align__(1024) uint8_t g_x[16 * 16 * kTileBytes];
__device__ __align__(1024) uint8_t g_o[16 * 16 * kTileBytes];
__device__ __align__(1024) uint8_t g_h[16 * 56 * kTileBytes];
__device__ __align__(128) uint2 g_stat[4 * 16 * 128 * 8];
__device__ __align__(128) unsigned g_cs[3 * kD + kF];
__device__ __align__(128) uint4 g_halo[2 * 16 * 16 * 256];
__device__ __align__(128) unsigned g_flag[kFlagLines * 32];
__device__ unsigned g_ticket;

#define TRACE_AT(tile, k)
#define TRACE_PUB(i, k, c)
#define TRACE_ISSUE(which, nb)

struct Params {
  const __nv_bfloat16* b1;
  const __nv_bfloat16* b2;
  uint32_t seg[kSegs];
};

__device__ __forceinline__ uint32_t smem_u32(const void* p) {
  return (uint32_t)__cvta_generic_to_shared(p);
}
__device__ __forceinline__ uint32_t mapa(uint32_t a, uint32_t cta) {
  uint32_t r;
  asm("mapa.shared::cluster.u32 %0, %1, %2;" : "=r"(r) : "r"(a), "r"(cta));
  return r;
}
__device__ __forceinline__ void mbar_init(uint32_t bar, int cnt) {
  asm volatile("mbarrier.init.shared::cta.b64 [%0], %1;" ::"r"(bar), "r"(cnt) : "memory");
}
__device__ __forceinline__ void mbar_expect_tx(uint32_t bar, uint32_t bytes) {
  asm volatile("mbarrier.arrive.expect_tx.shared::cta.b64 _, [%0], %1;" ::"r"(bar), "r"(bytes) : "memory");
}
__device__ __forceinline__ void mbar_arrive(uint32_t bar) {
  asm volatile("mbarrier.arrive.shared::cta.b64 _, [%0];" ::"r"(bar) : "memory");
}
__device__ __forceinline__ void mbar_arrive_cluster(uint32_t cluster_addr) {
  asm volatile("mbarrier.arrive.shared::cluster.b64 _, [%0];" ::"r"(cluster_addr) : "memory");
}
__device__ __forceinline__ void mbar_wait(uint32_t bar, uint32_t parity) {
  asm volatile("{\n.reg .pred p;\nRETRY:\nmbarrier.try_wait.parity.shared::cta.b64 p, [%0], %1;\n"
               "@!p bra.uni RETRY;\n}" ::"r"(bar), "r"(parity) : "memory");
}
__device__ __forceinline__ void mbar_wait_bounded(uint32_t bar, uint32_t parity) {
  asm volatile("{\n.reg .pred p;\n.reg .u32 c;\nmov.u32 c, 0;\nRETRY:\n"
               "mbarrier.try_wait.parity.shared::cta.b64 p, [%0], %1;\n@p bra.uni DONE;\n"
               "add.u32 c, c, 1;\nsetp.lt.u32 p, c, %2;\n@p bra.uni RETRY;\ntrap;\nDONE:\n}"
               ::"r"(bar), "r"(parity), "n"(1u << 19) : "memory");
}
__device__ __forceinline__ void tma3d(uint32_t dst, const CUtensorMap* m, uint32_t bar, int c0, int c1, int c2) {
  asm volatile(
      "cp.async.bulk.tensor.3d.shared::cluster.global.mbarrier::complete_tx::bytes [%0], [%1, {%3, %4, %5}], [%2];"
      ::"r"(dst), "l"(m), "r"(bar), "r"(c0), "r"(c1), "r"(c2) : "memory");
}
__device__ __forceinline__ void tma3d_mc(uint32_t dst, const CUtensorMap* m, uint32_t bar, int c0, int c1, int c2) {
  asm volatile(
      "cp.async.bulk.tensor.3d.shared::cluster.global.mbarrier::complete_tx::bytes.multicast::cluster"
      " [%0], [%1, {%3, %4, %5}], [%2], %6;"
      ::"r"(dst), "l"(m), "r"(bar), "r"(c0), "r"(c1), "r"(c2), "h"((uint16_t)3) : "memory");
}
__device__ __forceinline__ void tma2d(uint32_t dst, const CUtensorMap* m, uint32_t bar, int c0, int c1) {
  asm volatile(
      "cp.async.bulk.tensor.2d.shared::cluster.global.mbarrier::complete_tx::bytes [%0], [%1, {%3, %4}], [%2];"
      ::"r"(dst), "l"(m), "r"(bar), "r"(c0), "r"(c1) : "memory");
}
__device__ __forceinline__ void tma2d_store(const CUtensorMap* m, uint32_t src, int c0, int c1) {
  asm volatile("cp.async.bulk.tensor.2d.global.shared::cta.bulk_group [%0, {%2, %3}], [%1];"
               ::"l"(m), "r"(src), "r"(c0), "r"(c1) : "memory");
}
__device__ __forceinline__ int lane_id() {
  int l;
  asm volatile("mov.u32 %0, %%laneid;" : "=r"(l));
  return l;
}
__device__ __forceinline__ bool elect() {
  uint32_t p;
  asm volatile("{\n.reg .pred p;\nelect.sync _|p, 0xffffffff;\nselp.b32 %0, 1, 0, p;\n}" : "=r"(p));
  return p;
}
__device__ __forceinline__ void bulk_load(uint32_t dst, const void* src, uint32_t bytes, uint32_t bar) {
  asm volatile("cp.async.bulk.shared::cluster.global.mbarrier::complete_tx::bytes [%0], [%1], %2, [%3];"
               ::"r"(dst), "l"(src), "r"(bytes), "r"(bar) : "memory");
}
__device__ __forceinline__ void bulk_store(void* dst, uint32_t src, uint32_t bytes) {
  asm volatile("cp.async.bulk.global.shared::cta.bulk_group [%0], [%1], %2;" ::"l"(dst), "r"(src), "r"(bytes)
               : "memory");
}
__device__ __forceinline__ void bulk_commit() { asm volatile("cp.async.bulk.commit_group;" ::: "memory"); }
__device__ __forceinline__ void bulk_wait_read() { asm volatile("cp.async.bulk.wait_group.read 0;" ::: "memory"); }
__device__ __forceinline__ void bulk_wait() { asm volatile("cp.async.bulk.wait_group 0;" ::: "memory"); }
__device__ __forceinline__ void fence_async_smem() { asm volatile("fence.proxy.async.shared::cta;" ::: "memory"); }
__device__ __forceinline__ unsigned ld_relaxed(const unsigned* p) {
  unsigned v;
  asm volatile("ld.relaxed.gpu.global.u32 %0, [%1];" : "=r"(v) : "l"(p) : "memory");
  return v;
}
__device__ __forceinline__ uint2 ld_relaxed2(const uint2* p) {
  uint2 v;
  asm volatile("ld.relaxed.gpu.global.v2.u32 {%0, %1}, [%2];" : "=r"(v.x), "=r"(v.y) : "l"(p) : "memory");
  return v;
}
__device__ __forceinline__ void st_relaxed(unsigned* p, unsigned v) {
  asm volatile("st.relaxed.gpu.global.u32 [%0], %1;" ::"l"(p), "r"(v) : "memory");
}
__device__ __forceinline__ void st_release(unsigned* p, unsigned v) {
  asm volatile("st.release.gpu.global.u32 [%0], %1;" ::"l"(p), "r"(v) : "memory");
}
#define ACQ_MODE 1
__device__ __forceinline__ void wait_flags(const unsigned* p, unsigned epoch) {
  unsigned spins = 0;
  while (true) {
    const unsigned v = ld_relaxed(p);
    if (__all_sync(0xffffffffu, v == epoch)) break;
    if (++spins > kSpinLimit) __trap();
  }
  if (ACQ_MODE) asm volatile("fence.acquire.gpu;\nfence.proxy.async.global;" ::: "memory");
  __syncwarp();
}
__device__ __forceinline__ void st_packet(uint4* p, uint32_t d0, uint32_t d1, uint32_t tag) {
  asm volatile("{\n.reg .b128 v;\n.reg .b64 x, y;\nmov.b64 x, {%1, %2};\nmov.b64 y, {%3, %3};\nmov.b128 v, {x, y};\n"
               "st.relaxed.gpu.global.b128 [%0], v;\n}" ::"l"(p), "r"(d0), "r"(d1), "r"(tag) : "memory");
}
__device__ __forceinline__ void ld_packet(const uint4* p, uint32_t& d0, uint32_t& d1, uint32_t& tag) {
  asm volatile("{\n.reg .b128 v;\n.reg .b64 x, y;\n.reg .b32 u;\nld.relaxed.gpu.global.b128 v, [%3];\n"
               "mov.b128 {x, y}, v;\nmov.b64 {%0, %1}, x;\nmov.b64 {%2, u}, y;\n}"
               : "=r"(d0), "=r"(d1), "=r"(tag) : "l"(p) : "memory");
}
__device__ __forceinline__ unsigned tag_value(float v, unsigned epoch) {
  return (__float_as_uint(v) & ~7u) | (epoch & 7u);
}
__device__ __forceinline__ float untag_value(unsigned v) { return __uint_as_float(v & ~7u); }
__device__ __forceinline__ void stsm4(uint32_t a, uint32_t r0, uint32_t r1, uint32_t r2, uint32_t r3) {
  asm volatile("stmatrix.sync.aligned.m8n8.x4.shared.b16 [%0], {%1, %2, %3, %4};" ::"r"(a), "r"(r0), "r"(r1),
               "r"(r2), "r"(r3) : "memory");
}
__device__ __forceinline__ void stsm4_t(uint32_t a, uint32_t r0, uint32_t r1, uint32_t r2, uint32_t r3) {
  asm volatile("stmatrix.sync.aligned.m8n8.x4.trans.shared.b16 [%0], {%1, %2, %3, %4};" ::"r"(a), "r"(r0),
               "r"(r1), "r"(r2), "r"(r3) : "memory");
}
__device__ __forceinline__ uint32_t transpose8(uint32_t a) {
  uint32_t d;
  asm volatile("movmatrix.sync.aligned.m8n8.trans.b16 %0, %1;" : "=r"(d) : "r"(a));
  return d;
}
__device__ __forceinline__ void mma16816(float (&c)[4], uint32_t a0, uint32_t a1, uint32_t a2, uint32_t a3,
                                         uint32_t b0, uint32_t b1) {
  asm volatile("mma.sync.aligned.m16n8k16.row.col.f32.bf16.bf16.f32 {%0, %1, %2, %3}, {%4, %5, %6, %7}, {%8, %9}, "
               "{%0, %1, %2, %3};"
               : "+f"(c[0]), "+f"(c[1]), "+f"(c[2]), "+f"(c[3])
               : "r"(a0), "r"(a1), "r"(a2), "r"(a3), "r"(b0), "r"(b1));
}
__device__ __forceinline__ void mma1688(float (&c)[4], uint32_t a0, uint32_t a1, uint32_t b0) {
  asm volatile("mma.sync.aligned.m16n8k8.row.col.f32.bf16.bf16.f32 {%0, %1, %2, %3}, {%4, %5}, {%6}, {%0, %1, %2, %3};"
               : "+f"(c[0]), "+f"(c[1]), "+f"(c[2]), "+f"(c[3]) : "r"(a0), "r"(a1), "r"(b0));
}
__device__ __forceinline__ float shfl_xor(float v, int m) {
  float r;
  asm volatile("shfl.sync.bfly.b32 %0, %1, %2, 31, 0xffffffff;" : "=f"(r) : "f"(v), "r"(m));
  return r;
}
__device__ __forceinline__ float tanh_fast(float x) {
  float r;
  asm volatile("tanh.approx.f32 %0, %1;" : "=f"(r) : "f"(x));
  return r;
}
__device__ __forceinline__ void ldsm4(uint32_t a, uint32_t (&r)[4]) {
  asm volatile("ldmatrix.sync.aligned.m8n8.x4.shared.b16 {%0, %1, %2, %3}, [%4];"
               : "=r"(r[0]), "=r"(r[1]), "=r"(r[2]), "=r"(r[3]) : "r"(a) : "memory");
}
__device__ __forceinline__ void ldsm4_t(uint32_t a, uint32_t (&r)[4]) {
  asm volatile("ldmatrix.sync.aligned.m8n8.x4.trans.shared.b16 {%0, %1, %2, %3}, [%4];"
               : "=r"(r[0]), "=r"(r[1]), "=r"(r[2]), "=r"(r[3]) : "r"(a) : "memory");
}
__device__ __forceinline__ uint32_t pack2(float lo, float hi) {
  uint32_t r;
  asm volatile("cvt.rn.bf16x2.f32 %0, %1, %2;" : "=r"(r) : "f"(hi), "f"(lo));
  return r;
}
__device__ __forceinline__ float bf_lo(uint32_t r) { return __uint_as_float(r << 16); }
__device__ __forceinline__ float bf_hi(uint32_t r) { return __uint_as_float(r & 0xffff0000u); }
__device__ __forceinline__ float ex2(float x) {
  float r;
  asm("ex2.approx.ftz.f32 %0, %1;" : "=f"(r) : "f"(x));
  return r;
}
__device__ __forceinline__ float rcp(float x) {
  float r;
  asm("rcp.approx.ftz.f32 %0, %1;" : "=f"(r) : "f"(x));
  return r;
}
template <int N>
__device__ __forceinline__ void wg_wait() {
  asm volatile("wgmma.wait_group.sync.aligned %0;" ::"n"(N) : "memory");
}
__device__ __forceinline__ void yield_slot() { asm volatile("pmevent 0;"); }
__device__ __forceinline__ void wg_bar(int wg) { asm volatile("bar.sync %0, 128;" ::"r"(wg + 1) : "memory"); }

template <int N, int KIND>
__device__ __forceinline__ void mma_kblock(float (&acc)[2][96], uint32_t a, uint32_t b);

#define F8(m, d, i) m(d[i]), m(d[i + 1]), m(d[i + 2]), m(d[i + 3]), m(d[i + 4]), m(d[i + 5]), m(d[i + 6]), m(d[i + 7])
#define KSTEP(N, A, B, oa0, oa1, ob, sd)                                                   \
  "add.u32 t, " B ", " #ob ";\nmov.b64 db, {t, hb};\n"                                      \
  "add.u32 t, " A ", " #oa0 ";\nmov.b64 da, {t, ha};\n"                                     \
  "wgmma.mma_async.sync.aligned.m64n" #N "k16.f32.bf16.bf16 {" ACC##N##_0 "}, da, db, " #sd ", 1, 1, 0, 1;\n" \
  "add.u32 t, " A ", " #oa1 ";\nmov.b64 da, {t, ha};\n"                                     \
  "wgmma.mma_async.sync.aligned.m64n" #N "k16.f32.bf16.bf16 {" ACC##N##_1 "}, da, db, " #sd ", 1, 1, 0, 1;\n"

#define MMA_KBLOCK(N, KIND, A, B, ob2, ob3, sd, MID, MODE)                                 \
  template <>                                                                              \
  __device__ __forceinline__ void mma_kblock<N, KIND>(float (&acc)[2][96], uint32_t a, uint32_t b) { \
    asm volatile("{\n.reg .b32 t, ha, hb;\n.reg .b64 da, db;\n"                            \
                 "mov.b32 ha, 0x40000080;\nmov.b32 hb, 0x40000040;\n"                       \
                 "wgmma.fence.sync.aligned;\n"                                             \
                 KSTEP(N, A, B, 0, 64, 0, sd) KSTEP(N, A, B, 2, 66, 128, 1) KSTEP(N, A, B, 4, 68, ob2, 1) \
                 MID KSTEP(N, A, B, 6, 70, ob3, 1) "wgmma.commit_group.sync.aligned;\n}\n"  \
                 : OPS##N(MODE) : "r"(a), "r"(b) : "memory");                              \
  }
#define MMA_KBLOCKS(N, A, B, ob2, ob3)                                                     \
  MMA_KBLOCK(N, 0, A, B, ob2, ob3, 1, "", "+f")                                            \
  MMA_KBLOCK(N, 1, A, B, ob2, ob3, 1, "wgmma.commit_group.sync.aligned;\n", "+f")          \
  MMA_KBLOCK(N, 2, A, B, ob2, ob3, 0, "", "=f")

#define ACC128_0 \
  "%0, %1, %2, %3, %4, %5, %6, %7, %8, %9, %10, %11, %12, %13, %14, %15, " \
  "%16, %17, %18, %19, %20, %21, %22, %23, %24, %25, %26, %27, %28, %29, %30, %31, " \
  "%32, %33, %34, %35, %36, %37, %38, %39, %40, %41, %42, %43, %44, %45, %46, %47, " \
  "%48, %49, %50, %51, %52, %53, %54, %55, %56, %57, %58, %59, %60, %61, %62, %63"
#define ACC128_1 \
  "%64, %65, %66, %67, %68, %69, %70, %71, %72, %73, %74, %75, %76, %77, %78, %79, " \
  "%80, %81, %82, %83, %84, %85, %86, %87, %88, %89, %90, %91, %92, %93, %94, %95, " \
  "%96, %97, %98, %99, %100, %101, %102, %103, %104, %105, %106, %107, %108, %109, %110, %111, " \
  "%112, %113, %114, %115, %116, %117, %118, %119, %120, %121, %122, %123, %124, %125, %126, %127"
#define OPS128(m) \
  F8(m, acc[0], 0), F8(m, acc[0], 8), F8(m, acc[0], 16), F8(m, acc[0], 24), F8(m, acc[0], 32), F8(m, acc[0], 40), F8(m, acc[0], 48), F8(m, acc[0], 56), \
        F8(m, acc[1], 0), F8(m, acc[1], 8), F8(m, acc[1], 16), F8(m, acc[1], 24), F8(m, acc[1], 32), F8(m, acc[1], 40), F8(m, acc[1], 48), F8(m, acc[1], 56)
MMA_KBLOCKS(128, "%128", "%129", 512, 640)

#define ACC192_0 \
  "%0, %1, %2, %3, %4, %5, %6, %7, %8, %9, %10, %11, %12, %13, %14, %15, " \
  "%16, %17, %18, %19, %20, %21, %22, %23, %24, %25, %26, %27, %28, %29, %30, %31, " \
  "%32, %33, %34, %35, %36, %37, %38, %39, %40, %41, %42, %43, %44, %45, %46, %47, " \
  "%48, %49, %50, %51, %52, %53, %54, %55, %56, %57, %58, %59, %60, %61, %62, %63, " \
  "%64, %65, %66, %67, %68, %69, %70, %71, %72, %73, %74, %75, %76, %77, %78, %79, " \
  "%80, %81, %82, %83, %84, %85, %86, %87, %88, %89, %90, %91, %92, %93, %94, %95"
#define ACC192_1 \
  "%96, %97, %98, %99, %100, %101, %102, %103, %104, %105, %106, %107, %108, %109, %110, %111, " \
  "%112, %113, %114, %115, %116, %117, %118, %119, %120, %121, %122, %123, %124, %125, %126, %127, " \
  "%128, %129, %130, %131, %132, %133, %134, %135, %136, %137, %138, %139, %140, %141, %142, %143, " \
  "%144, %145, %146, %147, %148, %149, %150, %151, %152, %153, %154, %155, %156, %157, %158, %159, " \
  "%160, %161, %162, %163, %164, %165, %166, %167, %168, %169, %170, %171, %172, %173, %174, %175, " \
  "%176, %177, %178, %179, %180, %181, %182, %183, %184, %185, %186, %187, %188, %189, %190, %191"
#define OPS192(m) \
  F8(m, acc[0], 0), F8(m, acc[0], 8), F8(m, acc[0], 16), F8(m, acc[0], 24), F8(m, acc[0], 32), F8(m, acc[0], 40), F8(m, acc[0], 48), F8(m, acc[0], 56), F8(m, acc[0], 64), F8(m, acc[0], 72), F8(m, acc[0], 80), F8(m, acc[0], 88), \
        F8(m, acc[1], 0), F8(m, acc[1], 8), F8(m, acc[1], 16), F8(m, acc[1], 24), F8(m, acc[1], 32), F8(m, acc[1], 40), F8(m, acc[1], 48), F8(m, acc[1], 56), F8(m, acc[1], 64), F8(m, acc[1], 72), F8(m, acc[1], 80), F8(m, acc[1], 88)
MMA_KBLOCKS(192, "%192", "%193", 768, 896)

#define TSTEP(REGS, W, X, ow, ox)                                                           \
  "add.u32 t, " X ", " #ox ";\nmov.b64 db, {t, hi};\nadd.u32 t, " W ", " #ow ";\nmov.b64 da, {t, hi};\n" \
  "wgmma.mma_async.sync.aligned.m64n128k16.f32.bf16.bf16 {" REGS "}, da, db, 1, 1, 1, 1, 0;\n"
#define THEAD "{\n.reg .b32 t, hi;\n.reg .b64 da, db;\nmov.b32 hi, 0x40000040;\nwgmma.fence.sync.aligned;\n"
#define TTAIL "wgmma.commit_group.sync.aligned;\n}\n"
__device__ __forceinline__ void mma_kblock_t(float (&acc)[2][96], uint32_t wd, uint32_t xd) {
  asm volatile(THEAD TSTEP(ACC128_0, "%128", "%129", 0, 0) TSTEP(ACC128_1, "%128", "%129", 256, 0)
               TSTEP(ACC128_0, "%128", "%129", 128, 2) TSTEP(ACC128_1, "%128", "%129", 384, 2)
               TSTEP(ACC128_0, "%128", "%129", 512, 4) TSTEP(ACC128_1, "%128", "%129", 768, 4)
               TSTEP(ACC128_0, "%128", "%129", 640, 6) TSTEP(ACC128_1, "%128", "%129", 896, 6) TTAIL
               : OPS128("+f") : "r"(wd), "r"(xd) : "memory");
}
__device__ __forceinline__ void mma_half_t(float (&d)[96], uint32_t wd, uint32_t xd) {
  asm volatile(THEAD TSTEP(ACC128_0, "%64", "%65", 0, 0) TSTEP(ACC128_0, "%64", "%65", 128, 2)
               TSTEP(ACC128_0, "%64", "%65", 512, 4) TSTEP(ACC128_0, "%64", "%65", 640, 6) TTAIL
               : F8("+f", d, 0), F8("+f", d, 8), F8("+f", d, 16), F8("+f", d, 24), F8("+f", d, 32), F8("+f", d, 40),
                 F8("+f", d, 48), F8("+f", d, 56) : "r"(wd), "r"(xd) : "memory");
}

enum { kModePlain = 0, kModeHead = 1, kModeSkip = 2, kModeContinue = 3 };

template <int N>
__device__ __forceinline__ void fence_acc(float (&acc)[2][96]) {
#pragma unroll
  for (int h = 0; h < 2; h++)
#pragma unroll
    for (int i = 0; i < N / 2; i++) asm volatile("" : "+f"(acc[h][i])::"memory");
}

constexpr uint32_t kToB = (kTileBytes >> 4) + ((4096u >> 4) << 16) - (1u << 16);

#define TRACE_KB(nb)

#define HEAD_BOTH 4
template <int N>
__device__ __forceinline__ void head_blocks(float (&acc)[2][96], uint32_t sb, int n0, int slot, int xver,
                                            uint32_t rel_addr, bool rel) {
  const uint32_t ring = (((sb & 0x3FFFF) + kSmRing) >> 4) | (1u << 16);
  const uint32_t xdesc = (((sb & 0x3FFFF) + kSmX) >> 4) | (1u << 16);
  const uint32_t s0 = ring + slot * 2560, s1 = ring + ((slot + 1) & 3) * 2560;
  const uint32_t nb = n0 * 8, xbar = sb + kBarX + (xver - 1) * 16;
  if (xver > 0) {
    mbar_wait(xbar + ((HEAD_BOTH >> xver) & 1) * 8, 0);
    mbar_wait(sb + kBarTurn + (xver == 1 ? 2 : 3 * xver) * 8, 0);
  }
  mbar_wait(sb + kBarFull + (nb & 56), nb >> 6);
  if (n0 == 0) TRACE_AT(0, 1);
  TRACE_KB(nb);
  mma_kblock<N, 2>(acc, xver > 0 ? xdesc : s0, s0 + kToB);
  if (xver > 0) mbar_wait(xbar + 8, 0);
  mbar_wait(sb + kBarFull + (nb & 56) + 8, nb >> 6);
  TRACE_KB(nb + 8);
  mma_kblock<N, 0>(acc, xver > 0 ? xdesc + (kTileBytes >> 4) : s1, s1 + kToB);
  wg_wait<1>();
  if (rel) mbar_arrive_cluster(rel_addr + (nb & 56));
  wg_wait<0>();
  if (rel) mbar_arrive_cluster(rel_addr + (nb & 56) + 8);
  fence_acc<N>(acc);
}

template <int N, bool RESID, bool FRESH, class Pre>
__device__ __forceinline__ void mainloop(float (&acc)[2][96], uint32_t sb, int tile, int n0, int slot, int nkb,
                                         int pause_kk, int att, uint32_t rel_addr, bool rel, int own_kk, Pre pre) {
  constexpr uint32_t kStep = (N == 192 ? 5 : 4) * 512;
  const uint32_t ring = (((sb & 0x3FFFF) + kSmRing) >> 4) | (1u << 16);
  uint32_t st = ring + slot * kStep;
  uint32_t nb = n0 * 8, prev = 64;
  const uint32_t last = nb + 8 * (nkb - (RESID ? 3 : 1)), own = nb + 8 * own_kk;
  const uint32_t stg = (((sb & 0x3FFFF) + kSmStg) >> 4) | (1u << 16);
  uint32_t stop = pause_kk >= 0 ? nb + 8 * pause_kk : last;
  const bool signal = (threadIdx.x & 127) == 64;
  if (!FRESH) fence_acc<N>(acc);
  if (tile > 0) mbar_wait(sb + kBarTurn + (tile - 1) * 8, 0);
  TRACE_AT(tile, 0);
  if constexpr (FRESH) {
    mbar_wait(sb + kBarFull + (nb & 56), nb >> 6);
    TRACE_KB(nb);
    mma_kblock<N, 2>(acc, st, st + kToB);
    prev = nb & 56;
    st += kStep;
    nb += 8;
  }
#pragma unroll 1
  while (true) {
#pragma unroll 1
    do {
      mbar_wait(sb + kBarFull + (nb & 56), nb >> 6);
      TRACE_KB(nb);
      if constexpr (RESID) mma_kblock_t(acc, st + kToB, nb == own ? stg : st);
      else mma_kblock<N, 0>(acc, st, st + kToB);
      wg_wait<1>();
      if (rel) mbar_arrive_cluster(rel_addr + prev);
      prev = nb & 56;
      st += kStep;
      if (st == ring + 10240) st = ring;
      nb += 8;
    } while (nb != stop);
    if (stop == last) break;
    stop = last;
    if (signal) mbar_arrive(sb + kBarPause + att * 8);
    wg_wait<0>();
    if (rel) mbar_arrive_cluster(rel_addr + prev);
    prev = 64;
    mbar_wait(sb + kBarResume + att * 8, 0);
  }
  mbar_wait(sb + kBarFull + (nb & 56), nb >> 6);
  TRACE_KB(nb);
  if constexpr (RESID) {
    const uint32_t z = gridDim.y - 1;
    const uint32_t s2 = st + kStep, s3 = s2 == ring + 8192 ? ring : s2 + kStep;
    mma_half_t(acc[0], st + kToB, st);
    wg_wait<1>();
    if (rel) mbar_arrive_cluster(rel_addr + 32);
    mbar_wait(sb + kBarFull + 48, nb >> 6);
    TRACE_KB(nb + 8);
    mma_half_t(acc[0], s2 + kToB, s2);
    mbar_wait(sb + kBarFull + 56, nb >> 6);
    TRACE_KB(nb + 16);
    mma_half_t(acc[0], s3 + kToB, s3);
    mma_half_t(acc[1], st + kToB + 256, st + z);
    mma_half_t(acc[1], s2 + kToB + 256, s2 + z);
    wg_wait<2>();
#pragma unroll
    for (int i = 0; i < 64; i++) asm volatile("" : "+f"(acc[0][i])::"memory");
    pre(0);
    mma_half_t(acc[1], s3 + kToB + 256, s3 + z);
    wg_wait<2>();
    if (rel) mbar_arrive_cluster(rel_addr + 40);
    pre(1);
    wg_wait<1>();
    if (rel) mbar_arrive_cluster(rel_addr + 48);
    if (signal) mbar_arrive(sb + kBarTurn + tile * 8);
    wg_wait<0>();
    if (rel) mbar_arrive_cluster(rel_addr + 56);
#pragma unroll
    for (int i = 0; i < 64; i++) asm volatile("" : "+f"(acc[1][i])::"memory");
  } else {
    mma_kblock<N, 1>(acc, st, st + kToB);
    wg_wait<2>();
    if (rel) mbar_arrive_cluster(rel_addr + prev);
    pre();
    wg_wait<1>();
    if (signal) mbar_arrive(sb + kBarTurn + tile * 8);
    wg_wait<0>();
    if (rel) mbar_arrive_cluster(rel_addr + (nb & 56));
    fence_acc<N>(acc);
  }
}

__device__ __forceinline__ void publish_stats(uint32_t sb, uint2* stat, int w, int lane, unsigned epoch) {
  const uint32_t row = sb + kSmX + (32 * w + lane) * 128;
  float s[4], q[4];
#pragma unroll
  for (int c = 0; c < 4; c++) s[c] = q[c] = 0.f;
  uint32_t nx[4];
  ldsm4(row + ((lane & 7) << 4), nx);
#pragma unroll 1
  for (int J = 1; J <= 16; J++) {
    const uint32_t r[4] = {nx[0], nx[1], nx[2], nx[3]};
    ldsm4(row + ((J >> 3) & 1) * kTileBytes + (((J ^ lane) & 7) << 4), nx);
#pragma unroll
    for (int c = 0; c < 4; c++) {
      const float lo = bf_lo(r[c]);
      s[c] += lo;
      q[c] = fmaf(lo, lo, q[c]);
      if (c & 1) yield_slot();
    }
#pragma unroll
    for (int c = 0; c < 4; c++) {
      const float hi = bf_hi(r[c]);
      s[c] += hi;
      q[c] = fmaf(hi, hi, q[c]);
      if (c & 1) yield_slot();
    }
  }
#pragma unroll
  for (int c = 0; c < 4; c++) {
    s[c] += shfl_xor(s[c], 1);
    q[c] += shfl_xor(q[c], 1);
    s[c] += shfl_xor(s[c], 2);
    q[c] += shfl_xor(q[c], 2);
  }
  const int t = lane & 3, g = lane >> 2;
  const float so = t == 0 ? s[0] : t == 1 ? s[1] : t == 2 ? s[2] : s[3];
  const float qo = t == 0 ? q[0] : t == 1 ? q[1] : t == 2 ? q[2] : q[3];
  asm volatile("st.relaxed.gpu.global.v2.u32 [%0], {%1, %2};" ::"l"(stat + 32 * w + 8 * t + g),
               "r"(tag_value(so, epoch)), "r"(tag_value(qo, epoch)) : "memory");
}

__device__ __forceinline__ void add_chunk(float (&a)[8], const uint4& v) {
  a[0] += bf_lo(v.x); a[1] += bf_hi(v.x);
  a[2] += bf_lo(v.y); a[3] += bf_hi(v.y);
  a[4] += bf_lo(v.z); a[5] += bf_hi(v.z);
  a[6] += bf_lo(v.w); a[7] += bf_hi(v.w);
}

__device__ __forceinline__ int helper_col(int id, int slab) {
  return slab < 6 ? (slab % 3) * kD + (slab / 3) * 512 + id * 128 : (slab - 6) * 512 + id * 128;
}
__device__ __forceinline__ void helper_cta(const CUtensorMap* map_q, const CUtensorMap* map_1, uint8_t* sm,
                                           uint32_t sb, int id, int warp) {
  constexpr int kRed = 6 * 32768, kBar = kRed + 2 * 4096;
  const int tid = threadIdx.x;
  if (warp == 8 && elect()) {
#pragma unroll
    for (int s = 0; s < 6; s++) {
      mbar_init(sb + kBar + s * 8, 1);
      mbar_init(sb + kBar + 64 + s * 8, 4);
    }
    fence_async_smem();
#pragma unroll
    for (int s = 0; s < 6; s++) {
      mbar_expect_tx(sb + kBar + s * 8, 32768);
      tma2d(sb + s * 32768, map_q, sb + kBar + s * 8, id * 128, s * 128);
    }
  }
  __syncthreads();
  if (warp == 8) {
    int slot = 0, ph = 0;
#pragma unroll 1
    for (int n = 6; n < 104; n++) {
      mbar_wait(sb + kBar + 64 + slot * 8, ph);
      if (elect()) {
        mbar_expect_tx(sb + kBar + slot * 8, 32768);
        tma2d(sb + slot * 32768, n < 48 ? map_q : map_1, sb + kBar + slot * 8, helper_col(id, n >> 3), (n & 7) * 128);
      }
      if (++slot == 6) slot = 0, ph ^= 1;
    }
  } else if (warp < 8) {
    if (tid == 0) *reinterpret_cast<unsigned*>(sm + kBar + 128) = atomicAdd(&g_ticket, 1u) / kGrid + 1;
    int slot = warp >> 2, ph = 0;
#pragma unroll 1
    for (int slab = 0; slab < 13; slab++) {
      float a[8];
#pragma unroll
      for (int e = 0; e < 8; e++) a[e] = 0.f;
#pragma unroll 1
      for (int box = 0; box < 4; box++) {
        mbar_wait_bounded(sb + kBar + slot * 8, ph);
        const uint4* p = reinterpret_cast<const uint4*>(sm + slot * 32768) + (tid & 127);
        uint4 v[16];
#pragma unroll
        for (int i = 0; i < 16; i++) v[i] = p[i * 128];
        __syncwarp();
        if (elect()) mbar_arrive(sb + kBar + 64 + slot * 8);
#pragma unroll
        for (int i = 0; i < 16; i++) add_chunk(a, v[i]);
        slot += 2;
        if (slot >= 6) slot -= 6, ph ^= 1;
      }
      float* red = reinterpret_cast<float*>(sm + kRed + (slab & 1) * 4096);
#pragma unroll
      for (int e = 0; e < 8; e++) a[e] += shfl_xor(a[e], 16);
      if ((tid & 16) == 0) {
        float4* d = reinterpret_cast<float4*>(red + warp * 128 + (tid & 15) * 8);
        d[0] = make_float4(a[0], a[1], a[2], a[3]);
        d[1] = make_float4(a[4], a[5], a[6], a[7]);
      }
      asm volatile("bar.sync 1, 256;" ::: "memory");
      if (warp < 4) {
        float t = 0.f;
#pragma unroll
        for (int q = 0; q < 8; q++) t += red[q * 128 + tid];
        st_relaxed(g_cs + (slab < 6 ? 0 : 3 * kD) + helper_col(id, slab) + tid,
                   tag_value(t, *reinterpret_cast<volatile unsigned*>(sm + kBar + 128)));
      }
    }
  }
}

constexpr float kGeluBeta = 0.3292034911525734f;
constexpr float kGeluK = 2.423681954311584f;

__device__ __forceinline__ void store_staged(uint8_t* dst, uint32_t stg) {
  fence_async_smem();
  __syncwarp();
  if (elect()) {
    bulk_store(dst, stg, 4096);
    bulk_commit();
  }
}

#define GY_MASK 0x2a
#define GY_MASK2 0x2a
#define GY(k) if (((CH == 2 ? GY_MASK2 : GY_MASK) >> k) & 1) yield_slot()
template <int CH>
__device__ __forceinline__ void gelu_chunk(const float (&acc)[2][96], const float2 (&st)[4], const float4* vec,
                                           uint32_t stg, int lane, bool chained, uint8_t* prev, uint32_t free_bar) {
  uint32_t pk[8][4];
  float u[3][4], z[3][4];
  vec += lane & 3;
  const uint32_t row = (stg + lane * 128) ^ ((lane & 7) << 4);
  float4 v = vec[CH * 32], vn = v;
#pragma unroll
  for (int s = 0; s < 18; s++) {
    const int J = CH * 8 + (s >> 1), c0 = 2 * (s & 1), cur = s % 3, p1 = (s + 2) % 3, p2 = (s + 1) % 3;
    if (s < 16) {
      if (c0 == 0 && s < 14) vn = vec[(J + 1) * 4];
#pragma unroll
      for (int e = 0; e < 4; e++) {
        const int c = c0 + (e >> 1);
        z[cur][e] = fmaf(st[c].y, e & 1 ? v.y : v.x, e & 1 ? v.w : v.z);
      }
      if (c0 == 2) v = vn;
    }
    if (s >= 1 && s < 17) z[p1][0] = tanh_fast(z[p1][0]);
    GY(0);
    if (s < 16) {
#pragma unroll
      for (int e = 0; e < 4; e++) {
        const int c = c0 + (e >> 1);
        u[cur][e] = fmaf(acc[c & 1][4 * J + c0 + (e & 1)], st[c].x, z[cur][e]);
      }
    }
    if (s >= 1 && s < 17) z[p1][1] = tanh_fast(z[p1][1]);
    GY(1);
    if (s >= 11) {
      const int jj = s - 11;
      stsm4(row ^ (jj << 4), pk[jj][0], pk[jj][1], pk[jj][2], pk[jj][3]);
    }
    if (s < 16) {
#pragma unroll
      for (int e = 0; e < 4; e++) z[cur][e] = fmaf(u[cur][e], u[cur][e], kGeluK);
    }
    if (s >= 1 && s < 17) z[p1][2] = tanh_fast(z[p1][2]);
    GY(3);
    if (s >= 2) {
      pk[(s - 2) >> 1][c0] = pack2(fmaf(u[p2][0], z[p2][0], u[p2][0]), fmaf(u[p2][1], z[p2][1], u[p2][1]));
      pk[(s - 2) >> 1][c0 + 1] = pack2(fmaf(u[p2][2], z[p2][2], u[p2][2]), fmaf(u[p2][3], z[p2][3], u[p2][3]));
    }
    GY(4);
    if (s < 16) {
#pragma unroll
      for (int e = 0; e < 4; e++) z[cur][e] = u[cur][e] * z[cur][e];
    }
    if (s >= 1 && s < 17) z[p1][3] = tanh_fast(z[p1][3]);
    GY(5);
    if (CH < 2 && s == 1 && chained) store_staged(prev, stg);
    if (CH < 2 && s == 10) {
      if (chained) {
        if (elect()) bulk_wait();
        __syncwarp();
      } else {
        mbar_wait(free_bar, 0);
      }
    }
  }
  stsm4(row ^ (7 << 4), pk[7][0], pk[7][1], pk[7][2], pk[7][3]);
}

__device__ __forceinline__ void scale_stats(float2 (&st)[4]) {
#pragma unroll
  for (int c = 0; c < 4; c++) {
    st[c].x *= kGeluBeta;
    st[c].y *= st[c].x;
  }
}

__device__ __forceinline__ void add_mean_term(float (&acc)[2][96], const float2 (&st)[4], uint8_t* sm, int tq,
                                              int lane) {
  const float2* cs = reinterpret_cast<const float2*>(sm + kSmCsQ) + tq * 96 + (lane & 3);
  float2 vn = cs[0];
#pragma unroll
  for (int J = 0; J < 24; J++) {
    const float2 v = vn;
    if (J < 23) vn = cs[J * 4 + 4];
#pragma unroll
    for (int c = 0; c < 4; c++) {
      acc[c & 1][4 * J + (c & 2)] = fmaf(st[c].y, v.x, acc[c & 1][4 * J + (c & 2)]);
      acc[c & 1][4 * J + (c & 2) + 1] = fmaf(st[c].y, v.y, acc[c & 1][4 * J + (c & 2) + 1]);
    }
    yield_slot();
  }
}

#define TWO_PART 0
#define RESUME_LATE 0
#define HALO_AT 2
__device__ __forceinline__ void epilogue_attn(const float (&acc)[2][96], const float2 (&st)[4], uint8_t* sm,
                                              uint32_t sb, int layer, int tq, int b, int j, unsigned epoch, int tile,
                                              int wg, int w, int lane) {
  const int t = lane & 3, g = lane >> 2;
  const int hp = j + 8 * tq, att = 2 * layer + tq;
  uint32_t q[4][8], k[5][8], vt[5][8];
#define SCALED(c, J) pack2(acc[(c) & 1][4 * (J) + ((c) & 2)] * st[c].x, acc[(c) & 1][4 * (J) + ((c) & 2) + 1] * st[c].x)
#pragma unroll
  for (int J = 0; J < 8; J++) vt[4][J] = transpose8(SCALED(3, 16 + J));
#pragma unroll
  for (int J = 0; J < 8; J++) k[4][J] = SCALED(3, 8 + J);
  if (w < 3) {
    uint2* hs = reinterpret_cast<uint2*>(sm + kSmHalo + w * 2048) + lane;
#pragma unroll
    for (int i = 0; i < 4; i++) {
      hs[i * 32] = make_uint2(k[4][2 * i], k[4][2 * i + 1]);
      hs[128 + i * 32] = make_uint2(vt[4][2 * i], vt[4][2 * i + 1]);
    }
  } else if ((b & 7) != 7) {
    uint4* gh = g_halo + ((layer * 16 + b) * 16 + hp) * 256 + lane;
#pragma unroll
    for (int i = 0; i < 4; i++) {
      st_packet(gh + i * 32, k[4][2 * i], k[4][2 * i + 1], epoch);
      st_packet(gh + 128 + i * 32, vt[4][2 * i], vt[4][2 * i + 1], epoch);
    }
  }
#pragma unroll
  for (int c = 0; c < 3; c++)
#pragma unroll
    for (int J = 0; J < 8; J++) {
      k[c + 1][J] = SCALED(c, 8 + J);
      vt[c + 1][J] = transpose8(SCALED(c, 16 + J));
      yield_slot();
    }
  const bool first = w == 0 && (b & 7) == 0;
  const uint4* gh = g_halo + ((layer * 16 + b - 1) * 16 + hp) * 256 + lane;
  uint32_t tag[8];
#define LOAD_HALO()                                                                                    \
  _Pragma("unroll") for (int i = 0; i < 4; i++) {                                                      \
    ld_packet(gh + i * 32, k[0][2 * i], k[0][2 * i + 1], tag[i]);                                      \
    ld_packet(gh + 128 + i * 32, vt[0][2 * i], vt[0][2 * i + 1], tag[4 + i]);                          \
  }
#define AWAIT_HALO()                                                                                   \
  for (unsigned spins = 0;; spins++) {                                                                 \
    const unsigned d0 = (tag[0] ^ epoch) | (tag[1] ^ epoch) | (tag[2] ^ epoch) | (tag[3] ^ epoch);     \
    const unsigned d1 = (tag[4] ^ epoch) | (tag[5] ^ epoch) | (tag[6] ^ epoch) | (tag[7] ^ epoch);     \
    if (__all_sync(0xffffffffu, (d0 | d1) == 0)) break;                                                \
    if (spins > kSpinLimit) __trap();                                                                  \
    LOAD_HALO();                                                                                       \
  }
#pragma unroll
  for (int c = 0; c <= 4; c++) {
    if (c == HALO_AT) {
      if (w == 0 && !first) {
        LOAD_HALO();
      } else {
#pragma unroll
        for (int i = 0; i < 8; i++) k[0][i] = vt[0][i] = tag[i] = 0u;
      }
    }
#pragma unroll
    for (int J = 0; J < 8 && c < 4; J++) {
      q[c & 3][J] = SCALED(c & 3, J);
      if (J & 1) yield_slot();
    }
  }
#undef SCALED
  TRACE_AT(tile, 8);
  wg_bar(wg);
  if (w > 0) {
    const uint2* hs = reinterpret_cast<const uint2*>(sm + kSmHalo + (w - 1) * 2048) + lane;
#pragma unroll
    for (int i = 0; i < 4; i++) {
      const uint2 a = hs[i * 32], c = hs[128 + i * 32];
      k[0][2 * i] = a.x; k[0][2 * i + 1] = a.y;
      vt[0][2 * i] = c.x; vt[0][2 * i + 1] = c.y;
    }
  } else if (!first && tq == 0) {
    AWAIT_HALO();
  }
  constexpr float kScale = 0.17677669529663687f * 1.4426950408889634f;
  const bool own0 = 2 * t <= g, own1 = 2 * t + 1 <= g;
  const uint32_t own_mask = (own0 ? 0xffffu : 0u) | (own1 ? 0xffff0000u : 0u);
  const uint32_t stg = sb + kSmStg + w * 4096;
  const uint32_t orow = stg + (lane & 7) * 128, ochunk = (lane >> 3) ^ (lane & 7);
  TRACE_AT(tile, 9);
  mbar_wait(sb + kBarPause + att * 8, 0);
  TRACE_AT(tile, 10);

  float s[2][6][4], o[2][4][2][4];
  auto scores = [&](int hd, int m) {
    const int ca = 2 * (m / 3), kg = ca + m % 3;
#pragma unroll
    for (int e = 0; e < 4; e++) s[hd][m][e] = 0.f;
#pragma unroll
    for (int J = 4 * hd; J < 4 * hd + 4; J += 2)
      mma16816(s[hd][m], q[ca][J], q[ca + 1][J], q[ca][J + 1], q[ca + 1][J + 1], k[kg][J], k[kg][J + 1]);
  };
  auto attend = [&](int c0, int c1) {
    float v0[2][4], v1[2][4], m[2][4];
#define UNITS _Pragma("unroll") for (int hd = 0; hd < 2; hd++) _Pragma("unroll") for (int c = c0; c < c1; c++)
    UNITS {
      const int mp = 3 * (c >> 1) + (c & 1), r = 2 * (c & 1);
      float p0 = s[hd][mp][r], p1 = s[hd][mp][r + 1];
      if (c == 0 && first) p0 = p1 = -INFINITY;
      v0[hd][c] = own0 ? s[hd][mp + 1][r] : p0;
      v1[hd][c] = own1 ? s[hd][mp + 1][r + 1] : p1;
      m[hd][c] = fmaxf(v0[hd][c], v1[hd][c]);
    }
    UNITS m[hd][c] = fmaxf(m[hd][c], shfl_xor(m[hd][c], 1));
    UNITS m[hd][c] = fmaxf(m[hd][c], shfl_xor(m[hd][c], 2));
    UNITS {
      const float nm = -m[hd][c] * kScale;
      v0[hd][c] = ex2(fmaf(v0[hd][c], kScale, nm));
      v1[hd][c] = ex2(fmaf(v1[hd][c], kScale, nm));
      m[hd][c] = v0[hd][c] + v1[hd][c];
    }
    UNITS m[hd][c] += shfl_xor(m[hd][c], 1);
    UNITS m[hd][c] += shfl_xor(m[hd][c], 2);
    UNITS {
      const float inv = rcp(m[hd][c]);
      const uint32_t p = pack2(v0[hd][c] * inv, v1[hd][c] * inv);
#pragma unroll
      for (int ds = 0; ds < 2; ds++) {
        const int J = 4 * hd + 2 * ds;
#pragma unroll
        for (int e = 0; e < 4; e++) o[hd][c][ds][e] = 0.f;
        if (c & 1) {
          mma16816(o[hd][c][ds], vt[c][J], vt[c][J + 1], vt[c + 1][J], vt[c + 1][J + 1], p & ~own_mask, p & own_mask);
        } else {
          mma1688(o[hd][c][ds], vt[c + 1][J], vt[c + 1][J + 1], p & own_mask);
          mma1688(o[hd][c][ds], vt[c][J], vt[c][J + 1], p & ~own_mask);
        }
      }
    }
  };
  auto stage = [&](int c0, int c1) {
    UNITS stsm4_t(orow + c * 1024 + ((ochunk ^ (4 * hd)) << 4), pack2(o[hd][c][0][0], o[hd][c][0][1]),
                  pack2(o[hd][c][0][2], o[hd][c][0][3]), pack2(o[hd][c][1][0], o[hd][c][1][1]),
                  pack2(o[hd][c][1][2], o[hd][c][1][3]));
#undef UNITS
  };
  if (w == 0 && !first) AWAIT_HALO();
#pragma unroll
  for (int hd = 0; hd < 2; hd++)
#pragma unroll
    for (int m = 0; m < 6; m++) scores(hd, m);
  attend(0, 4);
  yield_slot();
  if (tq == 0 && elect()) mbar_arrive(sb + kBarResume + att * 8);
  TRACE_AT(tile, 11);
  stage(0, 4);
#undef AWAIT_HALO
#undef LOAD_HALO
  fence_async_smem();
  __syncwarp();
  TRACE_AT(tile, 12);
  if (elect()) {
    bulk_store(g_o + (b * 16 + hp) * kTileBytes + w * 4096, stg, 4096);
    bulk_commit();
    if (tq == 1 && !RESUME_LATE) mbar_arrive(sb + kBarResume + att * 8);
    bulk_wait();
    if (tq == 1 && RESUME_LATE) mbar_arrive(sb + kBarResume + att * 8);
    TRACE_AT(tile, 13);
    mbar_arrive(sb + kBarEpi + tile * 8);
  }
  __syncwarp();
}

__device__ __forceinline__ void gather_stats(uint8_t* sm, const uint2* stat, int r, unsigned epoch) {
  uint2 a[8];
  unsigned spins = 0;
  while (true) {
    unsigned diff = 0;
#pragma unroll
    for (int i = 0; i < 8; i++) {
      a[i] = ld_relaxed2(stat + i * 128 + r);
      diff |= (a[i].x ^ epoch) | (a[i].y ^ epoch);
    }
    if (__all_sync(0xffffffffu, (diff & 7u) == 0)) break;
    if (++spins > kSpinLimit) __trap();
    __nanosleep(200);
  }
  float s = 0.f, q = 0.f;
#pragma unroll
  for (int i = 0; i < 8; i++) {
    s += untag_value(a[i].x);
    q += untag_value(a[i].y);
  }
  const float mean = s * (1.f / 1024.f);
  const float var = fmaxf(fmaf(-mean, mean, q * (1.f / 1024.f)), 0.f);
  reinterpret_cast<float2*>(sm + kSmStat)[r] = make_float2(rsqrtf(var + 1e-5f), -mean);
}

__device__ __forceinline__ void gather_colsums(uint8_t* sm, int part, int j, int lane, unsigned epoch) {
#pragma unroll 1
  for (int blk = part < 4 ? 0 : 2 * part - 5; blk < (part < 4 ? 3 : 2 * part - 3); blk++) {
    const int col = part < 2 ? blk * kD + (j + 8 * part) * 64
                             : 3 * kD + 64 * (blk + (blk < 3 ? 3 * j : blk < 5 ? 21 + 2 * j : 35 + 2 * j));
    uint2 v;
    unsigned spins = 0;
    while (true) {
      v = ld_relaxed2(reinterpret_cast<const uint2*>(g_cs + col) + lane);
      if (__all_sync(0xffffffffu, (((v.x ^ epoch) | (v.y ^ epoch)) & 7u) == 0)) break;
      if (++spins > kSpinLimit) __trap();
      __nanosleep(100);
    }
    uint8_t* dst = part < 2 ? sm + kSmCsQ + (part * 96 + blk * 32 + lane) * 8 : sm + kSmV1 + (blk * 32 + lane) * 16;
    *reinterpret_cast<float2*>(dst) = make_float2(untag_value(v.x), untag_value(v.y));
  }
}

#define READBACK 0
#define FINE 3
#define LATE_REL2 1
#define XT_LATE 1
#define STAGE_YIELD 1
#define PAUSE_QKV2 7
#define PAUSE_WO 3

__global__ void __cluster_dims__(2, 1, 1) __launch_bounds__(384, 1)
fused_layers_kernel(const __grid_constant__ CUtensorMap map_x, const __grid_constant__ CUtensorMap map_out,
                    const __grid_constant__ CUtensorMap map_qkv, const __grid_constant__ CUtensorMap map_wo,
                    const __grid_constant__ CUtensorMap map_w1a, const __grid_constant__ CUtensorMap map_w1b,
                    const __grid_constant__ CUtensorMap map_w2, const __grid_constant__ CUtensorMap map_csq,
                    const __grid_constant__ CUtensorMap map_cs1, const __grid_constant__ Params prm) {
  extern __shared__ __align__(1024) uint8_t sm[];
  if (threadIdx.x < 128 && blockIdx.x < kCtas) TRACE_AT(15, 1);
  const uint32_t sb = __shfl_sync(0xffffffffu, smem_u32(sm), 0);
  const int warp = __shfl_sync(0xffffffffu, threadIdx.x >> 5, 0), lane = threadIdx.x & 31;
  const int cta = blockIdx.x, rank = cta & 1, cl = cta >> 1;
  const int grp = cl < 4 ? 0 : cl < 36 ? (cl - 4) & 7 : 1 + (cl - 36) % 7;
  const int j = cl < 4 ? 4 + cl : cl < 36 ? (cl - 4) >> 3 : 4 + (cl - 36) / 7;
  const int b = 2 * grp + rank;
  const int xcol = (b >> 3) * kD, xrow = (b & 7) * 128;

  if (cta >= kCtas) {
    helper_cta(&map_csq, &map_cs1, sm, sb, cta - kCtas, warp);
    return;
  }
  if (warp >= 8 && elect()) {
    if (warp == 9) {
#pragma unroll
      for (int s = 0; s < 8; s++) mbar_init(sb + kBarFull + s * 8, 1);
      mbar_init(sb + kBarInit, 1);
      fence_async_smem();
#pragma unroll
      for (int s = 0; s < 4; s++) {
        const uint32_t full = sb + kBarFull + s * 8, dst = sb + kSmRing + s * 40960;
        mbar_expect_tx(full, 40960);
        tma2d(dst, &map_x, full, xcol + (s & 1) * 64, xrow);
        tma3d(dst + kTileBytes, &map_qkv, full, (j + 4 * (s & 2)) * 64, (s & 1) * 64, 0);
        tma3d(dst + kTileBytes + 12288, &map_qkv, full, (j + 4 * (s & 2)) * 64, (s & 1) * 64 + 32, 0);
      }
      if (!XT_LATE) {
        mbar_expect_tx(sb + kBarInit, 32768);
        tma2d(sb + kSmX, &map_x, sb + kBarInit, xcol + j * 128, xrow);
        tma2d(sb + kSmX + kTileBytes, &map_x, sb + kBarInit, xcol + j * 128 + 64, xrow);
      }
    } else if (warp == 8) {
      if (sb & 1023) __trap();
#pragma unroll
      for (int o = kBarTurn; o < kBarPause; o += 8) mbar_init(sb + o, 1);
    } else if (warp == 10) {
#pragma unroll
      for (int o = kBarEpi; o < kSmEpoch; o += 8) mbar_init(sb + o, 4);
    } else {
#pragma unroll
      for (int o = kBarPause; o < kBarEpi; o += 8)
        if (o != kBarInit) mbar_init(sb + o, o < kBarEmpty ? 1 : 2);
    }
    asm volatile("fence.mbarrier_init.release.cluster;" ::: "memory");
  }
  __syncwarp();
  asm volatile("barrier.cluster.arrive.relaxed.aligned;" ::: "memory");

  if (warp >= 8) {
    asm volatile("setmaxnreg.dec.sync.aligned.u32 40;");
    if (warp < 10) {
      asm volatile("barrier.cluster.wait.aligned;" ::: "memory");
      uint32_t nb = 32, off = 0, kb = 0;
#define RING_STEP(WAIT, ISSUE)                                            \
  do {                                                                    \
    const uint32_t mb = nb - depth, full = sb + kBarFull + (nb & 56);     \
    if (kb == skip) kb += inc;                                            \
    mbar_wait(sb + kBarEmpty + (mb & 56), mb >> 6);                       \
    WAIT;                                                                 \
    if (elect()) { ISSUE; }                                               \
    TRACE_ISSUE(9 - warp, nb);                                            \
    kb += inc;                                                            \
    off = off == wrap ? 0 : off + step;                                   \
    nb += 8;                                                              \
  } while (nb != nend)
#pragma unroll 1
      for (int sg = 0; sg < kSegs; sg++) {
        const uint32_t e = prm.seg[sg];
        const int ty = e & 7, mode = (e >> 15) & 3, reset = (e >> 24) & 3;
        const uint32_t nend = nb + (e & 0x1f8);
        const uint32_t step = (e >> 17) & 1 ? 40960 : 32768, wrap = 163840 - step;
        const uint32_t depth = (e >> 18) & 1 ? 40 : 32;
        if (reset) off = reset == 1 ? 0 : reset == 2 ? 40960 : 131072;
        const uint32_t own = ty == 2 ? 8 + j : 2 * j;
        if (mode != kModeContinue) kb = mode == kModeHead ? own : (e >> 9) & 63;
        const uint32_t inc = mode >= kModeSkip && ty != 2 ? 2 : 1, skip = mode >= kModeSkip ? own + (kb & 1) : 255;
        if (warp == 8) {
          const CUtensorMap* map = ty < 2 ? &map_qkv : ty == 2 ? &map_wo : ty == 3 ? &map_w1a : ty < 6 ? &map_w1b : &map_w2;
          const int c0 = ty < 2 ? (j + 8 * ty) * 64 : 0;
          const int c2 = ty < 2 ? 0 : ty == 3 ? 3 * j : ty == 4 ? 24 + 2 * j : ty == 5 ? 40 + 2 * j : 2 * j;
          const uint32_t half = (ty < 2 || ty == 3) ? 12288 : 8192;
          const uint32_t bytes = 2 * half + (mode == kModeHead ? 0 : kTileBytes);
          const uint32_t dst = sb + kSmRing + kTileBytes + rank * half;
#pragma unroll 1
          RING_STEP(, mbar_expect_tx(full, bytes); tma3d_mc(dst + off, map, full, c0, kb * 64 + rank * 32, c2));
        } else if (mode == kModeHead) {
          off += ((nend - nb) >> 3) * step;
          nb = nend;
          if (off >= 163840) off -= 163840;
        } else if (sg < 2) {
#pragma unroll 1
          RING_STEP(, tma2d(sb + kSmRing + off, &map_x, full, xcol + kb * 64, xrow));
        } else {
          const uint8_t* src = ty == 6 ? g_h + b * 56 * kTileBytes : (ty == 2 ? g_o : g_x) + b * 16 * kTileBytes;
          const int dep = (e >> 19) & 31;
          if (dep < 28) mbar_wait(sb + kBarReady + dep * 8, 0);
          if ((dep & 30) == 28) {
#pragma unroll 1
            RING_STEP(mbar_wait(sb + kBarSrc + ((kb << (4 - inc)) & 56), dep),
                      bulk_load(sb + kSmRing + off, src + kb * kTileBytes, kTileBytes, full));
          } else {
#pragma unroll 1
            RING_STEP(, bulk_load(sb + kSmRing + off, src + kb * kTileBytes, kTileBytes, full));
          }
        }
      }
#undef RING_STEP
    } else if (warp == 10) {
      unsigned epoch = 0;
      if (lane == 0) epoch = atomicAdd(&g_ticket, 1u) / kGrid + 1;
      epoch = __shfl_sync(0xffffffffu, epoch, 0);
      *reinterpret_cast<unsigned*>(sm + kSmEpoch) = epoch;
      asm volatile("barrier.cluster.wait.aligned;" ::: "memory");
      if (elect()) mbar_arrive(sb + kBarEpoch);
#pragma unroll 1
      for (int i = 0; i < kTiles - 1; i++) {
        const bool xt = i == 2 || i == 6 || i == 9;
        const unsigned* line = g_flag + (i * 16 + b) * 32;
        mbar_wait(sb + (xt ? kBarX + (i >> 2) * 16 : kBarEpi + i * 8), 0);
        if ((xt && (FINE & 1)) || ((i == 1 || i == 8) && (FINE & 2))) {
          unsigned todo = 0xff, spins = 0;
          do {
            const unsigned now = __ballot_sync(0xffffffffu, ld_relaxed(line + (lane & 7)) == epoch) & todo;
            if (now) {
              asm volatile("fence.acquire.gpu;\nfence.proxy.async.global;" ::: "memory");
              if ((now >> lane) & 1) mbar_arrive(sb + kBarSrc + lane * 8);
              todo ^= now;
            }
            if (++spins > kSpinLimit) __trap();
          } while (todo);
        } else {
          wait_flags(line + (lane & 7), epoch);
          if (elect()) mbar_arrive(sb + kBarReady + i * 8);
        }
        if (xt) {
          wait_flags(line + 8 + (lane & 7), epoch);
          if (elect()) mbar_arrive(sb + kBarReady + (14 + (i >> 2)) * 8);
        }
      }
    } else {
      asm volatile("barrier.cluster.wait.aligned;" ::: "memory");
      if (XT_LATE) {
        mbar_wait_bounded(sb + kBarFull + 8 * (XT_LATE - 1), 0);
        if (elect()) {
          mbar_expect_tx(sb + kBarInit, 32768);
          tma2d(sb + kSmX, &map_x, sb + kBarInit, xcol + j * 128, xrow);
          tma2d(sb + kSmX + kTileBytes, &map_x, sb + kBarInit, xcol + j * 128 + 64, xrow);
        }
      }
      {
        uint32_t v[7];
#pragma unroll
        for (int q = 0; q < 7; q++)
          v[q] = reinterpret_cast<const uint32_t*>(prm.b1)[32 * (q + (q < 3 ? 3 * j : q < 5 ? 21 + 2 * j : 35 + 2 * j)) + lane];
        const uint2 u = reinterpret_cast<const uint2*>(prm.b2)[32 * j + lane];
#pragma unroll
        for (int q = 0; q < 7; q++)
          *reinterpret_cast<float2*>(sm + kSmV1 + (q * 32 + lane) * 16 + 8) = make_float2(kGeluBeta * bf_lo(v[q]), kGeluBeta * bf_hi(v[q]));
        reinterpret_cast<float4*>(sm + kSmB2)[lane] = make_float4(
            2.f * kGeluBeta * bf_lo(u.x), 2.f * kGeluBeta * bf_hi(u.x), 2.f * kGeluBeta * bf_lo(u.y), 2.f * kGeluBeta * bf_hi(u.y));
      }
      mbar_wait_bounded(sb + kBarEpoch, 0);
      const unsigned epoch = *reinterpret_cast<volatile unsigned*>(sm + kSmEpoch);
#pragma unroll 1
      for (int i = 0; i < kTiles - 1; i++) {
#pragma unroll 1
        for (int part = i == 4 ? 5 : i; part < (i < 2 ? i + 1 : i == 3 || i == 4 ? i + 2 : 0); part++) {
          gather_colsums(sm, part, j, lane, epoch);
          __syncwarp();
          if (elect()) mbar_arrive(sb + kBarCs + part * 8);
        }
        const bool xt = i == 2 || i == 6 || i == 9;
#pragma unroll 1
        for (int h = 0; h < (xt ? 2 : 1); h++) {
          mbar_wait_bounded(sb + (xt ? kBarX + (i >> 2) * 16 + 8 * h : kBarEpi + i * 8), 0);
          const int ty = i >= 7 ? i - 7 : i;
          if (ty >= 2 && elect()) {
            uint8_t* dst = xt ? g_x + (b * 16 + 2 * j + h) * kTileBytes
                              : g_h + (b * 56 + 1 + (ty == 3 ? 3 * j : 16 * ty - 40 + 2 * j)) * kTileBytes;
            bulk_store(dst, sb + (xt ? kSmX + h * kTileBytes : kSmStg), kTileBytes);
            bulk_commit();
            bulk_wait();
            if (!xt) mbar_arrive(sb + kBarFree + i * 8);
          }
          if (LATE_REL2 && h == 1) mbar_wait_bounded(sb + kBarFull + 32, i == 2 ? 6 : i == 6 ? 19 : 25);
          __syncwarp();
          if (elect()) st_release(&g_flag[(i * 16 + b) * 32 + h * 8 + j], epoch);
          __syncwarp();
        }
      }
#pragma unroll 1
      for (int h = 0; h < 2; h++) {
        mbar_wait_bounded(sb + kBarX + 48 + 8 * h, 0);
        if (elect()) {
          tma2d_store(&map_out, sb + kSmX + h * kTileBytes, xcol + j * 128 + h * 64, xrow);
          bulk_commit();
          if (h == 1) bulk_wait_read();
        }
      }
    }
    __syncwarp();
    asm volatile("barrier.cluster.arrive.relaxed.aligned;\nbarrier.cluster.wait.aligned;" ::: "memory");
  } else {
    asm volatile("setmaxnreg.inc.sync.aligned.u32 232;");
    asm volatile("barrier.cluster.wait.aligned;" ::: "memory");
    const int wg = warp >> 2, w = warp & 3;
    const bool rel = (threadIdx.x & 95) == 0;
    const uint32_t rel_addr = mapa(sb + kBarEmpty, w & 1);
    if (wg == 1) TRACE_AT(15, 0);
#define EPOCH (*reinterpret_cast<volatile unsigned*>(sm + kSmEpoch))

#pragma unroll 1
    for (int i = wg; i < kTiles; i += 2) {
      const int layer = i >= 7, ty = i - 7 * layer;
      TRACE_AT(i, 15);
      float acc[2][96];
      if (ty == 2 || ty == 6) {
        const int lane = lane_id();
        const uint32_t xa = sb + kSmX + ((lane >> 4) * 8 + (lane & 7)) * 128 + (((2 * w + ((lane >> 3) & 1)) ^ (lane & 7)) << 4);
        const float up = ty == 6 ? 2.f * kGeluBeta : 1.f, dn = ty == 6 ? 0.5f / kGeluBeta : 1.f;
#pragma unroll
        for (int h = 0; h < 2; h++) {
          const float* b2 = reinterpret_cast<const float*>(sm + kSmB2) + 64 * h + 16 * w + (lane >> 2);
          const float bias[2] = {ty == 6 ? b2[0] : 0.f, ty == 6 ? b2[8] : 0.f};
#pragma unroll
          for (int p = 0; p < 8; p++) {
            uint32_t r[4];
            ldsm4_t(xa + h * kTileBytes + p * 2048, r);
#pragma unroll
            for (int m = 0; m < 4; m++) {
              acc[h][8 * p + 2 * m] = fmaf(bf_lo(r[m]), up, bias[m & 1]);
              acc[h][8 * p + 2 * m + 1] = fmaf(bf_hi(r[m]), up, bias[m & 1]);
              asm volatile("" : "+f"(acc[h][8 * p + 2 * m]), "+f"(acc[h][8 * p + 2 * m + 1]));
              if (m & 1) yield_slot();
            }
          }
        }
        auto stage = [&](int qt) {
          const int h = qt >> 1;
#pragma unroll
          for (int p = 4 * (qt & 1); p < 4 * (qt & 1) + 4; p++) {
            const float* a = &acc[h][8 * p];
            stsm4_t(xa + h * kTileBytes + p * 2048, pack2(a[0] * dn, a[1] * dn), pack2(a[2] * dn, a[3] * dn),
                    pack2(a[4] * dn, a[5] * dn), pack2(a[6] * dn, a[7] * dn));
            if (STAGE_YIELD || (p & 3) == 3) yield_slot();
          }
          if (qt & 1) {
            fence_async_smem();
            __syncwarp();
            if (elect()) mbar_arrive(sb + kBarX + (i >> 2) * 16 + 8 * h);
            TRACE_AT(i, 8 + h);
          }
        };
        mainloop<128, true, false>(acc, sb, i, layer * 152 + ty * 16, ty == 6 ? 4 : 0, ty == 6 ? 56 : 16,
                            ty == 2 ? PAUSE_WO : -1, 2 * layer + 1, rel_addr, rel, ty == 2 ? 8 : -1, stage);
        TRACE_AT(i, 2);
        stage(2);
        stage(3);
      } else {
        const int xver = 2 * layer + (ty >= 3);
        const uint32_t stg = sb + kSmStg + w * 4096;
        const float4* vec = reinterpret_cast<const float4*>(sm + kSmV1) + (ty == 3 ? 0 : 64 * ty - 160);
        int lane;
        uint8_t* hdst = g_h + (b * 56 + (ty == 3 ? 3 * j : 16 * ty - 40 + 2 * j)) * kTileBytes + w * 4096;
        float2 st[4];
        unsigned epoch;
        auto pre = [&] {
          lane = lane_id();
          if (ty < 4) mbar_wait(sb + (ty == 1 ? kBarEpi + (i - 1) * 8 : kBarStat + xver * 8), 0);
#pragma unroll
          for (int c = 0; c < 4; c++) st[c] = reinterpret_cast<const float2*>(sm + kSmStat)[32 * w + 8 * c + (lane >> 2)];
          epoch = EPOCH;
        };
        auto team_stats = [&] {
          uint2* stat = g_stat + (xver * 16 + b) * 1024;
          lane = lane_id();
          publish_stats(sb, stat + j * 128, w, lane, EPOCH);
          gather_stats(sm, stat, 32 * w + lane, EPOCH);
          __syncwarp();
          if (elect()) mbar_arrive(sb + kBarStat + xver * 8);
          TRACE_AT(i, 14);
        };
        if (ty < 4) {
          head_blocks<192>(acc, sb, layer * 152 + (ty < 2 ? 2 * ty : 48), ty < 2 ? 2 * ty : 1, xver, rel_addr, rel);
          if (ty == 1) {
            if (i == 1) {
              mbar_wait(sb + kBarEpoch, 0);
              mbar_wait(sb + kBarInit, 0);
            }
            team_stats();
            if (i == 8) {
#pragma unroll
              for (int c = 0; c < 4; c++) st[c] = reinterpret_cast<const float2*>(sm + kSmStat)[32 * w + 8 * c + (lane >> 2)];
              add_mean_term(acc, st, sm, 1, lane);
            }
          }
          mainloop<192, false, false>(acc, sb, i, layer * 152 + (ty < 2 ? 4 + 14 * ty : 52), ty < 2 ? 2 * ty : 1, 14,
                                      ty == 1 ? PAUSE_QKV2 : -1, xver, rel_addr, rel, 0, pre);
          TRACE_AT(i, 2);
          if (layer == 0) mbar_wait(sb + kBarCs + ty * 8, 0);
          if (ty < 2) {
            if (i != 8) add_mean_term(acc, st, sm, ty, lane);
            epilogue_attn(acc, st, sm, sb, layer, ty, b, j, epoch, i, wg, w, lane);
            TRACE_AT(i, 3);
            continue;
          }
          scale_stats(st);
          gelu_chunk<2>(acc, st, vec, stg, lane, false, nullptr, 0);
        } else {
          if (ty == 4) {
            head_blocks<128>(acc, sb, layer * 152 + 50, 3, xver, rel_addr, rel);
            team_stats();
            mainloop<128, false, false>(acc, sb, i, layer * 152 + 66, 4, 14, -1, 0, rel_addr, rel, 0, pre);
          } else {
            mainloop<128, false, true>(acc, sb, i, layer * 152 + 80, 3, 16, -1, 0, rel_addr, rel, 0, pre);
          }
          TRACE_AT(i, 2);
          if (layer == 0) mbar_wait(sb + kBarCs + ty * 8, 0);
          scale_stats(st);
        }
        TRACE_AT(i, 8);
        gelu_chunk<0>(acc, st, vec, stg, lane, ty == 3, hdst + 2 * kTileBytes, sb + kBarFree + (i - 1) * 8);
        TRACE_AT(i, 9);
        gelu_chunk<1>(acc, st, vec, stg, lane, true, hdst, 0);
        TRACE_AT(i, 10);
        fence_async_smem();
        __syncwarp();
        if (elect()) mbar_arrive(sb + kBarEpi + i * 8);
      }
      TRACE_AT(i, 3);
    }
#undef EPOCH
    asm volatile("barrier.cluster.arrive.relaxed.aligned;\nbarrier.cluster.wait.aligned;" ::: "memory");
    if (wg == 1) TRACE_AT(15, 2);
  }
}

void build_segments(uint32_t* seg) {
  int n = 0, fine = 0;
  auto per_source = [&](int kind, int dep) { return (FINE & kind) ? 28 + (fine++ & 1) : dep; };
  auto add = [&](int ty, int cnt, int kb0, int mode, int wide, int depth5, int dep, int reset) {
    seg[n++] = ty | cnt << 3 | kb0 << 9 | mode << 15 | wide << 17 | depth5 << 18 | dep << 19 | reset << 24;
  };
  for (int l = 0; l < 2; l++) {
    const int t = 7 * l;
    if (l == 0) {
      add(0, 14, 2, kModePlain, 1, 0, 31, 1);
      add(1, 14, 2, kModePlain, 1, 0, 31, 0);
    } else {
      add(0, 2, 0, kModeHead, 1, 0, 31, 1);
      add(1, 2, 0, kModeHead, 1, 0, 31, 0);
      add(0, 7, 0, kModeSkip, 1, 0, per_source(1, 6), 0);
      add(0, 7, 1, kModeSkip, 1, 0, 15, 0);
      add(1, 7, 0, kModeSkip, 1, 0, 31, 0);
      add(1, 7, 1, kModeSkip, 1, 0, 31, 0);
    }
    add(2, 4, 0, kModePlain, 0, 0, t, 1);
    add(2, 4, 4, kModePlain, 0, 1, 31, 0);
    add(2, 1, 0, kModeHead, 0, 1, 31, 0);
    add(2, 7, 8, kModeSkip, 0, 1, per_source(2, t + 1), 0);
    add(3, 2, 0, kModeHead, 1, 0, 31, 2);
    add(4, 2, 0, kModeHead, 1, 0, 31, 0);
    add(3, 7, 0, kModeSkip, 1, 0, per_source(1, t + 2), 0);
    add(3, 7, 1, kModeSkip, 1, 0, 14 + 2 * l, 0);
    add(4, 4, 0, kModeSkip, 0, 0, 31, 3);
    add(4, 3, 0, kModeContinue, 0, 1, 31, 0);
    add(4, 7, 1, kModeSkip, 0, 1, 31, 0);
    add(5, 16, 0, kModePlain, 0, 1, 31, 0);
    add(6, 24, 0, kModePlain, 0, 1, t + 3, 0);
    add(6, 16, 24, kModePlain, 0, 1, t + 4, 0);
    add(6, 16, 40, kModePlain, 0, 1, t + 5, 0);
  }
}

typedef CUresult (*EncodeTiledFn)(CUtensorMap*, CUtensorMapDataType, cuuint32_t, void*, const cuuint64_t*,
                                  const cuuint64_t*, const cuuint32_t*, const cuuint32_t*, CUtensorMapInterleave,
                                  CUtensorMapSwizzle, CUtensorMapL2promotion, CUtensorMapFloatOOBfill);

CUtensorMap make_map(EncodeTiledFn enc, const void* p, int rank, const cuuint64_t* dims, const cuuint64_t* strides,
                     const cuuint32_t* box, CUtensorMapSwizzle swizzle = CU_TENSOR_MAP_SWIZZLE_128B) {
  CUtensorMap m;
  const cuuint32_t es[5] = {1, 1, 1, 1, 1};
  enc(&m, CU_TENSOR_MAP_DATA_TYPE_BFLOAT16, rank, const_cast<void*>(p), dims, strides, box, es,
      CU_TENSOR_MAP_INTERLEAVE_NONE, swizzle, CU_TENSOR_MAP_L2_PROMOTION_L2_128B,
      CU_TENSOR_MAP_FLOAT_OOB_FILL_NONE);
  return m;
}

CUtensorMap weight_map(EncodeTiledFn enc, const void* p, int k, int n, int blocks) {
  const cuuint64_t dims[3] = {64, (cuuint64_t)k, (cuuint64_t)n / 64};
  const cuuint64_t strides[2] = {(cuuint64_t)n * 2, 128};
  const cuuint32_t box[3] = {64, 32, (cuuint32_t)blocks};
  return make_map(enc, p, 3, dims, strides, box);
}

CUtensorMap slab_map(EncodeTiledFn enc, const void* p, int n) {
  const cuuint64_t dims[2] = {(cuuint64_t)n, kD};
  const cuuint64_t strides[1] = {(cuuint64_t)n * 2};
  const cuuint32_t box[2] = {128, 128};
  return make_map(enc, p, 2, dims, strides, box, CU_TENSOR_MAP_SWIZZLE_NONE);
}

CUtensorMap token_map(EncodeTiledFn enc, const void* p, int rows) {
  const cuuint64_t dims[2] = {2 * kD, 1024};
  const cuuint64_t strides[1] = {4 * kD};
  const cuuint32_t box[2] = {64, (cuuint32_t)rows};
  return make_map(enc, p, 2, dims, strides, box);
}

}

extern "C" void kernel_launch(void* const* d_in, const int* in_sizes, int n_in, void* d_out, int out_size) {
  (void)in_sizes; (void)n_in; (void)out_size;
  static EncodeTiledFn enc = nullptr;
  if (!enc) {
    void* fn = nullptr;
    cudaDriverEntryPointQueryResult q;
    cudaGetDriverEntryPoint("cuTensorMapEncodeTiled", &fn, cudaEnableDefault, &q);
    enc = (EncodeTiledFn)fn;
    cudaFuncSetAttribute(fused_layers_kernel, cudaFuncAttributeMaxDynamicSharedMemorySize, kSmBytes);
  }
  Params prm;
  prm.b1 = (const __nv_bfloat16*)d_in[5];
  prm.b2 = (const __nv_bfloat16*)d_in[7];
  build_segments(prm.seg);
  const cuuint64_t qd[3] = {kD, kD, 3}, qs[2] = {3 * kD * 2, kD * 2};
  const cuuint32_t qb[3] = {64, 32, 3};
  const CUtensorMap map_x = token_map(enc, d_in[0], 128);
  const CUtensorMap map_out = token_map(enc, d_out, 128);
  const CUtensorMap map_qkv = make_map(enc, d_in[1], 3, qd, qs, qb);
  const CUtensorMap map_wo = weight_map(enc, d_in[2], kD, kD, 2);
  const CUtensorMap map_w1a = weight_map(enc, d_in[4], kD, kF, 3);
  const CUtensorMap map_w1b = weight_map(enc, d_in[4], kD, kF, 2);
  const CUtensorMap map_w2 = weight_map(enc, d_in[6], kF, kD, 2);
  fused_layers_kernel<<<kGrid, 384, kSmBytes>>>(map_x, map_out, map_qkv, map_wo, map_w1a, map_w1b, map_w2,
                                                slab_map(enc, d_in[1], 3 * kD), slab_map(enc, d_in[4], kF), prm);
}
```

```cpp
#include <cuda.h>
#include <cuda_bf16.h>
#include <cuda_runtime.h>
#include <stdint.h>

namespace {

constexpr int kD = 1024;
constexpr int kF = 3584;
constexpr int kCtas = 128;
constexpr int kGrid = 132;
constexpr int kTiles = 14;
constexpr int kTileBytes = 16384;

constexpr int kSmRing = 0;
constexpr int kSmX = 163840;
constexpr int kSmStg = kSmX + 32768;
constexpr int kSmHalo = kSmStg + 16384;
constexpr int kSmCsQ = kSmHalo + 6144;
constexpr int kSmV1 = kSmCsQ + 384 * 4;
constexpr int kSmB2 = kSmV1 + 448 * 8;
constexpr int kSmStat = kSmB2 + 128 * 4;
constexpr int kSmBar = kSmStat + 128 * 8;
constexpr int kBarFull = kSmBar;
constexpr int kBarTurn = kBarFull + 8 * 8;
constexpr int kBarReady = kBarTurn + 14 * 8;
constexpr int kBarSrc = kBarReady + 17 * 8;
constexpr int kBarPause = kBarSrc + 8 * 8;
constexpr int kBarFree = kBarPause + 4 * 8;
constexpr int kBarCs = kBarFree + 14 * 8;
constexpr int kBarInit = kBarCs + 6 * 8;
constexpr int kBarEpoch = kBarInit + 8;
constexpr int kBarEmpty = kBarEpoch + 8;
constexpr int kBarEpi = kBarEmpty + 9 * 8;
constexpr int kBarX = kBarEpi + 14 * 8;
constexpr int kBarStat = kBarX + 8 * 8;
constexpr int kBarResume = kBarStat + 4 * 8;
constexpr int kSmEpoch = kBarResume + 4 * 8;
constexpr int kSmBytes = kSmEpoch + 16;
constexpr int kSegs = 38;

constexpr int kFlagLines = kTiles * 16;

constexpr unsigned kSpinLimit = 1u << 22;

__device__ __align__(1024) uint8_t g_x[16 * 16 * kTileBytes];
__device__ __align__(1024) uint8_t g_o[16 * 16 * kTileBytes];
__device__ __align__(1024) uint8_t g_h[16 * 56 * kTileBytes];
__device__ __align__(128) uint2 g_stat[4 * 16 * 128 * 8];
__device__ __align__(128) unsigned g_cs[3 * kD + kF];
__device__ __align__(128) uint4 g_halo[2 * 16 * 16 * 256];
__device__ __align__(128) unsigned g_flag[kFlagLines * 32];
__device__ unsigned g_ticket;

#define TRACE_AT(tile, k)
#define TRACE_PUB(i, k, c)
#define TRACE_ISSUE(which, nb)

struct Params {
  const __nv_bfloat16* b1;
  const __nv_bfloat16* b2;
  uint32_t seg[kSegs];
};

__device__ __forceinline__ uint32_t smem_u32(const void* p) {
  return (uint32_t)__cvta_generic_to_shared(p);
}
__device__ __forceinline__ uint32_t mapa(uint32_t a, uint32_t cta) {
  uint32_t r;
  asm("mapa.shared::cluster.u32 %0, %1, %2;" : "=r"(r) : "r"(a), "r"(cta));
  return r;
}
__device__ __forceinline__ void mbar_init(uint32_t bar, int cnt) {
  asm volatile("mbarrier.init.shared::cta.b64 [%0], %1;" ::"r"(bar), "r"(cnt) : "memory");
}
__device__ __forceinline__ void mbar_expect_tx(uint32_t bar, uint32_t bytes) {
  asm volatile("mbarrier.arrive.expect_tx.shared::cta.b64 _, [%0], %1;" ::"r"(bar), "r"(bytes) : "memory");
}
__device__ __forceinline__ void mbar_arrive(uint32_t bar) {
  asm volatile("mbarrier.arrive.shared::cta.b64 _, [%0];" ::"r"(bar) : "memory");
}
__device__ __forceinline__ void mbar_arrive_cluster(uint32_t cluster_addr) {
  asm volatile("mbarrier.arrive.shared::cluster.b64 _, [%0];" ::"r"(cluster_addr) : "memory");
}
__device__ __forceinline__ void mbar_wait(uint32_t bar, uint32_t parity) {
  asm volatile("{\n.reg .pred p;\nRETRY:\nmbarrier.try_wait.parity.shared::cta.b64 p, [%0], %1;\n"
               "@!p bra.uni RETRY;\n}" ::"r"(bar), "r"(parity) : "memory");
}
__device__ __forceinline__ void mbar_wait_bounded(uint32_t bar, uint32_t parity) {
  asm volatile("{\n.reg .pred p;\n.reg .u32 c;\nmov.u32 c, 0;\nRETRY:\n"
               "mbarrier.try_wait.parity.shared::cta.b64 p, [%0], %1;\n@p bra.uni DONE;\n"
               "add.u32 c, c, 1;\nsetp.lt.u32 p, c, %2;\n@p bra.uni RETRY;\ntrap;\nDONE:\n}"
               ::"r"(bar), "r"(parity), "n"(1u << 19) : "memory");
}
__device__ __forceinline__ void tma3d(uint32_t dst, const CUtensorMap* m, uint32_t bar, int c0, int c1, int c2) {
  asm volatile(
      "cp.async.bulk.tensor.3d.shared::cluster.global.mbarrier::complete_tx::bytes [%0], [%1, {%3, %4, %5}], [%2];"
      ::"r"(dst), "l"(m), "r"(bar), "r"(c0), "r"(c1), "r"(c2) : "memory");
}
__device__ __forceinline__ void tma3d_mc(uint32_t dst, const CUtensorMap* m, uint32_t bar, int c0, int c1, int c2) {
  asm volatile(
      "cp.async.bulk.tensor.3d.shared::cluster.global.mbarrier::complete_tx::bytes.multicast::cluster"
      " [%0], [%1, {%3, %4, %5}], [%2], %6;"
      ::"r"(dst), "l"(m), "r"(bar), "r"(c0), "r"(c1), "r"(c2), "h"((uint16_t)3) : "memory");
}
__device__ __forceinline__ void tma2d(uint32_t dst, const CUtensorMap* m, uint32_t bar, int c0, int c1) {
  asm volatile(
      "cp.async.bulk.tensor.2d.shared::cluster.global.mbarrier::complete_tx::bytes [%0], [%1, {%3, %4}], [%2];"
      ::"r"(dst), "l"(m), "r"(bar), "r"(c0), "r"(c1) : "memory");
}
__device__ __forceinline__ void tma2d_store(const CUtensorMap* m, uint32_t src, int c0, int c1) {
  asm volatile("cp.async.bulk.tensor.2d.global.shared::cta.bulk_group [%0, {%2, %3}], [%1];"
               ::"l"(m), "r"(src), "r"(c0), "r"(c1) : "memory");
}
__device__ __forceinline__ int lane_id() {
  int l;
  asm volatile("mov.u32 %0, %%laneid;" : "=r"(l));
  return l;
}
__device__ __forceinline__ bool elect() {
  uint32_t p;
  asm volatile("{\n.reg .pred p;\nelect.sync _|p, 0xffffffff;\nselp.b32 %0, 1, 0, p;\n}" : "=r"(p));
  return p;
}
__device__ __forceinline__ void bulk_load(uint32_t dst, const void* src, uint32_t bytes, uint32_t bar) {
  asm volatile("cp.async.bulk.shared::cluster.global.mbarrier::complete_tx::bytes [%0], [%1], %2, [%3];"
               ::"r"(dst), "l"(src), "r"(bytes), "r"(bar) : "memory");
}
__device__ __forceinline__ void bulk_store(void* dst, uint32_t src, uint32_t bytes) {
  asm volatile("cp.async.bulk.global.shared::cta.bulk_group [%0], [%1], %2;" ::"l"(dst), "r"(src), "r"(bytes)
               : "memory");
}
__device__ __forceinline__ void bulk_commit() { asm volatile("cp.async.bulk.commit_group;" ::: "memory"); }
__device__ __forceinline__ void bulk_wait_read() { asm volatile("cp.async.bulk.wait_group.read 0;" ::: "memory"); }
__device__ __forceinline__ void bulk_wait() { asm volatile("cp.async.bulk.wait_group 0;" ::: "memory"); }
__device__ __forceinline__ void fence_async_smem() { asm volatile("fence.proxy.async.shared::cta;" ::: "memory"); }
__device__ __forceinline__ unsigned ld_relaxed(const unsigned* p) {
  unsigned v;
  asm volatile("ld.relaxed.gpu.global.u32 %0, [%1];" : "=r"(v) : "l"(p) : "memory");
  return v;
}
__device__ __forceinline__ uint2 ld_relaxed2(const uint2* p) {
  uint2 v;
  asm volatile("ld.relaxed.gpu.global.v2.u32 {%0, %1}, [%2];" : "=r"(v.x), "=r"(v.y) : "l"(p) : "memory");
  return v;
}
__device__ __forceinline__ void st_relaxed(unsigned* p, unsigned v) {
  asm volatile("st.relaxed.gpu.global.u32 [%0], %1;" ::"l"(p), "r"(v) : "memory");
}
__device__ __forceinline__ void st_release(unsigned* p, unsigned v) {
  asm volatile("st.release.gpu.global.u32 [%0], %1;" ::"l"(p), "r"(v) : "memory");
}
#define ACQ_MODE 1
__device__ __forceinline__ void wait_flags(const unsigned* p, unsigned epoch) {
  unsigned spins = 0;
  while (true) {
    const unsigned v = ld_relaxed(p);
    if (__all_sync(0xffffffffu, v == epoch)) break;
    if (++spins > kSpinLimit) __trap();
  }
  if (ACQ_MODE) asm volatile("fence.acquire.gpu;\nfence.proxy.async.global;" ::: "memory");
  __syncwarp();
}
__device__ __forceinline__ void st_packet(uint4* p, uint32_t d0, uint32_t d1, uint32_t tag) {
  asm volatile("{\n.reg .b128 v;\n.reg .b64 x, y;\nmov.b64 x, {%1, %2};\nmov.b64 y, {%3, %3};\nmov.b128 v, {x, y};\n"
               "st.relaxed.gpu.global.b128 [%0], v;\n}" ::"l"(p), "r"(d0), "r"(d1), "r"(tag) : "memory");
}
__device__ __forceinline__ void ld_packet(const uint4* p, uint32_t& d0, uint32_t& d1, uint32_t& tag) {
  asm volatile("{\n.reg .b128 v;\n.reg .b64 x, y;\n.reg .b32 u;\nld.relaxed.gpu.global.b128 v, [%3];\n"
               "mov.b128 {x, y}, v;\nmov.b64 {%0, %1}, x;\nmov.b64 {%2, u}, y;\n}"
               : "=r"(d0), "=r"(d1), "=r"(tag) : "l"(p) : "memory");
}
__device__ __forceinline__ unsigned tag_value(float v, unsigned epoch) {
  return (__float_as_uint(v) & ~7u) | (epoch & 7u);
}
__device__ __forceinline__ float untag_value(unsigned v) { return __uint_as_float(v & ~7u); }
__device__ __forceinline__ void stsm4(uint32_t a, uint32_t r0, uint32_t r1, uint32_t r2, uint32_t r3) {
  asm volatile("stmatrix.sync.aligned.m8n8.x4.shared.b16 [%0], {%1, %2, %3, %4};" ::"r"(a), "r"(r0), "r"(r1),
               "r"(r2), "r"(r3) : "memory");
}
__device__ __forceinline__ void stsm4_t(uint32_t a, uint32_t r0, uint32_t r1, uint32_t r2, uint32_t r3) {
  asm volatile("stmatrix.sync.aligned.m8n8.x4.trans.shared.b16 [%0], {%1, %2, %3, %4};" ::"r"(a), "r"(r0),
               "r"(r1), "r"(r2), "r"(r3) : "memory");
}
__device__ __forceinline__ uint32_t transpose8(uint32_t a) {
  uint32_t d;
  asm volatile("movmatrix.sync.aligned.m8n8.trans.b16 %0, %1;" : "=r"(d) : "r"(a));
  return d;
}
__device__ __forceinline__ void mma16816(float (&c)[4], uint32_t a0, uint32_t a1, uint32_t a2, uint32_t a3,
                                         uint32_t b0, uint32_t b1) {
  asm volatile("mma.sync.aligned.m16n8k16.row.col.f32.bf16.bf16.f32 {%0, %1, %2, %3}, {%4, %5, %6, %7}, {%8, %9}, "
               "{%0, %1, %2, %3};"
               : "+f"(c[0]), "+f"(c[1]), "+f"(c[2]), "+f"(c[3])
               : "r"(a0), "r"(a1), "r"(a2), "r"(a3), "r"(b0), "r"(b1));
}
__device__ __forceinline__ void mma1688(float (&c)[4], uint32_t a0, uint32_t a1, uint32_t b0) {
  asm volatile("mma.sync.aligned.m16n8k8.row.col.f32.bf16.bf16.f32 {%0, %1, %2, %3}, {%4, %5}, {%6}, {%0, %1, %2, %3};"
               : "+f"(c[0]), "+f"(c[1]), "+f"(c[2]), "+f"(c[3]) : "r"(a0), "r"(a1), "r"(b0));
}
__device__ __forceinline__ float shfl_xor(float v, int m) {
  float r;
  asm volatile("shfl.sync.bfly.b32 %0, %1, %2, 31, 0xffffffff;" : "=f"(r) : "f"(v), "r"(m));
  return r;
}
__device__ __forceinline__ float tanh_fast(float x) {
  float r;
  asm volatile("tanh.approx.f32 %0, %1;" : "=f"(r) : "f"(x));
  return r;
}
__device__ __forceinline__ void ldsm4(uint32_t a, uint32_t (&r)[4]) {
  asm volatile("ldmatrix.sync.aligned.m8n8.x4.shared.b16 {%0, %1, %2, %3}, [%4];"
               : "=r"(r[0]), "=r"(r[1]), "=r"(r[2]), "=r"(r[3]) : "r"(a) : "memory");
}
__device__ __forceinline__ void ldsm4_t(uint32_t a, uint32_t (&r)[4]) {
  asm volatile("ldmatrix.sync.aligned.m8n8.x4.trans.shared.b16 {%0, %1, %2, %3}, [%4];"
               : "=r"(r[0]), "=r"(r[1]), "=r"(r[2]), "=r"(r[3]) : "r"(a) : "memory");
}
__device__ __forceinline__ uint32_t pack2(float lo, float hi) {
  uint32_t r;
  asm volatile("cvt.rn.bf16x2.f32 %0, %1, %2;" : "=r"(r) : "f"(hi), "f"(lo));
  return r;
}
__device__ __forceinline__ float bf_lo(uint32_t r) { return __uint_as_float(r << 16); }
__device__ __forceinline__ float bf_hi(uint32_t r) { return __uint_as_float(r & 0xffff0000u); }
__device__ __forceinline__ float ex2(float x) {
  float r;
  asm("ex2.approx.ftz.f32 %0, %1;" : "=f"(r) : "f"(x));
  return r;
}
__device__ __forceinline__ float rcp(float x) {
  float r;
  asm("rcp.approx.ftz.f32 %0, %1;" : "=f"(r) : "f"(x));
  return r;
}
template <int N>
__device__ __forceinline__ void wg_wait() {
  asm volatile("wgmma.wait_group.sync.aligned %0;" ::"n"(N) : "memory");
}
__device__ __forceinline__ void yield_slot() { asm volatile("pmevent 0;"); }
__device__ __forceinline__ void wg_bar(int wg) { asm volatile("bar.sync %0, 128;" ::"r"(wg + 1) : "memory"); }

template <int N, int KIND>
__device__ __forceinline__ void mma_kblock(float (&acc)[2][96], uint32_t a, uint32_t b);

#define F8(m, d, i) m(d[i]), m(d[i + 1]), m(d[i + 2]), m(d[i + 3]), m(d[i + 4]), m(d[i + 5]), m(d[i + 6]), m(d[i + 7])
#define KSTEP(N, A, B, oa0, oa1, ob, sd)                                                   \
  "add.u32 t, " B ", " #ob ";\nmov.b64 db, {t, hb};\n"                                      \
  "add.u32 t, " A ", " #oa0 ";\nmov.b64 da, {t, ha};\n"                                     \
  "wgmma.mma_async.sync.aligned.m64n" #N "k16.f32.bf16.bf16 {" ACC##N##_0 "}, da, db, " #sd ", 1, 1, 0, 1;\n" \
  "add.u32 t, " A ", " #oa1 ";\nmov.b64 da, {t, ha};\n"                                     \
  "wgmma.mma_async.sync.aligned.m64n" #N "k16.f32.bf16.bf16 {" ACC##N##_1 "}, da, db, " #sd ", 1, 1, 0, 1;\n"

#define MMA_KBLOCK(N, KIND, A, B, ob2, ob3, sd, MID, MODE)                                 \
  template <>                                                                              \
  __device__ __forceinline__ void mma_kblock<N, KIND>(float (&acc)[2][96], uint32_t a, uint32_t b) { \
    asm volatile("{\n.reg .b32 t, ha, hb;\n.reg .b64 da, db;\n"                            \
                 "mov.b32 ha, 0x40000080;\nmov.b32 hb, 0x40000040;\n"                       \
                 "wgmma.fence.sync.aligned;\n"                                             \
                 KSTEP(N, A, B, 0, 64, 0, sd) KSTEP(N, A, B, 2, 66, 128, 1) KSTEP(N, A, B, 4, 68, ob2, 1) \
                 MID KSTEP(N, A, B, 6, 70, ob3, 1) "wgmma.commit_group.sync.aligned;\n}\n"  \
                 : OPS##N(MODE) : "r"(a), "r"(b) : "memory");                              \
  }
#define MMA_KBLOCKS(N, A, B, ob2, ob3)                                                     \
  MMA_KBLOCK(N, 0, A, B, ob2, ob3, 1, "", "+f")                                            \
  MMA_KBLOCK(N, 1, A, B, ob2, ob3, 1, "wgmma.commit_group.sync.aligned;\n", "+f")          \
  MMA_KBLOCK(N, 2, A, B, ob2, ob3, 0, "", "=f")

#define ACC128_0 \
  "%0, %1, %2, %3, %4, %5, %6, %7, %8, %9, %10, %11, %12, %13, %14, %15, " \
  "%16, %17, %18, %19, %20, %21, %22, %23, %24, %25, %26, %27, %28, %29, %30, %31, " \
  "%32, %33, %34, %35, %36, %37, %38, %39, %40, %41, %42, %43, %44, %45, %46, %47, " \
  "%48, %49, %50, %51, %52, %53, %54, %55, %56, %57, %58, %59, %60, %61, %62, %63"
#define ACC128_1 \
  "%64, %65, %66, %67, %68, %69, %70, %71, %72, %73, %74, %75, %76, %77, %78, %79, " \
  "%80, %81, %82, %83, %84, %85, %86, %87, %88, %89, %90, %91, %92, %93, %94, %95, " \
  "%96, %97, %98, %99, %100, %101, %102, %103, %104, %105, %106, %107, %108, %109, %110, %111, " \
  "%112, %113, %114, %115, %116, %117, %118, %119, %120, %121, %122, %123, %124, %125, %126, %127"
#define OPS128(m) \
  F8(m, acc[0], 0), F8(m, acc[0], 8), F8(m, acc[0], 16), F8(m, acc[0], 24), F8(m, acc[0], 32), F8(m, acc[0], 40), F8(m, acc[0], 48), F8(m, acc[0], 56), \
        F8(m, acc[1], 0), F8(m, acc[1], 8), F8(m, acc[1], 16), F8(m, acc[1], 24), F8(m, acc[1], 32), F8(m, acc[1], 40), F8(m, acc[1], 48), F8(m, acc[1], 56)
MMA_KBLOCKS(128, "%128", "%129", 512, 640)

#define ACC192_0 \
  "%0, %1, %2, %3, %4, %5, %6, %7, %8, %9, %10, %11, %12, %13, %14, %15, " \
  "%16, %17, %18, %19, %20, %21, %22, %23, %24, %25, %26, %27, %28, %29, %30, %31, " \
  "%32, %33, %34, %35, %36, %37, %38, %39, %40, %41, %42, %43, %44, %45, %46, %47, " \
  "%48, %49, %50, %51, %52, %53, %54, %55, %56, %57, %58, %59, %60, %61, %62, %63, " \
  "%64, %65, %66, %67, %68, %69, %70, %71, %72, %73, %74, %75, %76, %77, %78, %79, " \
  "%80, %81, %82, %83, %84, %85, %86, %87, %88, %89, %90, %91, %92, %93, %94, %95"
#define ACC192_1 \
  "%96, %97, %98, %99, %100, %101, %102, %103, %104, %105, %106, %107, %108, %109, %110, %111, " \
  "%112, %113, %114, %115, %116, %117, %118, %119, %120, %121, %122, %123, %124, %125, %126, %127, " \
  "%128, %129, %130, %131, %132, %133, %134, %135, %136, %137, %138, %139, %140, %141, %142, %143, " \
  "%144, %145, %146, %147, %148, %149, %150, %151, %152, %153, %154, %155, %156, %157, %158, %159, " \
  "%160, %161, %162, %163, %164, %165, %166, %167, %168, %169, %170, %171, %172, %173, %174, %175, " \
  "%176, %177, %178, %179, %180, %181, %182, %183, %184, %185, %186, %187, %188, %189, %190, %191"
#define OPS192(m) \
  F8(m, acc[0], 0), F8(m, acc[0], 8), F8(m, acc[0], 16), F8(m, acc[0], 24), F8(m, acc[0], 32), F8(m, acc[0], 40), F8(m, acc[0], 48), F8(m, acc[0], 56), F8(m, acc[0], 64), F8(m, acc[0], 72), F8(m, acc[0], 80), F8(m, acc[0], 88), \
        F8(m, acc[1], 0), F8(m, acc[1], 8), F8(m, acc[1], 16), F8(m, acc[1], 24), F8(m, acc[1], 32), F8(m, acc[1], 40), F8(m, acc[1], 48), F8(m, acc[1], 56), F8(m, acc[1], 64), F8(m, acc[1], 72), F8(m, acc[1], 80), F8(m, acc[1], 88)
MMA_KBLOCKS(192, "%192", "%193", 768, 896)

#define TSTEP(REGS, W, X, ow, ox)                                                           \
  "add.u32 t, " X ", " #ox ";\nmov.b64 db, {t, hi};\nadd.u32 t, " W ", " #ow ";\nmov.b64 da, {t, hi};\n" \
  "wgmma.mma_async.sync.aligned.m64n128k16.f32.bf16.bf16 {" REGS "}, da, db, 1, 1, 1, 1, 0;\n"
#define THEAD "{\n.reg .b32 t, hi;\n.reg .b64 da, db;\nmov.b32 hi, 0x40000040;\nwgmma.fence.sync.aligned;\n"
#define TTAIL "wgmma.commit_group.sync.aligned;\n}\n"
__device__ __forceinline__ void mma_kblock_t(float (&acc)[2][96], uint32_t wd, uint32_t xd) {
  asm volatile(THEAD TSTEP(ACC128_0, "%128", "%129", 0, 0) TSTEP(ACC128_1, "%128", "%129", 256, 0)
               TSTEP(ACC128_0, "%128", "%129", 128, 2) TSTEP(ACC128_1, "%128", "%129", 384, 2)
               TSTEP(ACC128_0, "%128", "%129", 512, 4) TSTEP(ACC128_1, "%128", "%129", 768, 4)
               TSTEP(ACC128_0, "%128", "%129", 640, 6) TSTEP(ACC128_1, "%128", "%129", 896, 6) TTAIL
               : OPS128("+f") : "r"(wd), "r"(xd) : "memory");
}
__device__ __forceinline__ void mma_half_t(float (&d)[96], uint32_t wd, uint32_t xd) {
  asm volatile(THEAD TSTEP(ACC128_0, "%64", "%65", 0, 0) TSTEP(ACC128_0, "%64", "%65", 128, 2)
               TSTEP(ACC128_0, "%64", "%65", 512, 4) TSTEP(ACC128_0, "%64", "%65", 640, 6) TTAIL
               : F8("+f", d, 0), F8("+f", d, 8), F8("+f", d, 16), F8("+f", d, 24), F8("+f", d, 32), F8("+f", d, 40),
                 F8("+f", d, 48), F8("+f", d, 56) : "r"(wd), "r"(xd) : "memory");
}

enum { kModePlain = 0, kModeHead = 1, kModeSkip = 2, kModeContinue = 3 };

template <int N>
__device__ __forceinline__ void fence_acc(float (&acc)[2][96]) {
#pragma unroll
  for (int h = 0; h < 2; h++)
#pragma unroll
    for (int i = 0; i < N / 2; i++) asm volatile("" : "+f"(acc[h][i])::"memory");
}

constexpr uint32_t kToB = (kTileBytes >> 4) + ((4096u >> 4) << 16) - (1u << 16);

#define TRACE_KB(nb)

#define HEAD_BOTH 4
template <int N>
__device__ __forceinline__ void head_blocks(float (&acc)[2][96], uint32_t sb, int n0, int slot, int xver,
                                            uint32_t rel_addr, bool rel) {
  const uint32_t ring = (((sb & 0x3FFFF) + kSmRing) >> 4) | (1u << 16);
  const uint32_t xdesc = (((sb & 0x3FFFF) + kSmX) >> 4) | (1u << 16);
  const uint32_t s0 = ring + slot * 2560, s1 = ring + ((slot + 1) & 3) * 2560;
  const uint32_t nb = n0 * 8, xbar = sb + kBarX + (xver - 1) * 16;
  if (xver > 0) {
    mbar_wait(xbar + ((HEAD_BOTH >> xver) & 1) * 8, 0);
    mbar_wait(sb + kBarTurn + (xver == 1 ? 2 : 3 * xver) * 8, 0);
  }
  mbar_wait(sb + kBarFull + (nb & 56), nb >> 6);
  if (n0 == 0) TRACE_AT(0, 1);
  TRACE_KB(nb);
  mma_kblock<N, 2>(acc, xver > 0 ? xdesc : s0, s0 + kToB);
  if (xver > 0) mbar_wait(xbar + 8, 0);
  mbar_wait(sb + kBarFull + (nb & 56) + 8, nb >> 6);
  TRACE_KB(nb + 8);
  mma_kblock<N, 0>(acc, xver > 0 ? xdesc + (kTileBytes >> 4) : s1, s1 + kToB);
  wg_wait<1>();
  if (rel) mbar_arrive_cluster(rel_addr + (nb & 56));
  wg_wait<0>();
  if (rel) mbar_arrive_cluster(rel_addr + (nb & 56) + 8);
  fence_acc<N>(acc);
}

template <int N, bool RESID, bool FRESH, class Pre>
__device__ __forceinline__ void mainloop(float (&acc)[2][96], uint32_t sb, int tile, int n0, int slot, int nkb,
                                         int pause_kk, int att, uint32_t rel_addr, bool rel, int own_kk, Pre pre) {
  constexpr uint32_t kStep = (N == 192 ? 5 : 4) * 512;
  const uint32_t ring = (((sb & 0x3FFFF) + kSmRing) >> 4) | (1u << 16);
  uint32_t st = ring + slot * kStep;
  uint32_t nb = n0 * 8, prev = 64;
  const uint32_t last = nb + 8 * (nkb - (RESID ? 3 : 1)), own = nb + 8 * own_kk;
  const uint32_t stg = (((sb & 0x3FFFF) + kSmStg) >> 4) | (1u << 16);
  uint32_t stop = pause_kk >= 0 ? nb + 8 * pause_kk : last;
  const bool signal = (threadIdx.x & 127) == 64;
  if (!FRESH) fence_acc<N>(acc);
  if (tile > 0) mbar_wait(sb + kBarTurn + (tile - 1) * 8, 0);
  TRACE_AT(tile, 0);
  if constexpr (FRESH) {
    mbar_wait(sb + kBarFull + (nb & 56), nb >> 6);
    TRACE_KB(nb);
    mma_kblock<N, 2>(acc, st, st + kToB);
    prev = nb & 56;
    st += kStep;
    nb += 8;
  }
#pragma unroll 1
  while (true) {
#pragma unroll 1
    do {
      mbar_wait(sb + kBarFull + (nb & 56), nb >> 6);
      TRACE_KB(nb);
      if constexpr (RESID) mma_kblock_t(acc, st + kToB, nb == own ? stg : st);
      else mma_kblock<N, 0>(acc, st, st + kToB);
      wg_wait<1>();
      if (rel) mbar_arrive_cluster(rel_addr + prev);
      prev = nb & 56;
      st += kStep;
      if (st == ring + 10240) st = ring;
      nb += 8;
    } while (nb != stop);
    if (stop == last) break;
    stop = last;
    if (signal) mbar_arrive(sb + kBarPause + att * 8);
    wg_wait<0>();
    if (rel) mbar_arrive_cluster(rel_addr + prev);
    prev = 64;
    mbar_wait(sb + kBarResume + att * 8, 0);
  }
  mbar_wait(sb + kBarFull + (nb & 56), nb >> 6);
  TRACE_KB(nb);
  if constexpr (RESID) {
    const uint32_t z = gridDim.y - 1;
    const uint32_t s2 = st + kStep, s3 = s2 == ring + 8192 ? ring : s2 + kStep;
    mma_half_t(acc[0], st + kToB, st);
    wg_wait<1>();
    if (rel) mbar_arrive_cluster(rel_addr + 32);
    mbar_wait(sb + kBarFull + 48, nb >> 6);
    TRACE_KB(nb + 8);
    mma_half_t(acc[0], s2 + kToB, s2);
    mbar_wait(sb + kBarFull + 56, nb >> 6);
    TRACE_KB(nb + 16);
    mma_half_t(acc[0], s3 + kToB, s3);
    mma_half_t(acc[1], st + kToB + 256, st + z);
    mma_half_t(acc[1], s2 + kToB + 256, s2 + z);
    wg_wait<2>();
#pragma unroll
    for (int i = 0; i < 64; i++) asm volatile("" : "+f"(acc[0][i])::"memory");
    pre(0);
    mma_half_t(acc[1], s3 + kToB + 256, s3 + z);
    wg_wait<2>();
    if (rel) mbar_arrive_cluster(rel_addr + 40);
    pre(1);
    wg_wait<1>();
    if (rel) mbar_arrive_cluster(rel_addr + 48);
    if (signal) mbar_arrive(sb + kBarTurn + tile * 8);
    wg_wait<0>();
    if (rel) mbar_arrive_cluster(rel_addr + 56);
#pragma unroll
    for (int i = 0; i < 64; i++) asm volatile("" : "+f"(acc[1][i])::"memory");
  } else {
    mma_kblock<N, 1>(acc, st, st + kToB);
    wg_wait<2>();
    if (rel) mbar_arrive_cluster(rel_addr + prev);
    pre();
    wg_wait<1>();
    if (signal) mbar_arrive(sb + kBarTurn + tile * 8);
    wg_wait<0>();
    if (rel) mbar_arrive_cluster(rel_addr + (nb & 56));
    fence_acc<N>(acc);
  }
}

__device__ __forceinline__ void publish_stats(uint32_t sb, uint2* stat, int w, int lane, unsigned epoch) {
  const uint32_t row = sb + kSmX + (32 * w + lane) * 128;
  float s[4], q[4];
#pragma unroll
  for (int c = 0; c < 4; c++) s[c] = q[c] = 0.f;
  uint32_t nx[4];
  ldsm4(row + ((lane & 7) << 4), nx);
#pragma unroll 1
  for (int J = 1; J <= 16; J++) {
    const uint32_t r[4] = {nx[0], nx[1], nx[2], nx[3]};
    ldsm4(row + ((J >> 3) & 1) * kTileBytes + (((J ^ lane) & 7) << 4), nx);
#pragma unroll
    for (int c = 0; c < 4; c++) {
      const float lo = bf_lo(r[c]);
      s[c] += lo;
      q[c] = fmaf(lo, lo, q[c]);
      if (c & 1) yield_slot();
    }
#pragma unroll
    for (int c = 0; c < 4; c++) {
      const float hi = bf_hi(r[c]);
      s[c] += hi;
      q[c] = fmaf(hi, hi, q[c]);
      if (c & 1) yield_slot();
    }
  }
#pragma unroll
  for (int c = 0; c < 4; c++) {
    s[c] += shfl_xor(s[c], 1);
    q[c] += shfl_xor(q[c], 1);
    s[c] += shfl_xor(s[c], 2);
    q[c] += shfl_xor(q[c], 2);
  }
  const int t = lane & 3, g = lane >> 2;
  const float so = t == 0 ? s[0] : t == 1 ? s[1] : t == 2 ? s[2] : s[3];
  const float qo = t == 0 ? q[0] : t == 1 ? q[1] : t == 2 ? q[2] : q[3];
  asm volatile("st.relaxed.gpu.global.v2.u32 [%0], {%1, %2};" ::"l"(stat + 32 * w + 8 * t + g),
               "r"(tag_value(so, epoch)), "r"(tag_value(qo, epoch)) : "memory");
}

__device__ __forceinline__ void add_chunk(float (&a)[8], const uint4& v) {
  a[0] += bf_lo(v.x); a[1] += bf_hi(v.x);
  a[2] += bf_lo(v.y); a[3] += bf_hi(v.y);
  a[4] += bf_lo(v.z); a[5] += bf_hi(v.z);
  a[6] += bf_lo(v.w); a[7] += bf_hi(v.w);
}

__device__ __forceinline__ int helper_col(int id, int slab) {
  return slab < 6 ? (slab % 3) * kD + (slab / 3) * 512 + id * 128 : (slab - 6) * 512 + id * 128;
}
__device__ __forceinline__ void helper_cta(const CUtensorMap* map_q, const CUtensorMap* map_1, uint8_t* sm,
                                           uint32_t sb, int id, int warp) {
  constexpr int kRed = 6 * 32768, kBar = kRed + 2 * 4096;
  const int tid = threadIdx.x;
  if (warp == 8 && elect()) {
#pragma unroll
    for (int s = 0; s < 6; s++) {
      mbar_init(sb + kBar + s * 8, 1);
      mbar_init(sb + kBar + 64 + s * 8, 4);
    }
    fence_async_smem();
#pragma unroll
    for (int s = 0; s < 6; s++) {
      mbar_expect_tx(sb + kBar + s * 8, 32768);
      tma2d(sb + s * 32768, map_q, sb + kBar + s * 8, id * 128, s * 128);
    }
  }
  __syncthreads();
  if (warp == 8) {
    int slot = 0, ph = 0;
#pragma unroll 1
    for (int n = 6; n < 104; n++) {
      mbar_wait(sb + kBar + 64 + slot * 8, ph);
      if (elect()) {
        mbar_expect_tx(sb + kBar + slot * 8, 32768);
        tma2d(sb + slot * 32768, n < 48 ? map_q : map_1, sb + kBar + slot * 8, helper_col(id, n >> 3), (n & 7) * 128);
      }
      if (++slot == 6) slot = 0, ph ^= 1;
    }
  } else if (warp < 8) {
    if (tid == 0) *reinterpret_cast<unsigned*>(sm + kBar + 128) = atomicAdd(&g_ticket, 1u) / kGrid + 1;
    int slot = warp >> 2, ph = 0;
#pragma unroll 1
    for (int slab = 0; slab < 13; slab++) {
      float a[8];
#pragma unroll
      for (int e = 0; e < 8; e++) a[e] = 0.f;
#pragma unroll 1
      for (int box = 0; box < 4; box++) {
        mbar_wait_bounded(sb + kBar + slot * 8, ph);
        const uint4* p = reinterpret_cast<const uint4*>(sm + slot * 32768) + (tid & 127);
        uint4 v[16];
#pragma unroll
        for (int i = 0; i < 16; i++) v[i] = p[i * 128];
        __syncwarp();
        if (elect()) mbar_arrive(sb + kBar + 64 + slot * 8);
#pragma unroll
        for (int i = 0; i < 16; i++) add_chunk(a, v[i]);
        slot += 2;
        if (slot >= 6) slot -= 6, ph ^= 1;
      }
      float* red = reinterpret_cast<float*>(sm + kRed + (slab & 1) * 4096);
#pragma unroll
      for (int e = 0; e < 8; e++) a[e] += shfl_xor(a[e], 16);
      if ((tid & 16) == 0) {
        float4* d = reinterpret_cast<float4*>(red + warp * 128 + (tid & 15) * 8);
        d[0] = make_float4(a[0], a[1], a[2], a[3]);
        d[1] = make_float4(a[4], a[5], a[6], a[7]);
      }
      asm volatile("bar.sync 1, 256;" ::: "memory");
      if (warp < 4) {
        float t = 0.f;
#pragma unroll
        for (int q = 0; q < 8; q++) t += red[q * 128 + tid];
        st_relaxed(g_cs + (slab < 6 ? 0 : 3 * kD) + helper_col(id, slab) + tid,
                   tag_value(t, *reinterpret_cast<volatile unsigned*>(sm + kBar + 128)));
      }
    }
  }
}

constexpr float kGeluBeta = 0.3292034911525734f;
constexpr float kGeluK = 2.423681954311584f;

__device__ __forceinline__ void store_staged(uint8_t* dst, uint32_t stg) {
  fence_async_smem();
  __syncwarp();
  if (elect()) {
    bulk_store(dst, stg, 4096);
    bulk_commit();
  }
}

#define GY_MASK 5
#define GD 2
#define GF_MASK 3
#define GY(k) if ((GY_MASK >> k) & 1) yield_slot()
template <int J0, int J1>
__device__ __forceinline__ void fold_norm(float (&acc)[2][96], const float2 (&st)[4], const float4* vec) {
  float4 vn = vec[J0 * 4];
#pragma unroll
  for (int J = J0; J < J1; J++) {
    const float4 v = vn;
    if (J + 1 < J1) vn = vec[J * 4 + 4];
#pragma unroll
    for (int c = 0; c < 4; c++) {
      float& a0 = acc[c & 1][4 * J + (c & 2)];
      float& a1 = acc[c & 1][4 * J + (c & 2) + 1];
      a0 = fmaf(a0, st[c].x, fmaf(st[c].y, v.x, v.z));
      a1 = fmaf(a1, st[c].x, fmaf(st[c].y, v.y, v.w));
      asm volatile("" : "+f"(a0), "+f"(a1));
      if ((c & 1) && ((GF_MASK >> (c >> 1)) & 1)) yield_slot();
    }
  }
}

template <int CH, class Acquire>
__device__ __forceinline__ void gelu_chunk(const float (&acc)[2][96], uint32_t stg, int lane, uint8_t* prev,
                                           Acquire acquire) {
  uint32_t pk[8][4];
  float z[GD + 1][4];
  const uint32_t row = (stg + lane * 128) ^ ((lane & 7) << 4);
#define U(s, e) acc[(e) >> 1][4 * (CH * 8 + ((s) >> 1)) + 2 * ((s) & 1) + ((e) & 1)]
#pragma unroll
  for (int s = 0; s < 16 + GD; s++) {
    const int cur = s % (GD + 1), p1 = (s + GD) % (GD + 1), p2 = (s + 1) % (GD + 1), q = s - GD, jj = 2 * q - 24;
    const bool mid = s >= 1 && s < 17;
    if (mid) z[p1][0] = tanh_fast(z[p1][0]);
    if (s < 16) {
#pragma unroll
      for (int e = 0; e < 4; e++) {
        z[cur][e] = fmaf(U(s, e), U(s, e), kGeluK);
        asm volatile("" : "+f"(z[cur][e]));
      }
    }
    if (jj >= 0) stsm4(row ^ (jj << 4), pk[jj][0], pk[jj][1], pk[jj][2], pk[jj][3]);
    GY(0);
    if (mid) z[p1][1] = tanh_fast(z[p1][1]);
    if (q >= 0) {
      pk[q >> 1][2 * (q & 1)] = pack2(fmaf(U(q, 0), z[p2][0], U(q, 0)), fmaf(U(q, 1), z[p2][1], U(q, 1)));
      pk[q >> 1][2 * (q & 1) + 1] = pack2(fmaf(U(q, 2), z[p2][2], U(q, 2)), fmaf(U(q, 3), z[p2][3], U(q, 3)));
    }
    GY(1);
    if (mid) z[p1][2] = tanh_fast(z[p1][2]);
    if (s < 16) {
#pragma unroll
      for (int e = 0; e < 4; e++) {
        z[cur][e] *= U(s, e);
        asm volatile("" : "+f"(z[cur][e]));
      }
    }
    if (mid) z[p1][3] = tanh_fast(z[p1][3]);
    if (jj >= 0) stsm4(row ^ ((jj + 1) << 4), pk[jj + 1][0], pk[jj + 1][1], pk[jj + 1][2], pk[jj + 1][3]);
    GY(2);
    if (CH == 1 && s == 1) store_staged(prev, stg);
    if (q == 11) acquire();
  }
#undef U
}

__device__ __forceinline__ void scale_stats(float2 (&st)[4]) {
#pragma unroll
  for (int c = 0; c < 4; c++) {
    st[c].x *= kGeluBeta;
    st[c].y *= st[c].x;
  }
}

__device__ __forceinline__ void add_mean_term(float (&acc)[2][96], const float2 (&st)[4], uint8_t* sm, int tq,
                                              int lane) {
  const float2* cs = reinterpret_cast<const float2*>(sm + kSmCsQ) + tq * 96 + (lane & 3);
  float2 vn = cs[0];
#pragma unroll
  for (int J = 0; J < 24; J++) {
    const float2 v = vn;
    if (J < 23) vn = cs[J * 4 + 4];
#pragma unroll
    for (int c = 0; c < 4; c++) {
      acc[c & 1][4 * J + (c & 2)] = fmaf(st[c].y, v.x, acc[c & 1][4 * J + (c & 2)]);
      acc[c & 1][4 * J + (c & 2) + 1] = fmaf(st[c].y, v.y, acc[c & 1][4 * J + (c & 2) + 1]);
    }
    yield_slot();
  }
}

#define TWO_PART 0
#define RESUME_LATE 0
#define HALO_AT 2
__device__ __forceinline__ void epilogue_attn(const float (&acc)[2][96], const float2 (&st)[4], uint8_t* sm,
                                              uint32_t sb, int layer, int tq, int b, int j, unsigned epoch, int tile,
                                              int wg, int w, int lane) {
  const int t = lane & 3, g = lane >> 2;
  const int hp = j + 8 * tq, att = 2 * layer + tq;
  uint32_t q[4][8], k[5][8], vt[5][8];
#define SCALED(c, J) pack2(acc[(c) & 1][4 * (J) + ((c) & 2)] * st[c].x, acc[(c) & 1][4 * (J) + ((c) & 2) + 1] * st[c].x)
#pragma unroll
  for (int J = 0; J < 8; J++) vt[4][J] = transpose8(SCALED(3, 16 + J));
#pragma unroll
  for (int J = 0; J < 8; J++) k[4][J] = SCALED(3, 8 + J);
  if (w < 3) {
    uint2* hs = reinterpret_cast<uint2*>(sm + kSmHalo + w * 2048) + lane;
#pragma unroll
    for (int i = 0; i < 4; i++) {
      hs[i * 32] = make_uint2(k[4][2 * i], k[4][2 * i + 1]);
      hs[128 + i * 32] = make_uint2(vt[4][2 * i], vt[4][2 * i + 1]);
    }
  } else if ((b & 7) != 7) {
    uint4* gh = g_halo + ((layer * 16 + b) * 16 + hp) * 256 + lane;
#pragma unroll
    for (int i = 0; i < 4; i++) {
      st_packet(gh + i * 32, k[4][2 * i], k[4][2 * i + 1], epoch);
      st_packet(gh + 128 + i * 32, vt[4][2 * i], vt[4][2 * i + 1], epoch);
    }
  }
#pragma unroll
  for (int c = 0; c < 3; c++)
#pragma unroll
    for (int J = 0; J < 8; J++) {
      k[c + 1][J] = SCALED(c, 8 + J);
      vt[c + 1][J] = transpose8(SCALED(c, 16 + J));
      yield_slot();
    }
  const bool first = w == 0 && (b & 7) == 0;
  const uint4* gh = g_halo + ((layer * 16 + b - 1) * 16 + hp) * 256 + lane;
  uint32_t tag[8];
#define LOAD_HALO()                                                                                    \
  _Pragma("unroll") for (int i = 0; i < 4; i++) {                                                      \
    ld_packet(gh + i * 32, k[0][2 * i], k[0][2 * i + 1], tag[i]);                                      \
    ld_packet(gh + 128 + i * 32, vt[0][2 * i], vt[0][2 * i + 1], tag[4 + i]);                          \
  }
#define AWAIT_HALO()                                                                                   \
  for (unsigned spins = 0;; spins++) {                                                                 \
    const unsigned d0 = (tag[0] ^ epoch) | (tag[1] ^ epoch) | (tag[2] ^ epoch) | (tag[3] ^ epoch);     \
    const unsigned d1 = (tag[4] ^ epoch) | (tag[5] ^ epoch) | (tag[6] ^ epoch) | (tag[7] ^ epoch);     \
    if (__all_sync(0xffffffffu, (d0 | d1) == 0)) break;                                                \
    if (spins > kSpinLimit) __trap();                                                                  \
    LOAD_HALO();                                                                                       \
  }
#pragma unroll
  for (int c = 0; c <= 4; c++) {
    if (c == HALO_AT) {
      if (w == 0 && !first) {
        LOAD_HALO();
      } else {
#pragma unroll
        for (int i = 0; i < 8; i++) k[0][i] = vt[0][i] = tag[i] = 0u;
      }
    }
#pragma unroll
    for (int J = 0; J < 8 && c < 4; J++) {
      q[c & 3][J] = SCALED(c & 3, J);
      if (J & 1) yield_slot();
    }
  }
#undef SCALED
  TRACE_AT(tile, 8);
  wg_bar(wg);
  if (w > 0) {
    const uint2* hs = reinterpret_cast<const uint2*>(sm + kSmHalo + (w - 1) * 2048) + lane;
#pragma unroll
    for (int i = 0; i < 4; i++) {
      const uint2 a = hs[i * 32], c = hs[128 + i * 32];
      k[0][2 * i] = a.x; k[0][2 * i + 1] = a.y;
      vt[0][2 * i] = c.x; vt[0][2 * i + 1] = c.y;
    }
  } else if (!first && tq == 0) {
    AWAIT_HALO();
  }
  constexpr float kScale = 0.17677669529663687f * 1.4426950408889634f;
  const bool own0 = 2 * t <= g, own1 = 2 * t + 1 <= g;
  const uint32_t own_mask = (own0 ? 0xffffu : 0u) | (own1 ? 0xffff0000u : 0u);
  const uint32_t stg = sb + kSmStg + w * 4096;
  const uint32_t orow = stg + (lane & 7) * 128, ochunk = (lane >> 3) ^ (lane & 7);
  TRACE_AT(tile, 9);
  mbar_wait(sb + kBarPause + att * 8, 0);
  TRACE_AT(tile, 10);

  float s[2][6][4], o[2][4][2][4];
  auto scores = [&](int hd, int m) {
    const int ca = 2 * (m / 3), kg = ca + m % 3;
#pragma unroll
    for (int e = 0; e < 4; e++) s[hd][m][e] = 0.f;
#pragma unroll
    for (int J = 4 * hd; J < 4 * hd + 4; J += 2)
      mma16816(s[hd][m], q[ca][J], q[ca + 1][J], q[ca][J + 1], q[ca + 1][J + 1], k[kg][J], k[kg][J + 1]);
  };
  auto attend = [&](int c0, int c1) {
    float v0[2][4], v1[2][4], m[2][4];
#define UNITS _Pragma("unroll") for (int hd = 0; hd < 2; hd++) _Pragma("unroll") for (int c = c0; c < c1; c++)
    UNITS {
      const int mp = 3 * (c >> 1) + (c & 1), r = 2 * (c & 1);
      float p0 = s[hd][mp][r], p1 = s[hd][mp][r + 1];
      if (c == 0 && first) p0 = p1 = -INFINITY;
      v0[hd][c] = own0 ? s[hd][mp + 1][r] : p0;
      v1[hd][c] = own1 ? s[hd][mp + 1][r + 1] : p1;
      m[hd][c] = fmaxf(v0[hd][c], v1[hd][c]);
    }
    UNITS m[hd][c] = fmaxf(m[hd][c], shfl_xor(m[hd][c], 1));
    UNITS m[hd][c] = fmaxf(m[hd][c], shfl_xor(m[hd][c], 2));
    UNITS {
      const float nm = -m[hd][c] * kScale;
      v0[hd][c] = ex2(fmaf(v0[hd][c], kScale, nm));
      v1[hd][c] = ex2(fmaf(v1[hd][c], kScale, nm));
      m[hd][c] = v0[hd][c] + v1[hd][c];
    }
    UNITS m[hd][c] += shfl_xor(m[hd][c], 1);
    UNITS m[hd][c] += shfl_xor(m[hd][c], 2);
    UNITS {
      const float inv = rcp(m[hd][c]);
      const uint32_t p = pack2(v0[hd][c] * inv, v1[hd][c] * inv);
#pragma unroll
      for (int ds = 0; ds < 2; ds++) {
        const int J = 4 * hd + 2 * ds;
#pragma unroll
        for (int e = 0; e < 4; e++) o[hd][c][ds][e] = 0.f;
        if (c & 1) {
          mma16816(o[hd][c][ds], vt[c][J], vt[c][J + 1], vt[c + 1][J], vt[c + 1][J + 1], p & ~own_mask, p & own_mask);
        } else {
          mma1688(o[hd][c][ds], vt[c + 1][J], vt[c + 1][J + 1], p & own_mask);
          mma1688(o[hd][c][ds], vt[c][J], vt[c][J + 1], p & ~own_mask);
        }
      }
    }
  };
  auto stage = [&](int c0, int c1) {
    UNITS stsm4_t(orow + c * 1024 + ((ochunk ^ (4 * hd)) << 4), pack2(o[hd][c][0][0], o[hd][c][0][1]),
                  pack2(o[hd][c][0][2], o[hd][c][0][3]), pack2(o[hd][c][1][0], o[hd][c][1][1]),
                  pack2(o[hd][c][1][2], o[hd][c][1][3]));
#undef UNITS
  };
  if (w == 0 && !first) AWAIT_HALO();
#pragma unroll
  for (int hd = 0; hd < 2; hd++)
#pragma unroll
    for (int m = 0; m < 6; m++) scores(hd, m);
  attend(0, 4);
  yield_slot();
  if (tq == 0 && elect()) mbar_arrive(sb + kBarResume + att * 8);
  TRACE_AT(tile, 11);
  stage(0, 4);
#undef AWAIT_HALO
#undef LOAD_HALO
  fence_async_smem();
  __syncwarp();
  TRACE_AT(tile, 12);
  if (elect()) {
    bulk_store(g_o + (b * 16 + hp) * kTileBytes + w * 4096, stg, 4096);
    bulk_commit();
    if (tq == 1 && !RESUME_LATE) mbar_arrive(sb + kBarResume + att * 8);
    bulk_wait();
    if (tq == 1 && RESUME_LATE) mbar_arrive(sb + kBarResume + att * 8);
    TRACE_AT(tile, 13);
    mbar_arrive(sb + kBarEpi + tile * 8);
  }
  __syncwarp();
}

__device__ __forceinline__ void gather_stats(uint8_t* sm, const uint2* stat, int r, unsigned epoch) {
  uint2 a[8];
  unsigned spins = 0;
  while (true) {
    unsigned diff = 0;
#pragma unroll
    for (int i = 0; i < 8; i++) {
      a[i] = ld_relaxed2(stat + i * 128 + r);
      diff |= (a[i].x ^ epoch) | (a[i].y ^ epoch);
    }
    if (__all_sync(0xffffffffu, (diff & 7u) == 0)) break;
    if (++spins > kSpinLimit) __trap();
    __nanosleep(200);
  }
  float s = 0.f, q = 0.f;
#pragma unroll
  for (int i = 0; i < 8; i++) {
    s += untag_value(a[i].x);
    q += untag_value(a[i].y);
  }
  const float mean = s * (1.f / 1024.f);
  const float var = fmaxf(fmaf(-mean, mean, q * (1.f / 1024.f)), 0.f);
  reinterpret_cast<float2*>(sm + kSmStat)[r] = make_float2(rsqrtf(var + 1e-5f), -mean);
}

__device__ __forceinline__ void gather_colsums(uint8_t* sm, int part, int j, int lane, unsigned epoch) {
#pragma unroll 1
  for (int blk = part < 4 ? 0 : 2 * part - 5; blk < (part < 4 ? 3 : 2 * part - 3); blk++) {
    const int col = part < 2 ? blk * kD + (j + 8 * part) * 64
                             : 3 * kD + 64 * (blk + (blk < 3 ? 3 * j : blk < 5 ? 21 + 2 * j : 35 + 2 * j));
    uint2 v;
    unsigned spins = 0;
    while (true) {
      v = ld_relaxed2(reinterpret_cast<const uint2*>(g_cs + col) + lane);
      if (__all_sync(0xffffffffu, (((v.x ^ epoch) | (v.y ^ epoch)) & 7u) == 0)) break;
      if (++spins > kSpinLimit) __trap();
      __nanosleep(100);
    }
    uint8_t* dst = part < 2 ? sm + kSmCsQ + (part * 96 + blk * 32 + lane) * 8 : sm + kSmV1 + (blk * 32 + lane) * 16;
    *reinterpret_cast<float2*>(dst) = make_float2(untag_value(v.x), untag_value(v.y));
  }
}

#define FINE 3
#define LATE_REL2 1
#define XT_LATE 1
#define STAGE_YIELD 1
#define PAUSE_QKV2 7
#define PAUSE_WO 3

__global__ void __cluster_dims__(2, 1, 1) __launch_bounds__(384, 1)
fused_layers_kernel(const __grid_constant__ CUtensorMap map_x, const __grid_constant__ CUtensorMap map_out,
                    const __grid_constant__ CUtensorMap map_qkv, const __grid_constant__ CUtensorMap map_wo,
                    const __grid_constant__ CUtensorMap map_w1a, const __grid_constant__ CUtensorMap map_w1b,
                    const __grid_constant__ CUtensorMap map_w2, const __grid_constant__ CUtensorMap map_csq,
                    const __grid_constant__ CUtensorMap map_cs1, const __grid_constant__ Params prm) {
  extern __shared__ __align__(1024) uint8_t sm[];
  if (threadIdx.x < 128 && blockIdx.x < kCtas) TRACE_AT(15, 1);
  const uint32_t sb = __shfl_sync(0xffffffffu, smem_u32(sm), 0);
  const int warp = __shfl_sync(0xffffffffu, threadIdx.x >> 5, 0), lane = threadIdx.x & 31;
  const int cta = blockIdx.x, rank = cta & 1, cl = cta >> 1;
  const int grp = cl < 4 ? 0 : cl < 36 ? (cl - 4) & 7 : 1 + (cl - 36) % 7;
  const int j = cl < 4 ? 4 + cl : cl < 36 ? (cl - 4) >> 3 : 4 + (cl - 36) / 7;
  const int b = 2 * grp + rank;
  const int xcol = (b >> 3) * kD, xrow = (b & 7) * 128;

  if (cta >= kCtas) {
    helper_cta(&map_csq, &map_cs1, sm, sb, cta - kCtas, warp);
    return;
  }
  if (warp >= 8 && elect()) {
    if (warp == 9) {
#pragma unroll
      for (int s = 0; s < 8; s++) mbar_init(sb + kBarFull + s * 8, 1);
      mbar_init(sb + kBarInit, 1);
      fence_async_smem();
#pragma unroll
      for (int s = 0; s < 4; s++) {
        const uint32_t full = sb + kBarFull + s * 8, dst = sb + kSmRing + s * 40960;
        mbar_expect_tx(full, 40960);
        tma2d(dst, &map_x, full, xcol + (s & 1) * 64, xrow);
        tma3d(dst + kTileBytes, &map_qkv, full, (j + 4 * (s & 2)) * 64, (s & 1) * 64, 0);
        tma3d(dst + kTileBytes + 12288, &map_qkv, full, (j + 4 * (s & 2)) * 64, (s & 1) * 64 + 32, 0);
      }
      if (!XT_LATE) {
        mbar_expect_tx(sb + kBarInit, 32768);
        tma2d(sb + kSmX, &map_x, sb + kBarInit, xcol + j * 128, xrow);
        tma2d(sb + kSmX + kTileBytes, &map_x, sb + kBarInit, xcol + j * 128 + 64, xrow);
      }
    } else if (warp == 8) {
      if (sb & 1023) __trap();
#pragma unroll
      for (int o = kBarTurn; o < kBarPause; o += 8) mbar_init(sb + o, 1);
    } else if (warp == 10) {
#pragma unroll
      for (int o = kBarEpi; o < kSmEpoch; o += 8) mbar_init(sb + o, 4);
    } else {
#pragma unroll
      for (int o = kBarPause; o < kBarEpi; o += 8)
        if (o != kBarInit) mbar_init(sb + o, o < kBarEmpty ? 1 : 2);
    }
    asm volatile("fence.mbarrier_init.release.cluster;" ::: "memory");
  }
  __syncwarp();
  asm volatile("barrier.cluster.arrive.relaxed.aligned;" ::: "memory");

  if (warp >= 8) {
    asm volatile("setmaxnreg.dec.sync.aligned.u32 40;");
    if (warp < 10) {
      asm volatile("barrier.cluster.wait.aligned;" ::: "memory");
      uint32_t nb = 32, off = 0, kb = 0;
#define RING_STEP(WAIT, ISSUE)                                            \
  do {                                                                    \
    const uint32_t mb = nb - depth, full = sb + kBarFull + (nb & 56);     \
    if (kb == skip) kb += inc;                                            \
    mbar_wait(sb + kBarEmpty + (mb & 56), mb >> 6);                       \
    WAIT;                                                                 \
    if (elect()) { ISSUE; }                                               \
    TRACE_ISSUE(9 - warp, nb);                                            \
    kb += inc;                                                            \
    off = off == wrap ? 0 : off + step;                                   \
    nb += 8;                                                              \
  } while (nb != nend)
#pragma unroll 1
      for (int sg = 0; sg < kSegs; sg++) {
        const uint32_t e = prm.seg[sg];
        const int ty = e & 7, mode = (e >> 15) & 3, reset = (e >> 24) & 3;
        const uint32_t nend = nb + (e & 0x1f8);
        const uint32_t step = (e >> 17) & 1 ? 40960 : 32768, wrap = 163840 - step;
        const uint32_t depth = (e >> 18) & 1 ? 40 : 32;
        if (reset) off = reset == 1 ? 0 : reset == 2 ? 40960 : 131072;
        const uint32_t own = ty == 2 ? 8 + j : 2 * j;
        if (mode != kModeContinue) kb = mode == kModeHead ? own : (e >> 9) & 63;
        const uint32_t inc = mode >= kModeSkip && ty != 2 ? 2 : 1, skip = mode >= kModeSkip ? own + (kb & 1) : 255;
        if (warp == 8) {
          const CUtensorMap* map = ty < 2 ? &map_qkv : ty == 2 ? &map_wo : ty == 3 ? &map_w1a : ty < 6 ? &map_w1b : &map_w2;
          const int c0 = ty < 2 ? (j + 8 * ty) * 64 : 0;
          const int c2 = ty < 2 ? 0 : ty == 3 ? 3 * j : ty == 4 ? 24 + 2 * j : ty == 5 ? 40 + 2 * j : 2 * j;
          const uint32_t half = (ty < 2 || ty == 3) ? 12288 : 8192;
          const uint32_t bytes = 2 * half + (mode == kModeHead ? 0 : kTileBytes);
          const uint32_t dst = sb + kSmRing + kTileBytes + rank * half;
#pragma unroll 1
          RING_STEP(, mbar_expect_tx(full, bytes); tma3d_mc(dst + off, map, full, c0, kb * 64 + rank * 32, c2));
        } else if (mode == kModeHead) {
          off += ((nend - nb) >> 3) * step;
          nb = nend;
          if (off >= 163840) off -= 163840;
        } else if (sg < 2) {
#pragma unroll 1
          RING_STEP(, tma2d(sb + kSmRing + off, &map_x, full, xcol + kb * 64, xrow));
        } else {
          const uint8_t* src = ty == 6 ? g_h + b * 56 * kTileBytes : (ty == 2 ? g_o : g_x) + b * 16 * kTileBytes;
          const int dep = (e >> 19) & 31;
          if (dep < 28) mbar_wait(sb + kBarReady + dep * 8, 0);
          if ((dep & 30) == 28) {
#pragma unroll 1
            RING_STEP(mbar_wait(sb + kBarSrc + ((kb << (4 - inc)) & 56), dep),
                      bulk_load(sb + kSmRing + off, src + kb * kTileBytes, kTileBytes, full));
          } else {
#pragma unroll 1
            RING_STEP(, bulk_load(sb + kSmRing + off, src + kb * kTileBytes, kTileBytes, full));
          }
        }
      }
#undef RING_STEP
    } else if (warp == 10) {
      unsigned epoch = 0;
      if (lane == 0) epoch = atomicAdd(&g_ticket, 1u) / kGrid + 1;
      epoch = __shfl_sync(0xffffffffu, epoch, 0);
      *reinterpret_cast<unsigned*>(sm + kSmEpoch) = epoch;
      asm volatile("barrier.cluster.wait.aligned;" ::: "memory");
      if (elect()) mbar_arrive(sb + kBarEpoch);
#pragma unroll 1
      for (int i = 0; i < kTiles - 1; i++) {
        const bool xt = i == 2 || i == 6 || i == 9;
        const unsigned* line = g_flag + (i * 16 + b) * 32;
        mbar_wait(sb + (xt ? kBarX + (i >> 2) * 16 : kBarEpi + i * 8), 0);
        if ((xt && (FINE & 1)) || ((i == 1 || i == 8) && (FINE & 2))) {
          unsigned todo = 0xff, spins = 0;
          do {
            const unsigned now = __ballot_sync(0xffffffffu, ld_relaxed(line + (lane & 7)) == epoch) & todo;
            if (now) {
              asm volatile("fence.acquire.gpu;\nfence.proxy.async.global;" ::: "memory");
              if ((now >> lane) & 1) mbar_arrive(sb + kBarSrc + lane * 8);
              todo ^= now;
            }
            if (++spins > kSpinLimit) __trap();
          } while (todo);
        } else {
          wait_flags(line + (lane & 7), epoch);
          if (elect()) mbar_arrive(sb + kBarReady + i * 8);
        }
        if (xt) {
          wait_flags(line + 8 + (lane & 7), epoch);
          if (elect()) mbar_arrive(sb + kBarReady + (14 + (i >> 2)) * 8);
        }
      }
    } else {
      asm volatile("barrier.cluster.wait.aligned;" ::: "memory");
      if (XT_LATE) {
        mbar_wait_bounded(sb + kBarFull + 8 * (XT_LATE - 1), 0);
        if (elect()) {
          mbar_expect_tx(sb + kBarInit, 32768);
          tma2d(sb + kSmX, &map_x, sb + kBarInit, xcol + j * 128, xrow);
          tma2d(sb + kSmX + kTileBytes, &map_x, sb + kBarInit, xcol + j * 128 + 64, xrow);
        }
      }
      {
        uint32_t v[7];
#pragma unroll
        for (int q = 0; q < 7; q++)
          v[q] = reinterpret_cast<const uint32_t*>(prm.b1)[32 * (q + (q < 3 ? 3 * j : q < 5 ? 21 + 2 * j : 35 + 2 * j)) + lane];
        const uint2 u = reinterpret_cast<const uint2*>(prm.b2)[32 * j + lane];
#pragma unroll
        for (int q = 0; q < 7; q++)
          *reinterpret_cast<float2*>(sm + kSmV1 + (q * 32 + lane) * 16 + 8) = make_float2(kGeluBeta * bf_lo(v[q]), kGeluBeta * bf_hi(v[q]));
        reinterpret_cast<float4*>(sm + kSmB2)[lane] = make_float4(
            2.f * kGeluBeta * bf_lo(u.x), 2.f * kGeluBeta * bf_hi(u.x), 2.f * kGeluBeta * bf_lo(u.y), 2.f * kGeluBeta * bf_hi(u.y));
      }
      mbar_wait_bounded(sb + kBarEpoch, 0);
      const unsigned epoch = *reinterpret_cast<volatile unsigned*>(sm + kSmEpoch);
#pragma unroll 1
      for (int i = 0; i < kTiles - 1; i++) {
#pragma unroll 1
        for (int part = i == 4 ? 5 : i; part < (i < 2 ? i + 1 : i == 3 || i == 4 ? i + 2 : 0); part++) {
          gather_colsums(sm, part, j, lane, epoch);
          __syncwarp();
          if (elect()) mbar_arrive(sb + kBarCs + part * 8);
        }
        const bool xt = i == 2 || i == 6 || i == 9;
#pragma unroll 1
        for (int h = 0; h < (xt ? 2 : 1); h++) {
          mbar_wait_bounded(sb + (xt ? kBarX + (i >> 2) * 16 + 8 * h : kBarEpi + i * 8), 0);
          const int ty = i >= 7 ? i - 7 : i;
          if (ty >= 2 && elect()) {
            uint8_t* dst = xt ? g_x + (b * 16 + 2 * j + h) * kTileBytes
                              : g_h + (b * 56 + 1 + (ty == 3 ? 3 * j : 16 * ty - 40 + 2 * j)) * kTileBytes;
            bulk_store(dst, sb + (xt ? kSmX + h * kTileBytes : kSmStg), kTileBytes);
            bulk_commit();
            bulk_wait();
            if (!xt) mbar_arrive(sb + kBarFree + i * 8);
          }
          if (LATE_REL2 && h == 1) mbar_wait_bounded(sb + kBarFull + 32, i == 2 ? 6 : i == 6 ? 19 : 25);
          __syncwarp();
          if (elect()) st_release(&g_flag[(i * 16 + b) * 32 + h * 8 + j], epoch);
          __syncwarp();
        }
      }
#pragma unroll 1
      for (int h = 0; h < 2; h++) {
        mbar_wait_bounded(sb + kBarX + 48 + 8 * h, 0);
        if (elect()) {
          tma2d_store(&map_out, sb + kSmX + h * kTileBytes, xcol + j * 128 + h * 64, xrow);
          bulk_commit();
          if (h == 1) bulk_wait_read();
        }
      }
    }
    __syncwarp();
    asm volatile("barrier.cluster.arrive.relaxed.aligned;\nbarrier.cluster.wait.aligned;" ::: "memory");
  } else {
    asm volatile("setmaxnreg.inc.sync.aligned.u32 232;");
    asm volatile("barrier.cluster.wait.aligned;" ::: "memory");
    const int wg = warp >> 2, w = warp & 3;
    const bool rel = (threadIdx.x & 95) == 0;
    const uint32_t rel_addr = mapa(sb + kBarEmpty, w & 1);
    if (wg == 1) TRACE_AT(15, 0);
#define EPOCH (*reinterpret_cast<volatile unsigned*>(sm + kSmEpoch))

#pragma unroll 1
    for (int i = wg; i < kTiles; i += 2) {
      const int layer = i >= 7, ty = i - 7 * layer;
      TRACE_AT(i, 15);
      float acc[2][96];
      if (ty == 2 || ty == 6) {
        const int lane = lane_id();
        const uint32_t xa = sb + kSmX + ((lane >> 4) * 8 + (lane & 7)) * 128 + (((2 * w + ((lane >> 3) & 1)) ^ (lane & 7)) << 4);
        const float up = ty == 6 ? 2.f * kGeluBeta : 1.f, dn = ty == 6 ? 0.5f / kGeluBeta : 1.f;
#pragma unroll
        for (int h = 0; h < 2; h++) {
          const float* b2 = reinterpret_cast<const float*>(sm + kSmB2) + 64 * h + 16 * w + (lane >> 2);
          const float bias[2] = {ty == 6 ? b2[0] : 0.f, ty == 6 ? b2[8] : 0.f};
#pragma unroll
          for (int p = 0; p < 8; p++) {
            uint32_t r[4];
            ldsm4_t(xa + h * kTileBytes + p * 2048, r);
#pragma unroll
            for (int m = 0; m < 4; m++) {
              acc[h][8 * p + 2 * m] = fmaf(bf_lo(r[m]), up, bias[m & 1]);
              acc[h][8 * p + 2 * m + 1] = fmaf(bf_hi(r[m]), up, bias[m & 1]);
              asm volatile("" : "+f"(acc[h][8 * p + 2 * m]), "+f"(acc[h][8 * p + 2 * m + 1]));
              if (m & 1) yield_slot();
            }
          }
        }
        auto stage = [&](int qt) {
          const int h = qt >> 1;
#pragma unroll
          for (int p = 4 * (qt & 1); p < 4 * (qt & 1) + 4; p++) {
            const float* a = &acc[h][8 * p];
            stsm4_t(xa + h * kTileBytes + p * 2048, pack2(a[0] * dn, a[1] * dn), pack2(a[2] * dn, a[3] * dn),
                    pack2(a[4] * dn, a[5] * dn), pack2(a[6] * dn, a[7] * dn));
            if (STAGE_YIELD || (p & 3) == 3) yield_slot();
          }
          if (qt & 1) {
            fence_async_smem();
            __syncwarp();
            if (elect()) mbar_arrive(sb + kBarX + (i >> 2) * 16 + 8 * h);
            TRACE_AT(i, 8 + h);
          }
        };
        mainloop<128, true, false>(acc, sb, i, layer * 152 + ty * 16, ty == 6 ? 4 : 0, ty == 6 ? 56 : 16,
                            ty == 2 ? PAUSE_WO : -1, 2 * layer + 1, rel_addr, rel, ty == 2 ? 8 : -1, stage);
        TRACE_AT(i, 2);
        stage(2);
        stage(3);
      } else {
        const int xver = 2 * layer + (ty >= 3);
        const uint32_t stg = sb + kSmStg + w * 4096;
        const float4* vec = reinterpret_cast<const float4*>(sm + kSmV1) + (ty == 3 ? 0 : 64 * ty - 160);
        int lane;
        uint8_t* hdst = g_h + (b * 56 + (ty == 3 ? 3 * j : 16 * ty - 40 + 2 * j)) * kTileBytes + w * 4096;
        float2 st[4];
        unsigned epoch;
        auto pre = [&] {
          lane = lane_id();
          if (ty < 4) mbar_wait(sb + (ty == 1 ? kBarEpi + (i - 1) * 8 : kBarStat + xver * 8), 0);
#pragma unroll
          for (int c = 0; c < 4; c++) st[c] = reinterpret_cast<const float2*>(sm + kSmStat)[32 * w + 8 * c + (lane >> 2)];
          epoch = EPOCH;
        };
        auto team_stats = [&] {
          uint2* stat = g_stat + (xver * 16 + b) * 1024;
          lane = lane_id();
          publish_stats(sb, stat + j * 128, w, lane, EPOCH);
          gather_stats(sm, stat, 32 * w + lane, EPOCH);
          __syncwarp();
          if (elect()) mbar_arrive(sb + kBarStat + xver * 8);
          TRACE_AT(i, 14);
        };
        if (ty < 4) {
          head_blocks<192>(acc, sb, layer * 152 + (ty < 2 ? 2 * ty : 48), ty < 2 ? 2 * ty : 1, xver, rel_addr, rel);
          if (ty == 1) {
            if (i == 1) {
              mbar_wait(sb + kBarEpoch, 0);
              mbar_wait(sb + kBarInit, 0);
            }
            team_stats();
            if (i == 8) {
#pragma unroll
              for (int c = 0; c < 4; c++) st[c] = reinterpret_cast<const float2*>(sm + kSmStat)[32 * w + 8 * c + (lane >> 2)];
              add_mean_term(acc, st, sm, 1, lane);
            }
          }
          mainloop<192, false, false>(acc, sb, i, layer * 152 + (ty < 2 ? 4 + 14 * ty : 52), ty < 2 ? 2 * ty : 1, 14,
                                      ty == 1 ? PAUSE_QKV2 : -1, xver, rel_addr, rel, 0, pre);
          TRACE_AT(i, 2);
          if (layer == 0) mbar_wait(sb + kBarCs + ty * 8, 0);
          if (ty < 2) {
            if (i != 8) add_mean_term(acc, st, sm, ty, lane);
            epilogue_attn(acc, st, sm, sb, layer, ty, b, j, epoch, i, wg, w, lane);
            TRACE_AT(i, 3);
            continue;
          }
          scale_stats(st);
          fold_norm<16, 24>(acc, st, vec + (lane & 3));
          TRACE_AT(i, 11);
          gelu_chunk<2>(acc, stg, lane, nullptr, [] {});
          TRACE_AT(i, 12);
          fold_norm<0, 2>(acc, st, vec + (lane & 3));
          store_staged(hdst + 2 * kTileBytes, stg);
          fold_norm<2, 16>(acc, st, vec + (lane & 3));
        } else {
          if (ty == 4) {
            head_blocks<128>(acc, sb, layer * 152 + 50, 3, xver, rel_addr, rel);
            team_stats();
            mainloop<128, false, false>(acc, sb, i, layer * 152 + 66, 4, 14, -1, 0, rel_addr, rel, 0, pre);
          } else {
            mainloop<128, false, true>(acc, sb, i, layer * 152 + 80, 3, 16, -1, 0, rel_addr, rel, 0, pre);
          }
          TRACE_AT(i, 2);
          if (layer == 0) mbar_wait(sb + kBarCs + ty * 8, 0);
          scale_stats(st);
          fold_norm<0, 16>(acc, st, vec + (lane & 3));
        }
        auto own_store_done = [] {
          if (elect()) bulk_wait();
          __syncwarp();
        };
        TRACE_AT(i, 8);
        gelu_chunk<0>(acc, stg, lane, nullptr, [&] {
          if (ty == 3) own_store_done();
          else mbar_wait(sb + kBarFree + (i - 1) * 8, 0);
        });
        TRACE_AT(i, 9);
        gelu_chunk<1>(acc, stg, lane, hdst, own_store_done);
        TRACE_AT(i, 10);
        fence_async_smem();
        __syncwarp();
        if (elect()) mbar_arrive(sb + kBarEpi + i * 8);
      }
      TRACE_AT(i, 3);
    }
#undef EPOCH
    asm volatile("barrier.cluster.arrive.relaxed.aligned;\nbarrier.cluster.wait.aligned;" ::: "memory");
    if (wg == 1) TRACE_AT(15, 2);
  }
}

void build_segments(uint32_t* seg) {
  int n = 0, fine = 0;
  auto per_source = [&](int kind, int dep) { return (FINE & kind) ? 28 + (fine++ & 1) : dep; };
  auto add = [&](int ty, int cnt, int kb0, int mode, int wide, int depth5, int dep, int reset) {
    seg[n++] = ty | cnt << 3 | kb0 << 9 | mode << 15 | wide << 17 | depth5 << 18 | dep << 19 | reset << 24;
  };
  for (int l = 0; l < 2; l++) {
    const int t = 7 * l;
    if (l == 0) {
      add(0, 14, 2, kModePlain, 1, 0, 31, 1);
      add(1, 14, 2, kModePlain, 1, 0, 31, 0);
    } else {
      add(0, 2, 0, kModeHead, 1, 0, 31, 1);
      add(1, 2, 0, kModeHead, 1, 0, 31, 0);
      add(0, 7, 0, kModeSkip, 1, 0, per_source(1, 6), 0);
      add(0, 7, 1, kModeSkip, 1, 0, 15, 0);
      add(1, 7, 0, kModeSkip, 1, 0, 31, 0);
      add(1, 7, 1, kModeSkip, 1, 0, 31, 0);
    }
    add(2, 4, 0, kModePlain, 0, 0, t, 1);
    add(2, 4, 4, kModePlain, 0, 1, 31, 0);
    add(2, 1, 0, kModeHead, 0, 1, 31, 0);
    add(2, 7, 8, kModeSkip, 0, 1, per_source(2, t + 1), 0);
    add(3, 2, 0, kModeHead, 1, 0, 31, 2);
    add(4, 2, 0, kModeHead, 1, 0, 31, 0);
    add(3, 7, 0, kModeSkip, 1, 0, per_source(1, t + 2), 0);
    add(3, 7, 1, kModeSkip, 1, 0, 14 + 2 * l, 0);
    add(4, 4, 0, kModeSkip, 0, 0, 31, 3);
    add(4, 3, 0, kModeContinue, 0, 1, 31, 0);
    add(4, 7, 1, kModeSkip, 0, 1, 31, 0);
    add(5, 16, 0, kModePlain, 0, 1, 31, 0);
    add(6, 24, 0, kModePlain, 0, 1, t + 3, 0);
    add(6, 16, 24, kModePlain, 0, 1, t + 4, 0);
    add(6, 16, 40, kModePlain, 0, 1, t + 5, 0);
  }
}

typedef CUresult (*EncodeTiledFn)(CUtensorMap*, CUtensorMapDataType, cuuint32_t, void*, const cuuint64_t*,
                                  const cuuint64_t*, const cuuint32_t*, const cuuint32_t*, CUtensorMapInterleave,
                                  CUtensorMapSwizzle, CUtensorMapL2promotion, CUtensorMapFloatOOBfill);

CUtensorMap make_map(EncodeTiledFn enc, const void* p, int rank, const cuuint64_t* dims, const cuuint64_t* strides,
                     const cuuint32_t* box, CUtensorMapSwizzle swizzle = CU_TENSOR_MAP_SWIZZLE_128B) {
  CUtensorMap m;
  const cuuint32_t es[5] = {1, 1, 1, 1, 1};
  enc(&m, CU_TENSOR_MAP_DATA_TYPE_BFLOAT16, rank, const_cast<void*>(p), dims, strides, box, es,
      CU_TENSOR_MAP_INTERLEAVE_NONE, swizzle, CU_TENSOR_MAP_L2_PROMOTION_L2_128B,
      CU_TENSOR_MAP_FLOAT_OOB_FILL_NONE);
  return m;
}

CUtensorMap weight_map(EncodeTiledFn enc, const void* p, int k, int n, int blocks) {
  const cuuint64_t dims[3] = {64, (cuuint64_t)k, (cuuint64_t)n / 64};
  const cuuint64_t strides[2] = {(cuuint64_t)n * 2, 128};
  const cuuint32_t box[3] = {64, 32, (cuuint32_t)blocks};
  return make_map(enc, p, 3, dims, strides, box);
}

CUtensorMap slab_map(EncodeTiledFn enc, const void* p, int n) {
  const cuuint64_t dims[2] = {(cuuint64_t)n, kD};
  const cuuint64_t strides[1] = {(cuuint64_t)n * 2};
  const cuuint32_t box[2] = {128, 128};
  return make_map(enc, p, 2, dims, strides, box, CU_TENSOR_MAP_SWIZZLE_NONE);
}

CUtensorMap token_map(EncodeTiledFn enc, const void* p, int rows) {
  const cuuint64_t dims[2] = {2 * kD, 1024};
  const cuuint64_t strides[1] = {4 * kD};
  const cuuint32_t box[2] = {64, (cuuint32_t)rows};
  return make_map(enc, p, 2, dims, strides, box);
}

}

extern "C" void kernel_launch(void* const* d_in, const int* in_sizes, int n_in, void* d_out, int out_size) {
  (void)in_sizes; (void)n_in; (void)out_size;
  static EncodeTiledFn enc = nullptr;
  if (!enc) {
    void* fn = nullptr;
    cudaDriverEntryPointQueryResult q;
    cudaGetDriverEntryPoint("cuTensorMapEncodeTiled", &fn, cudaEnableDefault, &q);
    enc = (EncodeTiledFn)fn;
    cudaFuncSetAttribute(fused_layers_kernel, cudaFuncAttributeMaxDynamicSharedMemorySize, kSmBytes);
  }
  Params prm;
  prm.b1 = (const __nv_bfloat16*)d_in[5];
  prm.b2 = (const __nv_bfloat16*)d_in[7];
  build_segments(prm.seg);
  const cuuint64_t qd[3] = {kD, kD, 3}, qs[2] = {3 * kD * 2, kD * 2};
  const cuuint32_t qb[3] = {64, 32, 3};
  const CUtensorMap map_x = token_map(enc, d_in[0], 128);
  const CUtensorMap map_out = token_map(enc, d_out, 128);
  const CUtensorMap map_qkv = make_map(enc, d_in[1], 3, qd, qs, qb);
  const CUtensorMap map_wo = weight_map(enc, d_in[2], kD, kD, 2);
  const CUtensorMap map_w1a = weight_map(enc, d_in[4], kD, kF, 3);
  const CUtensorMap map_w1b = weight_map(enc, d_in[4], kD, kF, 2);
  const CUtensorMap map_w2 = weight_map(enc, d_in[6], kF, kD, 2);
  fused_layers_kernel<<<kGrid, 384, kSmBytes>>>(map_x, map_out, map_qkv, map_wo, map_w1a, map_w1b, map_w2,
                                                slab_map(enc, d_in[1], 3 * kD), slab_map(enc, d_in[4], kF), prm);
}
```

```cpp
#include <cuda.h>
#include <cuda_bf16.h>
#include <cuda_runtime.h>
#include <stdint.h>

namespace {

constexpr int kD = 1024;
constexpr int kF = 3584;
constexpr int kCtas = 128;
constexpr int kGrid = 132;
constexpr int kTiles = 14;
constexpr int kTileBytes = 16384;

constexpr int kSmRing = 0;
constexpr int kSmX = 163840;
constexpr int kSmStg = kSmX + 32768;
constexpr int kSmHalo = kSmStg + 16384;
constexpr int kSmCsQ = kSmHalo + 6144;
constexpr int kSmV1 = kSmCsQ + 384 * 4;
constexpr int kSmB2 = kSmV1 + 448 * 8;
constexpr int kSmStat = kSmB2 + 128 * 4;
constexpr int kSmBar = kSmStat + 128 * 8;
constexpr int kBarFull = kSmBar;
constexpr int kBarTurn = kBarFull + 8 * 8;
constexpr int kBarReady = kBarTurn + 14 * 8;
constexpr int kBarSrc = kBarReady + 17 * 8;
constexpr int kBarPause = kBarSrc + 8 * 8;
constexpr int kBarFree = kBarPause + 4 * 8;
constexpr int kBarCs = kBarFree + 14 * 8;
constexpr int kBarSlab = kBarCs + 3 * 8;
constexpr int kBarInit = kBarSlab + 4 * 8;
constexpr int kBarEpoch = kBarInit + 8;
constexpr int kBarEmpty = kBarEpoch + 8;
constexpr int kBarEpi = kBarEmpty + 9 * 8;
constexpr int kBarX = kBarEpi + 14 * 8;
constexpr int kBarStat = kBarX + 8 * 8;
constexpr int kBarResume = kBarStat + 4 * 8;
constexpr int kSmEpoch = kBarResume + 4 * 8;
constexpr int kSmBytes = kSmEpoch + 16;
constexpr int kSegs = 38;

constexpr int kFlagLines = kTiles * 16;

constexpr unsigned kSpinLimit = 1u << 22;

__device__ __align__(1024) uint8_t g_x[16 * 16 * kTileBytes];
__device__ __align__(1024) uint8_t g_o[16 * 16 * kTileBytes];
__device__ __align__(1024) uint8_t g_h[16 * 56 * kTileBytes];
__device__ __align__(128) uint2 g_stat[4 * 16 * 128 * 8];
__device__ __align__(128) unsigned g_cs[3 * kD + kF + 3 * kD];
__device__ __align__(128) uint4 g_halo[2 * 16 * 16 * 256];
__device__ __align__(128) unsigned g_flag[kFlagLines * 32];
__device__ unsigned g_ticket;

#define TRACE_AT(tile, k)
#define TRACE_PUB(i, k, c)
#define TRACE_ISSUE(which, nb)

struct Params {
  const __nv_bfloat16* b1;
  const __nv_bfloat16* b2;
  uint32_t seg[kSegs];
};

__device__ __forceinline__ uint32_t smem_u32(const void* p) {
  return (uint32_t)__cvta_generic_to_shared(p);
}
__device__ __forceinline__ uint32_t mapa(uint32_t a, uint32_t cta) {
  uint32_t r;
  asm("mapa.shared::cluster.u32 %0, %1, %2;" : "=r"(r) : "r"(a), "r"(cta));
  return r;
}
__device__ __forceinline__ void mbar_init(uint32_t bar, int cnt) {
  asm volatile("mbarrier.init.shared::cta.b64 [%0], %1;" ::"r"(bar), "r"(cnt) : "memory");
}
__device__ __forceinline__ void mbar_expect_tx(uint32_t bar, uint32_t bytes) {
  asm volatile("mbarrier.arrive.expect_tx.shared::cta.b64 _, [%0], %1;" ::"r"(bar), "r"(bytes) : "memory");
}
__device__ __forceinline__ void mbar_arrive(uint32_t bar) {
  asm volatile("mbarrier.arrive.shared::cta.b64 _, [%0];" ::"r"(bar) : "memory");
}
__device__ __forceinline__ void mbar_arrive_cluster(uint32_t cluster_addr) {
  asm volatile("mbarrier.arrive.shared::cluster.b64 _, [%0];" ::"r"(cluster_addr) : "memory");
}
__device__ __forceinline__ void mbar_wait(uint32_t bar, uint32_t parity) {
  asm volatile("{\n.reg .pred p;\nRETRY:\nmbarrier.try_wait.parity.shared::cta.b64 p, [%0], %1;\n"
               "@!p bra.uni RETRY;\n}" ::"r"(bar), "r"(parity) : "memory");
}
__device__ __forceinline__ void mbar_wait_bounded(uint32_t bar, uint32_t parity) {
  asm volatile("{\n.reg .pred p;\n.reg .u32 c;\nmov.u32 c, 0;\nRETRY:\n"
               "mbarrier.try_wait.parity.shared::cta.b64 p, [%0], %1;\n@p bra.uni DONE;\n"
               "add.u32 c, c, 1;\nsetp.lt.u32 p, c, %2;\n@p bra.uni RETRY;\ntrap;\nDONE:\n}"
               ::"r"(bar), "r"(parity), "n"(1u << 19) : "memory");
}
__device__ __forceinline__ void tma3d(uint32_t dst, const CUtensorMap* m, uint32_t bar, int c0, int c1, int c2) {
  asm volatile(
      "cp.async.bulk.tensor.3d.shared::cluster.global.mbarrier::complete_tx::bytes [%0], [%1, {%3, %4, %5}], [%2];"
      ::"r"(dst), "l"(m), "r"(bar), "r"(c0), "r"(c1), "r"(c2) : "memory");
}
__device__ __forceinline__ void tma3d_mc(uint32_t dst, const CUtensorMap* m, uint32_t bar, int c0, int c1, int c2) {
  asm volatile(
      "cp.async.bulk.tensor.3d.shared::cluster.global.mbarrier::complete_tx::bytes.multicast::cluster"
      " [%0], [%1, {%3, %4, %5}], [%2], %6;"
      ::"r"(dst), "l"(m), "r"(bar), "r"(c0), "r"(c1), "r"(c2), "h"((uint16_t)3) : "memory");
}
__device__ __forceinline__ void tma2d(uint32_t dst, const CUtensorMap* m, uint32_t bar, int c0, int c1) {
  asm volatile(
      "cp.async.bulk.tensor.2d.shared::cluster.global.mbarrier::complete_tx::bytes [%0], [%1, {%3, %4}], [%2];"
      ::"r"(dst), "l"(m), "r"(bar), "r"(c0), "r"(c1) : "memory");
}
__device__ __forceinline__ void tma2d_store(const CUtensorMap* m, uint32_t src, int c0, int c1) {
  asm volatile("cp.async.bulk.tensor.2d.global.shared::cta.bulk_group [%0, {%2, %3}], [%1];"
               ::"l"(m), "r"(src), "r"(c0), "r"(c1) : "memory");
}
__device__ __forceinline__ int lane_id() {
  int l;
  asm volatile("mov.u32 %0, %%laneid;" : "=r"(l));
  return l;
}
__device__ __forceinline__ bool elect() {
  uint32_t p;
  asm volatile("{\n.reg .pred p;\nelect.sync _|p, 0xffffffff;\nselp.b32 %0, 1, 0, p;\n}" : "=r"(p));
  return p;
}
__device__ __forceinline__ void bulk_load(uint32_t dst, const void* src, uint32_t bytes, uint32_t bar) {
  asm volatile("cp.async.bulk.shared::cluster.global.mbarrier::complete_tx::bytes [%0], [%1], %2, [%3];"
               ::"r"(dst), "l"(src), "r"(bytes), "r"(bar) : "memory");
}
__device__ __forceinline__ void bulk_store(void* dst, uint32_t src, uint32_t bytes) {
  asm volatile("cp.async.bulk.global.shared::cta.bulk_group [%0], [%1], %2;" ::"l"(dst), "r"(src), "r"(bytes)
               : "memory");
}
__device__ __forceinline__ void bulk_commit() { asm volatile("cp.async.bulk.commit_group;" ::: "memory"); }
__device__ __forceinline__ void bulk_wait_read() { asm volatile("cp.async.bulk.wait_group.read 0;" ::: "memory"); }
__device__ __forceinline__ void bulk_wait() { asm volatile("cp.async.bulk.wait_group 0;" ::: "memory"); }
__device__ __forceinline__ void fence_async_smem() { asm volatile("fence.proxy.async.shared::cta;" ::: "memory"); }
__device__ __forceinline__ unsigned ld_relaxed(const unsigned* p) {
  unsigned v;
  asm volatile("ld.relaxed.gpu.global.u32 %0, [%1];" : "=r"(v) : "l"(p) : "memory");
  return v;
}
__device__ __forceinline__ uint2 ld_relaxed2(const uint2* p) {
  uint2 v;
  asm volatile("ld.relaxed.gpu.global.v2.u32 {%0, %1}, [%2];" : "=r"(v.x), "=r"(v.y) : "l"(p) : "memory");
  return v;
}
__device__ __forceinline__ void st_relaxed(unsigned* p, unsigned v) {
  asm volatile("st.relaxed.gpu.global.u32 [%0], %1;" ::"l"(p), "r"(v) : "memory");
}
__device__ __forceinline__ void st_release(unsigned* p, unsigned v) {
  asm volatile("st.release.gpu.global.u32 [%0], %1;" ::"l"(p), "r"(v) : "memory");
}
#define ACQ_MODE 1
__device__ __forceinline__ void wait_flags(const unsigned* p, unsigned epoch) {
  unsigned spins = 0;
  while (true) {
    const unsigned v = ld_relaxed(p);
    if (__all_sync(0xffffffffu, v == epoch)) break;
    if (++spins > kSpinLimit) __trap();
  }
  if (ACQ_MODE) asm volatile("fence.acquire.gpu;\nfence.proxy.async.global;" ::: "memory");
  __syncwarp();
}
__device__ __forceinline__ void st_packet(uint4* p, uint32_t d0, uint32_t d1, uint32_t tag) {
  asm volatile("{\n.reg .b128 v;\n.reg .b64 x, y;\nmov.b64 x, {%1, %2};\nmov.b64 y, {%3, %3};\nmov.b128 v, {x, y};\n"
               "st.relaxed.gpu.global.b128 [%0], v;\n}" ::"l"(p), "r"(d0), "r"(d1), "r"(tag) : "memory");
}
__device__ __forceinline__ void ld_packet(const uint4* p, uint32_t& d0, uint32_t& d1, uint32_t& tag) {
  asm volatile("{\n.reg .b128 v;\n.reg .b64 x, y;\n.reg .b32 u;\nld.relaxed.gpu.global.b128 v, [%3];\n"
               "mov.b128 {x, y}, v;\nmov.b64 {%0, %1}, x;\nmov.b64 {%2, u}, y;\n}"
               : "=r"(d0), "=r"(d1), "=r"(tag) : "l"(p) : "memory");
}
__device__ __forceinline__ unsigned tag_value(float v, unsigned epoch) {
  return (__float_as_uint(v) & ~7u) | (epoch & 7u);
}
__device__ __forceinline__ float untag_value(unsigned v) { return __uint_as_float(v & ~7u); }
__device__ __forceinline__ void stsm4(uint32_t a, uint32_t r0, uint32_t r1, uint32_t r2, uint32_t r3) {
  asm volatile("stmatrix.sync.aligned.m8n8.x4.shared.b16 [%0], {%1, %2, %3, %4};" ::"r"(a), "r"(r0), "r"(r1),
               "r"(r2), "r"(r3) : "memory");
}
__device__ __forceinline__ void stsm4_t(uint32_t a, uint32_t r0, uint32_t r1, uint32_t r2, uint32_t r3) {
  asm volatile("stmatrix.sync.aligned.m8n8.x4.trans.shared.b16 [%0], {%1, %2, %3, %4};" ::"r"(a), "r"(r0),
               "r"(r1), "r"(r2), "r"(r3) : "memory");
}
__device__ __forceinline__ uint32_t transpose8(uint32_t a) {
  uint32_t d;
  asm volatile("movmatrix.sync.aligned.m8n8.trans.b16 %0, %1;" : "=r"(d) : "r"(a));
  return d;
}
__device__ __forceinline__ void mma16816(float (&c)[4], uint32_t a0, uint32_t a1, uint32_t a2, uint32_t a3,
                                         uint32_t b0, uint32_t b1) {
  asm volatile("mma.sync.aligned.m16n8k16.row.col.f32.bf16.bf16.f32 {%0, %1, %2, %3}, {%4, %5, %6, %7}, {%8, %9}, "
               "{%0, %1, %2, %3};"
               : "+f"(c[0]), "+f"(c[1]), "+f"(c[2]), "+f"(c[3])
               : "r"(a0), "r"(a1), "r"(a2), "r"(a3), "r"(b0), "r"(b1));
}
__device__ __forceinline__ void mma1688(float (&c)[4], uint32_t a0, uint32_t a1, uint32_t b0) {
  asm volatile("mma.sync.aligned.m16n8k8.row.col.f32.bf16.bf16.f32 {%0, %1, %2, %3}, {%4, %5}, {%6}, {%0, %1, %2, %3};"
               : "+f"(c[0]), "+f"(c[1]), "+f"(c[2]), "+f"(c[3]) : "r"(a0), "r"(a1), "r"(b0));
}
__device__ __forceinline__ float shfl_xor(float v, int m) {
  float r;
  asm volatile("shfl.sync.bfly.b32 %0, %1, %2, 31, 0xffffffff;" : "=f"(r) : "f"(v), "r"(m));
  return r;
}
__device__ __forceinline__ float tanh_fast(float x) {
  float r;
  asm volatile("tanh.approx.f32 %0, %1;" : "=f"(r) : "f"(x));
  return r;
}
__device__ __forceinline__ void ldsm4(uint32_t a, uint32_t (&r)[4]) {
  asm volatile("ldmatrix.sync.aligned.m8n8.x4.shared.b16 {%0, %1, %2, %3}, [%4];"
               : "=r"(r[0]), "=r"(r[1]), "=r"(r[2]), "=r"(r[3]) : "r"(a) : "memory");
}
__device__ __forceinline__ void ldsm4_t(uint32_t a, uint32_t (&r)[4]) {
  asm volatile("ldmatrix.sync.aligned.m8n8.x4.trans.shared.b16 {%0, %1, %2, %3}, [%4];"
               : "=r"(r[0]), "=r"(r[1]), "=r"(r[2]), "=r"(r[3]) : "r"(a) : "memory");
}
__device__ __forceinline__ uint32_t pack2(float lo, float hi) {
  uint32_t r;
  asm volatile("cvt.rn.bf16x2.f32 %0, %1, %2;" : "=r"(r) : "f"(hi), "f"(lo));
  return r;
}
__device__ __forceinline__ float bf_lo(uint32_t r) { return __uint_as_float(r << 16); }
__device__ __forceinline__ float bf_hi(uint32_t r) { return __uint_as_float(r & 0xffff0000u); }
__device__ __forceinline__ float ex2(float x) {
  float r;
  asm("ex2.approx.ftz.f32 %0, %1;" : "=f"(r) : "f"(x));
  return r;
}
__device__ __forceinline__ float rcp(float x) {
  float r;
  asm("rcp.approx.ftz.f32 %0, %1;" : "=f"(r) : "f"(x));
  return r;
}
template <int N>
__device__ __forceinline__ void wg_wait() {
  asm volatile("wgmma.wait_group.sync.aligned %0;" ::"n"(N) : "memory");
}
__device__ __forceinline__ void yield_slot() { asm volatile("pmevent 0;"); }
__device__ __forceinline__ void wg_bar(int wg) { asm volatile("bar.sync %0, 128;" ::"r"(wg + 1) : "memory"); }

template <int N, int KIND>
__device__ __forceinline__ void mma_kblock(float (&acc)[2][96], uint32_t a, uint32_t b);

#define F8(m, d, i) m(d[i]), m(d[i + 1]), m(d[i + 2]), m(d[i + 3]), m(d[i + 4]), m(d[i + 5]), m(d[i + 6]), m(d[i + 7])
#define KSTEP(N, A, B, oa0, oa1, ob, sd)                                                   \
  "add.u32 t, " B ", " #ob ";\nmov.b64 db, {t, hb};\n"                                      \
  "add.u32 t, " A ", " #oa0 ";\nmov.b64 da, {t, ha};\n"                                     \
  "wgmma.mma_async.sync.aligned.m64n" #N "k16.f32.bf16.bf16 {" ACC##N##_0 "}, da, db, " #sd ", 1, 1, 0, 1;\n" \
  "add.u32 t, " A ", " #oa1 ";\nmov.b64 da, {t, ha};\n"                                     \
  "wgmma.mma_async.sync.aligned.m64n" #N "k16.f32.bf16.bf16 {" ACC##N##_1 "}, da, db, " #sd ", 1, 1, 0, 1;\n"

#define MMA_KBLOCK(N, KIND, A, B, ob2, ob3, sd, MID, MODE)                                 \
  template <>                                                                              \
  __device__ __forceinline__ void mma_kblock<N, KIND>(float (&acc)[2][96], uint32_t a, uint32_t b) { \
    asm volatile("{\n.reg .b32 t, ha, hb;\n.reg .b64 da, db;\n"                            \
                 "mov.b32 ha, 0x40000080;\nmov.b32 hb, 0x40000040;\n"                       \
                 "wgmma.fence.sync.aligned;\n"                                             \
                 KSTEP(N, A, B, 0, 64, 0, sd) KSTEP(N, A, B, 2, 66, 128, 1) KSTEP(N, A, B, 4, 68, ob2, 1) \
                 MID KSTEP(N, A, B, 6, 70, ob3, 1) "wgmma.commit_group.sync.aligned;\n}\n"  \
                 : OPS##N(MODE) : "r"(a), "r"(b) : "memory");                              \
  }
#define MMA_KBLOCKS(N, A, B, ob2, ob3)                                                     \
  MMA_KBLOCK(N, 0, A, B, ob2, ob3, 1, "", "+f")                                            \
  MMA_KBLOCK(N, 1, A, B, ob2, ob3, 1, "wgmma.commit_group.sync.aligned;\n", "+f")          \
  MMA_KBLOCK(N, 2, A, B, ob2, ob3, 0, "", "=f")

#define ACC128_0 \
  "%0, %1, %2, %3, %4, %5, %6, %7, %8, %9, %10, %11, %12, %13, %14, %15, " \
  "%16, %17, %18, %19, %20, %21, %22, %23, %24, %25, %26, %27, %28, %29, %30, %31, " \
  "%32, %33, %34, %35, %36, %37, %38, %39, %40, %41, %42, %43, %44, %45, %46, %47, " \
  "%48, %49, %50, %51, %52, %53, %54, %55, %56, %57, %58, %59, %60, %61, %62, %63"
#define ACC128_1 \
  "%64, %65, %66, %67, %68, %69, %70, %71, %72, %73, %74, %75, %76, %77, %78, %79, " \
  "%80, %81, %82, %83, %84, %85, %86, %87, %88, %89, %90, %91, %92, %93, %94, %95, " \
  "%96, %97, %98, %99, %100, %101, %102, %103, %104, %105, %106, %107, %108, %109, %110, %111, " \
  "%112, %113, %114, %115, %116, %117, %118, %119, %120, %121, %122, %123, %124, %125, %126, %127"
#define OPS128(m) \
  F8(m, acc[0], 0), F8(m, acc[0], 8), F8(m, acc[0], 16), F8(m, acc[0], 24), F8(m, acc[0], 32), F8(m, acc[0], 40), F8(m, acc[0], 48), F8(m, acc[0], 56), \
        F8(m, acc[1], 0), F8(m, acc[1], 8), F8(m, acc[1], 16), F8(m, acc[1], 24), F8(m, acc[1], 32), F8(m, acc[1], 40), F8(m, acc[1], 48), F8(m, acc[1], 56)
MMA_KBLOCKS(128, "%128", "%129", 512, 640)

#define ACC192_0 \
  "%0, %1, %2, %3, %4, %5, %6, %7, %8, %9, %10, %11, %12, %13, %14, %15, " \
  "%16, %17, %18, %19, %20, %21, %22, %23, %24, %25, %26, %27, %28, %29, %30, %31, " \
  "%32, %33, %34, %35, %36, %37, %38, %39, %40, %41, %42, %43, %44, %45, %46, %47, " \
  "%48, %49, %50, %51, %52, %53, %54, %55, %56, %57, %58, %59, %60, %61, %62, %63, " \
  "%64, %65, %66, %67, %68, %69, %70, %71, %72, %73, %74, %75, %76, %77, %78, %79, " \
  "%80, %81, %82, %83, %84, %85, %86, %87, %88, %89, %90, %91, %92, %93, %94, %95"
#define ACC192_1 \
  "%96, %97, %98, %99, %100, %101, %102, %103, %104, %105, %106, %107, %108, %109, %110, %111, " \
  "%112, %113, %114, %115, %116, %117, %118, %119, %120, %121, %122, %123, %124, %125, %126, %127, " \
  "%128, %129, %130, %131, %132, %133, %134, %135, %136, %137, %138, %139, %140, %141, %142, %143, " \
  "%144, %145, %146, %147, %148, %149, %150, %151, %152, %153, %154, %155, %156, %157, %158, %159, " \
  "%160, %161, %162, %163, %164, %165, %166, %167, %168, %169, %170, %171, %172, %173, %174, %175, " \
  "%176, %177, %178, %179, %180, %181, %182, %183, %184, %185, %186, %187, %188, %189, %190, %191"
#define OPS192(m) \
  F8(m, acc[0], 0), F8(m, acc[0], 8), F8(m, acc[0], 16), F8(m, acc[0], 24), F8(m, acc[0], 32), F8(m, acc[0], 40), F8(m, acc[0], 48), F8(m, acc[0], 56), F8(m, acc[0], 64), F8(m, acc[0], 72), F8(m, acc[0], 80), F8(m, acc[0], 88), \
        F8(m, acc[1], 0), F8(m, acc[1], 8), F8(m, acc[1], 16), F8(m, acc[1], 24), F8(m, acc[1], 32), F8(m, acc[1], 40), F8(m, acc[1], 48), F8(m, acc[1], 56), F8(m, acc[1], 64), F8(m, acc[1], 72), F8(m, acc[1], 80), F8(m, acc[1], 88)
MMA_KBLOCKS(192, "%192", "%193", 768, 896)

#define TSTEP(REGS, W, X, ow, ox)                                                           \
  "add.u32 t, " X ", " #ox ";\nmov.b64 db, {t, hi};\nadd.u32 t, " W ", " #ow ";\nmov.b64 da, {t, hi};\n" \
  "wgmma.mma_async.sync.aligned.m64n128k16.f32.bf16.bf16 {" REGS "}, da, db, 1, 1, 1, 1, 0;\n"
#define THEAD "{\n.reg .b32 t, hi;\n.reg .b64 da, db;\nmov.b32 hi, 0x40000040;\nwgmma.fence.sync.aligned;\n"
#define TTAIL "wgmma.commit_group.sync.aligned;\n}\n"
__device__ __forceinline__ void mma_kblock_t(float (&acc)[2][96], uint32_t wd, uint32_t xd) {
  asm volatile(THEAD TSTEP(ACC128_0, "%128", "%129", 0, 0) TSTEP(ACC128_1, "%128", "%129", 256, 0)
               TSTEP(ACC128_0, "%128", "%129", 128, 2) TSTEP(ACC128_1, "%128", "%129", 384, 2)
               TSTEP(ACC128_0, "%128", "%129", 512, 4) TSTEP(ACC128_1, "%128", "%129", 768, 4)
               TSTEP(ACC128_0, "%128", "%129", 640, 6) TSTEP(ACC128_1, "%128", "%129", 896, 6) TTAIL
               : OPS128("+f") : "r"(wd), "r"(xd) : "memory");
}
__device__ __forceinline__ void mma_half_t(float (&d)[96], uint32_t wd, uint32_t xd) {
  asm volatile(THEAD TSTEP(ACC128_0, "%64", "%65", 0, 0) TSTEP(ACC128_0, "%64", "%65", 128, 2)
               TSTEP(ACC128_0, "%64", "%65", 512, 4) TSTEP(ACC128_0, "%64", "%65", 640, 6) TTAIL
               : F8("+f", d, 0), F8("+f", d, 8), F8("+f", d, 16), F8("+f", d, 24), F8("+f", d, 32), F8("+f", d, 40),
                 F8("+f", d, 48), F8("+f", d, 56) : "r"(wd), "r"(xd) : "memory");
}

enum { kModePlain = 0, kModeHead = 1, kModeSkip = 2, kModeContinue = 3 };

template <int N>
__device__ __forceinline__ void fence_acc(float (&acc)[2][96]) {
#pragma unroll
  for (int h = 0; h < 2; h++)
#pragma unroll
    for (int i = 0; i < N / 2; i++) asm volatile("" : "+f"(acc[h][i])::"memory");
}

constexpr uint32_t kToB = (kTileBytes >> 4) + ((4096u >> 4) << 16) - (1u << 16);

#define TRACE_KB(nb)

#define HEAD_BOTH 4
template <int N>
__device__ __forceinline__ void head_blocks(float (&acc)[2][96], uint32_t sb, int n0, int slot, int xver,
                                            uint32_t rel_addr, bool rel) {
  const uint32_t ring = (((sb & 0x3FFFF) + kSmRing) >> 4) | (1u << 16);
  const uint32_t xdesc = (((sb & 0x3FFFF) + kSmX) >> 4) | (1u << 16);
  const uint32_t s0 = ring + slot * 2560, s1 = ring + ((slot + 1) & 3) * 2560;
  const uint32_t nb = n0 * 8, xbar = sb + kBarX + (xver - 1) * 16;
  if (xver > 0) {
    mbar_wait(xbar + ((HEAD_BOTH >> xver) & 1) * 8, 0);
    mbar_wait(sb + kBarTurn + (xver == 1 ? 2 : 3 * xver) * 8, 0);
  }
  mbar_wait(sb + kBarFull + (nb & 56), nb >> 6);
  if (n0 == 0) TRACE_AT(0, 1);
  TRACE_KB(nb);
  mma_kblock<N, 2>(acc, xver > 0 ? xdesc : s0, s0 + kToB);
  if (xver > 0) mbar_wait(xbar + 8, 0);
  mbar_wait(sb + kBarFull + (nb & 56) + 8, nb >> 6);
  TRACE_KB(nb + 8);
  mma_kblock<N, 0>(acc, xver > 0 ? xdesc + (kTileBytes >> 4) : s1, s1 + kToB);
  wg_wait<1>();
  if (rel) mbar_arrive_cluster(rel_addr + (nb & 56));
  wg_wait<0>();
  if (rel) mbar_arrive_cluster(rel_addr + (nb & 56) + 8);
  fence_acc<N>(acc);
}

template <int N, bool RESID, bool FRESH, class Pre>
__device__ __forceinline__ void mainloop(float (&acc)[2][96], uint32_t sb, int tile, int n0, int slot, int nkb,
                                         int pause_kk, int att, uint32_t rel_addr, bool rel, int own_kk, Pre pre) {
  constexpr uint32_t kStep = (N == 192 ? 5 : 4) * 512;
  const uint32_t ring = (((sb & 0x3FFFF) + kSmRing) >> 4) | (1u << 16);
  uint32_t st = ring + slot * kStep;
  uint32_t nb = n0 * 8, prev = 64;
  const uint32_t last = nb + 8 * (nkb - (RESID ? 3 : 1)), own = nb + 8 * own_kk;
  const uint32_t stg = (((sb & 0x3FFFF) + kSmStg) >> 4) | (1u << 16);
  uint32_t stop = pause_kk >= 0 ? nb + 8 * pause_kk : last;
  const bool signal = (threadIdx.x & 127) == 64;
  if (!FRESH) fence_acc<N>(acc);
  if (tile > 0) mbar_wait(sb + kBarTurn + (tile - 1) * 8, 0);
  TRACE_AT(tile, 0);
  if constexpr (FRESH) {
    mbar_wait(sb + kBarFull + (nb & 56), nb >> 6);
    TRACE_KB(nb);
    mma_kblock<N, 2>(acc, st, st + kToB);
    prev = nb & 56;
    st += kStep;
    nb += 8;
  }
#pragma unroll 1
  while (true) {
#pragma unroll 1
    do {
      mbar_wait(sb + kBarFull + (nb & 56), nb >> 6);
      TRACE_KB(nb);
      if constexpr (RESID) mma_kblock_t(acc, st + kToB, nb == own ? stg : st);
      else mma_kblock<N, 0>(acc, st, st + kToB);
      wg_wait<1>();
      if (rel) mbar_arrive_cluster(rel_addr + prev);
      prev = nb & 56;
      st += kStep;
      if (st == ring + 10240) st = ring;
      nb += 8;
    } while (nb != stop);
    if (stop == last) break;
    stop = last;
    if (signal) mbar_arrive(sb + kBarPause + att * 8);
    wg_wait<0>();
    if (rel) mbar_arrive_cluster(rel_addr + prev);
    prev = 64;
    mbar_wait(sb + kBarResume + att * 8, 0);
  }
  mbar_wait(sb + kBarFull + (nb & 56), nb >> 6);
  TRACE_KB(nb);
  if constexpr (RESID) {
    const uint32_t z = gridDim.y - 1;
    const uint32_t s2 = st + kStep, s3 = s2 == ring + 8192 ? ring : s2 + kStep;
    mma_half_t(acc[0], st + kToB, st);
    wg_wait<1>();
    if (rel) mbar_arrive_cluster(rel_addr + 32);
    mbar_wait(sb + kBarFull + 48, nb >> 6);
    TRACE_KB(nb + 8);
    mma_half_t(acc[0], s2 + kToB, s2);
    mbar_wait(sb + kBarFull + 56, nb >> 6);
    TRACE_KB(nb + 16);
    mma_half_t(acc[0], s3 + kToB, s3);
    mma_half_t(acc[1], st + kToB + 256, st + z);
    mma_half_t(acc[1], s2 + kToB + 256, s2 + z);
    wg_wait<2>();
#pragma unroll
    for (int i = 0; i < 64; i++) asm volatile("" : "+f"(acc[0][i])::"memory");
    pre(0);
    mma_half_t(acc[1], s3 + kToB + 256, s3 + z);
    wg_wait<2>();
    if (rel) mbar_arrive_cluster(rel_addr + 40);
    pre(1);
    wg_wait<1>();
    if (rel) mbar_arrive_cluster(rel_addr + 48);
    if (signal) mbar_arrive(sb + kBarTurn + tile * 8);
    wg_wait<0>();
    if (rel) mbar_arrive_cluster(rel_addr + 56);
#pragma unroll
    for (int i = 0; i < 64; i++) asm volatile("" : "+f"(acc[1][i])::"memory");
  } else {
    mma_kblock<N, 1>(acc, st, st + kToB);
    wg_wait<2>();
    if (rel) mbar_arrive_cluster(rel_addr + prev);
    pre();
    wg_wait<1>();
    if (signal) mbar_arrive(sb + kBarTurn + tile * 8);
    wg_wait<0>();
    if (rel) mbar_arrive_cluster(rel_addr + (nb & 56));
    fence_acc<N>(acc);
  }
}

__device__ __forceinline__ void publish_stats(uint32_t sb, uint2* stat, int w, int lane, unsigned epoch) {
  const uint32_t row = sb + kSmX + (32 * w + lane) * 128;
  float s[4], q[4];
#pragma unroll
  for (int c = 0; c < 4; c++) s[c] = q[c] = 0.f;
  uint32_t nx[4];
  ldsm4(row + ((lane & 7) << 4), nx);
#pragma unroll 1
  for (int J = 1; J <= 16; J++) {
    const uint32_t r[4] = {nx[0], nx[1], nx[2], nx[3]};
    ldsm4(row + ((J >> 3) & 1) * kTileBytes + (((J ^ lane) & 7) << 4), nx);
#pragma unroll
    for (int c = 0; c < 4; c++) {
      const float lo = bf_lo(r[c]);
      s[c] += lo;
      q[c] = fmaf(lo, lo, q[c]);
      if (c & 1) yield_slot();
    }
#pragma unroll
    for (int c = 0; c < 4; c++) {
      const float hi = bf_hi(r[c]);
      s[c] += hi;
      q[c] = fmaf(hi, hi, q[c]);
      if (c & 1) yield_slot();
    }
  }
#pragma unroll
  for (int c = 0; c < 4; c++) {
    s[c] += shfl_xor(s[c], 1);
    q[c] += shfl_xor(q[c], 1);
    s[c] += shfl_xor(s[c], 2);
    q[c] += shfl_xor(q[c], 2);
  }
  const int t = lane & 3, g = lane >> 2;
  const float so = t == 0 ? s[0] : t == 1 ? s[1] : t == 2 ? s[2] : s[3];
  const float qo = t == 0 ? q[0] : t == 1 ? q[1] : t == 2 ? q[2] : q[3];
  asm volatile("st.relaxed.gpu.global.v2.u32 [%0], {%1, %2};" ::"l"(stat + 32 * w + 8 * t + g),
               "r"(tag_value(so, epoch)), "r"(tag_value(qo, epoch)) : "memory");
}

__device__ __forceinline__ void add_chunk(float (&a)[8], const uint4& v) {
  a[0] += bf_lo(v.x); a[1] += bf_hi(v.x);
  a[2] += bf_lo(v.y); a[3] += bf_hi(v.y);
  a[4] += bf_lo(v.z); a[5] += bf_hi(v.z);
  a[6] += bf_lo(v.w); a[7] += bf_hi(v.w);
}

__device__ __forceinline__ int helper_col(int id, int slab) {
  return (slab < 3 ? slab * kD : (slab - 3) * 512) + id * 128;
}
__device__ __forceinline__ void helper_cta(const CUtensorMap* map_q, const CUtensorMap* map_1, uint8_t* sm,
                                           uint32_t sb, int id, int warp) {
  constexpr int kRed = 6 * 32768, kBar = kRed + 2 * 4096;
  const int tid = threadIdx.x;
  if (warp == 8 && elect()) {
#pragma unroll
    for (int s = 0; s < 6; s++) {
      mbar_init(sb + kBar + s * 8, 1);
      mbar_init(sb + kBar + 64 + s * 8, 4);
    }
    fence_async_smem();
#pragma unroll
    for (int s = 0; s < 6; s++) {
      mbar_expect_tx(sb + kBar + s * 8, 32768);
      tma2d(sb + s * 32768, map_q, sb + kBar + s * 8, id * 128, s * 128);
    }
  }
  __syncthreads();
  if (warp == 8) {
    int slot = 0, ph = 0;
#pragma unroll 1
    for (int n = 6; n < 80; n++) {
      mbar_wait(sb + kBar + 64 + slot * 8, ph);
      if (elect()) {
        mbar_expect_tx(sb + kBar + slot * 8, 32768);
        tma2d(sb + slot * 32768, n < 24 ? map_q : map_1, sb + kBar + slot * 8, helper_col(id, n >> 3), (n & 7) * 128);
      }
      if (++slot == 6) slot = 0, ph ^= 1;
    }
  } else if (warp < 8) {
    if (tid == 0) *reinterpret_cast<unsigned*>(sm + kBar + 128) = atomicAdd(&g_ticket, 1u) / kGrid + 1;
    int slot = warp >> 2, ph = 0;
#pragma unroll 1
    for (int slab = 0; slab < 10; slab++) {
      float a[8];
#pragma unroll
      for (int e = 0; e < 8; e++) a[e] = 0.f;
#pragma unroll 1
      for (int box = 0; box < 4; box++) {
        mbar_wait_bounded(sb + kBar + slot * 8, ph);
        const uint4* p = reinterpret_cast<const uint4*>(sm + slot * 32768) + (tid & 127);
        uint4 v[16];
#pragma unroll
        for (int i = 0; i < 16; i++) v[i] = p[i * 128];
        __syncwarp();
        if (elect()) mbar_arrive(sb + kBar + 64 + slot * 8);
#pragma unroll
        for (int i = 0; i < 16; i++) add_chunk(a, v[i]);
        slot += 2;
        if (slot >= 6) slot -= 6, ph ^= 1;
      }
      float* red = reinterpret_cast<float*>(sm + kRed + (slab & 1) * 4096);
#pragma unroll
      for (int e = 0; e < 8; e++) a[e] += shfl_xor(a[e], 16);
      if ((tid & 16) == 0) {
        float4* d = reinterpret_cast<float4*>(red + warp * 128 + (tid & 15) * 8);
        d[0] = make_float4(a[0], a[1], a[2], a[3]);
        d[1] = make_float4(a[4], a[5], a[6], a[7]);
      }
      asm volatile("bar.sync 1, 256;" ::: "memory");
      if (warp < 4) {
        float t = 0.f;
#pragma unroll
        for (int q = 0; q < 8; q++) t += red[q * 128 + tid];
        st_relaxed(g_cs + (slab < 3 ? 0 : 3 * kD) + helper_col(id, slab) + tid,
                   tag_value(t, *reinterpret_cast<volatile unsigned*>(sm + kBar + 128)));
      }
    }
  }
}

__device__ __forceinline__ void colsum_strip(const CUtensorMap* map, uint8_t* sm, uint32_t sb, int col, int half,
                                             int lane, unsigned epoch) {
  const uint32_t bar = sb + kBarSlab + half * 16;
  const int buf = kSmStg + half * 8192;
  float a[8];
#pragma unroll
  for (int e = 0; e < 8; e++) a[e] = 0.f;
#pragma unroll 1
  for (int r = -2; r < 4; r++) {
    if (r >= 0) {
      mbar_wait(bar + (r & 1) * 8, r >> 1);
      const uint4* p = reinterpret_cast<const uint4*>(sm + buf + (r & 1) * 4096) + lane;
#pragma unroll 1
      for (int q = 0; q < 8; q += 4) {
        uint4 v[4];
#pragma unroll
        for (int u = 0; u < 4; u++) v[u] = p[(q + u) * 32];
#pragma unroll
        for (int u = 0; u < 4; u++) {
          a[0] += bf_lo(v[u].x); a[1] += bf_hi(v[u].x); a[2] += bf_lo(v[u].y); a[3] += bf_hi(v[u].y);
          yield_slot();
          a[4] += bf_lo(v[u].z); a[5] += bf_hi(v[u].z); a[6] += bf_lo(v[u].w); a[7] += bf_hi(v[u].w);
          yield_slot();
        }
      }
      fence_async_smem();
      __syncwarp();
    }
    if (r < 2 && elect()) {
      mbar_expect_tx(bar + (r & 1) * 8, 4096);
      tma2d(sb + buf + (r & 1) * 4096, map, bar + (r & 1) * 8, col, half * 512 + (r + 2) * 128);
    }
  }
#pragma unroll
  for (int e = 0; e < 4; e++) a[e] = (lane & 16 ? a[e + 4] : a[e]) + shfl_xor(lane & 16 ? a[e] : a[e + 4], 16);
#pragma unroll
  for (int e = 0; e < 2; e++) a[e] = (lane & 8 ? a[e + 2] : a[e]) + shfl_xor(lane & 8 ? a[e] : a[e + 2], 8);
  a[0] = (lane & 4 ? a[1] : a[0]) + shfl_xor(lane & 4 ? a[0] : a[1], 4);
  a[0] += shfl_xor(a[0], 2);
  if (!(lane & 2)) st_relaxed(g_cs + half * (3 * kD + kF) + col + (lane & 1) * 8 + (lane >> 2), tag_value(a[0], epoch));
}

constexpr float kGeluBeta = 0.3292034911525734f;
constexpr float kGeluK = 2.423681954311584f;

__device__ __forceinline__ void store_staged(uint8_t* dst, uint32_t stg) {
  fence_async_smem();
  __syncwarp();
  if (elect()) {
    bulk_store(dst, stg, 4096);
    bulk_commit();
  }
}

#define GY_MASK 5
#define GD 2
#define GF_MASK 3
#define GY(k) if ((GY_MASK >> k) & 1) yield_slot()
template <int J0, int J1>
__device__ __forceinline__ void fold_norm(float (&acc)[2][96], const float2 (&st)[4], const float4* vec) {
  float4 vn = vec[J0 * 4];
#pragma unroll
  for (int J = J0; J < J1; J++) {
    const float4 v = vn;
    if (J + 1 < J1) vn = vec[J * 4 + 4];
#pragma unroll
    for (int c = 0; c < 4; c++) {
      float& a0 = acc[c & 1][4 * J + (c & 2)];
      float& a1 = acc[c & 1][4 * J + (c & 2) + 1];
      a0 = fmaf(a0, st[c].x, fmaf(st[c].y, v.x, v.z));
      a1 = fmaf(a1, st[c].x, fmaf(st[c].y, v.y, v.w));
      asm volatile("" : "+f"(a0), "+f"(a1));
      if ((c & 1) && ((GF_MASK >> (c >> 1)) & 1)) yield_slot();
    }
  }
}

template <int CH, class Acquire>
__device__ __forceinline__ void gelu_chunk(const float (&acc)[2][96], uint32_t stg, int lane, uint8_t* prev,
                                           Acquire acquire) {
  uint32_t pk[8][4];
  float z[GD + 1][4];
  const uint32_t row = (stg + lane * 128) ^ ((lane & 7) << 4);
#define U(s, e) acc[(e) >> 1][4 * (CH * 8 + ((s) >> 1)) + 2 * ((s) & 1) + ((e) & 1)]
#pragma unroll
  for (int s = 0; s < 16 + GD; s++) {
    const int cur = s % (GD + 1), p1 = (s + GD) % (GD + 1), p2 = (s + 1) % (GD + 1), q = s - GD, jj = 2 * q - 24;
    const bool mid = s >= 1 && s < 17;
    if (mid) z[p1][0] = tanh_fast(z[p1][0]);
    if (s < 16) {
#pragma unroll
      for (int e = 0; e < 4; e++) {
        z[cur][e] = fmaf(U(s, e), U(s, e), kGeluK);
        asm volatile("" : "+f"(z[cur][e]));
      }
    }
    if (jj >= 0) stsm4(row ^ (jj << 4), pk[jj][0], pk[jj][1], pk[jj][2], pk[jj][3]);
    GY(0);
    if (mid) z[p1][1] = tanh_fast(z[p1][1]);
    if (q >= 0) {
      pk[q >> 1][2 * (q & 1)] = pack2(fmaf(U(q, 0), z[p2][0], U(q, 0)), fmaf(U(q, 1), z[p2][1], U(q, 1)));
      pk[q >> 1][2 * (q & 1) + 1] = pack2(fmaf(U(q, 2), z[p2][2], U(q, 2)), fmaf(U(q, 3), z[p2][3], U(q, 3)));
    }
    GY(1);
    if (mid) z[p1][2] = tanh_fast(z[p1][2]);
    if (s < 16) {
#pragma unroll
      for (int e = 0; e < 4; e++) {
        z[cur][e] *= U(s, e);
        asm volatile("" : "+f"(z[cur][e]));
      }
    }
    if (mid) z[p1][3] = tanh_fast(z[p1][3]);
    if (jj >= 0) stsm4(row ^ ((jj + 1) << 4), pk[jj + 1][0], pk[jj + 1][1], pk[jj + 1][2], pk[jj + 1][3]);
    GY(2);
    if (CH == 1 && s == 1) store_staged(prev, stg);
    if (q == 11) acquire();
  }
#undef U
}

__device__ __forceinline__ void scale_stats(float2 (&st)[4]) {
#pragma unroll
  for (int c = 0; c < 4; c++) {
    st[c].x *= kGeluBeta;
    st[c].y *= st[c].x;
  }
}

__device__ __forceinline__ void add_mean_term(float (&acc)[2][96], const float2 (&st)[4], uint8_t* sm, int tq,
                                              int lane) {
  const float2* cs = reinterpret_cast<const float2*>(sm + kSmCsQ) + tq * 96 + (lane & 3);
  float2 vn = cs[0];
#pragma unroll
  for (int J = 0; J < 24; J++) {
    const float2 v = vn;
    if (J < 23) vn = cs[J * 4 + 4];
#pragma unroll
    for (int c = 0; c < 4; c++) {
      acc[c & 1][4 * J + (c & 2)] = fmaf(st[c].y, v.x, acc[c & 1][4 * J + (c & 2)]);
      acc[c & 1][4 * J + (c & 2) + 1] = fmaf(st[c].y, v.y, acc[c & 1][4 * J + (c & 2) + 1]);
    }
    yield_slot();
  }
}

#define TWO_PART 0
#define RESUME_LATE 0
#define HALO_AT 2
__device__ __forceinline__ void epilogue_attn(const float (&acc)[2][96], const float2 (&st)[4], uint8_t* sm,
                                              uint32_t sb, int layer, int tq, int b, int j, unsigned epoch, int tile,
                                              int wg, int w, int lane) {
  const int t = lane & 3, g = lane >> 2;
  const int hp = j + 8 * tq, att = 2 * layer + tq;
  uint32_t q[4][8], k[5][8], vt[5][8];
#define SCALED(c, J) pack2(acc[(c) & 1][4 * (J) + ((c) & 2)] * st[c].x, acc[(c) & 1][4 * (J) + ((c) & 2) + 1] * st[c].x)
#pragma unroll
  for (int J = 0; J < 8; J++) vt[4][J] = transpose8(SCALED(3, 16 + J));
#pragma unroll
  for (int J = 0; J < 8; J++) k[4][J] = SCALED(3, 8 + J);
  if (w < 3) {
    uint2* hs = reinterpret_cast<uint2*>(sm + kSmHalo + w * 2048) + lane;
#pragma unroll
    for (int i = 0; i < 4; i++) {
      hs[i * 32] = make_uint2(k[4][2 * i], k[4][2 * i + 1]);
      hs[128 + i * 32] = make_uint2(vt[4][2 * i], vt[4][2 * i + 1]);
    }
  } else if ((b & 7) != 7) {
    uint4* gh = g_halo + ((layer * 16 + b) * 16 + hp) * 256 + lane;
#pragma unroll
    for (int i = 0; i < 4; i++) {
      st_packet(gh + i * 32, k[4][2 * i], k[4][2 * i + 1], epoch);
      st_packet(gh + 128 + i * 32, vt[4][2 * i], vt[4][2 * i + 1], epoch);
    }
  }
#pragma unroll
  for (int c = 0; c < 3; c++)
#pragma unroll
    for (int J = 0; J < 8; J++) {
      k[c + 1][J] = SCALED(c, 8 + J);
      vt[c + 1][J] = transpose8(SCALED(c, 16 + J));
      yield_slot();
    }
  const bool first = w == 0 && (b & 7) == 0;
  const uint4* gh = g_halo + ((layer * 16 + b - 1) * 16 + hp) * 256 + lane;
  uint32_t tag[8];
#define LOAD_HALO()                                                                                    \
  _Pragma("unroll") for (int i = 0; i < 4; i++) {                                                      \
    ld_packet(gh + i * 32, k[0][2 * i], k[0][2 * i + 1], tag[i]);                                      \
    ld_packet(gh + 128 + i * 32, vt[0][2 * i], vt[0][2 * i + 1], tag[4 + i]);                          \
  }
#define AWAIT_HALO()                                                                                   \
  for (unsigned spins = 0;; spins++) {                                                                 \
    const unsigned d0 = (tag[0] ^ epoch) | (tag[1] ^ epoch) | (tag[2] ^ epoch) | (tag[3] ^ epoch);     \
    const unsigned d1 = (tag[4] ^ epoch) | (tag[5] ^ epoch) | (tag[6] ^ epoch) | (tag[7] ^ epoch);     \
    if (__all_sync(0xffffffffu, (d0 | d1) == 0)) break;                                                \
    if (spins > kSpinLimit) __trap();                                                                  \
    LOAD_HALO();                                                                                       \
  }
#pragma unroll
  for (int c = 0; c <= 4; c++) {
    if (c == HALO_AT) {
      if (w == 0 && !first) {
        LOAD_HALO();
      } else {
#pragma unroll
        for (int i = 0; i < 8; i++) k[0][i] = vt[0][i] = tag[i] = 0u;
      }
    }
#pragma unroll
    for (int J = 0; J < 8 && c < 4; J++) {
      q[c & 3][J] = SCALED(c & 3, J);
      if (J & 1) yield_slot();
    }
  }
#undef SCALED
  TRACE_AT(tile, 8);
  wg_bar(wg);
  if (w > 0) {
    const uint2* hs = reinterpret_cast<const uint2*>(sm + kSmHalo + (w - 1) * 2048) + lane;
#pragma unroll
    for (int i = 0; i < 4; i++) {
      const uint2 a = hs[i * 32], c = hs[128 + i * 32];
      k[0][2 * i] = a.x; k[0][2 * i + 1] = a.y;
      vt[0][2 * i] = c.x; vt[0][2 * i + 1] = c.y;
    }
  } else if (!first && tq == 0) {
    AWAIT_HALO();
  }
  constexpr float kScale = 0.17677669529663687f * 1.4426950408889634f;
  const bool own0 = 2 * t <= g, own1 = 2 * t + 1 <= g;
  const uint32_t own_mask = (own0 ? 0xffffu : 0u) | (own1 ? 0xffff0000u : 0u);
  const uint32_t stg = sb + kSmStg + w * 4096;
  const uint32_t orow = stg + (lane & 7) * 128, ochunk = (lane >> 3) ^ (lane & 7);
  TRACE_AT(tile, 9);
  mbar_wait(sb + kBarPause + att * 8, 0);
  TRACE_AT(tile, 10);

  float s[2][6][4], o[2][4][2][4];
  auto scores = [&](int hd, int m) {
    const int ca = 2 * (m / 3), kg = ca + m % 3;
#pragma unroll
    for (int e = 0; e < 4; e++) s[hd][m][e] = 0.f;
#pragma unroll
    for (int J = 4 * hd; J < 4 * hd + 4; J += 2)
      mma16816(s[hd][m], q[ca][J], q[ca + 1][J], q[ca][J + 1], q[ca + 1][J + 1], k[kg][J], k[kg][J + 1]);
  };
  auto attend = [&](int c0, int c1) {
    float v0[2][4], v1[2][4], m[2][4];
#define UNITS _Pragma("unroll") for (int hd = 0; hd < 2; hd++) _Pragma("unroll") for (int c = c0; c < c1; c++)
    UNITS {
      const int mp = 3 * (c >> 1) + (c & 1), r = 2 * (c & 1);
      float p0 = s[hd][mp][r], p1 = s[hd][mp][r + 1];
      if (c == 0 && first) p0 = p1 = -INFINITY;
      v0[hd][c] = own0 ? s[hd][mp + 1][r] : p0;
      v1[hd][c] = own1 ? s[hd][mp + 1][r + 1] : p1;
      m[hd][c] = fmaxf(v0[hd][c], v1[hd][c]);
    }
    UNITS m[hd][c] = fmaxf(m[hd][c], shfl_xor(m[hd][c], 1));
    UNITS m[hd][c] = fmaxf(m[hd][c], shfl_xor(m[hd][c], 2));
    UNITS {
      const float nm = -m[hd][c] * kScale;
      v0[hd][c] = ex2(fmaf(v0[hd][c], kScale, nm));
      v1[hd][c] = ex2(fmaf(v1[hd][c], kScale, nm));
      m[hd][c] = v0[hd][c] + v1[hd][c];
    }
    UNITS m[hd][c] += shfl_xor(m[hd][c], 1);
    UNITS m[hd][c] += shfl_xor(m[hd][c], 2);
    UNITS {
      const float inv = rcp(m[hd][c]);
      const uint32_t p = pack2(v0[hd][c] * inv, v1[hd][c] * inv);
#pragma unroll
      for (int ds = 0; ds < 2; ds++) {
        const int J = 4 * hd + 2 * ds;
#pragma unroll
        for (int e = 0; e < 4; e++) o[hd][c][ds][e] = 0.f;
        if (c & 1) {
          mma16816(o[hd][c][ds], vt[c][J], vt[c][J + 1], vt[c + 1][J], vt[c + 1][J + 1], p & ~own_mask, p & own_mask);
        } else {
          mma1688(o[hd][c][ds], vt[c + 1][J], vt[c + 1][J + 1], p & own_mask);
          mma1688(o[hd][c][ds], vt[c][J], vt[c][J + 1], p & ~own_mask);
        }
      }
    }
  };
  auto stage = [&](int c0, int c1) {
    UNITS stsm4_t(orow + c * 1024 + ((ochunk ^ (4 * hd)) << 4), pack2(o[hd][c][0][0], o[hd][c][0][1]),
                  pack2(o[hd][c][0][2], o[hd][c][0][3]), pack2(o[hd][c][1][0], o[hd][c][1][1]),
                  pack2(o[hd][c][1][2], o[hd][c][1][3]));
#undef UNITS
  };
  if (w == 0 && !first) AWAIT_HALO();
#pragma unroll
  for (int hd = 0; hd < 2; hd++)
#pragma unroll
    for (int m = 0; m < 6; m++) scores(hd, m);
  attend(0, 4);
  yield_slot();
  if (tq == 0 && elect()) mbar_arrive(sb + kBarResume + att * 8);
  TRACE_AT(tile, 11);
  stage(0, 4);
#undef AWAIT_HALO
#undef LOAD_HALO
  fence_async_smem();
  __syncwarp();
  TRACE_AT(tile, 12);
  if (elect()) {
    bulk_store(g_o + (b * 16 + hp) * kTileBytes + w * 4096, stg, 4096);
    bulk_commit();
    if (tq == 1 && !RESUME_LATE) mbar_arrive(sb + kBarResume + att * 8);
    bulk_wait();
    if (tq == 1 && RESUME_LATE) mbar_arrive(sb + kBarResume + att * 8);
    TRACE_AT(tile, 13);
    mbar_arrive(sb + kBarEpi + tile * 8);
  }
  __syncwarp();
}

__device__ __forceinline__ void gather_stats(uint8_t* sm, const uint2* stat, int r, unsigned epoch) {
  uint2 a[8];
  unsigned spins = 0;
  while (true) {
    unsigned diff = 0;
#pragma unroll
    for (int i = 0; i < 8; i++) {
      a[i] = ld_relaxed2(stat + i * 128 + r);
      diff |= (a[i].x ^ epoch) | (a[i].y ^ epoch);
    }
    if (__all_sync(0xffffffffu, (diff & 7u) == 0)) break;
    if (++spins > kSpinLimit) __trap();
    __nanosleep(200);
  }
  float s = 0.f, q = 0.f;
#pragma unroll
  for (int i = 0; i < 8; i++) {
    s += untag_value(a[i].x);
    q += untag_value(a[i].y);
  }
  const float mean = s * (1.f / 1024.f);
  const float var = fmaxf(fmaf(-mean, mean, q * (1.f / 1024.f)), 0.f);
  reinterpret_cast<float2*>(sm + kSmStat)[r] = make_float2(rsqrtf(var + 1e-5f), -mean);
}

__device__ __forceinline__ void gather_colsums_qkv(uint8_t* sm, int tq, int j, int lane, unsigned epoch) {
  const uint2* src = reinterpret_cast<const uint2*>(g_cs + (j + 8 * tq) * 64) + lane;
  uint2 v[3], u[3];
  for (unsigned spins = 0;; spins++) {
    unsigned diff = 0;
#pragma unroll
    for (int q = 0; q < 3; q++) {
      v[q] = ld_relaxed2(src + q * (kD / 2));
      u[q] = make_uint2(epoch & 7u, epoch & 7u);
      if (tq) u[q] = ld_relaxed2(src + (q * kD + 3 * kD + kF) / 2);
    }
#pragma unroll
    for (int q = 0; q < 3; q++) diff |= (v[q].x ^ epoch) | (v[q].y ^ epoch) | (u[q].x ^ epoch) | (u[q].y ^ epoch);
    if (__all_sync(0xffffffffu, (diff & 7u) == 0)) break;
    if (spins > kSpinLimit) __trap();
  }
#pragma unroll
  for (int q = 0; q < 3; q++)
    reinterpret_cast<float2*>(sm + kSmCsQ)[tq * 96 + q * 32 + lane] =
        make_float2(untag_value(v[q].x) + untag_value(u[q].x), untag_value(v[q].y) + untag_value(u[q].y));
}

__device__ __forceinline__ void gather_colsums_w1(uint8_t* sm, const __nv_bfloat16* b1, int j, int lane,
                                                  unsigned epoch) {
#pragma unroll 1
  for (int blk = 0; blk < 7; blk++) {
    const int pair = 32 * (blk + (blk < 3 ? 3 * j : blk < 5 ? 21 + 2 * j : 35 + 2 * j)) + lane;
    const uint32_t bias = reinterpret_cast<const uint32_t*>(b1)[pair];
    uint2 v;
    for (unsigned spins = 0;; spins++) {
      v = ld_relaxed2(reinterpret_cast<const uint2*>(g_cs + 3 * kD) + pair);
      if (__all_sync(0xffffffffu, (((v.x ^ epoch) | (v.y ^ epoch)) & 7u) == 0)) break;
      if (spins > kSpinLimit) __trap();
    }
    reinterpret_cast<float4*>(sm + kSmV1)[blk * 32 + lane] =
        make_float4(untag_value(v.x), untag_value(v.y), kGeluBeta * bf_lo(bias), kGeluBeta * bf_hi(bias));
  }
}

#define FINE 3
#define LATE_REL2 1
#define STRIP_GATE kBarInit
#define STAGE_YIELD 1
#define PAUSE_QKV2 7
#define PAUSE_WO 3

__global__ void __cluster_dims__(2, 1, 1) __launch_bounds__(384, 1)
fused_layers_kernel(const __grid_constant__ CUtensorMap map_x, const __grid_constant__ CUtensorMap map_out,
                    const __grid_constant__ CUtensorMap map_qkv, const __grid_constant__ CUtensorMap map_wo,
                    const __grid_constant__ CUtensorMap map_w1a, const __grid_constant__ CUtensorMap map_w1b,
                    const __grid_constant__ CUtensorMap map_w2, const __grid_constant__ CUtensorMap map_csq,
                    const __grid_constant__ CUtensorMap map_cs1, const __grid_constant__ CUtensorMap map_css,
                    const __grid_constant__ Params prm) {
  extern __shared__ __align__(1024) uint8_t sm[];
  if (threadIdx.x < 128 && blockIdx.x < kCtas) TRACE_AT(15, 1);
  const uint32_t sb = __shfl_sync(0xffffffffu, smem_u32(sm), 0);
  const int warp = __shfl_sync(0xffffffffu, threadIdx.x >> 5, 0), lane = threadIdx.x & 31;
  const int cta = blockIdx.x, rank = cta & 1, cl = cta >> 1;
  const int grp = cl < 4 ? 0 : cl < 36 ? (cl - 4) & 7 : 1 + (cl - 36) % 7;
  const int j = cl < 4 ? 4 + cl : cl < 36 ? (cl - 4) >> 3 : 4 + (cl - 36) / 7;
  const int b = 2 * grp + rank;
  const int xcol = (b >> 3) * kD, xrow = (b & 7) * 128;

  if (cta >= kCtas) {
    helper_cta(&map_csq, &map_cs1, sm, sb, cta - kCtas, warp);
    return;
  }
  if (warp >= 8 && elect()) {
    if (warp == 9) {
#pragma unroll
      for (int s = 0; s < 8; s++) mbar_init(sb + kBarFull + s * 8, 1);
      mbar_init(sb + kBarInit, 1);
      fence_async_smem();
#pragma unroll
      for (int s = 0; s < 4; s++) {
        const uint32_t full = sb + kBarFull + s * 8, dst = sb + kSmRing + s * 40960;
        mbar_expect_tx(full, 40960);
        tma2d(dst, &map_x, full, xcol + (s & 1) * 64, xrow);
        tma3d(dst + kTileBytes, &map_qkv, full, (j + 4 * (s & 2)) * 64, (s & 1) * 64, 0);
        tma3d(dst + kTileBytes + 12288, &map_qkv, full, (j + 4 * (s & 2)) * 64, (s & 1) * 64 + 32, 0);
      }
    } else if (warp == 8) {
      if (sb & 1023) __trap();
#pragma unroll
      for (int o = kBarTurn; o < kBarPause; o += 8) mbar_init(sb + o, 1);
    } else if (warp == 10) {
#pragma unroll
      for (int o = kBarEpi; o < kSmEpoch; o += 8) mbar_init(sb + o, 4);
    } else {
#pragma unroll
      for (int o = kBarPause; o < kBarEpi; o += 8)
        if (o != kBarInit) mbar_init(sb + o, o < kBarEmpty ? 1 : 2);
    }
    asm volatile("fence.mbarrier_init.release.cluster;" ::: "memory");
  }
  __syncwarp();
  asm volatile("barrier.cluster.arrive.relaxed.aligned;" ::: "memory");

  if (warp >= 8) {
    asm volatile("setmaxnreg.dec.sync.aligned.u32 40;");
    if (warp < 10) {
      asm volatile("barrier.cluster.wait.aligned;" ::: "memory");
      uint32_t nb = 32, off = 0, kb = 0;
#define RING_STEP(WAIT, ISSUE)                                            \
  do {                                                                    \
    const uint32_t mb = nb - depth, full = sb + kBarFull + (nb & 56);     \
    if (kb == skip) kb += inc;                                            \
    mbar_wait(sb + kBarEmpty + (mb & 56), mb >> 6);                       \
    WAIT;                                                                 \
    if (elect()) { ISSUE; }                                               \
    TRACE_ISSUE(9 - warp, nb);                                            \
    kb += inc;                                                            \
    off = off == wrap ? 0 : off + step;                                   \
    nb += 8;                                                              \
  } while (nb != nend)
#pragma unroll 1
      for (int sg = 0; sg < kSegs; sg++) {
        const uint32_t e = prm.seg[sg];
        const int ty = e & 7, mode = (e >> 15) & 3, reset = (e >> 24) & 3;
        const uint32_t nend = nb + (e & 0x1f8);
        const uint32_t step = (e >> 17) & 1 ? 40960 : 32768, wrap = 163840 - step;
        const uint32_t depth = (e >> 18) & 1 ? 40 : 32;
        if (reset) off = reset == 1 ? 0 : reset == 2 ? 40960 : 131072;
        const uint32_t own = ty == 2 ? 8 + j : 2 * j;
        if (mode != kModeContinue) kb = mode == kModeHead ? own : (e >> 9) & 63;
        const uint32_t inc = mode >= kModeSkip && ty != 2 ? 2 : 1, skip = mode >= kModeSkip ? own + (kb & 1) : 255;
        if (warp == 8) {
          const CUtensorMap* map = ty < 2 ? &map_qkv : ty == 2 ? &map_wo : ty == 3 ? &map_w1a : ty < 6 ? &map_w1b : &map_w2;
          const int c0 = ty < 2 ? (j + 8 * ty) * 64 : 0;
          const int c2 = ty < 2 ? 0 : ty == 3 ? 3 * j : ty == 4 ? 24 + 2 * j : ty == 5 ? 40 + 2 * j : 2 * j;
          const uint32_t half = (ty < 2 || ty == 3) ? 12288 : 8192;
          const uint32_t bytes = 2 * half + (mode == kModeHead ? 0 : kTileBytes);
          const uint32_t dst = sb + kSmRing + kTileBytes + rank * half;
#pragma unroll 1
          RING_STEP(, mbar_expect_tx(full, bytes); tma3d_mc(dst + off, map, full, c0, kb * 64 + rank * 32, c2));
        } else if (mode == kModeHead) {
          off += ((nend - nb) >> 3) * step;
          nb = nend;
          if (off >= 163840) off -= 163840;
        } else if (sg < 2) {
#pragma unroll 1
          RING_STEP(, tma2d(sb + kSmRing + off, &map_x, full, xcol + kb * 64, xrow));
        } else {
          const uint8_t* src = ty == 6 ? g_h + b * 56 * kTileBytes : (ty == 2 ? g_o : g_x) + b * 16 * kTileBytes;
          const int dep = (e >> 19) & 31;
          if (dep < 28) mbar_wait(sb + kBarReady + dep * 8, 0);
          if ((dep & 30) == 28) {
#pragma unroll 1
            RING_STEP(mbar_wait(sb + kBarSrc + ((kb << (4 - inc)) & 56), dep),
                      bulk_load(sb + kSmRing + off, src + kb * kTileBytes, kTileBytes, full));
          } else {
#pragma unroll 1
            RING_STEP(, bulk_load(sb + kSmRing + off, src + kb * kTileBytes, kTileBytes, full));
          }
        }
      }
#undef RING_STEP
    } else {
      unsigned epoch = 0;
      if (warp == 10) {
        if (lane == 0) epoch = atomicAdd(&g_ticket, 1u) / kGrid + 1;
        *reinterpret_cast<unsigned*>(sm + kSmEpoch) = __shfl_sync(0xffffffffu, epoch, 0);
        asm volatile("barrier.cluster.wait.aligned;" ::: "memory");
        if (elect()) mbar_arrive(sb + kBarEpoch);
      } else {
        asm volatile("barrier.cluster.wait.aligned;" ::: "memory");
        mbar_wait_bounded(sb + kBarFull, 0);
        if (elect()) {
          mbar_expect_tx(sb + kBarInit, 32768);
          tma2d(sb + kSmX, &map_x, sb + kBarInit, xcol + j * 128, xrow);
          tma2d(sb + kSmX + kTileBytes, &map_x, sb + kBarInit, xcol + j * 128 + 64, xrow);
        }
        const uint2 u = reinterpret_cast<const uint2*>(prm.b2)[32 * j + lane];
        reinterpret_cast<float4*>(sm + kSmB2)[lane] = make_float4(
            2.f * kGeluBeta * bf_lo(u.x), 2.f * kGeluBeta * bf_hi(u.x), 2.f * kGeluBeta * bf_lo(u.y), 2.f * kGeluBeta * bf_hi(u.y));
      }
      mbar_wait_bounded(sb + kBarEpoch, 0);
      epoch = *reinterpret_cast<volatile unsigned*>(sm + kSmEpoch);
      if (cta < 96) {
        mbar_wait_bounded(sb + STRIP_GATE, 0);
        colsum_strip(&map_css, sm, sb, (cta >> 5) * kD + 512 + (cta & 31) * 16, warp - 10, lane, epoch);
      }
      gather_colsums_qkv(sm, 11 - warp, j, lane, epoch);
      __syncwarp();
      if (elect()) mbar_arrive(sb + kBarCs + (11 - warp) * 8);
     if (warp == 10) {
#pragma unroll 1
      for (int i = 0; i < kTiles - 1; i++) {
        const bool xt = i == 2 || i == 6 || i == 9;
        const unsigned* line = g_flag + (i * 16 + b) * 32;
        mbar_wait(sb + (xt ? kBarX + (i >> 2) * 16 : kBarEpi + i * 8), 0);
        if ((xt && (FINE & 1)) || ((i == 1 || i == 8) && (FINE & 2))) {
          unsigned todo = 0xff, spins = 0;
          do {
            const unsigned now = __ballot_sync(0xffffffffu, ld_relaxed(line + (lane & 7)) == epoch) & todo;
            if (now) {
              asm volatile("fence.acquire.gpu;\nfence.proxy.async.global;" ::: "memory");
              if ((now >> lane) & 1) mbar_arrive(sb + kBarSrc + lane * 8);
              todo ^= now;
            }
            if (++spins > kSpinLimit) __trap();
          } while (todo);
        } else {
          wait_flags(line + (lane & 7), epoch);
          if (elect()) mbar_arrive(sb + kBarReady + i * 8);
        }
        if (xt) {
          wait_flags(line + 8 + (lane & 7), epoch);
          if (elect()) mbar_arrive(sb + kBarReady + (14 + (i >> 2)) * 8);
        }
      }
     } else {
#pragma unroll 1
      for (int i = 0; i < kTiles - 1; i++) {
        if (i == 3) {
          gather_colsums_w1(sm, prm.b1, j, lane, epoch);
          __syncwarp();
          if (elect()) mbar_arrive(sb + kBarCs + 16);
        }
        const bool xt = i == 2 || i == 6 || i == 9;
#pragma unroll 1
        for (int h = 0; h < (xt ? 2 : 1); h++) {
          mbar_wait_bounded(sb + (xt ? kBarX + (i >> 2) * 16 + 8 * h : kBarEpi + i * 8), 0);
          const int ty = i >= 7 ? i - 7 : i;
          if (ty >= 2 && elect()) {
            uint8_t* dst = xt ? g_x + (b * 16 + 2 * j + h) * kTileBytes
                              : g_h + (b * 56 + 1 + (ty == 3 ? 3 * j : 16 * ty - 40 + 2 * j)) * kTileBytes;
            bulk_store(dst, sb + (xt ? kSmX + h * kTileBytes : kSmStg), kTileBytes);
            bulk_commit();
            bulk_wait();
            if (!xt) mbar_arrive(sb + kBarFree + i * 8);
          }
          if (LATE_REL2 && h == 1) mbar_wait_bounded(sb + kBarFull + 32, i == 2 ? 6 : i == 6 ? 19 : 25);
          __syncwarp();
          if (elect()) st_release(&g_flag[(i * 16 + b) * 32 + h * 8 + j], epoch);
          __syncwarp();
        }
      }
#pragma unroll 1
      for (int h = 0; h < 2; h++) {
        mbar_wait_bounded(sb + kBarX + 48 + 8 * h, 0);
        if (elect()) {
          tma2d_store(&map_out, sb + kSmX + h * kTileBytes, xcol + j * 128 + h * 64, xrow);
          bulk_commit();
          if (h == 1) bulk_wait_read();
        }
      }
     }
    }
    __syncwarp();
    asm volatile("barrier.cluster.arrive.relaxed.aligned;\nbarrier.cluster.wait.aligned;" ::: "memory");
  } else {
    asm volatile("setmaxnreg.inc.sync.aligned.u32 232;");
    asm volatile("barrier.cluster.wait.aligned;" ::: "memory");
    const int wg = warp >> 2, w = warp & 3;
    const bool rel = (threadIdx.x & 95) == 0;
    const uint32_t rel_addr = mapa(sb + kBarEmpty, w & 1);
    if (wg == 1) TRACE_AT(15, 0);
#define EPOCH (*reinterpret_cast<volatile unsigned*>(sm + kSmEpoch))

#pragma unroll 1
    for (int i = wg; i < kTiles; i += 2) {
      const int layer = i >= 7, ty = i - 7 * layer;
      TRACE_AT(i, 15);
      float acc[2][96];
      if (ty == 2 || ty == 6) {
        const int lane = lane_id();
        const uint32_t xa = sb + kSmX + ((lane >> 4) * 8 + (lane & 7)) * 128 + (((2 * w + ((lane >> 3) & 1)) ^ (lane & 7)) << 4);
        const float up = ty == 6 ? 2.f * kGeluBeta : 1.f, dn = ty == 6 ? 0.5f / kGeluBeta : 1.f;
#pragma unroll
        for (int h = 0; h < 2; h++) {
          const float* b2 = reinterpret_cast<const float*>(sm + kSmB2) + 64 * h + 16 * w + (lane >> 2);
          const float bias[2] = {ty == 6 ? b2[0] : 0.f, ty == 6 ? b2[8] : 0.f};
#pragma unroll
          for (int p = 0; p < 8; p++) {
            uint32_t r[4];
            ldsm4_t(xa + h * kTileBytes + p * 2048, r);
#pragma unroll
            for (int m = 0; m < 4; m++) {
              acc[h][8 * p + 2 * m] = fmaf(bf_lo(r[m]), up, bias[m & 1]);
              acc[h][8 * p + 2 * m + 1] = fmaf(bf_hi(r[m]), up, bias[m & 1]);
              asm volatile("" : "+f"(acc[h][8 * p + 2 * m]), "+f"(acc[h][8 * p + 2 * m + 1]));
              if (m & 1) yield_slot();
            }
          }
        }
        auto stage = [&](int qt) {
          const int h = qt >> 1;
#pragma unroll
          for (int p = 4 * (qt & 1); p < 4 * (qt & 1) + 4; p++) {
            const float* a = &acc[h][8 * p];
            stsm4_t(xa + h * kTileBytes + p * 2048, pack2(a[0] * dn, a[1] * dn), pack2(a[2] * dn, a[3] * dn),
                    pack2(a[4] * dn, a[5] * dn), pack2(a[6] * dn, a[7] * dn));
            if (STAGE_YIELD || (p & 3) == 3) yield_slot();
          }
          if (qt & 1) {
            fence_async_smem();
            __syncwarp();
            if (elect()) mbar_arrive(sb + kBarX + (i >> 2) * 16 + 8 * h);
            TRACE_AT(i, 8 + h);
          }
        };
        mainloop<128, true, false>(acc, sb, i, layer * 152 + ty * 16, ty == 6 ? 4 : 0, ty == 6 ? 56 : 16,
                            ty == 2 ? PAUSE_WO : -1, 2 * layer + 1, rel_addr, rel, ty == 2 ? 8 : -1, stage);
        TRACE_AT(i, 2);
        stage(2);
        stage(3);
      } else {
        const int xver = 2 * layer + (ty >= 3);
        const uint32_t stg = sb + kSmStg + w * 4096;
        const float4* vec = reinterpret_cast<const float4*>(sm + kSmV1) + (ty == 3 ? 0 : 64 * ty - 160);
        int lane;
        uint8_t* hdst = g_h + (b * 56 + (ty == 3 ? 3 * j : 16 * ty - 40 + 2 * j)) * kTileBytes + w * 4096;
        float2 st[4];
        unsigned epoch;
        auto pre = [&] {
          lane = lane_id();
          if (ty < 4) mbar_wait(sb + (ty == 1 ? kBarEpi + (i - 1) * 8 : kBarStat + xver * 8), 0);
#pragma unroll
          for (int c = 0; c < 4; c++) st[c] = reinterpret_cast<const float2*>(sm + kSmStat)[32 * w + 8 * c + (lane >> 2)];
          epoch = EPOCH;
        };
        auto team_stats = [&] {
          uint2* stat = g_stat + (xver * 16 + b) * 1024;
          lane = lane_id();
          publish_stats(sb, stat + j * 128, w, lane, EPOCH);
          gather_stats(sm, stat, 32 * w + lane, EPOCH);
          __syncwarp();
          if (elect()) mbar_arrive(sb + kBarStat + xver * 8);
          TRACE_AT(i, 14);
        };
        if (ty < 4) {
          head_blocks<192>(acc, sb, layer * 152 + (ty < 2 ? 2 * ty : 48), ty < 2 ? 2 * ty : 1, xver, rel_addr, rel);
          if (ty == 1) {
            if (i == 1) {
              mbar_wait(sb + kBarEpoch, 0);
              mbar_wait(sb + kBarInit, 0);
            }
            team_stats();
            if (i == 1) mbar_wait(sb + kBarCs + 8, 0);
#pragma unroll
            for (int c = 0; c < 4; c++) st[c] = reinterpret_cast<const float2*>(sm + kSmStat)[32 * w + 8 * c + (lane >> 2)];
            add_mean_term(acc, st, sm, 1, lane);
          }
          mainloop<192, false, false>(acc, sb, i, layer * 152 + (ty < 2 ? 4 + 14 * ty : 52), ty < 2 ? 2 * ty : 1, 14,
                                      ty == 1 ? PAUSE_QKV2 : -1, xver, rel_addr, rel, 0, pre);
          TRACE_AT(i, 2);
          if (ty < 2) {
            if (i == 0) mbar_wait(sb + kBarCs, 0);
            if (ty == 0) add_mean_term(acc, st, sm, 0, lane);
            epilogue_attn(acc, st, sm, sb, layer, ty, b, j, epoch, i, wg, w, lane);
            TRACE_AT(i, 3);
            continue;
          }
          if (i == 3) mbar_wait(sb + kBarCs + 16, 0);
          scale_stats(st);
          fold_norm<16, 24>(acc, st, vec + (lane & 3));
          TRACE_AT(i, 11);
          gelu_chunk<2>(acc, stg, lane, nullptr, [] {});
          TRACE_AT(i, 12);
          fold_norm<0, 2>(acc, st, vec + (lane & 3));
          store_staged(hdst + 2 * kTileBytes, stg);
          fold_norm<2, 16>(acc, st, vec + (lane & 3));
        } else {
          if (ty == 4) {
            head_blocks<128>(acc, sb, layer * 152 + 50, 3, xver, rel_addr, rel);
            team_stats();
            mainloop<128, false, false>(acc, sb, i, layer * 152 + 66, 4, 14, -1, 0, rel_addr, rel, 0, pre);
          } else {
            mainloop<128, false, true>(acc, sb, i, layer * 152 + 80, 3, 16, -1, 0, rel_addr, rel, 0, pre);
          }
          TRACE_AT(i, 2);
          if (i == 4) mbar_wait(sb + kBarCs + 16, 0);
          scale_stats(st);
          fold_norm<0, 16>(acc, st, vec + (lane & 3));
        }
        auto own_store_done = [] {
          if (elect()) bulk_wait();
          __syncwarp();
        };
        TRACE_AT(i, 8);
        gelu_chunk<0>(acc, stg, lane, nullptr, [&] {
          if (ty == 3) own_store_done();
          else mbar_wait(sb + kBarFree + (i - 1) * 8, 0);
        });
        TRACE_AT(i, 9);
        gelu_chunk<1>(acc, stg, lane, hdst, own_store_done);
        TRACE_AT(i, 10);
        fence_async_smem();
        __syncwarp();
        if (elect()) mbar_arrive(sb + kBarEpi + i * 8);
      }
      TRACE_AT(i, 3);
    }
#undef EPOCH
    asm volatile("barrier.cluster.arrive.relaxed.aligned;\nbarrier.cluster.wait.aligned;" ::: "memory");
    if (wg == 1) TRACE_AT(15, 2);
  }
}

void build_segments(uint32_t* seg) {
  int n = 0, fine = 0;
  auto per_source = [&](int kind, int dep) { return (FINE & kind) ? 28 + (fine++ & 1) : dep; };
  auto add = [&](int ty, int cnt, int kb0, int mode, int wide, int depth5, int dep, int reset) {
    seg[n++] = ty | cnt << 3 | kb0 << 9 | mode << 15 | wide << 17 | depth5 << 18 | dep << 19 | reset << 24;
  };
  for (int l = 0; l < 2; l++) {
    const int t = 7 * l;
    if (l == 0) {
      add(0, 14, 2, kModePlain, 1, 0, 31, 1);
      add(1, 14, 2, kModePlain, 1, 0, 31, 0);
    } else {
      add(0, 2, 0, kModeHead, 1, 0, 31, 1);
      add(1, 2, 0, kModeHead, 1, 0, 31, 0);
      add(0, 7, 0, kModeSkip, 1, 0, per_source(1, 6), 0);
      add(0, 7, 1, kModeSkip, 1, 0, 15, 0);
      add(1, 7, 0, kModeSkip, 1, 0, 31, 0);
      add(1, 7, 1, kModeSkip, 1, 0, 31, 0);
    }
    add(2, 4, 0, kModePlain, 0, 0, t, 1);
    add(2, 4, 4, kModePlain, 0, 1, 31, 0);
    add(2, 1, 0, kModeHead, 0, 1, 31, 0);
    add(2, 7, 8, kModeSkip, 0, 1, per_source(2, t + 1), 0);
    add(3, 2, 0, kModeHead, 1, 0, 31, 2);
    add(4, 2, 0, kModeHead, 1, 0, 31, 0);
    add(3, 7, 0, kModeSkip, 1, 0, per_source(1, t + 2), 0);
    add(3, 7, 1, kModeSkip, 1, 0, 14 + 2 * l, 0);
    add(4, 4, 0, kModeSkip, 0, 0, 31, 3);
    add(4, 3, 0, kModeContinue, 0, 1, 31, 0);
    add(4, 7, 1, kModeSkip, 0, 1, 31, 0);
    add(5, 16, 0, kModePlain, 0, 1, 31, 0);
    add(6, 24, 0, kModePlain, 0, 1, t + 3, 0);
    add(6, 16, 24, kModePlain, 0, 1, t + 4, 0);
    add(6, 16, 40, kModePlain, 0, 1, t + 5, 0);
  }
}

typedef CUresult (*EncodeTiledFn)(CUtensorMap*, CUtensorMapDataType, cuuint32_t, void*, const cuuint64_t*,
                                  const cuuint64_t*, const cuuint32_t*, const cuuint32_t*, CUtensorMapInterleave,
                                  CUtensorMapSwizzle, CUtensorMapL2promotion, CUtensorMapFloatOOBfill);

CUtensorMap make_map(EncodeTiledFn enc, const void* p, int rank, const cuuint64_t* dims, const cuuint64_t* strides,
                     const cuuint32_t* box, CUtensorMapSwizzle swizzle = CU_TENSOR_MAP_SWIZZLE_128B) {
  CUtensorMap m;
  const cuuint32_t es[5] = {1, 1, 1, 1, 1};
  enc(&m, CU_TENSOR_MAP_DATA_TYPE_BFLOAT16, rank, const_cast<void*>(p), dims, strides, box, es,
      CU_TENSOR_MAP_INTERLEAVE_NONE, swizzle, CU_TENSOR_MAP_L2_PROMOTION_L2_128B,
      CU_TENSOR_MAP_FLOAT_OOB_FILL_NONE);
  return m;
}

CUtensorMap weight_map(EncodeTiledFn enc, const void* p, int k, int n, int blocks) {
  const cuuint64_t dims[3] = {64, (cuuint64_t)k, (cuuint64_t)n / 64};
  const cuuint64_t strides[2] = {(cuuint64_t)n * 2, 128};
  const cuuint32_t box[3] = {64, 32, (cuuint32_t)blocks};
  return make_map(enc, p, 3, dims, strides, box);
}

CUtensorMap slab_map(EncodeTiledFn enc, const void* p, int n, int cols, int rows) {
  const cuuint64_t dims[2] = {(cuuint64_t)n, kD};
  const cuuint64_t strides[1] = {(cuuint64_t)n * 2};
  const cuuint32_t box[2] = {(cuuint32_t)cols, (cuuint32_t)rows};
  return make_map(enc, p, 2, dims, strides, box, CU_TENSOR_MAP_SWIZZLE_NONE);
}

CUtensorMap token_map(EncodeTiledFn enc, const void* p, int rows) {
  const cuuint64_t dims[2] = {2 * kD, 1024};
  const cuuint64_t strides[1] = {4 * kD};
  const cuuint32_t box[2] = {64, (cuuint32_t)rows};
  return make_map(enc, p, 2, dims, strides, box);
}

}

extern "C" void kernel_launch(void* const* d_in, const int* in_sizes, int n_in, void* d_out, int out_size) {
  (void)in_sizes; (void)n_in; (void)out_size;
  static EncodeTiledFn enc = nullptr;
  if (!enc) {
    void* fn = nullptr;
    cudaDriverEntryPointQueryResult q;
    cudaGetDriverEntryPoint("cuTensorMapEncodeTiled", &fn, cudaEnableDefault, &q);
    enc = (EncodeTiledFn)fn;
    cudaFuncSetAttribute(fused_layers_kernel, cudaFuncAttributeMaxDynamicSharedMemorySize, kSmBytes);
  }
  Params prm;
  prm.b1 = (const __nv_bfloat16*)d_in[5];
  prm.b2 = (const __nv_bfloat16*)d_in[7];
  build_segments(prm.seg);
  const cuuint64_t qd[3] = {kD, kD, 3}, qs[2] = {3 * kD * 2, kD * 2};
  const cuuint32_t qb[3] = {64, 32, 3};
  const CUtensorMap map_x = token_map(enc, d_in[0], 128);
  const CUtensorMap map_out = token_map(enc, d_out, 128);
  const CUtensorMap map_qkv = make_map(enc, d_in[1], 3, qd, qs, qb);
  const CUtensorMap map_wo = weight_map(enc, d_in[2], kD, kD, 2);
  const CUtensorMap map_w1a = weight_map(enc, d_in[4], kD, kF, 3);
  const CUtensorMap map_w1b = weight_map(enc, d_in[4], kD, kF, 2);
  const CUtensorMap map_w2 = weight_map(enc, d_in[6], kF, kD, 2);
  fused_layers_kernel<<<kGrid, 384, kSmBytes>>>(map_x, map_out, map_qkv, map_wo, map_w1a, map_w1b, map_w2,
                                                slab_map(enc, d_in[1], 3 * kD, 128, 128), slab_map(enc, d_in[4], kF, 128, 128),
                                                slab_map(enc, d_in[1], 3 * kD, 16, 128), prm);
}
```

```cpp
#include <cuda.h>
#include <cuda_bf16.h>
#include <cuda_runtime.h>
#include <stdint.h>

namespace {

constexpr int kD = 1024;
constexpr int kF = 3584;
constexpr int kCtas = 128;
constexpr int kGrid = 132;
constexpr int kTiles = 14;
constexpr int kTileBytes = 16384;

constexpr int kSmRing = 0;
constexpr int kSmX = 163840;
constexpr int kSmStg = kSmX + 32768;
constexpr int kSmHalo = kSmStg + 16384;
constexpr int kSmCsQ = kSmHalo + 6144;
constexpr int kSmV1 = kSmCsQ + 384 * 4;
constexpr int kSmB2 = kSmV1 + 448 * 8;
constexpr int kSmStat = kSmB2 + 128 * 4;
constexpr int kSmBar = kSmStat + 128 * 8;
constexpr int kBarFull = kSmBar;
constexpr int kBarTurn = kBarFull + 8 * 8;
constexpr int kBarReady = kBarTurn + 14 * 8;
constexpr int kBarSrc = kBarReady + 17 * 8;
constexpr int kBarPause = kBarSrc + 8 * 8;
constexpr int kBarFree = kBarPause + 4 * 8;
constexpr int kBarCs = kBarFree + 14 * 8;
constexpr int kBarSlab = kBarCs + 3 * 8;
constexpr int kBarInit = kBarSlab + 4 * 8;
constexpr int kBarEpoch = kBarInit + 8;
constexpr int kBarEmpty = kBarTurn + 5 * 128;
constexpr int kBarEpi = kBarEmpty + 128;
constexpr int kBarX = kBarEpi + 14 * 8;
constexpr int kBarStat = kBarX + 8 * 8;
constexpr int kBarResume = kBarStat + 4 * 8;
constexpr int kSmEpoch = kBarEpi + 2 * 128;
static_assert(kBarEpoch < kBarEmpty && kBarResume + 4 * 8 <= kSmEpoch, "barrier groups overflow");
constexpr int kSmBytes = kSmEpoch + 16;
constexpr int kSegs = 38;

constexpr int kFlagLines = kTiles * 16;

constexpr unsigned kSpinLimit = 1u << 22;

__device__ __align__(1024) uint8_t g_x[16 * 16 * kTileBytes];
__device__ __align__(1024) uint8_t g_o[16 * 16 * kTileBytes];
__device__ __align__(1024) uint8_t g_h[16 * 56 * kTileBytes];
__device__ __align__(128) uint2 g_stat[4 * 16 * 128 * 8];
__device__ __align__(128) unsigned g_cs[3 * kD + kF + 3 * kD];
__device__ __align__(128) uint4 g_halo[2 * 16 * 16 * 256];
__device__ __align__(128) unsigned g_flag[kFlagLines * 32];
__device__ unsigned g_ticket;

#define TRACE_AT(tile, k)
#define TRACE_PUB(i, k, c)
#define TRACE_ISSUE(which, nb)

struct Params {
  const __nv_bfloat16* b1;
  const __nv_bfloat16* b2;
  uint32_t seg[kSegs];
};

__device__ __forceinline__ uint32_t smem_u32(const void* p) {
  return (uint32_t)__cvta_generic_to_shared(p);
}
__device__ __forceinline__ uint32_t mapa(uint32_t a, uint32_t cta) {
  uint32_t r;
  asm("mapa.shared::cluster.u32 %0, %1, %2;" : "=r"(r) : "r"(a), "r"(cta));
  return r;
}
__device__ __forceinline__ void mbar_init(uint32_t bar, int cnt) {
  asm volatile("mbarrier.init.shared::cta.b64 [%0], %1;" ::"r"(bar), "r"(cnt) : "memory");
}
__device__ __forceinline__ void mbar_expect_tx(uint32_t bar, uint32_t bytes) {
  asm volatile("mbarrier.arrive.expect_tx.shared::cta.b64 _, [%0], %1;" ::"r"(bar), "r"(bytes) : "memory");
}
__device__ __forceinline__ void mbar_arrive(uint32_t bar) {
  asm volatile("mbarrier.arrive.shared::cta.b64 _, [%0];" ::"r"(bar) : "memory");
}
__device__ __forceinline__ void mbar_arrive_cluster(uint32_t cluster_addr) {
  asm volatile("mbarrier.arrive.shared::cluster.b64 _, [%0];" ::"r"(cluster_addr) : "memory");
}
__device__ __forceinline__ void mbar_wait(uint32_t bar, uint32_t parity) {
  asm volatile("{\n.reg .pred p;\nRETRY:\nmbarrier.try_wait.parity.shared::cta.b64 p, [%0], %1;\n"
               "@!p bra.uni RETRY;\n}" ::"r"(bar), "r"(parity) : "memory");
}
__device__ __forceinline__ void mbar_wait_bounded(uint32_t bar, uint32_t parity) {
  asm volatile("{\n.reg .pred p;\n.reg .u32 c;\nmov.u32 c, 0;\nRETRY:\n"
               "mbarrier.try_wait.parity.shared::cta.b64 p, [%0], %1;\n@p bra.uni DONE;\n"
               "add.u32 c, c, 1;\nsetp.lt.u32 p, c, %2;\n@p bra.uni RETRY;\ntrap;\nDONE:\n}"
               ::"r"(bar), "r"(parity), "n"(1u << 19) : "memory");
}
__device__ __forceinline__ void tma3d(uint32_t dst, const CUtensorMap* m, uint32_t bar, int c0, int c1, int c2) {
  asm volatile(
      "cp.async.bulk.tensor.3d.shared::cluster.global.mbarrier::complete_tx::bytes [%0], [%1, {%3, %4, %5}], [%2];"
      ::"r"(dst), "l"(m), "r"(bar), "r"(c0), "r"(c1), "r"(c2) : "memory");
}
__device__ __forceinline__ void tma3d_mc(uint32_t dst, const CUtensorMap* m, uint32_t bar, int c0, int c1, int c2) {
  asm volatile(
      "cp.async.bulk.tensor.3d.shared::cluster.global.mbarrier::complete_tx::bytes.multicast::cluster"
      " [%0], [%1, {%3, %4, %5}], [%2], %6;"
      ::"r"(dst), "l"(m), "r"(bar), "r"(c0), "r"(c1), "r"(c2), "h"((uint16_t)3) : "memory");
}
__device__ __forceinline__ void tma2d(uint32_t dst, const CUtensorMap* m, uint32_t bar, int c0, int c1) {
  asm volatile(
      "cp.async.bulk.tensor.2d.shared::cluster.global.mbarrier::complete_tx::bytes [%0], [%1, {%3, %4}], [%2];"
      ::"r"(dst), "l"(m), "r"(bar), "r"(c0), "r"(c1) : "memory");
}
__device__ __forceinline__ void tma2d_store(const CUtensorMap* m, uint32_t src, int c0, int c1) {
  asm volatile("cp.async.bulk.tensor.2d.global.shared::cta.bulk_group [%0, {%2, %3}], [%1];"
               ::"l"(m), "r"(src), "r"(c0), "r"(c1) : "memory");
}
__device__ __forceinline__ int lane_id() {
  int l;
  asm volatile("mov.u32 %0, %%laneid;" : "=r"(l));
  return l;
}
__device__ __forceinline__ bool elect() {
  uint32_t p;
  asm volatile("{\n.reg .pred p;\nelect.sync _|p, 0xffffffff;\nselp.b32 %0, 1, 0, p;\n}" : "=r"(p));
  return p;
}
__device__ __forceinline__ void bulk_load(uint32_t dst, const void* src, uint32_t bytes, uint32_t bar) {
  asm volatile("cp.async.bulk.shared::cluster.global.mbarrier::complete_tx::bytes [%0], [%1], %2, [%3];"
               ::"r"(dst), "l"(src), "r"(bytes), "r"(bar) : "memory");
}
__device__ __forceinline__ void bulk_store(void* dst, uint32_t src, uint32_t bytes) {
  asm volatile("cp.async.bulk.global.shared::cta.bulk_group [%0], [%1], %2;" ::"l"(dst), "r"(src), "r"(bytes)
               : "memory");
}
__device__ __forceinline__ void bulk_commit() { asm volatile("cp.async.bulk.commit_group;" ::: "memory"); }
__device__ __forceinline__ void bulk_wait_read() { asm volatile("cp.async.bulk.wait_group.read 0;" ::: "memory"); }
__device__ __forceinline__ void bulk_wait() { asm volatile("cp.async.bulk.wait_group 0;" ::: "memory"); }
__device__ __forceinline__ void fence_async_smem() { asm volatile("fence.proxy.async.shared::cta;" ::: "memory"); }
__device__ __forceinline__ unsigned ld_relaxed(const unsigned* p) {
  unsigned v;
  asm volatile("ld.relaxed.gpu.global.u32 %0, [%1];" : "=r"(v) : "l"(p) : "memory");
  return v;
}
__device__ __forceinline__ uint2 ld_relaxed2(const uint2* p) {
  uint2 v;
  asm volatile("ld.relaxed.gpu.global.v2.u32 {%0, %1}, [%2];" : "=r"(v.x), "=r"(v.y) : "l"(p) : "memory");
  return v;
}
__device__ __forceinline__ void st_relaxed(unsigned* p, unsigned v) {
  asm volatile("st.relaxed.gpu.global.u32 [%0], %1;" ::"l"(p), "r"(v) : "memory");
}
__device__ __forceinline__ void st_release(unsigned* p, unsigned v) {
  asm volatile("st.release.gpu.global.u32 [%0], %1;" ::"l"(p), "r"(v) : "memory");
}
#define ACQ_MODE 1
__device__ __forceinline__ void wait_flags(const unsigned* p, unsigned epoch) {
  unsigned spins = 0;
  while (true) {
    const unsigned v = ld_relaxed(p);
    if (__all_sync(0xffffffffu, v == epoch)) break;
    if (++spins > kSpinLimit) __trap();
  }
  if (ACQ_MODE) asm volatile("fence.acquire.gpu;\nfence.proxy.async.global;" ::: "memory");
  __syncwarp();
}
__device__ __forceinline__ void st_packet(uint4* p, uint32_t d0, uint32_t d1, uint32_t tag) {
  asm volatile("{\n.reg .b128 v;\n.reg .b64 x, y;\nmov.b64 x, {%1, %2};\nmov.b64 y, {%3, %3};\nmov.b128 v, {x, y};\n"
               "st.relaxed.gpu.global.b128 [%0], v;\n}" ::"l"(p), "r"(d0), "r"(d1), "r"(tag) : "memory");
}
__device__ __forceinline__ void ld_packet(const uint4* p, uint32_t& d0, uint32_t& d1, uint32_t& tag) {
  asm volatile("{\n.reg .b128 v;\n.reg .b64 x, y;\n.reg .b32 u;\nld.relaxed.gpu.global.b128 v, [%3];\n"
               "mov.b128 {x, y}, v;\nmov.b64 {%0, %1}, x;\nmov.b64 {%2, u}, y;\n}"
               : "=r"(d0), "=r"(d1), "=r"(tag) : "l"(p) : "memory");
}
__device__ __forceinline__ unsigned tag_value(float v, unsigned epoch) {
  return (__float_as_uint(v) & ~7u) | (epoch & 7u);
}
__device__ __forceinline__ float untag_value(unsigned v) { return __uint_as_float(v & ~7u); }
__device__ __forceinline__ void stsm4(uint32_t a, uint32_t r0, uint32_t r1, uint32_t r2, uint32_t r3) {
  asm volatile("stmatrix.sync.aligned.m8n8.x4.shared.b16 [%0], {%1, %2, %3, %4};" ::"r"(a), "r"(r0), "r"(r1),
               "r"(r2), "r"(r3) : "memory");
}
__device__ __forceinline__ void stsm4_t(uint32_t a, uint32_t r0, uint32_t r1, uint32_t r2, uint32_t r3) {
  asm volatile("stmatrix.sync.aligned.m8n8.x4.trans.shared.b16 [%0], {%1, %2, %3, %4};" ::"r"(a), "r"(r0),
               "r"(r1), "r"(r2), "r"(r3) : "memory");
}
__device__ __forceinline__ uint32_t transpose8(uint32_t a) {
  uint32_t d;
  asm volatile("movmatrix.sync.aligned.m8n8.trans.b16 %0, %1;" : "=r"(d) : "r"(a));
  return d;
}
__device__ __forceinline__ void mma16816(float (&c)[4], uint32_t a0, uint32_t a1, uint32_t a2, uint32_t a3,
                                         uint32_t b0, uint32_t b1) {
  asm volatile("mma.sync.aligned.m16n8k16.row.col.f32.bf16.bf16.f32 {%0, %1, %2, %3}, {%4, %5, %6, %7}, {%8, %9}, "
               "{%0, %1, %2, %3};"
               : "+f"(c[0]), "+f"(c[1]), "+f"(c[2]), "+f"(c[3])
               : "r"(a0), "r"(a1), "r"(a2), "r"(a3), "r"(b0), "r"(b1));
}
__device__ __forceinline__ void mma1688(float (&c)[4], uint32_t a0, uint32_t a1, uint32_t b0) {
  asm volatile("mma.sync.aligned.m16n8k8.row.col.f32.bf16.bf16.f32 {%0, %1, %2, %3}, {%4, %5}, {%6}, {%0, %1, %2, %3};"
               : "+f"(c[0]), "+f"(c[1]), "+f"(c[2]), "+f"(c[3]) : "r"(a0), "r"(a1), "r"(b0));
}
__device__ __forceinline__ float shfl_xor(float v, int m) {
  float r;
  asm volatile("shfl.sync.bfly.b32 %0, %1, %2, 31, 0xffffffff;" : "=f"(r) : "f"(v), "r"(m));
  return r;
}
__device__ __forceinline__ float tanh_fast(float x) {
  float r;
  asm volatile("tanh.approx.f32 %0, %1;" : "=f"(r) : "f"(x));
  return r;
}
__device__ __forceinline__ void ldsm4(uint32_t a, uint32_t (&r)[4]) {
  asm volatile("ldmatrix.sync.aligned.m8n8.x4.shared.b16 {%0, %1, %2, %3}, [%4];"
               : "=r"(r[0]), "=r"(r[1]), "=r"(r[2]), "=r"(r[3]) : "r"(a) : "memory");
}
__device__ __forceinline__ void ldsm4_t(uint32_t a, uint32_t (&r)[4]) {
  asm volatile("ldmatrix.sync.aligned.m8n8.x4.trans.shared.b16 {%0, %1, %2, %3}, [%4];"
               : "=r"(r[0]), "=r"(r[1]), "=r"(r[2]), "=r"(r[3]) : "r"(a) : "memory");
}
__device__ __forceinline__ uint32_t pack2(float lo, float hi) {
  uint32_t r;
  asm volatile("cvt.rn.bf16x2.f32 %0, %1, %2;" : "=r"(r) : "f"(hi), "f"(lo));
  return r;
}
__device__ __forceinline__ float bf_lo(uint32_t r) { return __uint_as_float(r << 16); }
__device__ __forceinline__ float bf_hi(uint32_t r) { return __uint_as_float(r & 0xffff0000u); }
__device__ __forceinline__ float ex2(float x) {
  float r;
  asm("ex2.approx.ftz.f32 %0, %1;" : "=f"(r) : "f"(x));
  return r;
}
__device__ __forceinline__ float rcp(float x) {
  float r;
  asm("rcp.approx.ftz.f32 %0, %1;" : "=f"(r) : "f"(x));
  return r;
}
template <int N>
__device__ __forceinline__ void wg_wait() {
  asm volatile("wgmma.wait_group.sync.aligned %0;" ::"n"(N) : "memory");
}
__device__ __forceinline__ void yield_slot() { asm volatile("pmevent 0;"); }
__device__ __forceinline__ void wg_bar(int wg) { asm volatile("bar.sync %0, 128;" ::"r"(wg + 1) : "memory"); }

template <int N, int KIND>
__device__ __forceinline__ void mma_kblock(float (&acc)[2][96], uint32_t a, uint32_t b);

#define F8(m, d, i) m(d[i]), m(d[i + 1]), m(d[i + 2]), m(d[i + 3]), m(d[i + 4]), m(d[i + 5]), m(d[i + 6]), m(d[i + 7])
#define KSTEP(N, A, B, oa0, oa1, ob, sd)                                                   \
  "add.u32 t, " B ", " #ob ";\nmov.b64 db, {t, hb};\n"                                      \
  "add.u32 t, " A ", " #oa0 ";\nmov.b64 da, {t, ha};\n"                                     \
  "wgmma.mma_async.sync.aligned.m64n" #N "k16.f32.bf16.bf16 {" ACC##N##_0 "}, da, db, " #sd ", 1, 1, 0, 1;\n" \
  "add.u32 t, " A ", " #oa1 ";\nmov.b64 da, {t, ha};\n"                                     \
  "wgmma.mma_async.sync.aligned.m64n" #N "k16.f32.bf16.bf16 {" ACC##N##_1 "}, da, db, " #sd ", 1, 1, 0, 1;\n"

#define MMA_KBLOCK(N, KIND, A, B, ob2, ob3, sd, MID, MODE)                                 \
  template <>                                                                              \
  __device__ __forceinline__ void mma_kblock<N, KIND>(float (&acc)[2][96], uint32_t a, uint32_t b) { \
    asm volatile("{\n.reg .b32 t, ha, hb;\n.reg .b64 da, db;\n"                            \
                 "mov.b32 ha, 0x40000080;\nmov.b32 hb, 0x40000040;\n"                       \
                 "wgmma.fence.sync.aligned;\n"                                             \
                 KSTEP(N, A, B, 0, 64, 0, sd) KSTEP(N, A, B, 2, 66, 128, 1) KSTEP(N, A, B, 4, 68, ob2, 1) \
                 MID KSTEP(N, A, B, 6, 70, ob3, 1) "wgmma.commit_group.sync.aligned;\n}\n"  \
                 : OPS##N(MODE) : "r"(a), "r"(b) : "memory");                              \
  }
#define MMA_KBLOCKS(N, A, B, ob2, ob3)                                                     \
  MMA_KBLOCK(N, 0, A, B, ob2, ob3, 1, "", "+f")                                            \
  MMA_KBLOCK(N, 1, A, B, ob2, ob3, 1, "wgmma.commit_group.sync.aligned;\n", "+f")          \
  MMA_KBLOCK(N, 2, A, B, ob2, ob3, 0, "", "=f")

#define ACC128_0 \
  "%0, %1, %2, %3, %4, %5, %6, %7, %8, %9, %10, %11, %12, %13, %14, %15, " \
  "%16, %17, %18, %19, %20, %21, %22, %23, %24, %25, %26, %27, %28, %29, %30, %31, " \
  "%32, %33, %34, %35, %36, %37, %38, %39, %40, %41, %42, %43, %44, %45, %46, %47, " \
  "%48, %49, %50, %51, %52, %53, %54, %55, %56, %57, %58, %59, %60, %61, %62, %63"
#define ACC128_1 \
  "%64, %65, %66, %67, %68, %69, %70, %71, %72, %73, %74, %75, %76, %77, %78, %79, " \
  "%80, %81, %82, %83, %84, %85, %86, %87, %88, %89, %90, %91, %92, %93, %94, %95, " \
  "%96, %97, %98, %99, %100, %101, %102, %103, %104, %105, %106, %107, %108, %109, %110, %111, " \
  "%112, %113, %114, %115, %116, %117, %118, %119, %120, %121, %122, %123, %124, %125, %126, %127"
#define OPS128(m) \
  F8(m, acc[0], 0), F8(m, acc[0], 8), F8(m, acc[0], 16), F8(m, acc[0], 24), F8(m, acc[0], 32), F8(m, acc[0], 40), F8(m, acc[0], 48), F8(m, acc[0], 56), \
        F8(m, acc[1], 0), F8(m, acc[1], 8), F8(m, acc[1], 16), F8(m, acc[1], 24), F8(m, acc[1], 32), F8(m, acc[1], 40), F8(m, acc[1], 48), F8(m, acc[1], 56)
MMA_KBLOCKS(128, "%128", "%129", 512, 640)

#define ACC192_0 \
  "%0, %1, %2, %3, %4, %5, %6, %7, %8, %9, %10, %11, %12, %13, %14, %15, " \
  "%16, %17, %18, %19, %20, %21, %22, %23, %24, %25, %26, %27, %28, %29, %30, %31, " \
  "%32, %33, %34, %35, %36, %37, %38, %39, %40, %41, %42, %43, %44, %45, %46, %47, " \
  "%48, %49, %50, %51, %52, %53, %54, %55, %56, %57, %58, %59, %60, %61, %62, %63, " \
  "%64, %65, %66, %67, %68, %69, %70, %71, %72, %73, %74, %75, %76, %77, %78, %79, " \
  "%80, %81, %82, %83, %84, %85, %86, %87, %88, %89, %90, %91, %92, %93, %94, %95"
#define ACC192_1 \
  "%96, %97, %98, %99, %100, %101, %102, %103, %104, %105, %106, %107, %108, %109, %110, %111, " \
  "%112, %113, %114, %115, %116, %117, %118, %119, %120, %121, %122, %123, %124, %125, %126, %127, " \
  "%128, %129, %130, %131, %132, %133, %134, %135, %136, %137, %138, %139, %140, %141, %142, %143, " \
  "%144, %145, %146, %147, %148, %149, %150, %151, %152, %153, %154, %155, %156, %157, %158, %159, " \
  "%160, %161, %162, %163, %164, %165, %166, %167, %168, %169, %170, %171, %172, %173, %174, %175, " \
  "%176, %177, %178, %179, %180, %181, %182, %183, %184, %185, %186, %187, %188, %189, %190, %191"
#define OPS192(m) \
  F8(m, acc[0], 0), F8(m, acc[0], 8), F8(m, acc[0], 16), F8(m, acc[0], 24), F8(m, acc[0], 32), F8(m, acc[0], 40), F8(m, acc[0], 48), F8(m, acc[0], 56), F8(m, acc[0], 64), F8(m, acc[0], 72), F8(m, acc[0], 80), F8(m, acc[0], 88), \
        F8(m, acc[1], 0), F8(m, acc[1], 8), F8(m, acc[1], 16), F8(m, acc[1], 24), F8(m, acc[1], 32), F8(m, acc[1], 40), F8(m, acc[1], 48), F8(m, acc[1], 56), F8(m, acc[1], 64), F8(m, acc[1], 72), F8(m, acc[1], 80), F8(m, acc[1], 88)
MMA_KBLOCKS(192, "%192", "%193", 768, 896)

#define HSTEP(oa, ob)                                                                       \
  "add.u32 t, %97, " #ob ";\nmov.b64 db, {t, hb};\nadd.u32 t, %96, " #oa ";\nmov.b64 da, {t, ha};\n" \
  "wgmma.mma_async.sync.aligned.m64n192k16.f32.bf16.bf16 {" ACC192_0 "}, da, db, 1, 1, 1, 0, 1;\n"
__device__ __forceinline__ void mma_half(float (&d)[96], uint32_t a, uint32_t b) {
  asm volatile("{\n.reg .b32 t, ha, hb;\n.reg .b64 da, db;\nmov.b32 ha, 0x40000080;\nmov.b32 hb, 0x40000040;\n"
               "wgmma.fence.sync.aligned;\n" HSTEP(0, 0) HSTEP(2, 128) HSTEP(4, 768) HSTEP(6, 896)
               "wgmma.commit_group.sync.aligned;\n}\n"
               : F8("+f", d, 0), F8("+f", d, 8), F8("+f", d, 16), F8("+f", d, 24), F8("+f", d, 32), F8("+f", d, 40),
                 F8("+f", d, 48), F8("+f", d, 56), F8("+f", d, 64), F8("+f", d, 72), F8("+f", d, 80), F8("+f", d, 88)
               : "r"(a), "r"(b) : "memory");
}

#define TSTEP(REGS, W, X, ow, ox)                                                           \
  "add.u32 t, " X ", " #ox ";\nmov.b64 db, {t, hi};\nadd.u32 t, " W ", " #ow ";\nmov.b64 da, {t, hi};\n" \
  "wgmma.mma_async.sync.aligned.m64n128k16.f32.bf16.bf16 {" REGS "}, da, db, 1, 1, 1, 1, 0;\n"
#define THEAD "{\n.reg .b32 t, hi;\n.reg .b64 da, db;\nmov.b32 hi, 0x40000040;\nwgmma.fence.sync.aligned;\n"
#define TTAIL "wgmma.commit_group.sync.aligned;\n}\n"
__device__ __forceinline__ void mma_kblock_t(float (&acc)[2][96], uint32_t wd, uint32_t xd) {
  asm volatile(THEAD TSTEP(ACC128_0, "%128", "%129", 0, 0) TSTEP(ACC128_1, "%128", "%129", 256, 0)
               TSTEP(ACC128_0, "%128", "%129", 128, 2) TSTEP(ACC128_1, "%128", "%129", 384, 2)
               TSTEP(ACC128_0, "%128", "%129", 512, 4) TSTEP(ACC128_1, "%128", "%129", 768, 4)
               TSTEP(ACC128_0, "%128", "%129", 640, 6) TSTEP(ACC128_1, "%128", "%129", 896, 6) TTAIL
               : OPS128("+f") : "r"(wd), "r"(xd) : "memory");
}
__device__ __forceinline__ void mma_half_t(float (&d)[96], uint32_t wd, uint32_t xd) {
  asm volatile(THEAD TSTEP(ACC128_0, "%64", "%65", 0, 0) TSTEP(ACC128_0, "%64", "%65", 128, 2)
               TSTEP(ACC128_0, "%64", "%65", 512, 4) TSTEP(ACC128_0, "%64", "%65", 640, 6) TTAIL
               : F8("+f", d, 0), F8("+f", d, 8), F8("+f", d, 16), F8("+f", d, 24), F8("+f", d, 32), F8("+f", d, 40),
                 F8("+f", d, 48), F8("+f", d, 56) : "r"(wd), "r"(xd) : "memory");
}

enum { kModePlain = 0, kModeHead = 1, kModeSkip = 2, kModeContinue = 3 };

template <int N>
__device__ __forceinline__ void fence_acc(float (&acc)[2][96]) {
#pragma unroll
  for (int h = 0; h < 2; h++)
#pragma unroll
    for (int i = 0; i < N / 2; i++) asm volatile("" : "+f"(acc[h][i])::"memory");
}

constexpr uint32_t kToB = (kTileBytes >> 4) + ((4096u >> 4) << 16) - (1u << 16);

#define TRACE_KB(nb)

#define HEAD_BOTH 4
template <int N>
__device__ __forceinline__ void head_blocks(float (&acc)[2][96], uint32_t sb, int n0, int slot, int xver,
                                            uint32_t rel_addr, bool rel) {
  const uint32_t ring = (((sb & 0x3FFFF) + kSmRing) >> 4) | (1u << 16);
  const uint32_t xdesc = (((sb & 0x3FFFF) + kSmX) >> 4) | (1u << 16);
  const uint32_t s0 = ring + slot * 2560, s1 = ring + ((slot + 1) & 3) * 2560;
  const uint32_t nb = n0 * 8, xbar = sb + kBarX + (xver - 1) * 16;
  if (xver > 0) {
    mbar_wait(xbar + ((HEAD_BOTH >> xver) & 1) * 8, 0);
    mbar_wait(sb + kBarTurn + (xver == 1 ? 2 : 3 * xver) * 8, 0);
  }
  mbar_wait(sb + kBarFull + (nb & 56), nb >> 6);
  if (n0 == 0) TRACE_AT(0, 1);
  TRACE_KB(nb);
  mma_kblock<N, 2>(acc, xver > 0 ? xdesc : s0, s0 + kToB);
  if (xver > 0) mbar_wait(xbar + 8, 0);
  mbar_wait(sb + kBarFull + (nb & 56) + 8, nb >> 6);
  TRACE_KB(nb + 8);
  mma_kblock<N, 0>(acc, xver > 0 ? xdesc + (kTileBytes >> 4) : s1, s1 + kToB);
  wg_wait<1>();
  if (rel) mbar_arrive_cluster(rel_addr + (nb & 56));
  wg_wait<0>();
  if (rel) mbar_arrive_cluster(rel_addr + (nb & 56) + 8);
  fence_acc<N>(acc);
}

enum { kPlain, kFresh, kResid, kStagger };
template <int N, int KIND, class Pre>
__device__ __forceinline__ void mainloop(float (&acc)[2][96], uint32_t sb, int tile, int n0, int slot, int nkb,
                                         int pause_kk, int att, uint32_t rel_addr, bool rel, int own_kk, Pre pre) {
  constexpr bool RESID = KIND == kResid, FRESH = KIND == kFresh;
  constexpr uint32_t kStep = (N == 192 ? 5 : 4) * 512;
  const uint32_t ring = (((sb & 0x3FFFF) + kSmRing) >> 4) | (1u << 16);
  uint32_t st = ring + slot * kStep;
  uint32_t nb = n0 * 8, prev = 64;
  const uint32_t last = nb + 8 * (nkb - (RESID ? 3 : KIND == kStagger ? 2 : 1)), own = nb + 8 * own_kk;
  const uint32_t stg = (((sb & 0x3FFFF) + kSmStg) >> 4) | (1u << 16);
  uint32_t stop = pause_kk >= 0 ? nb + 8 * pause_kk : last;
  const bool signal = (threadIdx.x & 127) == 64;
  if (!FRESH) fence_acc<N>(acc);
  if (tile > 0) mbar_wait(sb + kBarTurn + (tile - 1) * 8, 0);
  TRACE_AT(tile, 0);
  if constexpr (FRESH) {
    mbar_wait(sb + kBarFull + (nb & 56), nb >> 6);
    TRACE_KB(nb);
    mma_kblock<N, 2>(acc, st, st + kToB);
    prev = nb & 56;
    st += kStep;
    nb += 8;
  }
#pragma unroll 1
  while (true) {
#pragma unroll 1
    do {
      mbar_wait(sb + kBarFull + (nb & 56), nb >> 6);
      TRACE_KB(nb);
      if constexpr (RESID) mma_kblock_t(acc, st + kToB, nb == own ? stg : st);
      else mma_kblock<N, 0>(acc, st, st + kToB);
      wg_wait<1>();
      if (rel) mbar_arrive_cluster(rel_addr + prev);
      prev = nb & 56;
      st += kStep;
      if (st == ring + 10240) st = ring;
      nb += 8;
    } while (nb != stop);
    if (stop == last) break;
    stop = last;
    if (signal) mbar_arrive(sb + kBarPause + att * 8);
    wg_wait<0>();
    if (rel) mbar_arrive_cluster(rel_addr + prev);
    prev = 64;
    mbar_wait(sb + kBarResume + att * 8, 0);
  }
  mbar_wait(sb + kBarFull + (nb & 56), nb >> 6);
  TRACE_KB(nb);
  if constexpr (RESID) {
    const uint32_t z = gridDim.y - 1;
    const uint32_t s2 = st + kStep, s3 = s2 == ring + 8192 ? ring : s2 + kStep;
    mma_half_t(acc[0], st + kToB, st);
    wg_wait<1>();
    if (rel) mbar_arrive_cluster(rel_addr + 32);
    mbar_wait(sb + kBarFull + 48, nb >> 6);
    TRACE_KB(nb + 8);
    mma_half_t(acc[0], s2 + kToB, s2);
    mbar_wait(sb + kBarFull + 56, nb >> 6);
    TRACE_KB(nb + 16);
    mma_half_t(acc[0], s3 + kToB, s3);
    mma_half_t(acc[1], st + kToB + 256, st + z);
    mma_half_t(acc[1], s2 + kToB + 256, s2 + z);
    wg_wait<2>();
#pragma unroll
    for (int i = 0; i < 64; i++) asm volatile("" : "+f"(acc[0][i])::"memory");
    pre(0);
    mma_half_t(acc[1], s3 + kToB + 256, s3 + z);
    wg_wait<2>();
    if (rel) mbar_arrive_cluster(rel_addr + 40);
    pre(1);
    wg_wait<1>();
    if (rel) mbar_arrive_cluster(rel_addr + 48);
    if (signal) mbar_arrive(sb + kBarTurn + tile * 8);
    wg_wait<0>();
    if (rel) mbar_arrive_cluster(rel_addr + 56);
#pragma unroll
    for (int i = 0; i < 64; i++) asm volatile("" : "+f"(acc[1][i])::"memory");
  } else if constexpr (KIND == kStagger) {
    const uint32_t z = gridDim.y - 1, s2 = st + kStep;
    mma_half(acc[1], st + 64, st + kToB);
    wg_wait<1>();
    if (rel) mbar_arrive_cluster(rel_addr + 40);
    mbar_wait(sb + kBarFull + 56, nb >> 6);
    TRACE_KB(nb + 8);
    mma_half(acc[1], s2 + 64, s2 + kToB);
    mma_half(acc[0], st, st + z + kToB);
    pre(0);
    mma_half(acc[0], s2, s2 + z + kToB);
    wg_wait<2>();
#pragma unroll
    for (int i = 0; i < 96; i++) asm volatile("" : "+f"(acc[1][i])::"memory");
    pre(1);
    wg_wait<1>();
    if (rel) mbar_arrive_cluster(rel_addr + 48);
    pre(2);
    if (signal) mbar_arrive(sb + kBarTurn + tile * 8);
    pre(3);
    wg_wait<0>();
    if (rel) mbar_arrive_cluster(rel_addr + 56);
#pragma unroll
    for (int i = 0; i < 96; i++) asm volatile("" : "+f"(acc[0][i])::"memory");
  } else {
    mma_kblock<N, 1>(acc, st, st + kToB);
    wg_wait<2>();
    if (rel) mbar_arrive_cluster(rel_addr + prev);
    pre();
    wg_wait<1>();
    if (signal) mbar_arrive(sb + kBarTurn + tile * 8);
    wg_wait<0>();
    if (rel) mbar_arrive_cluster(rel_addr + (nb & 56));
    fence_acc<N>(acc);
  }
}

__device__ __forceinline__ void publish_stats(uint32_t sb, uint2* stat, int w, int lane, unsigned epoch) {
  const uint32_t row = sb + kSmX + (32 * w + lane) * 128;
  float s[4], q[4];
#pragma unroll
  for (int c = 0; c < 4; c++) s[c] = q[c] = 0.f;
  uint32_t nx[4];
  ldsm4(row + ((lane & 7) << 4), nx);
#pragma unroll 1
  for (int J = 1; J <= 16; J++) {
    const uint32_t r[4] = {nx[0], nx[1], nx[2], nx[3]};
    ldsm4(row + ((J >> 3) & 1) * kTileBytes + (((J ^ lane) & 7) << 4), nx);
#pragma unroll
    for (int c = 0; c < 4; c++) {
      const float lo = bf_lo(r[c]);
      s[c] += lo;
      q[c] = fmaf(lo, lo, q[c]);
      if (c & 1) yield_slot();
    }
#pragma unroll
    for (int c = 0; c < 4; c++) {
      const float hi = bf_hi(r[c]);
      s[c] += hi;
      q[c] = fmaf(hi, hi, q[c]);
      if (c & 1) yield_slot();
    }
  }
  const int t = lane & 3, g = lane >> 2;
#pragma unroll
  for (int c = 0; c < 2; c++) {
    s[c] = (t & 2 ? s[c + 2] : s[c]) + shfl_xor(t & 2 ? s[c] : s[c + 2], 2);
    q[c] = (t & 2 ? q[c + 2] : q[c]) + shfl_xor(t & 2 ? q[c] : q[c + 2], 2);
  }
  const float so = (t & 1 ? s[1] : s[0]) + shfl_xor(t & 1 ? s[0] : s[1], 1);
  const float qo = (t & 1 ? q[1] : q[0]) + shfl_xor(t & 1 ? q[0] : q[1], 1);
  asm volatile("st.relaxed.gpu.global.v2.u32 [%0], {%1, %2};" ::"l"(stat + 32 * w + 8 * t + g),
               "r"(tag_value(so, epoch)), "r"(tag_value(qo, epoch)) : "memory");
}

__device__ __forceinline__ void add_chunk(float (&a)[8], const uint4& v) {
  a[0] += bf_lo(v.x); a[1] += bf_hi(v.x);
  a[2] += bf_lo(v.y); a[3] += bf_hi(v.y);
  a[4] += bf_lo(v.z); a[5] += bf_hi(v.z);
  a[6] += bf_lo(v.w); a[7] += bf_hi(v.w);
}

__device__ __forceinline__ int helper_col(int id, int slab) {
  return (slab < 3 ? slab * kD : (slab - 3) * 512) + id * 128;
}
__device__ __forceinline__ void helper_cta(const CUtensorMap* map_q, const CUtensorMap* map_1, uint8_t* sm,
                                           uint32_t sb, int id, int warp) {
  constexpr int kRed = 6 * 32768, kBar = kRed + 2 * 4096;
  const int tid = threadIdx.x;
  if (warp == 8 && elect()) {
#pragma unroll
    for (int s = 0; s < 6; s++) {
      mbar_init(sb + kBar + s * 8, 1);
      mbar_init(sb + kBar + 64 + s * 8, 4);
    }
    fence_async_smem();
#pragma unroll
    for (int s = 0; s < 6; s++) {
      mbar_expect_tx(sb + kBar + s * 8, 32768);
      tma2d(sb + s * 32768, map_q, sb + kBar + s * 8, id * 128, s * 128);
    }
  }
  __syncthreads();
  if (warp == 8) {
    int slot = 0, ph = 0;
#pragma unroll 1
    for (int n = 6; n < 80; n++) {
      mbar_wait(sb + kBar + 64 + slot * 8, ph);
      if (elect()) {
        mbar_expect_tx(sb + kBar + slot * 8, 32768);
        tma2d(sb + slot * 32768, n < 24 ? map_q : map_1, sb + kBar + slot * 8, helper_col(id, n >> 3), (n & 7) * 128);
      }
      if (++slot == 6) slot = 0, ph ^= 1;
    }
  } else if (warp < 8) {
    if (tid == 0) *reinterpret_cast<unsigned*>(sm + kBar + 128) = atomicAdd(&g_ticket, 1u) / kGrid + 1;
    int slot = warp >> 2, ph = 0;
#pragma unroll 1
    for (int slab = 0; slab < 10; slab++) {
      float a[8];
#pragma unroll
      for (int e = 0; e < 8; e++) a[e] = 0.f;
#pragma unroll 1
      for (int box = 0; box < 4; box++) {
        mbar_wait_bounded(sb + kBar + slot * 8, ph);
        const uint4* p = reinterpret_cast<const uint4*>(sm + slot * 32768) + (tid & 127);
        uint4 v[16];
#pragma unroll
        for (int i = 0; i < 16; i++) v[i] = p[i * 128];
        __syncwarp();
        if (elect()) mbar_arrive(sb + kBar + 64 + slot * 8);
#pragma unroll
        for (int i = 0; i < 16; i++) add_chunk(a, v[i]);
        slot += 2;
        if (slot >= 6) slot -= 6, ph ^= 1;
      }
      float* red = reinterpret_cast<float*>(sm + kRed + (slab & 1) * 4096);
#pragma unroll
      for (int e = 0; e < 8; e++) a[e] += shfl_xor(a[e], 16);
      if ((tid & 16) == 0) {
        float4* d = reinterpret_cast<float4*>(red + warp * 128 + (tid & 15) * 8);
        d[0] = make_float4(a[0], a[1], a[2], a[3]);
        d[1] = make_float4(a[4], a[5], a[6], a[7]);
      }
      asm volatile("bar.sync 1, 256;" ::: "memory");
      if (warp < 4) {
        float t = 0.f;
#pragma unroll
        for (int q = 0; q < 8; q++) t += red[q * 128 + tid];
        st_relaxed(g_cs + (slab < 3 ? 0 : 3 * kD) + helper_col(id, slab) + tid,
                   tag_value(t, *reinterpret_cast<volatile unsigned*>(sm + kBar + 128)));
      }
    }
  }
}

__device__ __forceinline__ void colsum_strip(const CUtensorMap* map, uint8_t* sm, uint32_t sb, int col, int half,
                                             int lane, unsigned epoch) {
  const uint32_t bar = sb + kBarSlab + half * 16;
  const int buf = kSmStg + half * 8192;
  float a[8];
#pragma unroll
  for (int e = 0; e < 8; e++) a[e] = 0.f;
#pragma unroll 1
  for (int r = -2; r < 4; r++) {
    if (r >= 0) {
      mbar_wait(bar + (r & 1) * 8, r >> 1);
      const uint4* p = reinterpret_cast<const uint4*>(sm + buf + (r & 1) * 4096) + lane;
#pragma unroll 1
      for (int q = 0; q < 8; q += 4) {
        uint4 v[4];
#pragma unroll
        for (int u = 0; u < 4; u++) v[u] = p[(q + u) * 32];
#pragma unroll
        for (int u = 0; u < 4; u++) {
          a[0] += bf_lo(v[u].x); a[1] += bf_hi(v[u].x); a[2] += bf_lo(v[u].y); a[3] += bf_hi(v[u].y);
          yield_slot();
          a[4] += bf_lo(v[u].z); a[5] += bf_hi(v[u].z); a[6] += bf_lo(v[u].w); a[7] += bf_hi(v[u].w);
          yield_slot();
        }
      }
      fence_async_smem();
      __syncwarp();
    }
    if (r < 2 && elect()) {
      mbar_expect_tx(bar + (r & 1) * 8, 4096);
      tma2d(sb + buf + (r & 1) * 4096, map, bar + (r & 1) * 8, col, half * 512 + (r + 2) * 128);
    }
  }
#pragma unroll
  for (int e = 0; e < 4; e++) a[e] = (lane & 16 ? a[e + 4] : a[e]) + shfl_xor(lane & 16 ? a[e] : a[e + 4], 16);
#pragma unroll
  for (int e = 0; e < 2; e++) a[e] = (lane & 8 ? a[e + 2] : a[e]) + shfl_xor(lane & 8 ? a[e] : a[e + 2], 8);
  a[0] = (lane & 4 ? a[1] : a[0]) + shfl_xor(lane & 4 ? a[0] : a[1], 4);
  a[0] += shfl_xor(a[0], 2);
  if (!(lane & 2)) st_relaxed(g_cs + half * (3 * kD + kF) + col + (lane & 1) * 8 + (lane >> 2), tag_value(a[0], epoch));
}

constexpr float kGeluBeta = 0.3292034911525734f;
constexpr float kGeluK = 2.423681954311584f;

__device__ __forceinline__ void store_staged(uint8_t* dst, uint32_t stg) {
  fence_async_smem();
  __syncwarp();
  if (elect()) {
    bulk_store(dst, stg, 4096);
    bulk_commit();
  }
}

#define GY_MASK 5
#define GD 2
#define GF_MASK 3
#define GY(k) if ((GY_MASK >> k) & 1) yield_slot()
template <int J0, int J1>
__device__ __forceinline__ void fold_norm(float (&acc)[2][96], const float2 (&st)[4], const float4* vec) {
  float4 vn = vec[J0 * 4];
#pragma unroll
  for (int J = J0; J < J1; J++) {
    const float4 v = vn;
    if (J + 1 < J1) vn = vec[J * 4 + 4];
#pragma unroll
    for (int c = 0; c < 4; c++) {
      float& a0 = acc[c & 1][4 * J + (c & 2)];
      float& a1 = acc[c & 1][4 * J + (c & 2) + 1];
      a0 = fmaf(a0, st[c].x, fmaf(st[c].y, v.x, v.z));
      a1 = fmaf(a1, st[c].x, fmaf(st[c].y, v.y, v.w));
      asm volatile("" : "+f"(a0), "+f"(a1));
      if ((c & 1) && ((GF_MASK >> (c >> 1)) & 1)) yield_slot();
    }
  }
}

template <int CH, class Acquire>
__device__ __forceinline__ void gelu_chunk(const float (&acc)[2][96], uint32_t stg, int lane, uint8_t* prev,
                                           Acquire acquire) {
  uint32_t pk[8][4];
  float z[GD + 1][4];
  const uint32_t row = (stg + lane * 128) ^ ((lane & 7) << 4);
#define U(s, e) acc[(e) >> 1][4 * (CH * 8 + ((s) >> 1)) + 2 * ((s) & 1) + ((e) & 1)]
#pragma unroll
  for (int s = 0; s < 16 + GD; s++) {
    const int cur = s % (GD + 1), p1 = (s + GD) % (GD + 1), p2 = (s + 1) % (GD + 1), q = s - GD, jj = 2 * q - 24;
    const bool mid = s >= 1 && s < 17;
    if (mid) z[p1][0] = tanh_fast(z[p1][0]);
    if (s < 16) {
#pragma unroll
      for (int e = 0; e < 4; e++) {
        z[cur][e] = fmaf(U(s, e), U(s, e), kGeluK);
        asm volatile("" : "+f"(z[cur][e]));
      }
    }
    if (jj >= 0) stsm4(row ^ (jj << 4), pk[jj][0], pk[jj][1], pk[jj][2], pk[jj][3]);
    GY(0);
    if (mid) z[p1][1] = tanh_fast(z[p1][1]);
    if (q >= 0) {
      pk[q >> 1][2 * (q & 1)] = pack2(fmaf(U(q, 0), z[p2][0], U(q, 0)), fmaf(U(q, 1), z[p2][1], U(q, 1)));
      pk[q >> 1][2 * (q & 1) + 1] = pack2(fmaf(U(q, 2), z[p2][2], U(q, 2)), fmaf(U(q, 3), z[p2][3], U(q, 3)));
    }
    GY(1);
    if (mid) z[p1][2] = tanh_fast(z[p1][2]);
    if (s < 16) {
#pragma unroll
      for (int e = 0; e < 4; e++) {
        z[cur][e] *= U(s, e);
        asm volatile("" : "+f"(z[cur][e]));
      }
    }
    if (mid) z[p1][3] = tanh_fast(z[p1][3]);
    if (jj >= 0) stsm4(row ^ ((jj + 1) << 4), pk[jj + 1][0], pk[jj + 1][1], pk[jj + 1][2], pk[jj + 1][3]);
    GY(2);
    if (CH == 1 && s == 1) store_staged(prev, stg);
    if (q == 11) acquire();
  }
#undef U
}

__device__ __forceinline__ void scale_stats(float2 (&st)[4]) {
#pragma unroll
  for (int c = 0; c < 4; c++) {
    st[c].x *= kGeluBeta;
    st[c].y *= st[c].x;
  }
}

__device__ __forceinline__ void add_mean_term(float (&acc)[2][96], const float2 (&st)[4], uint8_t* sm, int tq,
                                              int lane) {
  const float2* cs = reinterpret_cast<const float2*>(sm + kSmCsQ) + tq * 96 + (lane & 3);
  float2 vn = cs[0];
#pragma unroll
  for (int J = 0; J < 24; J++) {
    const float2 v = vn;
    if (J < 23) vn = cs[J * 4 + 4];
#pragma unroll
    for (int c = 0; c < 4; c++) {
      acc[c & 1][4 * J + (c & 2)] = fmaf(st[c].y, v.x, acc[c & 1][4 * J + (c & 2)]);
      acc[c & 1][4 * J + (c & 2) + 1] = fmaf(st[c].y, v.y, acc[c & 1][4 * J + (c & 2) + 1]);
    }
    yield_slot();
  }
}

#define CV_MASK 1
#define HALO_AT 6
struct AttnRegs {
  uint32_t q[4][8], k[5][8], vt[5][8];
};
#define SCALED(c, J) pack2(acc[(c) & 1][4 * (J) + ((c) & 2)] * st[c].x, acc[(c) & 1][4 * (J) + ((c) & 2) + 1] * st[c].x)
__device__ __forceinline__ void convert_group(const float (&acc)[2][96], const float2 (&st)[4], AttnRegs& r, int c,
                                              int part) {
#pragma unroll
  for (int J = 0; J < 8; J++) {
    if (part == 0) r.q[c][J] = SCALED(c, J);
    if (part == 1) r.k[c + 1][J] = SCALED(c, 8 + J);
    if (part == 2) r.vt[c + 1][J] = transpose8(SCALED(c, 16 + J));
    if ((J & CV_MASK) == CV_MASK) yield_slot();
  }
}
#undef SCALED

__device__ __forceinline__ void convert_odd(const float (&acc)[2][96], const float2 (&st)[4], AttnRegs& r, int step,
                                            uint8_t* sm, uint4* halo_out, bool send, unsigned epoch, int w, int lane) {
  if (step == 1) {
    convert_group(acc, st, r, 3, 2);
    convert_group(acc, st, r, 3, 1);
    if (w < 3) {
      uint2* hs = reinterpret_cast<uint2*>(sm + kSmHalo + w * 2048) + lane;
#pragma unroll
      for (int i = 0; i < 4; i++) {
        hs[i * 32] = make_uint2(r.k[4][2 * i], r.k[4][2 * i + 1]);
        hs[128 + i * 32] = make_uint2(r.vt[4][2 * i], r.vt[4][2 * i + 1]);
      }
    } else if (send) {
#pragma unroll
      for (int i = 0; i < 4; i++) {
        st_packet(halo_out + lane + i * 32, r.k[4][2 * i], r.k[4][2 * i + 1], epoch);
        st_packet(halo_out + lane + 128 + i * 32, r.vt[4][2 * i], r.vt[4][2 * i + 1], epoch);
      }
    }
  } else if (step == 2) {
    convert_group(acc, st, r, 1, 2);
  } else {
    convert_group(acc, st, r, 1, 1);
    convert_group(acc, st, r, 3, 0);
    convert_group(acc, st, r, 1, 0);
  }
}

__device__ __forceinline__ void epilogue_attn(const float (&acc)[2][96], const float2 (&st)[4], AttnRegs& r,
                                              uint8_t* sm, uint32_t sb, int layer, int tq, int b, int j,
                                              unsigned epoch, int tile, int wg, int w, int lane) {
  const int t = lane & 3, g = lane >> 2;
  const int hp = j + 8 * tq, att = 2 * layer + tq;
  auto& q = r.q;
  auto& k = r.k;
  auto& vt = r.vt;
  const bool first = w == 0 && (b & 7) == 0;
  const uint4* gh = g_halo + ((layer * 16 + b - 1) * 16 + hp) * 256 + lane;
  uint32_t tag[8];
#define LOAD_HALO()                                                                                    \
  _Pragma("unroll") for (int i = 0; i < 4; i++) {                                                      \
    ld_packet(gh + i * 32, k[0][2 * i], k[0][2 * i + 1], tag[i]);                                      \
    ld_packet(gh + 128 + i * 32, vt[0][2 * i], vt[0][2 * i + 1], tag[4 + i]);                          \
  }
#define AWAIT_HALO()                                                                                   \
  for (unsigned spins = 0;; spins++) {                                                                 \
    const unsigned d0 = (tag[0] ^ epoch) | (tag[1] ^ epoch) | (tag[2] ^ epoch) | (tag[3] ^ epoch);     \
    const unsigned d1 = (tag[4] ^ epoch) | (tag[5] ^ epoch) | (tag[6] ^ epoch) | (tag[7] ^ epoch);     \
    if (__all_sync(0xffffffffu, (d0 | d1) == 0)) break;                                                \
    if (spins > kSpinLimit) __trap();                                                                  \
    LOAD_HALO();                                                                                       \
  }
#pragma unroll
  for (int c = 0; c <= 6; c++) {
    if (c == HALO_AT) {
      if (w == 0 && !first) {
        LOAD_HALO();
      } else {
#pragma unroll
        for (int i = 0; i < 8; i++) k[0][i] = vt[0][i] = tag[i] = 0u;
      }
    }
    if (c < 6) convert_group(acc, st, r, 2 * (c & 1), 2 - (c >> 1));
  }
  TRACE_AT(tile, 8);
  wg_bar(wg);
  if (w > 0) {
    const uint2* hs = reinterpret_cast<const uint2*>(sm + kSmHalo + (w - 1) * 2048) + lane;
#pragma unroll
    for (int i = 0; i < 4; i++) {
      const uint2 a = hs[i * 32], c = hs[128 + i * 32];
      k[0][2 * i] = a.x; k[0][2 * i + 1] = a.y;
      vt[0][2 * i] = c.x; vt[0][2 * i + 1] = c.y;
    }
  } else if (!first) {
    AWAIT_HALO();
  }
  constexpr float kScale = 0.17677669529663687f * 1.4426950408889634f;
  const bool own0 = 2 * t <= g, own1 = 2 * t + 1 <= g;
  const uint32_t own_mask = (own0 ? 0xffffu : 0u) | (own1 ? 0xffff0000u : 0u);
  const uint32_t stg = sb + kSmStg + w * 4096;
  const uint32_t orow = stg + (lane & 7) * 128, ochunk = (lane >> 3) ^ (lane & 7);
  TRACE_AT(tile, 9);
  mbar_wait(sb + kBarPause + att * 8, 0);
  TRACE_AT(tile, 10);

  float s[2][6][4], o[2][4][2][4];
  auto scores = [&](int hd, int m) {
    const int ca = 2 * (m / 3), kg = ca + m % 3;
#pragma unroll
    for (int e = 0; e < 4; e++) s[hd][m][e] = 0.f;
#pragma unroll
    for (int J = 4 * hd; J < 4 * hd + 4; J += 2)
      mma16816(s[hd][m], q[ca][J], q[ca + 1][J], q[ca][J + 1], q[ca + 1][J + 1], k[kg][J], k[kg][J + 1]);
  };
  auto attend = [&](int c0, int c1) {
    float v0[2][4], v1[2][4], m[2][4];
#define UNITS _Pragma("unroll") for (int hd = 0; hd < 2; hd++) _Pragma("unroll") for (int c = c0; c < c1; c++)
    UNITS {
      const int mp = 3 * (c >> 1) + (c & 1), r = 2 * (c & 1);
      float p0 = s[hd][mp][r], p1 = s[hd][mp][r + 1];
      if (c == 0 && first) p0 = p1 = -INFINITY;
      v0[hd][c] = own0 ? s[hd][mp + 1][r] : p0;
      v1[hd][c] = own1 ? s[hd][mp + 1][r + 1] : p1;
      m[hd][c] = fmaxf(v0[hd][c], v1[hd][c]);
    }
    UNITS m[hd][c] = fmaxf(m[hd][c], shfl_xor(m[hd][c], 1));
    UNITS m[hd][c] = fmaxf(m[hd][c], shfl_xor(m[hd][c], 2));
    UNITS {
      const float nm = -m[hd][c] * kScale;
      v0[hd][c] = ex2(fmaf(v0[hd][c], kScale, nm));
      v1[hd][c] = ex2(fmaf(v1[hd][c], kScale, nm));
      m[hd][c] = v0[hd][c] + v1[hd][c];
    }
    UNITS m[hd][c] += shfl_xor(m[hd][c], 1);
    UNITS m[hd][c] += shfl_xor(m[hd][c], 2);
    UNITS {
      const float inv = rcp(m[hd][c]);
      const uint32_t p = pack2(v0[hd][c] * inv, v1[hd][c] * inv);
#pragma unroll
      for (int ds = 0; ds < 2; ds++) {
        const int J = 4 * hd + 2 * ds;
#pragma unroll
        for (int e = 0; e < 4; e++) o[hd][c][ds][e] = 0.f;
        if (c & 1) {
          mma16816(o[hd][c][ds], vt[c][J], vt[c][J + 1], vt[c + 1][J], vt[c + 1][J + 1], p & ~own_mask, p & own_mask);
        } else {
          mma1688(o[hd][c][ds], vt[c + 1][J], vt[c + 1][J + 1], p & own_mask);
          mma1688(o[hd][c][ds], vt[c][J], vt[c][J + 1], p & ~own_mask);
        }
      }
    }
  };
  auto stage = [&](int c0, int c1) {
    UNITS stsm4_t(orow + c * 1024 + ((ochunk ^ (4 * hd)) << 4), pack2(o[hd][c][0][0], o[hd][c][0][1]),
                  pack2(o[hd][c][0][2], o[hd][c][0][3]), pack2(o[hd][c][1][0], o[hd][c][1][1]),
                  pack2(o[hd][c][1][2], o[hd][c][1][3]));
#undef UNITS
  };
#pragma unroll
  for (int hd = 0; hd < 2; hd++)
#pragma unroll
    for (int m = 0; m < 6; m++) scores(hd, m);
  attend(0, 4);
  yield_slot();
  if (tq == 0 && elect()) mbar_arrive(sb + kBarResume + att * 8);
  TRACE_AT(tile, 11);
  stage(0, 4);
#undef AWAIT_HALO
#undef LOAD_HALO
  fence_async_smem();
  __syncwarp();
  TRACE_AT(tile, 12);
  if (elect()) {
    bulk_store(g_o + (b * 16 + hp) * kTileBytes + w * 4096, stg, 4096);
    bulk_commit();
    if (tq == 1) mbar_arrive(sb + kBarResume + att * 8);
    bulk_wait();
    TRACE_AT(tile, 13);
    mbar_arrive(sb + kBarEpi + tile * 8);
  }
  __syncwarp();
}

__device__ __forceinline__ void gather_stats(uint8_t* sm, const uint2* stat, int r, unsigned epoch) {
  uint2 a[8];
#pragma unroll 1
  for (unsigned spins = 0;; spins++) {
    unsigned diff = 0;
#pragma unroll
    for (int i = 0; i < 8; i++) {
      a[i] = ld_relaxed2(stat + i * 128 + r);
      diff |= (a[i].x ^ epoch) | (a[i].y ^ epoch);
    }
    if (__all_sync(0xffffffffu, (diff & 7u) == 0)) break;
    if (spins > kSpinLimit) __trap();
  }
  float s = 0.f, q = 0.f;
#pragma unroll
  for (int i = 0; i < 8; i++) {
    s += untag_value(a[i].x);
    q += untag_value(a[i].y);
  }
  const float mean = s * (1.f / 1024.f);
  const float var = fmaxf(fmaf(-mean, mean, q * (1.f / 1024.f)), 0.f);
  reinterpret_cast<float2*>(sm + kSmStat)[r] = make_float2(rsqrtf(var + 1e-5f), -mean);
}

__device__ __forceinline__ void gather_colsums_qkv(uint8_t* sm, int tq, int j, int lane, unsigned epoch) {
  const uint2* src = reinterpret_cast<const uint2*>(g_cs + (j + 8 * tq) * 64) + lane;
  uint2 v[3], u[3];
  for (unsigned spins = 0;; spins++) {
    unsigned diff = 0;
#pragma unroll
    for (int q = 0; q < 3; q++) {
      v[q] = ld_relaxed2(src + q * (kD / 2));
      u[q] = make_uint2(epoch & 7u, epoch & 7u);
      if (tq) u[q] = ld_relaxed2(src + (q * kD + 3 * kD + kF) / 2);
    }
#pragma unroll
    for (int q = 0; q < 3; q++) diff |= (v[q].x ^ epoch) | (v[q].y ^ epoch) | (u[q].x ^ epoch) | (u[q].y ^ epoch);
    if (__all_sync(0xffffffffu, (diff & 7u) == 0)) break;
    if (spins > kSpinLimit) __trap();
  }
#pragma unroll
  for (int q = 0; q < 3; q++)
    reinterpret_cast<float2*>(sm + kSmCsQ)[tq * 96 + q * 32 + lane] =
        make_float2(untag_value(v[q].x) + untag_value(u[q].x), untag_value(v[q].y) + untag_value(u[q].y));
}

__device__ __forceinline__ void gather_colsums_w1(uint8_t* sm, const __nv_bfloat16* b1, int j, int lane,
                                                  unsigned epoch) {
#pragma unroll 1
  for (int blk = 0; blk < 7; blk++) {
    const int pair = 32 * (blk + (blk < 3 ? 3 * j : blk < 5 ? 21 + 2 * j : 35 + 2 * j)) + lane;
    const uint32_t bias = reinterpret_cast<const uint32_t*>(b1)[pair];
    uint2 v;
    for (unsigned spins = 0;; spins++) {
      v = ld_relaxed2(reinterpret_cast<const uint2*>(g_cs + 3 * kD) + pair);
      if (__all_sync(0xffffffffu, (((v.x ^ epoch) | (v.y ^ epoch)) & 7u) == 0)) break;
      if (spins > kSpinLimit) __trap();
    }
    reinterpret_cast<float4*>(sm + kSmV1)[blk * 32 + lane] =
        make_float4(untag_value(v.x), untag_value(v.y), kGeluBeta * bf_lo(bias), kGeluBeta * bf_hi(bias));
  }
}

#define FINE 3
#define LATE_REL2 1
#define STRIP_GATE kBarInit
#define XI_MASK 1
#define STAGE_YIELD 1
#define PAUSE_QKV2 7
#define PAUSE_WO 2

__global__ void __cluster_dims__(2, 1, 1) __launch_bounds__(384, 1)
fused_layers_kernel(const __grid_constant__ CUtensorMap map_x, const __grid_constant__ CUtensorMap map_out,
                    const __grid_constant__ CUtensorMap map_qkv, const __grid_constant__ CUtensorMap map_wo,
                    const __grid_constant__ CUtensorMap map_w1a, const __grid_constant__ CUtensorMap map_w1b,
                    const __grid_constant__ CUtensorMap map_w2, const __grid_constant__ CUtensorMap map_csq,
                    const __grid_constant__ CUtensorMap map_cs1, const __grid_constant__ CUtensorMap map_css,
                    const __grid_constant__ Params prm) {
  extern __shared__ __align__(1024) uint8_t sm[];
  if (threadIdx.x < 128 && blockIdx.x < kCtas) TRACE_AT(15, 1);
  const uint32_t sb = __shfl_sync(0xffffffffu, smem_u32(sm), 0);
  const int warp = __shfl_sync(0xffffffffu, threadIdx.x >> 5, 0), lane = threadIdx.x & 31;
  const int cta = blockIdx.x, rank = cta & 1, cl = cta >> 1;
  const int grp = cl < 4 ? 0 : cl < 36 ? (cl - 4) & 7 : 1 + (cl - 36) % 7;
  const int j = cl < 4 ? 4 + cl : cl < 36 ? (cl - 4) >> 3 : 4 + (cl - 36) / 7;
  const int b = 2 * grp + rank;
  const int xcol = (b >> 3) * kD, xrow = (b & 7) * 128;

  if (cta >= kCtas) {
    helper_cta(&map_csq, &map_cs1, sm, sb, cta - kCtas, warp);
    return;
  }
  if ((warp < 8 || warp == 9) && elect()) {
    if (warp == 9) {
#pragma unroll
      for (int s = 0; s < 8; s++) mbar_init(sb + kBarFull + s * 8, 1);
      fence_async_smem();
#pragma unroll
      for (int s = 0; s < 4; s++) {
        const uint32_t full = sb + kBarFull + s * 8, dst = sb + kSmRing + s * 40960;
        mbar_expect_tx(full, 40960);
        tma2d(dst, &map_x, full, xcol + (s & 1) * 64, xrow);
        tma3d(dst + kTileBytes, &map_qkv, full, (j + 4 * (s & 2)) * 64, (s & 1) * 64, 0);
        tma3d(dst + kTileBytes + 12288, &map_qkv, full, (j + 4 * (s & 2)) * 64, (s & 1) * 64 + 32, 0);
      }
    } else {
      if (sb & 1023) __trap();
#pragma unroll
      for (int s = 0; s < 16; s++) mbar_init(sb + kBarTurn + warp * 128 + s * 8, warp < 5 ? 1 : warp == 5 ? 2 : 4);
    }
    asm volatile("fence.mbarrier_init.release.cluster;" ::: "memory");
  }
  __syncwarp();
  asm volatile("barrier.cluster.arrive.relaxed.aligned;" ::: "memory");

  if (warp >= 8) {
    asm volatile("setmaxnreg.dec.sync.aligned.u32 40;");
    if (warp < 10) {
      asm volatile("barrier.cluster.wait.aligned;" ::: "memory");
      uint32_t nb = 32, off = 0, kb = 0;
#define RING_STEP(WAIT, ISSUE)                                            \
  do {                                                                    \
    const uint32_t mb = nb - depth, full = sb + kBarFull + (nb & 56);     \
    if (kb == skip) kb += inc;                                            \
    mbar_wait(sb + kBarEmpty + (mb & 56), mb >> 6);                       \
    WAIT;                                                                 \
    if (elect()) { ISSUE; }                                               \
    TRACE_ISSUE(9 - warp, nb);                                            \
    kb += inc;                                                            \
    off = off == wrap ? 0 : off + step;                                   \
    nb += 8;                                                              \
  } while (nb != nend)
#pragma unroll 1
      for (int sg = 0; sg < kSegs; sg++) {
        const uint32_t e = prm.seg[sg];
        const int ty = e & 7, mode = (e >> 15) & 3, reset = (e >> 24) & 3;
        const uint32_t nend = nb + (e & 0x1f8);
        const uint32_t step = (e >> 17) & 1 ? 40960 : 32768, wrap = 163840 - step;
        const uint32_t depth = (e >> 18) & 1 ? 40 : 32;
        if (reset) off = reset == 1 ? 0 : reset == 2 ? 40960 : 131072;
        const uint32_t own = ty == 2 ? 8 + j : 2 * j;
        if (mode != kModeContinue) kb = mode == kModeHead ? own : (e >> 9) & 63;
        const uint32_t inc = mode >= kModeSkip && ty != 2 ? 2 : 1, skip = mode >= kModeSkip ? own + (kb & 1) : 255;
        if (warp == 8) {
          const CUtensorMap* map = ty < 2 ? &map_qkv : ty == 2 ? &map_wo : ty == 3 ? &map_w1a : ty < 6 ? &map_w1b : &map_w2;
          const int c0 = ty < 2 ? (j + 8 * ty) * 64 : 0;
          const int c2 = ty < 2 ? 0 : ty == 3 ? 3 * j : ty == 4 ? 24 + 2 * j : ty == 5 ? 40 + 2 * j : 2 * j;
          const uint32_t half = (ty < 2 || ty == 3) ? 12288 : 8192;
          const uint32_t bytes = 2 * half + (mode == kModeHead ? 0 : kTileBytes);
          const uint32_t dst = sb + kSmRing + kTileBytes + rank * half;
#pragma unroll 1
          RING_STEP(, mbar_expect_tx(full, bytes); tma3d_mc(dst + off, map, full, c0, kb * 64 + rank * 32, c2));
        } else if (mode == kModeHead) {
          off += ((nend - nb) >> 3) * step;
          nb = nend;
          if (off >= 163840) off -= 163840;
        } else if (sg < 2) {
#pragma unroll 1
          RING_STEP(, tma2d(sb + kSmRing + off, &map_x, full, xcol + kb * 64, xrow));
        } else {
          const uint8_t* src = ty == 6 ? g_h + b * 56 * kTileBytes : (ty == 2 ? g_o : g_x) + b * 16 * kTileBytes;
          const int dep = (e >> 19) & 31;
          if (dep < 28) mbar_wait(sb + kBarReady + dep * 8, 0);
          if ((dep & 30) == 28) {
#pragma unroll 1
            RING_STEP(mbar_wait(sb + kBarSrc + ((kb << (4 - inc)) & 56), dep),
                      bulk_load(sb + kSmRing + off, src + kb * kTileBytes, kTileBytes, full));
          } else {
#pragma unroll 1
            RING_STEP(, bulk_load(sb + kSmRing + off, src + kb * kTileBytes, kTileBytes, full));
          }
        }
      }
#undef RING_STEP
    } else {
      unsigned epoch = 0;
      if (warp == 10) {
        if (lane == 0) epoch = atomicAdd(&g_ticket, 1u) / kGrid + 1;
        *reinterpret_cast<unsigned*>(sm + kSmEpoch) = __shfl_sync(0xffffffffu, epoch, 0);
        asm volatile("barrier.cluster.wait.aligned;" ::: "memory");
        if (elect()) mbar_arrive(sb + kBarEpoch);
      } else {
        asm volatile("barrier.cluster.wait.aligned;" ::: "memory");
        mbar_wait_bounded(sb + kBarFull, 0);
        if (elect()) {
          mbar_expect_tx(sb + kBarInit, 32768);
          tma2d(sb + kSmX, &map_x, sb + kBarInit, xcol + j * 128, xrow);
          tma2d(sb + kSmX + kTileBytes, &map_x, sb + kBarInit, xcol + j * 128 + 64, xrow);
        }
        const uint2 u = reinterpret_cast<const uint2*>(prm.b2)[32 * j + lane];
        reinterpret_cast<float4*>(sm + kSmB2)[lane] = make_float4(
            2.f * kGeluBeta * bf_lo(u.x), 2.f * kGeluBeta * bf_hi(u.x), 2.f * kGeluBeta * bf_lo(u.y), 2.f * kGeluBeta * bf_hi(u.y));
      }
      mbar_wait_bounded(sb + kBarEpoch, 0);
      epoch = *reinterpret_cast<volatile unsigned*>(sm + kSmEpoch);
      if (cta < 96) {
        mbar_wait_bounded(sb + STRIP_GATE, 0);
        colsum_strip(&map_css, sm, sb, (cta >> 5) * kD + 512 + (cta & 31) * 16, warp - 10, lane, epoch);
      }
      gather_colsums_qkv(sm, 11 - warp, j, lane, epoch);
      __syncwarp();
      if (elect()) mbar_arrive(sb + kBarCs + (11 - warp) * 8);
     if (warp == 10) {
#pragma unroll 1
      for (int i = 0; i < kTiles - 1; i++) {
        const bool xt = i == 2 || i == 6 || i == 9;
        const unsigned* line = g_flag + (i * 16 + b) * 32;
        mbar_wait(sb + (xt ? kBarX + (i >> 2) * 16 : kBarEpi + i * 8), 0);
        if ((xt && (FINE & 1)) || ((i == 1 || i == 8) && (FINE & 2))) {
          unsigned todo = 0xff, spins = 0;
          do {
            const unsigned now = __ballot_sync(0xffffffffu, ld_relaxed(line + (lane & 7)) == epoch) & todo;
            if (now) {
              asm volatile("fence.acquire.gpu;\nfence.proxy.async.global;" ::: "memory");
              if ((now >> lane) & 1) mbar_arrive(sb + kBarSrc + lane * 8);
              todo ^= now;
            }
            if (++spins > kSpinLimit) __trap();
          } while (todo);
        } else {
          wait_flags(line + (lane & 7), epoch);
          if (elect()) mbar_arrive(sb + kBarReady + i * 8);
        }
        if (xt) {
          wait_flags(line + 8 + (lane & 7), epoch);
          if (elect()) mbar_arrive(sb + kBarReady + (14 + (i >> 2)) * 8);
        }
      }
     } else {
#pragma unroll 1
      for (int i = 0; i < kTiles - 1; i++) {
        if (i == 3) {
          gather_colsums_w1(sm, prm.b1, j, lane, epoch);
          __syncwarp();
          if (elect()) mbar_arrive(sb + kBarCs + 16);
        }
        const bool xt = i == 2 || i == 6 || i == 9;
#pragma unroll 1
        for (int h = 0; h < (xt ? 2 : 1); h++) {
          mbar_wait_bounded(sb + (xt ? kBarX + (i >> 2) * 16 + 8 * h : kBarEpi + i * 8), 0);
          const int ty = i >= 7 ? i - 7 : i;
          if (ty >= 2 && elect()) {
            uint8_t* dst = xt ? g_x + (b * 16 + 2 * j + h) * kTileBytes
                              : g_h + (b * 56 + 1 + (ty == 3 ? 3 * j : 16 * ty - 40 + 2 * j)) * kTileBytes;
            bulk_store(dst, sb + (xt ? kSmX + h * kTileBytes : kSmStg), kTileBytes);
            bulk_commit();
            bulk_wait();
            if (!xt) mbar_arrive(sb + kBarFree + i * 8);
          }
          if (LATE_REL2 && h == 1) mbar_wait_bounded(sb + kBarFull + 32, i == 2 ? 6 : i == 6 ? 19 : 25);
          __syncwarp();
          if (elect()) st_release(&g_flag[(i * 16 + b) * 32 + h * 8 + j], epoch);
          __syncwarp();
        }
      }
#pragma unroll 1
      for (int h = 0; h < 2; h++) {
        mbar_wait_bounded(sb + kBarX + 48 + 8 * h, 0);
        if (elect()) {
          tma2d_store(&map_out, sb + kSmX + h * kTileBytes, xcol + j * 128 + h * 64, xrow);
          bulk_commit();
          if (h == 1) bulk_wait_read();
        }
      }
     }
    }
    __syncwarp();
    asm volatile("barrier.cluster.arrive.relaxed.aligned;\nbarrier.cluster.wait.aligned;" ::: "memory");
  } else {
    asm volatile("setmaxnreg.inc.sync.aligned.u32 232;");
    asm volatile("barrier.cluster.wait.aligned;" ::: "memory");
    const int wg = warp >> 2, w = warp & 3;
    const bool rel = (threadIdx.x & 95) == 0;
    const uint32_t rel_addr = mapa(sb + kBarEmpty, w & 1);
    if (wg == 1) TRACE_AT(15, 0);
#define EPOCH (*reinterpret_cast<volatile unsigned*>(sm + kSmEpoch))

#pragma unroll 1
    for (int i = wg; i < kTiles; i += 2) {
      const int layer = i >= 7, ty = i - 7 * layer;
      TRACE_AT(i, 15);
      float acc[2][96];
      if (ty == 2 || ty == 6) {
        const int lane = lane_id();
        const uint32_t xa = sb + kSmX + ((lane >> 4) * 8 + (lane & 7)) * 128 + (((2 * w + ((lane >> 3) & 1)) ^ (lane & 7)) << 4);
        const float up = ty == 6 ? 2.f * kGeluBeta : 1.f, dn = ty == 6 ? 0.5f / kGeluBeta : 1.f;
#pragma unroll
        for (int h = 0; h < 2; h++) {
          const float* b2 = reinterpret_cast<const float*>(sm + kSmB2) + 64 * h + 16 * w + (lane >> 2);
          const float bias[2] = {ty == 6 ? b2[0] : 0.f, ty == 6 ? b2[8] : 0.f};
#pragma unroll
          for (int p = 0; p < 8; p++) {
            uint32_t r[4];
            ldsm4_t(xa + h * kTileBytes + p * 2048, r);
#pragma unroll
            for (int m = 0; m < 4; m++) {
              acc[h][8 * p + 2 * m] = fmaf(bf_lo(r[m]), up, bias[m & 1]);
              acc[h][8 * p + 2 * m + 1] = fmaf(bf_hi(r[m]), up, bias[m & 1]);
              asm volatile("" : "+f"(acc[h][8 * p + 2 * m]), "+f"(acc[h][8 * p + 2 * m + 1]));
              if ((m & XI_MASK) == XI_MASK) yield_slot();
            }
          }
        }
        auto stage = [&](int qt) {
          const int h = qt >> 1;
#pragma unroll
          for (int p = 4 * (qt & 1); p < 4 * (qt & 1) + 4; p++) {
            const float* a = &acc[h][8 * p];
            stsm4_t(xa + h * kTileBytes + p * 2048, pack2(a[0] * dn, a[1] * dn), pack2(a[2] * dn, a[3] * dn),
                    pack2(a[4] * dn, a[5] * dn), pack2(a[6] * dn, a[7] * dn));
            if (STAGE_YIELD || (p & 3) == 3) yield_slot();
          }
          if (qt & 1) {
            fence_async_smem();
            __syncwarp();
            if (elect()) mbar_arrive(sb + kBarX + (i >> 2) * 16 + 8 * h);
            TRACE_AT(i, 8 + h);
          }
        };
        mainloop<128, kResid>(acc, sb, i, layer * 152 + ty * 16, ty == 6 ? 4 : 0, ty == 6 ? 56 : 16,
                            ty == 2 ? PAUSE_WO : -1, 2 * layer + 1, rel_addr, rel, ty == 2 ? 8 : -1, stage);
        TRACE_AT(i, 2);
        stage(2);
        stage(3);
      } else {
        const int xver = 2 * layer + (ty >= 3);
        const uint32_t stg = sb + kSmStg + w * 4096;
        const float4* vec = reinterpret_cast<const float4*>(sm + kSmV1) + (ty == 3 ? 0 : 64 * ty - 160);
        int lane;
        uint8_t* hdst = g_h + (b * 56 + (ty == 3 ? 3 * j : 16 * ty - 40 + 2 * j)) * kTileBytes + w * 4096;
        float2 st[4];
        unsigned epoch;
        auto pre = [&] {
          lane = lane_id();
          if (ty < 4) mbar_wait(sb + (ty == 1 ? kBarEpi + (i - 1) * 8 : kBarStat + xver * 8), 0);
#pragma unroll
          for (int c = 0; c < 4; c++) st[c] = reinterpret_cast<const float2*>(sm + kSmStat)[32 * w + 8 * c + (lane >> 2)];
          epoch = EPOCH;
        };
        auto team_stats = [&] {
          uint2* stat = g_stat + (xver * 16 + b) * 1024;
          lane = lane_id();
          publish_stats(sb, stat + j * 128, w, lane, EPOCH);
          gather_stats(sm, stat, 32 * w + lane, EPOCH);
          __syncwarp();
          if (elect()) mbar_arrive(sb + kBarStat + xver * 8);
          TRACE_AT(i, 14);
        };
        if (ty < 4) {
          AttnRegs ar;
          auto odd = [&](int step) {
            if (step == 0) pre();
            else convert_odd(acc, st, ar, step, sm, g_halo + ((layer * 16 + b) * 16 + j + 8 * ty) * 256, (b & 7) != 7, epoch, w, lane);
          };
          head_blocks<192>(acc, sb, layer * 152 + (ty < 2 ? 2 * ty : 48), ty < 2 ? 2 * ty : 1, xver, rel_addr, rel);
          if (ty == 1) {
            if (i == 1) {
              mbar_wait(sb + kBarEpoch, 0);
              mbar_wait(sb + kBarInit, 0);
            }
            team_stats();
            epoch = 0;
#pragma unroll
            for (int c = 0; c < 4; c++) st[c] = reinterpret_cast<const float2*>(sm + kSmStat)[32 * w + 8 * c + (lane >> 2)];
          } else {
            mainloop<192, kPlain>(acc, sb, i, layer * 152 + (ty ? 52 : 4), ty ? 1 : 0, 14, -1, 0, rel_addr, rel, 0, pre);
            TRACE_AT(i, 2);
            if (ty == 3) goto wide_gelu;
          }
          if (layer == 0) mbar_wait(sb + kBarCs + ty * 8, 0);
          add_mean_term(acc, st, sm, ty, lane);
          if (ty == 1) {
            mainloop<192, kStagger>(acc, sb, i, layer * 152 + 18, 2, 14, PAUSE_QKV2, xver, rel_addr, rel, 0, odd);
            TRACE_AT(i, 2);
          } else {
            odd(1);
            odd(2);
            odd(3);
          }
          epilogue_attn(acc, st, ar, sm, sb, layer, ty, b, j, epoch, i, wg, w, lane);
          TRACE_AT(i, 3);
          continue;
        wide_gelu:
          if (i == 3) mbar_wait(sb + kBarCs + 16, 0);
          scale_stats(st);
          fold_norm<16, 24>(acc, st, vec + (lane & 3));
          TRACE_AT(i, 11);
          gelu_chunk<2>(acc, stg, lane, nullptr, [] {});
          TRACE_AT(i, 12);
          fold_norm<0, 2>(acc, st, vec + (lane & 3));
          store_staged(hdst + 2 * kTileBytes, stg);
          fold_norm<2, 16>(acc, st, vec + (lane & 3));
        } else {
          if (ty == 4) {
            head_blocks<128>(acc, sb, layer * 152 + 50, 3, xver, rel_addr, rel);
            team_stats();
            mainloop<128, kPlain>(acc, sb, i, layer * 152 + 66, 4, 14, -1, 0, rel_addr, rel, 0, pre);
          } else {
            mainloop<128, kFresh>(acc, sb, i, layer * 152 + 80, 3, 16, -1, 0, rel_addr, rel, 0, pre);
          }
          TRACE_AT(i, 2);
          if (i == 4) mbar_wait(sb + kBarCs + 16, 0);
          scale_stats(st);
          fold_norm<0, 16>(acc, st, vec + (lane & 3));
        }
        auto own_store_done = [] {
          if (elect()) bulk_wait();
          __syncwarp();
        };
        TRACE_AT(i, 8);
        gelu_chunk<0>(acc, stg, lane, nullptr, [&] {
          if (ty == 3) own_store_done();
          else mbar_wait(sb + kBarFree + (i - 1) * 8, 0);
        });
        TRACE_AT(i, 9);
        gelu_chunk<1>(acc, stg, lane, hdst, own_store_done);
        TRACE_AT(i, 10);
        fence_async_smem();
        __syncwarp();
        if (elect()) mbar_arrive(sb + kBarEpi + i * 8);
      }
      TRACE_AT(i, 3);
    }
#undef EPOCH
    asm volatile("barrier.cluster.arrive.relaxed.aligned;\nbarrier.cluster.wait.aligned;" ::: "memory");
    if (wg == 1) TRACE_AT(15, 2);
  }
}

void build_segments(uint32_t* seg) {
  int n = 0, fine = 0;
  auto per_source = [&](int kind, int dep) { return (FINE & kind) ? 28 + (fine++ & 1) : dep; };
  auto add = [&](int ty, int cnt, int kb0, int mode, int wide, int depth5, int dep, int reset) {
    seg[n++] = ty | cnt << 3 | kb0 << 9 | mode << 15 | wide << 17 | depth5 << 18 | dep << 19 | reset << 24;
  };
  for (int l = 0; l < 2; l++) {
    const int t = 7 * l;
    if (l == 0) {
      add(0, 14, 2, kModePlain, 1, 0, 31, 1);
      add(1, 14, 2, kModePlain, 1, 0, 31, 0);
    } else {
      add(0, 2, 0, kModeHead, 1, 0, 31, 1);
      add(1, 2, 0, kModeHead, 1, 0, 31, 0);
      add(0, 7, 0, kModeSkip, 1, 0, per_source(1, 6), 0);
      add(0, 7, 1, kModeSkip, 1, 0, 15, 0);
      add(1, 7, 0, kModeSkip, 1, 0, 31, 0);
      add(1, 7, 1, kModeSkip, 1, 0, 31, 0);
    }
    add(2, 4, 0, kModePlain, 0, 0, t, 1);
    add(2, 4, 4, kModePlain, 0, 1, 31, 0);
    add(2, 1, 0, kModeHead, 0, 1, 31, 0);
    add(2, 7, 8, kModeSkip, 0, 1, per_source(2, t + 1), 0);
    add(3, 2, 0, kModeHead, 1, 0, 31, 2);
    add(4, 2, 0, kModeHead, 1, 0, 31, 0);
    add(3, 7, 0, kModeSkip, 1, 0, per_source(1, t + 2), 0);
    add(3, 7, 1, kModeSkip, 1, 0, 14 + 2 * l, 0);
    add(4, 4, 0, kModeSkip, 0, 0, 31, 3);
    add(4, 3, 0, kModeContinue, 0, 1, 31, 0);
    add(4, 7, 1, kModeSkip, 0, 1, 31, 0);
    add(5, 16, 0, kModePlain, 0, 1, 31, 0);
    add(6, 24, 0, kModePlain, 0, 1, t + 3, 0);
    add(6, 16, 24, kModePlain, 0, 1, t + 4, 0);
    add(6, 16, 40, kModePlain, 0, 1, t + 5, 0);
  }
}

typedef CUresult (*EncodeTiledFn)(CUtensorMap*, CUtensorMapDataType, cuuint32_t, void*, const cuuint64_t*,
                                  const cuuint64_t*, const cuuint32_t*, const cuuint32_t*, CUtensorMapInterleave,
                                  CUtensorMapSwizzle, CUtensorMapL2promotion, CUtensorMapFloatOOBfill);

CUtensorMap make_map(EncodeTiledFn enc, const void* p, int rank, const cuuint64_t* dims, const cuuint64_t* strides,
                     const cuuint32_t* box, CUtensorMapSwizzle swizzle = CU_TENSOR_MAP_SWIZZLE_128B) {
  CUtensorMap m;
  const cuuint32_t es[5] = {1, 1, 1, 1, 1};
  enc(&m, CU_TENSOR_MAP_DATA_TYPE_BFLOAT16, rank, const_cast<void*>(p), dims, strides, box, es,
      CU_TENSOR_MAP_INTERLEAVE_NONE, swizzle, CU_TENSOR_MAP_L2_PROMOTION_L2_128B,
      CU_TENSOR_MAP_FLOAT_OOB_FILL_NONE);
  return m;
}

CUtensorMap weight_map(EncodeTiledFn enc, const void* p, int k, int n, int blocks) {
  const cuuint64_t dims[3] = {64, (cuuint64_t)k, (cuuint64_t)n / 64};
  const cuuint64_t strides[2] = {(cuuint64_t)n * 2, 128};
  const cuuint32_t box[3] = {64, 32, (cuuint32_t)blocks};
  return make_map(enc, p, 3, dims, strides, box);
}

CUtensorMap slab_map(EncodeTiledFn enc, const void* p, int n, int cols, int rows) {
  const cuuint64_t dims[2] = {(cuuint64_t)n, kD};
  const cuuint64_t strides[1] = {(cuuint64_t)n * 2};
  const cuuint32_t box[2] = {(cuuint32_t)cols, (cuuint32_t)rows};
  return make_map(enc, p, 2, dims, strides, box, CU_TENSOR_MAP_SWIZZLE_NONE);
}

CUtensorMap token_map(EncodeTiledFn enc, const void* p, int rows) {
  const cuuint64_t dims[2] = {2 * kD, 1024};
  const cuuint64_t strides[1] = {4 * kD};
  const cuuint32_t box[2] = {64, (cuuint32_t)rows};
  return make_map(enc, p, 2, dims, strides, box);
}

}

extern "C" void kernel_launch(void* const* d_in, const int* in_sizes, int n_in, void* d_out, int out_size) {
  (void)in_sizes; (void)n_in; (void)out_size;
  static EncodeTiledFn enc = nullptr;
  if (!enc) {
    void* fn = nullptr;
    cudaDriverEntryPointQueryResult q;
    cudaGetDriverEntryPoint("cuTensorMapEncodeTiled", &fn, cudaEnableDefault, &q);
    enc = (EncodeTiledFn)fn;
    cudaFuncSetAttribute(fused_layers_kernel, cudaFuncAttributeMaxDynamicSharedMemorySize, kSmBytes);
  }
  Params prm;
  prm.b1 = (const __nv_bfloat16*)d_in[5];
  prm.b2 = (const __nv_bfloat16*)d_in[7];
  build_segments(prm.seg);
  const cuuint64_t qd[3] = {kD, kD, 3}, qs[2] = {3 * kD * 2, kD * 2};
  const cuuint32_t qb[3] = {64, 32, 3};
  const CUtensorMap map_x = token_map(enc, d_in[0], 128);
  const CUtensorMap map_out = token_map(enc, d_out, 128);
  const CUtensorMap map_qkv = make_map(enc, d_in[1], 3, qd, qs, qb);
  const CUtensorMap map_wo = weight_map(enc, d_in[2], kD, kD, 2);
  const CUtensorMap map_w1a = weight_map(enc, d_in[4], kD, kF, 3);
  const CUtensorMap map_w1b = weight_map(enc, d_in[4], kD, kF, 2);
  const CUtensorMap map_w2 = weight_map(enc, d_in[6], kF, kD, 2);
  fused_layers_kernel<<<kGrid, 384, kSmBytes>>>(map_x, map_out, map_qkv, map_wo, map_w1a, map_w1b, map_w2,
                                                slab_map(enc, d_in[1], 3 * kD, 128, 128), slab_map(enc, d_in[4], kF, 128, 128),
                                                slab_map(enc, d_in[1], 3 * kD, 16, 128), prm);
}
```

```cpp
#include <cuda.h>
#include <cuda_bf16.h>
#include <cuda_runtime.h>
#include <stdint.h>

namespace {

constexpr int kD = 1024;
constexpr int kF = 3584;
constexpr int kCtas = 128;
constexpr int kGrid = 132;
constexpr int kTiles = 14;
constexpr int kTileBytes = 16384;

constexpr int kSmRing = 0;
constexpr int kSmX = 163840;
constexpr int kSmStg = kSmX + 32768;
constexpr int kSmHalo = kSmStg + 16384;
constexpr int kSmCsQ = kSmHalo + 6144;
constexpr int kSmV1 = kSmCsQ + 384 * 4;
constexpr int kSmB2 = kSmV1 + 448 * 8;
constexpr int kSmStat = kSmB2 + 128 * 4;
constexpr int kSmBar = kSmStat + 128 * 8;
constexpr int kBarFull = kSmBar;
constexpr int kBarTurn = kBarFull + 8 * 8;
constexpr int kBarReady = kBarTurn + 14 * 8;
constexpr int kBarSrc = kBarReady + 17 * 8;
constexpr int kBarPause = kBarSrc + 8 * 8;
constexpr int kBarFree = kBarPause + 4 * 8;
constexpr int kBarCs = kBarFree + 14 * 8;
constexpr int kBarSlab = kBarCs + 3 * 8;
constexpr int kBarHalo = kBarSlab + 4 * 8;
constexpr int kBarInit = kBarHalo + 12 * 8;
constexpr int kBarEpoch = kBarInit + 8;
constexpr int kBarEmpty = kBarTurn + 5 * 128;
constexpr int kBarEpi = kBarEmpty + 128;
constexpr int kBarX = kBarEpi + 14 * 8;
constexpr int kBarStat = kBarX + 8 * 8;
constexpr int kBarResume = kBarStat + 4 * 8;
constexpr int kSmEpoch = kBarEpi + 2 * 128;
static_assert(kBarEpoch < kBarEmpty && kBarResume + 4 * 8 <= kSmEpoch, "barrier groups overflow");
constexpr int kSmBytes = kSmEpoch + 16;
constexpr int kSegs = 38;

constexpr int kFlagLines = kTiles * 16;

constexpr unsigned kSpinLimit = 1u << 22;

__device__ __align__(1024) uint8_t g_x[16 * 16 * kTileBytes];
__device__ __align__(1024) uint8_t g_o[16 * 16 * kTileBytes];
__device__ __align__(1024) uint8_t g_h[16 * 56 * kTileBytes];
__device__ __align__(128) uint2 g_stat[4 * 16 * 128 * 8];
__device__ __align__(128) unsigned g_cs[3 * kD + kF + 3 * kD];
__device__ __align__(128) uint4 g_halo[2 * 16 * 16 * 256];
__device__ __align__(128) unsigned g_flag[kFlagLines * 32];
__device__ unsigned g_ticket;

#define TRACE_AT(tile, k)
#define TRACE_PUB(i, k, c)
#define TRACE_ISSUE(which, nb)

struct Params {
  const __nv_bfloat16* b1;
  const __nv_bfloat16* b2;
  uint32_t seg[kSegs];
};

__device__ __forceinline__ uint32_t smem_u32(const void* p) {
  return (uint32_t)__cvta_generic_to_shared(p);
}
__device__ __forceinline__ uint32_t mapa(uint32_t a, uint32_t cta) {
  uint32_t r;
  asm("mapa.shared::cluster.u32 %0, %1, %2;" : "=r"(r) : "r"(a), "r"(cta));
  return r;
}
__device__ __forceinline__ void mbar_init(uint32_t bar, int cnt) {
  asm volatile("mbarrier.init.shared::cta.b64 [%0], %1;" ::"r"(bar), "r"(cnt) : "memory");
}
__device__ __forceinline__ void mbar_expect_tx(uint32_t bar, uint32_t bytes) {
  asm volatile("mbarrier.arrive.expect_tx.shared::cta.b64 _, [%0], %1;" ::"r"(bar), "r"(bytes) : "memory");
}
__device__ __forceinline__ void mbar_arrive(uint32_t bar) {
  asm volatile("mbarrier.arrive.shared::cta.b64 _, [%0];" ::"r"(bar) : "memory");
}
__device__ __forceinline__ void mbar_arrive_cluster(uint32_t cluster_addr) {
  asm volatile("mbarrier.arrive.shared::cluster.b64 _, [%0];" ::"r"(cluster_addr) : "memory");
}
__device__ __forceinline__ void mbar_wait(uint32_t bar, uint32_t parity) {
  asm volatile("{\n.reg .pred p;\nRETRY:\nmbarrier.try_wait.parity.shared::cta.b64 p, [%0], %1;\n"
               "@!p bra.uni RETRY;\n}" ::"r"(bar), "r"(parity) : "memory");
}
__device__ __forceinline__ void mbar_wait_bounded(uint32_t bar, uint32_t parity) {
  asm volatile("{\n.reg .pred p;\n.reg .u32 c;\nmov.u32 c, 0;\nRETRY:\n"
               "mbarrier.try_wait.parity.shared::cta.b64 p, [%0], %1;\n@p bra.uni DONE;\n"
               "add.u32 c, c, 1;\nsetp.lt.u32 p, c, %2;\n@p bra.uni RETRY;\ntrap;\nDONE:\n}"
               ::"r"(bar), "r"(parity), "n"(1u << 19) : "memory");
}
__device__ __forceinline__ void tma3d(uint32_t dst, const CUtensorMap* m, uint32_t bar, int c0, int c1, int c2) {
  asm volatile(
      "cp.async.bulk.tensor.3d.shared::cluster.global.mbarrier::complete_tx::bytes [%0], [%1, {%3, %4, %5}], [%2];"
      ::"r"(dst), "l"(m), "r"(bar), "r"(c0), "r"(c1), "r"(c2) : "memory");
}
__device__ __forceinline__ void tma3d_mc(uint32_t dst, const CUtensorMap* m, uint32_t bar, int c0, int c1, int c2) {
  asm volatile(
      "cp.async.bulk.tensor.3d.shared::cluster.global.mbarrier::complete_tx::bytes.multicast::cluster"
      " [%0], [%1, {%3, %4, %5}], [%2], %6;"
      ::"r"(dst), "l"(m), "r"(bar), "r"(c0), "r"(c1), "r"(c2), "h"((uint16_t)3) : "memory");
}
__device__ __forceinline__ void tma2d(uint32_t dst, const CUtensorMap* m, uint32_t bar, int c0, int c1) {
  asm volatile(
      "cp.async.bulk.tensor.2d.shared::cluster.global.mbarrier::complete_tx::bytes [%0], [%1, {%3, %4}], [%2];"
      ::"r"(dst), "l"(m), "r"(bar), "r"(c0), "r"(c1) : "memory");
}
__device__ __forceinline__ void tma2d_store(const CUtensorMap* m, uint32_t src, int c0, int c1) {
  asm volatile("cp.async.bulk.tensor.2d.global.shared::cta.bulk_group [%0, {%2, %3}], [%1];"
               ::"l"(m), "r"(src), "r"(c0), "r"(c1) : "memory");
}
__device__ __forceinline__ int lane_id() {
  int l;
  asm volatile("mov.u32 %0, %%laneid;" : "=r"(l));
  return l;
}
__device__ __forceinline__ bool elect() {
  uint32_t p;
  asm volatile("{\n.reg .pred p;\nelect.sync _|p, 0xffffffff;\nselp.b32 %0, 1, 0, p;\n}" : "=r"(p));
  return p;
}
__device__ __forceinline__ void bulk_load(uint32_t dst, const void* src, uint32_t bytes, uint32_t bar) {
  asm volatile("cp.async.bulk.shared::cluster.global.mbarrier::complete_tx::bytes [%0], [%1], %2, [%3];"
               ::"r"(dst), "l"(src), "r"(bytes), "r"(bar) : "memory");
}
__device__ __forceinline__ void bulk_store(void* dst, uint32_t src, uint32_t bytes) {
  asm volatile("cp.async.bulk.global.shared::cta.bulk_group [%0], [%1], %2;" ::"l"(dst), "r"(src), "r"(bytes)
               : "memory");
}
__device__ __forceinline__ void bulk_commit() { asm volatile("cp.async.bulk.commit_group;" ::: "memory"); }
__device__ __forceinline__ void bulk_wait_read() { asm volatile("cp.async.bulk.wait_group.read 0;" ::: "memory"); }
__device__ __forceinline__ void bulk_wait() { asm volatile("cp.async.bulk.wait_group 0;" ::: "memory"); }
__device__ __forceinline__ void fence_async_smem() { asm volatile("fence.proxy.async.shared::cta;" ::: "memory"); }
__device__ __forceinline__ unsigned ld_relaxed(const unsigned* p) {
  unsigned v;
  asm volatile("ld.relaxed.gpu.global.u32 %0, [%1];" : "=r"(v) : "l"(p) : "memory");
  return v;
}
__device__ __forceinline__ uint2 ld_relaxed2(const uint2* p) {
  uint2 v;
  asm volatile("ld.relaxed.gpu.global.v2.u32 {%0, %1}, [%2];" : "=r"(v.x), "=r"(v.y) : "l"(p) : "memory");
  return v;
}
__device__ __forceinline__ void st_relaxed(unsigned* p, unsigned v) {
  asm volatile("st.relaxed.gpu.global.u32 [%0], %1;" ::"l"(p), "r"(v) : "memory");
}
__device__ __forceinline__ void st_release(unsigned* p, unsigned v) {
  asm volatile("st.release.gpu.global.u32 [%0], %1;" ::"l"(p), "r"(v) : "memory");
}
#define ACQ_MODE 1
__device__ __forceinline__ void wait_flags(const unsigned* p, unsigned epoch) {
  unsigned spins = 0;
  while (true) {
    const unsigned v = ld_relaxed(p);
    if (__all_sync(0xffffffffu, v == epoch)) break;
    if (++spins > kSpinLimit) __trap();
  }
  if (ACQ_MODE) asm volatile("fence.acquire.gpu;\nfence.proxy.async.global;" ::: "memory");
  __syncwarp();
}
__device__ __forceinline__ void st_packet(uint4* p, uint32_t d0, uint32_t d1, uint32_t tag) {
  asm volatile("{\n.reg .b128 v;\n.reg .b64 x, y;\nmov.b64 x, {%1, %2};\nmov.b64 y, {%3, %3};\nmov.b128 v, {x, y};\n"
               "st.relaxed.gpu.global.b128 [%0], v;\n}" ::"l"(p), "r"(d0), "r"(d1), "r"(tag) : "memory");
}
__device__ __forceinline__ void ld_packet(const uint4* p, uint32_t& d0, uint32_t& d1, uint32_t& tag) {
  asm volatile("{\n.reg .b128 v;\n.reg .b64 x, y;\n.reg .b32 u;\nld.relaxed.gpu.global.b128 v, [%3];\n"
               "mov.b128 {x, y}, v;\nmov.b64 {%0, %1}, x;\nmov.b64 {%2, u}, y;\n}"
               : "=r"(d0), "=r"(d1), "=r"(tag) : "l"(p) : "memory");
}
__device__ __forceinline__ unsigned tag_value(float v, unsigned epoch) {
  return (__float_as_uint(v) & ~7u) | (epoch & 7u);
}
__device__ __forceinline__ float untag_value(unsigned v) { return __uint_as_float(v & ~7u); }
__device__ __forceinline__ void stsm4(uint32_t a, uint32_t r0, uint32_t r1, uint32_t r2, uint32_t r3) {
  asm volatile("stmatrix.sync.aligned.m8n8.x4.shared.b16 [%0], {%1, %2, %3, %4};" ::"r"(a), "r"(r0), "r"(r1),
               "r"(r2), "r"(r3) : "memory");
}
__device__ __forceinline__ void stsm4_t(uint32_t a, uint32_t r0, uint32_t r1, uint32_t r2, uint32_t r3) {
  asm volatile("stmatrix.sync.aligned.m8n8.x4.trans.shared.b16 [%0], {%1, %2, %3, %4};" ::"r"(a), "r"(r0),
               "r"(r1), "r"(r2), "r"(r3) : "memory");
}
__device__ __forceinline__ uint32_t transpose8(uint32_t a) {
  uint32_t d;
  asm volatile("movmatrix.sync.aligned.m8n8.trans.b16 %0, %1;" : "=r"(d) : "r"(a));
  return d;
}
__device__ __forceinline__ void mma16816(float (&c)[4], uint32_t a0, uint32_t a1, uint32_t a2, uint32_t a3,
                                         uint32_t b0, uint32_t b1) {
  asm volatile("mma.sync.aligned.m16n8k16.row.col.f32.bf16.bf16.f32 {%0, %1, %2, %3}, {%4, %5, %6, %7}, {%8, %9}, "
               "{%0, %1, %2, %3};"
               : "+f"(c[0]), "+f"(c[1]), "+f"(c[2]), "+f"(c[3])
               : "r"(a0), "r"(a1), "r"(a2), "r"(a3), "r"(b0), "r"(b1));
}
__device__ __forceinline__ void mma1688(float (&c)[4], uint32_t a0, uint32_t a1, uint32_t b0) {
  asm volatile("mma.sync.aligned.m16n8k8.row.col.f32.bf16.bf16.f32 {%0, %1, %2, %3}, {%4, %5}, {%6}, {%0, %1, %2, %3};"
               : "+f"(c[0]), "+f"(c[1]), "+f"(c[2]), "+f"(c[3]) : "r"(a0), "r"(a1), "r"(b0));
}
__device__ __forceinline__ float shfl_xor(float v, int m) {
  float r;
  asm volatile("shfl.sync.bfly.b32 %0, %1, %2, 31, 0xffffffff;" : "=f"(r) : "f"(v), "r"(m));
  return r;
}
__device__ __forceinline__ float tanh_fast(float x) {
  float r;
  asm volatile("tanh.approx.f32 %0, %1;" : "=f"(r) : "f"(x));
  return r;
}
__device__ __forceinline__ void ldsm4(uint32_t a, uint32_t (&r)[4]) {
  asm volatile("ldmatrix.sync.aligned.m8n8.x4.shared.b16 {%0, %1, %2, %3}, [%4];"
               : "=r"(r[0]), "=r"(r[1]), "=r"(r[2]), "=r"(r[3]) : "r"(a) : "memory");
}
__device__ __forceinline__ void ldsm4_t(uint32_t a, uint32_t (&r)[4]) {
  asm volatile("ldmatrix.sync.aligned.m8n8.x4.trans.shared.b16 {%0, %1, %2, %3}, [%4];"
               : "=r"(r[0]), "=r"(r[1]), "=r"(r[2]), "=r"(r[3]) : "r"(a) : "memory");
}
__device__ __forceinline__ uint32_t pack2(float lo, float hi) {
  uint32_t r;
  asm volatile("cvt.rn.bf16x2.f32 %0, %1, %2;" : "=r"(r) : "f"(hi), "f"(lo));
  return r;
}
__device__ __forceinline__ float bf_lo(uint32_t r) { return __uint_as_float(r << 16); }
__device__ __forceinline__ float bf_hi(uint32_t r) { return __uint_as_float(r & 0xffff0000u); }
__device__ __forceinline__ float ex2(float x) {
  float r;
  asm("ex2.approx.ftz.f32 %0, %1;" : "=f"(r) : "f"(x));
  return r;
}
__device__ __forceinline__ float rcp(float x) {
  float r;
  asm("rcp.approx.ftz.f32 %0, %1;" : "=f"(r) : "f"(x));
  return r;
}
template <int N>
__device__ __forceinline__ void wg_wait() {
  asm volatile("wgmma.wait_group.sync.aligned %0;" ::"n"(N) : "memory");
}
__device__ __forceinline__ void yield_slot() { asm volatile("pmevent 0;"); }

template <int N, int KIND>
__device__ __forceinline__ void mma_kblock(float (&acc)[2][96], uint32_t a, uint32_t b);

#define F8(m, d, i) m(d[i]), m(d[i + 1]), m(d[i + 2]), m(d[i + 3]), m(d[i + 4]), m(d[i + 5]), m(d[i + 6]), m(d[i + 7])
#define KSTEP(N, A, B, oa0, oa1, ob, sd)                                                   \
  "add.u32 t, " B ", " #ob ";\nmov.b64 db, {t, hb};\n"                                      \
  "add.u32 t, " A ", " #oa0 ";\nmov.b64 da, {t, ha};\n"                                     \
  "wgmma.mma_async.sync.aligned.m64n" #N "k16.f32.bf16.bf16 {" ACC##N##_0 "}, da, db, " #sd ", 1, 1, 0, 1;\n" \
  "add.u32 t, " A ", " #oa1 ";\nmov.b64 da, {t, ha};\n"                                     \
  "wgmma.mma_async.sync.aligned.m64n" #N "k16.f32.bf16.bf16 {" ACC##N##_1 "}, da, db, " #sd ", 1, 1, 0, 1;\n"

#define MMA_KBLOCK(N, KIND, A, B, ob2, ob3, sd, MID, MODE)                                 \
  template <>                                                                              \
  __device__ __forceinline__ void mma_kblock<N, KIND>(float (&acc)[2][96], uint32_t a, uint32_t b) { \
    asm volatile("{\n.reg .b32 t, ha, hb;\n.reg .b64 da, db;\n"                            \
                 "mov.b32 ha, 0x40000080;\nmov.b32 hb, 0x40000040;\n"                       \
                 "wgmma.fence.sync.aligned;\n"                                             \
                 KSTEP(N, A, B, 0, 64, 0, sd) KSTEP(N, A, B, 2, 66, 128, 1) KSTEP(N, A, B, 4, 68, ob2, 1) \
                 MID KSTEP(N, A, B, 6, 70, ob3, 1) "wgmma.commit_group.sync.aligned;\n}\n"  \
                 : OPS##N(MODE) : "r"(a), "r"(b) : "memory");                              \
  }
#define MMA_KBLOCKS(N, A, B, ob2, ob3)                                                     \
  MMA_KBLOCK(N, 0, A, B, ob2, ob3, 1, "", "+f")                                            \
  MMA_KBLOCK(N, 1, A, B, ob2, ob3, 1, "wgmma.commit_group.sync.aligned;\n", "+f")          \
  MMA_KBLOCK(N, 2, A, B, ob2, ob3, 0, "", "=f")

#define ACC128_0 \
  "%0, %1, %2, %3, %4, %5, %6, %7, %8, %9, %10, %11, %12, %13, %14, %15, " \
  "%16, %17, %18, %19, %20, %21, %22, %23, %24, %25, %26, %27, %28, %29, %30, %31, " \
  "%32, %33, %34, %35, %36, %37, %38, %39, %40, %41, %42, %43, %44, %45, %46, %47, " \
  "%48, %49, %50, %51, %52, %53, %54, %55, %56, %57, %58, %59, %60, %61, %62, %63"
#define ACC128_1 \
  "%64, %65, %66, %67, %68, %69, %70, %71, %72, %73, %74, %75, %76, %77, %78, %79, " \
  "%80, %81, %82, %83, %84, %85, %86, %87, %88, %89, %90, %91, %92, %93, %94, %95, " \
  "%96, %97, %98, %99, %100, %101, %102, %103, %104, %105, %106, %107, %108, %109, %110, %111, " \
  "%112, %113, %114, %115, %116, %117, %118, %119, %120, %121, %122, %123, %124, %125, %126, %127"
#define OPS128(m) \
  F8(m, acc[0], 0), F8(m, acc[0], 8), F8(m, acc[0], 16), F8(m, acc[0], 24), F8(m, acc[0], 32), F8(m, acc[0], 40), F8(m, acc[0], 48), F8(m, acc[0], 56), \
        F8(m, acc[1], 0), F8(m, acc[1], 8), F8(m, acc[1], 16), F8(m, acc[1], 24), F8(m, acc[1], 32), F8(m, acc[1], 40), F8(m, acc[1], 48), F8(m, acc[1], 56)
MMA_KBLOCKS(128, "%128", "%129", 512, 640)

#define ACC192_0 \
  "%0, %1, %2, %3, %4, %5, %6, %7, %8, %9, %10, %11, %12, %13, %14, %15, " \
  "%16, %17, %18, %19, %20, %21, %22, %23, %24, %25, %26, %27, %28, %29, %30, %31, " \
  "%32, %33, %34, %35, %36, %37, %38, %39, %40, %41, %42, %43, %44, %45, %46, %47, " \
  "%48, %49, %50, %51, %52, %53, %54, %55, %56, %57, %58, %59, %60, %61, %62, %63, " \
  "%64, %65, %66, %67, %68, %69, %70, %71, %72, %73, %74, %75, %76, %77, %78, %79, " \
  "%80, %81, %82, %83, %84, %85, %86, %87, %88, %89, %90, %91, %92, %93, %94, %95"
#define ACC192_1 \
  "%96, %97, %98, %99, %100, %101, %102, %103, %104, %105, %106, %107, %108, %109, %110, %111, " \
  "%112, %113, %114, %115, %116, %117, %118, %119, %120, %121, %122, %123, %124, %125, %126, %127, " \
  "%128, %129, %130, %131, %132, %133, %134, %135, %136, %137, %138, %139, %140, %141, %142, %143, " \
  "%144, %145, %146, %147, %148, %149, %150, %151, %152, %153, %154, %155, %156, %157, %158, %159, " \
  "%160, %161, %162, %163, %164, %165, %166, %167, %168, %169, %170, %171, %172, %173, %174, %175, " \
  "%176, %177, %178, %179, %180, %181, %182, %183, %184, %185, %186, %187, %188, %189, %190, %191"
#define OPS192(m) \
  F8(m, acc[0], 0), F8(m, acc[0], 8), F8(m, acc[0], 16), F8(m, acc[0], 24), F8(m, acc[0], 32), F8(m, acc[0], 40), F8(m, acc[0], 48), F8(m, acc[0], 56), F8(m, acc[0], 64), F8(m, acc[0], 72), F8(m, acc[0], 80), F8(m, acc[0], 88), \
        F8(m, acc[1], 0), F8(m, acc[1], 8), F8(m, acc[1], 16), F8(m, acc[1], 24), F8(m, acc[1], 32), F8(m, acc[1], 40), F8(m, acc[1], 48), F8(m, acc[1], 56), F8(m, acc[1], 64), F8(m, acc[1], 72), F8(m, acc[1], 80), F8(m, acc[1], 88)
MMA_KBLOCKS(192, "%192", "%193", 768, 896)

#define HSTEP(oa, ob)                                                                       \
  "add.u32 t, %97, " #ob ";\nmov.b64 db, {t, hb};\nadd.u32 t, %96, " #oa ";\nmov.b64 da, {t, ha};\n" \
  "wgmma.mma_async.sync.aligned.m64n192k16.f32.bf16.bf16 {" ACC192_0 "}, da, db, 1, 1, 1, 0, 1;\n"
__device__ __forceinline__ void mma_half(float (&d)[96], uint32_t a, uint32_t b) {
  asm volatile("{\n.reg .b32 t, ha, hb;\n.reg .b64 da, db;\nmov.b32 ha, 0x40000080;\nmov.b32 hb, 0x40000040;\n"
               "wgmma.fence.sync.aligned;\n" HSTEP(0, 0) HSTEP(2, 128) HSTEP(4, 768) HSTEP(6, 896)
               "wgmma.commit_group.sync.aligned;\n}\n"
               : F8("+f", d, 0), F8("+f", d, 8), F8("+f", d, 16), F8("+f", d, 24), F8("+f", d, 32), F8("+f", d, 40),
                 F8("+f", d, 48), F8("+f", d, 56), F8("+f", d, 64), F8("+f", d, 72), F8("+f", d, 80), F8("+f", d, 88)
               : "r"(a), "r"(b) : "memory");
}

#define TSTEP(REGS, W, X, ow, ox)                                                           \
  "add.u32 t, " X ", " #ox ";\nmov.b64 db, {t, hi};\nadd.u32 t, " W ", " #ow ";\nmov.b64 da, {t, hi};\n" \
  "wgmma.mma_async.sync.aligned.m64n128k16.f32.bf16.bf16 {" REGS "}, da, db, 1, 1, 1, 1, 0;\n"
#define THEAD "{\n.reg .b32 t, hi;\n.reg .b64 da, db;\nmov.b32 hi, 0x40000040;\nwgmma.fence.sync.aligned;\n"
#define TTAIL "wgmma.commit_group.sync.aligned;\n}\n"
__device__ __forceinline__ void mma_kblock_t(float (&acc)[2][96], uint32_t wd, uint32_t xd) {
  asm volatile(THEAD TSTEP(ACC128_0, "%128", "%129", 0, 0) TSTEP(ACC128_1, "%128", "%129", 256, 0)
               TSTEP(ACC128_0, "%128", "%129", 128, 2) TSTEP(ACC128_1, "%128", "%129", 384, 2)
               TSTEP(ACC128_0, "%128", "%129", 512, 4) TSTEP(ACC128_1, "%128", "%129", 768, 4)
               TSTEP(ACC128_0, "%128", "%129", 640, 6) TSTEP(ACC128_1, "%128", "%129", 896, 6) TTAIL
               : OPS128("+f") : "r"(wd), "r"(xd) : "memory");
}
__device__ __forceinline__ void mma_half_t(float (&d)[96], uint32_t wd, uint32_t xd) {
  asm volatile(THEAD TSTEP(ACC128_0, "%64", "%65", 0, 0) TSTEP(ACC128_0, "%64", "%65", 128, 2)
               TSTEP(ACC128_0, "%64", "%65", 512, 4) TSTEP(ACC128_0, "%64", "%65", 640, 6) TTAIL
               : F8("+f", d, 0), F8("+f", d, 8), F8("+f", d, 16), F8("+f", d, 24), F8("+f", d, 32), F8("+f", d, 40),
                 F8("+f", d, 48), F8("+f", d, 56) : "r"(wd), "r"(xd) : "memory");
}

enum { kModePlain = 0, kModeHead = 1, kModeSkip = 2, kModeContinue = 3 };

template <int N>
__device__ __forceinline__ void fence_acc(float (&acc)[2][96]) {
#pragma unroll
  for (int h = 0; h < 2; h++)
#pragma unroll
    for (int i = 0; i < N / 2; i++) asm volatile("" : "+f"(acc[h][i])::"memory");
}

constexpr uint32_t kToB = (kTileBytes >> 4) + ((4096u >> 4) << 16) - (1u << 16);

#define TRACE_KB(nb)

#define HEAD_BOTH 4
template <int N>
__device__ __forceinline__ void head_blocks(float (&acc)[2][96], uint32_t sb, int n0, int slot, int xver,
                                            uint32_t rel_addr, bool rel) {
  const uint32_t ring = (((sb & 0x3FFFF) + kSmRing) >> 4) | (1u << 16);
  const uint32_t xdesc = (((sb & 0x3FFFF) + kSmX) >> 4) | (1u << 16);
  const uint32_t s0 = ring + slot * 2560, s1 = ring + ((slot + 1) & 3) * 2560;
  const uint32_t nb = n0 * 8, xbar = sb + kBarX + (xver - 1) * 16;
  if (xver > 0) {
    mbar_wait(xbar + ((HEAD_BOTH >> xver) & 1) * 8, 0);
    mbar_wait(sb + kBarTurn + (xver == 1 ? 2 : 3 * xver) * 8, 0);
  }
  mbar_wait(sb + kBarFull + (nb & 56), nb >> 6);
  if (n0 == 0) TRACE_AT(0, 1);
  TRACE_KB(nb);
  mma_kblock<N, 2>(acc, xver > 0 ? xdesc : s0, s0 + kToB);
  if (xver > 0) mbar_wait(xbar + 8, 0);
  mbar_wait(sb + kBarFull + (nb & 56) + 8, nb >> 6);
  TRACE_KB(nb + 8);
  mma_kblock<N, 0>(acc, xver > 0 ? xdesc + (kTileBytes >> 4) : s1, s1 + kToB);
  wg_wait<1>();
  if (rel) mbar_arrive_cluster(rel_addr + (nb & 56));
  wg_wait<0>();
  if (rel) mbar_arrive_cluster(rel_addr + (nb & 56) + 8);
  fence_acc<N>(acc);
}

enum { kPlain, kFresh, kResid, kStagger };
template <int N, int KIND, class Pre>
__device__ __forceinline__ void mainloop(float (&acc)[2][96], uint32_t sb, int tile, int n0, int slot, int nkb,
                                         int pause_kk, int att, uint32_t rel_addr, bool rel, int own_kk, Pre pre) {
  constexpr bool RESID = KIND == kResid, FRESH = KIND == kFresh;
  constexpr uint32_t kStep = (N == 192 ? 5 : 4) * 512;
  const uint32_t ring = (((sb & 0x3FFFF) + kSmRing) >> 4) | (1u << 16);
  uint32_t st = ring + slot * kStep;
  uint32_t nb = n0 * 8, prev = 64;
  const uint32_t last = nb + 8 * (nkb - (RESID ? 3 : KIND == kStagger ? 2 : 1)), own = nb + 8 * own_kk;
  const uint32_t stg = (((sb & 0x3FFFF) + kSmStg) >> 4) | (1u << 16);
  uint32_t stop = pause_kk >= 0 ? nb + 8 * pause_kk : last;
  const bool signal = (threadIdx.x & 127) == 64;
  if (!FRESH) fence_acc<N>(acc);
  if (tile > 0) mbar_wait(sb + kBarTurn + (tile - 1) * 8, 0);
  TRACE_AT(tile, 0);
  if constexpr (FRESH) {
    mbar_wait(sb + kBarFull + (nb & 56), nb >> 6);
    TRACE_KB(nb);
    mma_kblock<N, 2>(acc, st, st + kToB);
    prev = nb & 56;
    st += kStep;
    nb += 8;
  }
#pragma unroll 1
  while (true) {
#pragma unroll 1
    do {
      mbar_wait(sb + kBarFull + (nb & 56), nb >> 6);
      TRACE_KB(nb);
      if constexpr (RESID) mma_kblock_t(acc, st + kToB, nb == own ? stg : st);
      else mma_kblock<N, 0>(acc, st, st + kToB);
      wg_wait<1>();
      if (rel) mbar_arrive_cluster(rel_addr + prev);
      prev = nb & 56;
      st += kStep;
      if (st == ring + 10240) st = ring;
      nb += 8;
    } while (nb != stop);
    if (stop == last) break;
    stop = last;
    if (signal) mbar_arrive(sb + kBarPause + att * 8);
    wg_wait<0>();
    if (rel) mbar_arrive_cluster(rel_addr + prev);
    prev = 64;
    mbar_wait(sb + kBarResume + att * 8, 0);
  }
  mbar_wait(sb + kBarFull + (nb & 56), nb >> 6);
  TRACE_KB(nb);
  if constexpr (RESID) {
    const uint32_t z = gridDim.y - 1;
    const uint32_t s2 = st + kStep, s3 = s2 == ring + 8192 ? ring : s2 + kStep;
    mma_half_t(acc[0], st + kToB, st);
    wg_wait<1>();
    if (rel) mbar_arrive_cluster(rel_addr + 32);
    mbar_wait(sb + kBarFull + 48, nb >> 6);
    TRACE_KB(nb + 8);
    mma_half_t(acc[0], s2 + kToB, s2);
    mbar_wait(sb + kBarFull + 56, nb >> 6);
    TRACE_KB(nb + 16);
    mma_half_t(acc[0], s3 + kToB, s3);
    mma_half_t(acc[1], st + kToB + 256, st + z);
    mma_half_t(acc[1], s2 + kToB + 256, s2 + z);
    wg_wait<2>();
#pragma unroll
    for (int i = 0; i < 64; i++) asm volatile("" : "+f"(acc[0][i])::"memory");
    pre(0);
    mma_half_t(acc[1], s3 + kToB + 256, s3 + z);
    wg_wait<2>();
    if (rel) mbar_arrive_cluster(rel_addr + 40);
    pre(1);
    wg_wait<1>();
    if (rel) mbar_arrive_cluster(rel_addr + 48);
    if (signal) mbar_arrive(sb + kBarTurn + tile * 8);
    wg_wait<0>();
    if (rel) mbar_arrive_cluster(rel_addr + 56);
#pragma unroll
    for (int i = 0; i < 64; i++) asm volatile("" : "+f"(acc[1][i])::"memory");
  } else if constexpr (KIND == kStagger) {
    const uint32_t z = gridDim.y - 1, s2 = st + kStep;
    mma_half(acc[1], st + 64, st + kToB);
    wg_wait<1>();
    if (rel) mbar_arrive_cluster(rel_addr + 40);
    mbar_wait(sb + kBarFull + 56, nb >> 6);
    TRACE_KB(nb + 8);
    mma_half(acc[1], s2 + 64, s2 + kToB);
    mma_half(acc[0], st, st + z + kToB);
    pre(0);
    mma_half(acc[0], s2, s2 + z + kToB);
    wg_wait<2>();
#pragma unroll
    for (int i = 0; i < 96; i++) asm volatile("" : "+f"(acc[1][i])::"memory");
    pre(1);
    wg_wait<1>();
    if (rel) mbar_arrive_cluster(rel_addr + 48);
    pre(2);
    if (signal) mbar_arrive(sb + kBarTurn + tile * 8);
    pre(3);
    wg_wait<0>();
    if (rel) mbar_arrive_cluster(rel_addr + 56);
#pragma unroll
    for (int i = 0; i < 96; i++) asm volatile("" : "+f"(acc[0][i])::"memory");
  } else {
    mma_kblock<N, 1>(acc, st, st + kToB);
    wg_wait<2>();
    if (rel) mbar_arrive_cluster(rel_addr + prev);
    pre();
    wg_wait<1>();
    if (signal) mbar_arrive(sb + kBarTurn + tile * 8);
    wg_wait<0>();
    if (rel) mbar_arrive_cluster(rel_addr + (nb & 56));
    fence_acc<N>(acc);
  }
}

__device__ __forceinline__ void publish_stats(uint32_t sb, uint2* stat, int w, int lane, unsigned epoch) {
  const uint32_t row = sb + kSmX + (32 * w + lane) * 128;
  float s[4], q[4];
#pragma unroll
  for (int c = 0; c < 4; c++) s[c] = q[c] = 0.f;
  uint32_t nx[4];
  ldsm4(row + ((lane & 7) << 4), nx);
#pragma unroll 1
  for (int J = 1; J <= 16; J++) {
    const uint32_t r[4] = {nx[0], nx[1], nx[2], nx[3]};
    ldsm4(row + ((J >> 3) & 1) * kTileBytes + (((J ^ lane) & 7) << 4), nx);
#pragma unroll
    for (int c = 0; c < 4; c++) {
      const float lo = bf_lo(r[c]);
      s[c] += lo;
      q[c] = fmaf(lo, lo, q[c]);
      if (c & 1) yield_slot();
    }
#pragma unroll
    for (int c = 0; c < 4; c++) {
      const float hi = bf_hi(r[c]);
      s[c] += hi;
      q[c] = fmaf(hi, hi, q[c]);
      if (c & 1) yield_slot();
    }
  }
  const int t = lane & 3, g = lane >> 2;
#pragma unroll
  for (int c = 0; c < 2; c++) {
    s[c] = (t & 2 ? s[c + 2] : s[c]) + shfl_xor(t & 2 ? s[c] : s[c + 2], 2);
    q[c] = (t & 2 ? q[c + 2] : q[c]) + shfl_xor(t & 2 ? q[c] : q[c + 2], 2);
  }
  const float so = (t & 1 ? s[1] : s[0]) + shfl_xor(t & 1 ? s[0] : s[1], 1);
  const float qo = (t & 1 ? q[1] : q[0]) + shfl_xor(t & 1 ? q[0] : q[1], 1);
  asm volatile("st.relaxed.gpu.global.v2.u32 [%0], {%1, %2};" ::"l"(stat + 32 * w + 8 * t + g),
               "r"(tag_value(so, epoch)), "r"(tag_value(qo, epoch)) : "memory");
}

__device__ __forceinline__ void add_chunk(float (&a)[8], const uint4& v) {
  a[0] += bf_lo(v.x); a[1] += bf_hi(v.x);
  a[2] += bf_lo(v.y); a[3] += bf_hi(v.y);
  a[4] += bf_lo(v.z); a[5] += bf_hi(v.z);
  a[6] += bf_lo(v.w); a[7] += bf_hi(v.w);
}

__device__ __forceinline__ int helper_col(int id, int slab) {
  return (slab < 3 ? slab * kD : (slab - 3) * 512) + id * 128;
}
__device__ __forceinline__ void helper_cta(const CUtensorMap* map_q, const CUtensorMap* map_1, uint8_t* sm,
                                           uint32_t sb, int id, int warp) {
  constexpr int kRed = 6 * 32768, kBar = kRed + 2 * 4096;
  const int tid = threadIdx.x;
  if (warp == 8 && elect()) {
#pragma unroll
    for (int s = 0; s < 6; s++) {
      mbar_init(sb + kBar + s * 8, 1);
      mbar_init(sb + kBar + 64 + s * 8, 4);
    }
    fence_async_smem();
#pragma unroll
    for (int s = 0; s < 6; s++) {
      mbar_expect_tx(sb + kBar + s * 8, 32768);
      tma2d(sb + s * 32768, map_q, sb + kBar + s * 8, id * 128, s * 128);
    }
  }
  __syncthreads();
  if (warp == 8) {
    int slot = 0, ph = 0;
#pragma unroll 1
    for (int n = 6; n < 80; n++) {
      mbar_wait(sb + kBar + 64 + slot * 8, ph);
      if (elect()) {
        mbar_expect_tx(sb + kBar + slot * 8, 32768);
        tma2d(sb + slot * 32768, n < 24 ? map_q : map_1, sb + kBar + slot * 8, helper_col(id, n >> 3), (n & 7) * 128);
      }
      if (++slot == 6) slot = 0, ph ^= 1;
    }
  } else if (warp < 8) {
    if (tid == 0) *reinterpret_cast<unsigned*>(sm + kBar + 128) = atomicAdd(&g_ticket, 1u) / kGrid + 1;
    int slot = warp >> 2, ph = 0;
#pragma unroll 1
    for (int slab = 0; slab < 10; slab++) {
      float a[8];
#pragma unroll
      for (int e = 0; e < 8; e++) a[e] = 0.f;
#pragma unroll 1
      for (int box = 0; box < 4; box++) {
        mbar_wait_bounded(sb + kBar + slot * 8, ph);
        const uint4* p = reinterpret_cast<const uint4*>(sm + slot * 32768) + (tid & 127);
        uint4 v[16];
#pragma unroll
        for (int i = 0; i < 16; i++) v[i] = p[i * 128];
        __syncwarp();
        if (elect()) mbar_arrive(sb + kBar + 64 + slot * 8);
#pragma unroll
        for (int i = 0; i < 16; i++) add_chunk(a, v[i]);
        slot += 2;
        if (slot >= 6) slot -= 6, ph ^= 1;
      }
      float* red = reinterpret_cast<float*>(sm + kRed + (slab & 1) * 4096);
#pragma unroll
      for (int e = 0; e < 8; e++) a[e] += shfl_xor(a[e], 16);
      if ((tid & 16) == 0) {
        float4* d = reinterpret_cast<float4*>(red + warp * 128 + (tid & 15) * 8);
        d[0] = make_float4(a[0], a[1], a[2], a[3]);
        d[1] = make_float4(a[4], a[5], a[6], a[7]);
      }
      asm volatile("bar.sync 1, 256;" ::: "memory");
      if (warp < 4) {
        float t = 0.f;
#pragma unroll
        for (int q = 0; q < 8; q++) t += red[q * 128 + tid];
        st_relaxed(g_cs + (slab < 3 ? 0 : 3 * kD) + helper_col(id, slab) + tid,
                   tag_value(t, *reinterpret_cast<volatile unsigned*>(sm + kBar + 128)));
      }
    }
  }
}

__device__ __forceinline__ void colsum_strip(const CUtensorMap* map, uint8_t* sm, uint32_t sb, int col, int half,
                                             int lane, unsigned epoch) {
  const uint32_t bar = sb + kBarSlab + half * 16;
  const int buf = kSmStg + half * 8192;
  float a[8];
#pragma unroll
  for (int e = 0; e < 8; e++) a[e] = 0.f;
#pragma unroll 1
  for (int r = -2; r < 4; r++) {
    if (r >= 0) {
      mbar_wait(bar + (r & 1) * 8, r >> 1);
      const uint4* p = reinterpret_cast<const uint4*>(sm + buf + (r & 1) * 4096) + lane;
#pragma unroll 1
      for (int q = 0; q < 8; q += 4) {
        uint4 v[4];
#pragma unroll
        for (int u = 0; u < 4; u++) v[u] = p[(q + u) * 32];
#pragma unroll
        for (int u = 0; u < 4; u++) {
          a[0] += bf_lo(v[u].x); a[1] += bf_hi(v[u].x); a[2] += bf_lo(v[u].y); a[3] += bf_hi(v[u].y);
          yield_slot();
          a[4] += bf_lo(v[u].z); a[5] += bf_hi(v[u].z); a[6] += bf_lo(v[u].w); a[7] += bf_hi(v[u].w);
          yield_slot();
        }
      }
      fence_async_smem();
      __syncwarp();
    }
    if (r < 2 && elect()) {
      mbar_expect_tx(bar + (r & 1) * 8, 4096);
      tma2d(sb + buf + (r & 1) * 4096, map, bar + (r & 1) * 8, col, half * 512 + (r + 2) * 128);
    }
  }
#pragma unroll
  for (int e = 0; e < 4; e++) a[e] = (lane & 16 ? a[e + 4] : a[e]) + shfl_xor(lane & 16 ? a[e] : a[e + 4], 16);
#pragma unroll
  for (int e = 0; e < 2; e++) a[e] = (lane & 8 ? a[e + 2] : a[e]) + shfl_xor(lane & 8 ? a[e] : a[e + 2], 8);
  a[0] = (lane & 4 ? a[1] : a[0]) + shfl_xor(lane & 4 ? a[0] : a[1], 4);
  a[0] += shfl_xor(a[0], 2);
  if (!(lane & 2)) st_relaxed(g_cs + half * (3 * kD + kF) + col + (lane & 1) * 8 + (lane >> 2), tag_value(a[0], epoch));
}

constexpr float kGeluBeta = 0.3292034911525734f;
constexpr float kGeluK = 2.423681954311584f;

__device__ __forceinline__ void store_staged(uint8_t* dst, uint32_t stg) {
  fence_async_smem();
  __syncwarp();
  if (elect()) {
    bulk_store(dst, stg, 4096);
    bulk_commit();
  }
}

#define GY_MASK 5
#define GD 2
#define GF_MASK 3
#define GY(k) if ((GY_MASK >> k) & 1) yield_slot()
template <int J0, int J1>
__device__ __forceinline__ void fold_norm(float (&acc)[2][96], const float2 (&st)[4], const float4* vec) {
  float4 vn = vec[J0 * 4];
#pragma unroll
  for (int J = J0; J < J1; J++) {
    const float4 v = vn;
    if (J + 1 < J1) vn = vec[J * 4 + 4];
#pragma unroll
    for (int c = 0; c < 4; c++) {
      float& a0 = acc[c & 1][4 * J + (c & 2)];
      float& a1 = acc[c & 1][4 * J + (c & 2) + 1];
      a0 = fmaf(a0, st[c].x, fmaf(st[c].y, v.x, v.z));
      a1 = fmaf(a1, st[c].x, fmaf(st[c].y, v.y, v.w));
      asm volatile("" : "+f"(a0), "+f"(a1));
      if ((c & 1) && ((GF_MASK >> (c >> 1)) & 1)) yield_slot();
    }
  }
}

template <int CH, class Acquire>
__device__ __forceinline__ void gelu_chunk(const float (&acc)[2][96], uint32_t stg, int lane, uint8_t* prev,
                                           Acquire acquire) {
  uint32_t pk[8][4];
  float z[GD + 1][4];
  const uint32_t row = (stg + lane * 128) ^ ((lane & 7) << 4);
#define U(s, e) acc[(e) >> 1][4 * (CH * 8 + ((s) >> 1)) + 2 * ((s) & 1) + ((e) & 1)]
#pragma unroll
  for (int s = 0; s < 16 + GD; s++) {
    const int cur = s % (GD + 1), p1 = (s + GD) % (GD + 1), p2 = (s + 1) % (GD + 1), q = s - GD, jj = 2 * q - 24;
    const bool mid = s >= 1 && s < 17;
    if (mid) z[p1][0] = tanh_fast(z[p1][0]);
    if (s < 16) {
#pragma unroll
      for (int e = 0; e < 4; e++) {
        z[cur][e] = fmaf(U(s, e), U(s, e), kGeluK);
        asm volatile("" : "+f"(z[cur][e]));
      }
    }
    if (jj >= 0) stsm4(row ^ (jj << 4), pk[jj][0], pk[jj][1], pk[jj][2], pk[jj][3]);
    GY(0);
    if (mid) z[p1][1] = tanh_fast(z[p1][1]);
    if (q >= 0) {
      pk[q >> 1][2 * (q & 1)] = pack2(fmaf(U(q, 0), z[p2][0], U(q, 0)), fmaf(U(q, 1), z[p2][1], U(q, 1)));
      pk[q >> 1][2 * (q & 1) + 1] = pack2(fmaf(U(q, 2), z[p2][2], U(q, 2)), fmaf(U(q, 3), z[p2][3], U(q, 3)));
    }
    GY(1);
    if (mid) z[p1][2] = tanh_fast(z[p1][2]);
    if (s < 16) {
#pragma unroll
      for (int e = 0; e < 4; e++) {
        z[cur][e] *= U(s, e);
        asm volatile("" : "+f"(z[cur][e]));
      }
    }
    if (mid) z[p1][3] = tanh_fast(z[p1][3]);
    if (jj >= 0) stsm4(row ^ ((jj + 1) << 4), pk[jj + 1][0], pk[jj + 1][1], pk[jj + 1][2], pk[jj + 1][3]);
    GY(2);
    if (CH == 1 && s == 1) store_staged(prev, stg);
    if (q == 11) acquire();
  }
#undef U
}

__device__ __forceinline__ void scale_stats(float2 (&st)[4]) {
#pragma unroll
  for (int c = 0; c < 4; c++) {
    st[c].x *= kGeluBeta;
    st[c].y *= st[c].x;
  }
}

__device__ __forceinline__ void add_mean_term(float (&acc)[2][96], const float2 (&st)[4], uint8_t* sm, int tq,
                                              int lane) {
  const float2* cs = reinterpret_cast<const float2*>(sm + kSmCsQ) + tq * 96 + (lane & 3);
  float2 vn = cs[0];
#pragma unroll
  for (int J = 0; J < 24; J++) {
    const float2 v = vn;
    if (J < 23) vn = cs[J * 4 + 4];
#pragma unroll
    for (int c = 0; c < 4; c++) {
      acc[c & 1][4 * J + (c & 2)] = fmaf(st[c].y, v.x, acc[c & 1][4 * J + (c & 2)]);
      acc[c & 1][4 * J + (c & 2) + 1] = fmaf(st[c].y, v.y, acc[c & 1][4 * J + (c & 2) + 1]);
    }
    yield_slot();
  }
}

#define CV_MASK 1
#define HALO_AT 2
struct AttnRegs {
  uint32_t q[4][8], k[5][8], vt[5][8];
};
#define SCALED(c, J) pack2(acc[(c) & 1][4 * (J) + ((c) & 2)] * st[c].x, acc[(c) & 1][4 * (J) + ((c) & 2) + 1] * st[c].x)
__device__ __forceinline__ void convert_group(const float (&acc)[2][96], const float2 (&st)[4], AttnRegs& r, int c,
                                              int part) {
#pragma unroll
  for (int J = 0; J < 8; J++) {
    if (part == 0) r.q[c][J] = SCALED(c, J);
    if (part == 1) r.k[c + 1][J] = SCALED(c, 8 + J);
    if (part == 2) r.vt[c + 1][J] = transpose8(SCALED(c, 16 + J));
    if ((J & CV_MASK) == CV_MASK) yield_slot();
  }
}
#undef SCALED

__device__ __forceinline__ void convert_odd(const float (&acc)[2][96], const float2 (&st)[4], AttnRegs& r, int step,
                                            uint8_t* sm, uint32_t halo_bar, uint4* halo_out, bool send,
                                            unsigned epoch, int w, int lane) {
  if (step == 1) {
    convert_group(acc, st, r, 3, 2);
    convert_group(acc, st, r, 3, 1);
    if (w < 3) {
      uint2* hs = reinterpret_cast<uint2*>(sm + kSmHalo + w * 2048) + lane;
#pragma unroll
      for (int i = 0; i < 4; i++) {
        hs[i * 32] = make_uint2(r.k[4][2 * i], r.k[4][2 * i + 1]);
        hs[128 + i * 32] = make_uint2(r.vt[4][2 * i], r.vt[4][2 * i + 1]);
      }
      __syncwarp();
      if (elect()) mbar_arrive(halo_bar + w * 8);
    } else if (send) {
#pragma unroll
      for (int i = 0; i < 4; i++) {
        st_packet(halo_out + lane + i * 32, r.k[4][2 * i], r.k[4][2 * i + 1], epoch);
        st_packet(halo_out + lane + 128 + i * 32, r.vt[4][2 * i], r.vt[4][2 * i + 1], epoch);
      }
    }
  } else if (step == 2) {
    convert_group(acc, st, r, 1, 2);
  } else {
    convert_group(acc, st, r, 1, 1);
    convert_group(acc, st, r, 3, 0);
    convert_group(acc, st, r, 1, 0);
  }
}

__device__ __forceinline__ void epilogue_attn(const float (&acc)[2][96], const float2 (&st)[4], AttnRegs& r,
                                              uint8_t* sm, uint32_t sb, int layer, int tq, int b, int j,
                                              unsigned epoch, int tile, int w, int lane) {
  const int t = lane & 3, g = lane >> 2;
  const int hp = j + 8 * tq, att = 2 * layer + tq;
  auto& q = r.q;
  auto& k = r.k;
  auto& vt = r.vt;
  const bool first = w == 0 && (b & 7) == 0;
  const uint4* gh = g_halo + ((layer * 16 + b - 1) * 16 + hp) * 256 + lane;
  uint32_t tag[8];
#define LOAD_HALO()                                                                                    \
  _Pragma("unroll") for (int i = 0; i < 4; i++) {                                                      \
    ld_packet(gh + i * 32, k[0][2 * i], k[0][2 * i + 1], tag[i]);                                      \
    ld_packet(gh + 128 + i * 32, vt[0][2 * i], vt[0][2 * i + 1], tag[4 + i]);                          \
  }
#define AWAIT_HALO()                                                                                   \
  for (unsigned spins = 0;; spins++) {                                                                 \
    const unsigned d0 = (tag[0] ^ epoch) | (tag[1] ^ epoch) | (tag[2] ^ epoch) | (tag[3] ^ epoch);     \
    const unsigned d1 = (tag[4] ^ epoch) | (tag[5] ^ epoch) | (tag[6] ^ epoch) | (tag[7] ^ epoch);     \
    if (__all_sync(0xffffffffu, (d0 | d1) == 0)) break;                                                \
    if (spins > kSpinLimit) __trap();                                                                  \
    LOAD_HALO();                                                                                       \
  }
#pragma unroll
  for (int c = 0; c <= 6; c++) {
    if (c == HALO_AT) {
#pragma unroll
      for (int i = 0; i < 8; i++) k[0][i] = vt[0][i] = tag[i] = 0u;
      if (w > 0) {
        mbar_wait(sb + kBarHalo + (att * 3 + w - 1) * 8, 0);
        const uint2* hs = reinterpret_cast<const uint2*>(sm + kSmHalo + (w - 1) * 2048) + lane;
#pragma unroll
        for (int i = 0; i < 4; i++) {
          const uint2 a = hs[i * 32], d = hs[128 + i * 32];
          k[0][2 * i] = a.x; k[0][2 * i + 1] = a.y;
          vt[0][2 * i] = d.x; vt[0][2 * i + 1] = d.y;
        }
      } else if (!first) {
        LOAD_HALO();
      }
    }
    if (c < 6) convert_group(acc, st, r, 2 * (c & 1), 2 - (c >> 1));
  }
  TRACE_AT(tile, 8);
  if (w == 0 && !first) AWAIT_HALO();
  constexpr float kScale = 0.17677669529663687f * 1.4426950408889634f;
  const bool own0 = 2 * t <= g, own1 = 2 * t + 1 <= g;
  const uint32_t own_mask = (own0 ? 0xffffu : 0u) | (own1 ? 0xffff0000u : 0u);
  const uint32_t stg = sb + kSmStg + w * 4096;
  const uint32_t orow = stg + (lane & 7) * 128, ochunk = (lane >> 3) ^ (lane & 7);
  TRACE_AT(tile, 9);
  mbar_wait(sb + kBarPause + att * 8, 0);
  TRACE_AT(tile, 10);

  float s[2][6][4], o[2][4][2][4];
  auto scores = [&](int hd, int m) {
    const int ca = 2 * (m / 3), kg = ca + m % 3;
#pragma unroll
    for (int e = 0; e < 4; e++) s[hd][m][e] = 0.f;
#pragma unroll
    for (int J = 4 * hd; J < 4 * hd + 4; J += 2)
      mma16816(s[hd][m], q[ca][J], q[ca + 1][J], q[ca][J + 1], q[ca + 1][J + 1], k[kg][J], k[kg][J + 1]);
  };
  auto attend = [&](int c0, int c1) {
    float v0[2][4], v1[2][4], m[2][4];
#define UNITS _Pragma("unroll") for (int hd = 0; hd < 2; hd++) _Pragma("unroll") for (int c = c0; c < c1; c++)
    UNITS {
      const int mp = 3 * (c >> 1) + (c & 1), r = 2 * (c & 1);
      float p0 = s[hd][mp][r], p1 = s[hd][mp][r + 1];
      if (c == 0 && first) p0 = p1 = -INFINITY;
      v0[hd][c] = own0 ? s[hd][mp + 1][r] : p0;
      v1[hd][c] = own1 ? s[hd][mp + 1][r + 1] : p1;
      m[hd][c] = fmaxf(v0[hd][c], v1[hd][c]);
    }
    UNITS m[hd][c] = fmaxf(m[hd][c], shfl_xor(m[hd][c], 1));
    UNITS m[hd][c] = fmaxf(m[hd][c], shfl_xor(m[hd][c], 2));
    UNITS {
      const float nm = -m[hd][c] * kScale;
      v0[hd][c] = ex2(fmaf(v0[hd][c], kScale, nm));
      v1[hd][c] = ex2(fmaf(v1[hd][c], kScale, nm));
      m[hd][c] = v0[hd][c] + v1[hd][c];
    }
    UNITS m[hd][c] += shfl_xor(m[hd][c], 1);
    UNITS m[hd][c] += shfl_xor(m[hd][c], 2);
    UNITS {
      const float inv = rcp(m[hd][c]);
      const uint32_t p = pack2(v0[hd][c] * inv, v1[hd][c] * inv);
#pragma unroll
      for (int ds = 0; ds < 2; ds++) {
        const int J = 4 * hd + 2 * ds;
#pragma unroll
        for (int e = 0; e < 4; e++) o[hd][c][ds][e] = 0.f;
        if (c & 1) {
          mma16816(o[hd][c][ds], vt[c][J], vt[c][J + 1], vt[c + 1][J], vt[c + 1][J + 1], p & ~own_mask, p & own_mask);
        } else {
          mma1688(o[hd][c][ds], vt[c + 1][J], vt[c + 1][J + 1], p & own_mask);
          mma1688(o[hd][c][ds], vt[c][J], vt[c][J + 1], p & ~own_mask);
        }
      }
    }
  };
  auto stage = [&](int c0, int c1) {
    UNITS stsm4_t(orow + c * 1024 + ((ochunk ^ (4 * hd)) << 4), pack2(o[hd][c][0][0], o[hd][c][0][1]),
                  pack2(o[hd][c][0][2], o[hd][c][0][3]), pack2(o[hd][c][1][0], o[hd][c][1][1]),
                  pack2(o[hd][c][1][2], o[hd][c][1][3]));
#undef UNITS
  };
#pragma unroll
  for (int hd = 0; hd < 2; hd++)
#pragma unroll
    for (int m = 0; m < 6; m++) scores(hd, m);
  attend(0, 4);
  yield_slot();
  if (tq == 0 && elect()) mbar_arrive(sb + kBarResume + att * 8);
  TRACE_AT(tile, 11);
  stage(0, 4);
#undef AWAIT_HALO
#undef LOAD_HALO
  fence_async_smem();
  __syncwarp();
  if (tq == 1 && elect()) mbar_arrive(sb + kBarResume + att * 8);
  TRACE_AT(tile, 12);
  if (elect()) {
    bulk_store(g_o + (b * 16 + hp) * kTileBytes + w * 4096, stg, 4096);
    bulk_commit();
    bulk_wait();
    TRACE_AT(tile, 13);
    mbar_arrive(sb + kBarEpi + tile * 8);
  }
  __syncwarp();
}

__device__ __forceinline__ void gather_stats(uint8_t* sm, const uint2* stat, int r, unsigned epoch) {
  uint2 a[8];
#pragma unroll 1
  for (unsigned spins = 0;; spins++) {
    unsigned diff = 0;
#pragma unroll
    for (int i = 0; i < 8; i++) {
      a[i] = ld_relaxed2(stat + i * 128 + r);
      diff |= (a[i].x ^ epoch) | (a[i].y ^ epoch);
    }
    if (__all_sync(0xffffffffu, (diff & 7u) == 0)) break;
    if (spins > kSpinLimit) __trap();
  }
  float s = 0.f, q = 0.f;
#pragma unroll
  for (int i = 0; i < 8; i++) {
    s += untag_value(a[i].x);
    q += untag_value(a[i].y);
  }
  const float mean = s * (1.f / 1024.f);
  const float var = fmaxf(fmaf(-mean, mean, q * (1.f / 1024.f)), 0.f);
  reinterpret_cast<float2*>(sm + kSmStat)[r] = make_float2(rsqrtf(var + 1e-5f), -mean);
}

__device__ __forceinline__ void gather_colsums_qkv(uint8_t* sm, int tq, int j, int lane, unsigned epoch) {
  const uint2* src = reinterpret_cast<const uint2*>(g_cs + (j + 8 * tq) * 64) + lane;
  uint2 v[3], u[3];
  for (unsigned spins = 0;; spins++) {
    unsigned diff = 0;
#pragma unroll
    for (int q = 0; q < 3; q++) {
      v[q] = ld_relaxed2(src + q * (kD / 2));
      u[q] = make_uint2(epoch & 7u, epoch & 7u);
      if (tq) u[q] = ld_relaxed2(src + (q * kD + 3 * kD + kF) / 2);
    }
#pragma unroll
    for (int q = 0; q < 3; q++) diff |= (v[q].x ^ epoch) | (v[q].y ^ epoch) | (u[q].x ^ epoch) | (u[q].y ^ epoch);
    if (__all_sync(0xffffffffu, (diff & 7u) == 0)) break;
    if (spins > kSpinLimit) __trap();
  }
#pragma unroll
  for (int q = 0; q < 3; q++)
    reinterpret_cast<float2*>(sm + kSmCsQ)[tq * 96 + q * 32 + lane] =
        make_float2(untag_value(v[q].x) + untag_value(u[q].x), untag_value(v[q].y) + untag_value(u[q].y));
}

__device__ __forceinline__ void gather_colsums_w1(uint8_t* sm, const __nv_bfloat16* b1, int j, int lane,
                                                  unsigned epoch) {
#pragma unroll 1
  for (int blk = 0; blk < 7; blk++) {
    const int pair = 32 * (blk + (blk < 3 ? 3 * j : blk < 5 ? 21 + 2 * j : 35 + 2 * j)) + lane;
    const uint32_t bias = reinterpret_cast<const uint32_t*>(b1)[pair];
    uint2 v;
    for (unsigned spins = 0;; spins++) {
      v = ld_relaxed2(reinterpret_cast<const uint2*>(g_cs + 3 * kD) + pair);
      if (__all_sync(0xffffffffu, (((v.x ^ epoch) | (v.y ^ epoch)) & 7u) == 0)) break;
      if (spins > kSpinLimit) __trap();
    }
    reinterpret_cast<float4*>(sm + kSmV1)[blk * 32 + lane] =
        make_float4(untag_value(v.x), untag_value(v.y), kGeluBeta * bf_lo(bias), kGeluBeta * bf_hi(bias));
  }
}

#define FINE 3
#define LATE_REL2 1
#define STRIP_GATE kBarInit
#define XI_MASK 1
#define STAGE_YIELD 1
#define PAUSE_QKV2 7
#define PAUSE_WO 2

__global__ void __cluster_dims__(2, 1, 1) __launch_bounds__(384, 1)
fused_layers_kernel(const __grid_constant__ CUtensorMap map_x, const __grid_constant__ CUtensorMap map_out,
                    const __grid_constant__ CUtensorMap map_qkv, const __grid_constant__ CUtensorMap map_wo,
                    const __grid_constant__ CUtensorMap map_w1a, const __grid_constant__ CUtensorMap map_w1b,
                    const __grid_constant__ CUtensorMap map_w2, const __grid_constant__ CUtensorMap map_csq,
                    const __grid_constant__ CUtensorMap map_cs1, const __grid_constant__ CUtensorMap map_css,
                    const __grid_constant__ Params prm) {
  extern __shared__ __align__(1024) uint8_t sm[];
  if (threadIdx.x < 128 && blockIdx.x < kCtas) TRACE_AT(15, 1);
  const uint32_t sb = __shfl_sync(0xffffffffu, smem_u32(sm), 0);
  const int warp = __shfl_sync(0xffffffffu, threadIdx.x >> 5, 0), lane = threadIdx.x & 31;
  const int cta = blockIdx.x, rank = cta & 1, cl = cta >> 1;
  const int grp = cl < 4 ? 0 : cl < 36 ? (cl - 4) & 7 : 1 + (cl - 36) % 7;
  const int j = cl < 4 ? 4 + cl : cl < 36 ? (cl - 4) >> 3 : 4 + (cl - 36) / 7;
  const int b = 2 * grp + rank;
  const int xcol = (b >> 3) * kD, xrow = (b & 7) * 128;

  if (cta >= kCtas) {
    helper_cta(&map_csq, &map_cs1, sm, sb, cta - kCtas, warp);
    return;
  }
  if ((warp < 8 || warp == 9) && elect()) {
    if (warp == 9) {
#pragma unroll
      for (int s = 0; s < 8; s++) mbar_init(sb + kBarFull + s * 8, 1);
      fence_async_smem();
#pragma unroll
      for (int s = 0; s < 4; s++) {
        const uint32_t full = sb + kBarFull + s * 8, dst = sb + kSmRing + s * 40960;
        mbar_expect_tx(full, 40960);
        tma2d(dst, &map_x, full, xcol + (s & 1) * 64, xrow);
        tma3d(dst + kTileBytes, &map_qkv, full, (j + 4 * (s & 2)) * 64, (s & 1) * 64, 0);
        tma3d(dst + kTileBytes + 12288, &map_qkv, full, (j + 4 * (s & 2)) * 64, (s & 1) * 64 + 32, 0);
      }
    } else {
      if (sb & 1023) __trap();
#pragma unroll
      for (int s = 0; s < 16; s++) mbar_init(sb + kBarTurn + warp * 128 + s * 8, warp < 5 ? 1 : warp == 5 ? 2 : 4);
    }
    asm volatile("fence.mbarrier_init.release.cluster;" ::: "memory");
  }
  __syncwarp();
  asm volatile("barrier.cluster.arrive.relaxed.aligned;" ::: "memory");

  if (warp >= 8) {
    asm volatile("setmaxnreg.dec.sync.aligned.u32 40;");
    if (warp < 10) {
      asm volatile("barrier.cluster.wait.aligned;" ::: "memory");
      uint32_t nb = 32, off = 0, kb = 0;
#define RING_STEP(WAIT, ISSUE)                                            \
  do {                                                                    \
    const uint32_t mb = nb - depth, full = sb + kBarFull + (nb & 56);     \
    if (kb == skip) kb += inc;                                            \
    mbar_wait(sb + kBarEmpty + (mb & 56), mb >> 6);                       \
    WAIT;                                                                 \
    if (elect()) { ISSUE; }                                               \
    TRACE_ISSUE(9 - warp, nb);                                            \
    kb += inc;                                                            \
    off = off == wrap ? 0 : off + step;                                   \
    nb += 8;                                                              \
  } while (nb != nend)
#pragma unroll 1
      for (int sg = 0; sg < kSegs; sg++) {
        const uint32_t e = prm.seg[sg];
        const int ty = e & 7, mode = (e >> 15) & 3, reset = (e >> 24) & 3;
        const uint32_t nend = nb + (e & 0x1f8);
        const uint32_t step = (e >> 17) & 1 ? 40960 : 32768, wrap = 163840 - step;
        const uint32_t depth = (e >> 18) & 1 ? 40 : 32;
        if (reset) off = reset == 1 ? 0 : reset == 2 ? 40960 : 131072;
        const uint32_t own = ty == 2 ? 8 + j : 2 * j;
        if (mode != kModeContinue) kb = mode == kModeHead ? own : (e >> 9) & 63;
        const uint32_t inc = mode >= kModeSkip && ty != 2 ? 2 : 1, skip = mode >= kModeSkip ? own + (kb & 1) : 255;
        if (warp == 8) {
          const CUtensorMap* map = ty < 2 ? &map_qkv : ty == 2 ? &map_wo : ty == 3 ? &map_w1a : ty < 6 ? &map_w1b : &map_w2;
          const int c0 = ty < 2 ? (j + 8 * ty) * 64 : 0;
          const int c2 = ty < 2 ? 0 : ty == 3 ? 3 * j : ty == 4 ? 24 + 2 * j : ty == 5 ? 40 + 2 * j : 2 * j;
          const uint32_t half = (ty < 2 || ty == 3) ? 12288 : 8192;
          const uint32_t bytes = 2 * half + (mode == kModeHead ? 0 : kTileBytes);
          const uint32_t dst = sb + kSmRing + kTileBytes + rank * half;
#pragma unroll 1
          RING_STEP(, mbar_expect_tx(full, bytes); tma3d_mc(dst + off, map, full, c0, kb * 64 + rank * 32, c2));
        } else if (mode == kModeHead) {
          off += ((nend - nb) >> 3) * step;
          nb = nend;
          if (off >= 163840) off -= 163840;
        } else if (sg < 2) {
#pragma unroll 1
          RING_STEP(, tma2d(sb + kSmRing + off, &map_x, full, xcol + kb * 64, xrow));
        } else {
          const uint8_t* src = ty == 6 ? g_h + b * 56 * kTileBytes : (ty == 2 ? g_o : g_x) + b * 16 * kTileBytes;
          const int dep = (e >> 19) & 31;
          if (dep < 28) mbar_wait(sb + kBarReady + dep * 8, 0);
          if ((dep & 30) == 28) {
#pragma unroll 1
            RING_STEP(mbar_wait(sb + kBarSrc + ((kb << (4 - inc)) & 56), dep),
                      bulk_load(sb + kSmRing + off, src + kb * kTileBytes, kTileBytes, full));
          } else {
#pragma unroll 1
            RING_STEP(, bulk_load(sb + kSmRing + off, src + kb * kTileBytes, kTileBytes, full));
          }
        }
      }
#undef RING_STEP
    } else {
      unsigned epoch = 0;
      if (warp == 10) {
        if (lane == 0) epoch = atomicAdd(&g_ticket, 1u) / kGrid + 1;
        *reinterpret_cast<unsigned*>(sm + kSmEpoch) = __shfl_sync(0xffffffffu, epoch, 0);
        asm volatile("barrier.cluster.wait.aligned;" ::: "memory");
        if (elect()) mbar_arrive(sb + kBarEpoch);
      } else {
        asm volatile("barrier.cluster.wait.aligned;" ::: "memory");
        mbar_wait_bounded(sb + kBarFull, 0);
        if (elect()) {
          mbar_expect_tx(sb + kBarInit, 32768);
          tma2d(sb + kSmX, &map_x, sb + kBarInit, xcol + j * 128, xrow);
          tma2d(sb + kSmX + kTileBytes, &map_x, sb + kBarInit, xcol + j * 128 + 64, xrow);
        }
        const uint2 u = reinterpret_cast<const uint2*>(prm.b2)[32 * j + lane];
        reinterpret_cast<float4*>(sm + kSmB2)[lane] = make_float4(
            2.f * kGeluBeta * bf_lo(u.x), 2.f * kGeluBeta * bf_hi(u.x), 2.f * kGeluBeta * bf_lo(u.y), 2.f * kGeluBeta * bf_hi(u.y));
      }
      mbar_wait_bounded(sb + kBarEpoch, 0);
      epoch = *reinterpret_cast<volatile unsigned*>(sm + kSmEpoch);
      if (cta < 96) {
        mbar_wait_bounded(sb + STRIP_GATE, 0);
        colsum_strip(&map_css, sm, sb, (cta >> 5) * kD + 512 + (cta & 31) * 16, warp - 10, lane, epoch);
      }
      gather_colsums_qkv(sm, 11 - warp, j, lane, epoch);
      __syncwarp();
      if (elect()) mbar_arrive(sb + kBarCs + (11 - warp) * 8);
     if (warp == 10) {
#pragma unroll 1
      for (int i = 0; i < kTiles - 1; i++) {
        const bool xt = i == 2 || i == 6 || i == 9;
        const unsigned* line = g_flag + (i * 16 + b) * 32;
        mbar_wait(sb + (xt ? kBarX + (i >> 2) * 16 : kBarEpi + i * 8), 0);
        if ((xt && (FINE & 1)) || ((i == 1 || i == 8) && (FINE & 2))) {
          unsigned todo = 0xff, spins = 0;
          do {
            const unsigned now = __ballot_sync(0xffffffffu, ld_relaxed(line + (lane & 7)) == epoch) & todo;
            if (now) {
              asm volatile("fence.acquire.gpu;\nfence.proxy.async.global;" ::: "memory");
              if ((now >> lane) & 1) mbar_arrive(sb + kBarSrc + lane * 8);
              todo ^= now;
            }
            if (++spins > kSpinLimit) __trap();
          } while (todo);
        } else {
          wait_flags(line + (lane & 7), epoch);
          if (elect()) mbar_arrive(sb + kBarReady + i * 8);
        }
        if (xt) {
          wait_flags(line + 8 + (lane & 7), epoch);
          if (elect()) mbar_arrive(sb + kBarReady + (14 + (i >> 2)) * 8);
        }
      }
     } else {
#pragma unroll 1
      for (int i = 0; i < kTiles - 1; i++) {
        if (i == 3) {
          gather_colsums_w1(sm, prm.b1, j, lane, epoch);
          __syncwarp();
          if (elect()) mbar_arrive(sb + kBarCs + 16);
        }
        const bool xt = i == 2 || i == 6 || i == 9;
#pragma unroll 1
        for (int h = 0; h < (xt ? 2 : 1); h++) {
          mbar_wait_bounded(sb + (xt ? kBarX + (i >> 2) * 16 + 8 * h : kBarEpi + i * 8), 0);
          const int ty = i >= 7 ? i - 7 : i;
          if (ty >= 2 && elect()) {
            uint8_t* dst = xt ? g_x + (b * 16 + 2 * j + h) * kTileBytes
                              : g_h + (b * 56 + 1 + (ty == 3 ? 3 * j : 16 * ty - 40 + 2 * j)) * kTileBytes;
            bulk_store(dst, sb + (xt ? kSmX + h * kTileBytes : kSmStg), kTileBytes);
            bulk_commit();
            bulk_wait();
            if (!xt) mbar_arrive(sb + kBarFree + i * 8);
          }
          if (LATE_REL2 && h == 1) mbar_wait_bounded(sb + kBarFull + 32, i == 2 ? 6 : i == 6 ? 19 : 25);
          __syncwarp();
          if (elect()) st_release(&g_flag[(i * 16 + b) * 32 + h * 8 + j], epoch);
          __syncwarp();
        }
      }
#pragma unroll 1
      for (int h = 0; h < 2; h++) {
        mbar_wait_bounded(sb + kBarX + 48 + 8 * h, 0);
        if (elect()) {
          tma2d_store(&map_out, sb + kSmX + h * kTileBytes, xcol + j * 128 + h * 64, xrow);
          bulk_commit();
          if (h == 1) bulk_wait_read();
        }
      }
     }
    }
    __syncwarp();
    asm volatile("barrier.cluster.arrive.relaxed.aligned;\nbarrier.cluster.wait.aligned;" ::: "memory");
  } else {
    asm volatile("setmaxnreg.inc.sync.aligned.u32 232;");
    asm volatile("barrier.cluster.wait.aligned;" ::: "memory");
    const int wg = warp >> 2, w = warp & 3;
    const bool rel = (threadIdx.x & 95) == 0;
    const uint32_t rel_addr = mapa(sb + kBarEmpty, w & 1);
    if (wg == 1) TRACE_AT(15, 0);
#define EPOCH (*reinterpret_cast<volatile unsigned*>(sm + kSmEpoch))

#pragma unroll 1
    for (int i = wg; i < kTiles; i += 2) {
      const int layer = i >= 7, ty = i - 7 * layer;
      TRACE_AT(i, 15);
      float acc[2][96];
      if (ty == 2 || ty == 6) {
        const int lane = lane_id();
        const uint32_t xa = sb + kSmX + ((lane >> 4) * 8 + (lane & 7)) * 128 + (((2 * w + ((lane >> 3) & 1)) ^ (lane & 7)) << 4);
        const float up = ty == 6 ? 2.f * kGeluBeta : 1.f, dn = ty == 6 ? 0.5f / kGeluBeta : 1.f;
#pragma unroll
        for (int h = 0; h < 2; h++) {
          const float* b2 = reinterpret_cast<const float*>(sm + kSmB2) + 64 * h + 16 * w + (lane >> 2);
          const float bias[2] = {ty == 6 ? b2[0] : 0.f, ty == 6 ? b2[8] : 0.f};
#pragma unroll
          for (int p = 0; p < 8; p++) {
            uint32_t r[4];
            ldsm4_t(xa + h * kTileBytes + p * 2048, r);
#pragma unroll
            for (int m = 0; m < 4; m++) {
              acc[h][8 * p + 2 * m] = fmaf(bf_lo(r[m]), up, bias[m & 1]);
              acc[h][8 * p + 2 * m + 1] = fmaf(bf_hi(r[m]), up, bias[m & 1]);
              asm volatile("" : "+f"(acc[h][8 * p + 2 * m]), "+f"(acc[h][8 * p + 2 * m + 1]));
              if ((m & XI_MASK) == XI_MASK) yield_slot();
            }
          }
        }
        auto stage = [&](int qt) {
          const int h = qt >> 1;
#pragma unroll
          for (int p = 4 * (qt & 1); p < 4 * (qt & 1) + 4; p++) {
            const float* a = &acc[h][8 * p];
            stsm4_t(xa + h * kTileBytes + p * 2048, pack2(a[0] * dn, a[1] * dn), pack2(a[2] * dn, a[3] * dn),
                    pack2(a[4] * dn, a[5] * dn), pack2(a[6] * dn, a[7] * dn));
            if (STAGE_YIELD || (p & 3) == 3) yield_slot();
          }
          if (qt & 1) {
            fence_async_smem();
            __syncwarp();
            if (elect()) mbar_arrive(sb + kBarX + (i >> 2) * 16 + 8 * h);
            TRACE_AT(i, 8 + h);
          }
        };
        mainloop<128, kResid>(acc, sb, i, layer * 152 + ty * 16, ty == 6 ? 4 : 0, ty == 6 ? 56 : 16,
                            ty == 2 ? PAUSE_WO : -1, 2 * layer + 1, rel_addr, rel, ty == 2 ? 8 : -1, stage);
        TRACE_AT(i, 2);
        stage(2);
        stage(3);
      } else {
        const int xver = 2 * layer + (ty >= 3);
        const uint32_t stg = sb + kSmStg + w * 4096;
        const float4* vec = reinterpret_cast<const float4*>(sm + kSmV1) + (ty == 3 ? 0 : 64 * ty - 160);
        int lane;
        uint8_t* hdst = g_h + (b * 56 + (ty == 3 ? 3 * j : 16 * ty - 40 + 2 * j)) * kTileBytes + w * 4096;
        float2 st[4];
        unsigned epoch;
        auto pre = [&] {
          lane = lane_id();
          if (ty < 4) mbar_wait(sb + (ty == 1 ? kBarEpi + (i - 1) * 8 : kBarStat + xver * 8), 0);
#pragma unroll
          for (int c = 0; c < 4; c++) st[c] = reinterpret_cast<const float2*>(sm + kSmStat)[32 * w + 8 * c + (lane >> 2)];
          epoch = EPOCH;
        };
        auto team_stats = [&] {
          uint2* stat = g_stat + (xver * 16 + b) * 1024;
          lane = lane_id();
          publish_stats(sb, stat + j * 128, w, lane, EPOCH);
          gather_stats(sm, stat, 32 * w + lane, EPOCH);
          __syncwarp();
          if (elect()) mbar_arrive(sb + kBarStat + xver * 8);
          TRACE_AT(i, 14);
        };
        if (ty < 4) {
          AttnRegs ar;
          auto odd = [&](int step) {
            if (step == 0) pre();
            else convert_odd(acc, st, ar, step, sm, sb + kBarHalo + (xver + ty) * 24,
                             g_halo + ((layer * 16 + b) * 16 + j + 8 * ty) * 256, (b & 7) != 7, epoch, w, lane);
          };
          head_blocks<192>(acc, sb, layer * 152 + (ty < 2 ? 2 * ty : 48), ty < 2 ? 2 * ty : 1, xver, rel_addr, rel);
          if (ty == 1) {
            if (i == 1) {
              mbar_wait(sb + kBarEpoch, 0);
              mbar_wait(sb + kBarInit, 0);
            }
            team_stats();
            epoch = 0;
#pragma unroll
            for (int c = 0; c < 4; c++) st[c] = reinterpret_cast<const float2*>(sm + kSmStat)[32 * w + 8 * c + (lane >> 2)];
          } else {
            mainloop<192, kPlain>(acc, sb, i, layer * 152 + (ty ? 52 : 4), ty ? 1 : 0, 14, -1, 0, rel_addr, rel, 0, pre);
            TRACE_AT(i, 2);
            if (ty == 3) goto wide_gelu;
          }
          if (layer == 0) mbar_wait(sb + kBarCs + ty * 8, 0);
          add_mean_term(acc, st, sm, ty, lane);
          if (ty == 1) {
            mainloop<192, kStagger>(acc, sb, i, layer * 152 + 18, 2, 14, PAUSE_QKV2, xver, rel_addr, rel, 0, odd);
            TRACE_AT(i, 2);
          } else {
            odd(1);
            odd(2);
            odd(3);
          }
          epilogue_attn(acc, st, ar, sm, sb, layer, ty, b, j, epoch, i, w, lane);
          TRACE_AT(i, 3);
          continue;
        wide_gelu:
          if (i == 3) mbar_wait(sb + kBarCs + 16, 0);
          scale_stats(st);
          fold_norm<16, 24>(acc, st, vec + (lane & 3));
          TRACE_AT(i, 11);
          gelu_chunk<2>(acc, stg, lane, nullptr, [] {});
          TRACE_AT(i, 12);
          fold_norm<0, 2>(acc, st, vec + (lane & 3));
          store_staged(hdst + 2 * kTileBytes, stg);
          fold_norm<2, 16>(acc, st, vec + (lane & 3));
        } else {
          if (ty == 4) {
            head_blocks<128>(acc, sb, layer * 152 + 50, 3, xver, rel_addr, rel);
            team_stats();
            mainloop<128, kPlain>(acc, sb, i, layer * 152 + 66, 4, 14, -1, 0, rel_addr, rel, 0, pre);
          } else {
            mainloop<128, kFresh>(acc, sb, i, layer * 152 + 80, 3, 16, -1, 0, rel_addr, rel, 0, pre);
          }
          TRACE_AT(i, 2);
          if (i == 4) mbar_wait(sb + kBarCs + 16, 0);
          scale_stats(st);
          fold_norm<0, 16>(acc, st, vec + (lane & 3));
        }
        auto own_store_done = [] {
          if (elect()) bulk_wait();
          __syncwarp();
        };
        TRACE_AT(i, 8);
        gelu_chunk<0>(acc, stg, lane, nullptr, [&] {
          if (ty == 3) own_store_done();
          else mbar_wait(sb + kBarFree + (i - 1) * 8, 0);
        });
        TRACE_AT(i, 9);
        gelu_chunk<1>(acc, stg, lane, hdst, own_store_done);
        TRACE_AT(i, 10);
        fence_async_smem();
        __syncwarp();
        if (elect()) mbar_arrive(sb + kBarEpi + i * 8);
      }
      TRACE_AT(i, 3);
    }
#undef EPOCH
    asm volatile("barrier.cluster.arrive.relaxed.aligned;\nbarrier.cluster.wait.aligned;" ::: "memory");
    if (wg == 1) TRACE_AT(15, 2);
  }
}

void build_segments(uint32_t* seg) {
  int n = 0, fine = 0;
  auto per_source = [&](int kind, int dep) { return (FINE & kind) ? 28 + (fine++ & 1) : dep; };
  auto add = [&](int ty, int cnt, int kb0, int mode, int wide, int depth5, int dep, int reset) {
    seg[n++] = ty | cnt << 3 | kb0 << 9 | mode << 15 | wide << 17 | depth5 << 18 | dep << 19 | reset << 24;
  };
  for (int l = 0; l < 2; l++) {
    const int t = 7 * l;
    if (l == 0) {
      add(0, 14, 2, kModePlain, 1, 0, 31, 1);
      add(1, 14, 2, kModePlain, 1, 0, 31, 0);
    } else {
      add(0, 2, 0, kModeHead, 1, 0, 31, 1);
      add(1, 2, 0, kModeHead, 1, 0, 31, 0);
      add(0, 7, 0, kModeSkip, 1, 0, per_source(1, 6), 0);
      add(0, 7, 1, kModeSkip, 1, 0, 15, 0);
      add(1, 7, 0, kModeSkip, 1, 0, 31, 0);
      add(1, 7, 1, kModeSkip, 1, 0, 31, 0);
    }
    add(2, 4, 0, kModePlain, 0, 0, t, 1);
    add(2, 4, 4, kModePlain, 0, 1, 31, 0);
    add(2, 1, 0, kModeHead, 0, 1, 31, 0);
    add(2, 7, 8, kModeSkip, 0, 1, per_source(2, t + 1), 0);
    add(3, 2, 0, kModeHead, 1, 0, 31, 2);
    add(4, 2, 0, kModeHead, 1, 0, 31, 0);
    add(3, 7, 0, kModeSkip, 1, 0, per_source(1, t + 2), 0);
    add(3, 7, 1, kModeSkip, 1, 0, 14 + 2 * l, 0);
    add(4, 4, 0, kModeSkip, 0, 0, 31, 3);
    add(4, 3, 0, kModeContinue, 0, 1, 31, 0);
    add(4, 7, 1, kModeSkip, 0, 1, 31, 0);
    add(5, 16, 0, kModePlain, 0, 1, 31, 0);
    add(6, 24, 0, kModePlain, 0, 1, t + 3, 0);
    add(6, 16, 24, kModePlain, 0, 1, t + 4, 0);
    add(6, 16, 40, kModePlain, 0, 1, t + 5, 0);
  }
}

typedef CUresult (*EncodeTiledFn)(CUtensorMap*, CUtensorMapDataType, cuuint32_t, void*, const cuuint64_t*,
                                  const cuuint64_t*, const cuuint32_t*, const cuuint32_t*, CUtensorMapInterleave,
                                  CUtensorMapSwizzle, CUtensorMapL2promotion, CUtensorMapFloatOOBfill);

CUtensorMap make_map(EncodeTiledFn enc, const void* p, int rank, const cuuint64_t* dims, const cuuint64_t* strides,
                     const cuuint32_t* box, CUtensorMapSwizzle swizzle = CU_TENSOR_MAP_SWIZZLE_128B) {
  CUtensorMap m;
  const cuuint32_t es[5] = {1, 1, 1, 1, 1};
  enc(&m, CU_TENSOR_MAP_DATA_TYPE_BFLOAT16, rank, const_cast<void*>(p), dims, strides, box, es,
      CU_TENSOR_MAP_INTERLEAVE_NONE, swizzle, CU_TENSOR_MAP_L2_PROMOTION_L2_128B,
      CU_TENSOR_MAP_FLOAT_OOB_FILL_NONE);
  return m;
}

CUtensorMap weight_map(EncodeTiledFn enc, const void* p, int k, int n, int blocks) {
  const cuuint64_t dims[3] = {64, (cuuint64_t)k, (cuuint64_t)n / 64};
  const cuuint64_t strides[2] = {(cuuint64_t)n * 2, 128};
  const cuuint32_t box[3] = {64, 32, (cuuint32_t)blocks};
  return make_map(enc, p, 3, dims, strides, box);
}

CUtensorMap slab_map(EncodeTiledFn enc, const void* p, int n, int cols, int rows) {
  const cuuint64_t dims[2] = {(cuuint64_t)n, kD};
  const cuuint64_t strides[1] = {(cuuint64_t)n * 2};
  const cuuint32_t box[2] = {(cuuint32_t)cols, (cuuint32_t)rows};
  return make_map(enc, p, 2, dims, strides, box, CU_TENSOR_MAP_SWIZZLE_NONE);
}

CUtensorMap token_map(EncodeTiledFn enc, const void* p, int rows) {
  const cuuint64_t dims[2] = {2 * kD, 1024};
  const cuuint64_t strides[1] = {4 * kD};
  const cuuint32_t box[2] = {64, (cuuint32_t)rows};
  return make_map(enc, p, 2, dims, strides, box);
}

}

extern "C" void kernel_launch(void* const* d_in, const int* in_sizes, int n_in, void* d_out, int out_size) {
  (void)in_sizes; (void)n_in; (void)out_size;
  static EncodeTiledFn enc = nullptr;
  if (!enc) {
    void* fn = nullptr;
    cudaDriverEntryPointQueryResult q;
    cudaGetDriverEntryPoint("cuTensorMapEncodeTiled", &fn, cudaEnableDefault, &q);
    enc = (EncodeTiledFn)fn;
    cudaFuncSetAttribute(fused_layers_kernel, cudaFuncAttributeMaxDynamicSharedMemorySize, kSmBytes);
  }
  Params prm;
  prm.b1 = (const __nv_bfloat16*)d_in[5];
  prm.b2 = (const __nv_bfloat16*)d_in[7];
  build_segments(prm.seg);
  const cuuint64_t qd[3] = {kD, kD, 3}, qs[2] = {3 * kD * 2, kD * 2};
  const cuuint32_t qb[3] = {64, 32, 3};
  const CUtensorMap map_x = token_map(enc, d_in[0], 128);
  const CUtensorMap map_out = token_map(enc, d_out, 128);
  const CUtensorMap map_qkv = make_map(enc, d_in[1], 3, qd, qs, qb);
  const CUtensorMap map_wo = weight_map(enc, d_in[2], kD, kD, 2);
  const CUtensorMap map_w1a = weight_map(enc, d_in[4], kD, kF, 3);
  const CUtensorMap map_w1b = weight_map(enc, d_in[4], kD, kF, 2);
  const CUtensorMap map_w2 = weight_map(enc, d_in[6], kF, kD, 2);
  fused_layers_kernel<<<kGrid, 384, kSmBytes>>>(map_x, map_out, map_qkv, map_wo, map_w1a, map_w1b, map_w2,
                                                slab_map(enc, d_in[1], 3 * kD, 128, 128), slab_map(enc, d_in[4], kF, 128, 128),
                                                slab_map(enc, d_in[1], 3 * kD, 16, 128), prm);
}
```

```cpp
#include <cuda.h>
#include <cuda_bf16.h>
#include <cuda_runtime.h>
#include <stdint.h>

namespace {

constexpr int kD = 1024;
constexpr int kF = 3584;
constexpr int kCtas = 128;
constexpr int kGrid = 132;
constexpr int kTiles = 14;
constexpr int kTileBytes = 16384;

constexpr int kSmRing = 0;
constexpr int kSmX = 163840;
constexpr int kSmStg = kSmX + 32768;
constexpr int kSmHalo = kSmStg + 16384;
constexpr int kSmCsQ = kSmHalo + 6144;
constexpr int kSmV1 = kSmCsQ + 384 * 4;
constexpr int kSmB2 = kSmV1 + 448 * 8;
constexpr int kSmStat = kSmB2 + 128 * 4;
constexpr int kSmBar = kSmStat + 128 * 8;
constexpr int kBarFull = kSmBar;
constexpr int kBarTurn = kBarFull + 8 * 8;
constexpr int kBarReady = kBarTurn + 14 * 8;
constexpr int kBarSrc = kBarReady + 17 * 8;
constexpr int kBarPause = kBarSrc + 8 * 8;
constexpr int kBarFree = kBarPause + 4 * 8;
constexpr int kBarCs = kBarFree + 14 * 8;
constexpr int kBarSlab = kBarCs + 3 * 8;
constexpr int kBarHalo = kBarSlab + 4 * 8;
constexpr int kBarInit = kBarHalo + 12 * 8;
constexpr int kBarEpoch = kBarInit + 8;
constexpr int kBarEmpty = kBarTurn + 5 * 128;
constexpr int kBarEpi = kBarEmpty + 128;
constexpr int kBarX = kBarEpi + 14 * 8;
constexpr int kBarStat = kBarX + 8 * 8;
constexpr int kBarResume = kBarStat + 4 * 8;
constexpr int kSmEpoch = kBarEpi + 2 * 128;
static_assert(kBarEpoch < kBarEmpty && kBarResume + 4 * 8 <= kSmEpoch, "barrier groups overflow");
constexpr int kSmBytes = kSmEpoch + 16;
constexpr int kSegs = 38;

constexpr int kFlagLines = kTiles * 16;

constexpr unsigned kSpinLimit = 1u << 22;

__device__ __align__(1024) uint8_t g_x[16 * 16 * kTileBytes];
__device__ __align__(1024) uint8_t g_o[16 * 16 * kTileBytes];
__device__ __align__(1024) uint8_t g_h[16 * 56 * kTileBytes];
__device__ __align__(128) uint2 g_stat[4 * 16 * 128 * 8];
__device__ __align__(128) unsigned g_cs[3 * kD + kF + 3 * kD];
__device__ __align__(128) uint4 g_halo[2 * 16 * 16 * 256];
__device__ __align__(128) unsigned g_flag[kFlagLines * 32];
__device__ unsigned g_ticket;

#define TRACE_AT(tile, k)
#define TRACE_PUB(i, k, c)
#define TRACE_ISSUE(which, nb)

struct Params {
  const __nv_bfloat16* b1;
  const __nv_bfloat16* b2;
  uint32_t seg[kSegs];
};

__device__ __forceinline__ uint32_t smem_u32(const void* p) {
  return (uint32_t)__cvta_generic_to_shared(p);
}
__device__ __forceinline__ uint32_t mapa(uint32_t a, uint32_t cta) {
  uint32_t r;
  asm("mapa.shared::cluster.u32 %0, %1, %2;" : "=r"(r) : "r"(a), "r"(cta));
  return r;
}
__device__ __forceinline__ void mbar_init(uint32_t bar, int cnt) {
  asm volatile("mbarrier.init.shared::cta.b64 [%0], %1;" ::"r"(bar), "r"(cnt) : "memory");
}
__device__ __forceinline__ void mbar_expect_tx(uint32_t bar, uint32_t bytes) {
  asm volatile("mbarrier.arrive.expect_tx.shared::cta.b64 _, [%0], %1;" ::"r"(bar), "r"(bytes) : "memory");
}
__device__ __forceinline__ void mbar_arrive(uint32_t bar) {
  asm volatile("mbarrier.arrive.shared::cta.b64 _, [%0];" ::"r"(bar) : "memory");
}
__device__ __forceinline__ void mbar_arrive_cluster(uint32_t cluster_addr) {
  asm volatile("mbarrier.arrive.shared::cluster.b64 _, [%0];" ::"r"(cluster_addr) : "memory");
}
__device__ __forceinline__ void mbar_wait(uint32_t bar, uint32_t parity) {
  asm volatile("{\n.reg .pred p;\nRETRY:\nmbarrier.try_wait.parity.shared::cta.b64 p, [%0], %1;\n"
               "@!p bra.uni RETRY;\n}" ::"r"(bar), "r"(parity) : "memory");
}
__device__ __forceinline__ void mbar_wait_bounded(uint32_t bar, uint32_t parity) {
  asm volatile("{\n.reg .pred p;\n.reg .u32 c;\nmov.u32 c, 0;\nRETRY:\n"
               "mbarrier.try_wait.parity.shared::cta.b64 p, [%0], %1;\n@p bra.uni DONE;\n"
               "add.u32 c, c, 1;\nsetp.lt.u32 p, c, %2;\n@p bra.uni RETRY;\ntrap;\nDONE:\n}"
               ::"r"(bar), "r"(parity), "n"(1u << 19) : "memory");
}
__device__ __forceinline__ void tma3d(uint32_t dst, const CUtensorMap* m, uint32_t bar, int c0, int c1, int c2) {
  asm volatile(
      "cp.async.bulk.tensor.3d.shared::cluster.global.mbarrier::complete_tx::bytes [%0], [%1, {%3, %4, %5}], [%2];"
      ::"r"(dst), "l"(m), "r"(bar), "r"(c0), "r"(c1), "r"(c2) : "memory");
}
__device__ __forceinline__ void tma3d_mc(uint32_t dst, const CUtensorMap* m, uint32_t bar, int c0, int c1, int c2) {
  asm volatile(
      "cp.async.bulk.tensor.3d.shared::cluster.global.mbarrier::complete_tx::bytes.multicast::cluster"
      " [%0], [%1, {%3, %4, %5}], [%2], %6;"
      ::"r"(dst), "l"(m), "r"(bar), "r"(c0), "r"(c1), "r"(c2), "h"((uint16_t)3) : "memory");
}
__device__ __forceinline__ void tma2d(uint32_t dst, const CUtensorMap* m, uint32_t bar, int c0, int c1) {
  asm volatile(
      "cp.async.bulk.tensor.2d.shared::cluster.global.mbarrier::complete_tx::bytes [%0], [%1, {%3, %4}], [%2];"
      ::"r"(dst), "l"(m), "r"(bar), "r"(c0), "r"(c1) : "memory");
}
__device__ __forceinline__ void tma2d_store(const CUtensorMap* m, uint32_t src, int c0, int c1) {
  asm volatile("cp.async.bulk.tensor.2d.global.shared::cta.bulk_group [%0, {%2, %3}], [%1];"
               ::"l"(m), "r"(src), "r"(c0), "r"(c1) : "memory");
}
__device__ __forceinline__ int lane_id() {
  int l;
  asm volatile("mov.u32 %0, %%laneid;" : "=r"(l));
  return l;
}
__device__ __forceinline__ bool elect() {
  uint32_t p;
  asm volatile("{\n.reg .pred p;\nelect.sync _|p, 0xffffffff;\nselp.b32 %0, 1, 0, p;\n}" : "=r"(p));
  return p;
}
__device__ __forceinline__ void bulk_load(uint32_t dst, const void* src, uint32_t bytes, uint32_t bar) {
  asm volatile("cp.async.bulk.shared::cluster.global.mbarrier::complete_tx::bytes [%0], [%1], %2, [%3];"
               ::"r"(dst), "l"(src), "r"(bytes), "r"(bar) : "memory");
}
__device__ __forceinline__ void bulk_store(void* dst, uint32_t src, uint32_t bytes) {
  asm volatile("cp.async.bulk.global.shared::cta.bulk_group [%0], [%1], %2;" ::"l"(dst), "r"(src), "r"(bytes)
               : "memory");
}
__device__ __forceinline__ void bulk_commit() { asm volatile("cp.async.bulk.commit_group;" ::: "memory"); }
__device__ __forceinline__ void bulk_wait_read() { asm volatile("cp.async.bulk.wait_group.read 0;" ::: "memory"); }
__device__ __forceinline__ void bulk_wait() { asm volatile("cp.async.bulk.wait_group 0;" ::: "memory"); }
__device__ __forceinline__ void fence_async_smem() { asm volatile("fence.proxy.async.shared::cta;" ::: "memory"); }
__device__ __forceinline__ unsigned ld_relaxed(const unsigned* p) {
  unsigned v;
  asm volatile("ld.relaxed.gpu.global.u32 %0, [%1];" : "=r"(v) : "l"(p) : "memory");
  return v;
}
__device__ __forceinline__ uint2 ld_relaxed2(const uint2* p) {
  uint2 v;
  asm volatile("ld.relaxed.gpu.global.v2.u32 {%0, %1}, [%2];" : "=r"(v.x), "=r"(v.y) : "l"(p) : "memory");
  return v;
}
__device__ __forceinline__ void st_relaxed(unsigned* p, unsigned v) {
  asm volatile("st.relaxed.gpu.global.u32 [%0], %1;" ::"l"(p), "r"(v) : "memory");
}
__device__ __forceinline__ void st_release(unsigned* p, unsigned v) {
  asm volatile("st.release.gpu.global.u32 [%0], %1;" ::"l"(p), "r"(v) : "memory");
}
#define ACQ_MODE 1
__device__ __forceinline__ void wait_flags(const unsigned* p, unsigned epoch) {
  unsigned spins = 0;
  while (true) {
    const unsigned v = ld_relaxed(p);
    if (__all_sync(0xffffffffu, v == epoch)) break;
    if (++spins > kSpinLimit) __trap();
  }
  if (ACQ_MODE) asm volatile("fence.acquire.gpu;\nfence.proxy.async.global;" ::: "memory");
  __syncwarp();
}
__device__ __forceinline__ void st_packet(uint4* p, uint32_t d0, uint32_t d1, uint32_t tag) {
  asm volatile("{\n.reg .b128 v;\n.reg .b64 x, y;\nmov.b64 x, {%1, %2};\nmov.b64 y, {%3, %3};\nmov.b128 v, {x, y};\n"
               "st.relaxed.gpu.global.b128 [%0], v;\n}" ::"l"(p), "r"(d0), "r"(d1), "r"(tag) : "memory");
}
__device__ __forceinline__ void ld_packet(const uint4* p, uint32_t& d0, uint32_t& d1, uint32_t& tag) {
  asm volatile("{\n.reg .b128 v;\n.reg .b64 x, y;\n.reg .b32 u;\nld.relaxed.gpu.global.b128 v, [%3];\n"
               "mov.b128 {x, y}, v;\nmov.b64 {%0, %1}, x;\nmov.b64 {%2, u}, y;\n}"
               : "=r"(d0), "=r"(d1), "=r"(tag) : "l"(p) : "memory");
}
__device__ __forceinline__ unsigned tag_value(float v, unsigned epoch) {
  return (__float_as_uint(v) & ~7u) | (epoch & 7u);
}
__device__ __forceinline__ float untag_value(unsigned v) { return __uint_as_float(v & ~7u); }
__device__ __forceinline__ void stsm4(uint32_t a, uint32_t r0, uint32_t r1, uint32_t r2, uint32_t r3) {
  asm volatile("stmatrix.sync.aligned.m8n8.x4.shared.b16 [%0], {%1, %2, %3, %4};" ::"r"(a), "r"(r0), "r"(r1),
               "r"(r2), "r"(r3) : "memory");
}
__device__ __forceinline__ void stsm4_t(uint32_t a, uint32_t r0, uint32_t r1, uint32_t r2, uint32_t r3) {
  asm volatile("stmatrix.sync.aligned.m8n8.x4.trans.shared.b16 [%0], {%1, %2, %3, %4};" ::"r"(a), "r"(r0),
               "r"(r1), "r"(r2), "r"(r3) : "memory");
}
__device__ __forceinline__ uint32_t transpose8(uint32_t a) {
  uint32_t d;
  asm volatile("movmatrix.sync.aligned.m8n8.trans.b16 %0, %1;" : "=r"(d) : "r"(a));
  return d;
}
__device__ __forceinline__ void mma16816(float (&c)[4], uint32_t a0, uint32_t a1, uint32_t a2, uint32_t a3,
                                         uint32_t b0, uint32_t b1) {
  asm volatile("mma.sync.aligned.m16n8k16.row.col.f32.bf16.bf16.f32 {%0, %1, %2, %3}, {%4, %5, %6, %7}, {%8, %9}, "
               "{%0, %1, %2, %3};"
               : "+f"(c[0]), "+f"(c[1]), "+f"(c[2]), "+f"(c[3])
               : "r"(a0), "r"(a1), "r"(a2), "r"(a3), "r"(b0), "r"(b1));
}
__device__ __forceinline__ void mma1688(float (&c)[4], uint32_t a0, uint32_t a1, uint32_t b0) {
  asm volatile("mma.sync.aligned.m16n8k8.row.col.f32.bf16.bf16.f32 {%0, %1, %2, %3}, {%4, %5}, {%6}, {%0, %1, %2, %3};"
               : "+f"(c[0]), "+f"(c[1]), "+f"(c[2]), "+f"(c[3]) : "r"(a0), "r"(a1), "r"(b0));
}
__device__ __forceinline__ float shfl_xor(float v, int m) {
  float r;
  asm volatile("shfl.sync.bfly.b32 %0, %1, %2, 31, 0xffffffff;" : "=f"(r) : "f"(v), "r"(m));
  return r;
}
__device__ __forceinline__ float tanh_fast(float x) {
  float r;
  asm volatile("tanh.approx.f32 %0, %1;" : "=f"(r) : "f"(x));
  return r;
}
__device__ __forceinline__ void ldsm4(uint32_t a, uint32_t (&r)[4]) {
  asm volatile("ldmatrix.sync.aligned.m8n8.x4.shared.b16 {%0, %1, %2, %3}, [%4];"
               : "=r"(r[0]), "=r"(r[1]), "=r"(r[2]), "=r"(r[3]) : "r"(a) : "memory");
}
__device__ __forceinline__ void ldsm4_t(uint32_t a, uint32_t (&r)[4]) {
  asm volatile("ldmatrix.sync.aligned.m8n8.x4.trans.shared.b16 {%0, %1, %2, %3}, [%4];"
               : "=r"(r[0]), "=r"(r[1]), "=r"(r[2]), "=r"(r[3]) : "r"(a) : "memory");
}
__device__ __forceinline__ uint32_t pack2(float lo, float hi) {
  uint32_t r;
  asm volatile("cvt.rn.bf16x2.f32 %0, %1, %2;" : "=r"(r) : "f"(hi), "f"(lo));
  return r;
}
__device__ __forceinline__ float bf_lo(uint32_t r) { return __uint_as_float(r << 16); }
__device__ __forceinline__ float bf_hi(uint32_t r) { return __uint_as_float(r & 0xffff0000u); }
__device__ __forceinline__ float ex2(float x) {
  float r;
  asm("ex2.approx.ftz.f32 %0, %1;" : "=f"(r) : "f"(x));
  return r;
}
__device__ __forceinline__ float rcp(float x) {
  float r;
  asm("rcp.approx.ftz.f32 %0, %1;" : "=f"(r) : "f"(x));
  return r;
}
template <int N>
__device__ __forceinline__ void wg_wait() {
  asm volatile("wgmma.wait_group.sync.aligned %0;" ::"n"(N) : "memory");
}
__device__ __forceinline__ void yield_slot() { asm volatile("pmevent 0;"); }

template <int N, int KIND>
__device__ __forceinline__ void mma_kblock(float (&acc)[2][96], uint32_t a, uint32_t b);

#define F8(m, d, i) m(d[i]), m(d[i + 1]), m(d[i + 2]), m(d[i + 3]), m(d[i + 4]), m(d[i + 5]), m(d[i + 6]), m(d[i + 7])
#define KSTEP(N, A, B, oa0, oa1, ob, sd)                                                   \
  "add.u32 t, " B ", " #ob ";\nmov.b64 db, {t, hb};\n"                                      \
  "add.u32 t, " A ", " #oa0 ";\nmov.b64 da, {t, ha};\n"                                     \
  "wgmma.mma_async.sync.aligned.m64n" #N "k16.f32.bf16.bf16 {" ACC##N##_0 "}, da, db, " #sd ", 1, 1, 0, 1;\n" \
  "add.u32 t, " A ", " #oa1 ";\nmov.b64 da, {t, ha};\n"                                     \
  "wgmma.mma_async.sync.aligned.m64n" #N "k16.f32.bf16.bf16 {" ACC##N##_1 "}, da, db, " #sd ", 1, 1, 0, 1;\n"

#define MMA_KBLOCK(N, KIND, A, B, ob2, ob3, sd, MID, MODE)                                 \
  template <>                                                                              \
  __device__ __forceinline__ void mma_kblock<N, KIND>(float (&acc)[2][96], uint32_t a, uint32_t b) { \
    asm volatile("{\n.reg .b32 t, ha, hb;\n.reg .b64 da, db;\n"                            \
                 "mov.b32 ha, 0x40000080;\nmov.b32 hb, 0x40000040;\n"                       \
                 "wgmma.fence.sync.aligned;\n"                                             \
                 KSTEP(N, A, B, 0, 64, 0, sd) KSTEP(N, A, B, 2, 66, 128, 1) KSTEP(N, A, B, 4, 68, ob2, 1) \
                 MID KSTEP(N, A, B, 6, 70, ob3, 1) "wgmma.commit_group.sync.aligned;\n}\n"  \
                 : OPS##N(MODE) : "r"(a), "r"(b) : "memory");                              \
  }
#define MMA_KBLOCKS(N, A, B, ob2, ob3)                                                     \
  MMA_KBLOCK(N, 0, A, B, ob2, ob3, 1, "", "+f")                                            \
  MMA_KBLOCK(N, 1, A, B, ob2, ob3, 1, "wgmma.commit_group.sync.aligned;\n", "+f")          \
  MMA_KBLOCK(N, 2, A, B, ob2, ob3, 0, "", "=f")

#define ACC128_0 \
  "%0, %1, %2, %3, %4, %5, %6, %7, %8, %9, %10, %11, %12, %13, %14, %15, " \
  "%16, %17, %18, %19, %20, %21, %22, %23, %24, %25, %26, %27, %28, %29, %30, %31, " \
  "%32, %33, %34, %35, %36, %37, %38, %39, %40, %41, %42, %43, %44, %45, %46, %47, " \
  "%48, %49, %50, %51, %52, %53, %54, %55, %56, %57, %58, %59, %60, %61, %62, %63"
#define ACC128_1 \
  "%64, %65, %66, %67, %68, %69, %70, %71, %72, %73, %74, %75, %76, %77, %78, %79, " \
  "%80, %81, %82, %83, %84, %85, %86, %87, %88, %89, %90, %91, %92, %93, %94, %95, " \
  "%96, %97, %98, %99, %100, %101, %102, %103, %104, %105, %106, %107, %108, %109, %110, %111, " \
  "%112, %113, %114, %115, %116, %117, %118, %119, %120, %121, %122, %123, %124, %125, %126, %127"
#define OPS128(m) \
  F8(m, acc[0], 0), F8(m, acc[0], 8), F8(m, acc[0], 16), F8(m, acc[0], 24), F8(m, acc[0], 32), F8(m, acc[0], 40), F8(m, acc[0], 48), F8(m, acc[0], 56), \
        F8(m, acc[1], 0), F8(m, acc[1], 8), F8(m, acc[1], 16), F8(m, acc[1], 24), F8(m, acc[1], 32), F8(m, acc[1], 40), F8(m, acc[1], 48), F8(m, acc[1], 56)
MMA_KBLOCKS(128, "%128", "%129", 512, 640)

#define ACC192_0 \
  "%0, %1, %2, %3, %4, %5, %6, %7, %8, %9, %10, %11, %12, %13, %14, %15, " \
  "%16, %17, %18, %19, %20, %21, %22, %23, %24, %25, %26, %27, %28, %29, %30, %31, " \
  "%32, %33, %34, %35, %36, %37, %38, %39, %40, %41, %42, %43, %44, %45, %46, %47, " \
  "%48, %49, %50, %51, %52, %53, %54, %55, %56, %57, %58, %59, %60, %61, %62, %63, " \
  "%64, %65, %66, %67, %68, %69, %70, %71, %72, %73, %74, %75, %76, %77, %78, %79, " \
  "%80, %81, %82, %83, %84, %85, %86, %87, %88, %89, %90, %91, %92, %93, %94, %95"
#define ACC192_1 \
  "%96, %97, %98, %99, %100, %101, %102, %103, %104, %105, %106, %107, %108, %109, %110, %111, " \
  "%112, %113, %114, %115, %116, %117, %118, %119, %120, %121, %122, %123, %124, %125, %126, %127, " \
  "%128, %129, %130, %131, %132, %133, %134, %135, %136, %137, %138, %139, %140, %141, %142, %143, " \
  "%144, %145, %146, %147, %148, %149, %150, %151, %152, %153, %154, %155, %156, %157, %158, %159, " \
  "%160, %161, %162, %163, %164, %165, %166, %167, %168, %169, %170, %171, %172, %173, %174, %175, " \
  "%176, %177, %178, %179, %180, %181, %182, %183, %184, %185, %186, %187, %188, %189, %190, %191"
#define OPS192(m) \
  F8(m, acc[0], 0), F8(m, acc[0], 8), F8(m, acc[0], 16), F8(m, acc[0], 24), F8(m, acc[0], 32), F8(m, acc[0], 40), F8(m, acc[0], 48), F8(m, acc[0], 56), F8(m, acc[0], 64), F8(m, acc[0], 72), F8(m, acc[0], 80), F8(m, acc[0], 88), \
        F8(m, acc[1], 0), F8(m, acc[1], 8), F8(m, acc[1], 16), F8(m, acc[1], 24), F8(m, acc[1], 32), F8(m, acc[1], 40), F8(m, acc[1], 48), F8(m, acc[1], 56), F8(m, acc[1], 64), F8(m, acc[1], 72), F8(m, acc[1], 80), F8(m, acc[1], 88)
MMA_KBLOCKS(192, "%192", "%193", 768, 896)

#define HSTEP(oa, ob)                                                                       \
  "add.u32 t, %97, " #ob ";\nmov.b64 db, {t, hb};\nadd.u32 t, %96, " #oa ";\nmov.b64 da, {t, ha};\n" \
  "wgmma.mma_async.sync.aligned.m64n192k16.f32.bf16.bf16 {" ACC192_0 "}, da, db, 1, 1, 1, 0, 1;\n"
__device__ __forceinline__ void mma_half(float (&d)[96], uint32_t a, uint32_t b) {
  asm volatile("{\n.reg .b32 t, ha, hb;\n.reg .b64 da, db;\nmov.b32 ha, 0x40000080;\nmov.b32 hb, 0x40000040;\n"
               "wgmma.fence.sync.aligned;\n" HSTEP(0, 0) HSTEP(2, 128) HSTEP(4, 768) HSTEP(6, 896)
               "wgmma.commit_group.sync.aligned;\n}\n"
               : F8("+f", d, 0), F8("+f", d, 8), F8("+f", d, 16), F8("+f", d, 24), F8("+f", d, 32), F8("+f", d, 40),
                 F8("+f", d, 48), F8("+f", d, 56), F8("+f", d, 64), F8("+f", d, 72), F8("+f", d, 80), F8("+f", d, 88)
               : "r"(a), "r"(b) : "memory");
}

#define TSTEP(REGS, W, X, ow, ox)                                                           \
  "add.u32 t, " X ", " #ox ";\nmov.b64 db, {t, hi};\nadd.u32 t, " W ", " #ow ";\nmov.b64 da, {t, hi};\n" \
  "wgmma.mma_async.sync.aligned.m64n128k16.f32.bf16.bf16 {" REGS "}, da, db, 1, 1, 1, 1, 0;\n"
#define THEAD "{\n.reg .b32 t, hi;\n.reg .b64 da, db;\nmov.b32 hi, 0x40000040;\nwgmma.fence.sync.aligned;\n"
#define TTAIL "wgmma.commit_group.sync.aligned;\n}\n"
__device__ __forceinline__ void mma_kblock_t(float (&acc)[2][96], uint32_t wd, uint32_t xd) {
  asm volatile(THEAD TSTEP(ACC128_0, "%128", "%129", 0, 0) TSTEP(ACC128_1, "%128", "%129", 256, 0)
               TSTEP(ACC128_0, "%128", "%129", 128, 2) TSTEP(ACC128_1, "%128", "%129", 384, 2)
               TSTEP(ACC128_0, "%128", "%129", 512, 4) TSTEP(ACC128_1, "%128", "%129", 768, 4)
               TSTEP(ACC128_0, "%128", "%129", 640, 6) TSTEP(ACC128_1, "%128", "%129", 896, 6) TTAIL
               : OPS128("+f") : "r"(wd), "r"(xd) : "memory");
}
__device__ __forceinline__ void mma_half_t(float (&d)[96], uint32_t wd, uint32_t xd) {
  asm volatile(THEAD TSTEP(ACC128_0, "%64", "%65", 0, 0) TSTEP(ACC128_0, "%64", "%65", 128, 2)
               TSTEP(ACC128_0, "%64", "%65", 512, 4) TSTEP(ACC128_0, "%64", "%65", 640, 6) TTAIL
               : F8("+f", d, 0), F8("+f", d, 8), F8("+f", d, 16), F8("+f", d, 24), F8("+f", d, 32), F8("+f", d, 40),
                 F8("+f", d, 48), F8("+f", d, 56) : "r"(wd), "r"(xd) : "memory");
}

enum { kModePlain = 0, kModeHead = 1, kModeSkip = 2, kModeContinue = 3 };

template <int N>
__device__ __forceinline__ void fence_acc(float (&acc)[2][96]) {
#pragma unroll
  for (int h = 0; h < 2; h++)
#pragma unroll
    for (int i = 0; i < N / 2; i++) asm volatile("" : "+f"(acc[h][i])::"memory");
}

constexpr uint32_t kToB = (kTileBytes >> 4) + ((4096u >> 4) << 16) - (1u << 16);

#define TRACE_KB(nb)

#define HEAD_BOTH 4
template <int N>
__device__ __forceinline__ void head_blocks(float (&acc)[2][96], uint32_t sb, int n0, int slot, int xver,
                                            uint32_t rel_addr, bool rel) {
  const uint32_t ring = (((sb & 0x3FFFF) + kSmRing) >> 4) | (1u << 16);
  const uint32_t xdesc = (((sb & 0x3FFFF) + kSmX) >> 4) | (1u << 16);
  const uint32_t s0 = ring + slot * 2560, s1 = ring + ((slot + 1) & 3) * 2560;
  const uint32_t nb = n0 * 8, xbar = sb + kBarX + (xver - 1) * 16;
  if (xver > 0) {
    mbar_wait(xbar + ((HEAD_BOTH >> xver) & 1) * 8, 0);
    mbar_wait(sb + kBarTurn + (xver == 1 ? 2 : 3 * xver) * 8, 0);
  }
  mbar_wait(sb + kBarFull + (nb & 56), nb >> 6);
  if (n0 == 0) TRACE_AT(0, 1);
  TRACE_KB(nb);
  mma_kblock<N, 2>(acc, xver > 0 ? xdesc : s0, s0 + kToB);
  if (xver > 0) mbar_wait(xbar + 8, 0);
  mbar_wait(sb + kBarFull + (nb & 56) + 8, nb >> 6);
  TRACE_KB(nb + 8);
  mma_kblock<N, 0>(acc, xver > 0 ? xdesc + (kTileBytes >> 4) : s1, s1 + kToB);
  wg_wait<1>();
  if (rel) mbar_arrive_cluster(rel_addr + (nb & 56));
  wg_wait<0>();
  if (rel) mbar_arrive_cluster(rel_addr + (nb & 56) + 8);
  fence_acc<N>(acc);
}

enum { kPlain, kFresh, kResid, kStagger };
template <int N, int KIND, class Pre>
__device__ __forceinline__ void mainloop(float (&acc)[2][96], uint32_t sb, int tile, int n0, int slot, int nkb,
                                         int pause_kk, int att, uint32_t rel_addr, bool rel, int own_kk, Pre pre) {
  constexpr bool RESID = KIND == kResid, FRESH = KIND == kFresh;
  constexpr uint32_t kStep = (N == 192 ? 5 : 4) * 512;
  const uint32_t ring = (((sb & 0x3FFFF) + kSmRing) >> 4) | (1u << 16);
  uint32_t st = ring + slot * kStep;
  uint32_t nb = n0 * 8, prev = 64;
  const uint32_t last = nb + 8 * (nkb - (RESID ? 3 : KIND == kStagger ? 2 : 1)), own = nb + 8 * own_kk;
  const uint32_t stg = (((sb & 0x3FFFF) + kSmStg) >> 4) | (1u << 16);
  uint32_t stop = pause_kk >= 0 ? nb + 8 * pause_kk : last;
  const bool signal = (threadIdx.x & 127) == 64;
  if (!FRESH) fence_acc<N>(acc);
  if (tile > 0) mbar_wait(sb + kBarTurn + (tile - 1) * 8, 0);
  TRACE_AT(tile, 0);
  if constexpr (FRESH) {
    mbar_wait(sb + kBarFull + (nb & 56), nb >> 6);
    TRACE_KB(nb);
    mma_kblock<N, 2>(acc, st, st + kToB);
    prev = nb & 56;
    st += kStep;
    nb += 8;
  }
#pragma unroll 1
  while (true) {
#pragma unroll 1
    do {
      mbar_wait(sb + kBarFull + (nb & 56), nb >> 6);
      TRACE_KB(nb);
      if constexpr (RESID) mma_kblock_t(acc, st + kToB, nb == own ? stg : st);
      else mma_kblock<N, 0>(acc, st, st + kToB);
      wg_wait<1>();
      if (rel) mbar_arrive_cluster(rel_addr + prev);
      prev = nb & 56;
      st += kStep;
      if (st == ring + 10240) st = ring;
      nb += 8;
    } while (nb != stop);
    if (stop == last) break;
    stop = last;
    if (signal) mbar_arrive(sb + kBarPause + att * 8);
    wg_wait<0>();
    if (rel) mbar_arrive_cluster(rel_addr + prev);
    prev = 64;
    mbar_wait(sb + kBarResume + att * 8, 0);
  }
  mbar_wait(sb + kBarFull + (nb & 56), nb >> 6);
  TRACE_KB(nb);
  if constexpr (RESID) {
    const uint32_t z = gridDim.y - 1;
    const uint32_t s2 = st + kStep, s3 = s2 == ring + 8192 ? ring : s2 + kStep;
    mma_half_t(acc[0], st + kToB, st);
    wg_wait<1>();
    if (rel) mbar_arrive_cluster(rel_addr + 32);
    mbar_wait(sb + kBarFull + 48, nb >> 6);
    TRACE_KB(nb + 8);
    mma_half_t(acc[0], s2 + kToB, s2);
    mbar_wait(sb + kBarFull + 56, nb >> 6);
    TRACE_KB(nb + 16);
    mma_half_t(acc[0], s3 + kToB, s3);
    mma_half_t(acc[1], st + kToB + 256, st + z);
    mma_half_t(acc[1], s2 + kToB + 256, s2 + z);
    wg_wait<2>();
#pragma unroll
    for (int i = 0; i < 64; i++) asm volatile("" : "+f"(acc[0][i])::"memory");
    pre(0);
    mma_half_t(acc[1], s3 + kToB + 256, s3 + z);
    wg_wait<2>();
    if (rel) mbar_arrive_cluster(rel_addr + 40);
    pre(1);
    wg_wait<1>();
    if (rel) mbar_arrive_cluster(rel_addr + 48);
    if (signal) mbar_arrive(sb + kBarTurn + tile * 8);
    wg_wait<0>();
    if (rel) mbar_arrive_cluster(rel_addr + 56);
#pragma unroll
    for (int i = 0; i < 64; i++) asm volatile("" : "+f"(acc[1][i])::"memory");
  } else if constexpr (KIND == kStagger) {
    const uint32_t z = gridDim.y - 1, s2 = st + kStep;
    mma_half(acc[1], st + 64, st + kToB);
    wg_wait<1>();
    if (rel) mbar_arrive_cluster(rel_addr + 40);
    mbar_wait(sb + kBarFull + 56, nb >> 6);
    TRACE_KB(nb + 8);
    mma_half(acc[1], s2 + 64, s2 + kToB);
    mma_half(acc[0], st, st + z + kToB);
    pre(0);
    mma_half(acc[0], s2, s2 + z + kToB);
    wg_wait<2>();
#pragma unroll
    for (int i = 0; i < 96; i++) asm volatile("" : "+f"(acc[1][i])::"memory");
    pre(1);
    wg_wait<1>();
    if (rel) mbar_arrive_cluster(rel_addr + 48);
    pre(2);
    if (signal) mbar_arrive(sb + kBarTurn + tile * 8);
    pre(3);
    wg_wait<0>();
    if (rel) mbar_arrive_cluster(rel_addr + 56);
#pragma unroll
    for (int i = 0; i < 96; i++) asm volatile("" : "+f"(acc[0][i])::"memory");
  } else {
    mma_kblock<N, 1>(acc, st, st + kToB);
    wg_wait<2>();
    if (rel) mbar_arrive_cluster(rel_addr + prev);
    pre();
    wg_wait<1>();
    if (signal) mbar_arrive(sb + kBarTurn + tile * 8);
    wg_wait<0>();
    if (rel) mbar_arrive_cluster(rel_addr + (nb & 56));
    fence_acc<N>(acc);
  }
}

__device__ __forceinline__ void publish_stats(uint32_t sb, uint2* stat, int w, int lane, unsigned epoch) {
  const uint32_t row = sb + kSmX + (32 * w + lane) * 128;
  float s[4], q[4];
#pragma unroll
  for (int c = 0; c < 4; c++) s[c] = q[c] = 0.f;
  uint32_t nx[4];
  ldsm4(row + ((lane & 7) << 4), nx);
#pragma unroll 1
  for (int J = 1; J <= 16; J++) {
    const uint32_t r[4] = {nx[0], nx[1], nx[2], nx[3]};
    ldsm4(row + ((J >> 3) & 1) * kTileBytes + (((J ^ lane) & 7) << 4), nx);
#pragma unroll
    for (int c = 0; c < 4; c++) {
      const float lo = bf_lo(r[c]);
      s[c] += lo;
      q[c] = fmaf(lo, lo, q[c]);
      if (c & 1) yield_slot();
    }
#pragma unroll
    for (int c = 0; c < 4; c++) {
      const float hi = bf_hi(r[c]);
      s[c] += hi;
      q[c] = fmaf(hi, hi, q[c]);
      if (c & 1) yield_slot();
    }
  }
  const int t = lane & 3, g = lane >> 2;
#pragma unroll
  for (int c = 0; c < 2; c++) {
    s[c] = (t & 2 ? s[c + 2] : s[c]) + shfl_xor(t & 2 ? s[c] : s[c + 2], 2);
    q[c] = (t & 2 ? q[c + 2] : q[c]) + shfl_xor(t & 2 ? q[c] : q[c + 2], 2);
  }
  const float so = (t & 1 ? s[1] : s[0]) + shfl_xor(t & 1 ? s[0] : s[1], 1);
  const float qo = (t & 1 ? q[1] : q[0]) + shfl_xor(t & 1 ? q[0] : q[1], 1);
  asm volatile("st.relaxed.gpu.global.v2.u32 [%0], {%1, %2};" ::"l"(stat + 32 * w + 8 * t + g),
               "r"(tag_value(so, epoch)), "r"(tag_value(qo, epoch)) : "memory");
}

__device__ __forceinline__ void add_chunk(float (&a)[8], const uint4& v) {
  a[0] += bf_lo(v.x); a[1] += bf_hi(v.x);
  a[2] += bf_lo(v.y); a[3] += bf_hi(v.y);
  a[4] += bf_lo(v.z); a[5] += bf_hi(v.z);
  a[6] += bf_lo(v.w); a[7] += bf_hi(v.w);
}

__device__ __forceinline__ int helper_col(int id, int slab) {
  return (slab < 3 ? slab * kD : (slab - 3) * 512) + id * 128;
}
__device__ __forceinline__ void helper_cta(const CUtensorMap* map_q, const CUtensorMap* map_1, uint8_t* sm,
                                           uint32_t sb, int id, int warp) {
  constexpr int kRed = 6 * 32768, kBar = kRed + 2 * 4096;
  const int tid = threadIdx.x;
  if (warp == 8 && elect()) {
#pragma unroll
    for (int s = 0; s < 6; s++) {
      mbar_init(sb + kBar + s * 8, 1);
      mbar_init(sb + kBar + 64 + s * 8, 4);
    }
    fence_async_smem();
#pragma unroll
    for (int s = 0; s < 6; s++) {
      mbar_expect_tx(sb + kBar + s * 8, 32768);
      tma2d(sb + s * 32768, map_q, sb + kBar + s * 8, id * 128, s * 128);
    }
  }
  __syncthreads();
  if (warp == 8) {
    int slot = 0, ph = 0;
#pragma unroll 1
    for (int n = 6; n < 80; n++) {
      mbar_wait(sb + kBar + 64 + slot * 8, ph);
      if (elect()) {
        mbar_expect_tx(sb + kBar + slot * 8, 32768);
        tma2d(sb + slot * 32768, n < 24 ? map_q : map_1, sb + kBar + slot * 8, helper_col(id, n >> 3), (n & 7) * 128);
      }
      if (++slot == 6) slot = 0, ph ^= 1;
    }
  } else if (warp < 8) {
    if (tid == 0) *reinterpret_cast<unsigned*>(sm + kBar + 128) = atomicAdd(&g_ticket, 1u) / kGrid + 1;
    int slot = warp >> 2, ph = 0;
#pragma unroll 1
    for (int slab = 0; slab < 10; slab++) {
      float a[8];
#pragma unroll
      for (int e = 0; e < 8; e++) a[e] = 0.f;
#pragma unroll 1
      for (int box = 0; box < 4; box++) {
        mbar_wait_bounded(sb + kBar + slot * 8, ph);
        const uint4* p = reinterpret_cast<const uint4*>(sm + slot * 32768) + (tid & 127);
        uint4 v[16];
#pragma unroll
        for (int i = 0; i < 16; i++) v[i] = p[i * 128];
        __syncwarp();
        if (elect()) mbar_arrive(sb + kBar + 64 + slot * 8);
#pragma unroll
        for (int i = 0; i < 16; i++) add_chunk(a, v[i]);
        slot += 2;
        if (slot >= 6) slot -= 6, ph ^= 1;
      }
      float* red = reinterpret_cast<float*>(sm + kRed + (slab & 1) * 4096);
#pragma unroll
      for (int e = 0; e < 8; e++) a[e] += shfl_xor(a[e], 16);
      if ((tid & 16) == 0) {
        float4* d = reinterpret_cast<float4*>(red + warp * 128 + (tid & 15) * 8);
        d[0] = make_float4(a[0], a[1], a[2], a[3]);
        d[1] = make_float4(a[4], a[5], a[6], a[7]);
      }
      asm volatile("bar.sync 1, 256;" ::: "memory");
      if (warp < 4) {
        float t = 0.f;
#pragma unroll
        for (int q = 0; q < 8; q++) t += red[q * 128 + tid];
        st_relaxed(g_cs + (slab < 3 ? 0 : 3 * kD) + helper_col(id, slab) + tid,
                   tag_value(t, *reinterpret_cast<volatile unsigned*>(sm + kBar + 128)));
      }
    }
  }
}

__device__ __forceinline__ void colsum_strip(const CUtensorMap* map, uint8_t* sm, uint32_t sb, int col, int half,
                                             int lane, unsigned epoch) {
  const uint32_t bar = sb + kBarSlab + half * 16;
  const int buf = kSmStg + half * 8192;
  float a[8];
#pragma unroll
  for (int e = 0; e < 8; e++) a[e] = 0.f;
#pragma unroll 1
  for (int r = -2; r < 4; r++) {
    if (r >= 0) {
      mbar_wait(bar + (r & 1) * 8, r >> 1);
      const uint4* p = reinterpret_cast<const uint4*>(sm + buf + (r & 1) * 4096) + lane;
#pragma unroll 1
      for (int q = 0; q < 8; q += 4) {
        uint4 v[4];
#pragma unroll
        for (int u = 0; u < 4; u++) v[u] = p[(q + u) * 32];
#pragma unroll
        for (int u = 0; u < 4; u++) {
          a[0] += bf_lo(v[u].x); a[1] += bf_hi(v[u].x); a[2] += bf_lo(v[u].y); a[3] += bf_hi(v[u].y);
          yield_slot();
          a[4] += bf_lo(v[u].z); a[5] += bf_hi(v[u].z); a[6] += bf_lo(v[u].w); a[7] += bf_hi(v[u].w);
          yield_slot();
        }
      }
      fence_async_smem();
      __syncwarp();
    }
    if (r < 2 && elect()) {
      mbar_expect_tx(bar + (r & 1) * 8, 4096);
      tma2d(sb + buf + (r & 1) * 4096, map, bar + (r & 1) * 8, col, half * 512 + (r + 2) * 128);
    }
  }
#pragma unroll
  for (int e = 0; e < 4; e++) a[e] = (lane & 16 ? a[e + 4] : a[e]) + shfl_xor(lane & 16 ? a[e] : a[e + 4], 16);
#pragma unroll
  for (int e = 0; e < 2; e++) a[e] = (lane & 8 ? a[e + 2] : a[e]) + shfl_xor(lane & 8 ? a[e] : a[e + 2], 8);
  a[0] = (lane & 4 ? a[1] : a[0]) + shfl_xor(lane & 4 ? a[0] : a[1], 4);
  a[0] += shfl_xor(a[0], 2);
  if (!(lane & 2)) st_relaxed(g_cs + half * (3 * kD + kF) + col + (lane & 1) * 8 + (lane >> 2), tag_value(a[0], epoch));
}

constexpr float kGeluBeta = 0.3292034911525734f;
constexpr float kGeluK = 2.423681954311584f;

__device__ __forceinline__ void store_staged(uint8_t* dst, uint32_t stg) {
  fence_async_smem();
  __syncwarp();
  if (elect()) {
    bulk_store(dst, stg, 4096);
    bulk_commit();
  }
}

#define GY_MASK 5
#define GD 2
#define GF_MASK 3
#define GY(k) if ((GY_MASK >> k) & 1) yield_slot()
template <int J0, int J1>
__device__ __forceinline__ void fold_norm(float (&acc)[2][96], const float2 (&st)[4], const float4* vec) {
  float4 vn = vec[J0 * 4];
#pragma unroll
  for (int J = J0; J < J1; J++) {
    const float4 v = vn;
    if (J + 1 < J1) vn = vec[J * 4 + 4];
#pragma unroll
    for (int c = 0; c < 4; c++) {
      float& a0 = acc[c & 1][4 * J + (c & 2)];
      float& a1 = acc[c & 1][4 * J + (c & 2) + 1];
      a0 = fmaf(a0, st[c].x, fmaf(st[c].y, v.x, v.z));
      a1 = fmaf(a1, st[c].x, fmaf(st[c].y, v.y, v.w));
      asm volatile("" : "+f"(a0), "+f"(a1));
      if ((c & 1) && ((GF_MASK >> (c >> 1)) & 1)) yield_slot();
    }
  }
}

template <int CH, class Acquire>
__device__ __forceinline__ void gelu_chunk(const float (&acc)[2][96], uint32_t stg, int lane, uint8_t* prev,
                                           Acquire acquire) {
  uint32_t pk[8][4];
  float z[GD + 1][4];
  const uint32_t row = (stg + lane * 128) ^ ((lane & 7) << 4);
#define U(s, e) acc[(e) >> 1][4 * (CH * 8 + ((s) >> 1)) + 2 * ((s) & 1) + ((e) & 1)]
#pragma unroll
  for (int s = 0; s < 16 + GD; s++) {
    const int cur = s % (GD + 1), p1 = (s + GD) % (GD + 1), p2 = (s + 1) % (GD + 1), q = s - GD, jj = 2 * q - 24;
    const bool mid = s >= 1 && s < 17;
    if (mid) z[p1][0] = tanh_fast(z[p1][0]);
    if (s < 16) {
#pragma unroll
      for (int e = 0; e < 4; e++) {
        z[cur][e] = fmaf(U(s, e), U(s, e), kGeluK);
        asm volatile("" : "+f"(z[cur][e]));
      }
    }
    if (jj >= 0) stsm4(row ^ (jj << 4), pk[jj][0], pk[jj][1], pk[jj][2], pk[jj][3]);
    GY(0);
    if (mid) z[p1][1] = tanh_fast(z[p1][1]);
    if (q >= 0) {
      pk[q >> 1][2 * (q & 1)] = pack2(fmaf(U(q, 0), z[p2][0], U(q, 0)), fmaf(U(q, 1), z[p2][1], U(q, 1)));
      pk[q >> 1][2 * (q & 1) + 1] = pack2(fmaf(U(q, 2), z[p2][2], U(q, 2)), fmaf(U(q, 3), z[p2][3], U(q, 3)));
    }
    GY(1);
    if (mid) z[p1][2] = tanh_fast(z[p1][2]);
    if (s < 16) {
#pragma unroll
      for (int e = 0; e < 4; e++) {
        z[cur][e] *= U(s, e);
        asm volatile("" : "+f"(z[cur][e]));
      }
    }
    if (mid) z[p1][3] = tanh_fast(z[p1][3]);
    if (jj >= 0) stsm4(row ^ ((jj + 1) << 4), pk[jj + 1][0], pk[jj + 1][1], pk[jj + 1][2], pk[jj + 1][3]);
    GY(2);
    if (CH == 1 && s == 1) store_staged(prev, stg);
    if (q == 11) acquire();
  }
#undef U
}

__device__ __forceinline__ void scale_stats(float2 (&st)[4]) {
#pragma unroll
  for (int c = 0; c < 4; c++) {
    st[c].x *= kGeluBeta;
    st[c].y *= st[c].x;
  }
}

__device__ __forceinline__ void add_mean_term(float (&acc)[2][96], const float2 (&st)[4], uint8_t* sm, int tq,
                                              int lane) {
  const float2* cs = reinterpret_cast<const float2*>(sm + kSmCsQ) + tq * 96 + (lane & 3);
  float2 vn = cs[0];
#pragma unroll
  for (int J = 0; J < 24; J++) {
    const float2 v = vn;
    if (J < 23) vn = cs[J * 4 + 4];
#pragma unroll
    for (int c = 0; c < 4; c++) {
      acc[c & 1][4 * J + (c & 2)] = fmaf(st[c].y, v.x, acc[c & 1][4 * J + (c & 2)]);
      acc[c & 1][4 * J + (c & 2) + 1] = fmaf(st[c].y, v.y, acc[c & 1][4 * J + (c & 2) + 1]);
    }
    yield_slot();
  }
}

#define CV_MASK 1
#define HALO_AT 2
struct AttnRegs {
  uint32_t q[4][8], k[5][8], vt[5][8];
};
#define SCALED(c, J) pack2(acc[(c) & 1][4 * (J) + ((c) & 2)] * st[c].x, acc[(c) & 1][4 * (J) + ((c) & 2) + 1] * st[c].x)
__device__ __forceinline__ void convert_group(const float (&acc)[2][96], const float2 (&st)[4], AttnRegs& r, int c,
                                              int part) {
#pragma unroll
  for (int J = 0; J < 8; J++) {
    if (part == 0) r.q[c][J] = SCALED(c, J);
    if (part == 1) r.k[c + 1][J] = SCALED(c, 8 + J);
    if (part == 2) r.vt[c + 1][J] = transpose8(SCALED(c, 16 + J));
    if ((J & CV_MASK) == CV_MASK) yield_slot();
  }
}
#undef SCALED

__device__ __forceinline__ void convert_odd(const float (&acc)[2][96], const float2 (&st)[4], AttnRegs& r, int step,
                                            uint8_t* sm, uint32_t halo_bar, uint4* halo_out, bool send,
                                            unsigned epoch, int w, int lane) {
  if (step == 1) {
    convert_group(acc, st, r, 3, 2);
    convert_group(acc, st, r, 3, 1);
    if (w < 3) {
      uint2* hs = reinterpret_cast<uint2*>(sm + kSmHalo + w * 2048) + lane;
#pragma unroll
      for (int i = 0; i < 4; i++) {
        hs[i * 32] = make_uint2(r.k[4][2 * i], r.k[4][2 * i + 1]);
        hs[128 + i * 32] = make_uint2(r.vt[4][2 * i], r.vt[4][2 * i + 1]);
      }
      __syncwarp();
      if (elect()) mbar_arrive(halo_bar + w * 8);
    } else if (send) {
#pragma unroll
      for (int i = 0; i < 4; i++) {
        st_packet(halo_out + lane + i * 32, r.k[4][2 * i], r.k[4][2 * i + 1], epoch);
        st_packet(halo_out + lane + 128 + i * 32, r.vt[4][2 * i], r.vt[4][2 * i + 1], epoch);
      }
    }
  } else if (step == 2) {
    convert_group(acc, st, r, 1, 2);
  } else {
    convert_group(acc, st, r, 1, 1);
    convert_group(acc, st, r, 3, 0);
    convert_group(acc, st, r, 1, 0);
  }
}

__device__ __forceinline__ void epilogue_attn(const float (&acc)[2][96], const float2 (&st)[4], AttnRegs& r,
                                              uint8_t* sm, uint32_t sb, int layer, int tq, int b, int j,
                                              unsigned epoch, int tile, int w, int lane) {
  const int t = lane & 3, g = lane >> 2;
  const int hp = j + 8 * tq, att = 2 * layer + tq;
  auto& q = r.q;
  auto& k = r.k;
  auto& vt = r.vt;
  const bool first = w == 0 && (b & 7) == 0;
  const uint4* gh = g_halo + ((layer * 16 + b - 1) * 16 + hp) * 256 + lane;
  uint32_t tag[8];
#define LOAD_HALO()                                                                                    \
  _Pragma("unroll") for (int i = 0; i < 4; i++) {                                                      \
    ld_packet(gh + i * 32, k[0][2 * i], k[0][2 * i + 1], tag[i]);                                      \
    ld_packet(gh + 128 + i * 32, vt[0][2 * i], vt[0][2 * i + 1], tag[4 + i]);                          \
  }
#define AWAIT_HALO()                                                                                   \
  for (unsigned spins = 0;; spins++) {                                                                 \
    const unsigned d0 = (tag[0] ^ epoch) | (tag[1] ^ epoch) | (tag[2] ^ epoch) | (tag[3] ^ epoch);     \
    const unsigned d1 = (tag[4] ^ epoch) | (tag[5] ^ epoch) | (tag[6] ^ epoch) | (tag[7] ^ epoch);     \
    if (__all_sync(0xffffffffu, (d0 | d1) == 0)) break;                                                \
    if (spins > kSpinLimit) __trap();                                                                  \
    LOAD_HALO();                                                                                       \
  }
#pragma unroll
  for (int c = 0; c <= 6; c++) {
    if (c == HALO_AT) {
#pragma unroll
      for (int i = 0; i < 8; i++) k[0][i] = vt[0][i] = tag[i] = 0u;
      if (w > 0) {
        mbar_wait(sb + kBarHalo + (att * 3 + w - 1) * 8, 0);
        const uint2* hs = reinterpret_cast<const uint2*>(sm + kSmHalo + (w - 1) * 2048) + lane;
#pragma unroll
        for (int i = 0; i < 4; i++) {
          const uint2 a = hs[i * 32], d = hs[128 + i * 32];
          k[0][2 * i] = a.x; k[0][2 * i + 1] = a.y;
          vt[0][2 * i] = d.x; vt[0][2 * i + 1] = d.y;
        }
      } else if (!first) {
        LOAD_HALO();
      }
    }
    if (c < 6) convert_group(acc, st, r, 2 * (c & 1), 2 - (c >> 1));
  }
  TRACE_AT(tile, 8);
  if (w == 0 && !first) AWAIT_HALO();
  constexpr float kScale = 0.17677669529663687f * 1.4426950408889634f;
  const bool own0 = 2 * t <= g, own1 = 2 * t + 1 <= g;
  const uint32_t own_mask = (own0 ? 0xffffu : 0u) | (own1 ? 0xffff0000u : 0u);
  const uint32_t stg = sb + kSmStg + w * 4096;
  const uint32_t orow = stg + (lane & 7) * 128, ochunk = (lane >> 3) ^ (lane & 7);
  TRACE_AT(tile, 9);
  mbar_wait(sb + kBarPause + att * 8, 0);
  TRACE_AT(tile, 10);

  float s[2][6][4], o[2][4][2][4];
#pragma unroll
  for (int n = 0; n < 24; n++) {
    const int ks = n / 12, hd = (n % 12) / 6, m = n % 6, ca = 2 * (m / 3), kg = ca + m % 3, J = 4 * hd + 2 * ks;
    if (ks == 0) s[hd][m][0] = s[hd][m][1] = s[hd][m][2] = s[hd][m][3] = 0.f;
    mma16816(s[hd][m], q[ca][J], q[ca + 1][J], q[ca][J + 1], q[ca + 1][J + 1], k[kg][J], k[kg][J + 1]);
  }
  float v0[2][4], v1[2][4], m[2][4];
  uint32_t pp[2][4], po[2][4];
#define UNITS _Pragma("unroll") for (int hd = 0; hd < 2; hd++) _Pragma("unroll") for (int c = 0; c < 4; c++)
  UNITS {
    const int mp = 3 * (c >> 1) + (c & 1), r = 2 * (c & 1);
    float p0 = s[hd][mp][r], p1 = s[hd][mp][r + 1];
    if (c == 0 && first) p0 = p1 = -INFINITY;
    v0[hd][c] = own0 ? s[hd][mp + 1][r] : p0;
    v1[hd][c] = own1 ? s[hd][mp + 1][r + 1] : p1;
    m[hd][c] = fmaxf(v0[hd][c], v1[hd][c]);
  }
  UNITS m[hd][c] = fmaxf(m[hd][c], shfl_xor(m[hd][c], 1));
  UNITS m[hd][c] = fmaxf(m[hd][c], shfl_xor(m[hd][c], 2));
  UNITS {
    const float nm = -m[hd][c] * kScale;
    v0[hd][c] = ex2(fmaf(v0[hd][c], kScale, nm));
    v1[hd][c] = ex2(fmaf(v1[hd][c], kScale, nm));
    m[hd][c] = v0[hd][c] + v1[hd][c];
  }
  UNITS m[hd][c] += shfl_xor(m[hd][c], 1);
  UNITS m[hd][c] += shfl_xor(m[hd][c], 2);
  UNITS {
    const float inv = rcp(m[hd][c]);
    const uint32_t p = pack2(v0[hd][c] * inv, v1[hd][c] * inv);
    pp[hd][c] = p & ~own_mask;
    po[hd][c] = p & own_mask;
    asm volatile("" : "+r"(pp[hd][c]), "+r"(po[hd][c]));
  }
#pragma unroll
  for (int n = 0; n < 24; n++) {
    const int ph = n / 8, hd = (n >> 2) & 1, c = 2 * ((n >> 1) & 1) + (ph == 1), ds = n & 1, J = 4 * hd + 2 * ds;
    float(&d)[4] = o[hd][c][ds];
    if (ph < 2) d[0] = d[1] = d[2] = d[3] = 0.f;
    if (ph == 0) mma1688(d, vt[c + 1][J], vt[c + 1][J + 1], po[hd][c]);
    if (ph == 1) mma16816(d, vt[c][J], vt[c][J + 1], vt[c + 1][J], vt[c + 1][J + 1], pp[hd][c], po[hd][c]);
    if (ph == 2) mma1688(d, vt[c][J], vt[c][J + 1], pp[hd][c]);
    if (n == 3) {
      yield_slot();
      if (tq == 0 && lane == 0) mbar_arrive(sb + kBarResume + att * 8);
    }
  }
  yield_slot();
  TRACE_AT(tile, 11);
  UNITS stsm4_t(orow + c * 1024 + ((ochunk ^ (4 * hd)) << 4), pack2(o[hd][c][0][0], o[hd][c][0][1]),
                pack2(o[hd][c][0][2], o[hd][c][0][3]), pack2(o[hd][c][1][0], o[hd][c][1][1]),
                pack2(o[hd][c][1][2], o[hd][c][1][3]));
#undef UNITS
#undef AWAIT_HALO
#undef LOAD_HALO
  fence_async_smem();
  __syncwarp();
  if (tq == 1 && lane == 0) mbar_arrive(sb + kBarResume + att * 8);
  TRACE_AT(tile, 12);
  if (elect()) {
    bulk_store(g_o + (b * 16 + hp) * kTileBytes + w * 4096, stg, 4096);
    bulk_commit();
    bulk_wait();
    TRACE_AT(tile, 13);
    mbar_arrive(sb + kBarEpi + tile * 8);
  }
  __syncwarp();
}

__device__ __forceinline__ void gather_stats(uint8_t* sm, const uint2* stat, int r, unsigned epoch) {
  uint2 a[8];
#pragma unroll 1
  for (unsigned spins = 0;; spins++) {
    unsigned diff = 0;
#pragma unroll
    for (int i = 0; i < 8; i++) {
      a[i] = ld_relaxed2(stat + i * 128 + r);
      diff |= (a[i].x ^ epoch) | (a[i].y ^ epoch);
    }
    if (__all_sync(0xffffffffu, (diff & 7u) == 0)) break;
    if (spins > kSpinLimit) __trap();
  }
  float s = 0.f, q = 0.f;
#pragma unroll
  for (int i = 0; i < 8; i++) {
    s += untag_value(a[i].x);
    q += untag_value(a[i].y);
  }
  const float mean = s * (1.f / 1024.f);
  const float var = fmaxf(fmaf(-mean, mean, q * (1.f / 1024.f)), 0.f);
  reinterpret_cast<float2*>(sm + kSmStat)[r] = make_float2(rsqrtf(var + 1e-5f), -mean);
}

__device__ __forceinline__ void gather_colsums_qkv(uint8_t* sm, int tq, int j, int lane, unsigned epoch) {
  const uint2* src = reinterpret_cast<const uint2*>(g_cs + (j + 8 * tq) * 64) + lane;
  uint2 v[3], u[3];
  for (unsigned spins = 0;; spins++) {
    unsigned diff = 0;
#pragma unroll
    for (int q = 0; q < 3; q++) {
      v[q] = ld_relaxed2(src + q * (kD / 2));
      u[q] = make_uint2(epoch & 7u, epoch & 7u);
      if (tq) u[q] = ld_relaxed2(src + (q * kD + 3 * kD + kF) / 2);
    }
#pragma unroll
    for (int q = 0; q < 3; q++) diff |= (v[q].x ^ epoch) | (v[q].y ^ epoch) | (u[q].x ^ epoch) | (u[q].y ^ epoch);
    if (__all_sync(0xffffffffu, (diff & 7u) == 0)) break;
    if (spins > kSpinLimit) __trap();
  }
#pragma unroll
  for (int q = 0; q < 3; q++)
    reinterpret_cast<float2*>(sm + kSmCsQ)[tq * 96 + q * 32 + lane] =
        make_float2(untag_value(v[q].x) + untag_value(u[q].x), untag_value(v[q].y) + untag_value(u[q].y));
}

__device__ __forceinline__ void gather_colsums_w1(uint8_t* sm, const __nv_bfloat16* b1, int j, int lane,
                                                  unsigned epoch) {
#pragma unroll 1
  for (int blk = 0; blk < 7; blk++) {
    const int pair = 32 * (blk + (blk < 3 ? 3 * j : blk < 5 ? 21 + 2 * j : 35 + 2 * j)) + lane;
    const uint32_t bias = reinterpret_cast<const uint32_t*>(b1)[pair];
    uint2 v;
    for (unsigned spins = 0;; spins++) {
      v = ld_relaxed2(reinterpret_cast<const uint2*>(g_cs + 3 * kD) + pair);
      if (__all_sync(0xffffffffu, (((v.x ^ epoch) | (v.y ^ epoch)) & 7u) == 0)) break;
      if (spins > kSpinLimit) __trap();
    }
    reinterpret_cast<float4*>(sm + kSmV1)[blk * 32 + lane] =
        make_float4(untag_value(v.x), untag_value(v.y), kGeluBeta * bf_lo(bias), kGeluBeta * bf_hi(bias));
  }
}

#define FINE 3
#define LATE_REL2 1
#define STRIP_GATE kBarInit
#define XI_MASK 1
#define PUB_SPLIT 4
#define STAGE_YIELD 1
#define PAUSE_QKV2 7
#define PAUSE_WO 2

__global__ void __cluster_dims__(2, 1, 1) __launch_bounds__(384, 1)
fused_layers_kernel(const __grid_constant__ CUtensorMap map_x, const __grid_constant__ CUtensorMap map_out,
                    const __grid_constant__ CUtensorMap map_qkv, const __grid_constant__ CUtensorMap map_wo,
                    const __grid_constant__ CUtensorMap map_w1a, const __grid_constant__ CUtensorMap map_w1b,
                    const __grid_constant__ CUtensorMap map_w2, const __grid_constant__ CUtensorMap map_csq,
                    const __grid_constant__ CUtensorMap map_cs1, const __grid_constant__ CUtensorMap map_css,
                    const __grid_constant__ Params prm) {
  extern __shared__ __align__(1024) uint8_t sm[];
  if (threadIdx.x < 128 && blockIdx.x < kCtas) TRACE_AT(15, 1);
  const uint32_t sb = __shfl_sync(0xffffffffu, smem_u32(sm), 0);
  const int warp = __shfl_sync(0xffffffffu, threadIdx.x >> 5, 0), lane = threadIdx.x & 31;
  const int cta = blockIdx.x, rank = cta & 1, cl = cta >> 1;
  const int grp = cl < 4 ? 0 : cl < 36 ? (cl - 4) & 7 : 1 + (cl - 36) % 7;
  const int j = cl < 4 ? 4 + cl : cl < 36 ? (cl - 4) >> 3 : 4 + (cl - 36) / 7;
  const int b = 2 * grp + rank;
  const int xcol = (b >> 3) * kD, xrow = (b & 7) * 128;

  if (cta >= kCtas) {
    helper_cta(&map_csq, &map_cs1, sm, sb, cta - kCtas, warp);
    return;
  }
  if ((warp < 8 || warp == 9) && elect()) {
    if (warp == 9) {
#pragma unroll
      for (int s = 0; s < 8; s++) mbar_init(sb + kBarFull + s * 8, 1);
      fence_async_smem();
#pragma unroll
      for (int s = 0; s < 4; s++) {
        const uint32_t full = sb + kBarFull + s * 8, dst = sb + kSmRing + s * 40960;
        mbar_expect_tx(full, 40960);
        tma2d(dst, &map_x, full, xcol + (s & 1) * 64, xrow);
        tma3d(dst + kTileBytes, &map_qkv, full, (j + 4 * (s & 2)) * 64, (s & 1) * 64, 0);
        tma3d(dst + kTileBytes + 12288, &map_qkv, full, (j + 4 * (s & 2)) * 64, (s & 1) * 64 + 32, 0);
      }
    } else {
      if (sb & 1023) __trap();
#pragma unroll
      for (int s = 0; s < 16; s++) mbar_init(sb + kBarTurn + warp * 128 + s * 8, warp < 5 ? 1 : warp == 5 ? 2 : 4);
    }
    asm volatile("fence.mbarrier_init.release.cluster;" ::: "memory");
  }
  __syncwarp();
  asm volatile("barrier.cluster.arrive.relaxed.aligned;" ::: "memory");

  if (warp >= 8) {
    asm volatile("setmaxnreg.dec.sync.aligned.u32 40;");
    if (warp < 10) {
      asm volatile("barrier.cluster.wait.aligned;" ::: "memory");
      uint32_t nb = 32, off = 0, kb = 0;
#define RING_STEP(WAIT, ISSUE)                                            \
  do {                                                                    \
    const uint32_t mb = nb - depth, full = sb + kBarFull + (nb & 56);     \
    if (kb == skip) kb += inc;                                            \
    mbar_wait(sb + kBarEmpty + (mb & 56), mb >> 6);                       \
    WAIT;                                                                 \
    if (elect()) { ISSUE; }                                               \
    TRACE_ISSUE(9 - warp, nb);                                            \
    kb += inc;                                                            \
    off = off == wrap ? 0 : off + step;                                   \
    nb += 8;                                                              \
  } while (nb != nend)
#pragma unroll 1
      for (int sg = 0; sg < kSegs; sg++) {
        const uint32_t e = prm.seg[sg];
        const int ty = e & 7, mode = (e >> 15) & 3, reset = (e >> 24) & 3;
        const uint32_t nend = nb + (e & 0x1f8);
        const uint32_t step = (e >> 17) & 1 ? 40960 : 32768, wrap = 163840 - step;
        const uint32_t depth = (e >> 18) & 1 ? 40 : 32;
        if (reset) off = reset == 1 ? 0 : reset == 2 ? 40960 : 131072;
        const uint32_t own = ty == 2 ? 8 + j : 2 * j;
        if (mode != kModeContinue) kb = mode == kModeHead ? own : (e >> 9) & 63;
        const uint32_t inc = mode >= kModeSkip && ty != 2 ? 2 : 1, skip = mode >= kModeSkip ? own + (kb & 1) : 255;
        if (warp == 8) {
          const CUtensorMap* map = ty < 2 ? &map_qkv : ty == 2 ? &map_wo : ty == 3 ? &map_w1a : ty < 6 ? &map_w1b : &map_w2;
          const int c0 = ty < 2 ? (j + 8 * ty) * 64 : 0;
          const int c2 = ty < 2 ? 0 : ty == 3 ? 3 * j : ty == 4 ? 24 + 2 * j : ty == 5 ? 40 + 2 * j : 2 * j;
          const uint32_t half = (ty < 2 || ty == 3) ? 12288 : 8192;
          const uint32_t bytes = 2 * half + (mode == kModeHead ? 0 : kTileBytes);
          const uint32_t dst = sb + kSmRing + kTileBytes + rank * half;
#pragma unroll 1
          RING_STEP(, mbar_expect_tx(full, bytes); tma3d_mc(dst + off, map, full, c0, kb * 64 + rank * 32, c2));
        } else if (mode == kModeHead) {
          off += ((nend - nb) >> 3) * step;
          nb = nend;
          if (off >= 163840) off -= 163840;
        } else if (sg < 2) {
#pragma unroll 1
          RING_STEP(, tma2d(sb + kSmRing + off, &map_x, full, xcol + kb * 64, xrow));
        } else {
          const uint8_t* src = ty == 6 ? g_h + b * 56 * kTileBytes : (ty == 2 ? g_o : g_x) + b * 16 * kTileBytes;
          const int dep = (e >> 19) & 31;
          if (dep < 28) mbar_wait(sb + kBarReady + dep * 8, 0);
          if ((dep & 30) == 28) {
#pragma unroll 1
            RING_STEP(mbar_wait(sb + kBarSrc + ((kb << (4 - inc)) & 56), dep),
                      bulk_load(sb + kSmRing + off, src + kb * kTileBytes, kTileBytes, full));
          } else {
#pragma unroll 1
            RING_STEP(, bulk_load(sb + kSmRing + off, src + kb * kTileBytes, kTileBytes, full));
          }
        }
      }
#undef RING_STEP
    } else {
      unsigned epoch = 0;
      if (warp == 10) {
        if (lane == 0) epoch = atomicAdd(&g_ticket, 1u) / kGrid + 1;
        *reinterpret_cast<unsigned*>(sm + kSmEpoch) = __shfl_sync(0xffffffffu, epoch, 0);
        asm volatile("barrier.cluster.wait.aligned;" ::: "memory");
        if (elect()) mbar_arrive(sb + kBarEpoch);
      } else {
        asm volatile("barrier.cluster.wait.aligned;" ::: "memory");
        mbar_wait_bounded(sb + kBarFull, 0);
        if (elect()) {
          mbar_expect_tx(sb + kBarInit, 32768);
          tma2d(sb + kSmX, &map_x, sb + kBarInit, xcol + j * 128, xrow);
          tma2d(sb + kSmX + kTileBytes, &map_x, sb + kBarInit, xcol + j * 128 + 64, xrow);
        }
        const uint2 u = reinterpret_cast<const uint2*>(prm.b2)[32 * j + lane];
        reinterpret_cast<float4*>(sm + kSmB2)[lane] = make_float4(
            2.f * kGeluBeta * bf_lo(u.x), 2.f * kGeluBeta * bf_hi(u.x), 2.f * kGeluBeta * bf_lo(u.y), 2.f * kGeluBeta * bf_hi(u.y));
      }
      mbar_wait_bounded(sb + kBarEpoch, 0);
      epoch = *reinterpret_cast<volatile unsigned*>(sm + kSmEpoch);
      if (cta < 96) {
        mbar_wait_bounded(sb + STRIP_GATE, 0);
        colsum_strip(&map_css, sm, sb, (cta >> 5) * kD + 512 + (cta & 31) * 16, warp - 10, lane, epoch);
      }
      gather_colsums_qkv(sm, 11 - warp, j, lane, epoch);
      __syncwarp();
      if (elect()) mbar_arrive(sb + kBarCs + (11 - warp) * 8);
     if (warp == 10) {
#pragma unroll 1
      for (int i = 0; i < kTiles - 1; i++) {
        const bool xt = i == 2 || i == 6 || i == 9;
        const unsigned* line = g_flag + (i * 16 + b) * 32;
        mbar_wait(sb + (xt ? kBarX + (i >> 2) * 16 : kBarEpi + i * 8), 0);
        if ((xt && (FINE & 1)) || ((i == 1 || i == 8) && (FINE & 2))) {
          unsigned todo = 0xff, spins = 0;
          do {
            const unsigned now = __ballot_sync(0xffffffffu, ld_relaxed(line + (lane & 7)) == epoch) & todo;
            if (now) {
              asm volatile("fence.acquire.gpu;\nfence.proxy.async.global;" ::: "memory");
              if ((now >> lane) & 1) mbar_arrive(sb + kBarSrc + lane * 8);
              todo ^= now;
            }
            if (++spins > kSpinLimit) __trap();
          } while (todo);
        } else {
          wait_flags(line + (lane & 7), epoch);
          if (elect()) mbar_arrive(sb + kBarReady + i * 8);
        }
        if (xt) {
          wait_flags(line + 8 + (lane & 7), epoch);
          if (elect()) mbar_arrive(sb + kBarReady + (14 + (i >> 2)) * 8);
        }
      }
     } else {
#pragma unroll 1
      for (int i = 0; i < kTiles - 1; i++) {
        if (i == 3) {
          gather_colsums_w1(sm, prm.b1, j, lane, epoch);
          __syncwarp();
          if (elect()) mbar_arrive(sb + kBarCs + 16);
        }
        const bool xt = i == 2 || i == 6 || i == 9;
#pragma unroll 1
        for (int h = 0; h < (xt ? 2 : 1); h++) {
          mbar_wait_bounded(sb + (xt ? kBarX + (i >> 2) * 16 + 8 * h : kBarEpi + i * 8), 0);
          const int ty = i >= 7 ? i - 7 : i;
          if (ty >= 2 && elect()) {
            uint8_t* dst = xt ? g_x + (b * 16 + 2 * j + h) * kTileBytes
                              : g_h + (b * 56 + 1 + (ty == 3 ? 3 * j : 16 * ty - 40 + 2 * j)) * kTileBytes;
            const int piece = (xt && h == 0) ? kTileBytes : kTileBytes / PUB_SPLIT;
#pragma unroll 1
            for (int o = 0; o < kTileBytes; o += piece) {
              bulk_store(dst + o, sb + (xt ? kSmX + h * kTileBytes : kSmStg) + o, piece);
              bulk_commit();
              bulk_wait();
            }
            if (!xt) mbar_arrive(sb + kBarFree + i * 8);
          }
          if (LATE_REL2 && h == 1) mbar_wait_bounded(sb + kBarFull + 32, i == 2 ? 6 : i == 6 ? 19 : 25);
          __syncwarp();
          if (elect()) st_release(&g_flag[(i * 16 + b) * 32 + h * 8 + j], epoch);
          __syncwarp();
        }
      }
#pragma unroll 1
      for (int h = 0; h < 2; h++) {
        mbar_wait_bounded(sb + kBarX + 48 + 8 * h, 0);
        if (elect()) {
          tma2d_store(&map_out, sb + kSmX + h * kTileBytes, xcol + j * 128 + h * 64, xrow);
          bulk_commit();
          if (h == 1) bulk_wait_read();
        }
      }
     }
    }
    __syncwarp();
    asm volatile("barrier.cluster.arrive.relaxed.aligned;\nbarrier.cluster.wait.aligned;" ::: "memory");
  } else {
    asm volatile("setmaxnreg.inc.sync.aligned.u32 232;");
    asm volatile("barrier.cluster.wait.aligned;" ::: "memory");
    const int wg = warp >> 2, w = warp & 3;
    const bool rel = (threadIdx.x & 95) == 0;
    const uint32_t rel_addr = mapa(sb + kBarEmpty, w & 1);
    if (wg == 1) TRACE_AT(15, 0);
#define EPOCH (*reinterpret_cast<volatile unsigned*>(sm + kSmEpoch))

#pragma unroll 1
    for (int i = wg; i < kTiles; i += 2) {
      const int layer = i >= 7, ty = i - 7 * layer;
      TRACE_AT(i, 15);
      float acc[2][96];
      if (ty == 2 || ty == 6) {
        const int lane = lane_id();
        const uint32_t xa = sb + kSmX + ((lane >> 4) * 8 + (lane & 7)) * 128 + (((2 * w + ((lane >> 3) & 1)) ^ (lane & 7)) << 4);
        const float up = ty == 6 ? 2.f * kGeluBeta : 1.f, dn = ty == 6 ? 0.5f / kGeluBeta : 1.f;
#pragma unroll
        for (int h = 0; h < 2; h++) {
          const float* b2 = reinterpret_cast<const float*>(sm + kSmB2) + 64 * h + 16 * w + (lane >> 2);
          const float bias[2] = {ty == 6 ? b2[0] : 0.f, ty == 6 ? b2[8] : 0.f};
#pragma unroll
          for (int p = 0; p < 8; p++) {
            uint32_t r[4];
            ldsm4_t(xa + h * kTileBytes + p * 2048, r);
#pragma unroll
            for (int m = 0; m < 4; m++) {
              acc[h][8 * p + 2 * m] = fmaf(bf_lo(r[m]), up, bias[m & 1]);
              acc[h][8 * p + 2 * m + 1] = fmaf(bf_hi(r[m]), up, bias[m & 1]);
              asm volatile("" : "+f"(acc[h][8 * p + 2 * m]), "+f"(acc[h][8 * p + 2 * m + 1]));
              if ((m & XI_MASK) == XI_MASK) yield_slot();
            }
          }
        }
        auto stage = [&](int qt) {
          const int h = qt >> 1;
#pragma unroll
          for (int p = 4 * (qt & 1); p < 4 * (qt & 1) + 4; p++) {
            const float* a = &acc[h][8 * p];
            stsm4_t(xa + h * kTileBytes + p * 2048, pack2(a[0] * dn, a[1] * dn), pack2(a[2] * dn, a[3] * dn),
                    pack2(a[4] * dn, a[5] * dn), pack2(a[6] * dn, a[7] * dn));
            if (STAGE_YIELD || (p & 3) == 3) yield_slot();
          }
          if (qt & 1) {
            fence_async_smem();
            __syncwarp();
            if (elect()) mbar_arrive(sb + kBarX + (i >> 2) * 16 + 8 * h);
            TRACE_AT(i, 8 + h);
          }
        };
        mainloop<128, kResid>(acc, sb, i, layer * 152 + ty * 16, ty == 6 ? 4 : 0, ty == 6 ? 56 : 16,
                            ty == 2 ? PAUSE_WO : -1, 2 * layer + 1, rel_addr, rel, ty == 2 ? 8 : -1, stage);
        TRACE_AT(i, 2);
        stage(2);
        stage(3);
      } else {
        const int xver = 2 * layer + (ty >= 3);
        const uint32_t stg = sb + kSmStg + w * 4096;
        const float4* vec = reinterpret_cast<const float4*>(sm + kSmV1) + (ty == 3 ? 0 : 64 * ty - 160);
        int lane;
        uint8_t* hdst = g_h + (b * 56 + (ty == 3 ? 3 * j : 16 * ty - 40 + 2 * j)) * kTileBytes + w * 4096;
        float2 st[4];
        unsigned epoch;
        auto pre = [&] {
          lane = lane_id();
          if (ty < 4) mbar_wait(sb + (ty == 1 ? kBarEpi + (i - 1) * 8 : kBarStat + xver * 8), 0);
#pragma unroll
          for (int c = 0; c < 4; c++) st[c] = reinterpret_cast<const float2*>(sm + kSmStat)[32 * w + 8 * c + (lane >> 2)];
          epoch = EPOCH;
        };
        auto team_stats = [&] {
          uint2* stat = g_stat + (xver * 16 + b) * 1024;
          lane = lane_id();
          publish_stats(sb, stat + j * 128, w, lane, EPOCH);
          gather_stats(sm, stat, 32 * w + lane, EPOCH);
          __syncwarp();
          if (elect()) mbar_arrive(sb + kBarStat + xver * 8);
          TRACE_AT(i, 14);
        };
        if (ty < 4) {
          AttnRegs ar;
          auto odd = [&](int step) {
            if (step == 0) pre();
            else convert_odd(acc, st, ar, step, sm, sb + kBarHalo + (xver + ty) * 24,
                             g_halo + ((layer * 16 + b) * 16 + j + 8 * ty) * 256, (b & 7) != 7, epoch, w, lane);
          };
          head_blocks<192>(acc, sb, layer * 152 + (ty < 2 ? 2 * ty : 48), ty < 2 ? 2 * ty : 1, xver, rel_addr, rel);
          if (ty == 1) {
            if (i == 1) {
              mbar_wait(sb + kBarEpoch, 0);
              mbar_wait(sb + kBarInit, 0);
            }
            team_stats();
            epoch = 0;
#pragma unroll
            for (int c = 0; c < 4; c++) st[c] = reinterpret_cast<const float2*>(sm + kSmStat)[32 * w + 8 * c + (lane >> 2)];
          } else {
            mainloop<192, kPlain>(acc, sb, i, layer * 152 + (ty ? 52 : 4), ty ? 1 : 0, 14, -1, 0, rel_addr, rel, 0, pre);
            TRACE_AT(i, 2);
            if (ty == 3) goto wide_gelu;
          }
          if (layer == 0) mbar_wait(sb + kBarCs + ty * 8, 0);
          add_mean_term(acc, st, sm, ty, lane);
          if (ty == 1) {
            mainloop<192, kStagger>(acc, sb, i, layer * 152 + 18, 2, 14, PAUSE_QKV2, xver, rel_addr, rel, 0, odd);
            TRACE_AT(i, 2);
          } else {
            odd(1);
            odd(2);
            odd(3);
          }
          epilogue_attn(acc, st, ar, sm, sb, layer, ty, b, j, epoch, i, w, lane);
          TRACE_AT(i, 3);
          continue;
        wide_gelu:
          if (i == 3) mbar_wait(sb + kBarCs + 16, 0);
          scale_stats(st);
          fold_norm<16, 24>(acc, st, vec + (lane & 3));
          TRACE_AT(i, 11);
          gelu_chunk<2>(acc, stg, lane, nullptr, [] {});
          TRACE_AT(i, 12);
          fold_norm<0, 2>(acc, st, vec + (lane & 3));
          store_staged(hdst + 2 * kTileBytes, stg);
          fold_norm<2, 16>(acc, st, vec + (lane & 3));
        } else {
          if (ty == 4) {
            head_blocks<128>(acc, sb, layer * 152 + 50, 3, xver, rel_addr, rel);
            team_stats();
            mainloop<128, kPlain>(acc, sb, i, layer * 152 + 66, 4, 14, -1, 0, rel_addr, rel, 0, pre);
          } else {
            mainloop<128, kFresh>(acc, sb, i, layer * 152 + 80, 3, 16, -1, 0, rel_addr, rel, 0, pre);
          }
          TRACE_AT(i, 2);
          if (i == 4) mbar_wait(sb + kBarCs + 16, 0);
          scale_stats(st);
          fold_norm<0, 16>(acc, st, vec + (lane & 3));
        }
        auto own_store_done = [] {
          if (elect()) bulk_wait();
          __syncwarp();
        };
        TRACE_AT(i, 8);
        gelu_chunk<0>(acc, stg, lane, nullptr, [&] {
          if (ty == 3) own_store_done();
          else mbar_wait(sb + kBarFree + (i - 1) * 8, 0);
        });
        TRACE_AT(i, 9);
        gelu_chunk<1>(acc, stg, lane, hdst, own_store_done);
        TRACE_AT(i, 10);
        fence_async_smem();
        __syncwarp();
        if (elect()) mbar_arrive(sb + kBarEpi + i * 8);
      }
      TRACE_AT(i, 3);
    }
#undef EPOCH
    asm volatile("barrier.cluster.arrive.relaxed.aligned;\nbarrier.cluster.wait.aligned;" ::: "memory");
    if (wg == 1) TRACE_AT(15, 2);
  }
}

void build_segments(uint32_t* seg) {
  int n = 0, fine = 0;
  auto per_source = [&](int kind, int dep) { return (FINE & kind) ? 28 + (fine++ & 1) : dep; };
  auto add = [&](int ty, int cnt, int kb0, int mode, int wide, int depth5, int dep, int reset) {
    seg[n++] = ty | cnt << 3 | kb0 << 9 | mode << 15 | wide << 17 | depth5 << 18 | dep << 19 | reset << 24;
  };
  for (int l = 0; l < 2; l++) {
    const int t = 7 * l;
    if (l == 0) {
      add(0, 14, 2, kModePlain, 1, 0, 31, 1);
      add(1, 14, 2, kModePlain, 1, 0, 31, 0);
    } else {
      add(0, 2, 0, kModeHead, 1, 0, 31, 1);
      add(1, 2, 0, kModeHead, 1, 0, 31, 0);
      add(0, 7, 0, kModeSkip, 1, 0, per_source(1, 6), 0);
      add(0, 7, 1, kModeSkip, 1, 0, 15, 0);
      add(1, 7, 0, kModeSkip, 1, 0, 31, 0);
      add(1, 7, 1, kModeSkip, 1, 0, 31, 0);
    }
    add(2, 4, 0, kModePlain, 0, 0, t, 1);
    add(2, 4, 4, kModePlain, 0, 1, 31, 0);
    add(2, 1, 0, kModeHead, 0, 1, 31, 0);
    add(2, 7, 8, kModeSkip, 0, 1, per_source(2, t + 1), 0);
    add(3, 2, 0, kModeHead, 1, 0, 31, 2);
    add(4, 2, 0, kModeHead, 1, 0, 31, 0);
    add(3, 7, 0, kModeSkip, 1, 0, per_source(1, t + 2), 0);
    add(3, 7, 1, kModeSkip, 1, 0, 14 + 2 * l, 0);
    add(4, 4, 0, kModeSkip, 0, 0, 31, 3);
    add(4, 3, 0, kModeContinue, 0, 1, 31, 0);
    add(4, 7, 1, kModeSkip, 0, 1, 31, 0);
    add(5, 16, 0, kModePlain, 0, 1, 31, 0);
    add(6, 24, 0, kModePlain, 0, 1, t + 3, 0);
    add(6, 16, 24, kModePlain, 0, 1, t + 4, 0);
    add(6, 16, 40, kModePlain, 0, 1, t + 5, 0);
  }
}

typedef CUresult (*EncodeTiledFn)(CUtensorMap*, CUtensorMapDataType, cuuint32_t, void*, const cuuint64_t*,
                                  const cuuint64_t*, const cuuint32_t*, const cuuint32_t*, CUtensorMapInterleave,
                                  CUtensorMapSwizzle, CUtensorMapL2promotion, CUtensorMapFloatOOBfill);

CUtensorMap make_map(EncodeTiledFn enc, const void* p, int rank, const cuuint64_t* dims, const cuuint64_t* strides,
                     const cuuint32_t* box, CUtensorMapSwizzle swizzle = CU_TENSOR_MAP_SWIZZLE_128B,
                     CUtensorMapL2promotion promo = CU_TENSOR_MAP_L2_PROMOTION_L2_128B) {
  CUtensorMap m;
  const cuuint32_t es[5] = {1, 1, 1, 1, 1};
  enc(&m, CU_TENSOR_MAP_DATA_TYPE_BFLOAT16, rank, const_cast<void*>(p), dims, strides, box, es,
      CU_TENSOR_MAP_INTERLEAVE_NONE, swizzle, promo,
      CU_TENSOR_MAP_FLOAT_OOB_FILL_NONE);
  return m;
}

CUtensorMap weight_map(EncodeTiledFn enc, const void* p, int k, int n, int blocks) {
  const cuuint64_t dims[3] = {64, (cuuint64_t)k, (cuuint64_t)n / 64};
  const cuuint64_t strides[2] = {(cuuint64_t)n * 2, 128};
  const cuuint32_t box[3] = {64, 32, (cuuint32_t)blocks};
  return make_map(enc, p, 3, dims, strides, box, CU_TENSOR_MAP_SWIZZLE_128B, CU_TENSOR_MAP_L2_PROMOTION_L2_256B);
}

CUtensorMap slab_map(EncodeTiledFn enc, const void* p, int n, int cols, int rows) {
  const cuuint64_t dims[2] = {(cuuint64_t)n, kD};
  const cuuint64_t strides[1] = {(cuuint64_t)n * 2};
  const cuuint32_t box[2] = {(cuuint32_t)cols, (cuuint32_t)rows};
  return make_map(enc, p, 2, dims, strides, box, CU_TENSOR_MAP_SWIZZLE_NONE);
}

CUtensorMap token_map(EncodeTiledFn enc, const void* p, int rows) {
  const cuuint64_t dims[2] = {2 * kD, 1024};
  const cuuint64_t strides[1] = {4 * kD};
  const cuuint32_t box[2] = {64, (cuuint32_t)rows};
  return make_map(enc, p, 2, dims, strides, box);
}

}

extern "C" void kernel_launch(void* const* d_in, const int* in_sizes, int n_in, void* d_out, int out_size) {
  (void)in_sizes; (void)n_in; (void)out_size;
  static EncodeTiledFn enc = nullptr;
  if (!enc) {
    void* fn = nullptr;
    cudaDriverEntryPointQueryResult q;
    cudaGetDriverEntryPoint("cuTensorMapEncodeTiled", &fn, cudaEnableDefault, &q);
    enc = (EncodeTiledFn)fn;
    cudaFuncSetAttribute(fused_layers_kernel, cudaFuncAttributeMaxDynamicSharedMemorySize, kSmBytes);
  }
  Params prm;
  prm.b1 = (const __nv_bfloat16*)d_in[5];
  prm.b2 = (const __nv_bfloat16*)d_in[7];
  build_segments(prm.seg);
  const cuuint64_t qd[3] = {kD, kD, 3}, qs[2] = {3 * kD * 2, kD * 2};
  const cuuint32_t qb[3] = {64, 32, 3};
  const CUtensorMap map_x = token_map(enc, d_in[0], 128);
  const CUtensorMap map_out = token_map(enc, d_out, 128);
  const CUtensorMap map_qkv = make_map(enc, d_in[1], 3, qd, qs, qb);
  const CUtensorMap map_wo = weight_map(enc, d_in[2], kD, kD, 2);
  const CUtensorMap map_w1a = weight_map(enc, d_in[4], kD, kF, 3);
  const CUtensorMap map_w1b = weight_map(enc, d_in[4], kD, kF, 2);
  const CUtensorMap map_w2 = weight_map(enc, d_in[6], kF, kD, 2);
  fused_layers_kernel<<<kGrid, 384, kSmBytes>>>(map_x, map_out, map_qkv, map_wo, map_w1a, map_w1b, map_w2,
                                                slab_map(enc, d_in[1], 3 * kD, 128, 128), slab_map(enc, d_in[4], kF, 128, 128),
                                                slab_map(enc, d_in[1], 3 * kD, 16, 128), prm);
}
```

```cpp
#include <cuda.h>
#include <cuda_bf16.h>
#include <cuda_runtime.h>
#include <stdint.h>

namespace {

constexpr int kD = 1024;
constexpr int kF = 3584;
constexpr int kCtas = 128;
constexpr int kGrid = 132;
constexpr int kTiles = 14;
constexpr int kTileBytes = 16384;

constexpr int kSmRing = 0;
constexpr int kSmX = 163840;
constexpr int kSmStg = kSmX + 32768;
constexpr int kSmHalo = kSmStg + 16384;
constexpr int kSmCsQ = kSmHalo + 6144;
constexpr int kSmV1 = kSmCsQ + 384 * 4;
constexpr int kSmB2 = kSmV1 + 448 * 8;
constexpr int kSmStat = kSmB2 + 128 * 4;
constexpr int kSmBar = kSmStat + 128 * 8;
constexpr int kBarFull = kSmBar;
constexpr int kBarTurn = kBarFull + 8 * 8;
constexpr int kBarReady = kBarTurn + 14 * 8;
constexpr int kBarSrc = kBarReady + 17 * 8;
constexpr int kBarPause = kBarSrc + 8 * 8;
constexpr int kBarFree = kBarPause + 4 * 8;
constexpr int kBarCs = kBarFree + 14 * 8;
constexpr int kBarSlab = kBarCs + 3 * 8;
constexpr int kBarHalo = kBarSlab + 4 * 8;
constexpr int kBarInit = kBarHalo + 12 * 8;
constexpr int kBarEpoch = kBarInit + 8;
constexpr int kBarEmpty = kBarTurn + 5 * 128;
constexpr int kBarEpi = kBarEmpty + 128;
constexpr int kBarX = kBarEpi + 14 * 8;
constexpr int kBarStat = kBarX + 8 * 8;
constexpr int kBarResume = kBarStat + 4 * 8;
constexpr int kSmEpoch = kBarEpi + 2 * 128;
static_assert(kBarEpoch < kBarEmpty && kBarResume + 4 * 8 <= kSmEpoch, "barrier groups overflow");
constexpr int kSmBytes = kSmEpoch + 16;
constexpr int kSegs = 38;

constexpr int kFlagLines = kTiles * 16;

constexpr unsigned kSpinLimit = 1u << 22;

__device__ __align__(1024) uint8_t g_x[16 * 16 * kTileBytes];
__device__ __align__(1024) uint8_t g_o[16 * 16 * kTileBytes];
__device__ __align__(1024) uint8_t g_h[16 * 56 * kTileBytes];
__device__ __align__(128) uint2 g_stat[4 * 16 * 128 * 8];
__device__ __align__(128) unsigned g_cs[3 * kD + kF + 3 * kD];
__device__ __align__(128) uint4 g_halo[2 * 16 * 16 * 256];
__device__ __align__(128) unsigned g_flag[kFlagLines * 32];
__device__ unsigned g_ticket;

#define TRACE_AT(tile, k)
#define TRACE_PUB(i, k, c)
#define TRACE_ISSUE(which, nb)

struct Params {
  const __nv_bfloat16* b1;
  const __nv_bfloat16* b2;
  uint32_t seg[kSegs];
};

__device__ __forceinline__ uint32_t smem_u32(const void* p) {
  return (uint32_t)__cvta_generic_to_shared(p);
}
__device__ __forceinline__ uint32_t mapa(uint32_t a, uint32_t cta) {
  uint32_t r;
  asm("mapa.shared::cluster.u32 %0, %1, %2;" : "=r"(r) : "r"(a), "r"(cta));
  return r;
}
__device__ __forceinline__ void mbar_init(uint32_t bar, int cnt) {
  asm volatile("mbarrier.init.shared::cta.b64 [%0], %1;" ::"r"(bar), "r"(cnt) : "memory");
}
__device__ __forceinline__ void mbar_expect_tx(uint32_t bar, uint32_t bytes) {
  asm volatile("mbarrier.arrive.expect_tx.shared::cta.b64 _, [%0], %1;" ::"r"(bar), "r"(bytes) : "memory");
}
__device__ __forceinline__ void mbar_arrive(uint32_t bar) {
  asm volatile("mbarrier.arrive.shared::cta.b64 _, [%0];" ::"r"(bar) : "memory");
}
__device__ __forceinline__ void mbar_arrive_cluster(uint32_t cluster_addr) {
  asm volatile("mbarrier.arrive.shared::cluster.b64 _, [%0];" ::"r"(cluster_addr) : "memory");
}
__device__ __forceinline__ void mbar_wait(uint32_t bar, uint32_t parity) {
  asm volatile("{\n.reg .pred p;\nRETRY:\nmbarrier.try_wait.parity.shared::cta.b64 p, [%0], %1;\n"
               "@!p bra.uni RETRY;\n}" ::"r"(bar), "r"(parity) : "memory");
}
__device__ __forceinline__ void mbar_wait_bounded(uint32_t bar, uint32_t parity) {
  asm volatile("{\n.reg .pred p;\n.reg .u32 c;\nmov.u32 c, 0;\nRETRY:\n"
               "mbarrier.try_wait.parity.shared::cta.b64 p, [%0], %1;\n@p bra.uni DONE;\n"
               "add.u32 c, c, 1;\nsetp.lt.u32 p, c, %2;\n@p bra.uni RETRY;\ntrap;\nDONE:\n}"
               ::"r"(bar), "r"(parity), "n"(1u << 19) : "memory");
}
__device__ __forceinline__ void tma3d(uint32_t dst, const CUtensorMap* m, uint32_t bar, int c0, int c1, int c2) {
  asm volatile(
      "cp.async.bulk.tensor.3d.shared::cluster.global.mbarrier::complete_tx::bytes [%0], [%1, {%3, %4, %5}], [%2];"
      ::"r"(dst), "l"(m), "r"(bar), "r"(c0), "r"(c1), "r"(c2) : "memory");
}
__device__ __forceinline__ void tma3d_mc(uint32_t dst, const CUtensorMap* m, uint32_t bar, int c0, int c1, int c2) {
  asm volatile(
      "cp.async.bulk.tensor.3d.shared::cluster.global.mbarrier::complete_tx::bytes.multicast::cluster"
      " [%0], [%1, {%3, %4, %5}], [%2], %6;"
      ::"r"(dst), "l"(m), "r"(bar), "r"(c0), "r"(c1), "r"(c2), "h"((uint16_t)3) : "memory");
}
__device__ __forceinline__ void tma2d(uint32_t dst, const CUtensorMap* m, uint32_t bar, int c0, int c1) {
  asm volatile(
      "cp.async.bulk.tensor.2d.shared::cluster.global.mbarrier::complete_tx::bytes [%0], [%1, {%3, %4}], [%2];"
      ::"r"(dst), "l"(m), "r"(bar), "r"(c0), "r"(c1) : "memory");
}
__device__ __forceinline__ void tma2d_store(const CUtensorMap* m, uint32_t src, int c0, int c1) {
  asm volatile("cp.async.bulk.tensor.2d.global.shared::cta.bulk_group [%0, {%2, %3}], [%1];"
               ::"l"(m), "r"(src), "r"(c0), "r"(c1) : "memory");
}
__device__ __forceinline__ int lane_id() {
  int l;
  asm volatile("mov.u32 %0, %%laneid;" : "=r"(l));
  return l;
}
__device__ __forceinline__ bool elect() {
  uint32_t p;
  asm volatile("{\n.reg .pred p;\nelect.sync _|p, 0xffffffff;\nselp.b32 %0, 1, 0, p;\n}" : "=r"(p));
  return p;
}
__device__ __forceinline__ void bulk_load(uint32_t dst, const void* src, uint32_t bytes, uint32_t bar) {
  asm volatile("cp.async.bulk.shared::cluster.global.mbarrier::complete_tx::bytes [%0], [%1], %2, [%3];"
               ::"r"(dst), "l"(src), "r"(bytes), "r"(bar) : "memory");
}
__device__ __forceinline__ void bulk_store(void* dst, uint32_t src, uint32_t bytes) {
  asm volatile("cp.async.bulk.global.shared::cta.bulk_group [%0], [%1], %2;" ::"l"(dst), "r"(src), "r"(bytes)
               : "memory");
}
__device__ __forceinline__ void bulk_commit() { asm volatile("cp.async.bulk.commit_group;" ::: "memory"); }
__device__ __forceinline__ void bulk_wait_read() { asm volatile("cp.async.bulk.wait_group.read 0;" ::: "memory"); }
__device__ __forceinline__ void bulk_wait() { asm volatile("cp.async.bulk.wait_group 0;" ::: "memory"); }
__device__ __forceinline__ void fence_async_smem() { asm volatile("fence.proxy.async.shared::cta;" ::: "memory"); }
__device__ __forceinline__ unsigned ld_relaxed(const unsigned* p) {
  unsigned v;
  asm volatile("ld.relaxed.gpu.global.u32 %0, [%1];" : "=r"(v) : "l"(p) : "memory");
  return v;
}
__device__ __forceinline__ uint2 ld_relaxed2(const uint2* p) {
  uint2 v;
  asm volatile("ld.relaxed.gpu.global.v2.u32 {%0, %1}, [%2];" : "=r"(v.x), "=r"(v.y) : "l"(p) : "memory");
  return v;
}
__device__ __forceinline__ void st_relaxed(unsigned* p, unsigned v) {
  asm volatile("st.relaxed.gpu.global.u32 [%0], %1;" ::"l"(p), "r"(v) : "memory");
}
__device__ __forceinline__ void st_release(unsigned* p, unsigned v) {
  asm volatile("st.release.gpu.global.u32 [%0], %1;" ::"l"(p), "r"(v) : "memory");
}
#define ACQ_MODE 1
__device__ __forceinline__ void wait_flags(const unsigned* p, unsigned epoch) {
  unsigned spins = 0;
  while (true) {
    const unsigned v = ld_relaxed(p);
    if (__all_sync(0xffffffffu, v == epoch)) break;
    if (++spins > kSpinLimit) __trap();
  }
  if (ACQ_MODE) asm volatile("fence.acquire.gpu;\nfence.proxy.async.global;" ::: "memory");
  __syncwarp();
}
__device__ __forceinline__ void st_packet(uint4* p, uint32_t d0, uint32_t d1, uint32_t tag) {
  asm volatile("{\n.reg .b128 v;\n.reg .b64 x, y;\nmov.b64 x, {%1, %2};\nmov.b64 y, {%3, %3};\nmov.b128 v, {x, y};\n"
               "st.relaxed.gpu.global.b128 [%0], v;\n}" ::"l"(p), "r"(d0), "r"(d1), "r"(tag) : "memory");
}
__device__ __forceinline__ void ld_packet(const uint4* p, uint32_t& d0, uint32_t& d1, uint32_t& tag) {
  asm volatile("{\n.reg .b128 v;\n.reg .b64 x, y;\n.reg .b32 u;\nld.relaxed.gpu.global.b128 v, [%3];\n"
               "mov.b128 {x, y}, v;\nmov.b64 {%0, %1}, x;\nmov.b64 {%2, u}, y;\n}"
               : "=r"(d0), "=r"(d1), "=r"(tag) : "l"(p) : "memory");
}
__device__ __forceinline__ unsigned tag_value(float v, unsigned epoch) {
  return (__float_as_uint(v) & ~7u) | (epoch & 7u);
}
__device__ __forceinline__ float untag_value(unsigned v) { return __uint_as_float(v & ~7u); }
__device__ __forceinline__ void stsm4(uint32_t a, uint32_t r0, uint32_t r1, uint32_t r2, uint32_t r3) {
  asm volatile("stmatrix.sync.aligned.m8n8.x4.shared.b16 [%0], {%1, %2, %3, %4};" ::"r"(a), "r"(r0), "r"(r1),
               "r"(r2), "r"(r3) : "memory");
}
__device__ __forceinline__ void stsm4_t(uint32_t a, uint32_t r0, uint32_t r1, uint32_t r2, uint32_t r3) {
  asm volatile("stmatrix.sync.aligned.m8n8.x4.trans.shared.b16 [%0], {%1, %2, %3, %4};" ::"r"(a), "r"(r0),
               "r"(r1), "r"(r2), "r"(r3) : "memory");
}
__device__ __forceinline__ uint32_t transpose8(uint32_t a) {
  uint32_t d;
  asm volatile("movmatrix.sync.aligned.m8n8.trans.b16 %0, %1;" : "=r"(d) : "r"(a));
  return d;
}
__device__ __forceinline__ void mma16816(float (&c)[4], uint32_t a0, uint32_t a1, uint32_t a2, uint32_t a3,
                                         uint32_t b0, uint32_t b1) {
  asm volatile("mma.sync.aligned.m16n8k16.row.col.f32.bf16.bf16.f32 {%0, %1, %2, %3}, {%4, %5, %6, %7}, {%8, %9}, "
               "{%0, %1, %2, %3};"
               : "+f"(c[0]), "+f"(c[1]), "+f"(c[2]), "+f"(c[3])
               : "r"(a0), "r"(a1), "r"(a2), "r"(a3), "r"(b0), "r"(b1));
}
__device__ __forceinline__ void mma1688(float (&c)[4], uint32_t a0, uint32_t a1, uint32_t b0) {
  asm volatile("mma.sync.aligned.m16n8k8.row.col.f32.bf16.bf16.f32 {%0, %1, %2, %3}, {%4, %5}, {%6}, {%0, %1, %2, %3};"
               : "+f"(c[0]), "+f"(c[1]), "+f"(c[2]), "+f"(c[3]) : "r"(a0), "r"(a1), "r"(b0));
}
__device__ __forceinline__ float shfl_xor(float v, int m) {
  float r;
  asm volatile("shfl.sync.bfly.b32 %0, %1, %2, 31, 0xffffffff;" : "=f"(r) : "f"(v), "r"(m));
  return r;
}
__device__ __forceinline__ float tanh_fast(float x) {
  float r;
  asm volatile("tanh.approx.f32 %0, %1;" : "=f"(r) : "f"(x));
  return r;
}
__device__ __forceinline__ void ldsm4(uint32_t a, uint32_t (&r)[4]) {
  asm volatile("ldmatrix.sync.aligned.m8n8.x4.shared.b16 {%0, %1, %2, %3}, [%4];"
               : "=r"(r[0]), "=r"(r[1]), "=r"(r[2]), "=r"(r[3]) : "r"(a) : "memory");
}
__device__ __forceinline__ void ldsm4_t(uint32_t a, uint32_t (&r)[4]) {
  asm volatile("ldmatrix.sync.aligned.m8n8.x4.trans.shared.b16 {%0, %1, %2, %3}, [%4];"
               : "=r"(r[0]), "=r"(r[1]), "=r"(r[2]), "=r"(r[3]) : "r"(a) : "memory");
}
__device__ __forceinline__ uint32_t pack2(float lo, float hi) {
  uint32_t r;
  asm volatile("cvt.rn.bf16x2.f32 %0, %1, %2;" : "=r"(r) : "f"(hi), "f"(lo));
  return r;
}
__device__ __forceinline__ float bf_lo(uint32_t r) { return __uint_as_float(r << 16); }
__device__ __forceinline__ float bf_hi(uint32_t r) { return __uint_as_float(r & 0xffff0000u); }
__device__ __forceinline__ float ex2(float x) {
  float r;
  asm("ex2.approx.ftz.f32 %0, %1;" : "=f"(r) : "f"(x));
  return r;
}
__device__ __forceinline__ float rcp(float x) {
  float r;
  asm("rcp.approx.ftz.f32 %0, %1;" : "=f"(r) : "f"(x));
  return r;
}
template <int N>
__device__ __forceinline__ void wg_wait() {
  asm volatile("wgmma.wait_group.sync.aligned %0;" ::"n"(N) : "memory");
}
__device__ __forceinline__ void yield_slot() { asm volatile("pmevent 0;"); }

template <int N, int KIND>
__device__ __forceinline__ void mma_kblock(float (&acc)[2][96], uint32_t a, uint32_t b);

#define F8(m, d, i) m(d[i]), m(d[i + 1]), m(d[i + 2]), m(d[i + 3]), m(d[i + 4]), m(d[i + 5]), m(d[i + 6]), m(d[i + 7])
#define KSTEP(N, A, B, oa0, oa1, ob, sd)                                                   \
  "mov.b64 db, {" B ", hb};\nadd.u64 db, db, " #ob ";\n"                                    \
  "mov.b64 da, {" A ", ha};\nadd.u64 da, da, " #oa0 ";\n"                                   \
  "wgmma.mma_async.sync.aligned.m64n" #N "k16.f32.bf16.bf16 {" ACC##N##_0 "}, da, db, " #sd ", 1, 1, 0, 1;\n" \
  "mov.b64 da, {" A ", ha};\nadd.u64 da, da, " #oa1 ";\n"                                   \
  "wgmma.mma_async.sync.aligned.m64n" #N "k16.f32.bf16.bf16 {" ACC##N##_1 "}, da, db, " #sd ", 1, 1, 0, 1;\n"

#define MMA_KBLOCK(N, KIND, A, B, ob2, ob3, sd, MID, MODE)                                 \
  template <>                                                                              \
  __device__ __forceinline__ void mma_kblock<N, KIND>(float (&acc)[2][96], uint32_t a, uint32_t b) { \
    asm volatile("{\n.reg .b32 ha, hb;\n.reg .b64 da, db;\n"                            \
                 "mov.b32 ha, 0x40000080;\nmov.b32 hb, 0x40000040;\n"                       \
                 "wgmma.fence.sync.aligned;\n"                                             \
                 KSTEP(N, A, B, 0, 64, 0, sd) KSTEP(N, A, B, 2, 66, 128, 1) KSTEP(N, A, B, 4, 68, ob2, 1) \
                 MID KSTEP(N, A, B, 6, 70, ob3, 1) "wgmma.commit_group.sync.aligned;\n}\n"  \
                 : OPS##N(MODE) : "r"(a), "r"(b) : "memory");                              \
  }
#define MMA_KBLOCKS(N, A, B, ob2, ob3)                                                     \
  MMA_KBLOCK(N, 0, A, B, ob2, ob3, 1, "", "+f")                                            \
  MMA_KBLOCK(N, 1, A, B, ob2, ob3, 1, "wgmma.commit_group.sync.aligned;\n", "+f")          \
  MMA_KBLOCK(N, 2, A, B, ob2, ob3, 0, "", "=f")

#define ACC128_0 \
  "%0, %1, %2, %3, %4, %5, %6, %7, %8, %9, %10, %11, %12, %13, %14, %15, " \
  "%16, %17, %18, %19, %20, %21, %22, %23, %24, %25, %26, %27, %28, %29, %30, %31, " \
  "%32, %33, %34, %35, %36, %37, %38, %39, %40, %41, %42, %43, %44, %45, %46, %47, " \
  "%48, %49, %50, %51, %52, %53, %54, %55, %56, %57, %58, %59, %60, %61, %62, %63"
#define ACC128_1 \
  "%64, %65, %66, %67, %68, %69, %70, %71, %72, %73, %74, %75, %76, %77, %78, %79, " \
  "%80, %81, %82, %83, %84, %85, %86, %87, %88, %89, %90, %91, %92, %93, %94, %95, " \
  "%96, %97, %98, %99, %100, %101, %102, %103, %104, %105, %106, %107, %108, %109, %110, %111, " \
  "%112, %113, %114, %115, %116, %117, %118, %119, %120, %121, %122, %123, %124, %125, %126, %127"
#define OPS128(m) \
  F8(m, acc[0], 0), F8(m, acc[0], 8), F8(m, acc[0], 16), F8(m, acc[0], 24), F8(m, acc[0], 32), F8(m, acc[0], 40), F8(m, acc[0], 48), F8(m, acc[0], 56), \
        F8(m, acc[1], 0), F8(m, acc[1], 8), F8(m, acc[1], 16), F8(m, acc[1], 24), F8(m, acc[1], 32), F8(m, acc[1], 40), F8(m, acc[1], 48), F8(m, acc[1], 56)
MMA_KBLOCKS(128, "%128", "%129", 512, 640)

#define ACC192_0 \
  "%0, %1, %2, %3, %4, %5, %6, %7, %8, %9, %10, %11, %12, %13, %14, %15, " \
  "%16, %17, %18, %19, %20, %21, %22, %23, %24, %25, %26, %27, %28, %29, %30, %31, " \
  "%32, %33, %34, %35, %36, %37, %38, %39, %40, %41, %42, %43, %44, %45, %46, %47, " \
  "%48, %49, %50, %51, %52, %53, %54, %55, %56, %57, %58, %59, %60, %61, %62, %63, " \
  "%64, %65, %66, %67, %68, %69, %70, %71, %72, %73, %74, %75, %76, %77, %78, %79, " \
  "%80, %81, %82, %83, %84, %85, %86, %87, %88, %89, %90, %91, %92, %93, %94, %95"
#define ACC192_1 \
  "%96, %97, %98, %99, %100, %101, %102, %103, %104, %105, %106, %107, %108, %109, %110, %111, " \
  "%112, %113, %114, %115, %116, %117, %118, %119, %120, %121, %122, %123, %124, %125, %126, %127, " \
  "%128, %129, %130, %131, %132, %133, %134, %135, %136, %137, %138, %139, %140, %141, %142, %143, " \
  "%144, %145, %146, %147, %148, %149, %150, %151, %152, %153, %154, %155, %156, %157, %158, %159, " \
  "%160, %161, %162, %163, %164, %165, %166, %167, %168, %169, %170, %171, %172, %173, %174, %175, " \
  "%176, %177, %178, %179, %180, %181, %182, %183, %184, %185, %186, %187, %188, %189, %190, %191"
#define OPS192(m) \
  F8(m, acc[0], 0), F8(m, acc[0], 8), F8(m, acc[0], 16), F8(m, acc[0], 24), F8(m, acc[0], 32), F8(m, acc[0], 40), F8(m, acc[0], 48), F8(m, acc[0], 56), F8(m, acc[0], 64), F8(m, acc[0], 72), F8(m, acc[0], 80), F8(m, acc[0], 88), \
        F8(m, acc[1], 0), F8(m, acc[1], 8), F8(m, acc[1], 16), F8(m, acc[1], 24), F8(m, acc[1], 32), F8(m, acc[1], 40), F8(m, acc[1], 48), F8(m, acc[1], 56), F8(m, acc[1], 64), F8(m, acc[1], 72), F8(m, acc[1], 80), F8(m, acc[1], 88)
MMA_KBLOCKS(192, "%192", "%193", 768, 896)

#define HSTEP(oa, ob)                                                                       \
  "mov.b64 db, {%97, hb};\nadd.u64 db, db, " #ob ";\nmov.b64 da, {%96, ha};\nadd.u64 da, da, " #oa ";\n" \
  "wgmma.mma_async.sync.aligned.m64n192k16.f32.bf16.bf16 {" ACC192_0 "}, da, db, 1, 1, 1, 0, 1;\n"
__device__ __forceinline__ void mma_half(float (&d)[96], uint32_t a, uint32_t b) {
  asm volatile("{\n.reg .b32 ha, hb;\n.reg .b64 da, db;\nmov.b32 ha, 0x40000080;\nmov.b32 hb, 0x40000040;\n"
               "wgmma.fence.sync.aligned;\n" HSTEP(0, 0) HSTEP(2, 128) HSTEP(4, 768) HSTEP(6, 896)
               "wgmma.commit_group.sync.aligned;\n}\n"
               : F8("+f", d, 0), F8("+f", d, 8), F8("+f", d, 16), F8("+f", d, 24), F8("+f", d, 32), F8("+f", d, 40),
                 F8("+f", d, 48), F8("+f", d, 56), F8("+f", d, 64), F8("+f", d, 72), F8("+f", d, 80), F8("+f", d, 88)
               : "r"(a), "r"(b) : "memory");
}

#define TSTEP(REGS, W, X, ow, ox)                                                           \
  "mov.b64 db, {" X ", hi};\nadd.u64 db, db, " #ox ";\nmov.b64 da, {" W ", hi};\nadd.u64 da, da, " #ow ";\n" \
  "wgmma.mma_async.sync.aligned.m64n128k16.f32.bf16.bf16 {" REGS "}, da, db, 1, 1, 1, 1, 0;\n"
#define THEAD "{\n.reg .b32 hi;\n.reg .b64 da, db;\nmov.b32 hi, 0x40000040;\nwgmma.fence.sync.aligned;\n"
#define TTAIL "wgmma.commit_group.sync.aligned;\n}\n"
__device__ __forceinline__ void mma_kblock_t(float (&acc)[2][96], uint32_t wd, uint32_t xd) {
  asm volatile(THEAD TSTEP(ACC128_0, "%128", "%129", 0, 0) TSTEP(ACC128_1, "%128", "%129", 256, 0)
               TSTEP(ACC128_0, "%128", "%129", 128, 2) TSTEP(ACC128_1, "%128", "%129", 384, 2)
               TSTEP(ACC128_0, "%128", "%129", 512, 4) TSTEP(ACC128_1, "%128", "%129", 768, 4)
               TSTEP(ACC128_0, "%128", "%129", 640, 6) TSTEP(ACC128_1, "%128", "%129", 896, 6) TTAIL
               : OPS128("+f") : "r"(wd), "r"(xd) : "memory");
}
__device__ __forceinline__ void mma_half_t(float (&d)[96], uint32_t wd, uint32_t xd) {
  asm volatile(THEAD TSTEP(ACC128_0, "%64", "%65", 0, 0) TSTEP(ACC128_0, "%64", "%65", 128, 2)
               TSTEP(ACC128_0, "%64", "%65", 512, 4) TSTEP(ACC128_0, "%64", "%65", 640, 6) TTAIL
               : F8("+f", d, 0), F8("+f", d, 8), F8("+f", d, 16), F8("+f", d, 24), F8("+f", d, 32), F8("+f", d, 40),
                 F8("+f", d, 48), F8("+f", d, 56) : "r"(wd), "r"(xd) : "memory");
}

enum { kModePlain = 0, kModeHead = 1, kModeSkip = 2, kModeContinue = 3 };

template <int N>
__device__ __forceinline__ void fence_acc(float (&acc)[2][96]) {
#pragma unroll
  for (int h = 0; h < 2; h++)
#pragma unroll
    for (int i = 0; i < N / 2; i++) asm volatile("" : "+f"(acc[h][i])::"memory");
}

constexpr uint32_t kToB = (kTileBytes >> 4) + ((4096u >> 4) << 16) - (1u << 16);

#define TRACE_KB(nb)

#define HEAD_BOTH 4
template <int N>
__device__ __forceinline__ void head_blocks(float (&acc)[2][96], uint32_t sb, int n0, int slot, int xver,
                                            uint32_t rel_addr, bool rel) {
  const uint32_t ring = (((sb & 0x3FFFF) + kSmRing) >> 4) | (1u << 16);
  const uint32_t xdesc = (((sb & 0x3FFFF) + kSmX) >> 4) | (1u << 16);
  const uint32_t s0 = ring + slot * 2560, s1 = ring + ((slot + 1) & 3) * 2560;
  const uint32_t nb = n0 * 8, xbar = sb + kBarX + (xver - 1) * 16;
  if (xver > 0) {
    mbar_wait(xbar + ((HEAD_BOTH >> xver) & 1) * 8, 0);
    mbar_wait(sb + kBarTurn + (xver == 1 ? 2 : 3 * xver) * 8, 0);
  }
  mbar_wait(sb + kBarFull + (nb & 56), nb >> 6);
  if (n0 == 0) TRACE_AT(0, 1);
  TRACE_KB(nb);
  mma_kblock<N, 2>(acc, xver > 0 ? xdesc : s0, s0 + kToB);
  if (xver > 0) mbar_wait(xbar + 8, 0);
  mbar_wait(sb + kBarFull + (nb & 56) + 8, nb >> 6);
  TRACE_KB(nb + 8);
  mma_kblock<N, 0>(acc, xver > 0 ? xdesc + (kTileBytes >> 4) : s1, s1 + kToB);
  wg_wait<1>();
  if (rel) mbar_arrive_cluster(rel_addr + (nb & 56));
  wg_wait<0>();
  if (rel) mbar_arrive_cluster(rel_addr + (nb & 56) + 8);
  fence_acc<N>(acc);
}

enum { kPlain, kFresh, kResid, kStagger };
template <int N, int KIND, class Pre>
__device__ __forceinline__ void mainloop(float (&acc)[2][96], uint32_t sb, int tile, int n0, int slot, int nkb,
                                         int pause_kk, int att, uint32_t rel_addr, bool rel, int own_kk, Pre pre) {
  constexpr bool RESID = KIND == kResid, FRESH = KIND == kFresh;
  constexpr uint32_t kStep = (N == 192 ? 5 : 4) * 512;
  const uint32_t ring = (((sb & 0x3FFFF) + kSmRing) >> 4) | (1u << 16);
  uint32_t st = ring + slot * kStep;
  uint32_t nb = n0 * 8, prev = 64;
  const uint32_t last = nb + 8 * (nkb - (RESID ? 3 : KIND == kStagger ? 2 : 1)), own = nb + 8 * own_kk;
  const uint32_t stg = (((sb & 0x3FFFF) + kSmStg) >> 4) | (1u << 16);
  uint32_t stop = pause_kk >= 0 ? nb + 8 * pause_kk : last;
  const bool signal = (threadIdx.x & 127) == 64;
  if (!FRESH) fence_acc<N>(acc);
  if (tile > 0) mbar_wait(sb + kBarTurn + (tile - 1) * 8, 0);
  TRACE_AT(tile, 0);
  if constexpr (FRESH) {
    mbar_wait(sb + kBarFull + (nb & 56), nb >> 6);
    TRACE_KB(nb);
    mma_kblock<N, 2>(acc, st, st + kToB);
    prev = nb & 56;
    st += kStep;
    nb += 8;
  }
#pragma unroll 1
  while (true) {
#pragma unroll 1
    do {
      mbar_wait(sb + kBarFull + (nb & 56), nb >> 6);
      TRACE_KB(nb);
      if constexpr (RESID) mma_kblock_t(acc, st + kToB, nb == own ? stg : st);
      else mma_kblock<N, 0>(acc, st, st + kToB);
      wg_wait<1>();
      if (rel) mbar_arrive_cluster(rel_addr + prev);
      prev = nb & 56;
      st += kStep;
      if (st == ring + 10240) st = ring;
      nb += 8;
    } while (nb != stop);
    if (stop == last) break;
    stop = last;
    if (signal) mbar_arrive(sb + kBarPause + att * 8);
    wg_wait<0>();
    if (rel) mbar_arrive_cluster(rel_addr + prev);
    prev = 64;
    mbar_wait(sb + kBarResume + att * 8, 0);
  }
  mbar_wait(sb + kBarFull + (nb & 56), nb >> 6);
  TRACE_KB(nb);
  if constexpr (RESID) {
    const uint32_t z = gridDim.y - 1;
    const uint32_t s2 = st + kStep, s3 = s2 == ring + 8192 ? ring : s2 + kStep;
    mma_half_t(acc[0], st + kToB, st);
    wg_wait<1>();
    if (rel) mbar_arrive_cluster(rel_addr + 32);
    mbar_wait(sb + kBarFull + 48, nb >> 6);
    TRACE_KB(nb + 8);
    mma_half_t(acc[0], s2 + kToB, s2);
    mbar_wait(sb + kBarFull + 56, nb >> 6);
    TRACE_KB(nb + 16);
    mma_half_t(acc[0], s3 + kToB, s3);
    mma_half_t(acc[1], st + kToB + 256, st + z);
    mma_half_t(acc[1], s2 + kToB + 256, s2 + z);
    wg_wait<2>();
#pragma unroll
    for (int i = 0; i < 64; i++) asm volatile("" : "+f"(acc[0][i])::"memory");
    pre(0);
    mma_half_t(acc[1], s3 + kToB + 256, s3 + z);
    wg_wait<2>();
    if (rel) mbar_arrive_cluster(rel_addr + 40);
    pre(1);
    wg_wait<1>();
    if (rel) mbar_arrive_cluster(rel_addr + 48);
    if (signal) mbar_arrive(sb + kBarTurn + tile * 8);
    wg_wait<0>();
    if (rel) mbar_arrive_cluster(rel_addr + 56);
#pragma unroll
    for (int i = 0; i < 64; i++) asm volatile("" : "+f"(acc[1][i])::"memory");
  } else if constexpr (KIND == kStagger) {
    const uint32_t z = gridDim.y - 1, s2 = st + kStep;
    mma_half(acc[1], st + 64, st + kToB);
    wg_wait<1>();
    if (rel) mbar_arrive_cluster(rel_addr + 40);
    mbar_wait(sb + kBarFull + 56, nb >> 6);
    TRACE_KB(nb + 8);
    mma_half(acc[1], s2 + 64, s2 + kToB);
    mma_half(acc[0], st, st + z + kToB);
    pre(0);
    mma_half(acc[0], s2, s2 + z + kToB);
    wg_wait<2>();
#pragma unroll
    for (int i = 0; i < 96; i++) asm volatile("" : "+f"(acc[1][i])::"memory");
    pre(1);
    wg_wait<1>();
    if (rel) mbar_arrive_cluster(rel_addr + 48);
    pre(2);
    if (signal) mbar_arrive(sb + kBarTurn + tile * 8);
    pre(3);
    wg_wait<0>();
    if (rel) mbar_arrive_cluster(rel_addr + 56);
#pragma unroll
    for (int i = 0; i < 96; i++) asm volatile("" : "+f"(acc[0][i])::"memory");
  } else {
    mma_kblock<N, 1>(acc, st, st + kToB);
    wg_wait<2>();
    if (rel) mbar_arrive_cluster(rel_addr + prev);
    pre();
    wg_wait<1>();
    if (signal) mbar_arrive(sb + kBarTurn + tile * 8);
    wg_wait<0>();
    if (rel) mbar_arrive_cluster(rel_addr + (nb & 56));
    fence_acc<N>(acc);
  }
}

__device__ __forceinline__ void publish_stats(uint32_t sb, uint2* stat, int w, int lane, unsigned epoch) {
  const uint32_t row = sb + kSmX + (32 * w + lane) * 128;
  float s[4], q[4];
#pragma unroll
  for (int c = 0; c < 4; c++) s[c] = q[c] = 0.f;
  uint32_t nx[4];
  ldsm4(row + ((lane & 7) << 4), nx);
#pragma unroll 1
  for (int J = 1; J <= 16; J++) {
    const uint32_t r[4] = {nx[0], nx[1], nx[2], nx[3]};
    ldsm4(row + ((J >> 3) & 1) * kTileBytes + (((J ^ lane) & 7) << 4), nx);
#pragma unroll
    for (int c = 0; c < 4; c++) {
      const float lo = bf_lo(r[c]);
      s[c] += lo;
      q[c] = fmaf(lo, lo, q[c]);
      if (c & 1) yield_slot();
    }
#pragma unroll
    for (int c = 0; c < 4; c++) {
      const float hi = bf_hi(r[c]);
      s[c] += hi;
      q[c] = fmaf(hi, hi, q[c]);
      if (c & 1) yield_slot();
    }
  }
  const int t = lane & 3, g = lane >> 2;
#pragma unroll
  for (int c = 0; c < 2; c++) {
    s[c] = (t & 2 ? s[c + 2] : s[c]) + shfl_xor(t & 2 ? s[c] : s[c + 2], 2);
    q[c] = (t & 2 ? q[c + 2] : q[c]) + shfl_xor(t & 2 ? q[c] : q[c + 2], 2);
  }
  const float so = (t & 1 ? s[1] : s[0]) + shfl_xor(t & 1 ? s[0] : s[1], 1);
  const float qo = (t & 1 ? q[1] : q[0]) + shfl_xor(t & 1 ? q[0] : q[1], 1);
  asm volatile("st.relaxed.gpu.global.v2.u32 [%0], {%1, %2};" ::"l"(stat + 32 * w + 8 * t + g),
               "r"(tag_value(so, epoch)), "r"(tag_value(qo, epoch)) : "memory");
}

__device__ __forceinline__ void add_chunk(float (&a)[8], const uint4& v) {
  a[0] += bf_lo(v.x); a[1] += bf_hi(v.x);
  a[2] += bf_lo(v.y); a[3] += bf_hi(v.y);
  a[4] += bf_lo(v.z); a[5] += bf_hi(v.z);
  a[6] += bf_lo(v.w); a[7] += bf_hi(v.w);
}

__device__ __forceinline__ int helper_col(int id, int slab) {
  return (slab < 3 ? slab * kD : (slab - 3) * 512) + id * 128;
}
__device__ __forceinline__ void helper_cta(const CUtensorMap* map_q, const CUtensorMap* map_1, uint8_t* sm,
                                           uint32_t sb, int id, int warp) {
  constexpr int kRed = 6 * 32768, kBar = kRed + 2 * 4096;
  const int tid = threadIdx.x;
  if (warp == 8 && elect()) {
#pragma unroll
    for (int s = 0; s < 6; s++) {
      mbar_init(sb + kBar + s * 8, 1);
      mbar_init(sb + kBar + 64 + s * 8, 4);
    }
    fence_async_smem();
#pragma unroll
    for (int s = 0; s < 6; s++) {
      mbar_expect_tx(sb + kBar + s * 8, 32768);
      tma2d(sb + s * 32768, map_q, sb + kBar + s * 8, id * 128, s * 128);
    }
  }
  __syncthreads();
  if (warp == 8) {
    int slot = 0, ph = 0;
#pragma unroll 1
    for (int n = 6; n < 80; n++) {
      mbar_wait(sb + kBar + 64 + slot * 8, ph);
      if (elect()) {
        mbar_expect_tx(sb + kBar + slot * 8, 32768);
        tma2d(sb + slot * 32768, n < 24 ? map_q : map_1, sb + kBar + slot * 8, helper_col(id, n >> 3), (n & 7) * 128);
      }
      if (++slot == 6) slot = 0, ph ^= 1;
    }
  } else if (warp < 8) {
    if (tid == 0) *reinterpret_cast<unsigned*>(sm + kBar + 128) = atomicAdd(&g_ticket, 1u) / kGrid + 1;
    int slot = warp >> 2, ph = 0;
#pragma unroll 1
    for (int slab = 0; slab < 10; slab++) {
      float a[8];
#pragma unroll
      for (int e = 0; e < 8; e++) a[e] = 0.f;
#pragma unroll 1
      for (int box = 0; box < 4; box++) {
        mbar_wait_bounded(sb + kBar + slot * 8, ph);
        const uint4* p = reinterpret_cast<const uint4*>(sm + slot * 32768) + (tid & 127);
        uint4 v[16];
#pragma unroll
        for (int i = 0; i < 16; i++) v[i] = p[i * 128];
        __syncwarp();
        if (elect()) mbar_arrive(sb + kBar + 64 + slot * 8);
#pragma unroll
        for (int i = 0; i < 16; i++) add_chunk(a, v[i]);
        slot += 2;
        if (slot >= 6) slot -= 6, ph ^= 1;
      }
      float* red = reinterpret_cast<float*>(sm + kRed + (slab & 1) * 4096);
#pragma unroll
      for (int e = 0; e < 8; e++) a[e] += shfl_xor(a[e], 16);
      if ((tid & 16) == 0) {
        float4* d = reinterpret_cast<float4*>(red + warp * 128 + (tid & 15) * 8);
        d[0] = make_float4(a[0], a[1], a[2], a[3]);
        d[1] = make_float4(a[4], a[5], a[6], a[7]);
      }
      asm volatile("bar.sync 1, 256;" ::: "memory");
      if (warp < 4) {
        float t = 0.f;
#pragma unroll
        for (int q = 0; q < 8; q++) t += red[q * 128 + tid];
        st_relaxed(g_cs + (slab < 3 ? 0 : 3 * kD) + helper_col(id, slab) + tid,
                   tag_value(t, *reinterpret_cast<volatile unsigned*>(sm + kBar + 128)));
      }
    }
  }
}

__device__ __forceinline__ void colsum_strip(const CUtensorMap* map, uint8_t* sm, uint32_t sb, int col, int half,
                                             int lane, unsigned epoch) {
  const uint32_t bar = sb + kBarSlab + half * 16;
  const int buf = kSmStg + half * 8192;
  float a[8];
#pragma unroll
  for (int e = 0; e < 8; e++) a[e] = 0.f;
#pragma unroll 1
  for (int r = -2; r < 4; r++) {
    if (r >= 0) {
      mbar_wait(bar + (r & 1) * 8, r >> 1);
      const uint4* p = reinterpret_cast<const uint4*>(sm + buf + (r & 1) * 4096) + lane;
#pragma unroll 1
      for (int q = 0; q < 8; q += 4) {
        uint4 v[4];
#pragma unroll
        for (int u = 0; u < 4; u++) v[u] = p[(q + u) * 32];
#pragma unroll
        for (int u = 0; u < 4; u++) {
          a[0] += bf_lo(v[u].x); a[1] += bf_hi(v[u].x); a[2] += bf_lo(v[u].y); a[3] += bf_hi(v[u].y);
          yield_slot();
          a[4] += bf_lo(v[u].z); a[5] += bf_hi(v[u].z); a[6] += bf_lo(v[u].w); a[7] += bf_hi(v[u].w);
          yield_slot();
        }
      }
      fence_async_smem();
      __syncwarp();
    }
    if (r < 2 && elect()) {
      mbar_expect_tx(bar + (r & 1) * 8, 4096);
      tma2d(sb + buf + (r & 1) * 4096, map, bar + (r & 1) * 8, col, half * 512 + (r + 2) * 128);
    }
  }
#pragma unroll
  for (int e = 0; e < 4; e++) a[e] = (lane & 16 ? a[e + 4] : a[e]) + shfl_xor(lane & 16 ? a[e] : a[e + 4], 16);
#pragma unroll
  for (int e = 0; e < 2; e++) a[e] = (lane & 8 ? a[e + 2] : a[e]) + shfl_xor(lane & 8 ? a[e] : a[e + 2], 8);
  a[0] = (lane & 4 ? a[1] : a[0]) + shfl_xor(lane & 4 ? a[0] : a[1], 4);
  a[0] += shfl_xor(a[0], 2);
  if (!(lane & 2)) st_relaxed(g_cs + half * (3 * kD + kF) + col + (lane & 1) * 8 + (lane >> 2), tag_value(a[0], epoch));
}

constexpr float kGeluBeta = 0.3292034911525734f;
constexpr float kGeluK = 2.423681954311584f;

__device__ __forceinline__ void store_staged(uint8_t* dst, uint32_t stg) {
  fence_async_smem();
  __syncwarp();
  if (elect()) {
    bulk_store(dst, stg, 4096);
    bulk_commit();
  }
}

#define GY_MASK 5
#define GD 2
#define GF_MASK 3
#define GY(k) if ((GY_MASK >> k) & 1) yield_slot()
template <int J0, int J1>
__device__ __forceinline__ void fold_norm(float (&acc)[2][96], const float2 (&st)[4], const float4* vec) {
  float4 vn = vec[J0 * 4];
#pragma unroll
  for (int J = J0; J < J1; J++) {
    const float4 v = vn;
    if (J + 1 < J1) vn = vec[J * 4 + 4];
#pragma unroll
    for (int c = 0; c < 4; c++) {
      float& a0 = acc[c & 1][4 * J + (c & 2)];
      float& a1 = acc[c & 1][4 * J + (c & 2) + 1];
      a0 = fmaf(a0, st[c].x, fmaf(st[c].y, v.x, v.z));
      a1 = fmaf(a1, st[c].x, fmaf(st[c].y, v.y, v.w));
      asm volatile("" : "+f"(a0), "+f"(a1));
      if ((c & 1) && ((GF_MASK >> (c >> 1)) & 1)) yield_slot();
    }
  }
}

template <int CH, class Acquire>
__device__ __forceinline__ void gelu_chunk(const float (&acc)[2][96], uint32_t stg, int lane, uint8_t* prev,
                                           Acquire acquire) {
  uint32_t pk[8][4];
  float z[GD + 1][4];
  const uint32_t row = (stg + lane * 128) ^ ((lane & 7) << 4);
#define U(s, e) acc[(e) >> 1][4 * (CH * 8 + ((s) >> 1)) + 2 * ((s) & 1) + ((e) & 1)]
#pragma unroll
  for (int s = 0; s < 16 + GD; s++) {
    const int cur = s % (GD + 1), p1 = (s + GD) % (GD + 1), p2 = (s + 1) % (GD + 1), q = s - GD, jj = 2 * q - 24;
    const bool mid = s >= 1 && s < 17;
    if (mid) z[p1][0] = tanh_fast(z[p1][0]);
    if (s < 16) {
#pragma unroll
      for (int e = 0; e < 4; e++) {
        z[cur][e] = fmaf(U(s, e), U(s, e), kGeluK);
        asm volatile("" : "+f"(z[cur][e]));
      }
    }
    if (jj >= 0) stsm4(row ^ (jj << 4), pk[jj][0], pk[jj][1], pk[jj][2], pk[jj][3]);
    GY(0);
    if (mid) z[p1][1] = tanh_fast(z[p1][1]);
    if (q >= 0) {
      pk[q >> 1][2 * (q & 1)] = pack2(fmaf(U(q, 0), z[p2][0], U(q, 0)), fmaf(U(q, 1), z[p2][1], U(q, 1)));
      pk[q >> 1][2 * (q & 1) + 1] = pack2(fmaf(U(q, 2), z[p2][2], U(q, 2)), fmaf(U(q, 3), z[p2][3], U(q, 3)));
    }
    GY(1);
    if (mid) z[p1][2] = tanh_fast(z[p1][2]);
    if (s < 16) {
#pragma unroll
      for (int e = 0; e < 4; e++) {
        z[cur][e] *= U(s, e);
        asm volatile("" : "+f"(z[cur][e]));
      }
    }
    if (mid) z[p1][3] = tanh_fast(z[p1][3]);
    if (jj >= 0) stsm4(row ^ ((jj + 1) << 4), pk[jj + 1][0], pk[jj + 1][1], pk[jj + 1][2], pk[jj + 1][3]);
    GY(2);
    if (CH == 1 && s == 1) store_staged(prev, stg);
    if (q == 11) acquire();
  }
#undef U
}

__device__ __forceinline__ void scale_stats(float2 (&st)[4]) {
#pragma unroll
  for (int c = 0; c < 4; c++) {
    st[c].x *= kGeluBeta;
    st[c].y *= st[c].x;
  }
}

__device__ __forceinline__ void add_mean_term(float (&acc)[2][96], const float2 (&st)[4], uint8_t* sm, int tq,
                                              int lane) {
  const float2* cs = reinterpret_cast<const float2*>(sm + kSmCsQ) + tq * 96 + (lane & 3);
  float2 vn = cs[0];
#pragma unroll
  for (int J = 0; J < 24; J++) {
    const float2 v = vn;
    if (J < 23) vn = cs[J * 4 + 4];
#pragma unroll
    for (int c = 0; c < 4; c++) {
      acc[c & 1][4 * J + (c & 2)] = fmaf(st[c].y, v.x, acc[c & 1][4 * J + (c & 2)]);
      acc[c & 1][4 * J + (c & 2) + 1] = fmaf(st[c].y, v.y, acc[c & 1][4 * J + (c & 2) + 1]);
    }
    yield_slot();
  }
}

#define CV_MASK 1
#define HALO_AT 2
struct AttnRegs {
  uint32_t q[4][8], k[5][8], vt[5][8];
};
#define SCALED(c, J) pack2(acc[(c) & 1][4 * (J) + ((c) & 2)] * st[c].x, acc[(c) & 1][4 * (J) + ((c) & 2) + 1] * st[c].x)
__device__ __forceinline__ void convert_group(const float (&acc)[2][96], const float2 (&st)[4], AttnRegs& r, int c,
                                              int part) {
#pragma unroll
  for (int J = 0; J < 8; J++) {
    if (part == 0) r.q[c][J] = SCALED(c, J);
    if (part == 1) r.k[c + 1][J] = SCALED(c, 8 + J);
    if (part == 2) r.vt[c + 1][J] = transpose8(SCALED(c, 16 + J));
    if ((J & CV_MASK) == CV_MASK) yield_slot();
  }
}
#undef SCALED

__device__ __forceinline__ void convert_odd(const float (&acc)[2][96], const float2 (&st)[4], AttnRegs& r, int step,
                                            uint8_t* sm, uint32_t halo_bar, uint4* halo_out, bool send,
                                            unsigned epoch, int w, int lane) {
  if (step == 1) {
    convert_group(acc, st, r, 3, 2);
    convert_group(acc, st, r, 3, 1);
    if (w < 3) {
      uint2* hs = reinterpret_cast<uint2*>(sm + kSmHalo + w * 2048) + lane;
#pragma unroll
      for (int i = 0; i < 4; i++) {
        hs[i * 32] = make_uint2(r.k[4][2 * i], r.k[4][2 * i + 1]);
        hs[128 + i * 32] = make_uint2(r.vt[4][2 * i], r.vt[4][2 * i + 1]);
      }
      __syncwarp();
      if (elect()) mbar_arrive(halo_bar + w * 8);
    } else if (send) {
#pragma unroll
      for (int i = 0; i < 4; i++) {
        st_packet(halo_out + lane + i * 32, r.k[4][2 * i], r.k[4][2 * i + 1], epoch);
        st_packet(halo_out + lane + 128 + i * 32, r.vt[4][2 * i], r.vt[4][2 * i + 1], epoch);
      }
    }
  } else if (step == 2) {
    convert_group(acc, st, r, 1, 2);
  } else {
    convert_group(acc, st, r, 1, 1);
    convert_group(acc, st, r, 3, 0);
    convert_group(acc, st, r, 1, 0);
  }
}

__device__ __forceinline__ void epilogue_attn(const float (&acc)[2][96], const float2 (&st)[4], AttnRegs& r,
                                              uint8_t* sm, uint32_t sb, int layer, int tq, int b, int j,
                                              unsigned epoch, int tile, int w, int lane) {
  const int t = lane & 3, g = lane >> 2;
  const int hp = j + 8 * tq, att = 2 * layer + tq;
  auto& q = r.q;
  auto& k = r.k;
  auto& vt = r.vt;
  const bool first = w == 0 && (b & 7) == 0;
  const uint4* gh = g_halo + ((layer * 16 + b - 1) * 16 + hp) * 256 + lane;
  uint32_t tag[8];
#define LOAD_HALO()                                                                                    \
  _Pragma("unroll") for (int i = 0; i < 4; i++) {                                                      \
    ld_packet(gh + i * 32, k[0][2 * i], k[0][2 * i + 1], tag[i]);                                      \
    ld_packet(gh + 128 + i * 32, vt[0][2 * i], vt[0][2 * i + 1], tag[4 + i]);                          \
  }
#define AWAIT_HALO()                                                                                   \
  for (unsigned spins = 0;; spins++) {                                                                 \
    const unsigned d0 = (tag[0] ^ epoch) | (tag[1] ^ epoch) | (tag[2] ^ epoch) | (tag[3] ^ epoch);     \
    const unsigned d1 = (tag[4] ^ epoch) | (tag[5] ^ epoch) | (tag[6] ^ epoch) | (tag[7] ^ epoch);     \
    if (__all_sync(0xffffffffu, (d0 | d1) == 0)) break;                                                \
    if (spins > kSpinLimit) __trap();                                                                  \
    LOAD_HALO();                                                                                       \
  }
#pragma unroll
  for (int c = 0; c <= 6; c++) {
    if (c == HALO_AT) {
#pragma unroll
      for (int i = 0; i < 8; i++) k[0][i] = vt[0][i] = tag[i] = 0u;
      if (w > 0) {
        mbar_wait(sb + kBarHalo + (att * 3 + w - 1) * 8, 0);
        const uint2* hs = reinterpret_cast<const uint2*>(sm + kSmHalo + (w - 1) * 2048) + lane;
#pragma unroll
        for (int i = 0; i < 4; i++) {
          const uint2 a = hs[i * 32], d = hs[128 + i * 32];
          k[0][2 * i] = a.x; k[0][2 * i + 1] = a.y;
          vt[0][2 * i] = d.x; vt[0][2 * i + 1] = d.y;
        }
      } else if (!first) {
        LOAD_HALO();
      }
    }
    if (c < 6) convert_group(acc, st, r, 2 * (c & 1), 2 - (c >> 1));
  }
  TRACE_AT(tile, 8);
  if (w == 0 && !first) AWAIT_HALO();
  constexpr float kScale = 0.17677669529663687f * 1.4426950408889634f;
  const bool own0 = 2 * t <= g, own1 = 2 * t + 1 <= g;
  const uint32_t own_mask = (own0 ? 0xffffu : 0u) | (own1 ? 0xffff0000u : 0u);
  const uint32_t stg = sb + kSmStg + w * 4096;
  const uint32_t orow = stg + (lane & 7) * 128, ochunk = (lane >> 3) ^ (lane & 7);
  TRACE_AT(tile, 9);
  mbar_wait(sb + kBarPause + att * 8, 0);
  TRACE_AT(tile, 10);

  float s[2][6][4], o[2][4][2][4];
#pragma unroll
  for (int n = 0; n < 24; n++) {
    const int ks = n / 12, hd = (n % 12) / 6, m = n % 6, ca = 2 * (m / 3), kg = ca + m % 3, J = 4 * hd + 2 * ks;
    if (ks == 0) s[hd][m][0] = s[hd][m][1] = s[hd][m][2] = s[hd][m][3] = 0.f;
    mma16816(s[hd][m], q[ca][J], q[ca + 1][J], q[ca][J + 1], q[ca + 1][J + 1], k[kg][J], k[kg][J + 1]);
  }
  float v0[2][4], v1[2][4], m[2][4];
  uint32_t pp[2][4], po[2][4];
#define UNITS _Pragma("unroll") for (int hd = 0; hd < 2; hd++) _Pragma("unroll") for (int c = 0; c < 4; c++)
  UNITS {
    const int mp = 3 * (c >> 1) + (c & 1), r = 2 * (c & 1);
    float p0 = s[hd][mp][r], p1 = s[hd][mp][r + 1];
    if (c == 0 && first) p0 = p1 = -INFINITY;
    v0[hd][c] = own0 ? s[hd][mp + 1][r] : p0;
    v1[hd][c] = own1 ? s[hd][mp + 1][r + 1] : p1;
    m[hd][c] = fmaxf(v0[hd][c], v1[hd][c]);
  }
  UNITS m[hd][c] = fmaxf(m[hd][c], shfl_xor(m[hd][c], 1));
  UNITS m[hd][c] = fmaxf(m[hd][c], shfl_xor(m[hd][c], 2));
  UNITS {
    const float nm = -m[hd][c] * kScale;
    v0[hd][c] = ex2(fmaf(v0[hd][c], kScale, nm));
    v1[hd][c] = ex2(fmaf(v1[hd][c], kScale, nm));
    m[hd][c] = v0[hd][c] + v1[hd][c];
  }
  UNITS m[hd][c] += shfl_xor(m[hd][c], 1);
  UNITS m[hd][c] += shfl_xor(m[hd][c], 2);
  UNITS {
    const float inv = rcp(m[hd][c]);
    const uint32_t p = pack2(v0[hd][c] * inv, v1[hd][c] * inv);
    pp[hd][c] = p & ~own_mask;
    po[hd][c] = p & own_mask;
    asm volatile("" : "+r"(pp[hd][c]), "+r"(po[hd][c]));
  }
#pragma unroll
  for (int n = 0; n < 24; n++) {
    const int ph = n / 8, hd = (n >> 2) & 1, c = 2 * ((n >> 1) & 1) + (ph == 1), ds = n & 1, J = 4 * hd + 2 * ds;
    float(&d)[4] = o[hd][c][ds];
    if (ph < 2) d[0] = d[1] = d[2] = d[3] = 0.f;
    if (ph == 0) mma1688(d, vt[c + 1][J], vt[c + 1][J + 1], po[hd][c]);
    if (ph == 1) mma16816(d, vt[c][J], vt[c][J + 1], vt[c + 1][J], vt[c + 1][J + 1], pp[hd][c], po[hd][c]);
    if (ph == 2) mma1688(d, vt[c][J], vt[c][J + 1], pp[hd][c]);
    if (n == 3) {
      yield_slot();
      if (tq == 0 && lane == 0) mbar_arrive(sb + kBarResume + att * 8);
    }
  }
  yield_slot();
  TRACE_AT(tile, 11);
  UNITS stsm4_t(orow + c * 1024 + ((ochunk ^ (4 * hd)) << 4), pack2(o[hd][c][0][0], o[hd][c][0][1]),
                pack2(o[hd][c][0][2], o[hd][c][0][3]), pack2(o[hd][c][1][0], o[hd][c][1][1]),
                pack2(o[hd][c][1][2], o[hd][c][1][3]));
#undef UNITS
#undef AWAIT_HALO
#undef LOAD_HALO
  fence_async_smem();
  __syncwarp();
  if (tq == 1 && lane == 0) mbar_arrive(sb + kBarResume + att * 8);
  TRACE_AT(tile, 12);
  if (elect()) {
    bulk_store(g_o + (b * 16 + hp) * kTileBytes + w * 4096, stg, 4096);
    bulk_commit();
    bulk_wait();
    TRACE_AT(tile, 13);
    mbar_arrive(sb + kBarEpi + tile * 8);
  }
  __syncwarp();
}

__device__ __forceinline__ void gather_stats(uint8_t* sm, const uint2* stat, int r, unsigned epoch) {
  uint2 a[8];
#pragma unroll 1
  for (unsigned spins = 0;; spins++) {
    unsigned diff = 0;
#pragma unroll
    for (int i = 0; i < 8; i++) {
      a[i] = ld_relaxed2(stat + i * 128 + r);
      diff |= (a[i].x ^ epoch) | (a[i].y ^ epoch);
    }
    if (__all_sync(0xffffffffu, (diff & 7u) == 0)) break;
    if (spins > kSpinLimit) __trap();
  }
  float s = 0.f, q = 0.f;
#pragma unroll
  for (int i = 0; i < 8; i++) {
    s += untag_value(a[i].x);
    q += untag_value(a[i].y);
  }
  const float mean = s * (1.f / 1024.f);
  const float var = fmaxf(fmaf(-mean, mean, q * (1.f / 1024.f)), 0.f);
  reinterpret_cast<float2*>(sm + kSmStat)[r] = make_float2(rsqrtf(var + 1e-5f), -mean);
}

__device__ __forceinline__ void gather_colsums_qkv(uint8_t* sm, int tq, int j, int lane, unsigned epoch) {
  const uint2* src = reinterpret_cast<const uint2*>(g_cs + (j + 8 * tq) * 64) + lane;
  uint2 v[3], u[3];
  for (unsigned spins = 0;; spins++) {
    unsigned diff = 0;
#pragma unroll
    for (int q = 0; q < 3; q++) {
      v[q] = ld_relaxed2(src + q * (kD / 2));
      u[q] = make_uint2(epoch & 7u, epoch & 7u);
      if (tq) u[q] = ld_relaxed2(src + (q * kD + 3 * kD + kF) / 2);
    }
#pragma unroll
    for (int q = 0; q < 3; q++) diff |= (v[q].x ^ epoch) | (v[q].y ^ epoch) | (u[q].x ^ epoch) | (u[q].y ^ epoch);
    if (__all_sync(0xffffffffu, (diff & 7u) == 0)) break;
    if (spins > kSpinLimit) __trap();
  }
#pragma unroll
  for (int q = 0; q < 3; q++)
    reinterpret_cast<float2*>(sm + kSmCsQ)[tq * 96 + q * 32 + lane] =
        make_float2(untag_value(v[q].x) + untag_value(u[q].x), untag_value(v[q].y) + untag_value(u[q].y));
}

__device__ __forceinline__ void gather_colsums_w1(uint8_t* sm, const __nv_bfloat16* b1, int j, int lane,
                                                  unsigned epoch) {
#pragma unroll 1
  for (int blk = 0; blk < 7; blk++) {
    const int pair = 32 * (blk + (blk < 3 ? 3 * j : blk < 5 ? 21 + 2 * j : 35 + 2 * j)) + lane;
    const uint32_t bias = reinterpret_cast<const uint32_t*>(b1)[pair];
    uint2 v;
    for (unsigned spins = 0;; spins++) {
      v = ld_relaxed2(reinterpret_cast<const uint2*>(g_cs + 3 * kD) + pair);
      if (__all_sync(0xffffffffu, (((v.x ^ epoch) | (v.y ^ epoch)) & 7u) == 0)) break;
      if (spins > kSpinLimit) __trap();
    }
    reinterpret_cast<float4*>(sm + kSmV1)[blk * 32 + lane] =
        make_float4(untag_value(v.x), untag_value(v.y), kGeluBeta * bf_lo(bias), kGeluBeta * bf_hi(bias));
  }
}

#define FINE 3
#define LATE_REL2 1
#define STRIP_GATE kBarInit
#define XI_MASK 3
#define PUB_SPLIT 4
#define STAGE_YIELD 1
#define PAUSE_QKV2 7
#define PAUSE_WO 2

__global__ void __cluster_dims__(2, 1, 1) __launch_bounds__(384, 1)
fused_layers_kernel(const __grid_constant__ CUtensorMap map_x, const __grid_constant__ CUtensorMap map_out,
                    const __grid_constant__ CUtensorMap map_qkv, const __grid_constant__ CUtensorMap map_wo,
                    const __grid_constant__ CUtensorMap map_w1a, const __grid_constant__ CUtensorMap map_w1b,
                    const __grid_constant__ CUtensorMap map_w2, const __grid_constant__ CUtensorMap map_csq,
                    const __grid_constant__ CUtensorMap map_cs1, const __grid_constant__ CUtensorMap map_css,
                    const __grid_constant__ Params prm) {
  extern __shared__ __align__(1024) uint8_t sm[];
  if (threadIdx.x < 128 && blockIdx.x < kCtas) TRACE_AT(15, 1);
  const uint32_t sb = __shfl_sync(0xffffffffu, smem_u32(sm), 0);
  const int warp = __shfl_sync(0xffffffffu, threadIdx.x >> 5, 0), lane = threadIdx.x & 31;
  const int cta = blockIdx.x, rank = cta & 1, cl = cta >> 1;
  const int grp = cl < 4 ? 0 : cl < 36 ? (cl - 4) & 7 : 1 + (cl - 36) % 7;
  const int j = cl < 4 ? 4 + cl : cl < 36 ? (cl - 4) >> 3 : 4 + (cl - 36) / 7;
  const int b = 2 * grp + rank;
  const int xcol = (b >> 3) * kD, xrow = (b & 7) * 128;

  if (cta >= kCtas) {
    helper_cta(&map_csq, &map_cs1, sm, sb, cta - kCtas, warp);
    return;
  }
  if ((warp < 8 || warp == 9) && elect()) {
    if (warp == 9) {
#pragma unroll
      for (int s = 0; s < 8; s++) mbar_init(sb + kBarFull + s * 8, 1);
      fence_async_smem();
#pragma unroll 1
      for (int s = 0; s < 4; s++) {
        const uint32_t full = sb + kBarFull + s * 8, dst = sb + kSmRing + s * 40960;
        mbar_expect_tx(full, 40960);
        tma2d(dst, &map_x, full, xcol + (s & 1) * 64, xrow);
        tma3d(dst + kTileBytes, &map_qkv, full, (j + 4 * (s & 2)) * 64, (s & 1) * 64, 0);
        tma3d(dst + kTileBytes + 12288, &map_qkv, full, (j + 4 * (s & 2)) * 64, (s & 1) * 64 + 32, 0);
      }
    } else {
      if (sb & 1023) __trap();
#pragma unroll
      for (int s = 0; s < 16; s++) mbar_init(sb + kBarTurn + warp * 128 + s * 8, warp < 5 ? 1 : warp == 5 ? 2 : 4);
    }
    asm volatile("fence.mbarrier_init.release.cluster;" ::: "memory");
  }
  __syncwarp();
  asm volatile("barrier.cluster.arrive.relaxed.aligned;" ::: "memory");

  if (warp >= 8) {
    asm volatile("setmaxnreg.dec.sync.aligned.u32 40;");
    if (warp < 10) {
      asm volatile("barrier.cluster.wait.aligned;" ::: "memory");
      uint32_t nb = 32, off = 0, kb = 0;
#define RING_STEP(WAIT, ISSUE)                                            \
  do {                                                                    \
    const uint32_t mb = nb - depth, full = sb + kBarFull + (nb & 56);     \
    if (kb == skip) kb += inc;                                            \
    mbar_wait(sb + kBarEmpty + (mb & 56), mb >> 6);                       \
    WAIT;                                                                 \
    if (elect()) { ISSUE; }                                               \
    TRACE_ISSUE(9 - warp, nb);                                            \
    kb += inc;                                                            \
    off = off == wrap ? 0 : off + step;                                   \
    nb += 8;                                                              \
  } while (nb != nend)
#pragma unroll 1
      for (int sg = 0; sg < kSegs; sg++) {
        const uint32_t e = prm.seg[sg];
        const int ty = e & 7, mode = (e >> 15) & 3, reset = (e >> 24) & 3;
        const uint32_t nend = nb + (e & 0x1f8);
        const uint32_t step = (e >> 17) & 1 ? 40960 : 32768, wrap = 163840 - step;
        const uint32_t depth = (e >> 18) & 1 ? 40 : 32;
        if (reset) off = reset == 1 ? 0 : reset == 2 ? 40960 : 131072;
        const uint32_t own = ty == 2 ? 8 + j : 2 * j;
        if (mode != kModeContinue) kb = mode == kModeHead ? own : (e >> 9) & 63;
        const uint32_t inc = mode >= kModeSkip && ty != 2 ? 2 : 1, skip = mode >= kModeSkip ? own + (kb & 1) : 255;
        if (warp == 8) {
          const CUtensorMap* map = ty < 2 ? &map_qkv : ty == 2 ? &map_wo : ty == 3 ? &map_w1a : ty < 6 ? &map_w1b : &map_w2;
          const int c0 = ty < 2 ? (j + 8 * ty) * 64 : 0;
          const int c2 = ty < 2 ? 0 : ty == 3 ? 3 * j : ty == 4 ? 24 + 2 * j : ty == 5 ? 40 + 2 * j : 2 * j;
          const uint32_t half = (ty < 2 || ty == 3) ? 12288 : 8192;
          const uint32_t bytes = 2 * half + (mode == kModeHead ? 0 : kTileBytes);
          const uint32_t dst = sb + kSmRing + kTileBytes + rank * half;
#pragma unroll 1
          RING_STEP(, mbar_expect_tx(full, bytes); tma3d_mc(dst + off, map, full, c0, kb * 64 + rank * 32, c2));
        } else if (mode == kModeHead) {
          off += ((nend - nb) >> 3) * step;
          nb = nend;
          if (off >= 163840) off -= 163840;
        } else if (sg < 2) {
#pragma unroll 1
          RING_STEP(, tma2d(sb + kSmRing + off, &map_x, full, xcol + kb * 64, xrow));
        } else {
          const uint8_t* src = ty == 6 ? g_h + b * 56 * kTileBytes : (ty == 2 ? g_o : g_x) + b * 16 * kTileBytes;
          const int dep = (e >> 19) & 31;
          if (dep < 28) mbar_wait(sb + kBarReady + dep * 8, 0);
          if ((dep & 30) == 28) {
#pragma unroll 1
            RING_STEP(mbar_wait(sb + kBarSrc + ((kb << (4 - inc)) & 56), dep),
                      bulk_load(sb + kSmRing + off, src + kb * kTileBytes, kTileBytes, full));
          } else {
#pragma unroll 1
            RING_STEP(, bulk_load(sb + kSmRing + off, src + kb * kTileBytes, kTileBytes, full));
          }
        }
      }
#undef RING_STEP
    } else {
      unsigned epoch = 0;
      if (warp == 10) {
        if (lane == 0) epoch = atomicAdd(&g_ticket, 1u) / kGrid + 1;
        *reinterpret_cast<unsigned*>(sm + kSmEpoch) = __shfl_sync(0xffffffffu, epoch, 0);
        asm volatile("barrier.cluster.wait.aligned;" ::: "memory");
        if (elect()) mbar_arrive(sb + kBarEpoch);
      } else {
        asm volatile("barrier.cluster.wait.aligned;" ::: "memory");
        mbar_wait_bounded(sb + kBarFull, 0);
        if (elect()) {
          mbar_expect_tx(sb + kBarInit, 32768);
          tma2d(sb + kSmX, &map_x, sb + kBarInit, xcol + j * 128, xrow);
          tma2d(sb + kSmX + kTileBytes, &map_x, sb + kBarInit, xcol + j * 128 + 64, xrow);
        }
        const uint2 u = reinterpret_cast<const uint2*>(prm.b2)[32 * j + lane];
        reinterpret_cast<float4*>(sm + kSmB2)[lane] = make_float4(
            2.f * kGeluBeta * bf_lo(u.x), 2.f * kGeluBeta * bf_hi(u.x), 2.f * kGeluBeta * bf_lo(u.y), 2.f * kGeluBeta * bf_hi(u.y));
      }
      mbar_wait_bounded(sb + kBarEpoch, 0);
      epoch = *reinterpret_cast<volatile unsigned*>(sm + kSmEpoch);
      if (cta < 96) {
        mbar_wait_bounded(sb + STRIP_GATE, 0);
        colsum_strip(&map_css, sm, sb, (cta >> 5) * kD + 512 + (cta & 31) * 16, warp - 10, lane, epoch);
      }
      gather_colsums_qkv(sm, 11 - warp, j, lane, epoch);
      __syncwarp();
      if (elect()) mbar_arrive(sb + kBarCs + (11 - warp) * 8);
     if (warp == 10) {
#pragma unroll 1
      for (int i = 0; i < kTiles - 1; i++) {
        const bool xt = i == 2 || i == 6 || i == 9;
        const unsigned* line = g_flag + (i * 16 + b) * 32;
        mbar_wait(sb + (xt ? kBarX + (i >> 2) * 16 : kBarEpi + i * 8), 0);
        if ((xt && (FINE & 1)) || ((i == 1 || i == 8) && (FINE & 2))) {
          unsigned todo = 0xff, spins = 0;
          do {
            const unsigned now = __ballot_sync(0xffffffffu, ld_relaxed(line + (lane & 7)) == epoch) & todo;
            if (now) {
              asm volatile("fence.acquire.gpu;\nfence.proxy.async.global;" ::: "memory");
              if ((now >> lane) & 1) mbar_arrive(sb + kBarSrc + lane * 8);
              todo ^= now;
            }
            if (++spins > kSpinLimit) __trap();
          } while (todo);
        } else {
          wait_flags(line + (lane & 7), epoch);
          if (elect()) mbar_arrive(sb + kBarReady + i * 8);
        }
        if (xt) {
          wait_flags(line + 8 + (lane & 7), epoch);
          if (elect()) mbar_arrive(sb + kBarReady + (14 + (i >> 2)) * 8);
        }
      }
     } else {
#pragma unroll 1
      for (int i = 0; i < kTiles - 1; i++) {
        if (i == 3) {
          gather_colsums_w1(sm, prm.b1, j, lane, epoch);
          __syncwarp();
          if (elect()) mbar_arrive(sb + kBarCs + 16);
        }
        const bool xt = i == 2 || i == 6 || i == 9;
#pragma unroll 1
        for (int h = 0; h < (xt ? 2 : 1); h++) {
          mbar_wait_bounded(sb + (xt ? kBarX + (i >> 2) * 16 + 8 * h : kBarEpi + i * 8), 0);
          const int ty = i >= 7 ? i - 7 : i;
          if (ty >= 2 && elect()) {
            uint8_t* dst = xt ? g_x + (b * 16 + 2 * j + h) * kTileBytes
                              : g_h + (b * 56 + 1 + (ty == 3 ? 3 * j : 16 * ty - 40 + 2 * j)) * kTileBytes;
            const int piece = (xt && h == 0) ? kTileBytes : kTileBytes / PUB_SPLIT;
#pragma unroll 1
            for (int o = 0; o < kTileBytes; o += piece) {
              bulk_store(dst + o, sb + (xt ? kSmX + h * kTileBytes : kSmStg) + o, piece);
              bulk_commit();
              bulk_wait();
            }
            if (!xt) mbar_arrive(sb + kBarFree + i * 8);
          }
          if (LATE_REL2 && h == 1) mbar_wait_bounded(sb + kBarFull + 32, i == 2 ? 6 : i == 6 ? 19 : 25);
          __syncwarp();
          if (elect()) st_release(&g_flag[(i * 16 + b) * 32 + h * 8 + j], epoch);
          __syncwarp();
        }
      }
#pragma unroll 1
      for (int h = 0; h < 2; h++) {
        mbar_wait_bounded(sb + kBarX + 48 + 8 * h, 0);
        if (elect()) {
          tma2d_store(&map_out, sb + kSmX + h * kTileBytes, xcol + j * 128 + h * 64, xrow);
          bulk_commit();
          if (h == 1) bulk_wait_read();
        }
      }
     }
    }
    __syncwarp();
    asm volatile("barrier.cluster.arrive.relaxed.aligned;\nbarrier.cluster.wait.aligned;" ::: "memory");
  } else {
    asm volatile("setmaxnreg.inc.sync.aligned.u32 232;");
    asm volatile("barrier.cluster.wait.aligned;" ::: "memory");
    const int wg = warp >> 2, w = warp & 3;
    const bool rel = (threadIdx.x & 95) == 0;
    const uint32_t rel_addr = mapa(sb + kBarEmpty, w & 1);
    if (wg == 1) TRACE_AT(15, 0);
#define EPOCH (*reinterpret_cast<volatile unsigned*>(sm + kSmEpoch))

#pragma unroll 1
    for (int i = wg; i < kTiles; i += 2) {
      const int layer = i >= 7, ty = i - 7 * layer;
      TRACE_AT(i, 15);
      float acc[2][96];
      if (ty == 2 || ty == 6) {
        const int lane = lane_id();
        const uint32_t xa = sb + kSmX + ((lane >> 4) * 8 + (lane & 7)) * 128 + (((2 * w + ((lane >> 3) & 1)) ^ (lane & 7)) << 4);
        const float up = ty == 6 ? 2.f * kGeluBeta : 1.f, dn = ty == 6 ? 0.5f / kGeluBeta : 1.f;
#pragma unroll
        for (int h = 0; h < 2; h++) {
          const float* b2 = reinterpret_cast<const float*>(sm + kSmB2) + 64 * h + 16 * w + (lane >> 2);
          const float bias[2] = {ty == 6 ? b2[0] : 0.f, ty == 6 ? b2[8] : 0.f};
#pragma unroll
          for (int p = 0; p < 8; p++) {
            uint32_t r[4];
            ldsm4_t(xa + h * kTileBytes + p * 2048, r);
#pragma unroll
            for (int m = 0; m < 4; m++) {
              acc[h][8 * p + 2 * m] = fmaf(bf_lo(r[m]), up, bias[m & 1]);
              acc[h][8 * p + 2 * m + 1] = fmaf(bf_hi(r[m]), up, bias[m & 1]);
              asm volatile("" : "+f"(acc[h][8 * p + 2 * m]), "+f"(acc[h][8 * p + 2 * m + 1]));
              if ((m & XI_MASK) == XI_MASK) yield_slot();
            }
          }
        }
        auto stage = [&](int qt) {
          const int h = qt >> 1;
#pragma unroll
          for (int p = 4 * (qt & 1); p < 4 * (qt & 1) + 4; p++) {
            const float* a = &acc[h][8 * p];
            stsm4_t(xa + h * kTileBytes + p * 2048, pack2(a[0] * dn, a[1] * dn), pack2(a[2] * dn, a[3] * dn),
                    pack2(a[4] * dn, a[5] * dn), pack2(a[6] * dn, a[7] * dn));
            if (STAGE_YIELD || (p & 3) == 3) yield_slot();
          }
          if (qt & 1) {
            fence_async_smem();
            __syncwarp();
            if (elect()) mbar_arrive(sb + kBarX + (i >> 2) * 16 + 8 * h);
            TRACE_AT(i, 8 + h);
          }
        };
        mainloop<128, kResid>(acc, sb, i, layer * 152 + ty * 16, ty == 6 ? 4 : 0, ty == 6 ? 56 : 16,
                            ty == 2 ? PAUSE_WO : -1, 2 * layer + 1, rel_addr, rel, ty == 2 ? 8 : -1, stage);
        TRACE_AT(i, 2);
        stage(2);
        stage(3);
      } else {
        const int xver = 2 * layer + (ty >= 3);
        const uint32_t stg = sb + kSmStg + w * 4096;
        const float4* vec = reinterpret_cast<const float4*>(sm + kSmV1) + (ty == 3 ? 0 : 64 * ty - 160);
        int lane;
        uint8_t* hdst = g_h + (b * 56 + (ty == 3 ? 3 * j : 16 * ty - 40 + 2 * j)) * kTileBytes + w * 4096;
        float2 st[4];
        unsigned epoch;
        auto pre = [&] {
          lane = lane_id();
          if (ty < 4) mbar_wait(sb + (ty == 1 ? kBarEpi + (i - 1) * 8 : kBarStat + xver * 8), 0);
#pragma unroll
          for (int c = 0; c < 4; c++) st[c] = reinterpret_cast<const float2*>(sm + kSmStat)[32 * w + 8 * c + (lane >> 2)];
          epoch = EPOCH;
        };
        auto team_stats = [&] {
          uint2* stat = g_stat + (xver * 16 + b) * 1024;
          lane = lane_id();
          publish_stats(sb, stat + j * 128, w, lane, EPOCH);
          gather_stats(sm, stat, 32 * w + lane, EPOCH);
          __syncwarp();
          if (elect()) mbar_arrive(sb + kBarStat + xver * 8);
          TRACE_AT(i, 14);
        };
        if (ty < 4) {
          AttnRegs ar;
          auto odd = [&](int step) {
            if (step == 0) pre();
            else convert_odd(acc, st, ar, step, sm, sb + kBarHalo + (xver + ty) * 24,
                             g_halo + ((layer * 16 + b) * 16 + j + 8 * ty) * 256, (b & 7) != 7, epoch, w, lane);
          };
          head_blocks<192>(acc, sb, layer * 152 + (ty < 2 ? 2 * ty : 48), ty < 2 ? 2 * ty : 1, xver, rel_addr, rel);
          if (ty == 1) {
            if (i == 1) {
              mbar_wait(sb + kBarEpoch, 0);
              mbar_wait(sb + kBarInit, 0);
            }
            team_stats();
            epoch = 0;
#pragma unroll
            for (int c = 0; c < 4; c++) st[c] = reinterpret_cast<const float2*>(sm + kSmStat)[32 * w + 8 * c + (lane >> 2)];
          } else {
            mainloop<192, kPlain>(acc, sb, i, layer * 152 + (ty ? 52 : 4), ty ? 1 : 0, 14, -1, 0, rel_addr, rel, 0, pre);
            TRACE_AT(i, 2);
            if (ty == 3) goto wide_gelu;
          }
          if (layer == 0) mbar_wait(sb + kBarCs + ty * 8, 0);
          add_mean_term(acc, st, sm, ty, lane);
          if (ty == 1) {
            mainloop<192, kStagger>(acc, sb, i, layer * 152 + 18, 2, 14, PAUSE_QKV2, xver, rel_addr, rel, 0, odd);
            TRACE_AT(i, 2);
          } else {
            odd(1);
            odd(2);
            odd(3);
          }
          epilogue_attn(acc, st, ar, sm, sb, layer, ty, b, j, epoch, i, w, lane);
          TRACE_AT(i, 3);
          continue;
        wide_gelu:
          if (i == 3) mbar_wait(sb + kBarCs + 16, 0);
          scale_stats(st);
          fold_norm<16, 24>(acc, st, vec + (lane & 3));
          TRACE_AT(i, 11);
          gelu_chunk<2>(acc, stg, lane, nullptr, [] {});
          TRACE_AT(i, 12);
          fold_norm<0, 2>(acc, st, vec + (lane & 3));
          store_staged(hdst + 2 * kTileBytes, stg);
          fold_norm<2, 16>(acc, st, vec + (lane & 3));
        } else {
          if (ty == 4) {
            head_blocks<128>(acc, sb, layer * 152 + 50, 3, xver, rel_addr, rel);
            team_stats();
            mainloop<128, kPlain>(acc, sb, i, layer * 152 + 66, 4, 14, -1, 0, rel_addr, rel, 0, pre);
          } else {
            mainloop<128, kFresh>(acc, sb, i, layer * 152 + 80, 3, 16, -1, 0, rel_addr, rel, 0, pre);
          }
          TRACE_AT(i, 2);
          if (i == 4) mbar_wait(sb + kBarCs + 16, 0);
          scale_stats(st);
          fold_norm<0, 16>(acc, st, vec + (lane & 3));
        }
        auto own_store_done = [] {
          if (elect()) bulk_wait();
          __syncwarp();
        };
        TRACE_AT(i, 8);
        gelu_chunk<0>(acc, stg, lane, nullptr, [&] {
          if (ty == 3) own_store_done();
          else mbar_wait(sb + kBarFree + (i - 1) * 8, 0);
        });
        TRACE_AT(i, 9);
        gelu_chunk<1>(acc, stg, lane, hdst, own_store_done);
        TRACE_AT(i, 10);
        fence_async_smem();
        __syncwarp();
        if (elect()) mbar_arrive(sb + kBarEpi + i * 8);
      }
      TRACE_AT(i, 3);
    }
#undef EPOCH
    asm volatile("barrier.cluster.arrive.relaxed.aligned;\nbarrier.cluster.wait.aligned;" ::: "memory");
    if (wg == 1) TRACE_AT(15, 2);
  }
}

void build_segments(uint32_t* seg) {
  int n = 0, fine = 0;
  auto per_source = [&](int kind, int dep) { return (FINE & kind) ? 28 + (fine++ & 1) : dep; };
  auto add = [&](int ty, int cnt, int kb0, int mode, int wide, int depth5, int dep, int reset) {
    seg[n++] = ty | cnt << 3 | kb0 << 9 | mode << 15 | wide << 17 | depth5 << 18 | dep << 19 | reset << 24;
  };
  for (int l = 0; l < 2; l++) {
    const int t = 7 * l;
    if (l == 0) {
      add(0, 14, 2, kModePlain, 1, 0, 31, 1);
      add(1, 14, 2, kModePlain, 1, 0, 31, 0);
    } else {
      add(0, 2, 0, kModeHead, 1, 0, 31, 1);
      add(1, 2, 0, kModeHead, 1, 0, 31, 0);
      add(0, 7, 0, kModeSkip, 1, 0, per_source(1, 6), 0);
      add(0, 7, 1, kModeSkip, 1, 0, 15, 0);
      add(1, 7, 0, kModeSkip, 1, 0, 31, 0);
      add(1, 7, 1, kModeSkip, 1, 0, 31, 0);
    }
    add(2, 4, 0, kModePlain, 0, 0, t, 1);
    add(2, 4, 4, kModePlain, 0, 1, 31, 0);
    add(2, 1, 0, kModeHead, 0, 1, 31, 0);
    add(2, 7, 8, kModeSkip, 0, 1, per_source(2, t + 1), 0);
    add(3, 2, 0, kModeHead, 1, 0, 31, 2);
    add(4, 2, 0, kModeHead, 1, 0, 31, 0);
    add(3, 7, 0, kModeSkip, 1, 0, per_source(1, t + 2), 0);
    add(3, 7, 1, kModeSkip, 1, 0, 14 + 2 * l, 0);
    add(4, 4, 0, kModeSkip, 0, 0, 31, 3);
    add(4, 3, 0, kModeContinue, 0, 1, 31, 0);
    add(4, 7, 1, kModeSkip, 0, 1, 31, 0);
    add(5, 16, 0, kModePlain, 0, 1, 31, 0);
    add(6, 24, 0, kModePlain, 0, 1, t + 3, 0);
    add(6, 16, 24, kModePlain, 0, 1, t + 4, 0);
    add(6, 16, 40, kModePlain, 0, 1, t + 5, 0);
  }
}

typedef CUresult (*EncodeTiledFn)(CUtensorMap*, CUtensorMapDataType, cuuint32_t, void*, const cuuint64_t*,
                                  const cuuint64_t*, const cuuint32_t*, const cuuint32_t*, CUtensorMapInterleave,
                                  CUtensorMapSwizzle, CUtensorMapL2promotion, CUtensorMapFloatOOBfill);

CUtensorMap make_map(EncodeTiledFn enc, const void* p, int rank, const cuuint64_t* dims, const cuuint64_t* strides,
                     const cuuint32_t* box, CUtensorMapSwizzle swizzle = CU_TENSOR_MAP_SWIZZLE_128B,
                     CUtensorMapL2promotion promo = CU_TENSOR_MAP_L2_PROMOTION_L2_128B) {
  CUtensorMap m;
  const cuuint32_t es[5] = {1, 1, 1, 1, 1};
  enc(&m, CU_TENSOR_MAP_DATA_TYPE_BFLOAT16, rank, const_cast<void*>(p), dims, strides, box, es,
      CU_TENSOR_MAP_INTERLEAVE_NONE, swizzle, promo,
      CU_TENSOR_MAP_FLOAT_OOB_FILL_NONE);
  return m;
}

CUtensorMap weight_map(EncodeTiledFn enc, const void* p, int k, int n, int blocks) {
  const cuuint64_t dims[3] = {64, (cuuint64_t)k, (cuuint64_t)n / 64};
  const cuuint64_t strides[2] = {(cuuint64_t)n * 2, 128};
  const cuuint32_t box[3] = {64, 32, (cuuint32_t)blocks};
  return make_map(enc, p, 3, dims, strides, box, CU_TENSOR_MAP_SWIZZLE_128B, CU_TENSOR_MAP_L2_PROMOTION_L2_256B);
}

CUtensorMap slab_map(EncodeTiledFn enc, const void* p, int n, int cols, int rows) {
  const cuuint64_t dims[2] = {(cuuint64_t)n, kD};
  const cuuint64_t strides[1] = {(cuuint64_t)n * 2};
  const cuuint32_t box[2] = {(cuuint32_t)cols, (cuuint32_t)rows};
  return make_map(enc, p, 2, dims, strides, box, CU_TENSOR_MAP_SWIZZLE_NONE);
}

CUtensorMap token_map(EncodeTiledFn enc, const void* p, int rows) {
  const cuuint64_t dims[2] = {2 * kD, 1024};
  const cuuint64_t strides[1] = {4 * kD};
  const cuuint32_t box[2] = {64, (cuuint32_t)rows};
  return make_map(enc, p, 2, dims, strides, box);
}

}

extern "C" void kernel_launch(void* const* d_in, const int* in_sizes, int n_in, void* d_out, int out_size) {
  (void)in_sizes; (void)n_in; (void)out_size;
  static EncodeTiledFn enc = nullptr;
  if (!enc) {
    void* fn = nullptr;
    cudaDriverEntryPointQueryResult q;
    cudaGetDriverEntryPoint("cuTensorMapEncodeTiled", &fn, cudaEnableDefault, &q);
    enc = (EncodeTiledFn)fn;
    cudaFuncSetAttribute(fused_layers_kernel, cudaFuncAttributeMaxDynamicSharedMemorySize, kSmBytes);
  }
  Params prm;
  prm.b1 = (const __nv_bfloat16*)d_in[5];
  prm.b2 = (const __nv_bfloat16*)d_in[7];
  build_segments(prm.seg);
  const cuuint64_t qd[3] = {kD, kD, 3}, qs[2] = {3 * kD * 2, kD * 2};
  const cuuint32_t qb[3] = {64, 32, 3};
  const CUtensorMap map_x = token_map(enc, d_in[0], 128);
  const CUtensorMap map_out = token_map(enc, d_out, 128);
  const CUtensorMap map_qkv = make_map(enc, d_in[1], 3, qd, qs, qb);
  const CUtensorMap map_wo = weight_map(enc, d_in[2], kD, kD, 2);
  const CUtensorMap map_w1a = weight_map(enc, d_in[4], kD, kF, 3);
  const CUtensorMap map_w1b = weight_map(enc, d_in[4], kD, kF, 2);
  const CUtensorMap map_w2 = weight_map(enc, d_in[6], kF, kD, 2);
  fused_layers_kernel<<<kGrid, 384, kSmBytes>>>(map_x, map_out, map_qkv, map_wo, map_w1a, map_w1b, map_w2,
                                                slab_map(enc, d_in[1], 3 * kD, 128, 128), slab_map(enc, d_in[4], kF, 128, 128),
                                                slab_map(enc, d_in[1], 3 * kD, 16, 128), prm);
}
```

```cpp
#include <cuda.h>
#include <cuda_bf16.h>
#include <cuda_runtime.h>
#include <stdint.h>

namespace {

constexpr int kD = 1024;
constexpr int kF = 3584;
constexpr int kCtas = 128;
constexpr int kGrid = 132;
constexpr int kTiles = 14;
constexpr int kTileBytes = 16384;

constexpr int kSmRing = 0;
constexpr int kSmX = 163840;
constexpr int kSmStg = kSmX + 32768;
constexpr int kSmHalo = kSmStg + 16384;
constexpr int kSmCsQ = kSmHalo + 6144;
constexpr int kSmV1 = kSmCsQ + 384 * 4;
constexpr int kSmB2 = kSmV1 + 448 * 8;
constexpr int kSmStat = kSmB2 + 128 * 4;
constexpr int kSmBar = kSmStat + 128 * 8;
constexpr int kBarFull = kSmBar;
constexpr int kBarTurn = kBarFull + 8 * 8;
constexpr int kBarReady = kBarTurn + 14 * 8;
constexpr int kBarSrc = kBarReady + 17 * 8;
constexpr int kBarPause = kBarSrc + 8 * 8;
constexpr int kBarFree = kBarPause + 4 * 8;
constexpr int kBarCs = kBarFree + 14 * 8;
constexpr int kBarSlab = kBarCs + 3 * 8;
constexpr int kBarHalo = kBarSlab + 4 * 8;
constexpr int kBarInit = kBarHalo + 12 * 8;
constexpr int kBarEpoch = kBarInit + 8;
constexpr int kBarEmpty = kBarTurn + 5 * 128;
constexpr int kBarEpi = kBarEmpty + 128;
constexpr int kBarX = kBarEpi + 14 * 8;
constexpr int kBarStat = kBarX + 8 * 8;
constexpr int kBarResume = kBarStat + 4 * 8;
constexpr int kSmEpoch = kBarEpi + 2 * 128;
static_assert(kBarEpoch < kBarEmpty && kBarResume + 4 * 8 <= kSmEpoch, "barrier groups overflow");
constexpr int kSmBytes = kSmEpoch + 16 + 256;
constexpr int kSegs = 38;

constexpr int kFlagLines = kTiles * 16;

constexpr unsigned kSpinLimit = 1u << 22;

__device__ __align__(1024) uint8_t g_x[16 * 16 * kTileBytes];
__device__ __align__(1024) uint8_t g_o[16 * 16 * kTileBytes];
__device__ __align__(1024) uint8_t g_h[16 * 56 * kTileBytes];
__device__ __align__(128) uint2 g_stat[4 * 16 * 128 * 8];
__device__ __align__(128) unsigned g_cs[3 * kD + kF + 3 * kD];
__device__ __align__(128) uint4 g_halo[2 * 16 * 16 * 256];
__device__ __align__(128) unsigned g_flag[kFlagLines * 32];
__device__ unsigned g_ticket;

#define TRACE_AT(tile, k)
#define TRACE_PUB(i, k, c)
#define TRACE_ISSUE(which, nb)

struct Params {
  const __nv_bfloat16* b1;
  const __nv_bfloat16* b2;
  uint32_t seg[kSegs];
};

__device__ __forceinline__ uint32_t smem_u32(const void* p) {
  return (uint32_t)__cvta_generic_to_shared(p);
}
__device__ __forceinline__ uint32_t mapa(uint32_t a, uint32_t cta) {
  uint32_t r;
  asm("mapa.shared::cluster.u32 %0, %1, %2;" : "=r"(r) : "r"(a), "r"(cta));
  return r;
}
__device__ __forceinline__ void mbar_init(uint32_t bar, int cnt) {
  asm volatile("mbarrier.init.shared::cta.b64 [%0], %1;" ::"r"(bar), "r"(cnt) : "memory");
}
__device__ __forceinline__ void mbar_expect_tx(uint32_t bar, uint32_t bytes) {
  asm volatile("mbarrier.arrive.expect_tx.shared::cta.b64 _, [%0], %1;" ::"r"(bar), "r"(bytes) : "memory");
}
__device__ __forceinline__ void mbar_arrive(uint32_t bar) {
  asm volatile("mbarrier.arrive.shared::cta.b64 _, [%0];" ::"r"(bar) : "memory");
}
__device__ __forceinline__ void mbar_arrive_cluster(uint32_t cluster_addr) {
  asm volatile("mbarrier.arrive.shared::cluster.b64 _, [%0];" ::"r"(cluster_addr) : "memory");
}
__device__ __forceinline__ void mbar_wait(uint32_t bar, uint32_t parity) {
  asm volatile("{\n.reg .pred p;\nRETRY:\nmbarrier.try_wait.parity.shared::cta.b64 p, [%0], %1;\n"
               "@!p bra.uni RETRY;\n}" ::"r"(bar), "r"(parity) : "memory");
}
__device__ __forceinline__ void mbar_wait_bounded(uint32_t bar, uint32_t parity) {
  asm volatile("{\n.reg .pred p;\n.reg .u32 c;\nmov.u32 c, 0;\nRETRY:\n"
               "mbarrier.try_wait.parity.shared::cta.b64 p, [%0], %1;\n@p bra.uni DONE;\n"
               "add.u32 c, c, 1;\nsetp.lt.u32 p, c, %2;\n@p bra.uni RETRY;\ntrap;\nDONE:\n}"
               ::"r"(bar), "r"(parity), "n"(1u << 19) : "memory");
}
__device__ __forceinline__ void tma3d(uint32_t dst, const CUtensorMap* m, uint32_t bar, int c0, int c1, int c2) {
  asm volatile(
      "cp.async.bulk.tensor.3d.shared::cluster.global.mbarrier::complete_tx::bytes [%0], [%1, {%3, %4, %5}], [%2];"
      ::"r"(dst), "l"(m), "r"(bar), "r"(c0), "r"(c1), "r"(c2) : "memory");
}
__device__ __forceinline__ void tma3d_mc(uint32_t dst, const CUtensorMap* m, uint32_t bar, int c0, int c1, int c2) {
  asm volatile(
      "cp.async.bulk.tensor.3d.shared::cluster.global.mbarrier::complete_tx::bytes.multicast::cluster"
      " [%0], [%1, {%3, %4, %5}], [%2], %6;"
      ::"r"(dst), "l"(m), "r"(bar), "r"(c0), "r"(c1), "r"(c2), "h"((uint16_t)3) : "memory");
}
__device__ __forceinline__ void tma2d(uint32_t dst, const CUtensorMap* m, uint32_t bar, int c0, int c1) {
  asm volatile(
      "cp.async.bulk.tensor.2d.shared::cluster.global.mbarrier::complete_tx::bytes [%0], [%1, {%3, %4}], [%2];"
      ::"r"(dst), "l"(m), "r"(bar), "r"(c0), "r"(c1) : "memory");
}
__device__ __forceinline__ void tma2d_store(const CUtensorMap* m, uint32_t src, int c0, int c1) {
  asm volatile("cp.async.bulk.tensor.2d.global.shared::cta.bulk_group [%0, {%2, %3}], [%1];"
               ::"l"(m), "r"(src), "r"(c0), "r"(c1) : "memory");
}
__device__ __forceinline__ int lane_id() {
  int l;
  asm volatile("mov.u32 %0, %%laneid;" : "=r"(l));
  return l;
}
__device__ __forceinline__ bool elect() {
  uint32_t p;
  asm volatile("{\n.reg .pred p;\nelect.sync _|p, 0xffffffff;\nselp.b32 %0, 1, 0, p;\n}" : "=r"(p));
  return p;
}
__device__ __forceinline__ void bulk_load(uint32_t dst, const void* src, uint32_t bytes, uint32_t bar) {
  asm volatile("cp.async.bulk.shared::cluster.global.mbarrier::complete_tx::bytes [%0], [%1], %2, [%3];"
               ::"r"(dst), "l"(src), "r"(bytes), "r"(bar) : "memory");
}
__device__ __forceinline__ void bulk_store(void* dst, uint32_t src, uint32_t bytes) {
  asm volatile("cp.async.bulk.global.shared::cta.bulk_group [%0], [%1], %2;" ::"l"(dst), "r"(src), "r"(bytes)
               : "memory");
}
__device__ __forceinline__ void bulk_commit() { asm volatile("cp.async.bulk.commit_group;" ::: "memory"); }
__device__ __forceinline__ void bulk_wait_read() { asm volatile("cp.async.bulk.wait_group.read 0;" ::: "memory"); }
__device__ __forceinline__ void bulk_wait() { asm volatile("cp.async.bulk.wait_group 0;" ::: "memory"); }
__device__ __forceinline__ void fence_async_smem() { asm volatile("fence.proxy.async.shared::cta;" ::: "memory"); }
__device__ __forceinline__ unsigned ld_relaxed(const unsigned* p) {
  unsigned v;
  asm volatile("ld.relaxed.gpu.global.u32 %0, [%1];" : "=r"(v) : "l"(p) : "memory");
  return v;
}
__device__ __forceinline__ uint2 ld_relaxed2(const uint2* p) {
  uint2 v;
  asm volatile("ld.relaxed.gpu.global.v2.u32 {%0, %1}, [%2];" : "=r"(v.x), "=r"(v.y) : "l"(p) : "memory");
  return v;
}
__device__ __forceinline__ void st_relaxed(unsigned* p, unsigned v) {
  asm volatile("st.relaxed.gpu.global.u32 [%0], %1;" ::"l"(p), "r"(v) : "memory");
}
__device__ __forceinline__ void st_release(unsigned* p, unsigned v) {
  asm volatile("st.release.gpu.global.u32 [%0], %1;" ::"l"(p), "r"(v) : "memory");
}
__device__ __forceinline__ void wait_flags(const unsigned* p, unsigned epoch) {
  unsigned spins = 0;
  while (true) {
    const unsigned v = ld_relaxed(p);
    if (__all_sync(0xffffffffu, v == epoch)) break;
    if (++spins > kSpinLimit) __trap();
  }
  asm volatile("fence.acquire.gpu;\nfence.proxy.async.global;" ::: "memory");
  __syncwarp();
}
__device__ __forceinline__ void st_packet(uint4* p, uint32_t d0, uint32_t d1, uint32_t tag) {
  asm volatile("{\n.reg .b128 v;\n.reg .b64 x, y;\nmov.b64 x, {%1, %2};\nmov.b64 y, {%3, %3};\nmov.b128 v, {x, y};\n"
               "st.relaxed.gpu.global.b128 [%0], v;\n}" ::"l"(p), "r"(d0), "r"(d1), "r"(tag) : "memory");
}
__device__ __forceinline__ void ld_packet(const uint4* p, uint32_t& d0, uint32_t& d1, uint32_t& tag) {
  asm volatile("{\n.reg .b128 v;\n.reg .b64 x, y;\n.reg .b32 u;\nld.relaxed.gpu.global.b128 v, [%3];\n"
               "mov.b128 {x, y}, v;\nmov.b64 {%0, %1}, x;\nmov.b64 {%2, u}, y;\n}"
               : "=r"(d0), "=r"(d1), "=r"(tag) : "l"(p) : "memory");
}
__device__ __forceinline__ unsigned tag_value(float v, unsigned epoch) {
  return (__float_as_uint(v) & ~7u) | (epoch & 7u);
}
__device__ __forceinline__ float untag_value(unsigned v) { return __uint_as_float(v & ~7u); }
__device__ __forceinline__ void stsm4(uint32_t a, uint32_t r0, uint32_t r1, uint32_t r2, uint32_t r3) {
  asm volatile("stmatrix.sync.aligned.m8n8.x4.shared.b16 [%0], {%1, %2, %3, %4};" ::"r"(a), "r"(r0), "r"(r1),
               "r"(r2), "r"(r3) : "memory");
}
__device__ __forceinline__ void stsm4_t(uint32_t a, uint32_t r0, uint32_t r1, uint32_t r2, uint32_t r3) {
  asm volatile("stmatrix.sync.aligned.m8n8.x4.trans.shared.b16 [%0], {%1, %2, %3, %4};" ::"r"(a), "r"(r0),
               "r"(r1), "r"(r2), "r"(r3) : "memory");
}
__device__ __forceinline__ uint32_t transpose8(uint32_t a) {
  uint32_t d;
  asm volatile("movmatrix.sync.aligned.m8n8.trans.b16 %0, %1;" : "=r"(d) : "r"(a));
  return d;
}
__device__ __forceinline__ void mma16816(float (&c)[4], uint32_t a0, uint32_t a1, uint32_t a2, uint32_t a3,
                                         uint32_t b0, uint32_t b1) {
  asm volatile("mma.sync.aligned.m16n8k16.row.col.f32.bf16.bf16.f32 {%0, %1, %2, %3}, {%4, %5, %6, %7}, {%8, %9}, "
               "{%0, %1, %2, %3};"
               : "+f"(c[0]), "+f"(c[1]), "+f"(c[2]), "+f"(c[3])
               : "r"(a0), "r"(a1), "r"(a2), "r"(a3), "r"(b0), "r"(b1));
}
__device__ __forceinline__ void mma1688(float (&c)[4], uint32_t a0, uint32_t a1, uint32_t b0) {
  asm volatile("mma.sync.aligned.m16n8k8.row.col.f32.bf16.bf16.f32 {%0, %1, %2, %3}, {%4, %5}, {%6}, {%0, %1, %2, %3};"
               : "+f"(c[0]), "+f"(c[1]), "+f"(c[2]), "+f"(c[3]) : "r"(a0), "r"(a1), "r"(b0));
}
__device__ __forceinline__ float shfl_xor(float v, int m) {
  float r;
  asm volatile("shfl.sync.bfly.b32 %0, %1, %2, 31, 0xffffffff;" : "=f"(r) : "f"(v), "r"(m));
  return r;
}
__device__ __forceinline__ float tanh_fast(float x) {
  float r;
  asm volatile("tanh.approx.f32 %0, %1;" : "=f"(r) : "f"(x));
  return r;
}
__device__ __forceinline__ void ldsm4(uint32_t a, uint32_t (&r)[4]) {
  asm volatile("ldmatrix.sync.aligned.m8n8.x4.shared.b16 {%0, %1, %2, %3}, [%4];"
               : "=r"(r[0]), "=r"(r[1]), "=r"(r[2]), "=r"(r[3]) : "r"(a) : "memory");
}
__device__ __forceinline__ void ldsm4_t(uint32_t a, uint32_t (&r)[4]) {
  asm volatile("ldmatrix.sync.aligned.m8n8.x4.trans.shared.b16 {%0, %1, %2, %3}, [%4];"
               : "=r"(r[0]), "=r"(r[1]), "=r"(r[2]), "=r"(r[3]) : "r"(a) : "memory");
}
__device__ __forceinline__ uint32_t pack2(float lo, float hi) {
  uint32_t r;
  asm volatile("cvt.rn.bf16x2.f32 %0, %1, %2;" : "=r"(r) : "f"(hi), "f"(lo));
  return r;
}
__device__ __forceinline__ float bf_lo(uint32_t r) { return __uint_as_float(r << 16); }
__device__ __forceinline__ float bf_hi(uint32_t r) { return __uint_as_float(r & 0xffff0000u); }
__device__ __forceinline__ float ex2(float x) {
  float r;
  asm("ex2.approx.ftz.f32 %0, %1;" : "=f"(r) : "f"(x));
  return r;
}
__device__ __forceinline__ float rcp(float x) {
  float r;
  asm("rcp.approx.ftz.f32 %0, %1;" : "=f"(r) : "f"(x));
  return r;
}
template <int N>
__device__ __forceinline__ void wg_wait() {
  asm volatile("wgmma.wait_group.sync.aligned %0;" ::"n"(N) : "memory");
}
__device__ __forceinline__ void yield_slot() { asm volatile("pmevent 0;"); }

template <int N, int KIND>
__device__ __forceinline__ void mma_kblock(float (&acc)[2][96], uint32_t a, uint32_t b);

#define F8(m, d, i) m(d[i]), m(d[i + 1]), m(d[i + 2]), m(d[i + 3]), m(d[i + 4]), m(d[i + 5]), m(d[i + 6]), m(d[i + 7])
#define KSTEP(N, A, B, oa0, oa1, ob, sd)                                                   \
  "mov.b64 db, {" B ", hb};\nadd.u64 db, db, " #ob ";\n"                                    \
  "mov.b64 da, {" A ", ha};\nadd.u64 da, da, " #oa0 ";\n"                                   \
  "wgmma.mma_async.sync.aligned.m64n" #N "k16.f32.bf16.bf16 {" ACC##N##_0 "}, da, db, " #sd ", 1, 1, 0, 1;\n" \
  "mov.b64 da, {" A ", ha};\nadd.u64 da, da, " #oa1 ";\n"                                   \
  "wgmma.mma_async.sync.aligned.m64n" #N "k16.f32.bf16.bf16 {" ACC##N##_1 "}, da, db, " #sd ", 1, 1, 0, 1;\n"

#define MMA_KBLOCK(N, KIND, A, B, ob2, ob3, sd, MID, MODE)                                 \
  template <>                                                                              \
  __device__ __forceinline__ void mma_kblock<N, KIND>(float (&acc)[2][96], uint32_t a, uint32_t b) { \
    asm volatile("{\n.reg .b32 ha, hb;\n.reg .b64 da, db;\n"                            \
                 "mov.b32 ha, 0x40000080;\nmov.b32 hb, 0x40000040;\n"                       \
                 "wgmma.fence.sync.aligned;\n"                                             \
                 KSTEP(N, A, B, 0, 64, 0, sd) KSTEP(N, A, B, 2, 66, 128, 1) MID               \
                 KSTEP(N, A, B, 4, 68, ob2, 1) KSTEP(N, A, B, 6, 70, ob3, 1) "wgmma.commit_group.sync.aligned;\n}\n"  \
                 : OPS##N(MODE) : "r"(a), "r"(b) : "memory");                              \
  }
#define MMA_KBLOCKS(N, A, B, ob2, ob3)                                                     \
  MMA_KBLOCK(N, 0, A, B, ob2, ob3, 1, "", "+f")                                            \
  MMA_KBLOCK(N, 1, A, B, ob2, ob3, 1, "wgmma.commit_group.sync.aligned;\n", "+f")          \
  MMA_KBLOCK(N, 2, A, B, ob2, ob3, 0, "", "=f")

#define ACC128_0 \
  "%0, %1, %2, %3, %4, %5, %6, %7, %8, %9, %10, %11, %12, %13, %14, %15, " \
  "%16, %17, %18, %19, %20, %21, %22, %23, %24, %25, %26, %27, %28, %29, %30, %31, " \
  "%32, %33, %34, %35, %36, %37, %38, %39, %40, %41, %42, %43, %44, %45, %46, %47, " \
  "%48, %49, %50, %51, %52, %53, %54, %55, %56, %57, %58, %59, %60, %61, %62, %63"
#define ACC128_1 \
  "%64, %65, %66, %67, %68, %69, %70, %71, %72, %73, %74, %75, %76, %77, %78, %79, " \
  "%80, %81, %82, %83, %84, %85, %86, %87, %88, %89, %90, %91, %92, %93, %94, %95, " \
  "%96, %97, %98, %99, %100, %101, %102, %103, %104, %105, %106, %107, %108, %109, %110, %111, " \
  "%112, %113, %114, %115, %116, %117, %118, %119, %120, %121, %122, %123, %124, %125, %126, %127"
#define OPS128(m) \
  F8(m, acc[0], 0), F8(m, acc[0], 8), F8(m, acc[0], 16), F8(m, acc[0], 24), F8(m, acc[0], 32), F8(m, acc[0], 40), F8(m, acc[0], 48), F8(m, acc[0], 56), \
        F8(m, acc[1], 0), F8(m, acc[1], 8), F8(m, acc[1], 16), F8(m, acc[1], 24), F8(m, acc[1], 32), F8(m, acc[1], 40), F8(m, acc[1], 48), F8(m, acc[1], 56)
MMA_KBLOCKS(128, "%128", "%129", 512, 640)

#define ACC192_0 \
  "%0, %1, %2, %3, %4, %5, %6, %7, %8, %9, %10, %11, %12, %13, %14, %15, " \
  "%16, %17, %18, %19, %20, %21, %22, %23, %24, %25, %26, %27, %28, %29, %30, %31, " \
  "%32, %33, %34, %35, %36, %37, %38, %39, %40, %41, %42, %43, %44, %45, %46, %47, " \
  "%48, %49, %50, %51, %52, %53, %54, %55, %56, %57, %58, %59, %60, %61, %62, %63, " \
  "%64, %65, %66, %67, %68, %69, %70, %71, %72, %73, %74, %75, %76, %77, %78, %79, " \
  "%80, %81, %82, %83, %84, %85, %86, %87, %88, %89, %90, %91, %92, %93, %94, %95"
#define ACC192_1 \
  "%96, %97, %98, %99, %100, %101, %102, %103, %104, %105, %106, %107, %108, %109, %110, %111, " \
  "%112, %113, %114, %115, %116, %117, %118, %119, %120, %121, %122, %123, %124, %125, %126, %127, " \
  "%128, %129, %130, %131, %132, %133, %134, %135, %136, %137, %138, %139, %140, %141, %142, %143, " \
  "%144, %145, %146, %147, %148, %149, %150, %151, %152, %153, %154, %155, %156, %157, %158, %159, " \
  "%160, %161, %162, %163, %164, %165, %166, %167, %168, %169, %170, %171, %172, %173, %174, %175, " \
  "%176, %177, %178, %179, %180, %181, %182, %183, %184, %185, %186, %187, %188, %189, %190, %191"
#define OPS192(m) \
  F8(m, acc[0], 0), F8(m, acc[0], 8), F8(m, acc[0], 16), F8(m, acc[0], 24), F8(m, acc[0], 32), F8(m, acc[0], 40), F8(m, acc[0], 48), F8(m, acc[0], 56), F8(m, acc[0], 64), F8(m, acc[0], 72), F8(m, acc[0], 80), F8(m, acc[0], 88), \
        F8(m, acc[1], 0), F8(m, acc[1], 8), F8(m, acc[1], 16), F8(m, acc[1], 24), F8(m, acc[1], 32), F8(m, acc[1], 40), F8(m, acc[1], 48), F8(m, acc[1], 56), F8(m, acc[1], 64), F8(m, acc[1], 72), F8(m, acc[1], 80), F8(m, acc[1], 88)
MMA_KBLOCKS(192, "%192", "%193", 768, 896)

#define HSTEP(oa, ob)                                                                       \
  "mov.b64 db, {%97, hb};\nadd.u64 db, db, " #ob ";\nmov.b64 da, {%96, ha};\nadd.u64 da, da, " #oa ";\n" \
  "wgmma.mma_async.sync.aligned.m64n192k16.f32.bf16.bf16 {" ACC192_0 "}, da, db, 1, 1, 1, 0, 1;\n"
__device__ __forceinline__ void mma_half(float (&d)[96], uint32_t a, uint32_t b) {
  asm volatile("{\n.reg .b32 ha, hb;\n.reg .b64 da, db;\nmov.b32 ha, 0x40000080;\nmov.b32 hb, 0x40000040;\n"
               "wgmma.fence.sync.aligned;\n" HSTEP(0, 0) HSTEP(2, 128) HSTEP(4, 768) HSTEP(6, 896)
               "wgmma.commit_group.sync.aligned;\n}\n"
               : F8("+f", d, 0), F8("+f", d, 8), F8("+f", d, 16), F8("+f", d, 24), F8("+f", d, 32), F8("+f", d, 40),
                 F8("+f", d, 48), F8("+f", d, 56), F8("+f", d, 64), F8("+f", d, 72), F8("+f", d, 80), F8("+f", d, 88)
               : "r"(a), "r"(b) : "memory");
}

#define TSTEP(REGS, W, X, ow, ox)                                                           \
  "mov.b64 db, {" X ", hi};\nadd.u64 db, db, " #ox ";\nmov.b64 da, {" W ", hi};\nadd.u64 da, da, " #ow ";\n" \
  "wgmma.mma_async.sync.aligned.m64n128k16.f32.bf16.bf16 {" REGS "}, da, db, 1, 1, 1, 1, 0;\n"
#define THEAD "{\n.reg .b32 hi;\n.reg .b64 da, db;\nmov.b32 hi, 0x40000040;\nwgmma.fence.sync.aligned;\n"
#define TTAIL "wgmma.commit_group.sync.aligned;\n}\n"
__device__ __forceinline__ void mma_kblock_t(float (&acc)[2][96], uint32_t wd, uint32_t xd) {
  asm volatile(THEAD TSTEP(ACC128_0, "%128", "%129", 0, 0) TSTEP(ACC128_1, "%128", "%129", 256, 0)
               TSTEP(ACC128_0, "%128", "%129", 128, 2) TSTEP(ACC128_1, "%128", "%129", 384, 2)
               TSTEP(ACC128_0, "%128", "%129", 512, 4) TSTEP(ACC128_1, "%128", "%129", 768, 4)
               TSTEP(ACC128_0, "%128", "%129", 640, 6) TSTEP(ACC128_1, "%128", "%129", 896, 6) TTAIL
               : OPS128("+f") : "r"(wd), "r"(xd) : "memory");
}
__device__ __forceinline__ void mma_half_t(float (&d)[96], uint32_t wd, uint32_t xd) {
  asm volatile(THEAD TSTEP(ACC128_0, "%64", "%65", 0, 0) TSTEP(ACC128_0, "%64", "%65", 128, 2)
               TSTEP(ACC128_0, "%64", "%65", 512, 4) TSTEP(ACC128_0, "%64", "%65", 640, 6) TTAIL
               : F8("+f", d, 0), F8("+f", d, 8), F8("+f", d, 16), F8("+f", d, 24), F8("+f", d, 32), F8("+f", d, 40),
                 F8("+f", d, 48), F8("+f", d, 56) : "r"(wd), "r"(xd) : "memory");
}

enum { kModePlain = 0, kModeHead = 1, kModeSkip = 2, kModeContinue = 3 };

template <int N>
__device__ __forceinline__ void fence_acc(float (&acc)[2][96]) {
#pragma unroll
  for (int h = 0; h < 2; h++)
#pragma unroll
    for (int i = 0; i < N / 2; i++) asm volatile("" : "+f"(acc[h][i])::"memory");
}

constexpr uint32_t kToB = (kTileBytes >> 4) + ((4096u >> 4) << 16) - (1u << 16);

#define TRACE_KB(nb)

template <int N>
__device__ __forceinline__ void head_blocks(float (&acc)[2][96], uint32_t sb, int n0, int slot, int xver,
                                            uint32_t rel_addr, bool rel) {
  const uint32_t ring = (((sb & 0x3FFFF) + kSmRing) >> 4) | (1u << 16);
  const uint32_t xdesc = (((sb & 0x3FFFF) + kSmX) >> 4) | (1u << 16);
  const uint32_t s0 = ring + slot * 2560, s1 = ring + ((slot + 1) & 3) * 2560;
  const uint32_t nb = n0 * 8, xbar = sb + kBarX + (xver - 1) * 16;
  if (xver > 0) mbar_wait(xbar, 0);
  mbar_wait(sb + kBarFull + (nb & 56), nb >> 6);
  if (n0 == 0) TRACE_AT(0, 1);
  TRACE_KB(nb);
  mma_kblock<N, 2>(acc, xver > 0 ? xdesc : s0, s0 + kToB);
  if (xver > 0) mbar_wait(xbar + 8, 0);
  mbar_wait(sb + kBarFull + (nb & 56) + 8, nb >> 6);
  TRACE_KB(nb + 8);
  mma_kblock<N, 0>(acc, xver > 0 ? xdesc + (kTileBytes >> 4) : s1, s1 + kToB);
  wg_wait<1>();
  if (rel) mbar_arrive_cluster(rel_addr + (nb & 56));
  wg_wait<0>();
  if (rel) mbar_arrive_cluster(rel_addr + (nb & 56) + 8);
  fence_acc<N>(acc);
}

enum { kPlain, kFresh, kResid, kStagger };
template <int N, int KIND, class Pre>
__device__ __forceinline__ void mainloop(float (&acc)[2][96], uint32_t sb, int tile, int n0, int slot, int nkb,
                                         int pause_kk, int att, uint32_t rel_addr, bool rel, int own_kk, Pre pre) {
  constexpr bool RESID = KIND == kResid, FRESH = KIND == kFresh;
  constexpr uint32_t kStep = (N == 192 ? 5 : 4) * 512;
  const uint32_t ring = (((sb & 0x3FFFF) + kSmRing) >> 4) | (1u << 16);
  uint32_t st = ring + slot * kStep;
  uint32_t nb = n0 * 8, prev = 64;
  const uint32_t last = nb + 8 * (nkb - (RESID ? 3 : KIND == kStagger ? 2 : 1)), own = nb + 8 * own_kk;
  const uint32_t stg = (((sb & 0x3FFFF) + kSmStg) >> 4) | (1u << 16);
  uint32_t stop = pause_kk >= 0 ? nb + 8 * pause_kk : last;
  const bool signal = (threadIdx.x & 127) == 64;
  if (!FRESH) fence_acc<N>(acc);
  if (tile > 0) mbar_wait(sb + kBarTurn + (tile - 1) * 8, 0);
  TRACE_AT(tile, 0);
  if constexpr (FRESH) {
    mbar_wait(sb + kBarFull + (nb & 56), nb >> 6);
    TRACE_KB(nb);
    mma_kblock<N, 2>(acc, st, st + kToB);
    prev = nb & 56;
    st += kStep;
    nb += 8;
  }
#pragma unroll 1
  while (true) {
#pragma unroll 1
    do {
      mbar_wait(sb + kBarFull + (nb & 56), nb >> 6);
      TRACE_KB(nb);
      if constexpr (RESID) mma_kblock_t(acc, st + kToB, nb == own ? stg : st);
      else mma_kblock<N, 0>(acc, st, st + kToB);
      wg_wait<1>();
      if (rel) mbar_arrive_cluster(rel_addr + prev);
      prev = nb & 56;
      st += kStep;
      if (st == ring + 10240) st = ring;
      nb += 8;
    } while (nb != stop);
    if (stop == last) break;
    stop = last;
    if (signal) mbar_arrive(sb + kBarPause + att * 8);
    wg_wait<0>();
    if (rel) mbar_arrive_cluster(rel_addr + prev);
    prev = 64;
    mbar_wait(sb + kBarResume + att * 8, 0);
  }
  mbar_wait(sb + kBarFull + (nb & 56), nb >> 6);
  TRACE_KB(nb);
  if constexpr (RESID) {
    const uint32_t z = gridDim.y - 1;
    const uint32_t s2 = st + kStep, s3 = s2 == ring + 8192 ? ring : s2 + kStep;
    mma_half_t(acc[0], st + kToB, st);
    wg_wait<1>();
    if (rel) mbar_arrive_cluster(rel_addr + 32);
    mbar_wait(sb + kBarFull + 48, nb >> 6);
    TRACE_KB(nb + 8);
    mma_half_t(acc[0], s2 + kToB, s2);
    mbar_wait(sb + kBarFull + 56, nb >> 6);
    TRACE_KB(nb + 16);
    mma_half_t(acc[0], s3 + kToB, s3);
    mma_half_t(acc[1], st + kToB + 256, st + z);
    mma_half_t(acc[1], s2 + kToB + 256, s2 + z);
    wg_wait<2>();
#pragma unroll
    for (int i = 0; i < 64; i++) asm volatile("" : "+f"(acc[0][i])::"memory");
    pre(0);
    mma_half_t(acc[1], s3 + kToB + 256, s3 + z);
    wg_wait<2>();
    if (rel) mbar_arrive_cluster(rel_addr + 40);
    if (signal) mbar_arrive(sb + kBarTurn + tile * 8);
    pre(1);
    wg_wait<1>();
    if (rel) mbar_arrive_cluster(rel_addr + 48);
    wg_wait<0>();
    if (rel) mbar_arrive_cluster(rel_addr + 56);
#pragma unroll
    for (int i = 0; i < 64; i++) asm volatile("" : "+f"(acc[1][i])::"memory");
  } else if constexpr (KIND == kStagger) {
    const uint32_t z = gridDim.y - 1, s2 = st + kStep;
    mma_half(acc[1], st + 64, st + kToB);
    wg_wait<1>();
    if (rel) mbar_arrive_cluster(rel_addr + 40);
    mbar_wait(sb + kBarFull + 56, nb >> 6);
    TRACE_KB(nb + 8);
    mma_half(acc[1], s2 + 64, s2 + kToB);
    mma_half(acc[0], st, st + z + kToB);
    pre(0);
    mma_half(acc[0], s2, s2 + z + kToB);
    wg_wait<2>();
#pragma unroll
    for (int i = 0; i < 96; i++) asm volatile("" : "+f"(acc[1][i])::"memory");
    pre(1);
    wg_wait<1>();
    if (rel) mbar_arrive_cluster(rel_addr + 48);
    pre(2);
    if (signal) mbar_arrive(sb + kBarTurn + tile * 8);
    pre(3);
    wg_wait<0>();
    if (rel) mbar_arrive_cluster(rel_addr + 56);
#pragma unroll
    for (int i = 0; i < 96; i++) asm volatile("" : "+f"(acc[0][i])::"memory");
  } else {
    mma_kblock<N, 1>(acc, st, st + kToB);
    wg_wait<2>();
    if (rel) mbar_arrive_cluster(rel_addr + prev);
    pre();
    wg_wait<1>();
    if (signal) mbar_arrive(sb + kBarTurn + tile * 8);
    wg_wait<0>();
    if (rel) mbar_arrive_cluster(rel_addr + (nb & 56));
    fence_acc<N>(acc);
  }
}

__device__ __forceinline__ void publish_stats(uint32_t sb, uint2* stat, int w, int lane, unsigned epoch) {
  const uint32_t row = sb + kSmX + (32 * w + lane) * 128;
  float s[4], q[4];
#pragma unroll
  for (int c = 0; c < 4; c++) s[c] = q[c] = 0.f;
  uint32_t nx[4];
  ldsm4(row + ((lane & 7) << 4), nx);
#pragma unroll 1
  for (int J = 1; J <= 16; J++) {
    const uint32_t r[4] = {nx[0], nx[1], nx[2], nx[3]};
    ldsm4(row + ((J >> 3) & 1) * kTileBytes + (((J ^ lane) & 7) << 4), nx);
#pragma unroll
    for (int c = 0; c < 4; c++) {
      const float lo = bf_lo(r[c]);
      s[c] += lo;
      q[c] = fmaf(lo, lo, q[c]);
      if (c & 1) yield_slot();
    }
#pragma unroll
    for (int c = 0; c < 4; c++) {
      const float hi = bf_hi(r[c]);
      s[c] += hi;
      q[c] = fmaf(hi, hi, q[c]);
      if (c & 1) yield_slot();
    }
  }
  const int t = lane & 3, g = lane >> 2;
#pragma unroll
  for (int c = 0; c < 2; c++) {
    s[c] = (t & 2 ? s[c + 2] : s[c]) + shfl_xor(t & 2 ? s[c] : s[c + 2], 2);
    q[c] = (t & 2 ? q[c + 2] : q[c]) + shfl_xor(t & 2 ? q[c] : q[c + 2], 2);
  }
  const float so = (t & 1 ? s[1] : s[0]) + shfl_xor(t & 1 ? s[0] : s[1], 1);
  const float qo = (t & 1 ? q[1] : q[0]) + shfl_xor(t & 1 ? q[0] : q[1], 1);
  asm volatile("st.relaxed.gpu.global.v2.u32 [%0], {%1, %2};" ::"l"(stat + 32 * w + 8 * t + g),
               "r"(tag_value(so, epoch)), "r"(tag_value(qo, epoch)) : "memory");
}

__device__ __forceinline__ void add_chunk(float (&a)[8], const uint4& v) {
  a[0] += bf_lo(v.x); a[1] += bf_hi(v.x);
  a[2] += bf_lo(v.y); a[3] += bf_hi(v.y);
  a[4] += bf_lo(v.z); a[5] += bf_hi(v.z);
  a[6] += bf_lo(v.w); a[7] += bf_hi(v.w);
}

__device__ __forceinline__ int helper_col(int id, int slab) {
  return (slab < 3 ? slab * kD : (slab - 3) * 512) + id * 128;
}
__device__ __forceinline__ void helper_cta(const CUtensorMap* map_q, const CUtensorMap* map_1, uint8_t* sm,
                                           uint32_t sb, int id, int warp) {
  constexpr int kRed = 6 * 32768, kBar = kRed + 2 * 4096;
  const int tid = threadIdx.x;
  if (warp == 8 && elect()) {
#pragma unroll
    for (int s = 0; s < 6; s++) {
      mbar_init(sb + kBar + s * 8, 1);
      mbar_init(sb + kBar + 64 + s * 8, 4);
    }
    fence_async_smem();
#pragma unroll
    for (int s = 0; s < 6; s++) {
      mbar_expect_tx(sb + kBar + s * 8, 32768);
      tma2d(sb + s * 32768, map_q, sb + kBar + s * 8, id * 128, s * 128);
    }
  }
  __syncthreads();
  if (warp == 8) {
    int slot = 0, ph = 0;
#pragma unroll 1
    for (int n = 6; n < 80; n++) {
      mbar_wait(sb + kBar + 64 + slot * 8, ph);
      if (elect()) {
        mbar_expect_tx(sb + kBar + slot * 8, 32768);
        tma2d(sb + slot * 32768, n < 24 ? map_q : map_1, sb + kBar + slot * 8, helper_col(id, n >> 3), (n & 7) * 128);
      }
      if (++slot == 6) slot = 0, ph ^= 1;
    }
  } else if (warp < 8) {
    if (tid == 0) *reinterpret_cast<unsigned*>(sm + kBar + 128) = atomicAdd(&g_ticket, 1u) / kGrid + 1;
    int slot = warp >> 2, ph = 0;
#pragma unroll 1
    for (int slab = 0; slab < 10; slab++) {
      float a[8];
#pragma unroll
      for (int e = 0; e < 8; e++) a[e] = 0.f;
#pragma unroll 1
      for (int box = 0; box < 4; box++) {
        mbar_wait_bounded(sb + kBar + slot * 8, ph);
        const uint4* p = reinterpret_cast<const uint4*>(sm + slot * 32768) + (tid & 127);
        uint4 v[16];
#pragma unroll
        for (int i = 0; i < 16; i++) v[i] = p[i * 128];
        __syncwarp();
        if (elect()) mbar_arrive(sb + kBar + 64 + slot * 8);
#pragma unroll
        for (int i = 0; i < 16; i++) add_chunk(a, v[i]);
        slot += 2;
        if (slot >= 6) slot -= 6, ph ^= 1;
      }
      float* red = reinterpret_cast<float*>(sm + kRed + (slab & 1) * 4096);
#pragma unroll
      for (int e = 0; e < 8; e++) a[e] += shfl_xor(a[e], 16);
      if ((tid & 16) == 0) {
        float4* d = reinterpret_cast<float4*>(red + warp * 128 + (tid & 15) * 8);
        d[0] = make_float4(a[0], a[1], a[2], a[3]);
        d[1] = make_float4(a[4], a[5], a[6], a[7]);
      }
      asm volatile("bar.sync 1, 256;" ::: "memory");
      if (warp < 4) {
        float t = 0.f;
#pragma unroll
        for (int q = 0; q < 8; q++) t += red[q * 128 + tid];
        st_relaxed(g_cs + (slab < 3 ? 0 : 3 * kD) + helper_col(id, slab) + tid,
                   tag_value(t, *reinterpret_cast<volatile unsigned*>(sm + kBar + 128)));
      }
    }
  }
}

__device__ __forceinline__ void colsum_strip(const CUtensorMap* map, uint8_t* sm, uint32_t sb, int col, int half,
                                             int lane, unsigned epoch) {
  const uint32_t bar = sb + kBarSlab + half * 16;
  const int buf = kSmStg + half * 8192;
  float a[8];
#pragma unroll
  for (int e = 0; e < 8; e++) a[e] = 0.f;
#pragma unroll 1
  for (int r = -2; r < 4; r++) {
    if (r >= 0) {
      mbar_wait(bar + (r & 1) * 8, r >> 1);
      const uint4* p = reinterpret_cast<const uint4*>(sm + buf + (r & 1) * 4096) + lane;
#pragma unroll 1
      for (int q = 0; q < 8; q += 4) {
        uint4 v[4];
#pragma unroll
        for (int u = 0; u < 4; u++) v[u] = p[(q + u) * 32];
#pragma unroll
        for (int u = 0; u < 4; u++) {
          a[0] += bf_lo(v[u].x); a[1] += bf_hi(v[u].x); a[2] += bf_lo(v[u].y); a[3] += bf_hi(v[u].y);
          yield_slot();
          a[4] += bf_lo(v[u].z); a[5] += bf_hi(v[u].z); a[6] += bf_lo(v[u].w); a[7] += bf_hi(v[u].w);
          yield_slot();
        }
      }
      fence_async_smem();
      __syncwarp();
    }
    if (r < 2 && elect()) {
      mbar_expect_tx(bar + (r & 1) * 8, 4096);
      tma2d(sb + buf + (r & 1) * 4096, map, bar + (r & 1) * 8, col, half * 512 + (r + 2) * 128);
    }
  }
#pragma unroll
  for (int e = 0; e < 4; e++) a[e] = (lane & 16 ? a[e + 4] : a[e]) + shfl_xor(lane & 16 ? a[e] : a[e + 4], 16);
#pragma unroll
  for (int e = 0; e < 2; e++) a[e] = (lane & 8 ? a[e + 2] : a[e]) + shfl_xor(lane & 8 ? a[e] : a[e + 2], 8);
  a[0] = (lane & 4 ? a[1] : a[0]) + shfl_xor(lane & 4 ? a[0] : a[1], 4);
  a[0] += shfl_xor(a[0], 2);
  if (!(lane & 2)) st_relaxed(g_cs + half * (3 * kD + kF) + col + (lane & 1) * 8 + (lane >> 2), tag_value(a[0], epoch));
}

constexpr float kGeluBeta = 0.3292034911525734f;
constexpr float kGeluK = 2.423681954311584f;

__device__ __forceinline__ void store_staged(uint8_t* dst, uint32_t stg) {
  fence_async_smem();
  __syncwarp();
  if (elect()) {
    bulk_store(dst, stg, 4096);
    bulk_commit();
  }
}

#define GY_MASK 5
#define GF_MASK 3
#define GY(k) if ((GY_MASK >> k) & 1) yield_slot()
template <int J0, int J1>
__device__ __forceinline__ void fold_norm(float (&acc)[2][96], const float2 (&st)[4], const float4* vec) {
  float4 vn = vec[J0 * 4];
#pragma unroll
  for (int J = J0; J < J1; J++) {
    const float4 v = vn;
    if (J + 1 < J1) vn = vec[J * 4 + 4];
#pragma unroll
    for (int c = 0; c < 4; c++) {
      float& a0 = acc[c & 1][4 * J + (c & 2)];
      float& a1 = acc[c & 1][4 * J + (c & 2) + 1];
      a0 = fmaf(a0, st[c].x, fmaf(st[c].y, v.x, v.z));
      a1 = fmaf(a1, st[c].x, fmaf(st[c].y, v.y, v.w));
      asm volatile("" : "+f"(a0), "+f"(a1));
      if ((c & 1) && ((GF_MASK >> (c >> 1)) & 1)) yield_slot();
    }
  }
}

template <int CH, class Acquire>
__device__ __forceinline__ void gelu_chunk(const float (&acc)[2][96], uint32_t stg, int lane, uint8_t* prev,
                                           Acquire acquire) {
  uint32_t pk[8][4];
  float z[3][4];
  const uint32_t row = (stg + lane * 128) ^ ((lane & 7) << 4);
#define U(s, e) acc[(e) >> 1][4 * (CH * 8 + ((s) >> 1)) + 2 * ((s) & 1) + ((e) & 1)]
#pragma unroll
  for (int s = 0; s < 18; s++) {
    const int cur = s % 3, p1 = (s + 2) % 3, p2 = (s + 1) % 3, q = s - 2, jj = 2 * q - 24;
    const bool mid = s >= 1 && s < 17;
    if (mid) z[p1][0] = tanh_fast(z[p1][0]);
    if (s < 16) {
#pragma unroll
      for (int e = 0; e < 4; e++) {
        z[cur][e] = fmaf(U(s, e), U(s, e), kGeluK);
        asm volatile("" : "+f"(z[cur][e]));
      }
    }
    if (jj >= 0) stsm4(row ^ (jj << 4), pk[jj][0], pk[jj][1], pk[jj][2], pk[jj][3]);
    GY(0);
    if (mid) z[p1][1] = tanh_fast(z[p1][1]);
    if (q >= 0) {
      pk[q >> 1][2 * (q & 1)] = pack2(fmaf(U(q, 0), z[p2][0], U(q, 0)), fmaf(U(q, 1), z[p2][1], U(q, 1)));
      pk[q >> 1][2 * (q & 1) + 1] = pack2(fmaf(U(q, 2), z[p2][2], U(q, 2)), fmaf(U(q, 3), z[p2][3], U(q, 3)));
    }
    GY(1);
    if (mid) z[p1][2] = tanh_fast(z[p1][2]);
    if (s < 16) {
#pragma unroll
      for (int e = 0; e < 4; e++) {
        z[cur][e] *= U(s, e);
        asm volatile("" : "+f"(z[cur][e]));
      }
    }
    if (mid) z[p1][3] = tanh_fast(z[p1][3]);
    if (jj >= 0) stsm4(row ^ ((jj + 1) << 4), pk[jj + 1][0], pk[jj + 1][1], pk[jj + 1][2], pk[jj + 1][3]);
    GY(2);
    if (CH == 1 && s == 1) store_staged(prev, stg);
    if (q == 11) acquire();
  }
#undef U
}

__device__ __forceinline__ void scale_stats(float2 (&st)[4]) {
#pragma unroll
  for (int c = 0; c < 4; c++) {
    st[c].x *= kGeluBeta;
    st[c].y *= st[c].x;
  }
}

__device__ __forceinline__ void add_mean_term(float (&acc)[2][96], const float2 (&st)[4], uint8_t* sm, int tq,
                                              int lane) {
  const float2* cs = reinterpret_cast<const float2*>(sm + kSmCsQ) + tq * 96 + (lane & 3);
  float2 vn = cs[0];
#pragma unroll
  for (int J = 0; J < 24; J++) {
    const float2 v = vn;
    if (J < 23) vn = cs[J * 4 + 4];
#pragma unroll
    for (int c = 0; c < 4; c++) {
      acc[c & 1][4 * J + (c & 2)] = fmaf(st[c].y, v.x, acc[c & 1][4 * J + (c & 2)]);
      acc[c & 1][4 * J + (c & 2) + 1] = fmaf(st[c].y, v.y, acc[c & 1][4 * J + (c & 2) + 1]);
    }
    yield_slot();
  }
}

#define CV_MASK 1
#define HALO_AT 2
struct AttnRegs {
  uint32_t q[4][8], k[5][8], vt[5][8];
};
#define SCALED(c, J) pack2(acc[(c) & 1][4 * (J) + ((c) & 2)] * st[c].x, acc[(c) & 1][4 * (J) + ((c) & 2) + 1] * st[c].x)
__device__ __forceinline__ void convert_group(const float (&acc)[2][96], const float2 (&st)[4], AttnRegs& r, int c,
                                              int part) {
#pragma unroll
  for (int J = 0; J < 8; J++) {
    if (part == 0) r.q[c][J] = SCALED(c, J);
    if (part == 1) r.k[c + 1][J] = SCALED(c, 8 + J);
    if (part == 2) r.vt[c + 1][J] = transpose8(SCALED(c, 16 + J));
    if ((J & CV_MASK) == CV_MASK) yield_slot();
  }
}
#undef SCALED

__device__ __forceinline__ void convert_odd(const float (&acc)[2][96], const float2 (&st)[4], AttnRegs& r, int step,
                                            uint8_t* sm, uint32_t halo_bar, uint4* halo_out, bool send,
                                            unsigned epoch, int w, int lane) {
  if (step == 1) {
    convert_group(acc, st, r, 3, 2);
    convert_group(acc, st, r, 3, 1);
    if (w < 3) {
      uint2* hs = reinterpret_cast<uint2*>(sm + kSmHalo + w * 2048) + lane;
#pragma unroll
      for (int i = 0; i < 4; i++) {
        hs[i * 32] = make_uint2(r.k[4][2 * i], r.k[4][2 * i + 1]);
        hs[128 + i * 32] = make_uint2(r.vt[4][2 * i], r.vt[4][2 * i + 1]);
      }
      __syncwarp();
      if (elect()) mbar_arrive(halo_bar + w * 8);
    } else if (send) {
#pragma unroll
      for (int i = 0; i < 4; i++) {
        st_packet(halo_out + lane + i * 32, r.k[4][2 * i], r.k[4][2 * i + 1], epoch);
        st_packet(halo_out + lane + 128 + i * 32, r.vt[4][2 * i], r.vt[4][2 * i + 1], epoch);
      }
    }
  } else if (step == 2) {
    convert_group(acc, st, r, 1, 2);
  } else {
    convert_group(acc, st, r, 1, 1);
    convert_group(acc, st, r, 3, 0);
    convert_group(acc, st, r, 1, 0);
  }
}

__device__ __forceinline__ void epilogue_attn(const float (&acc)[2][96], const float2 (&st)[4], AttnRegs& r,
                                              uint8_t* sm, uint32_t sb, int layer, int tq, int b, int j,
                                              unsigned epoch, int tile, int w, int lane) {
  const int t = lane & 3, g = lane >> 2;
  const int hp = j + 8 * tq, att = 2 * layer + tq;
  auto& q = r.q;
  auto& k = r.k;
  auto& vt = r.vt;
  const bool first = w == 0 && (b & 7) == 0;
  const uint4* gh = g_halo + ((layer * 16 + b - 1) * 16 + hp) * 256 + lane;
  uint32_t tag[8];
#define LOAD_HALO()                                                                                    \
  _Pragma("unroll") for (int i = 0; i < 4; i++) {                                                      \
    ld_packet(gh + i * 32, k[0][2 * i], k[0][2 * i + 1], tag[i]);                                      \
    ld_packet(gh + 128 + i * 32, vt[0][2 * i], vt[0][2 * i + 1], tag[4 + i]);                          \
  }
#define AWAIT_HALO()                                                                                   \
  for (unsigned spins = 0;; spins++) {                                                                 \
    const unsigned d0 = (tag[0] ^ epoch) | (tag[1] ^ epoch) | (tag[2] ^ epoch) | (tag[3] ^ epoch);     \
    const unsigned d1 = (tag[4] ^ epoch) | (tag[5] ^ epoch) | (tag[6] ^ epoch) | (tag[7] ^ epoch);     \
    if (__all_sync(0xffffffffu, (d0 | d1) == 0)) break;                                                \
    if (spins > kSpinLimit) __trap();                                                                  \
    LOAD_HALO();                                                                                       \
  }
#pragma unroll
  for (int c = 0; c <= 6; c++) {
    if (c == HALO_AT) {
#pragma unroll
      for (int i = 0; i < 8; i++) k[0][i] = vt[0][i] = tag[i] = 0u;
      if (w > 0) {
        mbar_wait(sb + kBarHalo + (att * 3 + w - 1) * 8, 0);
        const uint2* hs = reinterpret_cast<const uint2*>(sm + kSmHalo + (w - 1) * 2048) + lane;
#pragma unroll
        for (int i = 0; i < 4; i++) {
          const uint2 a = hs[i * 32], d = hs[128 + i * 32];
          k[0][2 * i] = a.x; k[0][2 * i + 1] = a.y;
          vt[0][2 * i] = d.x; vt[0][2 * i + 1] = d.y;
        }
      } else if (!first) {
        LOAD_HALO();
      }
    }
    if (c < 6) convert_group(acc, st, r, 2 * (c & 1), 2 - (c >> 1));
  }
  TRACE_AT(tile, 8);
  if (w == 0 && !first) AWAIT_HALO();
  constexpr float kScale = 0.17677669529663687f * 1.4426950408889634f;
  const bool own0 = 2 * t <= g, own1 = 2 * t + 1 <= g;
  const uint32_t own_mask = (own0 ? 0xffffu : 0u) | (own1 ? 0xffff0000u : 0u);
  const uint32_t stg = sb + kSmStg + w * 4096;
  const uint32_t orow = stg + (lane & 7) * 128, ochunk = (lane >> 3) ^ (lane & 7);
  TRACE_AT(tile, 9);
  mbar_wait(sb + kBarPause + att * 8, 0);
  TRACE_AT(tile, 10);

  float s[2][6][4], o[2][4][2][4];
#pragma unroll
  for (int n = 0; n < 24; n++) {
    const int ks = n / 12, hd = (n % 12) / 6, m = n % 6, ca = 2 * (m / 3), kg = ca + m % 3, J = 4 * hd + 2 * ks;
    if (ks == 0) s[hd][m][0] = s[hd][m][1] = s[hd][m][2] = s[hd][m][3] = 0.f;
    mma16816(s[hd][m], q[ca][J], q[ca + 1][J], q[ca][J + 1], q[ca + 1][J + 1], k[kg][J], k[kg][J + 1]);
  }
  float v0[2][4], v1[2][4], m[2][4];
  uint32_t pp[2][4], po[2][4];
#define UNITS _Pragma("unroll") for (int hd = 0; hd < 2; hd++) _Pragma("unroll") for (int c = 0; c < 4; c++)
  UNITS {
    const int mp = 3 * (c >> 1) + (c & 1), r = 2 * (c & 1);
    float p0 = s[hd][mp][r], p1 = s[hd][mp][r + 1];
    if (c == 0 && first) p0 = p1 = -INFINITY;
    v0[hd][c] = own0 ? s[hd][mp + 1][r] : p0;
    v1[hd][c] = own1 ? s[hd][mp + 1][r + 1] : p1;
    m[hd][c] = fmaxf(v0[hd][c], v1[hd][c]);
  }
  UNITS m[hd][c] = fmaxf(m[hd][c], shfl_xor(m[hd][c], 1));
  UNITS m[hd][c] = fmaxf(m[hd][c], shfl_xor(m[hd][c], 2));
  UNITS {
    const float nm = -m[hd][c] * kScale;
    v0[hd][c] = ex2(fmaf(v0[hd][c], kScale, nm));
    v1[hd][c] = ex2(fmaf(v1[hd][c], kScale, nm));
    m[hd][c] = v0[hd][c] + v1[hd][c];
  }
  UNITS m[hd][c] += shfl_xor(m[hd][c], 1);
  UNITS m[hd][c] += shfl_xor(m[hd][c], 2);
  UNITS {
    const float inv = rcp(m[hd][c]);
    const uint32_t p = pack2(v0[hd][c] * inv, v1[hd][c] * inv);
    pp[hd][c] = p & ~own_mask;
    po[hd][c] = p & own_mask;
    asm volatile("" : "+r"(pp[hd][c]), "+r"(po[hd][c]));
  }
#pragma unroll
  for (int n = 0; n < 24; n++) {
    const int ph = n / 8, hd = (n >> 2) & 1, c = 2 * ((n >> 1) & 1) + (ph == 1), ds = n & 1, J = 4 * hd + 2 * ds;
    float(&d)[4] = o[hd][c][ds];
    if (ph < 2) d[0] = d[1] = d[2] = d[3] = 0.f;
    if (ph == 0) mma1688(d, vt[c + 1][J], vt[c + 1][J + 1], po[hd][c]);
    if (ph == 1) mma16816(d, vt[c][J], vt[c][J + 1], vt[c + 1][J], vt[c + 1][J + 1], pp[hd][c], po[hd][c]);
    if (ph == 2) mma1688(d, vt[c][J], vt[c][J + 1], pp[hd][c]);
    if (n == 3) {
      yield_slot();
      if (tq == 0 && lane == 0) mbar_arrive(sb + kBarResume + att * 8);
    }
  }
  yield_slot();
  TRACE_AT(tile, 11);
  UNITS stsm4_t(orow + c * 1024 + ((ochunk ^ (4 * hd)) << 4), pack2(o[hd][c][0][0], o[hd][c][0][1]),
                pack2(o[hd][c][0][2], o[hd][c][0][3]), pack2(o[hd][c][1][0], o[hd][c][1][1]),
                pack2(o[hd][c][1][2], o[hd][c][1][3]));
#undef UNITS
#undef AWAIT_HALO
#undef LOAD_HALO
  fence_async_smem();
  __syncwarp();
  if (tq == 1 && lane == 0) mbar_arrive(sb + kBarResume + att * 8);
  TRACE_AT(tile, 12);
  if (elect()) {
    bulk_store(g_o + (b * 16 + hp) * kTileBytes + w * 4096, stg, 4096);
    bulk_commit();
    bulk_wait();
    TRACE_AT(tile, 13);
    mbar_arrive(sb + kBarEpi + tile * 8);
  }
  __syncwarp();
}

__device__ __forceinline__ void gather_stats(uint8_t* sm, const uint2* stat, int r, unsigned epoch) {
  uint2 a[8];
#pragma unroll 1
  for (unsigned spins = 0;; spins++) {
    unsigned diff = 0;
#pragma unroll
    for (int i = 0; i < 8; i++) {
      a[i] = ld_relaxed2(stat + i * 128 + r);
      diff |= (a[i].x ^ epoch) | (a[i].y ^ epoch);
    }
    if (__all_sync(0xffffffffu, (diff & 7u) == 0)) break;
    if (spins > kSpinLimit) __trap();
  }
  float s = 0.f, q = 0.f;
#pragma unroll
  for (int i = 0; i < 8; i++) {
    s += untag_value(a[i].x);
    q += untag_value(a[i].y);
  }
  const float mean = s * (1.f / 1024.f);
  const float var = fmaxf(fmaf(-mean, mean, q * (1.f / 1024.f)), 0.f);
  reinterpret_cast<float2*>(sm + kSmStat)[r] = make_float2(rsqrtf(var + 1e-5f), -mean);
}

__device__ __forceinline__ void gather_colsums_qkv(uint8_t* sm, int tq, int j, int lane, unsigned epoch) {
  const uint2* src = reinterpret_cast<const uint2*>(g_cs + (j + 8 * tq) * 64) + lane;
  uint2 v[3], u[3];
  for (unsigned spins = 0;; spins++) {
    unsigned diff = 0;
#pragma unroll
    for (int q = 0; q < 3; q++) {
      v[q] = ld_relaxed2(src + q * (kD / 2));
      u[q] = make_uint2(epoch & 7u, epoch & 7u);
      if (tq) u[q] = ld_relaxed2(src + (q * kD + 3 * kD + kF) / 2);
    }
#pragma unroll
    for (int q = 0; q < 3; q++) diff |= (v[q].x ^ epoch) | (v[q].y ^ epoch) | (u[q].x ^ epoch) | (u[q].y ^ epoch);
    if (__all_sync(0xffffffffu, (diff & 7u) == 0)) break;
    if (spins > kSpinLimit) __trap();
  }
#pragma unroll
  for (int q = 0; q < 3; q++)
    reinterpret_cast<float2*>(sm + kSmCsQ)[tq * 96 + q * 32 + lane] =
        make_float2(untag_value(v[q].x) + untag_value(u[q].x), untag_value(v[q].y) + untag_value(u[q].y));
}

__device__ __forceinline__ void gather_colsums_w1(uint8_t* sm, const __nv_bfloat16* b1, int j, int lane,
                                                  unsigned epoch) {
#pragma unroll 1
  for (int blk = 0; blk < 7; blk++) {
    const int pair = 32 * (blk + (blk < 3 ? 3 * j : blk < 5 ? 21 + 2 * j : 35 + 2 * j)) + lane;
    const uint32_t bias = reinterpret_cast<const uint32_t*>(b1)[pair];
    uint2 v;
    for (unsigned spins = 0;; spins++) {
      v = ld_relaxed2(reinterpret_cast<const uint2*>(g_cs + 3 * kD) + pair);
      if (__all_sync(0xffffffffu, (((v.x ^ epoch) | (v.y ^ epoch)) & 7u) == 0)) break;
      if (spins > kSpinLimit) __trap();
    }
    reinterpret_cast<float4*>(sm + kSmV1)[blk * 32 + lane] =
        make_float4(untag_value(v.x), untag_value(v.y), kGeluBeta * bf_lo(bias), kGeluBeta * bf_hi(bias));
  }
}

#define PAUSE_QKV2 7
#define PAUSE_WO 2

__global__ void __cluster_dims__(2, 1, 1) __launch_bounds__(384, 1)
fused_layers_kernel(const __grid_constant__ CUtensorMap map_x, const __grid_constant__ CUtensorMap map_out,
                    const __grid_constant__ CUtensorMap map_qkv, const __grid_constant__ CUtensorMap map_wo,
                    const __grid_constant__ CUtensorMap map_w1a, const __grid_constant__ CUtensorMap map_w1b,
                    const __grid_constant__ CUtensorMap map_w2, const __grid_constant__ CUtensorMap map_csq,
                    const __grid_constant__ CUtensorMap map_cs1, const __grid_constant__ CUtensorMap map_css,
                    const __grid_constant__ Params prm) {
  extern __shared__ __align__(1024) uint8_t sm[];
  if (threadIdx.x < 128 && blockIdx.x < kCtas) TRACE_AT(15, 1);
  const uint32_t sb = __shfl_sync(0xffffffffu, smem_u32(sm), 0);
  const int warp = __shfl_sync(0xffffffffu, threadIdx.x >> 5, 0), lane = threadIdx.x & 31;
  const int cta = blockIdx.x, rank = cta & 1, cl = cta >> 1;
  const int grp = cl < 4 ? 0 : cl < 36 ? (cl - 4) & 7 : 1 + (cl - 36) % 7;
  const int j = cl < 4 ? 4 + cl : cl < 36 ? (cl - 4) >> 3 : 4 + (cl - 36) / 7;
  const int b = 2 * grp + rank;
  const int xcol = (b >> 3) * kD, xrow = (b & 7) * 128;

  if (cta >= kCtas) {
    helper_cta(&map_csq, &map_cs1, sm, sb, cta - kCtas, warp);
    return;
  }
  if ((warp < 8 || warp == 9) && elect()) {
    if (warp == 9) {
#pragma unroll
      for (int s = 0; s < 8; s++) mbar_init(sb + kBarFull + s * 8, 1);
      fence_async_smem();
#pragma unroll 1
      for (int s = 0; s < 4; s++) {
        const uint32_t full = sb + kBarFull + s * 8, dst = sb + kSmRing + s * 40960;
        mbar_expect_tx(full, 40960);
        tma2d(dst, &map_x, full, xcol + (s & 1) * 64, xrow);
        tma3d(dst + kTileBytes, &map_qkv, full, (j + 4 * (s & 2)) * 64, (s & 1) * 64, 0);
        tma3d(dst + kTileBytes + 12288, &map_qkv, full, (j + 4 * (s & 2)) * 64, (s & 1) * 64 + 32, 0);
      }
    } else {
      if (sb & 1023) __trap();
#pragma unroll
      for (int s = 0; s < 16; s++) mbar_init(sb + kBarTurn + warp * 128 + s * 8, warp < 5 ? 1 : warp == 5 ? 2 : 4);
    }
    asm volatile("fence.mbarrier_init.release.cluster;" ::: "memory");
  }
  __syncwarp();
  asm volatile("barrier.cluster.arrive.relaxed.aligned;" ::: "memory");

  if (warp >= 8) {
    asm volatile("setmaxnreg.dec.sync.aligned.u32 40;");
    if (warp < 10) {
      asm volatile("barrier.cluster.wait.aligned;" ::: "memory");
      uint32_t nb = 32, off = 0, kb = 0;
#define RING_STEP(WAIT, ISSUE)                                            \
  do {                                                                    \
    const uint32_t mb = nb - depth, full = sb + kBarFull + (nb & 56);     \
    if (kb == skip) kb += inc;                                            \
    mbar_wait(sb + kBarEmpty + (mb & 56), mb >> 6);                       \
    WAIT;                                                                 \
    if (elect()) { ISSUE; }                                               \
    TRACE_ISSUE(9 - warp, nb);                                            \
    kb += inc;                                                            \
    off = off == wrap ? 0 : off + step;                                   \
    nb += 8;                                                              \
  } while (nb != nend)
#pragma unroll 1
      for (int sg = 0; sg < kSegs; sg++) {
        const uint32_t e = prm.seg[sg];
        const int ty = e & 7, mode = (e >> 15) & 3, reset = (e >> 24) & 3;
        const uint32_t nend = nb + (e & 0x1f8);
        const uint32_t step = (e >> 17) & 1 ? 40960 : 32768, wrap = 163840 - step;
        const uint32_t depth = (e >> 18) & 1 ? 40 : 32;
        if (reset) off = reset == 1 ? 0 : reset == 2 ? 40960 : 131072;
        const uint32_t own = ty == 2 ? 8 + j : 2 * j;
        if (mode != kModeContinue) kb = mode == kModeHead ? own : (e >> 9) & 63;
        const uint32_t inc = mode >= kModeSkip && ty != 2 ? 2 : 1, skip = mode >= kModeSkip ? own + (kb & 1) : 255;
        if (warp == 8) {
          const CUtensorMap* map = ty < 2 ? &map_qkv : ty == 2 ? &map_wo : ty == 3 ? &map_w1a : ty < 6 ? &map_w1b : &map_w2;
          const int c0 = ty < 2 ? (j + 8 * ty) * 64 : 0;
          const int c2 = ty < 2 ? 0 : ty == 3 ? 3 * j : ty == 4 ? 24 + 2 * j : ty == 5 ? 40 + 2 * j : 2 * j;
          const uint32_t half = (ty < 2 || ty == 3) ? 12288 : 8192;
          const uint32_t bytes = 2 * half + (mode == kModeHead ? 0 : kTileBytes);
          const uint32_t dst = sb + kSmRing + kTileBytes + rank * half;
#pragma unroll 1
          RING_STEP(, mbar_expect_tx(full, bytes); tma3d_mc(dst + off, map, full, c0, kb * 64 + rank * 32, c2));
        } else if (mode == kModeHead) {
          off += ((nend - nb) >> 3) * step;
          nb = nend;
          if (off >= 163840) off -= 163840;
        } else if (sg < 2) {
#pragma unroll 1
          RING_STEP(, tma2d(sb + kSmRing + off, &map_x, full, xcol + kb * 64, xrow));
        } else {
          const uint8_t* src = ty == 6 ? g_h + b * 56 * kTileBytes : (ty == 2 ? g_o : g_x) + b * 16 * kTileBytes;
          const int dep = (e >> 19) & 31;
          if (dep < 28) mbar_wait(sb + kBarReady + dep * 8, 0);
          if ((dep & 30) == 28) {
#pragma unroll 1
            RING_STEP(mbar_wait(sb + kBarSrc + ((kb << (4 - inc)) & 56), dep),
                      bulk_load(sb + kSmRing + off, src + kb * kTileBytes, kTileBytes, full));
          } else {
#pragma unroll 1
            RING_STEP(, bulk_load(sb + kSmRing + off, src + kb * kTileBytes, kTileBytes, full));
          }
        }
      }
#undef RING_STEP
    } else {
      unsigned epoch = 0;
      if (warp == 10) {
        if (lane == 0) epoch = atomicAdd(&g_ticket, 1u) / kGrid + 1;
        *reinterpret_cast<unsigned*>(sm + kSmEpoch) = __shfl_sync(0xffffffffu, epoch, 0);
        asm volatile("barrier.cluster.wait.aligned;" ::: "memory");
        if (elect()) mbar_arrive(sb + kBarEpoch);
      } else {
        asm volatile("barrier.cluster.wait.aligned;" ::: "memory");
        mbar_wait_bounded(sb + kBarFull, 0);
        if (elect()) {
          mbar_expect_tx(sb + kBarInit, 32768);
          tma2d(sb + kSmX, &map_x, sb + kBarInit, xcol + j * 128, xrow);
          tma2d(sb + kSmX + kTileBytes, &map_x, sb + kBarInit, xcol + j * 128 + 64, xrow);
        }
        const uint2 u = reinterpret_cast<const uint2*>(prm.b2)[32 * j + lane];
        reinterpret_cast<float4*>(sm + kSmB2)[lane] = make_float4(
            2.f * kGeluBeta * bf_lo(u.x), 2.f * kGeluBeta * bf_hi(u.x), 2.f * kGeluBeta * bf_lo(u.y), 2.f * kGeluBeta * bf_hi(u.y));
      }
      mbar_wait_bounded(sb + kBarEpoch, 0);
      epoch = *reinterpret_cast<volatile unsigned*>(sm + kSmEpoch);
      if (cta < 96) {
        mbar_wait_bounded(sb + kBarInit, 0);
        colsum_strip(&map_css, sm, sb, (cta >> 5) * kD + 512 + (cta & 31) * 16, warp - 10, lane, epoch);
      }
      gather_colsums_qkv(sm, 11 - warp, j, lane, epoch);
      __syncwarp();
      if (elect()) mbar_arrive(sb + kBarCs + (11 - warp) * 8);
     if (warp == 10) {
#pragma unroll 1
      for (int i = 0; i < kTiles - 1; i++) {
        const bool xt = i == 2 || i == 6 || i == 9;
        const unsigned* line = g_flag + (i * 16 + b) * 32;
        mbar_wait(sb + (xt ? kBarX + (i >> 2) * 16 : kBarEpi + i * 8), 0);
        if (xt || i == 1 || i == 8) {
          unsigned todo = 0xff, spins = 0;
          do {
            const unsigned now = __ballot_sync(0xffffffffu, ld_relaxed(line + (lane & 7)) == epoch) & todo;
            if (now) {
              asm volatile("fence.acquire.gpu;\nfence.proxy.async.global;" ::: "memory");
              if ((now >> lane) & 1) mbar_arrive(sb + kBarSrc + lane * 8);
              todo ^= now;
            }
            if (++spins > kSpinLimit) __trap();
          } while (todo);
        } else {
          wait_flags(line + (lane & 7), epoch);
          if (elect()) mbar_arrive(sb + kBarReady + i * 8);
        }
        if (xt) {
          wait_flags(line + 8 + (lane & 7), epoch);
          if (elect()) mbar_arrive(sb + kBarReady + (14 + (i >> 2)) * 8);
        }
      }
     } else {
#pragma unroll 1
      for (int i = 0; i < kTiles - 1; i++) {
        if (i == 3) {
          gather_colsums_w1(sm, prm.b1, j, lane, epoch);
          __syncwarp();
          if (elect()) mbar_arrive(sb + kBarCs + 16);
        }
        const bool xt = i == 2 || i == 6 || i == 9;
#pragma unroll 1
        for (int h = 0; h < (xt ? 2 : 1); h++) {
          mbar_wait_bounded(sb + (xt ? kBarX + (i >> 2) * 16 + 8 * h : kBarEpi + i * 8), 0);
          const int ty = i >= 7 ? i - 7 : i;
          if (ty >= 2 && elect()) {
            uint8_t* dst = xt ? g_x + (b * 16 + 2 * j + h) * kTileBytes
                              : g_h + (b * 56 + 1 + (ty == 3 ? 3 * j : 16 * ty - 40 + 2 * j)) * kTileBytes;
            const int piece = (xt && h == 0) ? kTileBytes : kTileBytes / 4;
#pragma unroll 1
            for (int o = 0; o < kTileBytes; o += piece) {
              bulk_store(dst + o, sb + (xt ? kSmX + h * kTileBytes : kSmStg) + o, piece);
              bulk_commit();
              bulk_wait();
            }
            if (!xt) mbar_arrive(sb + kBarFree + i * 8);
          }
          __syncwarp();
          if (elect()) st_release(&g_flag[(i * 16 + b) * 32 + h * 8 + j], epoch);
          __syncwarp();
        }
      }
#pragma unroll 1
      for (int h = 0; h < 2; h++) {
        mbar_wait_bounded(sb + kBarX + 48 + 8 * h, 0);
        if (elect()) {
          tma2d_store(&map_out, sb + kSmX + h * kTileBytes, xcol + j * 128 + h * 64, xrow);
          bulk_commit();
          if (h == 1) bulk_wait_read();
        }
      }
     }
    }
    __syncwarp();
    asm volatile("barrier.cluster.arrive.relaxed.aligned;\nbarrier.cluster.wait.aligned;" ::: "memory");
  } else {
    asm volatile("setmaxnreg.inc.sync.aligned.u32 232;");
    asm volatile("barrier.cluster.wait.aligned;" ::: "memory");
    const int wg = warp >> 2, w = warp & 3;
    const bool rel = (threadIdx.x & 95) == 0;
    const uint32_t rel_addr = mapa(sb + kBarEmpty, w & 1);
    if (wg == 1) TRACE_AT(15, 0);
#define EPOCH (*reinterpret_cast<volatile unsigned*>(sm + kSmEpoch))

#pragma unroll 1
    for (int i = wg; i < kTiles; i += 2) {
      const int layer = i >= 7, ty = i - 7 * layer;
      TRACE_AT(i, 15);
      float acc[2][96];
      if (ty == 2 || ty == 6) {
        const int lane = lane_id();
        const uint32_t xa = sb + kSmX + ((lane >> 4) * 8 + (lane & 7)) * 128 + (((2 * w + ((lane >> 3) & 1)) ^ (lane & 7)) << 4);
        const float up = ty == 6 ? 2.f * kGeluBeta : 1.f, dn = ty == 6 ? 0.5f / kGeluBeta : 1.f;
#pragma unroll
        for (int h = 0; h < 2; h++) {
          const float* b2 = reinterpret_cast<const float*>(sm + kSmB2) + 64 * h + 16 * w + (lane >> 2);
          const float bias[2] = {ty == 6 ? b2[0] : 0.f, ty == 6 ? b2[8] : 0.f};
#pragma unroll
          for (int p = 0; p < 8; p++) {
            uint32_t r[4];
            ldsm4_t(xa + h * kTileBytes + p * 2048, r);
#pragma unroll
            for (int m = 0; m < 4; m++) {
              acc[h][8 * p + 2 * m] = fmaf(bf_lo(r[m]), up, bias[m & 1]);
              acc[h][8 * p + 2 * m + 1] = fmaf(bf_hi(r[m]), up, bias[m & 1]);
              asm volatile("" : "+f"(acc[h][8 * p + 2 * m]), "+f"(acc[h][8 * p + 2 * m + 1]));
            }
            yield_slot();
          }
        }
        auto stage = [&](int qt) {
          const int h = qt >> 1;
#pragma unroll
          for (int p = 4 * (qt & 1); p < 4 * (qt & 1) + 4; p++) {
            const float* a = &acc[h][8 * p];
            stsm4_t(xa + h * kTileBytes + p * 2048, pack2(a[0] * dn, a[1] * dn), pack2(a[2] * dn, a[3] * dn),
                    pack2(a[4] * dn, a[5] * dn), pack2(a[6] * dn, a[7] * dn));
            yield_slot();
          }
          if (qt & 1) {
            fence_async_smem();
            __syncwarp();
            if (elect()) mbar_arrive(sb + kBarX + (i >> 2) * 16 + 8 * h);
            TRACE_AT(i, 8 + h);
          }
        };
        mainloop<128, kResid>(acc, sb, i, layer * 152 + ty * 16, ty == 6 ? 4 : 0, ty == 6 ? 56 : 16,
                            ty == 2 ? PAUSE_WO : -1, 2 * layer + 1, rel_addr, rel, ty == 2 ? 8 : -1, stage);
        TRACE_AT(i, 2);
        stage(2);
        stage(3);
      } else {
        const int xver = 2 * layer + (ty >= 3);
        const uint32_t stg = sb + kSmStg + w * 4096;
        const float4* vec = reinterpret_cast<const float4*>(sm + kSmV1) + (ty == 3 ? 0 : 64 * ty - 160);
        int lane;
        uint8_t* hdst = g_h + (b * 56 + (ty == 3 ? 3 * j : 16 * ty - 40 + 2 * j)) * kTileBytes + w * 4096;
        float2 st[4];
        unsigned epoch;
        auto pre = [&] {
          lane = lane_id();
          if (ty < 4) mbar_wait(sb + (ty == 1 ? kBarEpi + (i - 1) * 8 : kBarStat + xver * 8), 0);
#pragma unroll
          for (int c = 0; c < 4; c++) st[c] = reinterpret_cast<const float2*>(sm + kSmStat)[32 * w + 8 * c + (lane >> 2)];
          epoch = EPOCH;
        };
        auto team_stats = [&] {
          uint2* stat = g_stat + (xver * 16 + b) * 1024;
          lane = lane_id();
          publish_stats(sb, stat + j * 128, w, lane, EPOCH);
          gather_stats(sm, stat, 32 * w + lane, EPOCH);
          __syncwarp();
          if (elect()) mbar_arrive(sb + kBarStat + xver * 8);
          TRACE_AT(i, 14);
        };
        if (ty < 4) {
          AttnRegs ar;
          auto odd = [&](int step) {
            if (step == 0) pre();
            else convert_odd(acc, st, ar, step, sm, sb + kBarHalo + (xver + ty) * 24,
                             g_halo + ((layer * 16 + b) * 16 + j + 8 * ty) * 256, (b & 7) != 7, epoch, w, lane);
          };
          head_blocks<192>(acc, sb, layer * 152 + (ty < 2 ? 2 * ty : 48), ty < 2 ? 2 * ty : 1, xver, rel_addr, rel);
          if (ty == 1) {
            if (i == 1) {
              mbar_wait(sb + kBarEpoch, 0);
              mbar_wait(sb + kBarInit, 0);
            }
            team_stats();
            epoch = 0;
#pragma unroll
            for (int c = 0; c < 4; c++) st[c] = reinterpret_cast<const float2*>(sm + kSmStat)[32 * w + 8 * c + (lane >> 2)];
          } else {
            mainloop<192, kPlain>(acc, sb, i, layer * 152 + (ty ? 52 : 4), ty ? 1 : 0, 14, -1, 0, rel_addr, rel, 0, pre);
            TRACE_AT(i, 2);
            if (ty == 3) goto wide_gelu;
          }
          if (layer == 0) mbar_wait(sb + kBarCs + ty * 8, 0);
          add_mean_term(acc, st, sm, ty, lane);
          if (ty == 1) {
            mainloop<192, kStagger>(acc, sb, i, layer * 152 + 18, 2, 14, PAUSE_QKV2, xver, rel_addr, rel, 0, odd);
            TRACE_AT(i, 2);
          } else {
            odd(1);
            odd(2);
            odd(3);
          }
          epilogue_attn(acc, st, ar, sm, sb, layer, ty, b, j, epoch, i, w, lane);
          TRACE_AT(i, 3);
          continue;
        wide_gelu:
          if (i == 3) mbar_wait(sb + kBarCs + 16, 0);
          scale_stats(st);
          fold_norm<16, 24>(acc, st, vec + (lane & 3));
          TRACE_AT(i, 11);
          gelu_chunk<2>(acc, stg, lane, nullptr, [] {});
          TRACE_AT(i, 12);
          fold_norm<0, 2>(acc, st, vec + (lane & 3));
          store_staged(hdst + 2 * kTileBytes, stg);
          fold_norm<2, 16>(acc, st, vec + (lane & 3));
        } else {
          if (ty == 4) {
            head_blocks<128>(acc, sb, layer * 152 + 50, 3, xver, rel_addr, rel);
            team_stats();
            mainloop<128, kPlain>(acc, sb, i, layer * 152 + 66, 4, 14, -1, 0, rel_addr, rel, 0, pre);
          } else {
            mainloop<128, kFresh>(acc, sb, i, layer * 152 + 80, 3, 16, -1, 0, rel_addr, rel, 0, pre);
          }
          TRACE_AT(i, 2);
          if (i == 4) mbar_wait(sb + kBarCs + 16, 0);
          scale_stats(st);
          fold_norm<0, 16>(acc, st, vec + (lane & 3));
        }
        auto own_store_done = [] {
          if (elect()) bulk_wait();
          __syncwarp();
        };
        TRACE_AT(i, 8);
        gelu_chunk<0>(acc, stg, lane, nullptr, [&] {
          if (ty == 3) own_store_done();
          else mbar_wait(sb + kBarFree + (i - 1) * 8, 0);
        });
        TRACE_AT(i, 9);
        gelu_chunk<1>(acc, stg, lane, hdst, own_store_done);
        TRACE_AT(i, 10);
        fence_async_smem();
        __syncwarp();
        if (elect()) mbar_arrive(sb + kBarEpi + i * 8);
      }
      TRACE_AT(i, 3);
    }
#undef EPOCH
    asm volatile("barrier.cluster.arrive.relaxed.aligned;\nbarrier.cluster.wait.aligned;" ::: "memory");
    if (wg == 1) TRACE_AT(15, 2);
  }
}

void build_segments(uint32_t* seg) {
  int n = 0, fine = 0;
  auto per_source = [&] { return 28 + (fine++ & 1); };
  auto add = [&](int ty, int cnt, int kb0, int mode, int wide, int depth5, int dep, int reset) {
    seg[n++] = ty | cnt << 3 | kb0 << 9 | mode << 15 | wide << 17 | depth5 << 18 | dep << 19 | reset << 24;
  };
  for (int l = 0; l < 2; l++) {
    const int t = 7 * l;
    if (l == 0) {
      add(0, 14, 2, kModePlain, 1, 0, 31, 1);
      add(1, 14, 2, kModePlain, 1, 0, 31, 0);
    } else {
      add(0, 2, 0, kModeHead, 1, 0, 31, 1);
      add(1, 2, 0, kModeHead, 1, 0, 31, 0);
      add(0, 7, 0, kModeSkip, 1, 0, per_source(), 0);
      add(0, 7, 1, kModeSkip, 1, 0, 15, 0);
      add(1, 7, 0, kModeSkip, 1, 0, 31, 0);
      add(1, 7, 1, kModeSkip, 1, 0, 31, 0);
    }
    add(2, 4, 0, kModePlain, 0, 0, t, 1);
    add(2, 4, 4, kModePlain, 0, 1, 31, 0);
    add(2, 1, 0, kModeHead, 0, 1, 31, 0);
    add(2, 7, 8, kModeSkip, 0, 1, per_source(), 0);
    add(3, 2, 0, kModeHead, 1, 0, 31, 2);
    add(4, 2, 0, kModeHead, 1, 0, 31, 0);
    add(3, 7, 0, kModeSkip, 1, 0, per_source(), 0);
    add(3, 7, 1, kModeSkip, 1, 0, 14 + 2 * l, 0);
    add(4, 4, 0, kModeSkip, 0, 0, 31, 3);
    add(4, 3, 0, kModeContinue, 0, 1, 31, 0);
    add(4, 7, 1, kModeSkip, 0, 1, 31, 0);
    add(5, 16, 0, kModePlain, 0, 1, 31, 0);
    add(6, 24, 0, kModePlain, 0, 1, t + 3, 0);
    add(6, 16, 24, kModePlain, 0, 1, t + 4, 0);
    add(6, 16, 40, kModePlain, 0, 1, t + 5, 0);
  }
}

typedef CUresult (*EncodeTiledFn)(CUtensorMap*, CUtensorMapDataType, cuuint32_t, void*, const cuuint64_t*,
                                  const cuuint64_t*, const cuuint32_t*, const cuuint32_t*, CUtensorMapInterleave,
                                  CUtensorMapSwizzle, CUtensorMapL2promotion, CUtensorMapFloatOOBfill);

CUtensorMap make_map(EncodeTiledFn enc, const void* p, int rank, const cuuint64_t* dims, const cuuint64_t* strides,
                     const cuuint32_t* box, CUtensorMapSwizzle swizzle = CU_TENSOR_MAP_SWIZZLE_128B,
                     CUtensorMapL2promotion promo = CU_TENSOR_MAP_L2_PROMOTION_L2_128B) {
  CUtensorMap m;
  const cuuint32_t es[5] = {1, 1, 1, 1, 1};
  enc(&m, CU_TENSOR_MAP_DATA_TYPE_BFLOAT16, rank, const_cast<void*>(p), dims, strides, box, es,
      CU_TENSOR_MAP_INTERLEAVE_NONE, swizzle, promo,
      CU_TENSOR_MAP_FLOAT_OOB_FILL_NONE);
  return m;
}

CUtensorMap weight_map(EncodeTiledFn enc, const void* p, int k, int n, int blocks) {
  const cuuint64_t dims[3] = {64, (cuuint64_t)k, (cuuint64_t)n / 64};
  const cuuint64_t strides[2] = {(cuuint64_t)n * 2, 128};
  const cuuint32_t box[3] = {64, 32, (cuuint32_t)blocks};
  return make_map(enc, p, 3, dims, strides, box, CU_TENSOR_MAP_SWIZZLE_128B, CU_TENSOR_MAP_L2_PROMOTION_L2_256B);
}

CUtensorMap slab_map(EncodeTiledFn enc, const void* p, int n, int cols, int rows) {
  const cuuint64_t dims[2] = {(cuuint64_t)n, kD};
  const cuuint64_t strides[1] = {(cuuint64_t)n * 2};
  const cuuint32_t box[2] = {(cuuint32_t)cols, (cuuint32_t)rows};
  return make_map(enc, p, 2, dims, strides, box, CU_TENSOR_MAP_SWIZZLE_NONE);
}

CUtensorMap token_map(EncodeTiledFn enc, const void* p, int rows) {
  const cuuint64_t dims[2] = {2 * kD, 1024};
  const cuuint64_t strides[1] = {4 * kD};
  const cuuint32_t box[2] = {64, (cuuint32_t)rows};
  return make_map(enc, p, 2, dims, strides, box);
}

}

extern "C" void kernel_launch(void* const* d_in, const int* in_sizes, int n_in, void* d_out, int out_size) {
  (void)in_sizes; (void)n_in; (void)out_size;
  static EncodeTiledFn enc = nullptr;
  if (!enc) {
    void* fn = nullptr;
    cudaDriverEntryPointQueryResult q;
    cudaGetDriverEntryPoint("cuTensorMapEncodeTiled", &fn, cudaEnableDefault, &q);
    enc = (EncodeTiledFn)fn;
    cudaFuncSetAttribute(fused_layers_kernel, cudaFuncAttributeMaxDynamicSharedMemorySize, kSmBytes);
  }
  Params prm;
  prm.b1 = (const __nv_bfloat16*)d_in[5];
  prm.b2 = (const __nv_bfloat16*)d_in[7];
  build_segments(prm.seg);
  const cuuint64_t qd[3] = {kD, kD, 3}, qs[2] = {3 * kD * 2, kD * 2};
  const cuuint32_t qb[3] = {64, 32, 3};
  const CUtensorMap map_x = token_map(enc, d_in[0], 128);
  const CUtensorMap map_out = token_map(enc, d_out, 128);
  const CUtensorMap map_qkv = make_map(enc, d_in[1], 3, qd, qs, qb);
  const CUtensorMap map_wo = weight_map(enc, d_in[2], kD, kD, 2);
  const CUtensorMap map_w1a = weight_map(enc, d_in[4], kD, kF, 3);
  const CUtensorMap map_w1b = weight_map(enc, d_in[4], kD, kF, 2);
  const CUtensorMap map_w2 = weight_map(enc, d_in[6], kF, kD, 2);
  fused_layers_kernel<<<kGrid, 384, kSmBytes>>>(map_x, map_out, map_qkv, map_wo, map_w1a, map_w1b, map_w2,
                                                slab_map(enc, d_in[1], 3 * kD, 128, 128), slab_map(enc, d_in[4], kF, 128, 128),
                                                slab_map(enc, d_in[1], 3 * kD, 16, 128), prm);
}
```

```cpp
#include <cuda.h>
#include <cuda_bf16.h>
#include <cuda_runtime.h>
#include <stdint.h>

namespace {

constexpr int kD = 1024;
constexpr int kF = 3584;
constexpr int kCtas = 128;
constexpr int kGrid = 132;
constexpr int kTiles = 14;
constexpr int kTileBytes = 16384;

constexpr int kSmRing = 0;
constexpr int kSmX = 163840;
constexpr int kSmStg = kSmX + 32768;
constexpr int kSmHalo = kSmStg + 16384;
constexpr int kSmCsQ = kSmHalo + 6144;
constexpr int kSmV1 = kSmCsQ + 384 * 4;
constexpr int kSmB2 = kSmV1 + 448 * 8;
constexpr int kSmStat = kSmB2 + 128 * 4;
constexpr int kSmBar = kSmStat + 128 * 8;
constexpr int kBarFull = kSmBar;
constexpr int kBarTurn = kBarFull + 8 * 8;
constexpr int kBarReady = kBarTurn + 14 * 8;
constexpr int kBarSrc = kBarReady + 17 * 8;
constexpr int kBarPause = kBarSrc + 8 * 8;
constexpr int kBarFree = kBarPause + 4 * 8;
constexpr int kBarCs = kBarFree + 14 * 8;
constexpr int kBarSlab = kBarCs + 3 * 8;
constexpr int kBarHalo = kBarSlab + 4 * 8;
constexpr int kBarInit = kBarHalo + 12 * 8;
constexpr int kBarEpoch = kBarInit + 8;
constexpr int kBarEmpty = kBarTurn + 5 * 128;
constexpr int kBarEpi = kBarEmpty + 128;
constexpr int kBarX = kBarEpi + 14 * 8;
constexpr int kBarStat = kBarX + 8 * 8;
constexpr int kBarResume = kBarStat + 4 * 8;
constexpr int kSmEpoch = kBarEpi + 2 * 128;
static_assert(kBarEpoch < kBarEmpty && kBarResume + 4 * 8 <= kSmEpoch, "barrier groups overflow");
constexpr int kSmBytes = kSmEpoch + 16 + 256;
constexpr int kSegs = 38;

constexpr int kFlagLines = kTiles * 16;

constexpr unsigned kSpinLimit = 1u << 22;

__device__ __align__(1024) uint8_t g_x[16 * 16 * kTileBytes];
__device__ __align__(1024) uint8_t g_o[16 * 16 * kTileBytes];
__device__ __align__(1024) uint8_t g_h[16 * 56 * kTileBytes];
__device__ __align__(128) uint2 g_stat[4 * 16 * 128 * 8];
__device__ __align__(128) unsigned g_cs[3 * kD + kF + 3 * kD];
__device__ __align__(128) uint4 g_halo[2 * 16 * 16 * 256];
__device__ __align__(128) unsigned g_flag[kFlagLines * 32];
__device__ unsigned g_ticket;

#define TRACE_AT(tile, k)
#define TRACE_PUB(i, k, c)
#define TRACE_ISSUE(which, nb)

struct Params {
  const __nv_bfloat16* b1;
  const __nv_bfloat16* b2;
  uint32_t seg[kSegs];
};

__device__ __forceinline__ uint32_t smem_u32(const void* p) {
  return (uint32_t)__cvta_generic_to_shared(p);
}
__device__ __forceinline__ uint32_t mapa(uint32_t a, uint32_t cta) {
  uint32_t r;
  asm("mapa.shared::cluster.u32 %0, %1, %2;" : "=r"(r) : "r"(a), "r"(cta));
  return r;
}
__device__ __forceinline__ void mbar_init(uint32_t bar, int cnt) {
  asm volatile("mbarrier.init.shared::cta.b64 [%0], %1;" ::"r"(bar), "r"(cnt) : "memory");
}
__device__ __forceinline__ void mbar_expect_tx(uint32_t bar, uint32_t bytes) {
  asm volatile("mbarrier.arrive.expect_tx.shared::cta.b64 _, [%0], %1;" ::"r"(bar), "r"(bytes) : "memory");
}
__device__ __forceinline__ void mbar_arrive(uint32_t bar) {
  asm volatile("mbarrier.arrive.shared::cta.b64 _, [%0];" ::"r"(bar) : "memory");
}
__device__ __forceinline__ void mbar_arrive_cluster(uint32_t cluster_addr) {
  asm volatile("mbarrier.arrive.shared::cluster.b64 _, [%0];" ::"r"(cluster_addr) : "memory");
}
__device__ __forceinline__ void mbar_wait(uint32_t bar, uint32_t parity) {
  asm volatile("{\n.reg .pred p;\nRETRY:\nmbarrier.try_wait.parity.shared::cta.b64 p, [%0], %1;\n"
               "@!p bra.uni RETRY;\n}" ::"r"(bar), "r"(parity) : "memory");
}
__device__ __forceinline__ void mbar_wait_bounded(uint32_t bar, uint32_t parity) {
  asm volatile("{\n.reg .pred p;\n.reg .u32 c;\nmov.u32 c, 0;\nRETRY:\n"
               "mbarrier.try_wait.parity.shared::cta.b64 p, [%0], %1;\n@p bra.uni DONE;\n"
               "add.u32 c, c, 1;\nsetp.lt.u32 p, c, %2;\n@p bra.uni RETRY;\ntrap;\nDONE:\n}"
               ::"r"(bar), "r"(parity), "n"(1u << 19) : "memory");
}
__device__ __forceinline__ void tma3d(uint32_t dst, const CUtensorMap* m, uint32_t bar, int c0, int c1, int c2) {
  asm volatile(
      "cp.async.bulk.tensor.3d.shared::cluster.global.mbarrier::complete_tx::bytes [%0], [%1, {%3, %4, %5}], [%2];"
      ::"r"(dst), "l"(m), "r"(bar), "r"(c0), "r"(c1), "r"(c2) : "memory");
}
__device__ __forceinline__ void tma3d_mc(uint32_t dst, const CUtensorMap* m, uint32_t bar, int c0, int c1, int c2) {
  asm volatile(
      "cp.async.bulk.tensor.3d.shared::cluster.global.mbarrier::complete_tx::bytes.multicast::cluster"
      " [%0], [%1, {%3, %4, %5}], [%2], %6;"
      ::"r"(dst), "l"(m), "r"(bar), "r"(c0), "r"(c1), "r"(c2), "h"((uint16_t)3) : "memory");
}
__device__ __forceinline__ void tma2d(uint32_t dst, const CUtensorMap* m, uint32_t bar, int c0, int c1) {
  asm volatile(
      "cp.async.bulk.tensor.2d.shared::cluster.global.mbarrier::complete_tx::bytes [%0], [%1, {%3, %4}], [%2];"
      ::"r"(dst), "l"(m), "r"(bar), "r"(c0), "r"(c1) : "memory");
}
__device__ __forceinline__ void tma2d_store(const CUtensorMap* m, uint32_t src, int c0, int c1) {
  asm volatile("cp.async.bulk.tensor.2d.global.shared::cta.bulk_group [%0, {%2, %3}], [%1];"
               ::"l"(m), "r"(src), "r"(c0), "r"(c1) : "memory");
}
__device__ __forceinline__ int lane_id() {
  int l;
  asm volatile("mov.u32 %0, %%laneid;" : "=r"(l));
  return l;
}
__device__ __forceinline__ bool elect() {
  uint32_t p;
  asm volatile("{\n.reg .pred p;\nelect.sync _|p, 0xffffffff;\nselp.b32 %0, 1, 0, p;\n}" : "=r"(p));
  return p;
}
__device__ __forceinline__ void bulk_load(uint32_t dst, const void* src, uint32_t bytes, uint32_t bar) {
  asm volatile("cp.async.bulk.shared::cluster.global.mbarrier::complete_tx::bytes [%0], [%1], %2, [%3];"
               ::"r"(dst), "l"(src), "r"(bytes), "r"(bar) : "memory");
}
__device__ __forceinline__ void bulk_store(void* dst, uint32_t src, uint32_t bytes) {
  asm volatile("cp.async.bulk.global.shared::cta.bulk_group [%0], [%1], %2;" ::"l"(dst), "r"(src), "r"(bytes)
               : "memory");
}
__device__ __forceinline__ void bulk_commit() { asm volatile("cp.async.bulk.commit_group;" ::: "memory"); }
__device__ __forceinline__ void bulk_wait_read() { asm volatile("cp.async.bulk.wait_group.read 0;" ::: "memory"); }
__device__ __forceinline__ void bulk_wait() { asm volatile("cp.async.bulk.wait_group 0;" ::: "memory"); }
__device__ __forceinline__ void fence_async_smem() { asm volatile("fence.proxy.async.shared::cta;" ::: "memory"); }
__device__ __forceinline__ unsigned ld_relaxed(const unsigned* p) {
  unsigned v;
  asm volatile("ld.relaxed.gpu.global.u32 %0, [%1];" : "=r"(v) : "l"(p) : "memory");
  return v;
}
__device__ __forceinline__ uint2 ld_relaxed2(const uint2* p) {
  uint2 v;
  asm volatile("ld.relaxed.gpu.global.v2.u32 {%0, %1}, [%2];" : "=r"(v.x), "=r"(v.y) : "l"(p) : "memory");
  return v;
}
__device__ __forceinline__ void st_relaxed(unsigned* p, unsigned v) {
  asm volatile("st.relaxed.gpu.global.u32 [%0], %1;" ::"l"(p), "r"(v) : "memory");
}
__device__ __forceinline__ void st_release(unsigned* p, unsigned v) {
  asm volatile("st.release.gpu.global.u32 [%0], %1;" ::"l"(p), "r"(v) : "memory");
}
__device__ __forceinline__ void wait_flags(const unsigned* p, unsigned epoch) {
  unsigned spins = 0;
  while (true) {
    const unsigned v = ld_relaxed(p);
    if (__all_sync(0xffffffffu, v == epoch)) break;
    if (++spins > kSpinLimit) __trap();
  }
  asm volatile("fence.acquire.gpu;\nfence.proxy.async.global;" ::: "memory");
  __syncwarp();
}
__device__ __forceinline__ void st_packet(uint4* p, uint32_t d0, uint32_t d1, uint32_t tag) {
  asm volatile("{\n.reg .b128 v;\n.reg .b64 x, y;\nmov.b64 x, {%1, %2};\nmov.b64 y, {%3, %3};\nmov.b128 v, {x, y};\n"
               "st.relaxed.gpu.global.b128 [%0], v;\n}" ::"l"(p), "r"(d0), "r"(d1), "r"(tag) : "memory");
}
__device__ __forceinline__ void ld_packet(const uint4* p, uint32_t& d0, uint32_t& d1, uint32_t& tag) {
  asm volatile("{\n.reg .b128 v;\n.reg .b64 x, y;\n.reg .b32 u;\nld.relaxed.gpu.global.b128 v, [%3];\n"
               "mov.b128 {x, y}, v;\nmov.b64 {%0, %1}, x;\nmov.b64 {%2, u}, y;\n}"
               : "=r"(d0), "=r"(d1), "=r"(tag) : "l"(p) : "memory");
}
__device__ __forceinline__ unsigned tag_value(float v, unsigned epoch) {
  return (__float_as_uint(v) & ~7u) | (epoch & 7u);
}
__device__ __forceinline__ float untag_value(unsigned v) { return __uint_as_float(v & ~7u); }
__device__ __forceinline__ void stsm4(uint32_t a, uint32_t r0, uint32_t r1, uint32_t r2, uint32_t r3) {
  asm volatile("stmatrix.sync.aligned.m8n8.x4.shared.b16 [%0], {%1, %2, %3, %4};" ::"r"(a), "r"(r0), "r"(r1),
               "r"(r2), "r"(r3) : "memory");
}
__device__ __forceinline__ void stsm4_t(uint32_t a, uint32_t r0, uint32_t r1, uint32_t r2, uint32_t r3) {
  asm volatile("stmatrix.sync.aligned.m8n8.x4.trans.shared.b16 [%0], {%1, %2, %3, %4};" ::"r"(a), "r"(r0),
               "r"(r1), "r"(r2), "r"(r3) : "memory");
}
__device__ __forceinline__ uint32_t transpose8(uint32_t a) {
  uint32_t d;
  asm volatile("movmatrix.sync.aligned.m8n8.trans.b16 %0, %1;" : "=r"(d) : "r"(a));
  return d;
}
__device__ __forceinline__ void mma16816(float (&c)[4], uint32_t a0, uint32_t a1, uint32_t a2, uint32_t a3,
                                         uint32_t b0, uint32_t b1) {
  asm volatile("mma.sync.aligned.m16n8k16.row.col.f32.bf16.bf16.f32 {%0, %1, %2, %3}, {%4, %5, %6, %7}, {%8, %9}, "
               "{%0, %1, %2, %3};"
               : "+f"(c[0]), "+f"(c[1]), "+f"(c[2]), "+f"(c[3])
               : "r"(a0), "r"(a1), "r"(a2), "r"(a3), "r"(b0), "r"(b1));
}
__device__ __forceinline__ void mma1688(float (&c)[4], uint32_t a0, uint32_t a1, uint32_t b0) {
  asm volatile("mma.sync.aligned.m16n8k8.row.col.f32.bf16.bf16.f32 {%0, %1, %2, %3}, {%4, %5}, {%6}, {%0, %1, %2, %3};"
               : "+f"(c[0]), "+f"(c[1]), "+f"(c[2]), "+f"(c[3]) : "r"(a0), "r"(a1), "r"(b0));
}
__device__ __forceinline__ float shfl_xor(float v, int m) {
  float r;
  asm volatile("shfl.sync.bfly.b32 %0, %1, %2, 31, 0xffffffff;" : "=f"(r) : "f"(v), "r"(m));
  return r;
}
__device__ __forceinline__ float tanh_fast(float x) {
  float r;
  asm volatile("tanh.approx.f32 %0, %1;" : "=f"(r) : "f"(x));
  return r;
}
__device__ __forceinline__ void ldsm4(uint32_t a, uint32_t (&r)[4]) {
  asm volatile("ldmatrix.sync.aligned.m8n8.x4.shared.b16 {%0, %1, %2, %3}, [%4];"
               : "=r"(r[0]), "=r"(r[1]), "=r"(r[2]), "=r"(r[3]) : "r"(a) : "memory");
}
__device__ __forceinline__ void ldsm4_t(uint32_t a, uint32_t (&r)[4]) {
  asm volatile("ldmatrix.sync.aligned.m8n8.x4.trans.shared.b16 {%0, %1, %2, %3}, [%4];"
               : "=r"(r[0]), "=r"(r[1]), "=r"(r[2]), "=r"(r[3]) : "r"(a) : "memory");
}
__device__ __forceinline__ uint32_t pack2(float lo, float hi) {
  uint32_t r;
  asm volatile("cvt.rn.bf16x2.f32 %0, %1, %2;" : "=r"(r) : "f"(hi), "f"(lo));
  return r;
}
__device__ __forceinline__ float bf_lo(uint32_t r) { return __uint_as_float(r << 16); }
__device__ __forceinline__ float bf_hi(uint32_t r) { return __uint_as_float(r & 0xffff0000u); }
__device__ __forceinline__ float ex2(float x) {
  float r;
  asm("ex2.approx.ftz.f32 %0, %1;" : "=f"(r) : "f"(x));
  return r;
}
__device__ __forceinline__ float rcp(float x) {
  float r;
  asm("rcp.approx.ftz.f32 %0, %1;" : "=f"(r) : "f"(x));
  return r;
}
template <int N>
__device__ __forceinline__ void wg_wait() {
  asm volatile("wgmma.wait_group.sync.aligned %0;" ::"n"(N) : "memory");
}
__device__ __forceinline__ void yield_slot() { asm volatile("pmevent 0;"); }

template <int N, int KIND>
__device__ __forceinline__ void mma_kblock(float (&acc)[2][96], uint32_t a, uint32_t b);

#define F8(m, d, i) m(d[i]), m(d[i + 1]), m(d[i + 2]), m(d[i + 3]), m(d[i + 4]), m(d[i + 5]), m(d[i + 6]), m(d[i + 7])
#define KSTEP(N, A, B, oa0, oa1, ob, sd)                                                   \
  "mov.b64 db, {" B ", hb};\nadd.u64 db, db, " #ob ";\n"                                    \
  "mov.b64 da, {" A ", ha};\nadd.u64 da, da, " #oa0 ";\n"                                   \
  "wgmma.mma_async.sync.aligned.m64n" #N "k16.f32.bf16.bf16 {" ACC##N##_0 "}, da, db, " #sd ", 1, 1, 0, 1;\n" \
  "mov.b64 da, {" A ", ha};\nadd.u64 da, da, " #oa1 ";\n"                                   \
  "wgmma.mma_async.sync.aligned.m64n" #N "k16.f32.bf16.bf16 {" ACC##N##_1 "}, da, db, " #sd ", 1, 1, 0, 1;\n"

#define MMA_KBLOCK(N, KIND, A, B, ob2, ob3, sd, MID, MODE)                                 \
  template <>                                                                              \
  __device__ __forceinline__ void mma_kblock<N, KIND>(float (&acc)[2][96], uint32_t a, uint32_t b) { \
    asm volatile("{\n.reg .b32 ha, hb;\n.reg .b64 da, db;\n"                            \
                 "mov.b32 ha, 0x40000080;\nmov.b32 hb, 0x40000040;\n"                       \
                 "wgmma.fence.sync.aligned;\n"                                             \
                 KSTEP(N, A, B, 0, 64, 0, sd) KSTEP(N, A, B, 2, 66, 128, 1) MID               \
                 KSTEP(N, A, B, 4, 68, ob2, 1) KSTEP(N, A, B, 6, 70, ob3, 1) "wgmma.commit_group.sync.aligned;\n}\n"  \
                 : OPS##N(MODE) : "r"(a), "r"(b) : "memory");                              \
  }
#define MMA_KBLOCKS(N, A, B, ob2, ob3)                                                     \
  MMA_KBLOCK(N, 0, A, B, ob2, ob3, 1, "", "+f")                                            \
  MMA_KBLOCK(N, 1, A, B, ob2, ob3, 1, "wgmma.commit_group.sync.aligned;\n", "+f")          \
  MMA_KBLOCK(N, 2, A, B, ob2, ob3, 0, "", "=f")

#define ACC128_0 \
  "%0, %1, %2, %3, %4, %5, %6, %7, %8, %9, %10, %11, %12, %13, %14, %15, " \
  "%16, %17, %18, %19, %20, %21, %22, %23, %24, %25, %26, %27, %28, %29, %30, %31, " \
  "%32, %33, %34, %35, %36, %37, %38, %39, %40, %41, %42, %43, %44, %45, %46, %47, " \
  "%48, %49, %50, %51, %52, %53, %54, %55, %56, %57, %58, %59, %60, %61, %62, %63"
#define ACC128_1 \
  "%64, %65, %66, %67, %68, %69, %70, %71, %72, %73, %74, %75, %76, %77, %78, %79, " \
  "%80, %81, %82, %83, %84, %85, %86, %87, %88, %89, %90, %91, %92, %93, %94, %95, " \
  "%96, %97, %98, %99, %100, %101, %102, %103, %104, %105, %106, %107, %108, %109, %110, %111, " \
  "%112, %113, %114, %115, %116, %117, %118, %119, %120, %121, %122, %123, %124, %125, %126, %127"
#define OPS128(m) \
  F8(m, acc[0], 0), F8(m, acc[0], 8), F8(m, acc[0], 16), F8(m, acc[0], 24), F8(m, acc[0], 32), F8(m, acc[0], 40), F8(m, acc[0], 48), F8(m, acc[0], 56), \
        F8(m, acc[1], 0), F8(m, acc[1], 8), F8(m, acc[1], 16), F8(m, acc[1], 24), F8(m, acc[1], 32), F8(m, acc[1], 40), F8(m, acc[1], 48), F8(m, acc[1], 56)
MMA_KBLOCKS(128, "%128", "%129", 512, 640)

#define ACC192_0 \
  "%0, %1, %2, %3, %4, %5, %6, %7, %8, %9, %10, %11, %12, %13, %14, %15, " \
  "%16, %17, %18, %19, %20, %21, %22, %23, %24, %25, %26, %27, %28, %29, %30, %31, " \
  "%32, %33, %34, %35, %36, %37, %38, %39, %40, %41, %42, %43, %44, %45, %46, %47, " \
  "%48, %49, %50, %51, %52, %53, %54, %55, %56, %57, %58, %59, %60, %61, %62, %63, " \
  "%64, %65, %66, %67, %68, %69, %70, %71, %72, %73, %74, %75, %76, %77, %78, %79, " \
  "%80, %81, %82, %83, %84, %85, %86, %87, %88, %89, %90, %91, %92, %93, %94, %95"
#define ACC192_1 \
  "%96, %97, %98, %99, %100, %101, %102, %103, %104, %105, %106, %107, %108, %109, %110, %111, " \
  "%112, %113, %114, %115, %116, %117, %118, %119, %120, %121, %122, %123, %124, %125, %126, %127, " \
  "%128, %129, %130, %131, %132, %133, %134, %135, %136, %137, %138, %139, %140, %141, %142, %143, " \
  "%144, %145, %146, %147, %148, %149, %150, %151, %152, %153, %154, %155, %156, %157, %158, %159, " \
  "%160, %161, %162, %163, %164, %165, %166, %167, %168, %169, %170, %171, %172, %173, %174, %175, " \
  "%176, %177, %178, %179, %180, %181, %182, %183, %184, %185, %186, %187, %188, %189, %190, %191"
#define OPS192(m) \
  F8(m, acc[0], 0), F8(m, acc[0], 8), F8(m, acc[0], 16), F8(m, acc[0], 24), F8(m, acc[0], 32), F8(m, acc[0], 40), F8(m, acc[0], 48), F8(m, acc[0], 56), F8(m, acc[0], 64), F8(m, acc[0], 72), F8(m, acc[0], 80), F8(m, acc[0], 88), \
        F8(m, acc[1], 0), F8(m, acc[1], 8), F8(m, acc[1], 16), F8(m, acc[1], 24), F8(m, acc[1], 32), F8(m, acc[1], 40), F8(m, acc[1], 48), F8(m, acc[1], 56), F8(m, acc[1], 64), F8(m, acc[1], 72), F8(m, acc[1], 80), F8(m, acc[1], 88)
MMA_KBLOCKS(192, "%192", "%193", 768, 896)

#define HSTEP(oa, ob)                                                                       \
  "mov.b64 db, {%97, hb};\nadd.u64 db, db, " #ob ";\nmov.b64 da, {%96, ha};\nadd.u64 da, da, " #oa ";\n" \
  "wgmma.mma_async.sync.aligned.m64n192k16.f32.bf16.bf16 {" ACC192_0 "}, da, db, 1, 1, 1, 0, 1;\n"
__device__ __forceinline__ void mma_half(float (&d)[96], uint32_t a, uint32_t b) {
  asm volatile("{\n.reg .b32 ha, hb;\n.reg .b64 da, db;\nmov.b32 ha, 0x40000080;\nmov.b32 hb, 0x40000040;\n"
               "wgmma.fence.sync.aligned;\n" HSTEP(0, 0) HSTEP(2, 128) HSTEP(4, 768) HSTEP(6, 896)
               "wgmma.commit_group.sync.aligned;\n}\n"
               : F8("+f", d, 0), F8("+f", d, 8), F8("+f", d, 16), F8("+f", d, 24), F8("+f", d, 32), F8("+f", d, 40),
                 F8("+f", d, 48), F8("+f", d, 56), F8("+f", d, 64), F8("+f", d, 72), F8("+f", d, 80), F8("+f", d, 88)
               : "r"(a), "r"(b) : "memory");
}

#define TSTEP(REGS, W, X, ow, ox)                                                           \
  "mov.b64 db, {" X ", hi};\nadd.u64 db, db, " #ox ";\nmov.b64 da, {" W ", hi};\nadd.u64 da, da, " #ow ";\n" \
  "wgmma.mma_async.sync.aligned.m64n128k16.f32.bf16.bf16 {" REGS "}, da, db, 1, 1, 1, 1, 0;\n"
#define THEAD "{\n.reg .b32 hi;\n.reg .b64 da, db;\nmov.b32 hi, 0x40000040;\nwgmma.fence.sync.aligned;\n"
#define TTAIL "wgmma.commit_group.sync.aligned;\n}\n"
__device__ __forceinline__ void mma_kblock_t(float (&acc)[2][96], uint32_t wd, uint32_t xd) {
  asm volatile(THEAD TSTEP(ACC128_0, "%128", "%129", 0, 0) TSTEP(ACC128_1, "%128", "%129", 256, 0)
               TSTEP(ACC128_0, "%128", "%129", 128, 2) TSTEP(ACC128_1, "%128", "%129", 384, 2)
               TSTEP(ACC128_0, "%128", "%129", 512, 4) TSTEP(ACC128_1, "%128", "%129", 768, 4)
               TSTEP(ACC128_0, "%128", "%129", 640, 6) TSTEP(ACC128_1, "%128", "%129", 896, 6) TTAIL
               : OPS128("+f") : "r"(wd), "r"(xd) : "memory");
}
__device__ __forceinline__ void mma_half_t(float (&d)[96], uint32_t wd, uint32_t xd) {
  asm volatile(THEAD TSTEP(ACC128_0, "%64", "%65", 0, 0) TSTEP(ACC128_0, "%64", "%65", 128, 2)
               TSTEP(ACC128_0, "%64", "%65", 512, 4) TSTEP(ACC128_0, "%64", "%65", 640, 6) TTAIL
               : F8("+f", d, 0), F8("+f", d, 8), F8("+f", d, 16), F8("+f", d, 24), F8("+f", d, 32), F8("+f", d, 40),
                 F8("+f", d, 48), F8("+f", d, 56) : "r"(wd), "r"(xd) : "memory");
}

enum { kModePlain = 0, kModeHead = 1, kModeSkip = 2, kModeContinue = 3 };

template <int N>
__device__ __forceinline__ void fence_acc(float (&acc)[2][96]) {
#pragma unroll
  for (int h = 0; h < 2; h++)
#pragma unroll
    for (int i = 0; i < N / 2; i++) asm volatile("" : "+f"(acc[h][i])::"memory");
}

constexpr uint32_t kToB = (kTileBytes >> 4) + ((4096u >> 4) << 16) - (1u << 16);

#define TRACE_KB(nb)

template <int N>
__device__ __forceinline__ void head_blocks(float (&acc)[2][96], uint32_t sb, int n0, int slot, int xver,
                                            uint32_t rel_addr, bool rel) {
  const uint32_t ring = (((sb & 0x3FFFF) + kSmRing) >> 4) | (1u << 16);
  const uint32_t xdesc = (((sb & 0x3FFFF) + kSmX) >> 4) | (1u << 16);
  const uint32_t s0 = ring + slot * 2560, s1 = ring + ((slot + 1) & 3) * 2560;
  const uint32_t nb = n0 * 8, xbar = sb + kBarX + (xver - 1) * 16;
  if (xver > 0) {
    mbar_wait(xbar, 0);
    mbar_wait(sb + kBarTurn + (xver == 1 ? 2 : 3 * xver) * 8, 0);
  }
  mbar_wait(sb + kBarFull + (nb & 56), nb >> 6);
  if (n0 == 0) TRACE_AT(0, 1);
  TRACE_KB(nb);
  mma_kblock<N, 2>(acc, xver > 0 ? xdesc : s0, s0 + kToB);
  if (xver > 0) mbar_wait(xbar + 8, 0);
  mbar_wait(sb + kBarFull + (nb & 56) + 8, nb >> 6);
  TRACE_KB(nb + 8);
  mma_kblock<N, 0>(acc, xver > 0 ? xdesc + (kTileBytes >> 4) : s1, s1 + kToB);
  wg_wait<1>();
  if (rel) mbar_arrive_cluster(rel_addr + (nb & 56));
  wg_wait<0>();
  if (rel) mbar_arrive_cluster(rel_addr + (nb & 56) + 8);
  fence_acc<N>(acc);
}

enum { kPlain, kFresh, kResid, kStagger };
template <int N, int KIND, class Pre>
__device__ __forceinline__ void mainloop(float (&acc)[2][96], uint32_t sb, int tile, int n0, int slot, int nkb,
                                         int pause_kk, int att, uint32_t rel_addr, bool rel, int own_kk, Pre pre) {
  constexpr bool RESID = KIND == kResid, FRESH = KIND == kFresh;
  constexpr uint32_t kStep = (N == 192 ? 5 : 4) * 512;
  const uint32_t ring = (((sb & 0x3FFFF) + kSmRing) >> 4) | (1u << 16);
  uint32_t st = ring + slot * kStep;
  uint32_t nb = n0 * 8, prev = 64;
  const uint32_t last = nb + 8 * (nkb - (RESID ? 4 : KIND == kStagger ? 2 : 1)), own = nb + 8 * own_kk;
  const uint32_t stg = (((sb & 0x3FFFF) + kSmStg) >> 4) | (1u << 16);
  uint32_t stop = pause_kk >= 0 ? nb + 8 * pause_kk : last;
  const bool signal = (threadIdx.x & 127) == 64;
  if (!FRESH) fence_acc<N>(acc);
  if (tile > 0) mbar_wait(sb + kBarTurn + (tile - 1) * 8, 0);
  TRACE_AT(tile, 0);
  if constexpr (FRESH) {
    mbar_wait(sb + kBarFull + (nb & 56), nb >> 6);
    TRACE_KB(nb);
    mma_kblock<N, 2>(acc, st, st + kToB);
    prev = nb & 56;
    st += kStep;
    nb += 8;
  }
#pragma unroll 1
  while (true) {
#pragma unroll 1
    do {
      mbar_wait(sb + kBarFull + (nb & 56), nb >> 6);
      TRACE_KB(nb);
      if constexpr (RESID) mma_kblock_t(acc, st + kToB, nb == own ? stg : st);
      else mma_kblock<N, 0>(acc, st, st + kToB);
      wg_wait<1>();
      if (rel) mbar_arrive_cluster(rel_addr + prev);
      prev = nb & 56;
      st += kStep;
      if (st == ring + 10240) st = ring;
      nb += 8;
    } while (nb != stop);
    if (stop == last) break;
    stop = last;
    if (signal) mbar_arrive(sb + kBarPause + att * 8);
    wg_wait<0>();
    if (rel) mbar_arrive_cluster(rel_addr + prev);
    prev = 64;
    mbar_wait(sb + kBarResume + att * 8, 0);
  }
  mbar_wait(sb + kBarFull + (nb & 56), nb >> 6);
  TRACE_KB(nb);
  if constexpr (RESID) {
    const uint32_t z = gridDim.y - 1;
    const uint32_t s1 = st + kStep, s2 = s1 + kStep, s3 = s2 == ring + 8192 ? ring : s2 + kStep;
    mma_half_t(acc[0], st + kToB, st);
    wg_wait<1>();
    if (rel) mbar_arrive_cluster(rel_addr + 24);
    mbar_wait(sb + kBarFull + 40, nb >> 6);
    TRACE_KB(nb + 8);
    mma_half_t(acc[0], s1 + kToB, s1);
    mbar_wait(sb + kBarFull + 48, nb >> 6);
    TRACE_KB(nb + 16);
    mma_half_t(acc[0], s2 + kToB, s2);
    mbar_wait(sb + kBarFull + 56, nb >> 6);
    TRACE_KB(nb + 24);
    mma_half_t(acc[0], s3 + kToB, s3);
    mma_half_t(acc[1], st + kToB + 256, st + z);
    mma_half_t(acc[1], s1 + kToB + 256, s1 + z);
    wg_wait<2>();
#pragma unroll
    for (int i = 0; i < 64; i++) asm volatile("" : "+f"(acc[0][i])::"memory");
    pre(0);
    mma_half_t(acc[1], s2 + kToB + 256, s2 + z);
    wg_wait<2>();
    if (rel) mbar_arrive_cluster(rel_addr + 32);
    pre(1);
    mma_half_t(acc[1], s3 + kToB + 256, s3 + z);
    wg_wait<2>();
    if (rel) mbar_arrive_cluster(rel_addr + 40);
    wg_wait<1>();
    if (signal) mbar_arrive(sb + kBarTurn + tile * 8);
    if (rel) mbar_arrive_cluster(rel_addr + 48);
    wg_wait<0>();
    if (rel) mbar_arrive_cluster(rel_addr + 56);
#pragma unroll
    for (int i = 0; i < 64; i++) asm volatile("" : "+f"(acc[1][i])::"memory");
  } else if constexpr (KIND == kStagger) {
    const uint32_t z = gridDim.y - 1, s2 = st + kStep;
    mma_half(acc[1], st + 64, st + kToB);
    wg_wait<1>();
    if (rel) mbar_arrive_cluster(rel_addr + 40);
    mbar_wait(sb + kBarFull + 56, nb >> 6);
    TRACE_KB(nb + 8);
    mma_half(acc[1], s2 + 64, s2 + kToB);
    mma_half(acc[0], st, st + z + kToB);
    pre(0);
    mma_half(acc[0], s2, s2 + z + kToB);
    wg_wait<2>();
#pragma unroll
    for (int i = 0; i < 96; i++) asm volatile("" : "+f"(acc[1][i])::"memory");
    pre(1);
    wg_wait<1>();
    if (rel) mbar_arrive_cluster(rel_addr + 48);
    pre(2);
    if (signal) mbar_arrive(sb + kBarTurn + tile * 8);
    pre(3);
    wg_wait<0>();
    if (rel) mbar_arrive_cluster(rel_addr + 56);
#pragma unroll
    for (int i = 0; i < 96; i++) asm volatile("" : "+f"(acc[0][i])::"memory");
  } else {
    mma_kblock<N, 1>(acc, st, st + kToB);
    wg_wait<2>();
    if (rel) mbar_arrive_cluster(rel_addr + prev);
    pre();
    wg_wait<1>();
    if (signal) mbar_arrive(sb + kBarTurn + tile * 8);
    wg_wait<0>();
    if (rel) mbar_arrive_cluster(rel_addr + (nb & 56));
    fence_acc<N>(acc);
  }
}

__device__ __forceinline__ void publish_stats(uint32_t sb, uint2* stat, int w, int lane, unsigned epoch) {
  const uint32_t row = sb + kSmX + (32 * w + lane) * 128;
  float s[4], q[4];
#pragma unroll
  for (int c = 0; c < 4; c++) s[c] = q[c] = 0.f;
  uint32_t nx[4];
  ldsm4(row + ((lane & 7) << 4), nx);
#pragma unroll 1
  for (int J = 1; J <= 16; J++) {
    const uint32_t r[4] = {nx[0], nx[1], nx[2], nx[3]};
    ldsm4(row + ((J >> 3) & 1) * kTileBytes + (((J ^ lane) & 7) << 4), nx);
#pragma unroll
    for (int c = 0; c < 4; c++) {
      const float lo = bf_lo(r[c]);
      s[c] += lo;
      q[c] = fmaf(lo, lo, q[c]);
      if (c & 1) yield_slot();
    }
#pragma unroll
    for (int c = 0; c < 4; c++) {
      const float hi = bf_hi(r[c]);
      s[c] += hi;
      q[c] = fmaf(hi, hi, q[c]);
      if (c & 1) yield_slot();
    }
  }
  const int t = lane & 3, g = lane >> 2;
#pragma unroll
  for (int c = 0; c < 2; c++) {
    s[c] = (t & 2 ? s[c + 2] : s[c]) + shfl_xor(t & 2 ? s[c] : s[c + 2], 2);
    q[c] = (t & 2 ? q[c + 2] : q[c]) + shfl_xor(t & 2 ? q[c] : q[c + 2], 2);
  }
  const float so = (t & 1 ? s[1] : s[0]) + shfl_xor(t & 1 ? s[0] : s[1], 1);
  const float qo = (t & 1 ? q[1] : q[0]) + shfl_xor(t & 1 ? q[0] : q[1], 1);
  asm volatile("st.relaxed.gpu.global.v2.u32 [%0], {%1, %2};" ::"l"(stat + 32 * w + 8 * t + g),
               "r"(tag_value(so, epoch)), "r"(tag_value(qo, epoch)) : "memory");
}

__device__ __forceinline__ void add_chunk(float (&a)[8], const uint4& v) {
  a[0] += bf_lo(v.x); a[1] += bf_hi(v.x);
  a[2] += bf_lo(v.y); a[3] += bf_hi(v.y);
  a[4] += bf_lo(v.z); a[5] += bf_hi(v.z);
  a[6] += bf_lo(v.w); a[7] += bf_hi(v.w);
}

__device__ __forceinline__ int helper_col(int id, int slab) {
  return (slab < 3 ? slab * kD : (slab - 3) * 512) + id * 128;
}
__device__ __forceinline__ void helper_cta(const CUtensorMap* map_q, const CUtensorMap* map_1, uint8_t* sm,
                                           uint32_t sb, int id, int warp) {
  constexpr int kRed = 6 * 32768, kBar = kRed + 2 * 4096;
  const int tid = threadIdx.x;
  if (warp == 8 && elect()) {
#pragma unroll
    for (int s = 0; s < 6; s++) {
      mbar_init(sb + kBar + s * 8, 1);
      mbar_init(sb + kBar + 64 + s * 8, 4);
    }
    fence_async_smem();
#pragma unroll
    for (int s = 0; s < 6; s++) {
      mbar_expect_tx(sb + kBar + s * 8, 32768);
      tma2d(sb + s * 32768, map_q, sb + kBar + s * 8, id * 128, s * 128);
    }
  }
  __syncthreads();
  if (warp == 8) {
    int slot = 0, ph = 0;
#pragma unroll 1
    for (int n = 6; n < 80; n++) {
      mbar_wait(sb + kBar + 64 + slot * 8, ph);
      if (elect()) {
        mbar_expect_tx(sb + kBar + slot * 8, 32768);
        tma2d(sb + slot * 32768, n < 24 ? map_q : map_1, sb + kBar + slot * 8, helper_col(id, n >> 3), (n & 7) * 128);
      }
      if (++slot == 6) slot = 0, ph ^= 1;
    }
  } else if (warp < 8) {
    if (tid == 0) *reinterpret_cast<unsigned*>(sm + kBar + 128) = atomicAdd(&g_ticket, 1u) / kGrid + 1;
    int slot = warp >> 2, ph = 0;
#pragma unroll 1
    for (int slab = 0; slab < 10; slab++) {
      float a[8];
#pragma unroll
      for (int e = 0; e < 8; e++) a[e] = 0.f;
#pragma unroll 1
      for (int box = 0; box < 4; box++) {
        mbar_wait_bounded(sb + kBar + slot * 8, ph);
        const uint4* p = reinterpret_cast<const uint4*>(sm + slot * 32768) + (tid & 127);
        uint4 v[16];
#pragma unroll
        for (int i = 0; i < 16; i++) v[i] = p[i * 128];
        __syncwarp();
        if (elect()) mbar_arrive(sb + kBar + 64 + slot * 8);
#pragma unroll
        for (int i = 0; i < 16; i++) add_chunk(a, v[i]);
        slot += 2;
        if (slot >= 6) slot -= 6, ph ^= 1;
      }
      float* red = reinterpret_cast<float*>(sm + kRed + (slab & 1) * 4096);
#pragma unroll
      for (int e = 0; e < 8; e++) a[e] += shfl_xor(a[e], 16);
      if ((tid & 16) == 0) {
        float4* d = reinterpret_cast<float4*>(red + warp * 128 + (tid & 15) * 8);
        d[0] = make_float4(a[0], a[1], a[2], a[3]);
        d[1] = make_float4(a[4], a[5], a[6], a[7]);
      }
      asm volatile("bar.sync 1, 256;" ::: "memory");
      if (warp < 4) {
        float t = 0.f;
#pragma unroll
        for (int q = 0; q < 8; q++) t += red[q * 128 + tid];
        st_relaxed(g_cs + (slab < 3 ? 0 : 3 * kD) + helper_col(id, slab) + tid,
                   tag_value(t, *reinterpret_cast<volatile unsigned*>(sm + kBar + 128)));
      }
    }
  }
}

__device__ __forceinline__ void colsum_strip(const CUtensorMap* map, uint8_t* sm, uint32_t sb, int col, int half,
                                             int lane, unsigned epoch) {
  const uint32_t bar = sb + kBarSlab + half * 16;
  const int buf = kSmStg + half * 8192;
  float a[8];
#pragma unroll
  for (int e = 0; e < 8; e++) a[e] = 0.f;
#pragma unroll 1
  for (int r = -2; r < 4; r++) {
    if (r >= 0) {
      mbar_wait(bar + (r & 1) * 8, r >> 1);
      const uint4* p = reinterpret_cast<const uint4*>(sm + buf + (r & 1) * 4096) + lane;
#pragma unroll 1
      for (int q = 0; q < 8; q += 4) {
        uint4 v[4];
#pragma unroll
        for (int u = 0; u < 4; u++) v[u] = p[(q + u) * 32];
#pragma unroll
        for (int u = 0; u < 4; u++) {
          a[0] += bf_lo(v[u].x); a[1] += bf_hi(v[u].x); a[2] += bf_lo(v[u].y); a[3] += bf_hi(v[u].y);
          yield_slot();
          a[4] += bf_lo(v[u].z); a[5] += bf_hi(v[u].z); a[6] += bf_lo(v[u].w); a[7] += bf_hi(v[u].w);
          yield_slot();
        }
      }
      fence_async_smem();
      __syncwarp();
    }
    if (r < 2 && elect()) {
      mbar_expect_tx(bar + (r & 1) * 8, 4096);
      tma2d(sb + buf + (r & 1) * 4096, map, bar + (r & 1) * 8, col, half * 512 + (r + 2) * 128);
    }
  }
#pragma unroll
  for (int e = 0; e < 4; e++) a[e] = (lane & 16 ? a[e + 4] : a[e]) + shfl_xor(lane & 16 ? a[e] : a[e + 4], 16);
#pragma unroll
  for (int e = 0; e < 2; e++) a[e] = (lane & 8 ? a[e + 2] : a[e]) + shfl_xor(lane & 8 ? a[e] : a[e + 2], 8);
  a[0] = (lane & 4 ? a[1] : a[0]) + shfl_xor(lane & 4 ? a[0] : a[1], 4);
  a[0] += shfl_xor(a[0], 2);
  if (!(lane & 2)) st_relaxed(g_cs + half * (3 * kD + kF) + col + (lane & 1) * 8 + (lane >> 2), tag_value(a[0], epoch));
}

constexpr float kGeluBeta = 0.3292034911525734f;
constexpr float kGeluK = 2.423681954311584f;

__device__ __forceinline__ void store_staged(uint8_t* dst, uint32_t stg) {
  fence_async_smem();
  __syncwarp();
  if (elect()) {
    bulk_store(dst, stg, 4096);
    bulk_commit();
  }
}

#define GY_MASK 5
#define GF_MASK 3
#define GY(k) if ((GY_MASK >> k) & 1) yield_slot()
template <int J0, int J1>
__device__ __forceinline__ void fold_norm(float (&acc)[2][96], const float2 (&st)[4], const float4* vec) {
  float4 vn = vec[J0 * 4];
#pragma unroll
  for (int J = J0; J < J1; J++) {
    const float4 v = vn;
    if (J + 1 < J1) vn = vec[J * 4 + 4];
#pragma unroll
    for (int c = 0; c < 4; c++) {
      float& a0 = acc[c & 1][4 * J + (c & 2)];
      float& a1 = acc[c & 1][4 * J + (c & 2) + 1];
      a0 = fmaf(a0, st[c].x, fmaf(st[c].y, v.x, v.z));
      a1 = fmaf(a1, st[c].x, fmaf(st[c].y, v.y, v.w));
      asm volatile("" : "+f"(a0), "+f"(a1));
      if ((c & 1) && ((GF_MASK >> (c >> 1)) & 1)) yield_slot();
    }
  }
}

template <int CH, class Acquire>
__device__ __forceinline__ void gelu_chunk(const float (&acc)[2][96], uint32_t stg, int lane, uint8_t* prev,
                                           Acquire acquire) {
  uint32_t pk[8][4];
  float z[3][4];
  const uint32_t row = (stg + lane * 128) ^ ((lane & 7) << 4);
#define U(s, e) acc[(e) >> 1][4 * (CH * 8 + ((s) >> 1)) + 2 * ((s) & 1) + ((e) & 1)]
#pragma unroll
  for (int s = 0; s < 18; s++) {
    const int cur = s % 3, p1 = (s + 2) % 3, p2 = (s + 1) % 3, q = s - 2, jj = 2 * q - 24;
    const bool mid = s >= 1 && s < 17;
    if (mid) z[p1][0] = tanh_fast(z[p1][0]);
    if (s < 16) {
#pragma unroll
      for (int e = 0; e < 4; e++) {
        z[cur][e] = fmaf(U(s, e), U(s, e), kGeluK);
        asm volatile("" : "+f"(z[cur][e]));
      }
    }
    if (jj >= 0) stsm4(row ^ (jj << 4), pk[jj][0], pk[jj][1], pk[jj][2], pk[jj][3]);
    GY(0);
    if (mid) z[p1][1] = tanh_fast(z[p1][1]);
    if (q >= 0) {
      pk[q >> 1][2 * (q & 1)] = pack2(fmaf(U(q, 0), z[p2][0], U(q, 0)), fmaf(U(q, 1), z[p2][1], U(q, 1)));
      pk[q >> 1][2 * (q & 1) + 1] = pack2(fmaf(U(q, 2), z[p2][2], U(q, 2)), fmaf(U(q, 3), z[p2][3], U(q, 3)));
    }
    GY(1);
    if (mid) z[p1][2] = tanh_fast(z[p1][2]);
    if (s < 16) {
#pragma unroll
      for (int e = 0; e < 4; e++) {
        z[cur][e] *= U(s, e);
        asm volatile("" : "+f"(z[cur][e]));
      }
    }
    if (mid) z[p1][3] = tanh_fast(z[p1][3]);
    if (jj >= 0) stsm4(row ^ ((jj + 1) << 4), pk[jj + 1][0], pk[jj + 1][1], pk[jj + 1][2], pk[jj + 1][3]);
    GY(2);
    if (CH == 1 && s == 1) store_staged(prev, stg);
    if (q == 11) acquire();
  }
#undef U
}

__device__ __forceinline__ void scale_stats(float2 (&st)[4]) {
#pragma unroll
  for (int c = 0; c < 4; c++) {
    st[c].x *= kGeluBeta;
    st[c].y *= st[c].x;
  }
}

__device__ __forceinline__ void add_mean_term(float (&acc)[2][96], const float2 (&st)[4], uint8_t* sm, int tq,
                                              int lane) {
  const float2* cs = reinterpret_cast<const float2*>(sm + kSmCsQ) + tq * 96 + (lane & 3);
  float2 vn = cs[0];
#pragma unroll
  for (int J = 0; J < 24; J++) {
    const float2 v = vn;
    if (J < 23) vn = cs[J * 4 + 4];
#pragma unroll
    for (int c = 0; c < 4; c++) {
      acc[c & 1][4 * J + (c & 2)] = fmaf(st[c].y, v.x, acc[c & 1][4 * J + (c & 2)]);
      acc[c & 1][4 * J + (c & 2) + 1] = fmaf(st[c].y, v.y, acc[c & 1][4 * J + (c & 2) + 1]);
    }
    yield_slot();
  }
}

#define CV_MASK 1
#define HALO_AT 2
struct AttnRegs {
  uint32_t q[4][8], k[5][8], vt[5][8];
};
#define SCALED(c, J) pack2(acc[(c) & 1][4 * (J) + ((c) & 2)] * st[c].x, acc[(c) & 1][4 * (J) + ((c) & 2) + 1] * st[c].x)
__device__ __forceinline__ void convert_group(const float (&acc)[2][96], const float2 (&st)[4], AttnRegs& r, int c,
                                              int part) {
#pragma unroll
  for (int J = 0; J < 8; J++) {
    if (part == 0) r.q[c][J] = SCALED(c, J);
    if (part == 1) r.k[c + 1][J] = SCALED(c, 8 + J);
    if (part == 2) r.vt[c + 1][J] = transpose8(SCALED(c, 16 + J));
    if ((J & CV_MASK) == CV_MASK) yield_slot();
  }
}
#undef SCALED

__device__ __forceinline__ void convert_odd(const float (&acc)[2][96], const float2 (&st)[4], AttnRegs& r, int step,
                                            uint8_t* sm, uint32_t halo_bar, uint4* halo_out, bool send,
                                            unsigned epoch, int w, int lane) {
  if (step == 1) {
    convert_group(acc, st, r, 3, 2);
    convert_group(acc, st, r, 3, 1);
    if (w < 3) {
      uint2* hs = reinterpret_cast<uint2*>(sm + kSmHalo + w * 2048) + lane;
#pragma unroll
      for (int i = 0; i < 4; i++) {
        hs[i * 32] = make_uint2(r.k[4][2 * i], r.k[4][2 * i + 1]);
        hs[128 + i * 32] = make_uint2(r.vt[4][2 * i], r.vt[4][2 * i + 1]);
      }
      __syncwarp();
      if (elect()) mbar_arrive(halo_bar + w * 8);
    } else if (send) {
#pragma unroll
      for (int i = 0; i < 4; i++) {
        st_packet(halo_out + lane + i * 32, r.k[4][2 * i], r.k[4][2 * i + 1], epoch);
        st_packet(halo_out + lane + 128 + i * 32, r.vt[4][2 * i], r.vt[4][2 * i + 1], epoch);
      }
    }
  } else if (step == 2) {
    convert_group(acc, st, r, 1, 2);
  } else {
    convert_group(acc, st, r, 1, 1);
    convert_group(acc, st, r, 3, 0);
    convert_group(acc, st, r, 1, 0);
  }
}

__device__ __forceinline__ void epilogue_attn(const float (&acc)[2][96], const float2 (&st)[4], AttnRegs& r,
                                              uint8_t* sm, uint32_t sb, int layer, int tq, int b, int j,
                                              unsigned epoch, int tile, int w, int lane) {
  const int t = lane & 3, g = lane >> 2;
  const int hp = j + 8 * tq, att = 2 * layer + tq;
  auto& q = r.q;
  auto& k = r.k;
  auto& vt = r.vt;
  const bool first = w == 0 && (b & 7) == 0;
  const uint4* gh = g_halo + ((layer * 16 + b - 1) * 16 + hp) * 256 + lane;
  uint32_t tag[8];
#define LOAD_HALO()                                                                                    \
  _Pragma("unroll") for (int i = 0; i < 4; i++) {                                                      \
    ld_packet(gh + i * 32, k[0][2 * i], k[0][2 * i + 1], tag[i]);                                      \
    ld_packet(gh + 128 + i * 32, vt[0][2 * i], vt[0][2 * i + 1], tag[4 + i]);                          \
  }
#define AWAIT_HALO()                                                                                   \
  for (unsigned spins = 0;; spins++) {                                                                 \
    const unsigned d0 = (tag[0] ^ epoch) | (tag[1] ^ epoch) | (tag[2] ^ epoch) | (tag[3] ^ epoch);     \
    const unsigned d1 = (tag[4] ^ epoch) | (tag[5] ^ epoch) | (tag[6] ^ epoch) | (tag[7] ^ epoch);     \
    if (__all_sync(0xffffffffu, (d0 | d1) == 0)) break;                                                \
    if (spins > kSpinLimit) __trap();                                                                  \
    LOAD_HALO();                                                                                       \
  }
#pragma unroll
  for (int c = 0; c <= 6; c++) {
    if (c == HALO_AT) {
#pragma unroll
      for (int i = 0; i < 8; i++) k[0][i] = vt[0][i] = tag[i] = 0u;
      if (w > 0) {
        mbar_wait(sb + kBarHalo + (att * 3 + w - 1) * 8, 0);
        const uint2* hs = reinterpret_cast<const uint2*>(sm + kSmHalo + (w - 1) * 2048) + lane;
#pragma unroll
        for (int i = 0; i < 4; i++) {
          const uint2 a = hs[i * 32], d = hs[128 + i * 32];
          k[0][2 * i] = a.x; k[0][2 * i + 1] = a.y;
          vt[0][2 * i] = d.x; vt[0][2 * i + 1] = d.y;
        }
      } else if (!first) {
        LOAD_HALO();
      }
    }
    if (c < 6) convert_group(acc, st, r, 2 * (c & 1), 2 - (c >> 1));
  }
  TRACE_AT(tile, 8);
  if (w == 0 && !first) AWAIT_HALO();
  constexpr float kScale = 0.17677669529663687f * 1.4426950408889634f;
  const bool own0 = 2 * t <= g, own1 = 2 * t + 1 <= g;
  const uint32_t own_mask = (own0 ? 0xffffu : 0u) | (own1 ? 0xffff0000u : 0u);
  const uint32_t stg = sb + kSmStg + w * 4096;
  const uint32_t orow = stg + (lane & 7) * 128, ochunk = (lane >> 3) ^ (lane & 7);
  TRACE_AT(tile, 9);
  mbar_wait(sb + kBarPause + att * 8, 0);
  TRACE_AT(tile, 10);

  float s[2][6][4], o[2][4][2][4];
#pragma unroll
  for (int n = 0; n < 24; n++) {
    const int ks = n / 12, hd = (n % 12) / 6, m = n % 6, ca = 2 * (m / 3), kg = ca + m % 3, J = 4 * hd + 2 * ks;
    if (ks == 0) s[hd][m][0] = s[hd][m][1] = s[hd][m][2] = s[hd][m][3] = 0.f;
    mma16816(s[hd][m], q[ca][J], q[ca + 1][J], q[ca][J + 1], q[ca + 1][J + 1], k[kg][J], k[kg][J + 1]);
  }
  float v0[2][4], v1[2][4], m[2][4];
  uint32_t pp[2][4], po[2][4];
#define UNITS _Pragma("unroll") for (int hd = 0; hd < 2; hd++) _Pragma("unroll") for (int c = 0; c < 4; c++)
  UNITS {
    const int mp = 3 * (c >> 1) + (c & 1), r = 2 * (c & 1);
    float p0 = s[hd][mp][r], p1 = s[hd][mp][r + 1];
    if (c == 0 && first) p0 = p1 = -INFINITY;
    v0[hd][c] = own0 ? s[hd][mp + 1][r] : p0;
    v1[hd][c] = own1 ? s[hd][mp + 1][r + 1] : p1;
    m[hd][c] = fmaxf(v0[hd][c], v1[hd][c]);
  }
  UNITS m[hd][c] = fmaxf(m[hd][c], shfl_xor(m[hd][c], 1));
  UNITS m[hd][c] = fmaxf(m[hd][c], shfl_xor(m[hd][c], 2));
  UNITS {
    const float nm = -m[hd][c] * kScale;
    v0[hd][c] = ex2(fmaf(v0[hd][c], kScale, nm));
    v1[hd][c] = ex2(fmaf(v1[hd][c], kScale, nm));
    m[hd][c] = v0[hd][c] + v1[hd][c];
  }
  UNITS m[hd][c] += shfl_xor(m[hd][c], 1);
  UNITS m[hd][c] += shfl_xor(m[hd][c], 2);
  UNITS {
    const float inv = rcp(m[hd][c]);
    const uint32_t p = pack2(v0[hd][c] * inv, v1[hd][c] * inv);
    pp[hd][c] = p & ~own_mask;
    po[hd][c] = p & own_mask;
    asm volatile("" : "+r"(pp[hd][c]), "+r"(po[hd][c]));
  }
#pragma unroll
  for (int n = 0; n < 24; n++) {
    const int ph = n / 8, hd = (n >> 2) & 1, c = 2 * ((n >> 1) & 1) + (ph == 1), ds = n & 1, J = 4 * hd + 2 * ds;
    float(&d)[4] = o[hd][c][ds];
    if (ph < 2) d[0] = d[1] = d[2] = d[3] = 0.f;
    if (ph == 0) mma1688(d, vt[c + 1][J], vt[c + 1][J + 1], po[hd][c]);
    if (ph == 1) mma16816(d, vt[c][J], vt[c][J + 1], vt[c + 1][J], vt[c + 1][J + 1], pp[hd][c], po[hd][c]);
    if (ph == 2) mma1688(d, vt[c][J], vt[c][J + 1], pp[hd][c]);
    if (n == 3) {
      yield_slot();
      if (tq == 0 && lane == 0) mbar_arrive(sb + kBarResume + att * 8);
    }
  }
  yield_slot();
  if (tq == 1 && lane == 0) mbar_arrive(sb + kBarResume + att * 8);
  TRACE_AT(tile, 11);
  UNITS stsm4_t(orow + c * 1024 + ((ochunk ^ (4 * hd)) << 4), pack2(o[hd][c][0][0], o[hd][c][0][1]),
                pack2(o[hd][c][0][2], o[hd][c][0][3]), pack2(o[hd][c][1][0], o[hd][c][1][1]),
                pack2(o[hd][c][1][2], o[hd][c][1][3]));
#undef UNITS
#undef AWAIT_HALO
#undef LOAD_HALO
  fence_async_smem();
  __syncwarp();
  TRACE_AT(tile, 12);
  if (elect()) {
    bulk_store(g_o + (b * 16 + hp) * kTileBytes + w * 4096, stg, 4096);
    bulk_commit();
    bulk_wait();
    TRACE_AT(tile, 13);
    mbar_arrive(sb + kBarEpi + tile * 8);
  }
  __syncwarp();
}

__device__ __forceinline__ void gather_stats(uint8_t* sm, const uint2* stat, int r, unsigned epoch) {
  uint2 a[8];
#pragma unroll 1
  for (unsigned spins = 0;; spins++) {
    unsigned diff = 0;
#pragma unroll
    for (int i = 0; i < 8; i++) {
      a[i] = ld_relaxed2(stat + i * 128 + r);
      diff |= (a[i].x ^ epoch) | (a[i].y ^ epoch);
    }
    if (__all_sync(0xffffffffu, (diff & 7u) == 0)) break;
    if (spins > kSpinLimit) __trap();
  }
  float s = 0.f, q = 0.f;
#pragma unroll
  for (int i = 0; i < 8; i++) {
    s += untag_value(a[i].x);
    q += untag_value(a[i].y);
  }
  const float mean = s * (1.f / 1024.f);
  const float var = fmaxf(fmaf(-mean, mean, q * (1.f / 1024.f)), 0.f);
  reinterpret_cast<float2*>(sm + kSmStat)[r] = make_float2(rsqrtf(var + 1e-5f), -mean);
}

__device__ __forceinline__ void gather_colsums_qkv(uint8_t* sm, int tq, int j, int lane, unsigned epoch) {
  const uint2* src = reinterpret_cast<const uint2*>(g_cs + (j + 8 * tq) * 64) + lane;
  uint2 v[3], u[3];
  for (unsigned spins = 0;; spins++) {
    unsigned diff = 0;
#pragma unroll
    for (int q = 0; q < 3; q++) {
      v[q] = ld_relaxed2(src + q * (kD / 2));
      u[q] = make_uint2(epoch & 7u, epoch & 7u);
      if (tq) u[q] = ld_relaxed2(src + (q * kD + 3 * kD + kF) / 2);
    }
#pragma unroll
    for (int q = 0; q < 3; q++) diff |= (v[q].x ^ epoch) | (v[q].y ^ epoch) | (u[q].x ^ epoch) | (u[q].y ^ epoch);
    if (__all_sync(0xffffffffu, (diff & 7u) == 0)) break;
    if (spins > kSpinLimit) __trap();
  }
#pragma unroll
  for (int q = 0; q < 3; q++)
    reinterpret_cast<float2*>(sm + kSmCsQ)[tq * 96 + q * 32 + lane] =
        make_float2(untag_value(v[q].x) + untag_value(u[q].x), untag_value(v[q].y) + untag_value(u[q].y));
}

__device__ __forceinline__ void gather_colsums_w1(uint8_t* sm, const __nv_bfloat16* b1, int j, int lane,
                                                  unsigned epoch) {
#pragma unroll 1
  for (int blk = 0; blk < 7; blk++) {
    const int pair = 32 * (blk + (blk < 3 ? 3 * j : blk < 5 ? 21 + 2 * j : 35 + 2 * j)) + lane;
    const uint32_t bias = reinterpret_cast<const uint32_t*>(b1)[pair];
    uint2 v;
    for (unsigned spins = 0;; spins++) {
      v = ld_relaxed2(reinterpret_cast<const uint2*>(g_cs + 3 * kD) + pair);
      if (__all_sync(0xffffffffu, (((v.x ^ epoch) | (v.y ^ epoch)) & 7u) == 0)) break;
      if (spins > kSpinLimit) __trap();
    }
    reinterpret_cast<float4*>(sm + kSmV1)[blk * 32 + lane] =
        make_float4(untag_value(v.x), untag_value(v.y), kGeluBeta * bf_lo(bias), kGeluBeta * bf_hi(bias));
  }
}

#define PAUSE_QKV2 7
#define PAUSE_WO 2

__global__ void __cluster_dims__(2, 1, 1) __launch_bounds__(384, 1)
fused_layers_kernel(const __grid_constant__ CUtensorMap map_x, const __grid_constant__ CUtensorMap map_out,
                    const __grid_constant__ CUtensorMap map_qkv, const __grid_constant__ CUtensorMap map_wo,
                    const __grid_constant__ CUtensorMap map_w1a, const __grid_constant__ CUtensorMap map_w1b,
                    const __grid_constant__ CUtensorMap map_w2, const __grid_constant__ CUtensorMap map_csq,
                    const __grid_constant__ CUtensorMap map_cs1, const __grid_constant__ CUtensorMap map_css,
                    const __grid_constant__ Params prm) {
  extern __shared__ __align__(1024) uint8_t sm[];
  if (threadIdx.x < 128 && blockIdx.x < kCtas) TRACE_AT(15, 1);
  const uint32_t sb = __shfl_sync(0xffffffffu, smem_u32(sm), 0);
  const int warp = __shfl_sync(0xffffffffu, threadIdx.x >> 5, 0), lane = threadIdx.x & 31;
  const int cta = blockIdx.x, rank = cta & 1, cl = cta >> 1;
  const int grp = cl < 4 ? 0 : cl < 36 ? (cl - 4) & 7 : 1 + (cl - 36) % 7;
  const int j = cl < 4 ? 4 + cl : cl < 36 ? (cl - 4) >> 3 : 4 + (cl - 36) / 7;
  const int b = 2 * grp + rank;
  const int xcol = (b >> 3) * kD, xrow = (b & 7) * 128;

  if (cta >= kCtas) {
    helper_cta(&map_csq, &map_cs1, sm, sb, cta - kCtas, warp);
    return;
  }
  if ((warp < 8 || warp == 9) && elect()) {
    if (warp == 9) {
#pragma unroll
      for (int s = 0; s < 8; s++) mbar_init(sb + kBarFull + s * 8, 1);
      fence_async_smem();
#pragma unroll 1
      for (int s = 0; s < 4; s++) {
        const uint32_t full = sb + kBarFull + s * 8, dst = sb + kSmRing + s * 40960;
        mbar_expect_tx(full, 40960);
        tma2d(dst, &map_x, full, xcol + (s & 1) * 64, xrow);
        tma3d(dst + kTileBytes, &map_qkv, full, (j + 4 * (s & 2)) * 64, (s & 1) * 64, 0);
        tma3d(dst + kTileBytes + 12288, &map_qkv, full, (j + 4 * (s & 2)) * 64, (s & 1) * 64 + 32, 0);
      }
    } else {
      if (sb & 1023) __trap();
#pragma unroll
      for (int s = 0; s < 16; s++) mbar_init(sb + kBarTurn + warp * 128 + s * 8, warp < 5 ? 1 : warp == 5 ? 2 : 4);
    }
    asm volatile("fence.mbarrier_init.release.cluster;" ::: "memory");
  }
  __syncwarp();
  asm volatile("barrier.cluster.arrive.relaxed.aligned;" ::: "memory");

  if (warp >= 8) {
    asm volatile("setmaxnreg.dec.sync.aligned.u32 40;");
    if (warp < 10) {
      asm volatile("barrier.cluster.wait.aligned;" ::: "memory");
      uint32_t nb = 32, off = 0, kb = 0;
#define RING_STEP(WAIT, ISSUE)                                            \
  do {                                                                    \
    const uint32_t mb = nb - depth, full = sb + kBarFull + (nb & 56);     \
    if (kb == skip) kb += inc;                                            \
    mbar_wait(sb + kBarEmpty + (mb & 56), mb >> 6);                       \
    WAIT;                                                                 \
    if (elect()) { ISSUE; }                                               \
    TRACE_ISSUE(9 - warp, nb);                                            \
    kb += inc;                                                            \
    off = off == wrap ? 0 : off + step;                                   \
    nb += 8;                                                              \
  } while (nb != nend)
#pragma unroll 1
      for (int sg = 0; sg < kSegs; sg++) {
        const uint32_t e = prm.seg[sg];
        const int ty = e & 7, mode = (e >> 15) & 3, reset = (e >> 24) & 3;
        const uint32_t nend = nb + (e & 0x1f8);
        const uint32_t step = (e >> 17) & 1 ? 40960 : 32768, wrap = 163840 - step;
        const uint32_t depth = (e >> 18) & 1 ? 40 : 32;
        if (reset) off = reset == 1 ? 0 : reset == 2 ? 40960 : 131072;
        const uint32_t own = ty == 2 ? 8 + j : 2 * j;
        if (mode != kModeContinue) kb = mode == kModeHead ? own : (e >> 9) & 63;
        const uint32_t inc = mode >= kModeSkip && ty != 2 ? 2 : 1, skip = mode >= kModeSkip ? own + (kb & 1) : 255;
        if (warp == 8) {
          const CUtensorMap* map = ty < 2 ? &map_qkv : ty == 2 ? &map_wo : ty == 3 ? &map_w1a : ty < 6 ? &map_w1b : &map_w2;
          const int c0 = ty < 2 ? (j + 8 * ty) * 64 : 0;
          const int c2 = ty < 2 ? 0 : ty == 3 ? 3 * j : ty == 4 ? 24 + 2 * j : ty == 5 ? 40 + 2 * j : 2 * j;
          const uint32_t half = (ty < 2 || ty == 3) ? 12288 : 8192;
          const uint32_t bytes = 2 * half + (mode == kModeHead ? 0 : kTileBytes);
          const uint32_t dst = sb + kSmRing + kTileBytes + rank * half;
          if (ty == 2 && mode == kModeHead) mbar_wait(sb + kBarEpi + ((e >> 19) & 31) * 8, 0);
#pragma unroll 1
          RING_STEP(, mbar_expect_tx(full, bytes); tma3d_mc(dst + off, map, full, c0, kb * 64 + rank * 32, c2));
        } else if (mode == kModeHead) {
          off += ((nend - nb) >> 3) * step;
          nb = nend;
          if (off >= 163840) off -= 163840;
        } else if (sg < 2) {
#pragma unroll 1
          RING_STEP(, tma2d(sb + kSmRing + off, &map_x, full, xcol + kb * 64, xrow));
        } else {
          const uint8_t* src = ty == 6 ? g_h + b * 56 * kTileBytes : (ty == 2 ? g_o : g_x) + b * 16 * kTileBytes;
          const int dep = (e >> 19) & 31;
          if (dep < 28) mbar_wait(sb + kBarReady + dep * 8, 0);
          if ((dep & 30) == 28) {
#pragma unroll 1
            RING_STEP(mbar_wait(sb + kBarSrc + ((kb << (4 - inc)) & 56), dep),
                      bulk_load(sb + kSmRing + off, src + kb * kTileBytes, kTileBytes, full));
          } else {
#pragma unroll 1
            RING_STEP(, bulk_load(sb + kSmRing + off, src + kb * kTileBytes, kTileBytes, full));
          }
        }
      }
#undef RING_STEP
    } else {
      unsigned epoch = 0;
      if (warp == 10) {
        if (lane == 0) epoch = atomicAdd(&g_ticket, 1u) / kGrid + 1;
        *reinterpret_cast<unsigned*>(sm + kSmEpoch) = __shfl_sync(0xffffffffu, epoch, 0);
        asm volatile("barrier.cluster.wait.aligned;" ::: "memory");
        if (elect()) mbar_arrive(sb + kBarEpoch);
      } else {
        asm volatile("barrier.cluster.wait.aligned;" ::: "memory");
        mbar_wait_bounded(sb + kBarFull, 0);
        if (elect()) {
          mbar_expect_tx(sb + kBarInit, 32768);
          tma2d(sb + kSmX, &map_x, sb + kBarInit, xcol + j * 128, xrow);
          tma2d(sb + kSmX + kTileBytes, &map_x, sb + kBarInit, xcol + j * 128 + 64, xrow);
        }
        const uint2 u = reinterpret_cast<const uint2*>(prm.b2)[32 * j + lane];
        reinterpret_cast<float4*>(sm + kSmB2)[lane] = make_float4(
            2.f * kGeluBeta * bf_lo(u.x), 2.f * kGeluBeta * bf_hi(u.x), 2.f * kGeluBeta * bf_lo(u.y), 2.f * kGeluBeta * bf_hi(u.y));
      }
      mbar_wait_bounded(sb + kBarEpoch, 0);
      epoch = *reinterpret_cast<volatile unsigned*>(sm + kSmEpoch);
      if (cta < 96) {
        mbar_wait_bounded(sb + kBarInit, 0);
        colsum_strip(&map_css, sm, sb, (cta >> 5) * kD + 512 + (cta & 31) * 16, warp - 10, lane, epoch);
      }
      gather_colsums_qkv(sm, 11 - warp, j, lane, epoch);
      __syncwarp();
      if (elect()) mbar_arrive(sb + kBarCs + (11 - warp) * 8);
     if (warp == 10) {
#pragma unroll 1
      for (int i = 0; i < kTiles - 1; i++) {
        const bool xt = i == 2 || i == 6 || i == 9;
        const unsigned* line = g_flag + (i * 16 + b) * 32;
        mbar_wait(sb + (xt ? kBarX + (i >> 2) * 16 : kBarEpi + i * 8), 0);
        if (xt || i == 1 || i == 8) {
          unsigned todo = 0xff, spins = 0;
          do {
            const unsigned now = __ballot_sync(0xffffffffu, ld_relaxed(line + (lane & 7)) == epoch) & todo;
            if (now) {
              asm volatile("fence.acquire.gpu;\nfence.proxy.async.global;" ::: "memory");
              if ((now >> lane) & 1) mbar_arrive(sb + kBarSrc + lane * 8);
              todo ^= now;
            }
            if (++spins > kSpinLimit) __trap();
          } while (todo);
        } else {
          wait_flags(line + (lane & 7), epoch);
          if (elect()) mbar_arrive(sb + kBarReady + i * 8);
        }
        if (xt) {
          wait_flags(line + 8 + (lane & 7), epoch);
          if (elect()) mbar_arrive(sb + kBarReady + (14 + (i >> 2)) * 8);
        }
      }
     } else {
#pragma unroll 1
      for (int i = 0; i < kTiles - 1; i++) {
        if (i == 3) {
          gather_colsums_w1(sm, prm.b1, j, lane, epoch);
          __syncwarp();
          if (elect()) mbar_arrive(sb + kBarCs + 16);
        }
        const bool xt = i == 2 || i == 6 || i == 9;
#pragma unroll 1
        for (int h = 0; h < (xt ? 2 : 1); h++) {
          mbar_wait_bounded(sb + (xt ? kBarX + (i >> 2) * 16 + 8 * h : kBarEpi + i * 8), 0);
          const int ty = i >= 7 ? i - 7 : i;
          if (ty >= 2 && elect()) {
            uint8_t* dst = xt ? g_x + (b * 16 + 2 * j + h) * kTileBytes
                              : g_h + (b * 56 + 1 + (ty == 3 ? 3 * j : 16 * ty - 40 + 2 * j)) * kTileBytes;
            const int piece = (xt && h == 0) ? kTileBytes : kTileBytes / 4;
#pragma unroll 1
            for (int o = 0; o < kTileBytes; o += piece) {
              bulk_store(dst + o, sb + (xt ? kSmX + h * kTileBytes : kSmStg) + o, piece);
              bulk_commit();
              bulk_wait();
            }
            if (!xt) mbar_arrive(sb + kBarFree + i * 8);
          }
          __syncwarp();
          if (elect()) st_release(&g_flag[(i * 16 + b) * 32 + h * 8 + j], epoch);
          __syncwarp();
        }
      }
#pragma unroll 1
      for (int h = 0; h < 2; h++) {
        mbar_wait_bounded(sb + kBarX + 48 + 8 * h, 0);
        if (elect()) {
          tma2d_store(&map_out, sb + kSmX + h * kTileBytes, xcol + j * 128 + h * 64, xrow);
          bulk_commit();
          if (h == 1) bulk_wait_read();
        }
      }
     }
    }
    __syncwarp();
    asm volatile("barrier.cluster.arrive.relaxed.aligned;\nbarrier.cluster.wait.aligned;" ::: "memory");
  } else {
    asm volatile("setmaxnreg.inc.sync.aligned.u32 232;");
    asm volatile("barrier.cluster.wait.aligned;" ::: "memory");
    const int wg = warp >> 2, w = warp & 3;
    const bool rel = (threadIdx.x & 95) == 0;
    const uint32_t rel_addr = mapa(sb + kBarEmpty, w & 1);
    if (wg == 1) TRACE_AT(15, 0);
#define EPOCH (*reinterpret_cast<volatile unsigned*>(sm + kSmEpoch))

#pragma unroll 1
    for (int i = wg; i < kTiles; i += 2) {
      const int layer = i >= 7, ty = i - 7 * layer;
      TRACE_AT(i, 15);
      float acc[2][96];
      if (ty == 2 || ty == 6) {
        const int lane = lane_id();
        const uint32_t xa = sb + kSmX + ((lane >> 4) * 8 + (lane & 7)) * 128 + (((2 * w + ((lane >> 3) & 1)) ^ (lane & 7)) << 4);
        const float up = ty == 6 ? 2.f * kGeluBeta : 1.f, dn = ty == 6 ? 0.5f / kGeluBeta : 1.f;
#pragma unroll
        for (int h = 0; h < 2; h++) {
          const float* b2 = reinterpret_cast<const float*>(sm + kSmB2) + 64 * h + 16 * w + (lane >> 2);
          const float bias[2] = {ty == 6 ? b2[0] : 0.f, ty == 6 ? b2[8] : 0.f};
#pragma unroll
          for (int p = 0; p < 8; p++) {
            uint32_t r[4];
            ldsm4_t(xa + h * kTileBytes + p * 2048, r);
#pragma unroll
            for (int m = 0; m < 4; m++) {
              acc[h][8 * p + 2 * m] = fmaf(bf_lo(r[m]), up, bias[m & 1]);
              acc[h][8 * p + 2 * m + 1] = fmaf(bf_hi(r[m]), up, bias[m & 1]);
              asm volatile("" : "+f"(acc[h][8 * p + 2 * m]), "+f"(acc[h][8 * p + 2 * m + 1]));
            }
            yield_slot();
          }
        }
        auto stage = [&](int qt) {
          const int h = qt >> 1;
#pragma unroll
          for (int p = 4 * (qt & 1); p < 4 * (qt & 1) + 4; p++) {
            const float* a = &acc[h][8 * p];
            stsm4_t(xa + h * kTileBytes + p * 2048, pack2(a[0] * dn, a[1] * dn), pack2(a[2] * dn, a[3] * dn),
                    pack2(a[4] * dn, a[5] * dn), pack2(a[6] * dn, a[7] * dn));
            yield_slot();
          }
          if (qt & 1) {
            fence_async_smem();
            __syncwarp();
            if (elect()) mbar_arrive(sb + kBarX + (i >> 2) * 16 + 8 * h);
            TRACE_AT(i, 8 + h);
          }
        };
        mainloop<128, kResid>(acc, sb, i, layer * 152 + ty * 16, ty == 6 ? 4 : 0, ty == 6 ? 56 : 16,
                            ty == 2 ? PAUSE_WO : -1, 2 * layer + 1, rel_addr, rel, ty == 2 ? 8 : -1, stage);
        TRACE_AT(i, 2);
        stage(2);
        stage(3);
      } else {
        const int xver = 2 * layer + (ty >= 3);
        const uint32_t stg = sb + kSmStg + w * 4096;
        const float4* vec = reinterpret_cast<const float4*>(sm + kSmV1) + (ty == 3 ? 0 : 64 * ty - 160);
        int lane;
        uint8_t* hdst = g_h + (b * 56 + (ty == 3 ? 3 * j : 16 * ty - 40 + 2 * j)) * kTileBytes + w * 4096;
        float2 st[4];
        unsigned epoch;
        auto pre = [&] {
          lane = lane_id();
          if (ty < 4) mbar_wait(sb + (ty == 1 ? kBarEpi + (i - 1) * 8 : kBarStat + xver * 8), 0);
#pragma unroll
          for (int c = 0; c < 4; c++) st[c] = reinterpret_cast<const float2*>(sm + kSmStat)[32 * w + 8 * c + (lane >> 2)];
          epoch = EPOCH;
        };
        auto team_stats = [&] {
          uint2* stat = g_stat + (xver * 16 + b) * 1024;
          lane = lane_id();
          publish_stats(sb, stat + j * 128, w, lane, EPOCH);
          gather_stats(sm, stat, 32 * w + lane, EPOCH);
          __syncwarp();
          if (elect()) mbar_arrive(sb + kBarStat + xver * 8);
          TRACE_AT(i, 14);
        };
        if (ty < 4) {
          AttnRegs ar;
          auto odd = [&](int step) {
            if (step == 0) pre();
            else convert_odd(acc, st, ar, step, sm, sb + kBarHalo + (xver + ty) * 24,
                             g_halo + ((layer * 16 + b) * 16 + j + 8 * ty) * 256, (b & 7) != 7, epoch, w, lane);
          };
          head_blocks<192>(acc, sb, layer * 152 + (ty < 2 ? 2 * ty : 48), ty < 2 ? 2 * ty : 1, xver, rel_addr, rel);
          if (ty == 1) {
            if (i == 1) {
              mbar_wait(sb + kBarEpoch, 0);
              mbar_wait(sb + kBarInit, 0);
            }
            team_stats();
            epoch = 0;
#pragma unroll
            for (int c = 0; c < 4; c++) st[c] = reinterpret_cast<const float2*>(sm + kSmStat)[32 * w + 8 * c + (lane >> 2)];
          } else {
            mainloop<192, kPlain>(acc, sb, i, layer * 152 + (ty ? 52 : 4), ty ? 1 : 0, 14, -1, 0, rel_addr, rel, 0, pre);
            TRACE_AT(i, 2);
            if (ty == 3) goto wide_gelu;
          }
          if (layer == 0) mbar_wait(sb + kBarCs + ty * 8, 0);
          add_mean_term(acc, st, sm, ty, lane);
          if (ty == 1) {
            mainloop<192, kStagger>(acc, sb, i, layer * 152 + 18, 2, 14, PAUSE_QKV2, xver, rel_addr, rel, 0, odd);
            TRACE_AT(i, 2);
          } else {
            odd(1);
            odd(2);
            odd(3);
          }
          epilogue_attn(acc, st, ar, sm, sb, layer, ty, b, j, epoch, i, w, lane);
          TRACE_AT(i, 3);
          continue;
        wide_gelu:
          if (i == 3) mbar_wait(sb + kBarCs + 16, 0);
          scale_stats(st);
          fold_norm<16, 24>(acc, st, vec + (lane & 3));
          TRACE_AT(i, 11);
          gelu_chunk<2>(acc, stg, lane, nullptr, [] {});
          TRACE_AT(i, 12);
          fold_norm<0, 2>(acc, st, vec + (lane & 3));
          store_staged(hdst + 2 * kTileBytes, stg);
          fold_norm<2, 16>(acc, st, vec + (lane & 3));
        } else {
          if (ty == 4) {
            head_blocks<128>(acc, sb, layer * 152 + 50, 3, xver, rel_addr, rel);
            team_stats();
            mainloop<128, kPlain>(acc, sb, i, layer * 152 + 66, 4, 14, -1, 0, rel_addr, rel, 0, pre);
          } else {
            mainloop<128, kFresh>(acc, sb, i, layer * 152 + 80, 3, 16, -1, 0, rel_addr, rel, 0, pre);
          }
          TRACE_AT(i, 2);
          if (i == 4) mbar_wait(sb + kBarCs + 16, 0);
          scale_stats(st);
          fold_norm<0, 16>(acc, st, vec + (lane & 3));
        }
        auto own_store_done = [] {
          if (elect()) bulk_wait();
          __syncwarp();
        };
        TRACE_AT(i, 8);
        gelu_chunk<0>(acc, stg, lane, nullptr, [&] {
          if (ty == 3) own_store_done();
          else mbar_wait(sb + kBarFree + (i - 1) * 8, 0);
        });
        TRACE_AT(i, 9);
        gelu_chunk<1>(acc, stg, lane, hdst, own_store_done);
        TRACE_AT(i, 10);
        fence_async_smem();
        __syncwarp();
        if (elect()) mbar_arrive(sb + kBarEpi + i * 8);
      }
      TRACE_AT(i, 3);
    }
#undef EPOCH
    asm volatile("barrier.cluster.arrive.relaxed.aligned;\nbarrier.cluster.wait.aligned;" ::: "memory");
    if (wg == 1) TRACE_AT(15, 2);
  }
}

void build_segments(uint32_t* seg) {
  int n = 0, fine = 0;
  auto per_source = [&] { return 28 + (fine++ & 1); };
  auto add = [&](int ty, int cnt, int kb0, int mode, int wide, int depth5, int dep, int reset) {
    seg[n++] = ty | cnt << 3 | kb0 << 9 | mode << 15 | wide << 17 | depth5 << 18 | dep << 19 | reset << 24;
  };
  for (int l = 0; l < 2; l++) {
    const int t = 7 * l;
    if (l == 0) {
      add(0, 14, 2, kModePlain, 1, 0, 31, 1);
      add(1, 14, 2, kModePlain, 1, 0, 31, 0);
    } else {
      add(0, 2, 0, kModeHead, 1, 0, 31, 1);
      add(1, 2, 0, kModeHead, 1, 0, 31, 0);
      add(0, 7, 0, kModeSkip, 1, 0, per_source(), 0);
      add(0, 7, 1, kModeSkip, 1, 0, 15, 0);
      add(1, 7, 0, kModeSkip, 1, 0, 31, 0);
      add(1, 7, 1, kModeSkip, 1, 0, 31, 0);
    }
    add(2, 4, 0, kModePlain, 0, 0, t, 1);
    add(2, 4, 4, kModePlain, 0, 1, 31, 0);
    add(2, 1, 0, kModeHead, 0, 1, t + 1, 0);
    add(2, 7, 8, kModeSkip, 0, 1, per_source(), 0);
    add(3, 2, 0, kModeHead, 1, 0, 31, 2);
    add(4, 2, 0, kModeHead, 1, 0, 31, 0);
    add(3, 7, 0, kModeSkip, 1, 0, per_source(), 0);
    add(3, 7, 1, kModeSkip, 1, 0, 14 + 2 * l, 0);
    add(4, 4, 0, kModeSkip, 0, 0, 31, 3);
    add(4, 3, 0, kModeContinue, 0, 1, 31, 0);
    add(4, 7, 1, kModeSkip, 0, 1, 31, 0);
    add(5, 16, 0, kModePlain, 0, 1, 31, 0);
    add(6, 24, 0, kModePlain, 0, 1, t + 3, 0);
    add(6, 16, 24, kModePlain, 0, 1, t + 4, 0);
    add(6, 16, 40, kModePlain, 0, 1, t + 5, 0);
  }
}

typedef CUresult (*EncodeTiledFn)(CUtensorMap*, CUtensorMapDataType, cuuint32_t, void*, const cuuint64_t*,
                                  const cuuint64_t*, const cuuint32_t*, const cuuint32_t*, CUtensorMapInterleave,
                                  CUtensorMapSwizzle, CUtensorMapL2promotion, CUtensorMapFloatOOBfill);

CUtensorMap make_map(EncodeTiledFn enc, const void* p, int rank, const cuuint64_t* dims, const cuuint64_t* strides,
                     const cuuint32_t* box, CUtensorMapSwizzle swizzle = CU_TENSOR_MAP_SWIZZLE_128B,
                     CUtensorMapL2promotion promo = CU_TENSOR_MAP_L2_PROMOTION_L2_128B) {
  CUtensorMap m;
  const cuuint32_t es[5] = {1, 1, 1, 1, 1};
  enc(&m, CU_TENSOR_MAP_DATA_TYPE_BFLOAT16, rank, const_cast<void*>(p), dims, strides, box, es,
      CU_TENSOR_MAP_INTERLEAVE_NONE, swizzle, promo,
      CU_TENSOR_MAP_FLOAT_OOB_FILL_NONE);
  return m;
}

CUtensorMap weight_map(EncodeTiledFn enc, const void* p, int k, int n, int blocks) {
  const cuuint64_t dims[3] = {64, (cuuint64_t)k, (cuuint64_t)n / 64};
  const cuuint64_t strides[2] = {(cuuint64_t)n * 2, 128};
  const cuuint32_t box[3] = {64, 32, (cuuint32_t)blocks};
  return make_map(enc, p, 3, dims, strides, box, CU_TENSOR_MAP_SWIZZLE_128B, CU_TENSOR_MAP_L2_PROMOTION_L2_256B);
}

CUtensorMap slab_map(EncodeTiledFn enc, const void* p, int n, int cols, int rows) {
  const cuuint64_t dims[2] = {(cuuint64_t)n, kD};
  const cuuint64_t strides[1] = {(cuuint64_t)n * 2};
  const cuuint32_t box[2] = {(cuuint32_t)cols, (cuuint32_t)rows};
  return make_map(enc, p, 2, dims, strides, box, CU_TENSOR_MAP_SWIZZLE_NONE);
}

CUtensorMap token_map(EncodeTiledFn enc, const void* p, int rows) {
  const cuuint64_t dims[2] = {2 * kD, 1024};
  const cuuint64_t strides[1] = {4 * kD};
  const cuuint32_t box[2] = {64, (cuuint32_t)rows};
  return make_map(enc, p, 2, dims, strides, box);
}

}

extern "C" void kernel_launch(void* const* d_in, const int* in_sizes, int n_in, void* d_out, int out_size) {
  (void)in_sizes; (void)n_in; (void)out_size;
  static EncodeTiledFn enc = nullptr;
  if (!enc) {
    void* fn = nullptr;
    cudaDriverEntryPointQueryResult q;
    cudaGetDriverEntryPoint("cuTensorMapEncodeTiled", &fn, cudaEnableDefault, &q);
    enc = (EncodeTiledFn)fn;
    cudaFuncSetAttribute(fused_layers_kernel, cudaFuncAttributeMaxDynamicSharedMemorySize, kSmBytes);
  }
  Params prm;
  prm.b1 = (const __nv_bfloat16*)d_in[5];
  prm.b2 = (const __nv_bfloat16*)d_in[7];
  build_segments(prm.seg);
  const cuuint64_t qd[3] = {kD, kD, 3}, qs[2] = {3 * kD * 2, kD * 2};
  const cuuint32_t qb[3] = {64, 32, 3};
  const CUtensorMap map_x = token_map(enc, d_in[0], 128);
  const CUtensorMap map_out = token_map(enc, d_out, 128);
  const CUtensorMap map_qkv = make_map(enc, d_in[1], 3, qd, qs, qb);
  const CUtensorMap map_wo = weight_map(enc, d_in[2], kD, kD, 2);
  const CUtensorMap map_w1a = weight_map(enc, d_in[4], kD, kF, 3);
  const CUtensorMap map_w1b = weight_map(enc, d_in[4], kD, kF, 2);
  const CUtensorMap map_w2 = weight_map(enc, d_in[6], kF, kD, 2);
  fused_layers_kernel<<<kGrid, 384, kSmBytes>>>(map_x, map_out, map_qkv, map_wo, map_w1a, map_w1b, map_w2,
                                                slab_map(enc, d_in[1], 3 * kD, 128, 128), slab_map(enc, d_in[4], kF, 128, 128),
                                                slab_map(enc, d_in[1], 3 * kD, 16, 128), prm);
}
```

```cpp
#include <cuda.h>
#include <cuda_bf16.h>
#include <cuda_runtime.h>
#include <stdint.h>

namespace {

constexpr int kD = 1024;
constexpr int kF = 3584;
constexpr int kCtas = 128;
constexpr int kGrid = 132;
constexpr int kTiles = 14;
constexpr int kTileBytes = 16384;

constexpr int kSmRing = 0;
constexpr int kSmX = 163840;
constexpr int kSmStg = kSmX + 32768;
constexpr int kSmHalo = kSmStg + 16384;
constexpr int kSmCsQ = kSmHalo + 6144;
constexpr int kSmV1 = kSmCsQ + 384 * 4;
constexpr int kSmB2 = kSmV1 + 448 * 8;
constexpr int kSmStat = kSmB2 + 128 * 4;
constexpr int kSmBar = kSmStat + 128 * 8;
constexpr int kBarFull = kSmBar;
constexpr int kBarTurn = kBarFull + 8 * 8;
constexpr int kBarReady = kBarTurn + 14 * 8;
constexpr int kBarSrc = kBarReady + 17 * 8;
constexpr int kBarPause = kBarSrc + 8 * 8;
constexpr int kBarFree = kBarPause + 4 * 8;
constexpr int kBarCs = kBarFree + 14 * 8;
constexpr int kBarSlab = kBarCs + 3 * 8;
constexpr int kBarHalo = kBarSlab + 4 * 8;
constexpr int kBarInit = kBarHalo + 12 * 8;
constexpr int kBarEpoch = kBarInit + 8;
constexpr int kBarEmpty = kBarTurn + 5 * 128;
constexpr int kBarEpi = kBarEmpty + 128;
constexpr int kBarX = kBarEpi + 14 * 8;
constexpr int kBarStat = kBarX + 8 * 8;
constexpr int kBarResume = kBarStat + 4 * 8;
constexpr int kSmEpoch = kBarEpi + 2 * 128;
static_assert(kBarEpoch < kBarEmpty && kBarResume + 4 * 8 <= kSmEpoch, "barrier groups overflow");
constexpr int kSmBytes = kSmEpoch + 16 + 256;
constexpr int kSegs = 38;

constexpr int kFlagLines = kTiles * 16;

constexpr float kXScale = 1.f / 16.f;

constexpr unsigned kSpinLimit = 1u << 22;

__device__ __align__(1024) uint8_t g_x[16 * 16 * kTileBytes];
__device__ __align__(1024) uint8_t g_o[16 * 16 * kTileBytes];
__device__ __align__(1024) uint8_t g_h[16 * 56 * kTileBytes];
__device__ __align__(128) uint2 g_stat[4 * 16 * 128 * 8];
__device__ __align__(128) unsigned g_cs[3 * kD + kF + 3 * kD];
__device__ __align__(128) uint4 g_halo[2 * 16 * 16 * 256];
__device__ __align__(128) unsigned g_flag[kFlagLines * 32];
__device__ unsigned g_ticket;

#define TRACE_AT(tile, k)
#define TRACE_PUB(i, k, c)
#define TRACE_ISSUE(which, nb)

struct Params {
  const __nv_bfloat16* b1;
  const __nv_bfloat16* b2;
  uint32_t seg[kSegs];
};

__device__ __forceinline__ uint32_t smem_u32(const void* p) {
  return (uint32_t)__cvta_generic_to_shared(p);
}
__device__ __forceinline__ uint32_t mapa(uint32_t a, uint32_t cta) {
  uint32_t r;
  asm("mapa.shared::cluster.u32 %0, %1, %2;" : "=r"(r) : "r"(a), "r"(cta));
  return r;
}
__device__ __forceinline__ void mbar_init(uint32_t bar, int cnt) {
  asm volatile("mbarrier.init.shared::cta.b64 [%0], %1;" ::"r"(bar), "r"(cnt) : "memory");
}
__device__ __forceinline__ void mbar_expect_tx(uint32_t bar, uint32_t bytes) {
  asm volatile("mbarrier.arrive.expect_tx.shared::cta.b64 _, [%0], %1;" ::"r"(bar), "r"(bytes) : "memory");
}
__device__ __forceinline__ void mbar_arrive(uint32_t bar) {
  asm volatile("mbarrier.arrive.shared::cta.b64 _, [%0];" ::"r"(bar) : "memory");
}
__device__ __forceinline__ void mbar_arrive_cluster(uint32_t cluster_addr) {
  asm volatile("mbarrier.arrive.shared::cluster.b64 _, [%0];" ::"r"(cluster_addr) : "memory");
}
__device__ __forceinline__ void mbar_wait(uint32_t bar, uint32_t parity) {
  asm volatile("{\n.reg .pred p;\nRETRY:\nmbarrier.try_wait.parity.shared::cta.b64 p, [%0], %1;\n"
               "@!p bra.uni RETRY;\n}" ::"r"(bar), "r"(parity) : "memory");
}
__device__ __forceinline__ void mbar_wait_bounded(uint32_t bar, uint32_t parity) {
  asm volatile("{\n.reg .pred p;\n.reg .u32 c;\nmov.u32 c, 0;\nRETRY:\n"
               "mbarrier.try_wait.parity.shared::cta.b64 p, [%0], %1;\n@p bra.uni DONE;\n"
               "add.u32 c, c, 1;\nsetp.lt.u32 p, c, %2;\n@p bra.uni RETRY;\ntrap;\nDONE:\n}"
               ::"r"(bar), "r"(parity), "n"(1u << 19) : "memory");
}
__device__ __forceinline__ void tma3d(uint32_t dst, const CUtensorMap* m, uint32_t bar, int c0, int c1, int c2) {
  asm volatile(
      "cp.async.bulk.tensor.3d.shared::cluster.global.mbarrier::complete_tx::bytes [%0], [%1, {%3, %4, %5}], [%2];"
      ::"r"(dst), "l"(m), "r"(bar), "r"(c0), "r"(c1), "r"(c2) : "memory");
}
__device__ __forceinline__ void tma3d_mc(uint32_t dst, const CUtensorMap* m, uint32_t bar, int c0, int c1, int c2) {
  asm volatile(
      "cp.async.bulk.tensor.3d.shared::cluster.global.mbarrier::complete_tx::bytes.multicast::cluster"
      " [%0], [%1, {%3, %4, %5}], [%2], %6;"
      ::"r"(dst), "l"(m), "r"(bar), "r"(c0), "r"(c1), "r"(c2), "h"((uint16_t)3) : "memory");
}
__device__ __forceinline__ void tma2d(uint32_t dst, const CUtensorMap* m, uint32_t bar, int c0, int c1) {
  asm volatile(
      "cp.async.bulk.tensor.2d.shared::cluster.global.mbarrier::complete_tx::bytes [%0], [%1, {%3, %4}], [%2];"
      ::"r"(dst), "l"(m), "r"(bar), "r"(c0), "r"(c1) : "memory");
}
__device__ __forceinline__ void tma2d_store(const CUtensorMap* m, uint32_t src, int c0, int c1) {
  asm volatile("cp.async.bulk.tensor.2d.global.shared::cta.bulk_group [%0, {%2, %3}], [%1];"
               ::"l"(m), "r"(src), "r"(c0), "r"(c1) : "memory");
}
__device__ __forceinline__ int lane_id() {
  int l;
  asm volatile("mov.u32 %0, %%laneid;" : "=r"(l));
  return l;
}
__device__ __forceinline__ bool elect() {
  uint32_t p;
  asm volatile("{\n.reg .pred p;\nelect.sync _|p, 0xffffffff;\nselp.b32 %0, 1, 0, p;\n}" : "=r"(p));
  return p;
}
__device__ __forceinline__ void bulk_load(uint32_t dst, const void* src, uint32_t bytes, uint32_t bar) {
  asm volatile("cp.async.bulk.shared::cluster.global.mbarrier::complete_tx::bytes [%0], [%1], %2, [%3];"
               ::"r"(dst), "l"(src), "r"(bytes), "r"(bar) : "memory");
}
__device__ __forceinline__ void bulk_store(void* dst, uint32_t src, uint32_t bytes) {
  asm volatile("cp.async.bulk.global.shared::cta.bulk_group [%0], [%1], %2;" ::"l"(dst), "r"(src), "r"(bytes)
               : "memory");
}
__device__ __forceinline__ void bulk_commit() { asm volatile("cp.async.bulk.commit_group;" ::: "memory"); }
__device__ __forceinline__ void bulk_wait_read() { asm volatile("cp.async.bulk.wait_group.read 0;" ::: "memory"); }
__device__ __forceinline__ void bulk_wait() { asm volatile("cp.async.bulk.wait_group 0;" ::: "memory"); }
__device__ __forceinline__ void fence_async_smem() { asm volatile("fence.proxy.async.shared::cta;" ::: "memory"); }
__device__ __forceinline__ unsigned ld_relaxed(const unsigned* p) {
  unsigned v;
  asm volatile("ld.relaxed.gpu.global.u32 %0, [%1];" : "=r"(v) : "l"(p) : "memory");
  return v;
}
__device__ __forceinline__ uint2 ld_relaxed2(const uint2* p) {
  uint2 v;
  asm volatile("ld.relaxed.gpu.global.v2.u32 {%0, %1}, [%2];" : "=r"(v.x), "=r"(v.y) : "l"(p) : "memory");
  return v;
}
__device__ __forceinline__ void st_relaxed(unsigned* p, unsigned v) {
  asm volatile("st.relaxed.gpu.global.u32 [%0], %1;" ::"l"(p), "r"(v) : "memory");
}
__device__ __forceinline__ void st_release(unsigned* p, unsigned v) {
  asm volatile("st.release.gpu.global.u32 [%0], %1;" ::"l"(p), "r"(v) : "memory");
}
__device__ __forceinline__ void wait_flags(const unsigned* p, unsigned epoch) {
  unsigned spins = 0;
  while (true) {
    const unsigned v = ld_relaxed(p);
    if (__all_sync(0xffffffffu, v == epoch)) break;
    if (++spins > kSpinLimit) __trap();
  }
  asm volatile("fence.acquire.gpu;\nfence.proxy.async.global;" ::: "memory");
  __syncwarp();
}
__device__ __forceinline__ void st_packet(uint4* p, uint32_t d0, uint32_t d1, uint32_t tag) {
  asm volatile("{\n.reg .b128 v;\n.reg .b64 x, y;\nmov.b64 x, {%1, %2};\nmov.b64 y, {%3, %3};\nmov.b128 v, {x, y};\n"
               "st.relaxed.gpu.global.b128 [%0], v;\n}" ::"l"(p), "r"(d0), "r"(d1), "r"(tag) : "memory");
}
__device__ __forceinline__ void ld_packet(const uint4* p, uint32_t& d0, uint32_t& d1, uint32_t& tag) {
  asm volatile("{\n.reg .b128 v;\n.reg .b64 x, y;\n.reg .b32 u;\nld.relaxed.gpu.global.b128 v, [%3];\n"
               "mov.b128 {x, y}, v;\nmov.b64 {%0, %1}, x;\nmov.b64 {%2, u}, y;\n}"
               : "=r"(d0), "=r"(d1), "=r"(tag) : "l"(p) : "memory");
}
__device__ __forceinline__ unsigned tag_value(float v, unsigned epoch) {
  return (__float_as_uint(v) & ~7u) | (epoch & 7u);
}
__device__ __forceinline__ float untag_value(unsigned v) { return __uint_as_float(v & ~7u); }
__device__ __forceinline__ void stsm4(uint32_t a, uint32_t r0, uint32_t r1, uint32_t r2, uint32_t r3) {
  asm volatile("stmatrix.sync.aligned.m8n8.x4.shared.b16 [%0], {%1, %2, %3, %4};" ::"r"(a), "r"(r0), "r"(r1),
               "r"(r2), "r"(r3) : "memory");
}
__device__ __forceinline__ void stsm4_t(uint32_t a, uint32_t r0, uint32_t r1, uint32_t r2, uint32_t r3) {
  asm volatile("stmatrix.sync.aligned.m8n8.x4.trans.shared.b16 [%0], {%1, %2, %3, %4};" ::"r"(a), "r"(r0),
               "r"(r1), "r"(r2), "r"(r3) : "memory");
}
__device__ __forceinline__ uint32_t transpose8(uint32_t a) {
  uint32_t d;
  asm volatile("movmatrix.sync.aligned.m8n8.trans.b16 %0, %1;" : "=r"(d) : "r"(a));
  return d;
}
__device__ __forceinline__ void mma16816(float (&c)[4], uint32_t a0, uint32_t a1, uint32_t a2, uint32_t a3,
                                         uint32_t b0, uint32_t b1) {
  asm volatile("mma.sync.aligned.m16n8k16.row.col.f32.bf16.bf16.f32 {%0, %1, %2, %3}, {%4, %5, %6, %7}, {%8, %9}, "
               "{%0, %1, %2, %3};"
               : "+f"(c[0]), "+f"(c[1]), "+f"(c[2]), "+f"(c[3])
               : "r"(a0), "r"(a1), "r"(a2), "r"(a3), "r"(b0), "r"(b1));
}
__device__ __forceinline__ void mma1688(float (&c)[4], uint32_t a0, uint32_t a1, uint32_t b0) {
  asm volatile("mma.sync.aligned.m16n8k8.row.col.f32.bf16.bf16.f32 {%0, %1, %2, %3}, {%4, %5}, {%6}, {%0, %1, %2, %3};"
               : "+f"(c[0]), "+f"(c[1]), "+f"(c[2]), "+f"(c[3]) : "r"(a0), "r"(a1), "r"(b0));
}
__device__ __forceinline__ float shfl_xor(float v, int m) {
  float r;
  asm volatile("shfl.sync.bfly.b32 %0, %1, %2, 31, 0xffffffff;" : "=f"(r) : "f"(v), "r"(m));
  return r;
}
__device__ __forceinline__ float tanh_fast(float x) {
  float r;
  asm volatile("tanh.approx.f32 %0, %1;" : "=f"(r) : "f"(x));
  return r;
}
__device__ __forceinline__ void ldsm4(uint32_t a, uint32_t (&r)[4]) {
  asm volatile("ldmatrix.sync.aligned.m8n8.x4.shared.b16 {%0, %1, %2, %3}, [%4];"
               : "=r"(r[0]), "=r"(r[1]), "=r"(r[2]), "=r"(r[3]) : "r"(a) : "memory");
}
__device__ __forceinline__ void ldsm4_t(uint32_t a, uint32_t (&r)[4]) {
  asm volatile("ldmatrix.sync.aligned.m8n8.x4.trans.shared.b16 {%0, %1, %2, %3}, [%4];"
               : "=r"(r[0]), "=r"(r[1]), "=r"(r[2]), "=r"(r[3]) : "r"(a) : "memory");
}
__device__ __forceinline__ uint32_t pack2(float lo, float hi) {
  uint32_t r;
  asm volatile("cvt.rn.bf16x2.f32 %0, %1, %2;" : "=r"(r) : "f"(hi), "f"(lo));
  return r;
}
__device__ __forceinline__ float bf_lo(uint32_t r) { return __uint_as_float(r << 16); }
__device__ __forceinline__ float bf_hi(uint32_t r) { return __uint_as_float(r & 0xffff0000u); }
__device__ __forceinline__ float ex2(float x) {
  float r;
  asm("ex2.approx.ftz.f32 %0, %1;" : "=f"(r) : "f"(x));
  return r;
}
__device__ __forceinline__ float rcp(float x) {
  float r;
  asm("rcp.approx.ftz.f32 %0, %1;" : "=f"(r) : "f"(x));
  return r;
}
template <int N>
__device__ __forceinline__ void wg_wait() {
  asm volatile("wgmma.wait_group.sync.aligned %0;" ::"n"(N) : "memory");
}
__device__ __forceinline__ void yield_slot() { asm volatile("pmevent 0;"); }

template <int N, int KIND>
__device__ __forceinline__ void mma_kblock(float (&acc)[2][96], uint32_t a, uint32_t b);

#define F8(m, d, i) m(d[i]), m(d[i + 1]), m(d[i + 2]), m(d[i + 3]), m(d[i + 4]), m(d[i + 5]), m(d[i + 6]), m(d[i + 7])
#define KSTEP(N, A, B, oa0, oa1, ob, sd)                                                   \
  "mov.b64 db, {" B ", hb};\nadd.u64 db, db, " #ob ";\n"                                    \
  "mov.b64 da, {" A ", ha};\nadd.u64 da, da, " #oa0 ";\n"                                   \
  "wgmma.mma_async.sync.aligned.m64n" #N "k16.f32.bf16.bf16 {" ACC##N##_0 "}, da, db, " #sd ", 1, 1, 0, 1;\n" \
  "mov.b64 da, {" A ", ha};\nadd.u64 da, da, " #oa1 ";\n"                                   \
  "wgmma.mma_async.sync.aligned.m64n" #N "k16.f32.bf16.bf16 {" ACC##N##_1 "}, da, db, " #sd ", 1, 1, 0, 1;\n"

#define MMA_KBLOCK(N, KIND, A, B, ob2, ob3, sd, MID, MODE)                                 \
  template <>                                                                              \
  __device__ __forceinline__ void mma_kblock<N, KIND>(float (&acc)[2][96], uint32_t a, uint32_t b) { \
    asm volatile("{\n.reg .b32 ha, hb;\n.reg .b64 da, db;\n"                            \
                 "mov.b32 ha, 0x40000080;\nmov.b32 hb, 0x40000040;\n"                       \
                 "wgmma.fence.sync.aligned;\n"                                             \
                 KSTEP(N, A, B, 0, 64, 0, sd) KSTEP(N, A, B, 2, 66, 128, 1) MID               \
                 KSTEP(N, A, B, 4, 68, ob2, 1) KSTEP(N, A, B, 6, 70, ob3, 1) "wgmma.commit_group.sync.aligned;\n}\n"  \
                 : OPS##N(MODE) : "r"(a), "r"(b) : "memory");                              \
  }
#define MMA_KBLOCKS(N, A, B, ob2, ob3)                                                     \
  MMA_KBLOCK(N, 0, A, B, ob2, ob3, 1, "", "+f")                                            \
  MMA_KBLOCK(N, 1, A, B, ob2, ob3, 1, "wgmma.commit_group.sync.aligned;\n", "+f")          \
  MMA_KBLOCK(N, 2, A, B, ob2, ob3, 0, "", "=f")

#define ACC128_0 \
  "%0, %1, %2, %3, %4, %5, %6, %7, %8, %9, %10, %11, %12, %13, %14, %15, " \
  "%16, %17, %18, %19, %20, %21, %22, %23, %24, %25, %26, %27, %28, %29, %30, %31, " \
  "%32, %33, %34, %35, %36, %37, %38, %39, %40, %41, %42, %43, %44, %45, %46, %47, " \
  "%48, %49, %50, %51, %52, %53, %54, %55, %56, %57, %58, %59, %60, %61, %62, %63"
#define ACC128_1 \
  "%64, %65, %66, %67, %68, %69, %70, %71, %72, %73, %74, %75, %76, %77, %78, %79, " \
  "%80, %81, %82, %83, %84, %85, %86, %87, %88, %89, %90, %91, %92, %93, %94, %95, " \
  "%96, %97, %98, %99, %100, %101, %102, %103, %104, %105, %106, %107, %108, %109, %110, %111, " \
  "%112, %113, %114, %115, %116, %117, %118, %119, %120, %121, %122, %123, %124, %125, %126, %127"
#define OPS128(m) \
  F8(m, acc[0], 0), F8(m, acc[0], 8), F8(m, acc[0], 16), F8(m, acc[0], 24), F8(m, acc[0], 32), F8(m, acc[0], 40), F8(m, acc[0], 48), F8(m, acc[0], 56), \
        F8(m, acc[1], 0), F8(m, acc[1], 8), F8(m, acc[1], 16), F8(m, acc[1], 24), F8(m, acc[1], 32), F8(m, acc[1], 40), F8(m, acc[1], 48), F8(m, acc[1], 56)
MMA_KBLOCKS(128, "%128", "%129", 512, 640)

#define ACC192_0 \
  "%0, %1, %2, %3, %4, %5, %6, %7, %8, %9, %10, %11, %12, %13, %14, %15, " \
  "%16, %17, %18, %19, %20, %21, %22, %23, %24, %25, %26, %27, %28, %29, %30, %31, " \
  "%32, %33, %34, %35, %36, %37, %38, %39, %40, %41, %42, %43, %44, %45, %46, %47, " \
  "%48, %49, %50, %51, %52, %53, %54, %55, %56, %57, %58, %59, %60, %61, %62, %63, " \
  "%64, %65, %66, %67, %68, %69, %70, %71, %72, %73, %74, %75, %76, %77, %78, %79, " \
  "%80, %81, %82, %83, %84, %85, %86, %87, %88, %89, %90, %91, %92, %93, %94, %95"
#define ACC192_1 \
  "%96, %97, %98, %99, %100, %101, %102, %103, %104, %105, %106, %107, %108, %109, %110, %111, " \
  "%112, %113, %114, %115, %116, %117, %118, %119, %120, %121, %122, %123, %124, %125, %126, %127, " \
  "%128, %129, %130, %131, %132, %133, %134, %135, %136, %137, %138, %139, %140, %141, %142, %143, " \
  "%144, %145, %146, %147, %148, %149, %150, %151, %152, %153, %154, %155, %156, %157, %158, %159, " \
  "%160, %161, %162, %163, %164, %165, %166, %167, %168, %169, %170, %171, %172, %173, %174, %175, " \
  "%176, %177, %178, %179, %180, %181, %182, %183, %184, %185, %186, %187, %188, %189, %190, %191"
#define OPS192(m) \
  F8(m, acc[0], 0), F8(m, acc[0], 8), F8(m, acc[0], 16), F8(m, acc[0], 24), F8(m, acc[0], 32), F8(m, acc[0], 40), F8(m, acc[0], 48), F8(m, acc[0], 56), F8(m, acc[0], 64), F8(m, acc[0], 72), F8(m, acc[0], 80), F8(m, acc[0], 88), \
        F8(m, acc[1], 0), F8(m, acc[1], 8), F8(m, acc[1], 16), F8(m, acc[1], 24), F8(m, acc[1], 32), F8(m, acc[1], 40), F8(m, acc[1], 48), F8(m, acc[1], 56), F8(m, acc[1], 64), F8(m, acc[1], 72), F8(m, acc[1], 80), F8(m, acc[1], 88)
MMA_KBLOCKS(192, "%192", "%193", 768, 896)

#define HSTEP(oa, ob)                                                                       \
  "mov.b64 db, {%97, hb};\nadd.u64 db, db, " #ob ";\nmov.b64 da, {%96, ha};\nadd.u64 da, da, " #oa ";\n" \
  "wgmma.mma_async.sync.aligned.m64n192k16.f32.bf16.bf16 {" ACC192_0 "}, da, db, 1, 1, 1, 0, 1;\n"
__device__ __forceinline__ void mma_half(float (&d)[96], uint32_t a, uint32_t b) {
  asm volatile("{\n.reg .b32 ha, hb;\n.reg .b64 da, db;\nmov.b32 ha, 0x40000080;\nmov.b32 hb, 0x40000040;\n"
               "wgmma.fence.sync.aligned;\n" HSTEP(0, 0) HSTEP(2, 128) HSTEP(4, 768) HSTEP(6, 896)
               "wgmma.commit_group.sync.aligned;\n}\n"
               : F8("+f", d, 0), F8("+f", d, 8), F8("+f", d, 16), F8("+f", d, 24), F8("+f", d, 32), F8("+f", d, 40),
                 F8("+f", d, 48), F8("+f", d, 56), F8("+f", d, 64), F8("+f", d, 72), F8("+f", d, 80), F8("+f", d, 88)
               : "r"(a), "r"(b) : "memory");
}

#define TSTEP(REGS, W, X, ow, ox)                                                           \
  "mov.b64 db, {" X ", hi};\nadd.u64 db, db, " #ox ";\nmov.b64 da, {" W ", hi};\nadd.u64 da, da, " #ow ";\n" \
  "wgmma.mma_async.sync.aligned.m64n128k16.f32.bf16.bf16 {" REGS "}, da, db, 1, 1, 1, 1, 0;\n"
#define THEAD "{\n.reg .b32 hi;\n.reg .b64 da, db;\nmov.b32 hi, 0x40000040;\nwgmma.fence.sync.aligned;\n"
#define TTAIL "wgmma.commit_group.sync.aligned;\n}\n"
__device__ __forceinline__ void mma_kblock_t(float (&acc)[2][96], uint32_t wd, uint32_t xd) {
  asm volatile(THEAD TSTEP(ACC128_0, "%128", "%129", 0, 0) TSTEP(ACC128_1, "%128", "%129", 256, 0)
               TSTEP(ACC128_0, "%128", "%129", 128, 2) TSTEP(ACC128_1, "%128", "%129", 384, 2)
               TSTEP(ACC128_0, "%128", "%129", 512, 4) TSTEP(ACC128_1, "%128", "%129", 768, 4)
               TSTEP(ACC128_0, "%128", "%129", 640, 6) TSTEP(ACC128_1, "%128", "%129", 896, 6) TTAIL
               : OPS128("+f") : "r"(wd), "r"(xd) : "memory");
}
__device__ __forceinline__ void mma_half_t(float (&d)[96], uint32_t wd, uint32_t xd) {
  asm volatile(THEAD TSTEP(ACC128_0, "%64", "%65", 0, 0) TSTEP(ACC128_0, "%64", "%65", 128, 2)
               TSTEP(ACC128_0, "%64", "%65", 512, 4) TSTEP(ACC128_0, "%64", "%65", 640, 6) TTAIL
               : F8("+f", d, 0), F8("+f", d, 8), F8("+f", d, 16), F8("+f", d, 24), F8("+f", d, 32), F8("+f", d, 40),
                 F8("+f", d, 48), F8("+f", d, 56) : "r"(wd), "r"(xd) : "memory");
}

enum { kModePlain = 0, kModeHead = 1, kModeSkip = 2, kModeContinue = 3 };

template <int N>
__device__ __forceinline__ void fence_acc(float (&acc)[2][96]) {
#pragma unroll
  for (int h = 0; h < 2; h++)
#pragma unroll
    for (int i = 0; i < N / 2; i++) asm volatile("" : "+f"(acc[h][i])::"memory");
}

constexpr uint32_t kToB = (kTileBytes >> 4) + ((4096u >> 4) << 16) - (1u << 16);

#define TRACE_KB(nb)

template <int N>
__device__ __forceinline__ void head_blocks(float (&acc)[2][96], uint32_t sb, int n0, int slot, int xver,
                                            uint32_t rel_addr, bool rel) {
  const uint32_t ring = (((sb & 0x3FFFF) + kSmRing) >> 4) | (1u << 16);
  const uint32_t xdesc = (((sb & 0x3FFFF) + kSmX) >> 4) | (1u << 16);
  const uint32_t s0 = ring + slot * 2560, s1 = ring + ((slot + 1) & 3) * 2560;
  const uint32_t nb = n0 * 8, xbar = sb + kBarX + (xver - 1) * 16;
  if (xver > 0) {
    mbar_wait(xbar, 0);
    mbar_wait(sb + kBarTurn + (xver == 1 ? 2 : 3 * xver) * 8, 0);
  }
  mbar_wait(sb + kBarFull + (nb & 56), nb >> 6);
  if (n0 == 0) TRACE_AT(0, 1);
  TRACE_KB(nb);
  mma_kblock<N, 2>(acc, xver > 0 ? xdesc : s0, s0 + kToB);
  if (xver > 0) mbar_wait(xbar + 8, 0);
  mbar_wait(sb + kBarFull + (nb & 56) + 8, nb >> 6);
  TRACE_KB(nb + 8);
  mma_kblock<N, 0>(acc, xver > 0 ? xdesc + (kTileBytes >> 4) : s1, s1 + kToB);
  wg_wait<1>();
  if (rel) mbar_arrive_cluster(rel_addr + (nb & 56));
  wg_wait<0>();
  if (rel) mbar_arrive_cluster(rel_addr + (nb & 56) + 8);
  fence_acc<N>(acc);
}

enum { kPlain, kFresh, kResid, kStagger };
template <int N, int KIND, class Pre>
__device__ __forceinline__ void mainloop(float (&acc)[2][96], uint32_t sb, int tile, int n0, int slot, int nkb,
                                         int pause_kk, int att, uint32_t rel_addr, bool rel, int own_kk, Pre pre) {
  constexpr bool RESID = KIND == kResid, FRESH = KIND == kFresh;
  constexpr uint32_t kStep = (N == 192 ? 5 : 4) * 512;
  const uint32_t ring = (((sb & 0x3FFFF) + kSmRing) >> 4) | (1u << 16);
  uint32_t st = ring + slot * kStep;
  uint32_t nb = n0 * 8, prev = 64;
  const uint32_t last = nb + 8 * (nkb - (RESID ? 4 : KIND == kStagger ? 2 : 1)), own = nb + 8 * own_kk;
  const uint32_t stg = (((sb & 0x3FFFF) + kSmStg) >> 4) | (1u << 16);
  uint32_t stop = pause_kk >= 0 ? nb + 8 * pause_kk : last;
  const bool signal = (threadIdx.x & 127) == 64;
  if (!FRESH) fence_acc<N>(acc);
  if (tile > 0) mbar_wait(sb + kBarTurn + (tile - 1) * 8, 0);
  TRACE_AT(tile, 0);
  if constexpr (FRESH) {
    mbar_wait(sb + kBarFull + (nb & 56), nb >> 6);
    TRACE_KB(nb);
    mma_kblock<N, 2>(acc, st, st + kToB);
    prev = nb & 56;
    st += kStep;
    nb += 8;
  }
#pragma unroll 1
  while (true) {
#pragma unroll 1
    do {
      mbar_wait(sb + kBarFull + (nb & 56), nb >> 6);
      TRACE_KB(nb);
      if constexpr (RESID) mma_kblock_t(acc, st + kToB, nb == own ? stg : st);
      else mma_kblock<N, 0>(acc, st, st + kToB);
      wg_wait<1>();
      if (rel) mbar_arrive_cluster(rel_addr + prev);
      prev = nb & 56;
      st += kStep;
      if (st == ring + 10240) st = ring;
      nb += 8;
    } while (nb != stop);
    if (stop == last) break;
    stop = last;
    if (signal) mbar_arrive(sb + kBarPause + att * 8);
    wg_wait<0>();
    if (rel) mbar_arrive_cluster(rel_addr + prev);
    prev = 64;
    mbar_wait(sb + kBarResume + att * 8, 0);
  }
  mbar_wait(sb + kBarFull + (nb & 56), nb >> 6);
  TRACE_KB(nb);
  if constexpr (RESID) {
    const uint32_t z = gridDim.y - 1;
    const uint32_t s1 = st + kStep, s2 = s1 + kStep, s3 = s2 == ring + 8192 ? ring : s2 + kStep;
    mma_half_t(acc[0], st + kToB, st);
    wg_wait<1>();
    if (rel) mbar_arrive_cluster(rel_addr + 24);
    mbar_wait(sb + kBarFull + 40, nb >> 6);
    TRACE_KB(nb + 8);
    mma_half_t(acc[0], s1 + kToB, s1);
    mbar_wait(sb + kBarFull + 48, nb >> 6);
    TRACE_KB(nb + 16);
    mma_half_t(acc[0], s2 + kToB, s2);
    mbar_wait(sb + kBarFull + 56, nb >> 6);
    TRACE_KB(nb + 24);
    mma_half_t(acc[0], s3 + kToB, s3);
    mma_half_t(acc[1], st + kToB + 256, st + z);
    mma_half_t(acc[1], s1 + kToB + 256, s1 + z);
    wg_wait<2>();
#pragma unroll
    for (int i = 0; i < 64; i++) asm volatile("" : "+f"(acc[0][i])::"memory");
    pre(0);
    mma_half_t(acc[1], s2 + kToB + 256, s2 + z);
    wg_wait<2>();
    if (rel) mbar_arrive_cluster(rel_addr + 32);
    pre(1);
    mma_half_t(acc[1], s3 + kToB + 256, s3 + z);
    wg_wait<2>();
    if (rel) mbar_arrive_cluster(rel_addr + 40);
    wg_wait<1>();
    if (signal) mbar_arrive(sb + kBarTurn + tile * 8);
    if (rel) mbar_arrive_cluster(rel_addr + 48);
    wg_wait<0>();
    if (rel) mbar_arrive_cluster(rel_addr + 56);
#pragma unroll
    for (int i = 0; i < 64; i++) asm volatile("" : "+f"(acc[1][i])::"memory");
  } else if constexpr (KIND == kStagger) {
    const uint32_t z = gridDim.y - 1, s2 = st + kStep;
    mma_half(acc[1], st + 64, st + kToB);
    wg_wait<1>();
    if (rel) mbar_arrive_cluster(rel_addr + 40);
    mbar_wait(sb + kBarFull + 56, nb >> 6);
    TRACE_KB(nb + 8);
    mma_half(acc[1], s2 + 64, s2 + kToB);
    mma_half(acc[0], st, st + z + kToB);
    pre(0);
    mma_half(acc[0], s2, s2 + z + kToB);
    wg_wait<2>();
#pragma unroll
    for (int i = 0; i < 96; i++) asm volatile("" : "+f"(acc[1][i])::"memory");
    pre(1);
    wg_wait<1>();
    if (rel) mbar_arrive_cluster(rel_addr + 48);
    pre(2);
    if (signal) mbar_arrive(sb + kBarTurn + tile * 8);
    pre(3);
    wg_wait<0>();
    if (rel) mbar_arrive_cluster(rel_addr + 56);
#pragma unroll
    for (int i = 0; i < 96; i++) asm volatile("" : "+f"(acc[0][i])::"memory");
  } else {
    mma_kblock<N, 1>(acc, st, st + kToB);
    wg_wait<2>();
    if (rel) mbar_arrive_cluster(rel_addr + prev);
    pre();
    wg_wait<1>();
    if (signal) mbar_arrive(sb + kBarTurn + tile * 8);
    wg_wait<0>();
    if (rel) mbar_arrive_cluster(rel_addr + (nb & 56));
    fence_acc<N>(acc);
  }
}

__device__ __forceinline__ void publish_stats(uint32_t sb, uint2* stat, int w, int lane, unsigned epoch) {
  const uint32_t row = sb + kSmX + (32 * w + lane) * 128;
  float s[4], q[4];
#pragma unroll
  for (int c = 0; c < 4; c++) s[c] = q[c] = 0.f;
  uint32_t nx[4];
  ldsm4(row + ((lane & 7) << 4), nx);
#pragma unroll 1
  for (int J = 1; J <= 16; J++) {
    const uint32_t r[4] = {nx[0], nx[1], nx[2], nx[3]};
    ldsm4(row + ((J >> 3) & 1) * kTileBytes + (((J ^ lane) & 7) << 4), nx);
#pragma unroll
    for (int c = 0; c < 4; c++) {
      const float lo = bf_lo(r[c]);
      s[c] += lo;
      q[c] = fmaf(lo, lo, q[c]);
      if (c & 1) yield_slot();
    }
#pragma unroll
    for (int c = 0; c < 4; c++) {
      const float hi = bf_hi(r[c]);
      s[c] += hi;
      q[c] = fmaf(hi, hi, q[c]);
      if (c & 1) yield_slot();
    }
  }
  const int t = lane & 3, g = lane >> 2;
#pragma unroll
  for (int c = 0; c < 2; c++) {
    s[c] = (t & 2 ? s[c + 2] : s[c]) + shfl_xor(t & 2 ? s[c] : s[c + 2], 2);
    q[c] = (t & 2 ? q[c + 2] : q[c]) + shfl_xor(t & 2 ? q[c] : q[c + 2], 2);
  }
  const float so = (t & 1 ? s[1] : s[0]) + shfl_xor(t & 1 ? s[0] : s[1], 1);
  const float qo = (t & 1 ? q[1] : q[0]) + shfl_xor(t & 1 ? q[0] : q[1], 1);
  asm volatile("st.relaxed.gpu.global.v2.u32 [%0], {%1, %2};" ::"l"(stat + 32 * w + 8 * t + g),
               "r"(tag_value(so, epoch)), "r"(tag_value(qo, epoch)) : "memory");
}

__device__ __forceinline__ void add_chunk(float (&a)[8], const uint4& v) {
  a[0] += bf_lo(v.x); a[1] += bf_hi(v.x);
  a[2] += bf_lo(v.y); a[3] += bf_hi(v.y);
  a[4] += bf_lo(v.z); a[5] += bf_hi(v.z);
  a[6] += bf_lo(v.w); a[7] += bf_hi(v.w);
}

__device__ __forceinline__ int helper_col(int id, int slab) {
  return (slab < 3 ? slab * kD : (slab - 3) * 512) + id * 128;
}
__device__ __forceinline__ void helper_cta(const CUtensorMap* map_q, const CUtensorMap* map_1, uint8_t* sm,
                                           uint32_t sb, int id, int warp) {
  constexpr int kRed = 6 * 32768, kBar = kRed + 2 * 4096;
  const int tid = threadIdx.x;
  if (warp == 8 && elect()) {
#pragma unroll
    for (int s = 0; s < 6; s++) {
      mbar_init(sb + kBar + s * 8, 1);
      mbar_init(sb + kBar + 64 + s * 8, 4);
    }
    fence_async_smem();
#pragma unroll
    for (int s = 0; s < 6; s++) {
      mbar_expect_tx(sb + kBar + s * 8, 32768);
      tma2d(sb + s * 32768, map_q, sb + kBar + s * 8, id * 128, s * 128);
    }
  }
  __syncthreads();
  if (warp == 8) {
    int slot = 0, ph = 0;
#pragma unroll 1
    for (int n = 6; n < 80; n++) {
      mbar_wait(sb + kBar + 64 + slot * 8, ph);
      if (elect()) {
        mbar_expect_tx(sb + kBar + slot * 8, 32768);
        tma2d(sb + slot * 32768, n < 24 ? map_q : map_1, sb + kBar + slot * 8, helper_col(id, n >> 3), (n & 7) * 128);
      }
      if (++slot == 6) slot = 0, ph ^= 1;
    }
  } else if (warp < 8) {
    if (tid == 0) *reinterpret_cast<unsigned*>(sm + kBar + 128) = atomicAdd(&g_ticket, 1u) / kGrid + 1;
    int slot = warp >> 2, ph = 0;
#pragma unroll 1
    for (int slab = 0; slab < 10; slab++) {
      float a[8];
#pragma unroll
      for (int e = 0; e < 8; e++) a[e] = 0.f;
#pragma unroll 1
      for (int box = 0; box < 4; box++) {
        mbar_wait_bounded(sb + kBar + slot * 8, ph);
        const uint4* p = reinterpret_cast<const uint4*>(sm + slot * 32768) + (tid & 127);
        uint4 v[16];
#pragma unroll
        for (int i = 0; i < 16; i++) v[i] = p[i * 128];
        __syncwarp();
        if (elect()) mbar_arrive(sb + kBar + 64 + slot * 8);
#pragma unroll
        for (int i = 0; i < 16; i++) add_chunk(a, v[i]);
        slot += 2;
        if (slot >= 6) slot -= 6, ph ^= 1;
      }
      float* red = reinterpret_cast<float*>(sm + kRed + (slab & 1) * 4096);
#pragma unroll
      for (int e = 0; e < 8; e++) a[e] += shfl_xor(a[e], 16);
      if ((tid & 16) == 0) {
        float4* d = reinterpret_cast<float4*>(red + warp * 128 + (tid & 15) * 8);
        d[0] = make_float4(a[0], a[1], a[2], a[3]);
        d[1] = make_float4(a[4], a[5], a[6], a[7]);
      }
      asm volatile("bar.sync 1, 256;" ::: "memory");
      if (warp < 4) {
        float t = 0.f;
#pragma unroll
        for (int q = 0; q < 8; q++) t += red[q * 128 + tid];
        st_relaxed(g_cs + (slab < 3 ? 0 : 3 * kD) + helper_col(id, slab) + tid,
                   tag_value(t, *reinterpret_cast<volatile unsigned*>(sm + kBar + 128)));
      }
    }
  }
}

__device__ __forceinline__ void colsum_strip(const CUtensorMap* map, uint8_t* sm, uint32_t sb, int col, int half,
                                             int lane, unsigned epoch) {
  const uint32_t bar = sb + kBarSlab + half * 16;
  const int buf = kSmStg + half * 8192;
  float a[8];
#pragma unroll
  for (int e = 0; e < 8; e++) a[e] = 0.f;
#pragma unroll 1
  for (int r = -2; r < 4; r++) {
    if (r >= 0) {
      mbar_wait(bar + (r & 1) * 8, r >> 1);
      const uint4* p = reinterpret_cast<const uint4*>(sm + buf + (r & 1) * 4096) + lane;
#pragma unroll 1
      for (int q = 0; q < 8; q += 4) {
        uint4 v[4];
#pragma unroll
        for (int u = 0; u < 4; u++) v[u] = p[(q + u) * 32];
#pragma unroll
        for (int u = 0; u < 4; u++) {
          a[0] += bf_lo(v[u].x); a[1] += bf_hi(v[u].x); a[2] += bf_lo(v[u].y); a[3] += bf_hi(v[u].y);
          yield_slot();
          a[4] += bf_lo(v[u].z); a[5] += bf_hi(v[u].z); a[6] += bf_lo(v[u].w); a[7] += bf_hi(v[u].w);
          yield_slot();
        }
      }
      fence_async_smem();
      __syncwarp();
    }
    if (r < 2 && elect()) {
      mbar_expect_tx(bar + (r & 1) * 8, 4096);
      tma2d(sb + buf + (r & 1) * 4096, map, bar + (r & 1) * 8, col, half * 512 + (r + 2) * 128);
    }
  }
#pragma unroll
  for (int e = 0; e < 4; e++) a[e] = (lane & 16 ? a[e + 4] : a[e]) + shfl_xor(lane & 16 ? a[e] : a[e + 4], 16);
#pragma unroll
  for (int e = 0; e < 2; e++) a[e] = (lane & 8 ? a[e + 2] : a[e]) + shfl_xor(lane & 8 ? a[e] : a[e + 2], 8);
  a[0] = (lane & 4 ? a[1] : a[0]) + shfl_xor(lane & 4 ? a[0] : a[1], 4);
  a[0] += shfl_xor(a[0], 2);
  if (!(lane & 2)) st_relaxed(g_cs + half * (3 * kD + kF) + col + (lane & 1) * 8 + (lane >> 2), tag_value(a[0], epoch));
}

constexpr float kGeluBeta = 0.3292034911525734f / 2.f;
constexpr float kGeluK = 2.423681954311584f / 4.f;
constexpr float kHScale = 2.f * kGeluBeta;

__device__ __forceinline__ void store_staged(uint8_t* dst, uint32_t stg) {
  fence_async_smem();
  __syncwarp();
  if (elect()) {
    bulk_store(dst, stg, 4096);
    bulk_commit();
  }
}

#define GY_MASK 5
#define GF_MASK 3
#define GY(k) if ((GY_MASK >> k) & 1) yield_slot()
template <int J0, int J1>
__device__ __forceinline__ void fold_norm(float (&acc)[2][96], const float2 (&st)[4], const float4* vec) {
  float4 vn = vec[J0 * 4];
#pragma unroll
  for (int J = J0; J < J1; J++) {
    const float4 v = vn;
    if (J + 1 < J1) vn = vec[J * 4 + 4];
#pragma unroll
    for (int c = 0; c < 4; c++) {
      float& a0 = acc[c & 1][4 * J + (c & 2)];
      float& a1 = acc[c & 1][4 * J + (c & 2) + 1];
      a0 = fmaf(a0, st[c].x, fmaf(st[c].y, v.x, v.z));
      a1 = fmaf(a1, st[c].x, fmaf(st[c].y, v.y, v.w));
      asm volatile("" : "+f"(a0), "+f"(a1));
      if ((c & 1) && ((GF_MASK >> (c >> 1)) & 1)) yield_slot();
    }
  }
}

template <int CH, class Acquire>
__device__ __forceinline__ void gelu_chunk(const float (&acc)[2][96], uint32_t stg, int lane, uint8_t* prev,
                                           Acquire acquire) {
  uint32_t pk[8][4];
  float z[3][4];
  const uint32_t row = (stg + lane * 128) ^ ((lane & 7) << 4);
#define U(s, e) acc[(e) >> 1][4 * (CH * 8 + ((s) >> 1)) + 2 * ((s) & 1) + ((e) & 1)]
#pragma unroll
  for (int s = 0; s < 18; s++) {
    const int cur = s % 3, p1 = (s + 2) % 3, p2 = (s + 1) % 3, q = s - 2, jj = 2 * q - 24;
    const bool mid = s >= 1 && s < 17;
    if (mid) z[p1][0] = tanh_fast(z[p1][0]);
    if (s < 16) {
#pragma unroll
      for (int e = 0; e < 4; e++) {
        z[cur][e] = fmaf(U(s, e), U(s, e), kGeluK);
        asm volatile("" : "+f"(z[cur][e]));
      }
    }
    if (jj >= 0) stsm4(row ^ (jj << 4), pk[jj][0], pk[jj][1], pk[jj][2], pk[jj][3]);
    GY(0);
    if (mid) z[p1][1] = tanh_fast(z[p1][1]);
    if (q >= 0) {
      pk[q >> 1][2 * (q & 1)] = pack2(fmaf(U(q, 0), z[p2][0], U(q, 0)), fmaf(U(q, 1), z[p2][1], U(q, 1)));
      pk[q >> 1][2 * (q & 1) + 1] = pack2(fmaf(U(q, 2), z[p2][2], U(q, 2)), fmaf(U(q, 3), z[p2][3], U(q, 3)));
    }
    GY(1);
    if (mid) z[p1][2] = tanh_fast(z[p1][2]);
    if (s < 16) {
#pragma unroll
      for (int e = 0; e < 4; e++) {
        z[cur][e] = z[cur][e] * U(s, e) * 8.f;
        asm volatile("" : "+f"(z[cur][e]));
      }
    }
    if (mid) z[p1][3] = tanh_fast(z[p1][3]);
    if (jj >= 0) stsm4(row ^ ((jj + 1) << 4), pk[jj + 1][0], pk[jj + 1][1], pk[jj + 1][2], pk[jj + 1][3]);
    GY(2);
    if (CH == 1 && s == 1) store_staged(prev, stg);
    if (q == 11) acquire();
  }
#undef U
}

__device__ __forceinline__ void scale_stats(float2 (&st)[4]) {
#pragma unroll
  for (int c = 0; c < 4; c++) {
    st[c].x *= kGeluBeta;
    st[c].y *= st[c].x;
  }
}

__device__ __forceinline__ void add_mean_term(float (&acc)[2][96], const float2 (&st)[4], uint8_t* sm, int tq,
                                              int lane) {
  const float2* cs = reinterpret_cast<const float2*>(sm + kSmCsQ) + tq * 96 + (lane & 3);
  float2 vn = cs[0];
#pragma unroll
  for (int J = 0; J < 24; J++) {
    const float2 v = vn;
    if (J < 23) vn = cs[J * 4 + 4];
#pragma unroll
    for (int c = 0; c < 4; c++) {
      acc[c & 1][4 * J + (c & 2)] = fmaf(st[c].y, v.x, acc[c & 1][4 * J + (c & 2)]);
      acc[c & 1][4 * J + (c & 2) + 1] = fmaf(st[c].y, v.y, acc[c & 1][4 * J + (c & 2) + 1]);
    }
    yield_slot();
  }
}

#define CV_MASK 1
#define HALO_AT 2
struct AttnRegs {
  uint32_t q[4][8], k[5][8], vt[5][8];
};
#define SCALED(c, J) pack2(acc[(c) & 1][4 * (J) + ((c) & 2)] * st[c].x, acc[(c) & 1][4 * (J) + ((c) & 2) + 1] * st[c].x)
__device__ __forceinline__ void convert_group(const float (&acc)[2][96], const float2 (&st)[4], AttnRegs& r, int c,
                                              int part) {
#pragma unroll
  for (int J = 0; J < 8; J++) {
    if (part == 0) r.q[c][J] = SCALED(c, J);
    if (part == 1) r.k[c + 1][J] = SCALED(c, 8 + J);
    if (part == 2) r.vt[c + 1][J] = transpose8(SCALED(c, 16 + J));
    if ((J & CV_MASK) == CV_MASK) yield_slot();
  }
}
#undef SCALED

__device__ __forceinline__ void convert_odd(const float (&acc)[2][96], const float2 (&st)[4], AttnRegs& r, int step,
                                            uint8_t* sm, uint32_t halo_bar, uint4* halo_out, bool send,
                                            unsigned epoch, int w, int lane) {
  if (step == 1) {
    convert_group(acc, st, r, 3, 2);
    convert_group(acc, st, r, 3, 1);
    if (w < 3) {
      uint2* hs = reinterpret_cast<uint2*>(sm + kSmHalo + w * 2048) + lane;
#pragma unroll
      for (int i = 0; i < 4; i++) {
        hs[i * 32] = make_uint2(r.k[4][2 * i], r.k[4][2 * i + 1]);
        hs[128 + i * 32] = make_uint2(r.vt[4][2 * i], r.vt[4][2 * i + 1]);
      }
      __syncwarp();
      if (elect()) mbar_arrive(halo_bar + w * 8);
    } else if (send) {
#pragma unroll
      for (int i = 0; i < 4; i++) {
        st_packet(halo_out + lane + i * 32, r.k[4][2 * i], r.k[4][2 * i + 1], epoch);
        st_packet(halo_out + lane + 128 + i * 32, r.vt[4][2 * i], r.vt[4][2 * i + 1], epoch);
      }
    }
  } else if (step == 2) {
    convert_group(acc, st, r, 1, 2);
  } else {
    convert_group(acc, st, r, 1, 1);
    convert_group(acc, st, r, 3, 0);
    convert_group(acc, st, r, 1, 0);
  }
}

__device__ __forceinline__ void epilogue_attn(const float (&acc)[2][96], const float2 (&st)[4], AttnRegs& r,
                                              uint8_t* sm, uint32_t sb, int layer, int tq, int b, int j,
                                              unsigned epoch, int tile, int w, int lane) {
  const int t = lane & 3, g = lane >> 2;
  const int hp = j + 8 * tq, att = 2 * layer + tq;
  auto& q = r.q;
  auto& k = r.k;
  auto& vt = r.vt;
  const bool first = w == 0 && (b & 7) == 0;
  const uint4* gh = g_halo + ((layer * 16 + b - 1) * 16 + hp) * 256 + lane;
  uint32_t tag[8];
#define LOAD_HALO()                                                                                    \
  _Pragma("unroll") for (int i = 0; i < 4; i++) {                                                      \
    ld_packet(gh + i * 32, k[0][2 * i], k[0][2 * i + 1], tag[i]);                                      \
    ld_packet(gh + 128 + i * 32, vt[0][2 * i], vt[0][2 * i + 1], tag[4 + i]);                          \
  }
#define AWAIT_HALO()                                                                                   \
  for (unsigned spins = 0;; spins++) {                                                                 \
    const unsigned d0 = (tag[0] ^ epoch) | (tag[1] ^ epoch) | (tag[2] ^ epoch) | (tag[3] ^ epoch);     \
    const unsigned d1 = (tag[4] ^ epoch) | (tag[5] ^ epoch) | (tag[6] ^ epoch) | (tag[7] ^ epoch);     \
    if (__all_sync(0xffffffffu, (d0 | d1) == 0)) break;                                                \
    if (spins > kSpinLimit) __trap();                                                                  \
    LOAD_HALO();                                                                                       \
  }
#pragma unroll
  for (int c = 0; c <= 6; c++) {
    if (c == HALO_AT) {
#pragma unroll
      for (int i = 0; i < 8; i++) k[0][i] = vt[0][i] = tag[i] = 0u;
      if (w > 0) {
        mbar_wait(sb + kBarHalo + (att * 3 + w - 1) * 8, 0);
        const uint2* hs = reinterpret_cast<const uint2*>(sm + kSmHalo + (w - 1) * 2048) + lane;
#pragma unroll
        for (int i = 0; i < 4; i++) {
          const uint2 a = hs[i * 32], d = hs[128 + i * 32];
          k[0][2 * i] = a.x; k[0][2 * i + 1] = a.y;
          vt[0][2 * i] = d.x; vt[0][2 * i + 1] = d.y;
        }
      } else if (!first) {
        LOAD_HALO();
      }
    }
    if (c < 6) convert_group(acc, st, r, 2 * (c & 1), 2 - (c >> 1));
  }
  TRACE_AT(tile, 8);
  if (w == 0 && !first) AWAIT_HALO();
  constexpr float kScale = 0.17677669529663687f * 1.4426950408889634f;
  const bool own0 = 2 * t <= g, own1 = 2 * t + 1 <= g;
  const uint32_t own_mask = (own0 ? 0xffffu : 0u) | (own1 ? 0xffff0000u : 0u);
  const uint32_t stg = sb + kSmStg + w * 4096;
  const uint32_t orow = stg + (lane & 7) * 128, ochunk = (lane >> 3) ^ (lane & 7);
  TRACE_AT(tile, 9);
  mbar_wait(sb + kBarPause + att * 8, 0);
  TRACE_AT(tile, 10);

  float s[2][6][4], o[2][4][2][4];
#pragma unroll
  for (int n = 0; n < 24; n++) {
    const int ks = n / 12, hd = (n % 12) / 6, m = n % 6, ca = 2 * (m / 3), kg = ca + m % 3, J = 4 * hd + 2 * ks;
    if (ks == 0) s[hd][m][0] = s[hd][m][1] = s[hd][m][2] = s[hd][m][3] = 0.f;
    mma16816(s[hd][m], q[ca][J], q[ca + 1][J], q[ca][J + 1], q[ca + 1][J + 1], k[kg][J], k[kg][J + 1]);
  }
  float v0[2][4], v1[2][4], m[2][4];
  uint32_t pp[2][4], po[2][4];
#define UNITS _Pragma("unroll") for (int hd = 0; hd < 2; hd++) _Pragma("unroll") for (int c = 0; c < 4; c++)
  UNITS {
    const int mp = 3 * (c >> 1) + (c & 1), r = 2 * (c & 1);
    float p0 = s[hd][mp][r], p1 = s[hd][mp][r + 1];
    if (c == 0 && first) p0 = p1 = -INFINITY;
    v0[hd][c] = own0 ? s[hd][mp + 1][r] : p0;
    v1[hd][c] = own1 ? s[hd][mp + 1][r + 1] : p1;
    m[hd][c] = fmaxf(v0[hd][c], v1[hd][c]);
  }
  UNITS m[hd][c] = fmaxf(m[hd][c], shfl_xor(m[hd][c], 1));
  UNITS m[hd][c] = fmaxf(m[hd][c], shfl_xor(m[hd][c], 2));
  UNITS {
    const float nm = -m[hd][c] * kScale;
    v0[hd][c] = ex2(fmaf(v0[hd][c], kScale, nm));
    v1[hd][c] = ex2(fmaf(v1[hd][c], kScale, nm));
    m[hd][c] = v0[hd][c] + v1[hd][c];
  }
  UNITS m[hd][c] += shfl_xor(m[hd][c], 1);
  UNITS m[hd][c] += shfl_xor(m[hd][c], 2);
  UNITS {
    const float inv = rcp(m[hd][c]);
    const uint32_t p = pack2(v0[hd][c] * inv, v1[hd][c] * inv);
    pp[hd][c] = p & ~own_mask;
    po[hd][c] = p & own_mask;
    asm volatile("" : "+r"(pp[hd][c]), "+r"(po[hd][c]));
  }
#pragma unroll
  for (int n = 0; n < 24; n++) {
    const int ph = n / 8, hd = (n >> 2) & 1, c = 2 * ((n >> 1) & 1) + (ph == 1), ds = n & 1, J = 4 * hd + 2 * ds;
    float(&d)[4] = o[hd][c][ds];
    if (ph < 2) d[0] = d[1] = d[2] = d[3] = 0.f;
    if (ph == 0) mma1688(d, vt[c + 1][J], vt[c + 1][J + 1], po[hd][c]);
    if (ph == 1) mma16816(d, vt[c][J], vt[c][J + 1], vt[c + 1][J], vt[c + 1][J + 1], pp[hd][c], po[hd][c]);
    if (ph == 2) mma1688(d, vt[c][J], vt[c][J + 1], pp[hd][c]);
    if (n == 3) {
      yield_slot();
      if (tq == 0 && lane == 0) mbar_arrive(sb + kBarResume + att * 8);
    }
  }
  yield_slot();
  if (tq == 1 && lane == 0) mbar_arrive(sb + kBarResume + att * 8);
  TRACE_AT(tile, 11);
  UNITS stsm4_t(orow + c * 1024 + ((ochunk ^ (4 * hd)) << 4), pack2(o[hd][c][0][0], o[hd][c][0][1]),
                pack2(o[hd][c][0][2], o[hd][c][0][3]), pack2(o[hd][c][1][0], o[hd][c][1][1]),
                pack2(o[hd][c][1][2], o[hd][c][1][3]));
#undef UNITS
#undef AWAIT_HALO
#undef LOAD_HALO
  fence_async_smem();
  __syncwarp();
  TRACE_AT(tile, 12);
  if (elect()) {
    bulk_store(g_o + (b * 16 + hp) * kTileBytes + w * 4096, stg, 4096);
    bulk_commit();
    bulk_wait();
    TRACE_AT(tile, 13);
    mbar_arrive(sb + kBarEpi + tile * 8);
  }
  __syncwarp();
}

__device__ __forceinline__ void gather_stats(uint8_t* sm, const uint2* stat, int r, float eps, unsigned epoch) {
  uint2 a[8];
#pragma unroll 1
  for (unsigned spins = 0;; spins++) {
    unsigned diff = 0;
#pragma unroll
    for (int i = 0; i < 8; i++) {
      a[i] = ld_relaxed2(stat + i * 128 + r);
      diff |= (a[i].x ^ epoch) | (a[i].y ^ epoch);
    }
    if (__all_sync(0xffffffffu, (diff & 7u) == 0)) break;
    if (spins > kSpinLimit) __trap();
  }
  float s = 0.f, q = 0.f;
#pragma unroll
  for (int i = 0; i < 8; i++) {
    s += untag_value(a[i].x);
    q += untag_value(a[i].y);
  }
  const float mean = s * (1.f / 1024.f);
  const float var = fmaxf(fmaf(-mean, mean, q * (1.f / 1024.f)), 0.f);
  reinterpret_cast<float2*>(sm + kSmStat)[r] = make_float2(rsqrtf(var + eps), -mean);
}

__device__ __forceinline__ void gather_colsums_qkv(uint8_t* sm, int tq, int j, int lane, unsigned epoch) {
  const uint2* src = reinterpret_cast<const uint2*>(g_cs + (j + 8 * tq) * 64) + lane;
  uint2 v[3], u[3];
  for (unsigned spins = 0;; spins++) {
    unsigned diff = 0;
#pragma unroll
    for (int q = 0; q < 3; q++) {
      v[q] = ld_relaxed2(src + q * (kD / 2));
      u[q] = make_uint2(epoch & 7u, epoch & 7u);
      if (tq) u[q] = ld_relaxed2(src + (q * kD + 3 * kD + kF) / 2);
    }
#pragma unroll
    for (int q = 0; q < 3; q++) diff |= (v[q].x ^ epoch) | (v[q].y ^ epoch) | (u[q].x ^ epoch) | (u[q].y ^ epoch);
    if (__all_sync(0xffffffffu, (diff & 7u) == 0)) break;
    if (spins > kSpinLimit) __trap();
  }
#pragma unroll
  for (int q = 0; q < 3; q++)
    reinterpret_cast<float2*>(sm + kSmCsQ)[tq * 96 + q * 32 + lane] =
        make_float2(untag_value(v[q].x) + untag_value(u[q].x), untag_value(v[q].y) + untag_value(u[q].y));
}

__device__ __forceinline__ void gather_colsums_w1(uint8_t* sm, const __nv_bfloat16* b1, int j, int lane,
                                                  unsigned epoch) {
#pragma unroll 1
  for (int blk = 0; blk < 7; blk++) {
    const int pair = 32 * (blk + (blk < 3 ? 3 * j : blk < 5 ? 21 + 2 * j : 35 + 2 * j)) + lane;
    const uint32_t bias = reinterpret_cast<const uint32_t*>(b1)[pair];
    uint2 v;
    for (unsigned spins = 0;; spins++) {
      v = ld_relaxed2(reinterpret_cast<const uint2*>(g_cs + 3 * kD) + pair);
      if (__all_sync(0xffffffffu, (((v.x ^ epoch) | (v.y ^ epoch)) & 7u) == 0)) break;
      if (spins > kSpinLimit) __trap();
    }
    reinterpret_cast<float4*>(sm + kSmV1)[blk * 32 + lane] =
        make_float4(untag_value(v.x), untag_value(v.y), kGeluBeta * bf_lo(bias), kGeluBeta * bf_hi(bias));
  }
}

#define PAUSE_QKV2 7
#define PAUSE_WO 2

__global__ void __cluster_dims__(2, 1, 1) __launch_bounds__(384, 1)
fused_layers_kernel(const __grid_constant__ CUtensorMap map_x, const __grid_constant__ CUtensorMap map_out,
                    const __grid_constant__ CUtensorMap map_qkv, const __grid_constant__ CUtensorMap map_wo,
                    const __grid_constant__ CUtensorMap map_w1a, const __grid_constant__ CUtensorMap map_w1b,
                    const __grid_constant__ CUtensorMap map_w2, const __grid_constant__ CUtensorMap map_csq,
                    const __grid_constant__ CUtensorMap map_cs1, const __grid_constant__ CUtensorMap map_css,
                    const __grid_constant__ Params prm) {
  extern __shared__ __align__(1024) uint8_t sm[];
  if (threadIdx.x < 128 && blockIdx.x < kCtas) TRACE_AT(15, 1);
  const uint32_t sb = __shfl_sync(0xffffffffu, smem_u32(sm), 0);
  const int warp = __shfl_sync(0xffffffffu, threadIdx.x >> 5, 0), lane = threadIdx.x & 31;
  const int cta = blockIdx.x, rank = cta & 1, cl = cta >> 1;
  const int grp = cl < 4 ? 0 : cl < 36 ? (cl - 4) & 7 : 1 + (cl - 36) % 7;
  const int j = cl < 4 ? 4 + cl : cl < 36 ? (cl - 4) >> 3 : 4 + (cl - 36) / 7;
  const int b = 2 * grp + rank;
  const int xcol = (b >> 3) * kD, xrow = (b & 7) * 128;

  if (cta >= kCtas) {
    helper_cta(&map_csq, &map_cs1, sm, sb, cta - kCtas, warp);
    return;
  }
  if ((warp < 8 || warp == 9) && elect()) {
    if (warp == 9) {
#pragma unroll
      for (int s = 0; s < 8; s++) mbar_init(sb + kBarFull + s * 8, 1);
      fence_async_smem();
#pragma unroll 1
      for (int s = 0; s < 4; s++) {
        const uint32_t full = sb + kBarFull + s * 8, dst = sb + kSmRing + s * 40960;
        mbar_expect_tx(full, 40960);
        tma2d(dst, &map_x, full, xcol + (s & 1) * 64, xrow);
        tma3d(dst + kTileBytes, &map_qkv, full, (j + 4 * (s & 2)) * 64, (s & 1) * 64, 0);
        tma3d(dst + kTileBytes + 12288, &map_qkv, full, (j + 4 * (s & 2)) * 64, (s & 1) * 64 + 32, 0);
      }
    } else {
      if (sb & 1023) __trap();
#pragma unroll
      for (int s = 0; s < 16; s++) mbar_init(sb + kBarTurn + warp * 128 + s * 8, warp < 5 ? 1 : warp == 5 ? 2 : 4);
    }
    asm volatile("fence.mbarrier_init.release.cluster;" ::: "memory");
  }
  __syncwarp();
  asm volatile("barrier.cluster.arrive.relaxed.aligned;" ::: "memory");

  if (warp >= 8) {
    asm volatile("setmaxnreg.dec.sync.aligned.u32 40;");
    if (warp < 10) {
      asm volatile("barrier.cluster.wait.aligned;" ::: "memory");
      uint32_t nb = 32, off = 0, kb = 0;
#define RING_STEP(WAIT, ISSUE)                                            \
  do {                                                                    \
    const uint32_t mb = nb - depth, full = sb + kBarFull + (nb & 56);     \
    if (kb == skip) kb += inc;                                            \
    mbar_wait(sb + kBarEmpty + (mb & 56), mb >> 6);                       \
    WAIT;                                                                 \
    if (elect()) { ISSUE; }                                               \
    TRACE_ISSUE(9 - warp, nb);                                            \
    kb += inc;                                                            \
    off = off == wrap ? 0 : off + step;                                   \
    nb += 8;                                                              \
  } while (nb != nend)
#pragma unroll 1
      for (int sg = 0; sg < kSegs; sg++) {
        const uint32_t e = prm.seg[sg];
        const int ty = e & 7, mode = (e >> 15) & 3, reset = (e >> 24) & 3;
        const uint32_t nend = nb + (e & 0x1f8);
        const uint32_t step = (e >> 17) & 1 ? 40960 : 32768, wrap = 163840 - step;
        const uint32_t depth = (e >> 18) & 1 ? 40 : 32;
        if (reset) off = reset == 1 ? 0 : reset == 2 ? 40960 : 131072;
        const uint32_t own = ty == 2 ? 8 + j : 2 * j;
        if (mode != kModeContinue) kb = mode == kModeHead ? own : (e >> 9) & 63;
        const uint32_t inc = mode >= kModeSkip && ty != 2 ? 2 : 1, skip = mode >= kModeSkip ? own + (kb & 1) : 255;
        if (warp == 8) {
          const CUtensorMap* map = ty < 2 ? &map_qkv : ty == 2 ? &map_wo : ty == 3 ? &map_w1a : ty < 6 ? &map_w1b : &map_w2;
          const int c0 = ty < 2 ? (j + 8 * ty) * 64 : 0;
          const int c2 = ty < 2 ? 0 : ty == 3 ? 3 * j : ty == 4 ? 24 + 2 * j : ty == 5 ? 40 + 2 * j : 2 * j;
          const uint32_t half = (ty < 2 || ty == 3) ? 12288 : 8192;
          const uint32_t bytes = 2 * half + (mode == kModeHead ? 0 : kTileBytes);
          const uint32_t dst = sb + kSmRing + kTileBytes + rank * half;
          if (ty == 2 && mode == kModeHead) mbar_wait(sb + kBarEpi + ((e >> 19) & 31) * 8, 0);
#pragma unroll 1
          RING_STEP(, mbar_expect_tx(full, bytes); tma3d_mc(dst + off, map, full, c0, kb * 64 + rank * 32, c2));
        } else if (mode == kModeHead) {
          off += ((nend - nb) >> 3) * step;
          nb = nend;
          if (off >= 163840) off -= 163840;
        } else if (sg < 2) {
#pragma unroll 1
          RING_STEP(, tma2d(sb + kSmRing + off, &map_x, full, xcol + kb * 64, xrow));
        } else {
          const uint8_t* src = ty == 6 ? g_h + b * 56 * kTileBytes : (ty == 2 ? g_o : g_x) + b * 16 * kTileBytes;
          const int dep = (e >> 19) & 31;
          if (dep < 28) mbar_wait(sb + kBarReady + dep * 8, 0);
          if ((dep & 30) == 28) {
#pragma unroll 1
            RING_STEP(mbar_wait(sb + kBarSrc + ((kb << (4 - inc)) & 56), dep),
                      bulk_load(sb + kSmRing + off, src + kb * kTileBytes, kTileBytes, full));
          } else {
#pragma unroll 1
            RING_STEP(, bulk_load(sb + kSmRing + off, src + kb * kTileBytes, kTileBytes, full));
          }
        }
      }
#undef RING_STEP
    } else {
      unsigned epoch = 0;
      if (warp == 10) {
        if (lane == 0) epoch = atomicAdd(&g_ticket, 1u) / kGrid + 1;
        *reinterpret_cast<unsigned*>(sm + kSmEpoch) = __shfl_sync(0xffffffffu, epoch, 0);
        asm volatile("barrier.cluster.wait.aligned;" ::: "memory");
        if (elect()) mbar_arrive(sb + kBarEpoch);
      } else {
        asm volatile("barrier.cluster.wait.aligned;" ::: "memory");
        mbar_wait_bounded(sb + kBarFull, 0);
        if (elect()) {
          mbar_expect_tx(sb + kBarInit, 32768);
          tma2d(sb + kSmX, &map_x, sb + kBarInit, xcol + j * 128, xrow);
          tma2d(sb + kSmX + kTileBytes, &map_x, sb + kBarInit, xcol + j * 128 + 64, xrow);
        }
        const uint2 u = reinterpret_cast<const uint2*>(prm.b2)[32 * j + lane];
        reinterpret_cast<float4*>(sm + kSmB2)[lane] = make_float4(
            kHScale * bf_lo(u.x), kHScale * bf_hi(u.x), kHScale * bf_lo(u.y), kHScale * bf_hi(u.y));
      }
      mbar_wait_bounded(sb + kBarEpoch, 0);
      epoch = *reinterpret_cast<volatile unsigned*>(sm + kSmEpoch);
      if (cta < 96) {
        mbar_wait_bounded(sb + kBarInit, 0);
        colsum_strip(&map_css, sm, sb, (cta >> 5) * kD + 512 + (cta & 31) * 16, warp - 10, lane, epoch);
      }
      gather_colsums_qkv(sm, 11 - warp, j, lane, epoch);
      __syncwarp();
      if (elect()) mbar_arrive(sb + kBarCs + (11 - warp) * 8);
     if (warp == 10) {
#pragma unroll 1
      for (int i = 0; i < kTiles - 1; i++) {
        const bool xt = i == 2 || i == 6 || i == 9;
        const unsigned* line = g_flag + (i * 16 + b) * 32;
        mbar_wait(sb + (xt ? kBarX + (i >> 2) * 16 : kBarEpi + i * 8), 0);
        if (xt || i == 1 || i == 8) {
          unsigned todo = 0xff, spins = 0;
          do {
            const unsigned now = __ballot_sync(0xffffffffu, ld_relaxed(line + (lane & 7)) == epoch) & todo;
            if (now) {
              asm volatile("fence.acquire.gpu;\nfence.proxy.async.global;" ::: "memory");
              if ((now >> lane) & 1) mbar_arrive(sb + kBarSrc + lane * 8);
              todo ^= now;
            }
            if (++spins > kSpinLimit) __trap();
          } while (todo);
        } else {
          wait_flags(line + (lane & 7), epoch);
          if (elect()) mbar_arrive(sb + kBarReady + i * 8);
        }
        if (xt) {
          wait_flags(line + 8 + (lane & 7), epoch);
          if (elect()) mbar_arrive(sb + kBarReady + (14 + (i >> 2)) * 8);
        }
      }
     } else {
#pragma unroll 1
      for (int i = 0; i < kTiles - 1; i++) {
        if (i == 3) {
          gather_colsums_w1(sm, prm.b1, j, lane, epoch);
          __syncwarp();
          if (elect()) mbar_arrive(sb + kBarCs + 16);
        }
        const bool xt = i == 2 || i == 6 || i == 9;
#pragma unroll 1
        for (int h = 0; h < (xt ? 2 : 1); h++) {
          mbar_wait_bounded(sb + (xt ? kBarX + (i >> 2) * 16 + 8 * h : kBarEpi + i * 8), 0);
          const int ty = i >= 7 ? i - 7 : i;
          if (ty >= 2 && elect()) {
            uint8_t* dst = xt ? g_x + (b * 16 + 2 * j + h) * kTileBytes
                              : g_h + (b * 56 + 1 + (ty == 3 ? 3 * j : 16 * ty - 40 + 2 * j)) * kTileBytes;
            const int piece = (xt && h == 0) ? kTileBytes : kTileBytes / 4;
#pragma unroll 1
            for (int o = 0; o < kTileBytes; o += piece) {
              bulk_store(dst + o, sb + (xt ? kSmX + h * kTileBytes : kSmStg) + o, piece);
              bulk_commit();
              bulk_wait();
            }
            if (!xt) mbar_arrive(sb + kBarFree + i * 8);
          }
          __syncwarp();
          if (elect()) st_release(&g_flag[(i * 16 + b) * 32 + h * 8 + j], epoch);
          __syncwarp();
        }
      }
#pragma unroll 1
      for (int h = 0; h < 2; h++) {
        mbar_wait_bounded(sb + kBarX + 48 + 8 * h, 0);
        if (elect()) {
          tma2d_store(&map_out, sb + kSmX + h * kTileBytes, xcol + j * 128 + h * 64, xrow);
          bulk_commit();
          if (h == 1) bulk_wait_read();
        }
      }
     }
    }
    __syncwarp();
    asm volatile("barrier.cluster.arrive.relaxed.aligned;\nbarrier.cluster.wait.aligned;" ::: "memory");
  } else {
    asm volatile("setmaxnreg.inc.sync.aligned.u32 232;");
    asm volatile("barrier.cluster.wait.aligned;" ::: "memory");
    const int wg = warp >> 2, w = warp & 3;
    const bool rel = (threadIdx.x & 95) == 0;
    const uint32_t rel_addr = mapa(sb + kBarEmpty, w & 1);
    if (wg == 1) TRACE_AT(15, 0);
#define EPOCH (*reinterpret_cast<volatile unsigned*>(sm + kSmEpoch))

#pragma unroll 1
    for (int i = wg; i < kTiles; i += 2) {
      const int layer = i >= 7, ty = i - 7 * layer;
      TRACE_AT(i, 15);
      float acc[2][96];
      if (ty == 2 || ty == 6) {
        const int lane = lane_id();
        const uint32_t xa = sb + kSmX + ((lane >> 4) * 8 + (lane & 7)) * 128 + (((2 * w + ((lane >> 3) & 1)) ^ (lane & 7)) << 4);
        const float up = ty == 6 ? kHScale / kXScale : layer ? 1.f / kXScale : 1.f;
        const float dn = ty == 2 ? kXScale : layer ? 1.f / kHScale : kXScale / kHScale;
#pragma unroll
        for (int h = 0; h < 2; h++) {
          const float* b2 = reinterpret_cast<const float*>(sm + kSmB2) + 64 * h + 16 * w + (lane >> 2);
          const float bias[2] = {ty == 6 ? b2[0] : 0.f, ty == 6 ? b2[8] : 0.f};
#pragma unroll
          for (int p = 0; p < 8; p++) {
            uint32_t r[4];
            ldsm4_t(xa + h * kTileBytes + p * 2048, r);
#pragma unroll
            for (int m = 0; m < 4; m++) {
              acc[h][8 * p + 2 * m] = fmaf(bf_lo(r[m]), up, bias[m & 1]);
              acc[h][8 * p + 2 * m + 1] = fmaf(bf_hi(r[m]), up, bias[m & 1]);
              asm volatile("" : "+f"(acc[h][8 * p + 2 * m]), "+f"(acc[h][8 * p + 2 * m + 1]));
            }
            yield_slot();
          }
        }
        auto stage = [&](int qt) {
          const int h = qt >> 1;
#pragma unroll
          for (int p = 4 * (qt & 1); p < 4 * (qt & 1) + 4; p++) {
            const float* a = &acc[h][8 * p];
            stsm4_t(xa + h * kTileBytes + p * 2048, pack2(a[0] * dn, a[1] * dn), pack2(a[2] * dn, a[3] * dn),
                    pack2(a[4] * dn, a[5] * dn), pack2(a[6] * dn, a[7] * dn));
            yield_slot();
          }
          if (qt & 1) {
            fence_async_smem();
            __syncwarp();
            if (elect()) mbar_arrive(sb + kBarX + (i >> 2) * 16 + 8 * h);
            TRACE_AT(i, 8 + h);
          }
        };
        mainloop<128, kResid>(acc, sb, i, layer * 152 + ty * 16, ty == 6 ? 4 : 0, ty == 6 ? 56 : 16,
                            ty == 2 ? PAUSE_WO : -1, 2 * layer + 1, rel_addr, rel, ty == 2 ? 8 : -1, stage);
        TRACE_AT(i, 2);
        stage(2);
        stage(3);
      } else {
        const int xver = 2 * layer + (ty >= 3);
        const uint32_t stg = sb + kSmStg + w * 4096;
        const float4* vec = reinterpret_cast<const float4*>(sm + kSmV1) + (ty == 3 ? 0 : 64 * ty - 160);
        int lane;
        uint8_t* hdst = g_h + (b * 56 + (ty == 3 ? 3 * j : 16 * ty - 40 + 2 * j)) * kTileBytes + w * 4096;
        float2 st[4];
        unsigned epoch;
        auto pre = [&] {
          lane = lane_id();
          if (ty < 4) mbar_wait(sb + (ty == 1 ? kBarEpi + (i - 1) * 8 : kBarStat + xver * 8), 0);
#pragma unroll
          for (int c = 0; c < 4; c++) st[c] = reinterpret_cast<const float2*>(sm + kSmStat)[32 * w + 8 * c + (lane >> 2)];
          epoch = EPOCH;
        };
        auto team_stats = [&] {
          uint2* stat = g_stat + (xver * 16 + b) * 1024;
          lane = lane_id();
          publish_stats(sb, stat + j * 128, w, lane, EPOCH);
          gather_stats(sm, stat, 32 * w + lane, xver ? 1e-5f * kXScale * kXScale : 1e-5f, EPOCH);
          __syncwarp();
          if (elect()) mbar_arrive(sb + kBarStat + xver * 8);
          TRACE_AT(i, 14);
        };
        if (ty < 4) {
          AttnRegs ar;
          auto odd = [&](int step) {
            if (step == 0) pre();
            else convert_odd(acc, st, ar, step, sm, sb + kBarHalo + (xver + ty) * 24,
                             g_halo + ((layer * 16 + b) * 16 + j + 8 * ty) * 256, (b & 7) != 7, epoch, w, lane);
          };
          head_blocks<192>(acc, sb, layer * 152 + (ty < 2 ? 2 * ty : 48), ty < 2 ? 2 * ty : 1, xver, rel_addr, rel);
          if (ty == 1) {
            if (i == 1) {
              mbar_wait(sb + kBarEpoch, 0);
              mbar_wait(sb + kBarInit, 0);
            }
            team_stats();
            epoch = 0;
#pragma unroll
            for (int c = 0; c < 4; c++) st[c] = reinterpret_cast<const float2*>(sm + kSmStat)[32 * w + 8 * c + (lane >> 2)];
          } else {
            mainloop<192, kPlain>(acc, sb, i, layer * 152 + (ty ? 52 : 4), ty ? 1 : 0, 14, -1, 0, rel_addr, rel, 0, pre);
            TRACE_AT(i, 2);
            if (ty == 3) goto wide_gelu;
          }
          if (layer == 0) mbar_wait(sb + kBarCs + ty * 8, 0);
          add_mean_term(acc, st, sm, ty, lane);
          if (ty == 1) {
            mainloop<192, kStagger>(acc, sb, i, layer * 152 + 18, 2, 14, PAUSE_QKV2, xver, rel_addr, rel, 0, odd);
            TRACE_AT(i, 2);
          } else {
            odd(1);
            odd(2);
            odd(3);
          }
          epilogue_attn(acc, st, ar, sm, sb, layer, ty, b, j, epoch, i, w, lane);
          TRACE_AT(i, 3);
          continue;
        wide_gelu:
          if (i == 3) mbar_wait(sb + kBarCs + 16, 0);
          scale_stats(st);
          fold_norm<16, 24>(acc, st, vec + (lane & 3));
          TRACE_AT(i, 11);
          gelu_chunk<2>(acc, stg, lane, nullptr, [] {});
          TRACE_AT(i, 12);
          fold_norm<0, 2>(acc, st, vec + (lane & 3));
          store_staged(hdst + 2 * kTileBytes, stg);
          fold_norm<2, 16>(acc, st, vec + (lane & 3));
        } else {
          if (ty == 4) {
            head_blocks<128>(acc, sb, layer * 152 + 50, 3, xver, rel_addr, rel);
            team_stats();
            mainloop<128, kPlain>(acc, sb, i, layer * 152 + 66, 4, 14, -1, 0, rel_addr, rel, 0, pre);
          } else {
            mainloop<128, kFresh>(acc, sb, i, layer * 152 + 80, 3, 16, -1, 0, rel_addr, rel, 0, pre);
          }
          TRACE_AT(i, 2);
          if (i == 4) mbar_wait(sb + kBarCs + 16, 0);
          scale_stats(st);
          fold_norm<0, 16>(acc, st, vec + (lane & 3));
        }
        auto own_store_done = [] {
          if (elect()) bulk_wait();
          __syncwarp();
        };
        TRACE_AT(i, 8);
        gelu_chunk<0>(acc, stg, lane, nullptr, [&] {
          if (ty == 3) own_store_done();
          else mbar_wait(sb + kBarFree + (i - 1) * 8, 0);
        });
        TRACE_AT(i, 9);
        gelu_chunk<1>(acc, stg, lane, hdst, own_store_done);
        TRACE_AT(i, 10);
        fence_async_smem();
        __syncwarp();
        if (elect()) mbar_arrive(sb + kBarEpi + i * 8);
      }
      TRACE_AT(i, 3);
    }
#undef EPOCH
    asm volatile("barrier.cluster.arrive.relaxed.aligned;\nbarrier.cluster.wait.aligned;" ::: "memory");
    if (wg == 1) TRACE_AT(15, 2);
  }
}

void build_segments(uint32_t* seg) {
  int n = 0, fine = 0;
  auto per_source = [&] { return 28 + (fine++ & 1); };
  auto add = [&](int ty, int cnt, int kb0, int mode, int wide, int depth5, int dep, int reset) {
    seg[n++] = ty | cnt << 3 | kb0 << 9 | mode << 15 | wide << 17 | depth5 << 18 | dep << 19 | reset << 24;
  };
  for (int l = 0; l < 2; l++) {
    const int t = 7 * l;
    if (l == 0) {
      add(0, 14, 2, kModePlain, 1, 0, 31, 1);
      add(1, 14, 2, kModePlain, 1, 0, 31, 0);
    } else {
      add(0, 2, 0, kModeHead, 1, 0, 31, 1);
      add(1, 2, 0, kModeHead, 1, 0, 31, 0);
      add(0, 7, 0, kModeSkip, 1, 0, per_source(), 0);
      add(0, 7, 1, kModeSkip, 1, 0, 15, 0);
      add(1, 7, 0, kModeSkip, 1, 0, 31, 0);
      add(1, 7, 1, kModeSkip, 1, 0, 31, 0);
    }
    add(2, 4, 0, kModePlain, 0, 0, t, 1);
    add(2, 4, 4, kModePlain, 0, 1, 31, 0);
    add(2, 1, 0, kModeHead, 0, 1, t + 1, 0);
    add(2, 7, 8, kModeSkip, 0, 1, per_source(), 0);
    add(3, 2, 0, kModeHead, 1, 0, 31, 2);
    add(4, 2, 0, kModeHead, 1, 0, 31, 0);
    add(3, 7, 0, kModeSkip, 1, 0, per_source(), 0);
    add(3, 7, 1, kModeSkip, 1, 0, 14 + 2 * l, 0);
    add(4, 4, 0, kModeSkip, 0, 0, 31, 3);
    add(4, 3, 0, kModeContinue, 0, 1, 31, 0);
    add(4, 7, 1, kModeSkip, 0, 1, 31, 0);
    add(5, 16, 0, kModePlain, 0, 1, 31, 0);
    add(6, 24, 0, kModePlain, 0, 1, t + 3, 0);
    add(6, 16, 24, kModePlain, 0, 1, t + 4, 0);
    add(6, 16, 40, kModePlain, 0, 1, t + 5, 0);
  }
}

typedef CUresult (*EncodeTiledFn)(CUtensorMap*, CUtensorMapDataType, cuuint32_t, void*, const cuuint64_t*,
                                  const cuuint64_t*, const cuuint32_t*, const cuuint32_t*, CUtensorMapInterleave,
                                  CUtensorMapSwizzle, CUtensorMapL2promotion, CUtensorMapFloatOOBfill);

CUtensorMap make_map(EncodeTiledFn enc, const void* p, int rank, const cuuint64_t* dims, const cuuint64_t* strides,
                     const cuuint32_t* box, CUtensorMapSwizzle swizzle = CU_TENSOR_MAP_SWIZZLE_128B,
                     CUtensorMapL2promotion promo = CU_TENSOR_MAP_L2_PROMOTION_L2_128B) {
  CUtensorMap m;
  const cuuint32_t es[5] = {1, 1, 1, 1, 1};
  enc(&m, CU_TENSOR_MAP_DATA_TYPE_BFLOAT16, rank, const_cast<void*>(p), dims, strides, box, es,
      CU_TENSOR_MAP_INTERLEAVE_NONE, swizzle, promo,
      CU_TENSOR_MAP_FLOAT_OOB_FILL_NONE);
  return m;
}

CUtensorMap weight_map(EncodeTiledFn enc, const void* p, int k, int n, int blocks) {
  const cuuint64_t dims[3] = {64, (cuuint64_t)k, (cuuint64_t)n / 64};
  const cuuint64_t strides[2] = {(cuuint64_t)n * 2, 128};
  const cuuint32_t box[3] = {64, 32, (cuuint32_t)blocks};
  return make_map(enc, p, 3, dims, strides, box, CU_TENSOR_MAP_SWIZZLE_128B, CU_TENSOR_MAP_L2_PROMOTION_L2_256B);
}

CUtensorMap slab_map(EncodeTiledFn enc, const void* p, int n, int cols, int rows) {
  const cuuint64_t dims[2] = {(cuuint64_t)n, kD};
  const cuuint64_t strides[1] = {(cuuint64_t)n * 2};
  const cuuint32_t box[2] = {(cuuint32_t)cols, (cuuint32_t)rows};
  return make_map(enc, p, 2, dims, strides, box, CU_TENSOR_MAP_SWIZZLE_NONE);
}

CUtensorMap token_map(EncodeTiledFn enc, const void* p, int rows) {
  const cuuint64_t dims[2] = {2 * kD, 1024};
  const cuuint64_t strides[1] = {4 * kD};
  const cuuint32_t box[2] = {64, (cuuint32_t)rows};
  return make_map(enc, p, 2, dims, strides, box);
}

}

extern "C" void kernel_launch(void* const* d_in, const int* in_sizes, int n_in, void* d_out, int out_size) {
  (void)in_sizes; (void)n_in; (void)out_size;
  static EncodeTiledFn enc = nullptr;
  if (!enc) {
    void* fn = nullptr;
    cudaDriverEntryPointQueryResult q;
    cudaGetDriverEntryPoint("cuTensorMapEncodeTiled", &fn, cudaEnableDefault, &q);
    enc = (EncodeTiledFn)fn;
    cudaFuncSetAttribute(fused_layers_kernel, cudaFuncAttributeMaxDynamicSharedMemorySize, kSmBytes);
  }
  Params prm;
  prm.b1 = (const __nv_bfloat16*)d_in[5];
  prm.b2 = (const __nv_bfloat16*)d_in[7];
  build_segments(prm.seg);
  const cuuint64_t qd[3] = {kD, kD, 3}, qs[2] = {3 * kD * 2, kD * 2};
  const cuuint32_t qb[3] = {64, 32, 3};
  const CUtensorMap map_x = token_map(enc, d_in[0], 128);
  const CUtensorMap map_out = token_map(enc, d_out, 128);
  const CUtensorMap map_qkv = make_map(enc, d_in[1], 3, qd, qs, qb);
  const CUtensorMap map_wo = weight_map(enc, d_in[2], kD, kD, 2);
  const CUtensorMap map_w1a = weight_map(enc, d_in[4], kD, kF, 3);
  const CUtensorMap map_w1b = weight_map(enc, d_in[4], kD, kF, 2);
  const CUtensorMap map_w2 = weight_map(enc, d_in[6], kF, kD, 2);
  fused_layers_kernel<<<kGrid, 384, kSmBytes>>>(map_x, map_out, map_qkv, map_wo, map_w1a, map_w1b, map_w2,
                                                slab_map(enc, d_in[1], 3 * kD, 128, 128), slab_map(enc, d_in[4], kF, 128, 128),
                                                slab_map(enc, d_in[1], 3 * kD, 16, 128), prm);
}
```

```cpp
#include <cuda.h>
#include <cuda_bf16.h>
#include <cuda_runtime.h>
#include <stdint.h>

namespace {

constexpr int kD = 1024;
constexpr int kF = 3584;
constexpr int kCtas = 128;
constexpr int kGrid = 132;
constexpr int kTiles = 14;
constexpr int kTileBytes = 16384;

constexpr int kSmRing = 0;
constexpr int kSmX = 163840;
constexpr int kSmStg = kSmX + 32768;
constexpr int kSmHalo = kSmStg + 16384;
constexpr int kSmCsQ = kSmHalo + 6144;
constexpr int kSmV1 = kSmCsQ + 384 * 4;
constexpr int kSmB2 = kSmV1 + 448 * 8;
constexpr int kSmStat = kSmB2 + 128 * 4;
constexpr int kSmBar = kSmStat + 128 * 8;
constexpr int kBarFull = kSmBar;
constexpr int kBarTurn = kBarFull + 8 * 8;
constexpr int kBarReady = kBarTurn + 14 * 8;
constexpr int kBarSrc = kBarReady + 17 * 8;
constexpr int kBarPause = kBarSrc + 8 * 8;
constexpr int kBarFree = kBarPause + 4 * 8;
constexpr int kBarCs = kBarFree + 14 * 8;
constexpr int kBarSlab = kBarCs + 3 * 8;
constexpr int kBarHalo = kBarSlab + 4 * 8;
constexpr int kBarInit = kBarHalo + 12 * 8;
constexpr int kBarEpoch = kBarInit + 8;
constexpr int kBarEmpty = kBarTurn + 5 * 128;
constexpr int kBarEpi = kBarEmpty + 128;
constexpr int kBarX = kBarEpi + 14 * 8;
constexpr int kBarStat = kBarX + 8 * 8;
constexpr int kBarResume = kBarStat + 4 * 8;
constexpr int kSmEpoch = kBarEpi + 2 * 128;
static_assert(kBarEpoch < kBarEmpty && kBarResume + 4 * 8 <= kSmEpoch, "barrier groups overflow");
constexpr int kSmBytes = kSmEpoch + 16 + 256;
constexpr int kSegs = 38;

constexpr int kFlagLines = kTiles * 16;

constexpr float kXScale = 1.f / 16.f;

constexpr unsigned kSpinLimit = 1u << 22;

__device__ __align__(1024) uint8_t g_x[16 * 16 * kTileBytes];
__device__ __align__(1024) uint8_t g_o[16 * 16 * kTileBytes];
__device__ __align__(1024) uint8_t g_h[16 * 56 * kTileBytes];
__device__ __align__(128) uint2 g_stat[4 * 16 * 128 * 8];
__device__ __align__(128) unsigned g_cs[3 * kD + kF + 3 * kD];
__device__ __align__(128) uint4 g_halo[2 * 16 * 16 * 256];
__device__ __align__(128) unsigned g_flag[kFlagLines * 32];
__device__ unsigned g_ticket;

#define TRACE_AT(tile, k)
#define TRACE_PUB(i, k, c)
#define TRACE_ISSUE(which, nb)

struct Params {
  const __nv_bfloat16* b1;
  const __nv_bfloat16* b2;
  uint32_t seg[kSegs];
};

__device__ __forceinline__ uint32_t smem_u32(const void* p) {
  return (uint32_t)__cvta_generic_to_shared(p);
}
__device__ __forceinline__ uint32_t mapa(uint32_t a, uint32_t cta) {
  uint32_t r;
  asm("mapa.shared::cluster.u32 %0, %1, %2;" : "=r"(r) : "r"(a), "r"(cta));
  return r;
}
__device__ __forceinline__ void mbar_init(uint32_t bar, int cnt) {
  asm volatile("mbarrier.init.shared::cta.b64 [%0], %1;" ::"r"(bar), "r"(cnt) : "memory");
}
__device__ __forceinline__ void mbar_expect_tx(uint32_t bar, uint32_t bytes) {
  asm volatile("mbarrier.arrive.expect_tx.shared::cta.b64 _, [%0], %1;" ::"r"(bar), "r"(bytes) : "memory");
}
__device__ __forceinline__ void mbar_arrive(uint32_t bar) {
  asm volatile("mbarrier.arrive.shared::cta.b64 _, [%0];" ::"r"(bar) : "memory");
}
__device__ __forceinline__ void mbar_arrive_cluster(uint32_t cluster_addr) {
  asm volatile("mbarrier.arrive.shared::cluster.b64 _, [%0];" ::"r"(cluster_addr) : "memory");
}
__device__ __forceinline__ void mbar_wait(uint32_t bar, uint32_t parity) {
  asm volatile("{\n.reg .pred p;\nRETRY:\nmbarrier.try_wait.parity.shared::cta.b64 p, [%0], %1;\n"
               "@!p bra.uni RETRY;\n}" ::"r"(bar), "r"(parity) : "memory");
}
__device__ __forceinline__ void mbar_wait_bounded(uint32_t bar, uint32_t parity) {
  asm volatile("{\n.reg .pred p;\n.reg .u32 c;\nmov.u32 c, 0;\nRETRY:\n"
               "mbarrier.try_wait.parity.shared::cta.b64 p, [%0], %1;\n@p bra.uni DONE;\n"
               "add.u32 c, c, 1;\nsetp.lt.u32 p, c, %2;\n@p bra.uni RETRY;\ntrap;\nDONE:\n}"
               ::"r"(bar), "r"(parity), "n"(1u << 19) : "memory");
}
__device__ __forceinline__ void tma3d(uint32_t dst, const CUtensorMap* m, uint32_t bar, int c0, int c1, int c2) {
  asm volatile(
      "cp.async.bulk.tensor.3d.shared::cluster.global.mbarrier::complete_tx::bytes [%0], [%1, {%3, %4, %5}], [%2];"
      ::"r"(dst), "l"(m), "r"(bar), "r"(c0), "r"(c1), "r"(c2) : "memory");
}
__device__ __forceinline__ void tma3d_mc(uint32_t dst, const CUtensorMap* m, uint32_t bar, int c0, int c1, int c2) {
  asm volatile(
      "cp.async.bulk.tensor.3d.shared::cluster.global.mbarrier::complete_tx::bytes.multicast::cluster"
      " [%0], [%1, {%3, %4, %5}], [%2], %6;"
      ::"r"(dst), "l"(m), "r"(bar), "r"(c0), "r"(c1), "r"(c2), "h"((uint16_t)3) : "memory");
}
__device__ __forceinline__ void tma2d(uint32_t dst, const CUtensorMap* m, uint32_t bar, int c0, int c1) {
  asm volatile(
      "cp.async.bulk.tensor.2d.shared::cluster.global.mbarrier::complete_tx::bytes [%0], [%1, {%3, %4}], [%2];"
      ::"r"(dst), "l"(m), "r"(bar), "r"(c0), "r"(c1) : "memory");
}
__device__ __forceinline__ void tma2d_store(const CUtensorMap* m, uint32_t src, int c0, int c1) {
  asm volatile("cp.async.bulk.tensor.2d.global.shared::cta.bulk_group [%0, {%2, %3}], [%1];"
               ::"l"(m), "r"(src), "r"(c0), "r"(c1) : "memory");
}
__device__ __forceinline__ int lane_id() {
  int l;
  asm volatile("mov.u32 %0, %%laneid;" : "=r"(l));
  return l;
}
__device__ __forceinline__ bool elect() {
  uint32_t p;
  asm volatile("{\n.reg .pred p;\nelect.sync _|p, 0xffffffff;\nselp.b32 %0, 1, 0, p;\n}" : "=r"(p));
  return p;
}
__device__ __forceinline__ void bulk_load(uint32_t dst, const void* src, uint32_t bytes, uint32_t bar) {
  asm volatile("cp.async.bulk.shared::cluster.global.mbarrier::complete_tx::bytes [%0], [%1], %2, [%3];"
               ::"r"(dst), "l"(src), "r"(bytes), "r"(bar) : "memory");
}
__device__ __forceinline__ void bulk_store(void* dst, uint32_t src, uint32_t bytes) {
  asm volatile("cp.async.bulk.global.shared::cta.bulk_group [%0], [%1], %2;" ::"l"(dst), "r"(src), "r"(bytes)
               : "memory");
}
__device__ __forceinline__ void bulk_commit() { asm volatile("cp.async.bulk.commit_group;" ::: "memory"); }
__device__ __forceinline__ void bulk_wait_read() { asm volatile("cp.async.bulk.wait_group.read 0;" ::: "memory"); }
__device__ __forceinline__ void bulk_wait() { asm volatile("cp.async.bulk.wait_group 0;" ::: "memory"); }
__device__ __forceinline__ void fence_async_smem() { asm volatile("fence.proxy.async.shared::cta;" ::: "memory"); }
__device__ __forceinline__ unsigned ld_relaxed(const unsigned* p) {
  unsigned v;
  asm volatile("ld.relaxed.gpu.global.u32 %0, [%1];" : "=r"(v) : "l"(p) : "memory");
  return v;
}
__device__ __forceinline__ uint2 ld_relaxed2(const uint2* p) {
  uint2 v;
  asm volatile("ld.relaxed.gpu.global.v2.u32 {%0, %1}, [%2];" : "=r"(v.x), "=r"(v.y) : "l"(p) : "memory");
  return v;
}
__device__ __forceinline__ void st_relaxed(unsigned* p, unsigned v) {
  asm volatile("st.relaxed.gpu.global.u32 [%0], %1;" ::"l"(p), "r"(v) : "memory");
}
__device__ __forceinline__ void st_release(unsigned* p, unsigned v) {
  asm volatile("st.release.gpu.global.u32 [%0], %1;" ::"l"(p), "r"(v) : "memory");
}
__device__ __forceinline__ void wait_flags(const unsigned* p, unsigned epoch) {
  unsigned spins = 0;
  while (true) {
    const unsigned v = ld_relaxed(p);
    if (__all_sync(0xffffffffu, v == epoch)) break;
    if (++spins > kSpinLimit) __trap();
  }
  asm volatile("fence.acquire.gpu;\nfence.proxy.async.global;" ::: "memory");
  __syncwarp();
}
__device__ __forceinline__ void st_packet(uint4* p, uint32_t d0, uint32_t d1, uint32_t tag) {
  asm volatile("{\n.reg .b128 v;\n.reg .b64 x, y;\nmov.b64 x, {%1, %2};\nmov.b64 y, {%3, %3};\nmov.b128 v, {x, y};\n"
               "st.relaxed.gpu.global.b128 [%0], v;\n}" ::"l"(p), "r"(d0), "r"(d1), "r"(tag) : "memory");
}
__device__ __forceinline__ void ld_packet(const uint4* p, uint32_t& d0, uint32_t& d1, uint32_t& tag) {
  asm volatile("{\n.reg .b128 v;\n.reg .b64 x, y;\n.reg .b32 u;\nld.relaxed.gpu.global.b128 v, [%3];\n"
               "mov.b128 {x, y}, v;\nmov.b64 {%0, %1}, x;\nmov.b64 {%2, u}, y;\n}"
               : "=r"(d0), "=r"(d1), "=r"(tag) : "l"(p) : "memory");
}
__device__ __forceinline__ unsigned tag_value(float v, unsigned epoch) {
  return (__float_as_uint(v) & ~7u) | (epoch & 7u);
}
__device__ __forceinline__ float untag_value(unsigned v) { return __uint_as_float(v & ~7u); }
__device__ __forceinline__ void stsm4(uint32_t a, uint32_t r0, uint32_t r1, uint32_t r2, uint32_t r3) {
  asm volatile("stmatrix.sync.aligned.m8n8.x4.shared.b16 [%0], {%1, %2, %3, %4};" ::"r"(a), "r"(r0), "r"(r1),
               "r"(r2), "r"(r3) : "memory");
}
__device__ __forceinline__ void stsm4_t(uint32_t a, uint32_t r0, uint32_t r1, uint32_t r2, uint32_t r3) {
  asm volatile("stmatrix.sync.aligned.m8n8.x4.trans.shared.b16 [%0], {%1, %2, %3, %4};" ::"r"(a), "r"(r0),
               "r"(r1), "r"(r2), "r"(r3) : "memory");
}
__device__ __forceinline__ uint32_t transpose8(uint32_t a) {
  uint32_t d;
  asm volatile("movmatrix.sync.aligned.m8n8.trans.b16 %0, %1;" : "=r"(d) : "r"(a));
  return d;
}
__device__ __forceinline__ void mma16816(float (&c)[4], uint32_t a0, uint32_t a1, uint32_t a2, uint32_t a3,
                                         uint32_t b0, uint32_t b1) {
  asm volatile("mma.sync.aligned.m16n8k16.row.col.f32.bf16.bf16.f32 {%0, %1, %2, %3}, {%4, %5, %6, %7}, {%8, %9}, "
               "{%0, %1, %2, %3};"
               : "+f"(c[0]), "+f"(c[1]), "+f"(c[2]), "+f"(c[3])
               : "r"(a0), "r"(a1), "r"(a2), "r"(a3), "r"(b0), "r"(b1));
}
__device__ __forceinline__ void mma1688(float (&c)[4], uint32_t a0, uint32_t a1, uint32_t b0) {
  asm volatile("mma.sync.aligned.m16n8k8.row.col.f32.bf16.bf16.f32 {%0, %1, %2, %3}, {%4, %5}, {%6}, {%0, %1, %2, %3};"
               : "+f"(c[0]), "+f"(c[1]), "+f"(c[2]), "+f"(c[3]) : "r"(a0), "r"(a1), "r"(b0));
}
__device__ __forceinline__ float shfl_xor(float v, int m) {
  float r;
  asm volatile("shfl.sync.bfly.b32 %0, %1, %2, 31, 0xffffffff;" : "=f"(r) : "f"(v), "r"(m));
  return r;
}
__device__ __forceinline__ float tanh_fast(float x) {
  float r;
  asm volatile("tanh.approx.f32 %0, %1;" : "=f"(r) : "f"(x));
  return r;
}
__device__ __forceinline__ void ldsm4(uint32_t a, uint32_t (&r)[4]) {
  asm volatile("ldmatrix.sync.aligned.m8n8.x4.shared.b16 {%0, %1, %2, %3}, [%4];"
               : "=r"(r[0]), "=r"(r[1]), "=r"(r[2]), "=r"(r[3]) : "r"(a) : "memory");
}
__device__ __forceinline__ void ldsm4_t(uint32_t a, uint32_t (&r)[4]) {
  asm volatile("ldmatrix.sync.aligned.m8n8.x4.trans.shared.b16 {%0, %1, %2, %3}, [%4];"
               : "=r"(r[0]), "=r"(r[1]), "=r"(r[2]), "=r"(r[3]) : "r"(a) : "memory");
}
__device__ __forceinline__ uint32_t pack2(float lo, float hi) {
  uint32_t r;
  asm volatile("cvt.rn.bf16x2.f32 %0, %1, %2;" : "=r"(r) : "f"(hi), "f"(lo));
  return r;
}
__device__ __forceinline__ float bf_lo(uint32_t r) { return __uint_as_float(r << 16); }
__device__ __forceinline__ float bf_hi(uint32_t r) { return __uint_as_float(r & 0xffff0000u); }
__device__ __forceinline__ float ex2(float x) {
  float r;
  asm("ex2.approx.ftz.f32 %0, %1;" : "=f"(r) : "f"(x));
  return r;
}
__device__ __forceinline__ float rcp(float x) {
  float r;
  asm("rcp.approx.ftz.f32 %0, %1;" : "=f"(r) : "f"(x));
  return r;
}
template <int N>
__device__ __forceinline__ void wg_wait() {
  asm volatile("wgmma.wait_group.sync.aligned %0;" ::"n"(N) : "memory");
}
__device__ __forceinline__ void yield_slot() { asm volatile("pmevent 0;"); }

template <int N, int KIND>
__device__ __forceinline__ void mma_kblock(float (&acc)[2][96], uint32_t a, uint32_t b);

#define F8(m, d, i) m(d[i]), m(d[i + 1]), m(d[i + 2]), m(d[i + 3]), m(d[i + 4]), m(d[i + 5]), m(d[i + 6]), m(d[i + 7])
#define KSTEP(N, A, B, oa0, oa1, ob, sd)                                                   \
  "mov.b64 db, {" B ", hb};\nadd.u64 db, db, " #ob ";\n"                                    \
  "mov.b64 da, {" A ", ha};\nadd.u64 da, da, " #oa0 ";\n"                                   \
  "wgmma.mma_async.sync.aligned.m64n" #N "k16.f32.bf16.bf16 {" ACC##N##_0 "}, da, db, " #sd ", 1, 1, 0, 1;\n" \
  "mov.b64 da, {" A ", ha};\nadd.u64 da, da, " #oa1 ";\n"                                   \
  "wgmma.mma_async.sync.aligned.m64n" #N "k16.f32.bf16.bf16 {" ACC##N##_1 "}, da, db, " #sd ", 1, 1, 0, 1;\n"

#define MMA_KBLOCK(N, KIND, A, B, ob2, ob3, sd, MID, MODE)                                 \
  template <>                                                                              \
  __device__ __forceinline__ void mma_kblock<N, KIND>(float (&acc)[2][96], uint32_t a, uint32_t b) { \
    asm volatile("{\n.reg .b32 ha, hb;\n.reg .b64 da, db;\n"                            \
                 "mov.b32 ha, 0x40000080;\nmov.b32 hb, 0x40000040;\n"                       \
                 "wgmma.fence.sync.aligned;\n"                                             \
                 KSTEP(N, A, B, 0, 64, 0, sd) KSTEP(N, A, B, 2, 66, 128, 1) MID               \
                 KSTEP(N, A, B, 4, 68, ob2, 1) KSTEP(N, A, B, 6, 70, ob3, 1) "wgmma.commit_group.sync.aligned;\n}\n"  \
                 : OPS##N(MODE) : "r"(a), "r"(b) : "memory");                              \
  }
#define MMA_KBLOCKS(N, A, B, ob2, ob3)                                                     \
  MMA_KBLOCK(N, 0, A, B, ob2, ob3, 1, "", "+f")                                            \
  MMA_KBLOCK(N, 1, A, B, ob2, ob3, 1, "wgmma.commit_group.sync.aligned;\n", "+f")          \
  MMA_KBLOCK(N, 2, A, B, ob2, ob3, 0, "", "=f")

#define ACC128_0 \
  "%0, %1, %2, %3, %4, %5, %6, %7, %8, %9, %10, %11, %12, %13, %14, %15, " \
  "%16, %17, %18, %19, %20, %21, %22, %23, %24, %25, %26, %27, %28, %29, %30, %31, " \
  "%32, %33, %34, %35, %36, %37, %38, %39, %40, %41, %42, %43, %44, %45, %46, %47, " \
  "%48, %49, %50, %51, %52, %53, %54, %55, %56, %57, %58, %59, %60, %61, %62, %63"
#define ACC128_1 \
  "%64, %65, %66, %67, %68, %69, %70, %71, %72, %73, %74, %75, %76, %77, %78, %79, " \
  "%80, %81, %82, %83, %84, %85, %86, %87, %88, %89, %90, %91, %92, %93, %94, %95, " \
  "%96, %97, %98, %99, %100, %101, %102, %103, %104, %105, %106, %107, %108, %109, %110, %111, " \
  "%112, %113, %114, %115, %116, %117, %118, %119, %120, %121, %122, %123, %124, %125, %126, %127"
#define OPS128(m) \
  F8(m, acc[0], 0), F8(m, acc[0], 8), F8(m, acc[0], 16), F8(m, acc[0], 24), F8(m, acc[0], 32), F8(m, acc[0], 40), F8(m, acc[0], 48), F8(m, acc[0], 56), \
        F8(m, acc[1], 0), F8(m, acc[1], 8), F8(m, acc[1], 16), F8(m, acc[1], 24), F8(m, acc[1], 32), F8(m, acc[1], 40), F8(m, acc[1], 48), F8(m, acc[1], 56)
MMA_KBLOCKS(128, "%128", "%129", 512, 640)

#define ACC192_0 \
  "%0, %1, %2, %3, %4, %5, %6, %7, %8, %9, %10, %11, %12, %13, %14, %15, " \
  "%16, %17, %18, %19, %20, %21, %22, %23, %24, %25, %26, %27, %28, %29, %30, %31, " \
  "%32, %33, %34, %35, %36, %37, %38, %39, %40, %41, %42, %43, %44, %45, %46, %47, " \
  "%48, %49, %50, %51, %52, %53, %54, %55, %56, %57, %58, %59, %60, %61, %62, %63, " \
  "%64, %65, %66, %67, %68, %69, %70, %71, %72, %73, %74, %75, %76, %77, %78, %79, " \
  "%80, %81, %82, %83, %84, %85, %86, %87, %88, %89, %90, %91, %92, %93, %94, %95"
#define ACC192_1 \
  "%96, %97, %98, %99, %100, %101, %102, %103, %104, %105, %106, %107, %108, %109, %110, %111, " \
  "%112, %113, %114, %115, %116, %117, %118, %119, %120, %121, %122, %123, %124, %125, %126, %127, " \
  "%128, %129, %130, %131, %132, %133, %134, %135, %136, %137, %138, %139, %140, %141, %142, %143, " \
  "%144, %145, %146, %147, %148, %149, %150, %151, %152, %153, %154, %155, %156, %157, %158, %159, " \
  "%160, %161, %162, %163, %164, %165, %166, %167, %168, %169, %170, %171, %172, %173, %174, %175, " \
  "%176, %177, %178, %179, %180, %181, %182, %183, %184, %185, %186, %187, %188, %189, %190, %191"
#define OPS192(m) \
  F8(m, acc[0], 0), F8(m, acc[0], 8), F8(m, acc[0], 16), F8(m, acc[0], 24), F8(m, acc[0], 32), F8(m, acc[0], 40), F8(m, acc[0], 48), F8(m, acc[0], 56), F8(m, acc[0], 64), F8(m, acc[0], 72), F8(m, acc[0], 80), F8(m, acc[0], 88), \
        F8(m, acc[1], 0), F8(m, acc[1], 8), F8(m, acc[1], 16), F8(m, acc[1], 24), F8(m, acc[1], 32), F8(m, acc[1], 40), F8(m, acc[1], 48), F8(m, acc[1], 56), F8(m, acc[1], 64), F8(m, acc[1], 72), F8(m, acc[1], 80), F8(m, acc[1], 88)
MMA_KBLOCKS(192, "%192", "%193", 768, 896)

#define HSTEP(oa, ob)                                                                       \
  "mov.b64 db, {%97, hb};\nadd.u64 db, db, " #ob ";\nmov.b64 da, {%96, ha};\nadd.u64 da, da, " #oa ";\n" \
  "wgmma.mma_async.sync.aligned.m64n192k16.f32.bf16.bf16 {" ACC192_0 "}, da, db, 1, 1, 1, 0, 1;\n"
__device__ __forceinline__ void mma_half(float (&d)[96], uint32_t a, uint32_t b) {
  asm volatile("{\n.reg .b32 ha, hb;\n.reg .b64 da, db;\nmov.b32 ha, 0x40000080;\nmov.b32 hb, 0x40000040;\n"
               "wgmma.fence.sync.aligned;\n" HSTEP(0, 0) HSTEP(2, 128) HSTEP(4, 768) HSTEP(6, 896)
               "wgmma.commit_group.sync.aligned;\n}\n"
               : F8("+f", d, 0), F8("+f", d, 8), F8("+f", d, 16), F8("+f", d, 24), F8("+f", d, 32), F8("+f", d, 40),
                 F8("+f", d, 48), F8("+f", d, 56), F8("+f", d, 64), F8("+f", d, 72), F8("+f", d, 80), F8("+f", d, 88)
               : "r"(a), "r"(b) : "memory");
}

#define TSTEP(REGS, W, X, ow, ox)                                                           \
  "mov.b64 db, {" X ", hi};\nadd.u64 db, db, " #ox ";\nmov.b64 da, {" W ", hi};\nadd.u64 da, da, " #ow ";\n" \
  "wgmma.mma_async.sync.aligned.m64n128k16.f32.bf16.bf16 {" REGS "}, da, db, 1, 1, 1, 1, 0;\n"
#define THEAD "{\n.reg .b32 hi;\n.reg .b64 da, db;\nmov.b32 hi, 0x40000040;\nwgmma.fence.sync.aligned;\n"
#define TTAIL "wgmma.commit_group.sync.aligned;\n}\n"
__device__ __forceinline__ void mma_kblock_t(float (&acc)[2][96], uint32_t wd, uint32_t xd) {
  asm volatile(THEAD TSTEP(ACC128_0, "%128", "%129", 0, 0) TSTEP(ACC128_1, "%128", "%129", 256, 0)
               TSTEP(ACC128_0, "%128", "%129", 128, 2) TSTEP(ACC128_1, "%128", "%129", 384, 2)
               TSTEP(ACC128_0, "%128", "%129", 512, 4) TSTEP(ACC128_1, "%128", "%129", 768, 4)
               TSTEP(ACC128_0, "%128", "%129", 640, 6) TSTEP(ACC128_1, "%128", "%129", 896, 6) TTAIL
               : OPS128("+f") : "r"(wd), "r"(xd) : "memory");
}
__device__ __forceinline__ void mma_half_t(float (&d)[96], uint32_t wd, uint32_t xd) {
  asm volatile(THEAD TSTEP(ACC128_0, "%64", "%65", 0, 0) TSTEP(ACC128_0, "%64", "%65", 128, 2)
               TSTEP(ACC128_0, "%64", "%65", 512, 4) TSTEP(ACC128_0, "%64", "%65", 640, 6) TTAIL
               : F8("+f", d, 0), F8("+f", d, 8), F8("+f", d, 16), F8("+f", d, 24), F8("+f", d, 32), F8("+f", d, 40),
                 F8("+f", d, 48), F8("+f", d, 56) : "r"(wd), "r"(xd) : "memory");
}

enum { kModePlain = 0, kModeHead = 1, kModeSkip = 2, kModeContinue = 3 };

template <int N>
__device__ __forceinline__ void fence_acc(float (&acc)[2][96]) {
#pragma unroll
  for (int h = 0; h < 2; h++)
#pragma unroll
    for (int i = 0; i < N / 2; i++) asm volatile("" : "+f"(acc[h][i])::"memory");
}

constexpr uint32_t kToB = (kTileBytes >> 4) + ((4096u >> 4) << 16) - (1u << 16);

#define TRACE_KB(nb)

template <int N>
__device__ __forceinline__ void head_blocks(float (&acc)[2][96], uint32_t sb, int n0, int slot, int xver,
                                            uint32_t rel_addr, bool rel) {
  const uint32_t ring = (((sb & 0x3FFFF) + kSmRing) >> 4) | (1u << 16);
  const uint32_t xdesc = (((sb & 0x3FFFF) + kSmX) >> 4) | (1u << 16);
  const uint32_t s0 = ring + slot * 2560, s1 = ring + ((slot + 1) & 3) * 2560;
  const uint32_t nb = n0 * 8, xbar = sb + kBarX + (xver - 1) * 16;
  if (xver > 0) {
    mbar_wait(xbar, 0);
    mbar_wait(sb + kBarTurn + (xver == 1 ? 2 : 3 * xver) * 8, 0);
  }
  mbar_wait(sb + kBarFull + (nb & 56), nb >> 6);
  if (n0 == 0) TRACE_AT(0, 1);
  TRACE_KB(nb);
  mma_kblock<N, 2>(acc, xver > 0 ? xdesc : s0, s0 + kToB);
  if (xver > 0) mbar_wait(xbar + 8, 0);
  mbar_wait(sb + kBarFull + (nb & 56) + 8, nb >> 6);
  TRACE_KB(nb + 8);
  mma_kblock<N, 0>(acc, xver > 0 ? xdesc + (kTileBytes >> 4) : s1, s1 + kToB);
  wg_wait<1>();
  if (rel) mbar_arrive_cluster(rel_addr + (nb & 56));
  wg_wait<0>();
  if (rel) mbar_arrive_cluster(rel_addr + (nb & 56) + 8);
  fence_acc<N>(acc);
}

enum { kPlain, kFresh, kResid, kStagger };
template <int N, int KIND, class Pre>
__device__ __forceinline__ void mainloop(float (&acc)[2][96], uint32_t sb, int tile, int n0, int slot, int nkb,
                                         int pause_kk, int att, uint32_t rel_addr, bool rel, int own_kk, Pre pre) {
  constexpr bool RESID = KIND == kResid, FRESH = KIND == kFresh;
  constexpr uint32_t kStep = (N == 192 ? 5 : 4) * 512;
  const uint32_t ring = (((sb & 0x3FFFF) + kSmRing) >> 4) | (1u << 16);
  uint32_t st = ring + slot * kStep;
  uint32_t nb = n0 * 8, prev = 64;
  const uint32_t last = nb + 8 * (nkb - (RESID ? 4 : KIND == kStagger ? 2 : 1)), own = nb + 8 * own_kk;
  const uint32_t stg = (((sb & 0x3FFFF) + kSmStg) >> 4) | (1u << 16);
  uint32_t stop = pause_kk >= 0 ? nb + 8 * pause_kk : last;
  const bool signal = (threadIdx.x & 127) == 64;
  if (!FRESH) fence_acc<N>(acc);
  if (tile > 0) mbar_wait(sb + kBarTurn + (tile - 1) * 8, 0);
  TRACE_AT(tile, 0);
  if constexpr (FRESH) {
    mbar_wait(sb + kBarFull + (nb & 56), nb >> 6);
    TRACE_KB(nb);
    mma_kblock<N, 2>(acc, st, st + kToB);
    prev = nb & 56;
    st += kStep;
    nb += 8;
  }
#pragma unroll 1
  while (true) {
#pragma unroll 1
    do {
      mbar_wait(sb + kBarFull + (nb & 56), nb >> 6);
      TRACE_KB(nb);
      if constexpr (RESID) mma_kblock_t(acc, st + kToB, nb == own ? stg : st);
      else mma_kblock<N, 0>(acc, st, st + kToB);
      wg_wait<1>();
      if (rel) mbar_arrive_cluster(rel_addr + prev);
      prev = nb & 56;
      st += kStep;
      if (st == ring + 10240) st = ring;
      nb += 8;
    } while (nb != stop);
    if (stop == last) break;
    stop = last;
    if (signal) mbar_arrive(sb + kBarPause + att * 8);
    wg_wait<0>();
    if (rel) mbar_arrive_cluster(rel_addr + prev);
    prev = 64;
    mbar_wait(sb + kBarResume + att * 8, 0);
  }
  mbar_wait(sb + kBarFull + (nb & 56), nb >> 6);
  TRACE_KB(nb);
  if constexpr (RESID) {
    const uint32_t z = gridDim.y - 1;
    const uint32_t s1 = st + kStep, s2 = s1 + kStep, s3 = s2 == ring + 8192 ? ring : s2 + kStep;
    mma_half_t(acc[0], st + kToB, st);
    wg_wait<1>();
    if (rel) mbar_arrive_cluster(rel_addr + 24);
    mbar_wait(sb + kBarFull + 40, nb >> 6);
    TRACE_KB(nb + 8);
    mma_half_t(acc[0], s1 + kToB, s1);
    mbar_wait(sb + kBarFull + 48, nb >> 6);
    TRACE_KB(nb + 16);
    mma_half_t(acc[0], s2 + kToB, s2);
    mbar_wait(sb + kBarFull + 56, nb >> 6);
    TRACE_KB(nb + 24);
    mma_half_t(acc[0], s3 + kToB, s3);
    mma_half_t(acc[1], st + kToB + 256, st + z);
    mma_half_t(acc[1], s1 + kToB + 256, s1 + z);
    wg_wait<2>();
#pragma unroll
    for (int i = 0; i < 64; i++) asm volatile("" : "+f"(acc[0][i])::"memory");
    pre(0);
    mma_half_t(acc[1], s2 + kToB + 256, s2 + z);
    wg_wait<2>();
    if (rel) mbar_arrive_cluster(rel_addr + 32);
    pre(1);
    mma_half_t(acc[1], s3 + kToB + 256, s3 + z);
    wg_wait<2>();
    if (rel) mbar_arrive_cluster(rel_addr + 40);
    wg_wait<1>();
    if (signal) mbar_arrive(sb + kBarTurn + tile * 8);
    if (rel) mbar_arrive_cluster(rel_addr + 48);
    wg_wait<0>();
    if (rel) mbar_arrive_cluster(rel_addr + 56);
#pragma unroll
    for (int i = 0; i < 64; i++) asm volatile("" : "+f"(acc[1][i])::"memory");
  } else if constexpr (KIND == kStagger) {
    const uint32_t z = gridDim.y - 1, s2 = st + kStep;
    mma_half(acc[1], st + 64, st + kToB);
    wg_wait<1>();
    if (rel) mbar_arrive_cluster(rel_addr + 40);
    mbar_wait(sb + kBarFull + 56, nb >> 6);
    TRACE_KB(nb + 8);
    mma_half(acc[1], s2 + 64, s2 + kToB);
    mma_half(acc[0], st, st + z + kToB);
    pre(0);
    mma_half(acc[0], s2, s2 + z + kToB);
    wg_wait<2>();
#pragma unroll
    for (int i = 0; i < 96; i++) asm volatile("" : "+f"(acc[1][i])::"memory");
    pre(1);
    wg_wait<1>();
    if (rel) mbar_arrive_cluster(rel_addr + 48);
    pre(2);
    if (signal) mbar_arrive(sb + kBarTurn + tile * 8);
    pre(3);
    wg_wait<0>();
    if (rel) mbar_arrive_cluster(rel_addr + 56);
#pragma unroll
    for (int i = 0; i < 96; i++) asm volatile("" : "+f"(acc[0][i])::"memory");
  } else {
    mma_kblock<N, 1>(acc, st, st + kToB);
    wg_wait<2>();
    if (rel) mbar_arrive_cluster(rel_addr + prev);
    pre();
    wg_wait<1>();
    if (signal) mbar_arrive(sb + kBarTurn + tile * 8);
    wg_wait<0>();
    if (rel) mbar_arrive_cluster(rel_addr + (nb & 56));
    fence_acc<N>(acc);
  }
}

__device__ __forceinline__ void publish_stats(uint32_t sb, uint2* stat, int w, int lane, unsigned epoch) {
  const uint32_t row = sb + kSmX + (32 * w + lane) * 128;
  float s[4], q[4];
#pragma unroll
  for (int c = 0; c < 4; c++) s[c] = q[c] = 0.f;
  uint32_t nx[4];
  ldsm4(row + ((lane & 7) << 4), nx);
#pragma unroll 1
  for (int J = 1; J <= 16; J++) {
    const uint32_t r[4] = {nx[0], nx[1], nx[2], nx[3]};
    ldsm4(row + ((J >> 3) & 1) * kTileBytes + (((J ^ lane) & 7) << 4), nx);
#pragma unroll
    for (int c = 0; c < 4; c++) {
      const float lo = bf_lo(r[c]);
      s[c] += lo;
      q[c] = fmaf(lo, lo, q[c]);
      if (c & 1) yield_slot();
    }
#pragma unroll
    for (int c = 0; c < 4; c++) {
      const float hi = bf_hi(r[c]);
      s[c] += hi;
      q[c] = fmaf(hi, hi, q[c]);
      if (c & 1) yield_slot();
    }
  }
  const int t = lane & 3, g = lane >> 2;
#pragma unroll
  for (int c = 0; c < 2; c++) {
    s[c] = (t & 2 ? s[c + 2] : s[c]) + shfl_xor(t & 2 ? s[c] : s[c + 2], 2);
    q[c] = (t & 2 ? q[c + 2] : q[c]) + shfl_xor(t & 2 ? q[c] : q[c + 2], 2);
  }
  const float so = (t & 1 ? s[1] : s[0]) + shfl_xor(t & 1 ? s[0] : s[1], 1);
  const float qo = (t & 1 ? q[1] : q[0]) + shfl_xor(t & 1 ? q[0] : q[1], 1);
  asm volatile("st.relaxed.gpu.global.v2.u32 [%0], {%1, %2};" ::"l"(stat + 32 * w + 8 * t + g),
               "r"(tag_value(so, epoch)), "r"(tag_value(qo, epoch)) : "memory");
}

__device__ __forceinline__ void add_chunk(float (&a)[8], const uint4& v) {
  a[0] += bf_lo(v.x); a[1] += bf_hi(v.x);
  a[2] += bf_lo(v.y); a[3] += bf_hi(v.y);
  a[4] += bf_lo(v.z); a[5] += bf_hi(v.z);
  a[6] += bf_lo(v.w); a[7] += bf_hi(v.w);
}

__device__ __forceinline__ int helper_col(int id, int slab) {
  return (slab < 3 ? slab * kD : (slab - 3) * 512) + id * 128;
}
__device__ __forceinline__ void helper_cta(const CUtensorMap* map_q, const CUtensorMap* map_1, uint8_t* sm,
                                           uint32_t sb, int id, int warp) {
  constexpr int kRed = 6 * 32768, kBar = kRed + 2 * 4096;
  const int tid = threadIdx.x;
  if (warp == 8 && elect()) {
#pragma unroll
    for (int s = 0; s < 6; s++) {
      mbar_init(sb + kBar + s * 8, 1);
      mbar_init(sb + kBar + 64 + s * 8, 4);
    }
    fence_async_smem();
#pragma unroll
    for (int s = 0; s < 6; s++) {
      mbar_expect_tx(sb + kBar + s * 8, 32768);
      tma2d(sb + s * 32768, map_q, sb + kBar + s * 8, id * 128, s * 128);
    }
  }
  __syncthreads();
  if (warp == 8) {
    int slot = 0, ph = 0;
#pragma unroll 1
    for (int n = 6; n < 80; n++) {
      mbar_wait(sb + kBar + 64 + slot * 8, ph);
      if (elect()) {
        mbar_expect_tx(sb + kBar + slot * 8, 32768);
        tma2d(sb + slot * 32768, n < 24 ? map_q : map_1, sb + kBar + slot * 8, helper_col(id, n >> 3), (n & 7) * 128);
      }
      if (++slot == 6) slot = 0, ph ^= 1;
    }
  } else if (warp < 8) {
    if (tid == 0) *reinterpret_cast<unsigned*>(sm + kBar + 128) = atomicAdd(&g_ticket, 1u) / kGrid + 1;
    int slot = warp >> 2, ph = 0;
#pragma unroll 1
    for (int slab = 0; slab < 10; slab++) {
      float a[8];
#pragma unroll
      for (int e = 0; e < 8; e++) a[e] = 0.f;
#pragma unroll 1
      for (int box = 0; box < 4; box++) {
        mbar_wait_bounded(sb + kBar + slot * 8, ph);
        const uint4* p = reinterpret_cast<const uint4*>(sm + slot * 32768) + (tid & 127);
        uint4 v[16];
#pragma unroll
        for (int i = 0; i < 16; i++) v[i] = p[i * 128];
        __syncwarp();
        if (elect()) mbar_arrive(sb + kBar + 64 + slot * 8);
#pragma unroll
        for (int i = 0; i < 16; i++) add_chunk(a, v[i]);
        slot += 2;
        if (slot >= 6) slot -= 6, ph ^= 1;
      }
      float* red = reinterpret_cast<float*>(sm + kRed + (slab & 1) * 4096);
#pragma unroll
      for (int e = 0; e < 8; e++) a[e] += shfl_xor(a[e], 16);
      if ((tid & 16) == 0) {
        float4* d = reinterpret_cast<float4*>(red + warp * 128 + (tid & 15) * 8);
        d[0] = make_float4(a[0], a[1], a[2], a[3]);
        d[1] = make_float4(a[4], a[5], a[6], a[7]);
      }
      asm volatile("bar.sync 1, 256;" ::: "memory");
      if (warp < 4) {
        float t = 0.f;
#pragma unroll
        for (int q = 0; q < 8; q++) t += red[q * 128 + tid];
        st_relaxed(g_cs + (slab < 3 ? 0 : 3 * kD) + helper_col(id, slab) + tid,
                   tag_value(t, *reinterpret_cast<volatile unsigned*>(sm + kBar + 128)));
      }
    }
  }
}

__device__ __forceinline__ void colsum_strip(const CUtensorMap* map, uint8_t* sm, uint32_t sb, int col, int half,
                                             int lane, unsigned epoch) {
  const uint32_t bar = sb + kBarSlab + half * 16;
  const int buf = kSmStg + half * 8192;
  float a[8];
#pragma unroll
  for (int e = 0; e < 8; e++) a[e] = 0.f;
#pragma unroll 1
  for (int r = -2; r < 4; r++) {
    if (r >= 0) {
      mbar_wait(bar + (r & 1) * 8, r >> 1);
      const uint4* p = reinterpret_cast<const uint4*>(sm + buf + (r & 1) * 4096) + lane;
#pragma unroll 1
      for (int q = 0; q < 8; q += 4) {
        uint4 v[4];
#pragma unroll
        for (int u = 0; u < 4; u++) v[u] = p[(q + u) * 32];
#pragma unroll
        for (int u = 0; u < 4; u++) {
          a[0] += bf_lo(v[u].x); a[1] += bf_hi(v[u].x); a[2] += bf_lo(v[u].y); a[3] += bf_hi(v[u].y);
          yield_slot();
          a[4] += bf_lo(v[u].z); a[5] += bf_hi(v[u].z); a[6] += bf_lo(v[u].w); a[7] += bf_hi(v[u].w);
          yield_slot();
        }
      }
      fence_async_smem();
      __syncwarp();
    }
    if (r < 2 && elect()) {
      mbar_expect_tx(bar + (r & 1) * 8, 4096);
      tma2d(sb + buf + (r & 1) * 4096, map, bar + (r & 1) * 8, col, half * 512 + (r + 2) * 128);
    }
  }
#pragma unroll
  for (int e = 0; e < 4; e++) a[e] = (lane & 16 ? a[e + 4] : a[e]) + shfl_xor(lane & 16 ? a[e] : a[e + 4], 16);
#pragma unroll
  for (int e = 0; e < 2; e++) a[e] = (lane & 8 ? a[e + 2] : a[e]) + shfl_xor(lane & 8 ? a[e] : a[e + 2], 8);
  a[0] = (lane & 4 ? a[1] : a[0]) + shfl_xor(lane & 4 ? a[0] : a[1], 4);
  a[0] += shfl_xor(a[0], 2);
  if (!(lane & 2)) st_relaxed(g_cs + half * (3 * kD + kF) + col + (lane & 1) * 8 + (lane >> 2), tag_value(a[0], epoch));
}

constexpr float kGeluBeta = 0.3292034911525734f / 2.f;
constexpr float kGeluK = 2.423681954311584f / 4.f;
constexpr float kHScale = 2.f * kGeluBeta;

__device__ __forceinline__ void store_staged(uint8_t* dst, uint32_t stg) {
  fence_async_smem();
  __syncwarp();
  if (elect()) {
    bulk_store(dst, stg, 4096);
    bulk_commit();
  }
}

#define GY_MASK 5
#define GF_MASK 3
#define GY(k) if ((GY_MASK >> k) & 1) yield_slot()
template <int J0, int J1>
__device__ __forceinline__ void fold_norm(float (&acc)[2][96], const float2 (&st)[4], const float4* vec) {
  float4 vn = vec[J0 * 4];
#pragma unroll
  for (int J = J0; J < J1; J++) {
    const float4 v = vn;
    if (J + 1 < J1) vn = vec[J * 4 + 4];
#pragma unroll
    for (int c = 0; c < 4; c++) {
      float& a0 = acc[c & 1][4 * J + (c & 2)];
      float& a1 = acc[c & 1][4 * J + (c & 2) + 1];
      a0 = fmaf(a0, st[c].x, fmaf(st[c].y, v.x, v.z));
      a1 = fmaf(a1, st[c].x, fmaf(st[c].y, v.y, v.w));
      asm volatile("" : "+f"(a0), "+f"(a1));
      if ((c & 1) && ((GF_MASK >> (c >> 1)) & 1)) yield_slot();
    }
  }
}

template <int CH, class Acquire>
__device__ __forceinline__ void gelu_chunk(const float (&acc)[2][96], uint32_t stg, int lane, uint8_t* prev,
                                           Acquire acquire) {
  uint32_t pk[8][4];
  float z[3][4];
  const uint32_t row = (stg + lane * 128) ^ ((lane & 7) << 4);
#define U(s, e) acc[(e) >> 1][4 * (CH * 8 + ((s) >> 1)) + 2 * ((s) & 1) + ((e) & 1)]
#pragma unroll
  for (int s = 0; s < 18; s++) {
    const int cur = s % 3, p1 = (s + 2) % 3, p2 = (s + 1) % 3, q = s - 2, jj = 2 * q - 24;
    const bool mid = s >= 1 && s < 17;
    if (mid) z[p1][0] = tanh_fast(z[p1][0]);
    if (s < 16) {
#pragma unroll
      for (int e = 0; e < 4; e++) {
        z[cur][e] = fmaf(U(s, e), U(s, e), kGeluK);
        asm volatile("" : "+f"(z[cur][e]));
      }
    }
    if (jj >= 0) stsm4(row ^ (jj << 4), pk[jj][0], pk[jj][1], pk[jj][2], pk[jj][3]);
    GY(0);
    if (mid) z[p1][1] = tanh_fast(z[p1][1]);
    if (q >= 0) {
      pk[q >> 1][2 * (q & 1)] = pack2(fmaf(U(q, 0), z[p2][0], U(q, 0)), fmaf(U(q, 1), z[p2][1], U(q, 1)));
      pk[q >> 1][2 * (q & 1) + 1] = pack2(fmaf(U(q, 2), z[p2][2], U(q, 2)), fmaf(U(q, 3), z[p2][3], U(q, 3)));
    }
    GY(1);
    if (mid) z[p1][2] = tanh_fast(z[p1][2]);
    if (s < 16) {
#pragma unroll
      for (int e = 0; e < 4; e++) {
        z[cur][e] = z[cur][e] * U(s, e) * 8.f;
        asm volatile("" : "+f"(z[cur][e]));
      }
    }
    if (mid) z[p1][3] = tanh_fast(z[p1][3]);
    if (jj >= 0) stsm4(row ^ ((jj + 1) << 4), pk[jj + 1][0], pk[jj + 1][1], pk[jj + 1][2], pk[jj + 1][3]);
    GY(2);
    if (CH == 1 && s == 1) store_staged(prev, stg);
    if (q == 11) acquire();
  }
#undef U
}

__device__ __forceinline__ void scale_stats(float2 (&st)[4]) {
#pragma unroll
  for (int c = 0; c < 4; c++) {
    st[c].x *= kGeluBeta;
    st[c].y *= st[c].x;
  }
}

__device__ __forceinline__ void add_mean_term(float (&acc)[2][96], const float2 (&st)[4], uint8_t* sm, int tq,
                                              int lane) {
  const float2* cs = reinterpret_cast<const float2*>(sm + kSmCsQ) + tq * 96 + (lane & 3);
  float2 vn = cs[0];
#pragma unroll
  for (int J = 0; J < 24; J++) {
    const float2 v = vn;
    if (J < 23) vn = cs[J * 4 + 4];
#pragma unroll
    for (int c = 0; c < 4; c++) {
      acc[c & 1][4 * J + (c & 2)] = fmaf(st[c].y, v.x, acc[c & 1][4 * J + (c & 2)]);
      acc[c & 1][4 * J + (c & 2) + 1] = fmaf(st[c].y, v.y, acc[c & 1][4 * J + (c & 2) + 1]);
    }
    yield_slot();
  }
}

#define CV_MASK 1
#define HALO_AT 2
struct AttnRegs {
  uint32_t q[4][8], k[5][8], vt[5][8];
};
#define SCALED(c, J) pack2(acc[(c) & 1][4 * (J) + ((c) & 2)] * st[c].x, acc[(c) & 1][4 * (J) + ((c) & 2) + 1] * st[c].x)
__device__ __forceinline__ void convert_group(const float (&acc)[2][96], const float2 (&st)[4], AttnRegs& r, int c,
                                              int part) {
#pragma unroll
  for (int J = 0; J < 8; J++) {
    if (part == 0) r.q[c][J] = SCALED(c, J);
    if (part == 1) r.k[c + 1][J] = SCALED(c, 8 + J);
    if (part == 2) r.vt[c + 1][J] = transpose8(SCALED(c, 16 + J));
    if ((J & CV_MASK) == CV_MASK) yield_slot();
  }
}
#undef SCALED

__device__ __forceinline__ void convert_odd(const float (&acc)[2][96], const float2 (&st)[4], AttnRegs& r, int step,
                                            uint8_t* sm, uint32_t halo_bar, uint4* halo_out, bool send,
                                            unsigned epoch, int w, int lane) {
  if (step == 1) {
    convert_group(acc, st, r, 3, 2);
    convert_group(acc, st, r, 3, 1);
    if (w < 3) {
      uint2* hs = reinterpret_cast<uint2*>(sm + kSmHalo + w * 2048) + lane;
#pragma unroll
      for (int i = 0; i < 4; i++) {
        hs[i * 32] = make_uint2(r.k[4][2 * i], r.k[4][2 * i + 1]);
        hs[128 + i * 32] = make_uint2(r.vt[4][2 * i], r.vt[4][2 * i + 1]);
      }
      __syncwarp();
      if (elect()) mbar_arrive(halo_bar + w * 8);
    } else if (send) {
#pragma unroll
      for (int i = 0; i < 4; i++) {
        st_packet(halo_out + lane + i * 32, r.k[4][2 * i], r.k[4][2 * i + 1], epoch);
        st_packet(halo_out + lane + 128 + i * 32, r.vt[4][2 * i], r.vt[4][2 * i + 1], epoch);
      }
    }
  } else if (step == 2) {
    convert_group(acc, st, r, 1, 2);
  } else {
    convert_group(acc, st, r, 1, 1);
    convert_group(acc, st, r, 3, 0);
    convert_group(acc, st, r, 1, 0);
  }
}

__device__ __forceinline__ void epilogue_attn(const float (&acc)[2][96], const float2 (&st)[4], AttnRegs& r,
                                              uint8_t* sm, uint32_t sb, int layer, int tq, int b, int j,
                                              unsigned epoch, int tile, int w, int lane) {
  const int t = lane & 3, g = lane >> 2;
  const int hp = j + 8 * tq, att = 2 * layer + tq;
  auto& q = r.q;
  auto& k = r.k;
  auto& vt = r.vt;
  const bool first = w == 0 && (b & 7) == 0;
  const uint4* gh = g_halo + ((layer * 16 + b - 1) * 16 + hp) * 256 + lane;
  uint32_t tag[8];
#define LOAD_HALO()                                                                                    \
  _Pragma("unroll") for (int i = 0; i < 4; i++) {                                                      \
    ld_packet(gh + i * 32, k[0][2 * i], k[0][2 * i + 1], tag[i]);                                      \
    ld_packet(gh + 128 + i * 32, vt[0][2 * i], vt[0][2 * i + 1], tag[4 + i]);                          \
  }
#define AWAIT_HALO()                                                                                   \
  for (unsigned spins = 0;; spins++) {                                                                 \
    const unsigned d0 = (tag[0] ^ epoch) | (tag[1] ^ epoch) | (tag[2] ^ epoch) | (tag[3] ^ epoch);     \
    const unsigned d1 = (tag[4] ^ epoch) | (tag[5] ^ epoch) | (tag[6] ^ epoch) | (tag[7] ^ epoch);     \
    if (__all_sync(0xffffffffu, (d0 | d1) == 0)) break;                                                \
    if (spins > kSpinLimit) __trap();                                                                  \
    LOAD_HALO();                                                                                       \
  }
#pragma unroll
  for (int c = 0; c <= 6; c++) {
    if (c == HALO_AT) {
#pragma unroll
      for (int i = 0; i < 8; i++) k[0][i] = vt[0][i] = tag[i] = 0u;
      if (w > 0) {
        mbar_wait(sb + kBarHalo + (att * 3 + w - 1) * 8, 0);
        const uint2* hs = reinterpret_cast<const uint2*>(sm + kSmHalo + (w - 1) * 2048) + lane;
#pragma unroll
        for (int i = 0; i < 4; i++) {
          const uint2 a = hs[i * 32], d = hs[128 + i * 32];
          k[0][2 * i] = a.x; k[0][2 * i + 1] = a.y;
          vt[0][2 * i] = d.x; vt[0][2 * i + 1] = d.y;
        }
      } else if (!first) {
        LOAD_HALO();
      }
    }
    if (c < 6) convert_group(acc, st, r, 2 * (c & 1), 2 - (c >> 1));
  }
  TRACE_AT(tile, 8);
  if (w == 0 && !first) AWAIT_HALO();
  constexpr float kScale = 0.17677669529663687f * 1.4426950408889634f;
  const bool own0 = 2 * t <= g, own1 = 2 * t + 1 <= g;
  const uint32_t own_mask = (own0 ? 0xffffu : 0u) | (own1 ? 0xffff0000u : 0u);
  const uint32_t stg = sb + kSmStg + w * 4096;
  const uint32_t orow = stg + (lane & 7) * 128, ochunk = (lane >> 3) ^ (lane & 7);
  TRACE_AT(tile, 9);
  mbar_wait(sb + kBarPause + att * 8, 0);
  TRACE_AT(tile, 10);

  float s[2][6][4], o[2][4][2][4];
#pragma unroll
  for (int n = 0; n < 24; n++) {
    const int ks = n / 12, hd = (n % 12) / 6, m = n % 6, ca = 2 * (m / 3), kg = ca + m % 3, J = 4 * hd + 2 * ks;
    if (ks == 0) s[hd][m][0] = s[hd][m][1] = s[hd][m][2] = s[hd][m][3] = 0.f;
    mma16816(s[hd][m], q[ca][J], q[ca + 1][J], q[ca][J + 1], q[ca + 1][J + 1], k[kg][J], k[kg][J + 1]);
  }
  float v0[2][4], v1[2][4], m[2][4];
  uint32_t pp[2][4], po[2][4];
#define UNITS _Pragma("unroll") for (int hd = 0; hd < 2; hd++) _Pragma("unroll") for (int c = 0; c < 4; c++)
  UNITS {
    const int mp = 3 * (c >> 1) + (c & 1), r = 2 * (c & 1);
    float p0 = s[hd][mp][r], p1 = s[hd][mp][r + 1];
    if (c == 0 && first) p0 = p1 = -INFINITY;
    v0[hd][c] = own0 ? s[hd][mp + 1][r] : p0;
    v1[hd][c] = own1 ? s[hd][mp + 1][r + 1] : p1;
    m[hd][c] = fmaxf(v0[hd][c], v1[hd][c]);
  }
  UNITS m[hd][c] = fmaxf(m[hd][c], shfl_xor(m[hd][c], 1));
  UNITS m[hd][c] = fmaxf(m[hd][c], shfl_xor(m[hd][c], 2));
  UNITS {
    const float nm = -m[hd][c] * kScale;
    v0[hd][c] = ex2(fmaf(v0[hd][c], kScale, nm));
    v1[hd][c] = ex2(fmaf(v1[hd][c], kScale, nm));
    m[hd][c] = v0[hd][c] + v1[hd][c];
  }
  UNITS m[hd][c] += shfl_xor(m[hd][c], 1);
  UNITS m[hd][c] += shfl_xor(m[hd][c], 2);
  UNITS {
    const float inv = rcp(m[hd][c]);
    const uint32_t p = pack2(v0[hd][c] * inv, v1[hd][c] * inv);
    pp[hd][c] = p & ~own_mask;
    po[hd][c] = p & own_mask;
    asm volatile("" : "+r"(pp[hd][c]), "+r"(po[hd][c]));
  }
#pragma unroll
  for (int n = 0; n < 24; n++) {
    const int ph = n / 8, hd = (n >> 2) & 1, c = 2 * ((n >> 1) & 1) + (ph == 1), ds = n & 1, J = 4 * hd + 2 * ds;
    float(&d)[4] = o[hd][c][ds];
    if (ph < 2) d[0] = d[1] = d[2] = d[3] = 0.f;
    if (ph == 0) mma1688(d, vt[c + 1][J], vt[c + 1][J + 1], po[hd][c]);
    if (ph == 1) mma16816(d, vt[c][J], vt[c][J + 1], vt[c + 1][J], vt[c + 1][J + 1], pp[hd][c], po[hd][c]);
    if (ph == 2) mma1688(d, vt[c][J], vt[c][J + 1], pp[hd][c]);
    if (n == 3) {
      yield_slot();
      if (tq == 0 && lane == 0) mbar_arrive(sb + kBarResume + att * 8);
    }
  }
  yield_slot();
  if (tq == 1 && lane == 0) mbar_arrive(sb + kBarResume + att * 8);
  TRACE_AT(tile, 11);
  UNITS stsm4_t(orow + c * 1024 + ((ochunk ^ (4 * hd)) << 4), pack2(o[hd][c][0][0], o[hd][c][0][1]),
                pack2(o[hd][c][0][2], o[hd][c][0][3]), pack2(o[hd][c][1][0], o[hd][c][1][1]),
                pack2(o[hd][c][1][2], o[hd][c][1][3]));
#undef UNITS
#undef AWAIT_HALO
#undef LOAD_HALO
  fence_async_smem();
  __syncwarp();
  TRACE_AT(tile, 12);
  if (elect()) {
    bulk_store(g_o + (b * 16 + hp) * kTileBytes + w * 4096, stg, 4096);
    bulk_commit();
    bulk_wait();
    TRACE_AT(tile, 13);
    mbar_arrive(sb + kBarEpi + tile * 8);
  }
  __syncwarp();
}

__device__ __forceinline__ void gather_stats(uint8_t* sm, const uint2* stat, int r, float eps, unsigned epoch) {
  uint2 a[8];
#pragma unroll 1
  for (unsigned spins = 0;; spins++) {
    unsigned diff = 0;
#pragma unroll
    for (int i = 0; i < 8; i++) {
      a[i] = ld_relaxed2(stat + i * 128 + r);
      diff |= (a[i].x ^ epoch) | (a[i].y ^ epoch);
    }
    if (__all_sync(0xffffffffu, (diff & 7u) == 0)) break;
    if (spins > kSpinLimit) __trap();
  }
  float s = 0.f, q = 0.f;
#pragma unroll
  for (int i = 0; i < 8; i++) {
    s += untag_value(a[i].x);
    q += untag_value(a[i].y);
  }
  const float mean = s * (1.f / 1024.f);
  const float var = fmaxf(fmaf(-mean, mean, q * (1.f / 1024.f)), 0.f);
  reinterpret_cast<float2*>(sm + kSmStat)[r] = make_float2(rsqrtf(var + eps), -mean);
}

__device__ __forceinline__ void gather_colsums_qkv(uint8_t* sm, int tq, int j, int lane, unsigned epoch) {
  const uint2* src = reinterpret_cast<const uint2*>(g_cs + (j + 8 * tq) * 64) + lane;
  uint2 v[3], u[3];
  for (unsigned spins = 0;; spins++) {
    unsigned diff = 0;
#pragma unroll
    for (int q = 0; q < 3; q++) {
      v[q] = ld_relaxed2(src + q * (kD / 2));
      u[q] = make_uint2(epoch & 7u, epoch & 7u);
      if (tq) u[q] = ld_relaxed2(src + (q * kD + 3 * kD + kF) / 2);
    }
#pragma unroll
    for (int q = 0; q < 3; q++) diff |= (v[q].x ^ epoch) | (v[q].y ^ epoch) | (u[q].x ^ epoch) | (u[q].y ^ epoch);
    if (__all_sync(0xffffffffu, (diff & 7u) == 0)) break;
    if (spins > kSpinLimit) __trap();
  }
#pragma unroll
  for (int q = 0; q < 3; q++)
    reinterpret_cast<float2*>(sm + kSmCsQ)[tq * 96 + q * 32 + lane] =
        make_float2(untag_value(v[q].x) + untag_value(u[q].x), untag_value(v[q].y) + untag_value(u[q].y));
}

__device__ __forceinline__ void gather_colsums_w1(uint8_t* sm, const __nv_bfloat16* b1, int j, int lane,
                                                  unsigned epoch) {
#pragma unroll 1
  for (int blk = 0; blk < 7; blk++) {
    const int pair = 32 * (blk + (blk < 3 ? 3 * j : blk < 5 ? 21 + 2 * j : 35 + 2 * j)) + lane;
    const uint32_t bias = reinterpret_cast<const uint32_t*>(b1)[pair];
    uint2 v;
    for (unsigned spins = 0;; spins++) {
      v = ld_relaxed2(reinterpret_cast<const uint2*>(g_cs + 3 * kD) + pair);
      if (__all_sync(0xffffffffu, (((v.x ^ epoch) | (v.y ^ epoch)) & 7u) == 0)) break;
      if (spins > kSpinLimit) __trap();
    }
    reinterpret_cast<float4*>(sm + kSmV1)[blk * 32 + lane] =
        make_float4(untag_value(v.x), untag_value(v.y), kGeluBeta * bf_lo(bias), kGeluBeta * bf_hi(bias));
  }
}

#define PAUSE_QKV2 7
#define PAUSE_WO 2

__global__ void __cluster_dims__(2, 1, 1) __launch_bounds__(384, 1)
fused_layers_kernel(const __grid_constant__ CUtensorMap map_x, const __grid_constant__ CUtensorMap map_out,
                    const __grid_constant__ CUtensorMap map_qkv, const __grid_constant__ CUtensorMap map_wo,
                    const __grid_constant__ CUtensorMap map_w1a, const __grid_constant__ CUtensorMap map_w1b,
                    const __grid_constant__ CUtensorMap map_w2, const __grid_constant__ CUtensorMap map_csq,
                    const __grid_constant__ CUtensorMap map_cs1, const __grid_constant__ CUtensorMap map_css,
                    const __grid_constant__ Params prm) {
  extern __shared__ __align__(1024) uint8_t sm[];
  if (threadIdx.x < 128 && blockIdx.x < kCtas) TRACE_AT(15, 1);
  const uint32_t sb = __shfl_sync(0xffffffffu, smem_u32(sm), 0);
  const int warp = __shfl_sync(0xffffffffu, threadIdx.x >> 5, 0), lane = threadIdx.x & 31;
  const int cta = blockIdx.x, rank = cta & 1, cl = cta >> 1;
  const int grp = cl < 4 ? 0 : cl < 36 ? (cl - 4) & 7 : 1 + (cl - 36) % 7;
  const int j = cl < 4 ? 4 + cl : cl < 36 ? (cl - 4) >> 3 : 4 + (cl - 36) / 7;
  const int b = 2 * grp + rank;
  const int xcol = (b >> 3) * kD, xrow = (b & 7) * 128;

  if (cta >= kCtas) {
    helper_cta(&map_csq, &map_cs1, sm, sb, cta - kCtas, warp);
    return;
  }
  if ((warp < 8 || warp == 9) && elect()) {
    if (warp == 9) {
#pragma unroll
      for (int s = 0; s < 8; s++) mbar_init(sb + kBarFull + s * 8, 1);
      fence_async_smem();
#pragma unroll 1
      for (int s = 0; s < 4; s++) {
        const uint32_t full = sb + kBarFull + s * 8, dst = sb + kSmRing + s * 40960;
        mbar_expect_tx(full, 40960);
        tma2d(dst, &map_x, full, xcol + (s & 1) * 64, xrow);
        tma3d(dst + kTileBytes, &map_qkv, full, (j + 4 * (s & 2)) * 64, (s & 1) * 64, 0);
        tma3d(dst + kTileBytes + 12288, &map_qkv, full, (j + 4 * (s & 2)) * 64, (s & 1) * 64 + 32, 0);
      }
    } else {
      if (sb & 1023) __trap();
#pragma unroll
      for (int s = 0; s < 16; s++) mbar_init(sb + kBarTurn + warp * 128 + s * 8, warp < 5 ? 1 : warp == 5 ? 2 : 4);
    }
    asm volatile("fence.mbarrier_init.release.cluster;" ::: "memory");
  }
  __syncwarp();
  asm volatile("barrier.cluster.arrive.relaxed.aligned;" ::: "memory");

  if (warp >= 8) {
    asm volatile("setmaxnreg.dec.sync.aligned.u32 40;");
    if (warp < 10) {
      asm volatile("barrier.cluster.wait.aligned;" ::: "memory");
      uint32_t nb = 32, off = 0, kb = 0;
#define RING_STEP(WAIT, ISSUE)                                            \
  do {                                                                    \
    const uint32_t mb = nb - depth, full = sb + kBarFull + (nb & 56);     \
    if (kb == skip) kb += inc;                                            \
    mbar_wait(sb + kBarEmpty + (mb & 56), mb >> 6);                       \
    WAIT;                                                                 \
    if (elect()) { ISSUE; }                                               \
    TRACE_ISSUE(9 - warp, nb);                                            \
    kb += inc;                                                            \
    off = off == wrap ? 0 : off + step;                                   \
    nb += 8;                                                              \
  } while (nb != nend)
#pragma unroll 1
      for (int sg = 0; sg < kSegs; sg++) {
        const uint32_t e = prm.seg[sg];
        const int ty = e & 7, mode = (e >> 15) & 3, reset = (e >> 24) & 3;
        const uint32_t nend = nb + (e & 0x1f8);
        const uint32_t step = (e >> 17) & 1 ? 40960 : 32768, wrap = 163840 - step;
        const uint32_t depth = (e >> 18) & 1 ? 40 : 32;
        if (reset) off = reset == 1 ? 0 : reset == 2 ? 40960 : 131072;
        const uint32_t own = ty == 2 ? 8 + j : 2 * j;
        if (mode != kModeContinue) kb = mode == kModeHead ? own : (e >> 9) & 63;
        const uint32_t inc = mode >= kModeSkip && ty != 2 ? 2 : 1, skip = mode >= kModeSkip ? own + (kb & 1) : 255;
        if (warp == 8) {
          const CUtensorMap* map = ty < 2 ? &map_qkv : ty == 2 ? &map_wo : ty == 3 ? &map_w1a : ty < 6 ? &map_w1b : &map_w2;
          const int c0 = ty < 2 ? (j + 8 * ty) * 64 : 0;
          const int c2 = ty < 2 ? 0 : ty == 3 ? 3 * j : ty == 4 ? 24 + 2 * j : ty == 5 ? 40 + 2 * j : 2 * j;
          const uint32_t half = (ty < 2 || ty == 3) ? 12288 : 8192;
          const uint32_t bytes = 2 * half + (mode == kModeHead ? 0 : kTileBytes);
          const uint32_t dst = sb + kSmRing + kTileBytes + rank * half;
          if (e >> 26) {
            const bool second = (grp & 6) == 2;
            const int pk = grp < 4 ? 2 * j + (grp & 1) : 2 * (grp - 4 + (grp - 4 >= j));
            const CUtensorMap* pm = ty == 6 ? &map_qkv : second ? &map_w1b : &map_w1a;
            if (elect())
              asm volatile("cp.async.bulk.prefetch.tensor.3d.L2.global [%0, {%1, %2, %3}];" ::"l"(pm),
                           "r"(ty == 6 ? (j + 8 * second) * 64 : 0), "r"(pk * 64 + rank * 32),
                           "r"(ty == 6 ? 0 : second ? 24 + 2 * j : 3 * j) : "memory");
          }
          if (ty == 2 && mode == kModeHead) mbar_wait(sb + kBarEpi + ((e >> 19) & 31) * 8, 0);
#pragma unroll 1
          RING_STEP(, mbar_expect_tx(full, bytes); tma3d_mc(dst + off, map, full, c0, kb * 64 + rank * 32, c2));
        } else if (mode == kModeHead) {
          off += ((nend - nb) >> 3) * step;
          nb = nend;
          if (off >= 163840) off -= 163840;
        } else if (sg < 2) {
#pragma unroll 1
          RING_STEP(, tma2d(sb + kSmRing + off, &map_x, full, xcol + kb * 64, xrow));
        } else {
          const uint8_t* src = ty == 6 ? g_h + b * 56 * kTileBytes : (ty == 2 ? g_o : g_x) + b * 16 * kTileBytes;
          const int dep = (e >> 19) & 31;
          if (dep < 28) mbar_wait(sb + kBarReady + dep * 8, 0);
          if ((dep & 30) == 28) {
#pragma unroll 1
            RING_STEP(mbar_wait(sb + kBarSrc + ((kb << (4 - inc)) & 56), dep),
                      bulk_load(sb + kSmRing + off, src + kb * kTileBytes, kTileBytes, full));
          } else {
#pragma unroll 1
            RING_STEP(, bulk_load(sb + kSmRing + off, src + kb * kTileBytes, kTileBytes, full));
          }
        }
      }
#undef RING_STEP
    } else {
      unsigned epoch = 0;
      if (warp == 10) {
        if (lane == 0) epoch = atomicAdd(&g_ticket, 1u) / kGrid + 1;
        *reinterpret_cast<unsigned*>(sm + kSmEpoch) = __shfl_sync(0xffffffffu, epoch, 0);
        asm volatile("barrier.cluster.wait.aligned;" ::: "memory");
        if (elect()) mbar_arrive(sb + kBarEpoch);
      } else {
        asm volatile("barrier.cluster.wait.aligned;" ::: "memory");
        mbar_wait_bounded(sb + kBarFull, 0);
        if (elect()) {
          mbar_expect_tx(sb + kBarInit, 32768);
          tma2d(sb + kSmX, &map_x, sb + kBarInit, xcol + j * 128, xrow);
          tma2d(sb + kSmX + kTileBytes, &map_x, sb + kBarInit, xcol + j * 128 + 64, xrow);
        }
        const uint2 u = reinterpret_cast<const uint2*>(prm.b2)[32 * j + lane];
        reinterpret_cast<float4*>(sm + kSmB2)[lane] = make_float4(
            kHScale * bf_lo(u.x), kHScale * bf_hi(u.x), kHScale * bf_lo(u.y), kHScale * bf_hi(u.y));
      }
      mbar_wait_bounded(sb + kBarEpoch, 0);
      epoch = *reinterpret_cast<volatile unsigned*>(sm + kSmEpoch);
      if (cta < 96) {
        mbar_wait_bounded(sb + kBarInit, 0);
        colsum_strip(&map_css, sm, sb, (cta >> 5) * kD + 512 + (cta & 31) * 16, warp - 10, lane, epoch);
      }
      gather_colsums_qkv(sm, 11 - warp, j, lane, epoch);
      __syncwarp();
      if (elect()) mbar_arrive(sb + kBarCs + (11 - warp) * 8);
     if (warp == 10) {
#pragma unroll 1
      for (int i = 0; i < kTiles - 1; i++) {
        const bool xt = i == 2 || i == 6 || i == 9;
        const unsigned* line = g_flag + (i * 16 + b) * 32;
        mbar_wait(sb + (xt ? kBarX + (i >> 2) * 16 : kBarEpi + i * 8), 0);
        if (xt || i == 1 || i == 8) {
          unsigned todo = 0xff, spins = 0;
          do {
            const unsigned now = __ballot_sync(0xffffffffu, ld_relaxed(line + (lane & 7)) == epoch) & todo;
            if (now) {
              asm volatile("fence.acquire.gpu;\nfence.proxy.async.global;" ::: "memory");
              if ((now >> lane) & 1) mbar_arrive(sb + kBarSrc + lane * 8);
              todo ^= now;
            }
            if (++spins > kSpinLimit) __trap();
          } while (todo);
        } else {
          wait_flags(line + (lane & 7), epoch);
          if (elect()) mbar_arrive(sb + kBarReady + i * 8);
        }
        if (xt) {
          wait_flags(line + 8 + (lane & 7), epoch);
          if (elect()) mbar_arrive(sb + kBarReady + (14 + (i >> 2)) * 8);
        }
      }
     } else {
#pragma unroll 1
      for (int i = 0; i < kTiles - 1; i++) {
        if (i == 3) {
          gather_colsums_w1(sm, prm.b1, j, lane, epoch);
          __syncwarp();
          if (elect()) mbar_arrive(sb + kBarCs + 16);
        }
        const bool xt = i == 2 || i == 6 || i == 9;
#pragma unroll 1
        for (int h = 0; h < (xt ? 2 : 1); h++) {
          if (xt && h == 0) {
            mbar_wait_bounded(sb + kBarEpi + i * 8, 0);
            if (elect()) bulk_store(g_x + (b * 16 + 2 * j) * kTileBytes, sb + kSmX, kTileBytes / 2);
          }
          mbar_wait_bounded(sb + (xt ? kBarX + (i >> 2) * 16 + 8 * h : kBarEpi + i * 8), 0);
          const int ty = i >= 7 ? i - 7 : i;
          if (ty >= 2 && elect()) {
            uint8_t* dst = xt ? g_x + (b * 16 + 2 * j + h) * kTileBytes
                              : g_h + (b * 56 + 1 + (ty == 3 ? 3 * j : 16 * ty - 40 + 2 * j)) * kTileBytes;
            const int piece = (xt && h == 0) ? kTileBytes / 2 : kTileBytes / 4;
#pragma unroll 1
            for (int o = xt && h == 0 ? piece : 0; o < kTileBytes; o += piece) {
              bulk_store(dst + o, sb + (xt ? kSmX + h * kTileBytes : kSmStg) + o, piece);
              bulk_commit();
              bulk_wait();
            }
            if (!xt) mbar_arrive(sb + kBarFree + i * 8);
          }
          __syncwarp();
          if (elect()) st_release(&g_flag[(i * 16 + b) * 32 + h * 8 + j], epoch);
          __syncwarp();
        }
      }
#pragma unroll 1
      for (int h = 0; h < 2; h++) {
        mbar_wait_bounded(sb + kBarX + 48 + 8 * h, 0);
        if (elect()) {
          tma2d_store(&map_out, sb + kSmX + h * kTileBytes, xcol + j * 128 + h * 64, xrow);
          bulk_commit();
          if (h == 1) bulk_wait_read();
        }
      }
     }
    }
    __syncwarp();
    asm volatile("barrier.cluster.arrive.relaxed.aligned;\nbarrier.cluster.wait.aligned;" ::: "memory");
  } else {
    asm volatile("setmaxnreg.inc.sync.aligned.u32 232;");
    asm volatile("barrier.cluster.wait.aligned;" ::: "memory");
    const int wg = warp >> 2, w = warp & 3;
    const bool rel = (threadIdx.x & 95) == 0;
    const uint32_t rel_addr = mapa(sb + kBarEmpty, w & 1);
    if (wg == 1) TRACE_AT(15, 0);
#define EPOCH (*reinterpret_cast<volatile unsigned*>(sm + kSmEpoch))

#pragma unroll 1
    for (int i = wg; i < kTiles; i += 2) {
      const int layer = i >= 7, ty = i - 7 * layer;
      TRACE_AT(i, 15);
      float acc[2][96];
      if (ty == 2 || ty == 6) {
        const int lane = lane_id();
        const uint32_t xa = sb + kSmX + ((lane >> 4) * 8 + (lane & 7)) * 128 + (((2 * w + ((lane >> 3) & 1)) ^ (lane & 7)) << 4);
        const float up = ty == 6 ? kHScale / kXScale : layer ? 1.f / kXScale : 1.f;
        const float dn = ty == 2 ? kXScale : layer ? 1.f / kHScale : kXScale / kHScale;
#pragma unroll
        for (int h = 0; h < 2; h++) {
          const float* b2 = reinterpret_cast<const float*>(sm + kSmB2) + 64 * h + 16 * w + (lane >> 2);
          const float bias[2] = {ty == 6 ? b2[0] : 0.f, ty == 6 ? b2[8] : 0.f};
#pragma unroll
          for (int p = 0; p < 8; p++) {
            uint32_t r[4];
            ldsm4_t(xa + h * kTileBytes + p * 2048, r);
#pragma unroll
            for (int m = 0; m < 4; m++) {
              acc[h][8 * p + 2 * m] = fmaf(bf_lo(r[m]), up, bias[m & 1]);
              acc[h][8 * p + 2 * m + 1] = fmaf(bf_hi(r[m]), up, bias[m & 1]);
              asm volatile("" : "+f"(acc[h][8 * p + 2 * m]), "+f"(acc[h][8 * p + 2 * m + 1]));
            }
            yield_slot();
          }
        }
        auto stage = [&](int qt) {
          const int h = qt >> 1;
          if (qt == 1) {
            fence_async_smem();
            __syncwarp();
            if (lane == 0) mbar_arrive(sb + kBarEpi + i * 8);
          }
#pragma unroll
          for (int p = 4 * (qt & 1); p < 4 * (qt & 1) + 4; p++) {
            const float* a = &acc[h][8 * p];
            stsm4_t(xa + h * kTileBytes + p * 2048, pack2(a[0] * dn, a[1] * dn), pack2(a[2] * dn, a[3] * dn),
                    pack2(a[4] * dn, a[5] * dn), pack2(a[6] * dn, a[7] * dn));
            yield_slot();
          }
          if (qt & 1) {
            fence_async_smem();
            __syncwarp();
            if (elect()) mbar_arrive(sb + kBarX + (i >> 2) * 16 + 8 * h);
            TRACE_AT(i, 8 + h);
          }
        };
        mainloop<128, kResid>(acc, sb, i, layer * 152 + ty * 16, ty == 6 ? 4 : 0, ty == 6 ? 56 : 16,
                            ty == 2 ? PAUSE_WO : -1, 2 * layer + 1, rel_addr, rel, ty == 2 ? 8 : -1, stage);
        TRACE_AT(i, 2);
        stage(2);
        stage(3);
      } else {
        const int xver = 2 * layer + (ty >= 3);
        const uint32_t stg = sb + kSmStg + w * 4096;
        const float4* vec = reinterpret_cast<const float4*>(sm + kSmV1) + (ty == 3 ? 0 : 64 * ty - 160);
        int lane;
        uint8_t* hdst = g_h + (b * 56 + (ty == 3 ? 3 * j : 16 * ty - 40 + 2 * j)) * kTileBytes + w * 4096;
        float2 st[4];
        unsigned epoch;
        auto pre = [&] {
          lane = lane_id();
          if (ty < 4) mbar_wait(sb + (ty == 1 ? kBarEpi + (i - 1) * 8 : kBarStat + xver * 8), 0);
#pragma unroll
          for (int c = 0; c < 4; c++) st[c] = reinterpret_cast<const float2*>(sm + kSmStat)[32 * w + 8 * c + (lane >> 2)];
          epoch = EPOCH;
        };
        auto team_stats = [&] {
          uint2* stat = g_stat + (xver * 16 + b) * 1024;
          lane = lane_id();
          publish_stats(sb, stat + j * 128, w, lane, EPOCH);
          gather_stats(sm, stat, 32 * w + lane, xver ? 1e-5f * kXScale * kXScale : 1e-5f, EPOCH);
          __syncwarp();
          if (elect()) mbar_arrive(sb + kBarStat + xver * 8);
          TRACE_AT(i, 14);
        };
        if (ty < 4) {
          AttnRegs ar;
          auto odd = [&](int step) {
            if (step == 0) pre();
            else convert_odd(acc, st, ar, step, sm, sb + kBarHalo + (xver + ty) * 24,
                             g_halo + ((layer * 16 + b) * 16 + j + 8 * ty) * 256, (b & 7) != 7, epoch, w, lane);
          };
          head_blocks<192>(acc, sb, layer * 152 + (ty < 2 ? 2 * ty : 48), ty < 2 ? 2 * ty : 1, xver, rel_addr, rel);
          if (ty == 1) {
            if (i == 1) {
              mbar_wait(sb + kBarEpoch, 0);
              mbar_wait(sb + kBarInit, 0);
            }
            team_stats();
            epoch = 0;
#pragma unroll
            for (int c = 0; c < 4; c++) st[c] = reinterpret_cast<const float2*>(sm + kSmStat)[32 * w + 8 * c + (lane >> 2)];
          } else {
            mainloop<192, kPlain>(acc, sb, i, layer * 152 + (ty ? 52 : 4), ty ? 1 : 0, 14, -1, 0, rel_addr, rel, 0, pre);
            TRACE_AT(i, 2);
            if (ty == 3) goto wide_gelu;
          }
          if (layer == 0) mbar_wait(sb + kBarCs + ty * 8, 0);
          add_mean_term(acc, st, sm, ty, lane);
          if (ty == 1) {
            mainloop<192, kStagger>(acc, sb, i, layer * 152 + 18, 2, 14, PAUSE_QKV2, xver, rel_addr, rel, 0, odd);
            TRACE_AT(i, 2);
          } else {
            odd(1);
            odd(2);
            odd(3);
          }
          epilogue_attn(acc, st, ar, sm, sb, layer, ty, b, j, epoch, i, w, lane);
          TRACE_AT(i, 3);
          continue;
        wide_gelu:
          if (i == 3) mbar_wait(sb + kBarCs + 16, 0);
          scale_stats(st);
          fold_norm<16, 24>(acc, st, vec + (lane & 3));
          TRACE_AT(i, 11);
          gelu_chunk<2>(acc, stg, lane, nullptr, [] {});
          TRACE_AT(i, 12);
          fold_norm<0, 2>(acc, st, vec + (lane & 3));
          store_staged(hdst + 2 * kTileBytes, stg);
          fold_norm<2, 16>(acc, st, vec + (lane & 3));
        } else {
          if (ty == 4) {
            head_blocks<128>(acc, sb, layer * 152 + 50, 3, xver, rel_addr, rel);
            team_stats();
            mainloop<128, kPlain>(acc, sb, i, layer * 152 + 66, 4, 14, -1, 0, rel_addr, rel, 0, pre);
          } else {
            mainloop<128, kFresh>(acc, sb, i, layer * 152 + 80, 3, 16, -1, 0, rel_addr, rel, 0, pre);
          }
          TRACE_AT(i, 2);
          if (i == 4) mbar_wait(sb + kBarCs + 16, 0);
          scale_stats(st);
          fold_norm<0, 16>(acc, st, vec + (lane & 3));
        }
        auto own_store_done = [] {
          if (elect()) bulk_wait();
          __syncwarp();
        };
        TRACE_AT(i, 8);
        gelu_chunk<0>(acc, stg, lane, nullptr, [&] {
          if (ty == 3) own_store_done();
          else mbar_wait(sb + kBarFree + (i - 1) * 8, 0);
        });
        TRACE_AT(i, 9);
        gelu_chunk<1>(acc, stg, lane, hdst, own_store_done);
        TRACE_AT(i, 10);
        fence_async_smem();
        __syncwarp();
        if (elect()) mbar_arrive(sb + kBarEpi + i * 8);
      }
      TRACE_AT(i, 3);
    }
#undef EPOCH
    asm volatile("barrier.cluster.arrive.relaxed.aligned;\nbarrier.cluster.wait.aligned;" ::: "memory");
    if (wg == 1) TRACE_AT(15, 2);
  }
}

void build_segments(uint32_t* seg) {
  int n = 0, fine = 0;
  auto per_source = [&] { return 28 + (fine++ & 1); };
  auto add = [&](int ty, int cnt, int kb0, int mode, int wide, int depth5, int dep, int reset) {
    seg[n++] = ty | cnt << 3 | kb0 << 9 | mode << 15 | wide << 17 | depth5 << 18 | dep << 19 | reset << 24;
  };
  for (int l = 0; l < 2; l++) {
    const int t = 7 * l;
    if (l == 0) {
      add(0, 14, 2, kModePlain, 1, 0, 31, 1);
      add(1, 14, 2, kModePlain, 1, 0, 31, 0);
    } else {
      add(0, 2, 0, kModeHead, 1, 0, 31, 1);
      add(1, 2, 0, kModeHead, 1, 0, 31, 0);
      add(0, 7, 0, kModeSkip, 1, 0, per_source(), 0);
      add(0, 7, 1, kModeSkip, 1, 0, 15, 0);
      add(1, 7, 0, kModeSkip, 1, 0, 31, 0);
      add(1, 7, 1, kModeSkip, 1, 0, 31, 0);
    }
    add(2, 4, 0, kModePlain, 0, 0, t, 1);
    add(2, 4, 4, kModePlain, 0, 1, 31, 4);
    add(2, 1, 0, kModeHead, 0, 1, t + 1, 0);
    add(2, 7, 8, kModeSkip, 0, 1, per_source(), 0);
    add(3, 2, 0, kModeHead, 1, 0, 31, 2);
    add(4, 2, 0, kModeHead, 1, 0, 31, 0);
    add(3, 7, 0, kModeSkip, 1, 0, per_source(), 0);
    add(3, 7, 1, kModeSkip, 1, 0, 14 + 2 * l, 0);
    add(4, 4, 0, kModeSkip, 0, 0, 31, 3);
    add(4, 3, 0, kModeContinue, 0, 1, 31, 0);
    add(4, 7, 1, kModeSkip, 0, 1, 31, 0);
    add(5, 16, 0, kModePlain, 0, 1, 31, 0);
    add(6, 24, 0, kModePlain, 0, 1, t + 3, 0);
    add(6, 16, 24, kModePlain, 0, 1, t + 4, 0);
    add(6, 16, 40, kModePlain, 0, 1, t + 5, l ? 0 : 4);
  }
}

typedef CUresult (*EncodeTiledFn)(CUtensorMap*, CUtensorMapDataType, cuuint32_t, void*, const cuuint64_t*,
                                  const cuuint64_t*, const cuuint32_t*, const cuuint32_t*, CUtensorMapInterleave,
                                  CUtensorMapSwizzle, CUtensorMapL2promotion, CUtensorMapFloatOOBfill);

CUtensorMap make_map(EncodeTiledFn enc, const void* p, int rank, const cuuint64_t* dims, const cuuint64_t* strides,
                     const cuuint32_t* box, CUtensorMapSwizzle swizzle = CU_TENSOR_MAP_SWIZZLE_128B,
                     CUtensorMapL2promotion promo = CU_TENSOR_MAP_L2_PROMOTION_L2_128B) {
  CUtensorMap m;
  const cuuint32_t es[5] = {1, 1, 1, 1, 1};
  enc(&m, CU_TENSOR_MAP_DATA_TYPE_BFLOAT16, rank, const_cast<void*>(p), dims, strides, box, es,
      CU_TENSOR_MAP_INTERLEAVE_NONE, swizzle, promo,
      CU_TENSOR_MAP_FLOAT_OOB_FILL_NONE);
  return m;
}

CUtensorMap weight_map(EncodeTiledFn enc, const void* p, int k, int n, int blocks) {
  const cuuint64_t dims[3] = {64, (cuuint64_t)k, (cuuint64_t)n / 64};
  const cuuint64_t strides[2] = {(cuuint64_t)n * 2, 128};
  const cuuint32_t box[3] = {64, 32, (cuuint32_t)blocks};
  return make_map(enc, p, 3, dims, strides, box, CU_TENSOR_MAP_SWIZZLE_128B, CU_TENSOR_MAP_L2_PROMOTION_L2_256B);
}

CUtensorMap slab_map(EncodeTiledFn enc, const void* p, int n, int cols, int rows) {
  const cuuint64_t dims[2] = {(cuuint64_t)n, kD};
  const cuuint64_t strides[1] = {(cuuint64_t)n * 2};
  const cuuint32_t box[2] = {(cuuint32_t)cols, (cuuint32_t)rows};
  return make_map(enc, p, 2, dims, strides, box, CU_TENSOR_MAP_SWIZZLE_NONE);
}

CUtensorMap token_map(EncodeTiledFn enc, const void* p, int rows) {
  const cuuint64_t dims[2] = {2 * kD, 1024};
  const cuuint64_t strides[1] = {4 * kD};
  const cuuint32_t box[2] = {64, (cuuint32_t)rows};
  return make_map(enc, p, 2, dims, strides, box);
}

}

extern "C" void kernel_launch(void* const* d_in, const int* in_sizes, int n_in, void* d_out, int out_size) {
  (void)in_sizes; (void)n_in; (void)out_size;
  static EncodeTiledFn enc = nullptr;
  if (!enc) {
    void* fn = nullptr;
    cudaDriverEntryPointQueryResult q;
    cudaGetDriverEntryPoint("cuTensorMapEncodeTiled", &fn, cudaEnableDefault, &q);
    enc = (EncodeTiledFn)fn;
    cudaFuncSetAttribute(fused_layers_kernel, cudaFuncAttributeMaxDynamicSharedMemorySize, kSmBytes);
  }
  Params prm;
  prm.b1 = (const __nv_bfloat16*)d_in[5];
  prm.b2 = (const __nv_bfloat16*)d_in[7];
  build_segments(prm.seg);
  const cuuint64_t qd[3] = {kD, kD, 3}, qs[2] = {3 * kD * 2, kD * 2};
  const cuuint32_t qb[3] = {64, 32, 3};
  const CUtensorMap map_x = token_map(enc, d_in[0], 128);
  const CUtensorMap map_out = token_map(enc, d_out, 128);
  const CUtensorMap map_qkv = make_map(enc, d_in[1], 3, qd, qs, qb);
  const CUtensorMap map_wo = weight_map(enc, d_in[2], kD, kD, 2);
  const CUtensorMap map_w1a = weight_map(enc, d_in[4], kD, kF, 3);
  const CUtensorMap map_w1b = weight_map(enc, d_in[4], kD, kF, 2);
  const CUtensorMap map_w2 = weight_map(enc, d_in[6], kF, kD, 2);
  fused_layers_kernel<<<kGrid, 384, kSmBytes>>>(map_x, map_out, map_qkv, map_wo, map_w1a, map_w1b, map_w2,
                                                slab_map(enc, d_in[1], 3 * kD, 128, 128), slab_map(enc, d_in[4], kF, 128, 128),
                                                slab_map(enc, d_in[1], 3 * kD, 16, 128), prm);
}
```

```cpp
#include <cuda.h>
#include <cuda_bf16.h>
#include <cuda_runtime.h>
#include <stdint.h>

namespace {

constexpr int kD = 1024;
constexpr int kF = 3584;
constexpr int kCtas = 128;
constexpr int kGrid = 132;
constexpr int kTiles = 14;
constexpr int kTileBytes = 16384;

constexpr int kSmRing = 0;
constexpr int kSmX = 163840;
constexpr int kSmStg = kSmX + 32768;
constexpr int kSmHalo = kSmStg + 16384;
constexpr int kSmCsQ = kSmHalo + 6144;
constexpr int kSmV1 = kSmCsQ + 384 * 4;
constexpr int kSmB2 = kSmV1 + 448 * 8;
constexpr int kSmStat = kSmB2 + 128 * 4;
constexpr int kSmBar = kSmStat + 128 * 8;
constexpr int kBarFull = kSmBar;
constexpr int kBarTurn = kBarFull + 8 * 8;
constexpr int kBarReady = kBarTurn + 14 * 8;
constexpr int kBarSrc = kBarReady + 17 * 8;
constexpr int kBarPause = kBarSrc + 8 * 8;
constexpr int kBarFree = kBarPause + 4 * 8;
constexpr int kBarCs = kBarFree + 14 * 8;
constexpr int kBarSlab = kBarCs + 3 * 8;
constexpr int kBarHalo = kBarSlab + 4 * 8;
constexpr int kBarInit = kBarHalo + 12 * 8;
constexpr int kBarEpoch = kBarInit + 8;
constexpr int kBarEmpty = kBarTurn + 5 * 128;
constexpr int kBarEpi = kBarEmpty + 128;
constexpr int kBarX = kBarEpi + 14 * 8;
constexpr int kBarStat = kBarX + 8 * 8;
constexpr int kBarResume = kBarStat + 4 * 8;
constexpr int kSmEpoch = kBarEpi + 2 * 128;
static_assert(kBarEpoch < kBarEmpty && kBarResume + 4 * 8 <= kSmEpoch, "barrier groups overflow");
constexpr int kSmBytes = kSmEpoch + 16 + 256;
constexpr int kSegs = 38;

constexpr int kFlagLines = kTiles * 16;

constexpr float kXScale = 1.f / 16.f;

constexpr unsigned kSpinLimit = 1u << 22;

__device__ __align__(1024) uint8_t g_x[16 * 16 * kTileBytes];
__device__ __align__(1024) uint8_t g_o[16 * 16 * kTileBytes];
__device__ __align__(1024) uint8_t g_h[16 * 56 * kTileBytes];
__device__ __align__(128) uint2 g_stat[4 * 16 * 128 * 8];
__device__ __align__(128) unsigned g_cs[3 * kD + kF + 3 * kD];
__device__ __align__(128) uint4 g_halo[2 * 16 * 16 * 256];
__device__ __align__(128) unsigned g_flag[kFlagLines * 32];
__device__ unsigned g_ticket;

#define TRACE_AT(tile, k)
#define TRACE_PUB(i, k, c)
#define TRACE_ISSUE(which, nb)

struct Params {
  const __nv_bfloat16* b1;
  const __nv_bfloat16* b2;
  uint32_t seg[kSegs];
};

__device__ __forceinline__ uint32_t smem_u32(const void* p) {
  return (uint32_t)__cvta_generic_to_shared(p);
}
__device__ __forceinline__ uint32_t mapa(uint32_t a, uint32_t cta) {
  uint32_t r;
  asm("mapa.shared::cluster.u32 %0, %1, %2;" : "=r"(r) : "r"(a), "r"(cta));
  return r;
}
__device__ __forceinline__ void mbar_init(uint32_t bar, int cnt) {
  asm volatile("mbarrier.init.shared::cta.b64 [%0], %1;" ::"r"(bar), "r"(cnt) : "memory");
}
__device__ __forceinline__ void mbar_expect_tx(uint32_t bar, uint32_t bytes) {
  asm volatile("mbarrier.arrive.expect_tx.shared::cta.b64 _, [%0], %1;" ::"r"(bar), "r"(bytes) : "memory");
}
__device__ __forceinline__ void mbar_arrive(uint32_t bar) {
  asm volatile("mbarrier.arrive.shared::cta.b64 _, [%0];" ::"r"(bar) : "memory");
}
__device__ __forceinline__ void mbar_arrive_cluster(uint32_t cluster_addr) {
  asm volatile("mbarrier.arrive.shared::cluster.b64 _, [%0];" ::"r"(cluster_addr) : "memory");
}
__device__ __forceinline__ void mbar_wait(uint32_t bar, uint32_t parity) {
  asm volatile("{\n.reg .pred p;\nRETRY:\nmbarrier.try_wait.parity.shared::cta.b64 p, [%0], %1;\n"
               "@!p bra.uni RETRY;\n}" ::"r"(bar), "r"(parity) : "memory");
}
__device__ __forceinline__ void mbar_wait_bounded(uint32_t bar, uint32_t parity) {
  asm volatile("{\n.reg .pred p;\n.reg .u32 c;\nmov.u32 c, 0;\nRETRY:\n"
               "mbarrier.try_wait.parity.shared::cta.b64 p, [%0], %1;\n@p bra.uni DONE;\n"
               "add.u32 c, c, 1;\nsetp.lt.u32 p, c, %2;\n@p bra.uni RETRY;\ntrap;\nDONE:\n}"
               ::"r"(bar), "r"(parity), "n"(1u << 19) : "memory");
}
__device__ __forceinline__ void tma3d(uint32_t dst, const CUtensorMap* m, uint32_t bar, int c0, int c1, int c2) {
  asm volatile(
      "cp.async.bulk.tensor.3d.shared::cluster.global.mbarrier::complete_tx::bytes [%0], [%1, {%3, %4, %5}], [%2];"
      ::"r"(dst), "l"(m), "r"(bar), "r"(c0), "r"(c1), "r"(c2) : "memory");
}
__device__ __forceinline__ void tma3d_mc(uint32_t dst, const CUtensorMap* m, uint32_t bar, int c0, int c1, int c2) {
  asm volatile(
      "cp.async.bulk.tensor.3d.shared::cluster.global.mbarrier::complete_tx::bytes.multicast::cluster"
      " [%0], [%1, {%3, %4, %5}], [%2], %6;"
      ::"r"(dst), "l"(m), "r"(bar), "r"(c0), "r"(c1), "r"(c2), "h"((uint16_t)3) : "memory");
}
__device__ __forceinline__ void tma2d(uint32_t dst, const CUtensorMap* m, uint32_t bar, int c0, int c1) {
  asm volatile(
      "cp.async.bulk.tensor.2d.shared::cluster.global.mbarrier::complete_tx::bytes [%0], [%1, {%3, %4}], [%2];"
      ::"r"(dst), "l"(m), "r"(bar), "r"(c0), "r"(c1) : "memory");
}
__device__ __forceinline__ void tma2d_store(const CUtensorMap* m, uint32_t src, int c0, int c1) {
  asm volatile("cp.async.bulk.tensor.2d.global.shared::cta.bulk_group [%0, {%2, %3}], [%1];"
               ::"l"(m), "r"(src), "r"(c0), "r"(c1) : "memory");
}
__device__ __forceinline__ int lane_id() {
  int l;
  asm volatile("mov.u32 %0, %%laneid;" : "=r"(l));
  return l;
}
__device__ __forceinline__ bool elect() {
  uint32_t p;
  asm volatile("{\n.reg .pred p;\nelect.sync _|p, 0xffffffff;\nselp.b32 %0, 1, 0, p;\n}" : "=r"(p));
  return p;
}
__device__ __forceinline__ void bulk_load(uint32_t dst, const void* src, uint32_t bytes, uint32_t bar) {
  asm volatile("cp.async.bulk.shared::cluster.global.mbarrier::complete_tx::bytes [%0], [%1], %2, [%3];"
               ::"r"(dst), "l"(src), "r"(bytes), "r"(bar) : "memory");
}
__device__ __forceinline__ void bulk_store(void* dst, uint32_t src, uint32_t bytes) {
  asm volatile("cp.async.bulk.global.shared::cta.bulk_group [%0], [%1], %2;" ::"l"(dst), "r"(src), "r"(bytes)
               : "memory");
}
__device__ __forceinline__ void bulk_commit() { asm volatile("cp.async.bulk.commit_group;" ::: "memory"); }
__device__ __forceinline__ void bulk_wait_read() { asm volatile("cp.async.bulk.wait_group.read 0;" ::: "memory"); }
__device__ __forceinline__ void bulk_wait() { asm volatile("cp.async.bulk.wait_group 0;" ::: "memory"); }
__device__ __forceinline__ void fence_async_smem() { asm volatile("fence.proxy.async.shared::cta;" ::: "memory"); }
__device__ __forceinline__ unsigned ld_relaxed(const unsigned* p) {
  unsigned v;
  asm volatile("ld.relaxed.gpu.global.u32 %0, [%1];" : "=r"(v) : "l"(p) : "memory");
  return v;
}
__device__ __forceinline__ uint2 ld_relaxed2(const uint2* p) {
  uint2 v;
  asm volatile("{\n.reg .b64 t;\nld.relaxed.gpu.global.b64 t, [%2];\nmov.b64 {%0, %1}, t;\n}"
               : "=r"(v.x), "=r"(v.y) : "l"(p) : "memory");
  return v;
}
__device__ __forceinline__ void st_relaxed(unsigned* p, unsigned v) {
  asm volatile("st.relaxed.gpu.global.u32 [%0], %1;" ::"l"(p), "r"(v) : "memory");
}
__device__ __forceinline__ void st_release(unsigned* p, unsigned v) {
  asm volatile("st.release.gpu.global.u32 [%0], %1;" ::"l"(p), "r"(v) : "memory");
}
__device__ __forceinline__ void wait_flags(const unsigned* p, unsigned epoch) {
  while (__any_sync(0xffffffffu, ld_relaxed(p) != epoch)) {
  }
  asm volatile("fence.acquire.gpu;\nfence.proxy.async.global;" ::: "memory");
  __syncwarp();
}
__device__ __forceinline__ void st_packet(uint4* p, uint32_t d0, uint32_t d1, uint32_t tag) {
  asm volatile("{\n.reg .b128 v;\n.reg .b64 x, y;\nmov.b64 x, {%1, %2};\nmov.b64 y, {%3, %3};\nmov.b128 v, {x, y};\n"
               "st.relaxed.gpu.global.b128 [%0], v;\n}" ::"l"(p), "r"(d0), "r"(d1), "r"(tag) : "memory");
}
__device__ __forceinline__ void ld_packet(const uint4* p, uint32_t& d0, uint32_t& d1, uint32_t& tag) {
  asm volatile("{\n.reg .b128 v;\n.reg .b64 x, y;\n.reg .b32 u;\nld.relaxed.gpu.global.b128 v, [%3];\n"
               "mov.b128 {x, y}, v;\nmov.b64 {%0, %1}, x;\nmov.b64 {%2, u}, y;\n}"
               : "=r"(d0), "=r"(d1), "=r"(tag) : "l"(p) : "memory");
}
__device__ __forceinline__ unsigned tag_value(float v, unsigned epoch) {
  return (__float_as_uint(v) & ~7u) | (epoch & 7u);
}
__device__ __forceinline__ float untag_value(unsigned v) { return __uint_as_float(v & ~7u); }
__device__ __forceinline__ void stsm4(uint32_t a, uint32_t r0, uint32_t r1, uint32_t r2, uint32_t r3) {
  asm volatile("stmatrix.sync.aligned.m8n8.x4.shared.b16 [%0], {%1, %2, %3, %4};" ::"r"(a), "r"(r0), "r"(r1),
               "r"(r2), "r"(r3) : "memory");
}
__device__ __forceinline__ void stsm4_t(uint32_t a, uint32_t r0, uint32_t r1, uint32_t r2, uint32_t r3) {
  asm volatile("stmatrix.sync.aligned.m8n8.x4.trans.shared.b16 [%0], {%1, %2, %3, %4};" ::"r"(a), "r"(r0),
               "r"(r1), "r"(r2), "r"(r3) : "memory");
}
__device__ __forceinline__ uint32_t transpose8(uint32_t a) {
  uint32_t d;
  asm volatile("movmatrix.sync.aligned.m8n8.trans.b16 %0, %1;" : "=r"(d) : "r"(a));
  return d;
}
__device__ __forceinline__ void mma16816(float (&c)[4], uint32_t a0, uint32_t a1, uint32_t a2, uint32_t a3,
                                         uint32_t b0, uint32_t b1) {
  asm volatile("mma.sync.aligned.m16n8k16.row.col.f32.bf16.bf16.f32 {%0, %1, %2, %3}, {%4, %5, %6, %7}, {%8, %9}, "
               "{%0, %1, %2, %3};"
               : "+f"(c[0]), "+f"(c[1]), "+f"(c[2]), "+f"(c[3])
               : "r"(a0), "r"(a1), "r"(a2), "r"(a3), "r"(b0), "r"(b1));
}
__device__ __forceinline__ void mma1688(float (&c)[4], uint32_t a0, uint32_t a1, uint32_t b0) {
  asm volatile("mma.sync.aligned.m16n8k8.row.col.f32.bf16.bf16.f32 {%0, %1, %2, %3}, {%4, %5}, {%6}, {%0, %1, %2, %3};"
               : "+f"(c[0]), "+f"(c[1]), "+f"(c[2]), "+f"(c[3]) : "r"(a0), "r"(a1), "r"(b0));
}
__device__ __forceinline__ float shfl_xor(float v, int m) {
  float r;
  asm volatile("shfl.sync.bfly.b32 %0, %1, %2, 31, 0xffffffff;" : "=f"(r) : "f"(v), "r"(m));
  return r;
}
__device__ __forceinline__ float tanh_fast(float x) {
  float r;
  asm volatile("tanh.approx.f32 %0, %1;" : "=f"(r) : "f"(x));
  return r;
}
__device__ __forceinline__ void ldsm4(uint32_t a, uint32_t (&r)[4]) {
  asm volatile("ldmatrix.sync.aligned.m8n8.x4.shared.b16 {%0, %1, %2, %3}, [%4];"
               : "=r"(r[0]), "=r"(r[1]), "=r"(r[2]), "=r"(r[3]) : "r"(a) : "memory");
}
__device__ __forceinline__ void ldsm4_t(uint32_t a, uint32_t (&r)[4]) {
  asm volatile("ldmatrix.sync.aligned.m8n8.x4.trans.shared.b16 {%0, %1, %2, %3}, [%4];"
               : "=r"(r[0]), "=r"(r[1]), "=r"(r[2]), "=r"(r[3]) : "r"(a) : "memory");
}
__device__ __forceinline__ uint32_t pack2(float lo, float hi) {
  uint32_t r;
  asm volatile("cvt.rn.bf16x2.f32 %0, %1, %2;" : "=r"(r) : "f"(hi), "f"(lo));
  return r;
}
__device__ __forceinline__ float bf_lo(uint32_t r) { return __uint_as_float(r << 16); }
__device__ __forceinline__ float bf_hi(uint32_t r) { return __uint_as_float(r & 0xffff0000u); }
__device__ __forceinline__ float ex2(float x) {
  float r;
  asm("ex2.approx.ftz.f32 %0, %1;" : "=f"(r) : "f"(x));
  return r;
}
__device__ __forceinline__ float rcp(float x) {
  float r;
  asm("rcp.approx.ftz.f32 %0, %1;" : "=f"(r) : "f"(x));
  return r;
}
template <int N>
__device__ __forceinline__ void wg_wait() {
  asm volatile("wgmma.wait_group.sync.aligned %0;" ::"n"(N) : "memory");
}
__device__ __forceinline__ void yield_slot() { asm volatile("pmevent 0;"); }

template <int N, int KIND>
__device__ __forceinline__ void mma_kblock(float (&acc)[2][96], uint32_t a, uint32_t b);

#define F8(m, d, i) m(d[i]), m(d[i + 1]), m(d[i + 2]), m(d[i + 3]), m(d[i + 4]), m(d[i + 5]), m(d[i + 6]), m(d[i + 7])
#define KSTEP(N, A, B, oa0, oa1, ob, sd)                                                   \
  "mov.b64 db, {" B ", hb};\nadd.u64 db, db, " #ob ";\n"                                    \
  "mov.b64 da, {" A ", ha};\nadd.u64 da, da, " #oa0 ";\n"                                   \
  "wgmma.mma_async.sync.aligned.m64n" #N "k16.f32.bf16.bf16 {" ACC##N##_0 "}, da, db, " #sd ", 1, 1, 0, 1;\n" \
  "mov.b64 da, {" A ", ha};\nadd.u64 da, da, " #oa1 ";\n"                                   \
  "wgmma.mma_async.sync.aligned.m64n" #N "k16.f32.bf16.bf16 {" ACC##N##_1 "}, da, db, " #sd ", 1, 1, 0, 1;\n"

#define MMA_KBLOCK(N, KIND, A, B, ob2, ob3, sd, MID, MODE)                                 \
  template <>                                                                              \
  __device__ __forceinline__ void mma_kblock<N, KIND>(float (&acc)[2][96], uint32_t a, uint32_t b) { \
    asm volatile("{\n.reg .b32 ha, hb;\n.reg .b64 da, db;\n"                            \
                 "mov.b32 ha, 0x40000080;\nmov.b32 hb, 0x40000040;\n"                       \
                 "wgmma.fence.sync.aligned;\n"                                             \
                 KSTEP(N, A, B, 0, 64, 0, sd) KSTEP(N, A, B, 2, 66, 128, 1) MID               \
                 KSTEP(N, A, B, 4, 68, ob2, 1) KSTEP(N, A, B, 6, 70, ob3, 1) "wgmma.commit_group.sync.aligned;\n}\n"  \
                 : OPS##N(MODE) : "r"(a), "r"(b) : "memory");                              \
  }
#define MMA_KBLOCKS(N, A, B, ob2, ob3)                                                     \
  MMA_KBLOCK(N, 0, A, B, ob2, ob3, 1, "", "+f")                                            \
  MMA_KBLOCK(N, 1, A, B, ob2, ob3, 1, "wgmma.commit_group.sync.aligned;\n", "+f")          \
  MMA_KBLOCK(N, 2, A, B, ob2, ob3, 0, "", "=f")

#define ACC128_0 \
  "%0, %1, %2, %3, %4, %5, %6, %7, %8, %9, %10, %11, %12, %13, %14, %15, " \
  "%16, %17, %18, %19, %20, %21, %22, %23, %24, %25, %26, %27, %28, %29, %30, %31, " \
  "%32, %33, %34, %35, %36, %37, %38, %39, %40, %41, %42, %43, %44, %45, %46, %47, " \
  "%48, %49, %50, %51, %52, %53, %54, %55, %56, %57, %58, %59, %60, %61, %62, %63"
#define ACC128_1 \
  "%64, %65, %66, %67, %68, %69, %70, %71, %72, %73, %74, %75, %76, %77, %78, %79, " \
  "%80, %81, %82, %83, %84, %85, %86, %87, %88, %89, %90, %91, %92, %93, %94, %95, " \
  "%96, %97, %98, %99, %100, %101, %102, %103, %104, %105, %106, %107, %108, %109, %110, %111, " \
  "%112, %113, %114, %115, %116, %117, %118, %119, %120, %121, %122, %123, %124, %125, %126, %127"
#define OPS128(m) \
  F8(m, acc[0], 0), F8(m, acc[0], 8), F8(m, acc[0], 16), F8(m, acc[0], 24), F8(m, acc[0], 32), F8(m, acc[0], 40), F8(m, acc[0], 48), F8(m, acc[0], 56), \
        F8(m, acc[1], 0), F8(m, acc[1], 8), F8(m, acc[1], 16), F8(m, acc[1], 24), F8(m, acc[1], 32), F8(m, acc[1], 40), F8(m, acc[1], 48), F8(m, acc[1], 56)
MMA_KBLOCKS(128, "%128", "%129", 512, 640)

#define ACC192_0 \
  "%0, %1, %2, %3, %4, %5, %6, %7, %8, %9, %10, %11, %12, %13, %14, %15, " \
  "%16, %17, %18, %19, %20, %21, %22, %23, %24, %25, %26, %27, %28, %29, %30, %31, " \
  "%32, %33, %34, %35, %36, %37, %38, %39, %40, %41, %42, %43, %44, %45, %46, %47, " \
  "%48, %49, %50, %51, %52, %53, %54, %55, %56, %57, %58, %59, %60, %61, %62, %63, " \
  "%64, %65, %66, %67, %68, %69, %70, %71, %72, %73, %74, %75, %76, %77, %78, %79, " \
  "%80, %81, %82, %83, %84, %85, %86, %87, %88, %89, %90, %91, %92, %93, %94, %95"
#define ACC192_1 \
  "%96, %97, %98, %99, %100, %101, %102, %103, %104, %105, %106, %107, %108, %109, %110, %111, " \
  "%112, %113, %114, %115, %116, %117, %118, %119, %120, %121, %122, %123, %124, %125, %126, %127, " \
  "%128, %129, %130, %131, %132, %133, %134, %135, %136, %137, %138, %139, %140, %141, %142, %143, " \
  "%144, %145, %146, %147, %148, %149, %150, %151, %152, %153, %154, %155, %156, %157, %158, %159, " \
  "%160, %161, %162, %163, %164, %165, %166, %167, %168, %169, %170, %171, %172, %173, %174, %175, " \
  "%176, %177, %178, %179, %180, %181, %182, %183, %184, %185, %186, %187, %188, %189, %190, %191"
#define OPS192(m) \
  F8(m, acc[0], 0), F8(m, acc[0], 8), F8(m, acc[0], 16), F8(m, acc[0], 24), F8(m, acc[0], 32), F8(m, acc[0], 40), F8(m, acc[0], 48), F8(m, acc[0], 56), F8(m, acc[0], 64), F8(m, acc[0], 72), F8(m, acc[0], 80), F8(m, acc[0], 88), \
        F8(m, acc[1], 0), F8(m, acc[1], 8), F8(m, acc[1], 16), F8(m, acc[1], 24), F8(m, acc[1], 32), F8(m, acc[1], 40), F8(m, acc[1], 48), F8(m, acc[1], 56), F8(m, acc[1], 64), F8(m, acc[1], 72), F8(m, acc[1], 80), F8(m, acc[1], 88)
MMA_KBLOCKS(192, "%192", "%193", 768, 896)

#define HSTEP(oa, ob)                                                                       \
  "mov.b64 db, {%97, hb};\nadd.u64 db, db, " #ob ";\nmov.b64 da, {%96, ha};\nadd.u64 da, da, " #oa ";\n" \
  "wgmma.mma_async.sync.aligned.m64n192k16.f32.bf16.bf16 {" ACC192_0 "}, da, db, 1, 1, 1, 0, 1;\n"
__device__ __forceinline__ void mma_half(float (&d)[96], uint32_t a, uint32_t b) {
  asm volatile("{\n.reg .b32 ha, hb;\n.reg .b64 da, db;\nmov.b32 ha, 0x40000080;\nmov.b32 hb, 0x40000040;\n"
               "wgmma.fence.sync.aligned;\n" HSTEP(0, 0) HSTEP(2, 128) HSTEP(4, 768) HSTEP(6, 896)
               "wgmma.commit_group.sync.aligned;\n}\n"
               : F8("+f", d, 0), F8("+f", d, 8), F8("+f", d, 16), F8("+f", d, 24), F8("+f", d, 32), F8("+f", d, 40),
                 F8("+f", d, 48), F8("+f", d, 56), F8("+f", d, 64), F8("+f", d, 72), F8("+f", d, 80), F8("+f", d, 88)
               : "r"(a), "r"(b) : "memory");
}

#define TSTEP(REGS, W, X, ow, ox)                                                           \
  "mov.b64 db, {" X ", hi};\nadd.u64 db, db, " #ox ";\nmov.b64 da, {" W ", hi};\nadd.u64 da, da, " #ow ";\n" \
  "wgmma.mma_async.sync.aligned.m64n128k16.f32.bf16.bf16 {" REGS "}, da, db, 1, 1, 1, 1, 0;\n"
#define THEAD "{\n.reg .b32 hi;\n.reg .b64 da, db;\nmov.b32 hi, 0x40000040;\nwgmma.fence.sync.aligned;\n"
#define TTAIL "wgmma.commit_group.sync.aligned;\n}\n"
__device__ __forceinline__ void mma_kblock_t(float (&acc)[2][96], uint32_t wd, uint32_t xd) {
  asm volatile(THEAD TSTEP(ACC128_0, "%128", "%129", 0, 0) TSTEP(ACC128_1, "%128", "%129", 256, 0)
               TSTEP(ACC128_0, "%128", "%129", 128, 2) TSTEP(ACC128_1, "%128", "%129", 384, 2)
               TSTEP(ACC128_0, "%128", "%129", 512, 4) TSTEP(ACC128_1, "%128", "%129", 768, 4)
               TSTEP(ACC128_0, "%128", "%129", 640, 6) TSTEP(ACC128_1, "%128", "%129", 896, 6) TTAIL
               : OPS128("+f") : "r"(wd), "r"(xd) : "memory");
}
__device__ __forceinline__ void mma_half_t(float (&d)[96], uint32_t wd, uint32_t xd) {
  asm volatile(THEAD TSTEP(ACC128_0, "%64", "%65", 0, 0) TSTEP(ACC128_0, "%64", "%65", 128, 2)
               TSTEP(ACC128_0, "%64", "%65", 512, 4) TSTEP(ACC128_0, "%64", "%65", 640, 6) TTAIL
               : F8("+f", d, 0), F8("+f", d, 8), F8("+f", d, 16), F8("+f", d, 24), F8("+f", d, 32), F8("+f", d, 40),
                 F8("+f", d, 48), F8("+f", d, 56) : "r"(wd), "r"(xd) : "memory");
}

enum { kModePlain = 0, kModeHead = 1, kModeSkip = 2, kModeContinue = 3 };

template <int N>
__device__ __forceinline__ void fence_acc(float (&acc)[2][96]) {
#pragma unroll
  for (int h = 0; h < 2; h++)
#pragma unroll
    for (int i = 0; i < N / 2; i++) asm volatile("" : "+f"(acc[h][i])::"memory");
}

constexpr uint32_t kToB = (kTileBytes >> 4) + ((4096u >> 4) << 16) - (1u << 16);

#define TRACE_KB(nb)

template <int N>
__device__ __forceinline__ void head_blocks(float (&acc)[2][96], uint32_t sb, int n0, int slot, int xver,
                                            uint32_t rel_addr, bool rel) {
  const uint32_t ring = (((sb & 0x3FFFF) + kSmRing) >> 4) | (1u << 16);
  const uint32_t xdesc = (((sb & 0x3FFFF) + kSmX) >> 4) | (1u << 16);
  const uint32_t s0 = ring + slot * 2560, s1 = ring + ((slot + 1) & 3) * 2560;
  const uint32_t nb = n0 * 8, xbar = sb + kBarX + (xver - 1) * 16;
  if (xver > 0) {
    mbar_wait(xbar, 0);
    mbar_wait(sb + kBarTurn + (xver == 1 ? 2 : 3 * xver) * 8, 0);
  }
  mbar_wait(sb + kBarFull + (nb & 56), nb >> 6);
  if (n0 == 0) TRACE_AT(0, 1);
  TRACE_KB(nb);
  mma_kblock<N, 2>(acc, xver > 0 ? xdesc : s0, s0 + kToB);
  if (xver > 0) mbar_wait(xbar + 8, 0);
  mbar_wait(sb + kBarFull + (nb & 56) + 8, nb >> 6);
  TRACE_KB(nb + 8);
  mma_kblock<N, 0>(acc, xver > 0 ? xdesc + (kTileBytes >> 4) : s1, s1 + kToB);
  wg_wait<1>();
  if (rel) mbar_arrive_cluster(rel_addr + (nb & 56));
  wg_wait<0>();
  if (rel) mbar_arrive_cluster(rel_addr + (nb & 56) + 8);
  fence_acc<N>(acc);
}

enum { kPlain, kResid, kStagger };
template <int N, int KIND, class Pre>
__device__ __forceinline__ void mainloop(float (&acc)[2][96], uint32_t sb, int tile, int n0, int slot, int nkb,
                                         int pause_kk, int att, uint32_t rel_addr, bool rel, int own_kk, Pre pre,
                                         uint32_t prev = 64) {
  constexpr bool RESID = KIND == kResid;
  constexpr uint32_t kStep = (N == 192 ? 5 : 4) * 512;
  const uint32_t ring = (((sb & 0x3FFFF) + kSmRing) >> 4) | (1u << 16);
  uint32_t st = ring + slot * kStep;
  uint32_t nb = n0 * 8;
  const uint32_t last = nb + 8 * (nkb - (RESID ? 4 : KIND == kStagger ? 2 : 1)), own = nb + 8 * own_kk;
  const uint32_t stg = (((sb & 0x3FFFF) + kSmStg) >> 4) | (1u << 16);
  uint32_t stop = pause_kk >= 0 ? nb + 8 * pause_kk : last;
  const bool signal = (threadIdx.x & 127) == 64;
  fence_acc<N>(acc);
  if (tile > 0) mbar_wait(sb + kBarTurn + (tile - 1) * 8, 0);
  TRACE_AT(tile, 0);
#pragma unroll 1
  while (true) {
#pragma unroll 1
    do {
      mbar_wait(sb + kBarFull + (nb & 56), nb >> 6);
      TRACE_KB(nb);
      if constexpr (RESID) mma_kblock_t(acc, st + kToB, nb == own ? stg : st);
      else mma_kblock<N, 0>(acc, st, st + kToB);
      wg_wait<1>();
      if (rel) mbar_arrive_cluster(rel_addr + prev);
      prev = nb & 56;
      st += kStep;
      if (st == ring + 10240) st = ring;
      nb += 8;
    } while (nb != stop);
    if (stop == last) break;
    stop = last;
    if (signal) mbar_arrive(sb + kBarPause + att * 8);
    wg_wait<0>();
    if (rel) mbar_arrive_cluster(rel_addr + prev);
    prev = 64;
    mbar_wait(sb + kBarResume + att * 8, 0);
  }
  mbar_wait(sb + kBarFull + (nb & 56), nb >> 6);
  TRACE_KB(nb);
  if constexpr (RESID) {
    const uint32_t z = gridDim.y - 1;
    const uint32_t s1 = st + kStep, s2 = s1 + kStep, s3 = s2 == ring + 8192 ? ring : s2 + kStep;
    mma_half_t(acc[0], st + kToB, st);
    wg_wait<1>();
    if (rel) mbar_arrive_cluster(rel_addr + 24);
    mbar_wait(sb + kBarFull + 40, nb >> 6);
    TRACE_KB(nb + 8);
    mma_half_t(acc[0], s1 + kToB, s1);
    mbar_wait(sb + kBarFull + 48, nb >> 6);
    TRACE_KB(nb + 16);
    mma_half_t(acc[0], s2 + kToB, s2);
    mbar_wait(sb + kBarFull + 56, nb >> 6);
    TRACE_KB(nb + 24);
    mma_half_t(acc[0], s3 + kToB, s3);
    mma_half_t(acc[1], st + kToB + 256, st + z);
    mma_half_t(acc[1], s1 + kToB + 256, s1 + z);
    wg_wait<2>();
#pragma unroll
    for (int i = 0; i < 64; i++) asm volatile("" : "+f"(acc[0][i])::"memory");
    pre(0);
    mma_half_t(acc[1], s2 + kToB + 256, s2 + z);
    wg_wait<2>();
    if (rel) mbar_arrive_cluster(rel_addr + 32);
    pre(1);
    mma_half_t(acc[1], s3 + kToB + 256, s3 + z);
    wg_wait<2>();
    if (rel) mbar_arrive_cluster(rel_addr + 40);
    wg_wait<1>();
    if (signal) mbar_arrive(sb + kBarTurn + tile * 8);
    if (rel) mbar_arrive_cluster(rel_addr + 48);
    wg_wait<0>();
    if (rel) mbar_arrive_cluster(rel_addr + 56);
#pragma unroll
    for (int i = 0; i < 64; i++) asm volatile("" : "+f"(acc[1][i])::"memory");
  } else if constexpr (KIND == kStagger) {
    const uint32_t z = gridDim.y - 1, s2 = st + kStep;
    mma_half(acc[1], st + 64, st + kToB);
    wg_wait<1>();
    if (rel) mbar_arrive_cluster(rel_addr + 40);
    mbar_wait(sb + kBarFull + 56, nb >> 6);
    TRACE_KB(nb + 8);
    mma_half(acc[1], s2 + 64, s2 + kToB);
    mma_half(acc[0], st, st + z + kToB);
    pre(0);
    mma_half(acc[0], s2, s2 + z + kToB);
    wg_wait<2>();
#pragma unroll
    for (int i = 0; i < 96; i++) asm volatile("" : "+f"(acc[1][i])::"memory");
    pre(1);
    wg_wait<1>();
    if (rel) mbar_arrive_cluster(rel_addr + 48);
    pre(2);
    if (signal) mbar_arrive(sb + kBarTurn + tile * 8);
    pre(3);
    wg_wait<0>();
    if (rel) mbar_arrive_cluster(rel_addr + 56);
#pragma unroll
    for (int i = 0; i < 96; i++) asm volatile("" : "+f"(acc[0][i])::"memory");
  } else {
    mma_kblock<N, 1>(acc, st, st + kToB);
    wg_wait<2>();
    if (rel) mbar_arrive_cluster(rel_addr + prev);
    pre();
    wg_wait<1>();
    if (signal) mbar_arrive(sb + kBarTurn + tile * 8);
    wg_wait<0>();
    if (rel) mbar_arrive_cluster(rel_addr + (nb & 56));
    fence_acc<N>(acc);
  }
}

__device__ __forceinline__ void publish_stats(uint32_t sb, uint2* stat, int w, int lane, unsigned epoch) {
  const uint32_t row = sb + kSmX + (32 * w + lane) * 128;
  float s[4], q[4];
#pragma unroll
  for (int c = 0; c < 4; c++) s[c] = q[c] = 0.f;
  uint32_t nx[4];
  ldsm4(row + ((lane & 7) << 4), nx);
#pragma unroll 1
  for (int J = 1; J <= 16; J++) {
    const uint32_t r[4] = {nx[0], nx[1], nx[2], nx[3]};
    ldsm4(row + ((J >> 3) & 1) * kTileBytes + (((J ^ lane) & 7) << 4), nx);
#pragma unroll
    for (int c = 0; c < 4; c++) {
      const float lo = bf_lo(r[c]);
      s[c] += lo;
      q[c] = fmaf(lo, lo, q[c]);
      if (c & 1) yield_slot();
    }
#pragma unroll
    for (int c = 0; c < 4; c++) {
      const float hi = bf_hi(r[c]);
      s[c] += hi;
      q[c] = fmaf(hi, hi, q[c]);
      if (c & 1) yield_slot();
    }
  }
  const int t = lane & 3, g = lane >> 2;
#pragma unroll
  for (int c = 0; c < 2; c++) {
    s[c] = (t & 2 ? s[c + 2] : s[c]) + shfl_xor(t & 2 ? s[c] : s[c + 2], 2);
    q[c] = (t & 2 ? q[c + 2] : q[c]) + shfl_xor(t & 2 ? q[c] : q[c + 2], 2);
  }
  const float so = (t & 1 ? s[1] : s[0]) + shfl_xor(t & 1 ? s[0] : s[1], 1);
  const float qo = (t & 1 ? q[1] : q[0]) + shfl_xor(t & 1 ? q[0] : q[1], 1);
  asm volatile("{\n.reg .b64 t;\nmov.b64 t, {%1, %2};\nst.relaxed.gpu.global.b64 [%0], t;\n}" ::"l"(stat + 32 * w + 8 * t + g),
               "r"(tag_value(so, epoch)), "r"(__float_as_uint(qo)) : "memory");
}

__device__ __forceinline__ void add_chunk(float (&a)[8], const uint4& v) {
  a[0] += bf_lo(v.x); a[1] += bf_hi(v.x);
  a[2] += bf_lo(v.y); a[3] += bf_hi(v.y);
  a[4] += bf_lo(v.z); a[5] += bf_hi(v.z);
  a[6] += bf_lo(v.w); a[7] += bf_hi(v.w);
}

__device__ __forceinline__ int helper_col(int id, int slab) {
  return (slab < 3 ? slab * kD : (slab - 3) * 512) + id * 128;
}
__device__ __forceinline__ void helper_cta(const CUtensorMap* map_q, const CUtensorMap* map_1, uint8_t* sm,
                                           uint32_t sb, int id, int warp) {
  constexpr int kRed = 6 * 32768, kBar = kRed + 2 * 4096;
  const int tid = threadIdx.x;
  if (warp == 8 && elect()) {
#pragma unroll
    for (int s = 0; s < 6; s++) {
      mbar_init(sb + kBar + s * 8, 1);
      mbar_init(sb + kBar + 64 + s * 8, 4);
    }
    fence_async_smem();
#pragma unroll
    for (int s = 0; s < 6; s++) {
      mbar_expect_tx(sb + kBar + s * 8, 32768);
      tma2d(sb + s * 32768, map_q, sb + kBar + s * 8, id * 128, s * 128);
    }
  }
  __syncthreads();
  if (warp == 8) {
    int slot = 0, ph = 0;
#pragma unroll 1
    for (int n = 6; n < 80; n++) {
      mbar_wait(sb + kBar + 64 + slot * 8, ph);
      if (elect()) {
        mbar_expect_tx(sb + kBar + slot * 8, 32768);
        tma2d(sb + slot * 32768, n < 24 ? map_q : map_1, sb + kBar + slot * 8, helper_col(id, n >> 3), (n & 7) * 128);
      }
      if (++slot == 6) slot = 0, ph ^= 1;
    }
  } else if (warp < 8) {
    if (tid == 0) *reinterpret_cast<unsigned*>(sm + kBar + 128) = atomicAdd(&g_ticket, 1u) / kGrid + 1;
    int slot = warp >> 2, ph = 0;
#pragma unroll 1
    for (int slab = 0; slab < 10; slab++) {
      float a[8];
#pragma unroll
      for (int e = 0; e < 8; e++) a[e] = 0.f;
#pragma unroll 1
      for (int box = 0; box < 4; box++) {
        mbar_wait_bounded(sb + kBar + slot * 8, ph);
        const uint4* p = reinterpret_cast<const uint4*>(sm + slot * 32768) + (tid & 127);
        uint4 v[16];
#pragma unroll
        for (int i = 0; i < 16; i++) v[i] = p[i * 128];
        __syncwarp();
        if (elect()) mbar_arrive(sb + kBar + 64 + slot * 8);
#pragma unroll
        for (int i = 0; i < 16; i++) add_chunk(a, v[i]);
        slot += 2;
        if (slot >= 6) slot -= 6, ph ^= 1;
      }
      float* red = reinterpret_cast<float*>(sm + kRed + (slab & 1) * 4096);
#pragma unroll
      for (int e = 0; e < 8; e++) a[e] += shfl_xor(a[e], 16);
      if ((tid & 16) == 0) {
        float4* d = reinterpret_cast<float4*>(red + warp * 128 + (tid & 15) * 8);
        d[0] = make_float4(a[0], a[1], a[2], a[3]);
        d[1] = make_float4(a[4], a[5], a[6], a[7]);
      }
      asm volatile("bar.sync 1, 256;" ::: "memory");
      if (warp < 4) {
        float t = 0.f;
#pragma unroll
        for (int q = 0; q < 8; q++) t += red[q * 128 + tid];
        st_relaxed(g_cs + (slab < 3 ? 0 : 3 * kD) + helper_col(id, slab) + tid,
                   tag_value(t, *reinterpret_cast<volatile unsigned*>(sm + kBar + 128)));
      }
    }
  }
}

__device__ __forceinline__ void colsum_strip(const CUtensorMap* map, uint8_t* sm, uint32_t sb, int col, int half,
                                             int lane, unsigned epoch) {
  const uint32_t bar = sb + kBarSlab + half * 16;
  const int buf = kSmStg + half * 8192;
  float a[8];
#pragma unroll
  for (int e = 0; e < 8; e++) a[e] = 0.f;
#pragma unroll 1
  for (int r = -2; r < 4; r++) {
    if (r >= 0) {
      mbar_wait(bar + (r & 1) * 8, r >> 1);
      const uint4* p = reinterpret_cast<const uint4*>(sm + buf + (r & 1) * 4096) + lane;
#pragma unroll 1
      for (int q = 0; q < 8; q += 4) {
        uint4 v[4];
#pragma unroll
        for (int u = 0; u < 4; u++) v[u] = p[(q + u) * 32];
#pragma unroll
        for (int u = 0; u < 4; u++) {
          a[0] += bf_lo(v[u].x); a[1] += bf_hi(v[u].x); a[2] += bf_lo(v[u].y); a[3] += bf_hi(v[u].y);
          yield_slot();
          a[4] += bf_lo(v[u].z); a[5] += bf_hi(v[u].z); a[6] += bf_lo(v[u].w); a[7] += bf_hi(v[u].w);
          yield_slot();
        }
      }
      fence_async_smem();
      __syncwarp();
    }
    if (r < 2 && elect()) {
      mbar_expect_tx(bar + (r & 1) * 8, 4096);
      tma2d(sb + buf + (r & 1) * 4096, map, bar + (r & 1) * 8, col, half * 512 + (r + 2) * 128);
    }
  }
#pragma unroll
  for (int e = 0; e < 4; e++) a[e] = (lane & 16 ? a[e + 4] : a[e]) + shfl_xor(lane & 16 ? a[e] : a[e + 4], 16);
#pragma unroll
  for (int e = 0; e < 2; e++) a[e] = (lane & 8 ? a[e + 2] : a[e]) + shfl_xor(lane & 8 ? a[e] : a[e + 2], 8);
  a[0] = (lane & 4 ? a[1] : a[0]) + shfl_xor(lane & 4 ? a[0] : a[1], 4);
  a[0] += shfl_xor(a[0], 2);
  if (!(lane & 2)) st_relaxed(g_cs + half * (3 * kD + kF) + col + (lane & 1) * 8 + (lane >> 2), tag_value(a[0], epoch));
}

constexpr float kGeluBeta = 0.3292034911525734f / 2.f;
constexpr float kGeluK = 2.423681954311584f / 4.f;
constexpr float kHScale = 2.f * kGeluBeta;

__device__ __forceinline__ void store_staged(uint8_t* dst, uint32_t stg) {
  fence_async_smem();
  __syncwarp();
  if (elect()) {
    bulk_store(dst, stg, 4096);
    bulk_commit();
  }
}

#define GY_MASK 5
#define GF_MASK 3
#define GY(k) if ((GY_MASK >> k) & 1) yield_slot()
template <int J0, int J1>
__device__ __forceinline__ void fold_norm(float (&acc)[2][96], const float2 (&st)[4], const float4* vec) {
  float4 vn = vec[J0 * 4];
#pragma unroll
  for (int J = J0; J < J1; J++) {
    const float4 v = vn;
    if (J + 1 < J1) vn = vec[J * 4 + 4];
#pragma unroll
    for (int c = 0; c < 4; c++) {
      float& a0 = acc[c & 1][4 * J + (c & 2)];
      float& a1 = acc[c & 1][4 * J + (c & 2) + 1];
      a0 = fmaf(a0, st[c].x, fmaf(st[c].y, v.x, v.z));
      a1 = fmaf(a1, st[c].x, fmaf(st[c].y, v.y, v.w));
      asm volatile("" : "+f"(a0), "+f"(a1));
      if ((c & 1) && ((GF_MASK >> (c >> 1)) & 1)) yield_slot();
    }
  }
}

template <int CH, class Acquire>
__device__ __forceinline__ void gelu_chunk(const float (&acc)[2][96], uint32_t stg, int lane, uint8_t* prev,
                                           Acquire acquire) {
  uint32_t pk[8][4];
  float z[3][4];
  const uint32_t row = (stg + lane * 128) ^ ((lane & 7) << 4);
#define U(s, e) acc[(e) >> 1][4 * (CH * 8 + ((s) >> 1)) + 2 * ((s) & 1) + ((e) & 1)]
#pragma unroll
  for (int s = 0; s < 18; s++) {
    const int cur = s % 3, p1 = (s + 2) % 3, p2 = (s + 1) % 3, q = s - 2, jj = 2 * q - 24;
    const bool mid = s >= 1 && s < 17;
    if (mid) z[p1][0] = tanh_fast(z[p1][0]);
    if (s < 16) {
#pragma unroll
      for (int e = 0; e < 4; e++) {
        z[cur][e] = fmaf(U(s, e), U(s, e), kGeluK);
        asm volatile("" : "+f"(z[cur][e]));
      }
    }
    if (jj >= 0) stsm4(row ^ (jj << 4), pk[jj][0], pk[jj][1], pk[jj][2], pk[jj][3]);
    GY(0);
    if (mid) z[p1][1] = tanh_fast(z[p1][1]);
    if (q >= 0) {
      pk[q >> 1][2 * (q & 1)] = pack2(fmaf(U(q, 0), z[p2][0], U(q, 0)), fmaf(U(q, 1), z[p2][1], U(q, 1)));
      pk[q >> 1][2 * (q & 1) + 1] = pack2(fmaf(U(q, 2), z[p2][2], U(q, 2)), fmaf(U(q, 3), z[p2][3], U(q, 3)));
    }
    GY(1);
    if (mid) z[p1][2] = tanh_fast(z[p1][2]);
    if (s < 16) {
#pragma unroll
      for (int e = 0; e < 4; e++) {
        z[cur][e] = z[cur][e] * U(s, e) * 8.f;
        asm volatile("" : "+f"(z[cur][e]));
      }
    }
    if (mid) z[p1][3] = tanh_fast(z[p1][3]);
    if (jj >= 0) stsm4(row ^ ((jj + 1) << 4), pk[jj + 1][0], pk[jj + 1][1], pk[jj + 1][2], pk[jj + 1][3]);
    GY(2);
    if (CH == 1 && s == 1) store_staged(prev, stg);
    if (q == 11) acquire();
  }
#undef U
}

__device__ __forceinline__ void scale_stats(float2 (&st)[4]) {
#pragma unroll
  for (int c = 0; c < 4; c++) {
    st[c].x *= kGeluBeta;
    st[c].y *= st[c].x;
  }
}

__device__ __forceinline__ void add_mean_term(float (&acc)[2][96], const float2 (&st)[4], uint8_t* sm, int tq,
                                              int lane) {
  const float2* cs = reinterpret_cast<const float2*>(sm + kSmCsQ) + tq * 96 + (lane & 3);
  float2 vn = cs[0];
#pragma unroll
  for (int J = 0; J < 24; J++) {
    const float2 v = vn;
    if (J < 23) vn = cs[J * 4 + 4];
#pragma unroll
    for (int c = 0; c < 4; c++) {
      acc[c & 1][4 * J + (c & 2)] = fmaf(st[c].y, v.x, acc[c & 1][4 * J + (c & 2)]);
      acc[c & 1][4 * J + (c & 2) + 1] = fmaf(st[c].y, v.y, acc[c & 1][4 * J + (c & 2) + 1]);
    }
    yield_slot();
  }
}

#define CV_MASK 1
#define HALO_AT 2
struct AttnRegs {
  uint32_t q[4][8], k[5][8], vt[5][8];
};
#define SCALED(c, J) pack2(acc[(c) & 1][4 * (J) + ((c) & 2)] * st[c].x, acc[(c) & 1][4 * (J) + ((c) & 2) + 1] * st[c].x)
__device__ __forceinline__ void convert_group(const float (&acc)[2][96], const float2 (&st)[4], AttnRegs& r, int c,
                                              int part) {
#pragma unroll
  for (int J = 0; J < 8; J++) {
    if (part == 0) r.q[c][J] = SCALED(c, J);
    if (part == 1) r.k[c + 1][J] = SCALED(c, 8 + J);
    if (part == 2) r.vt[c + 1][J] = transpose8(SCALED(c, 16 + J));
    if ((J & CV_MASK) == CV_MASK) yield_slot();
  }
}
#undef SCALED

__device__ __forceinline__ void convert_odd(const float (&acc)[2][96], const float2 (&st)[4], AttnRegs& r, int step,
                                            uint8_t* sm, uint32_t halo_bar, uint4* halo_out, bool send,
                                            unsigned epoch, int w, int lane) {
  if (step == 1) {
    convert_group(acc, st, r, 3, 2);
    convert_group(acc, st, r, 3, 1);
    if (w < 3) {
      uint2* hs = reinterpret_cast<uint2*>(sm + kSmHalo + w * 2048) + lane;
#pragma unroll
      for (int i = 0; i < 4; i++) {
        hs[i * 32] = make_uint2(r.k[4][2 * i], r.k[4][2 * i + 1]);
        hs[128 + i * 32] = make_uint2(r.vt[4][2 * i], r.vt[4][2 * i + 1]);
      }
      __syncwarp();
      if (elect()) mbar_arrive(halo_bar + w * 8);
    } else if (send) {
#pragma unroll
      for (int i = 0; i < 4; i++) {
        st_packet(halo_out + lane + i * 32, r.k[4][2 * i], r.k[4][2 * i + 1], epoch);
        st_packet(halo_out + lane + 128 + i * 32, r.vt[4][2 * i], r.vt[4][2 * i + 1], epoch);
      }
    }
  } else if (step == 2) {
    convert_group(acc, st, r, 1, 2);
  } else {
    convert_group(acc, st, r, 1, 1);
    convert_group(acc, st, r, 3, 0);
    convert_group(acc, st, r, 1, 0);
  }
}

__device__ __forceinline__ void epilogue_attn(const float (&acc)[2][96], const float2 (&st)[4], AttnRegs& r,
                                              uint8_t* sm, uint32_t sb, int layer, int tq, int b, int j,
                                              unsigned epoch, int tile, int w, int lane) {
  const int t = lane & 3, g = lane >> 2;
  const int hp = j + 8 * tq, att = 2 * layer + tq;
  auto& q = r.q;
  auto& k = r.k;
  auto& vt = r.vt;
  const bool first = w == 0 && (b & 7) == 0;
  const uint4* gh = g_halo + ((layer * 16 + b - 1) * 16 + hp) * 256 + lane;
  uint32_t tag[8];
#define LOAD_HALO()                                                                                    \
  _Pragma("unroll") for (int i = 0; i < 4; i++) {                                                      \
    ld_packet(gh + i * 32, k[0][2 * i], k[0][2 * i + 1], tag[i]);                                      \
    ld_packet(gh + 128 + i * 32, vt[0][2 * i], vt[0][2 * i + 1], tag[4 + i]);                          \
  }
#pragma unroll
  for (int c = 0; c <= 6; c++) {
    if (c == HALO_AT) {
#pragma unroll
      for (int i = 0; i < 8; i++) k[0][i] = vt[0][i] = tag[i] = 0u;
      if (w > 0) {
        mbar_wait(sb + kBarHalo + (att * 3 + w - 1) * 8, 0);
        const uint2* hs = reinterpret_cast<const uint2*>(sm + kSmHalo + (w - 1) * 2048) + lane;
#pragma unroll
        for (int i = 0; i < 4; i++) {
          const uint2 a = hs[i * 32], d = hs[128 + i * 32];
          k[0][2 * i] = a.x; k[0][2 * i + 1] = a.y;
          vt[0][2 * i] = d.x; vt[0][2 * i + 1] = d.y;
        }
      } else if (!first) {
        LOAD_HALO();
      }
    }
    if (c < 6) convert_group(acc, st, r, 2 * (c & 1), 2 - (c >> 1));
  }
  TRACE_AT(tile, 8);
  if (w == 0 && !first) {
#pragma unroll 1
    while (__any_sync(0xffffffffu, ((tag[0] ^ epoch) | (tag[1] ^ epoch) | (tag[2] ^ epoch) | (tag[3] ^ epoch)) |
                                       ((tag[4] ^ epoch) | (tag[5] ^ epoch) | (tag[6] ^ epoch) | (tag[7] ^ epoch)))) {
      LOAD_HALO();
    }
  }
  constexpr float kScale = 0.17677669529663687f * 1.4426950408889634f;
  const bool own0 = 2 * t <= g, own1 = 2 * t + 1 <= g;
  const uint32_t own_mask = (own0 ? 0xffffu : 0u) | (own1 ? 0xffff0000u : 0u);
  const uint32_t stg = sb + kSmStg + w * 4096;
  const uint32_t orow = stg + (lane & 7) * 128, ochunk = (lane >> 3) ^ (lane & 7);
  TRACE_AT(tile, 9);
  mbar_wait(sb + kBarPause + att * 8, 0);
  TRACE_AT(tile, 10);

  float s[2][6][4], o[2][4][2][4];
#pragma unroll
  for (int n = 0; n < 24; n++) {
    const int ks = n / 12, hd = (n % 12) / 6, m = n % 6, ca = 2 * (m / 3), kg = ca + m % 3, J = 4 * hd + 2 * ks;
    if (ks == 0) s[hd][m][0] = s[hd][m][1] = s[hd][m][2] = s[hd][m][3] = 0.f;
    mma16816(s[hd][m], q[ca][J], q[ca + 1][J], q[ca][J + 1], q[ca + 1][J + 1], k[kg][J], k[kg][J + 1]);
  }
  float v0[2][4], v1[2][4], m[2][4];
  uint32_t pp[2][4], po[2][4];
#define UNITS _Pragma("unroll") for (int hd = 0; hd < 2; hd++) _Pragma("unroll") for (int c = 0; c < 4; c++)
  UNITS {
    const int mp = 3 * (c >> 1) + (c & 1), r = 2 * (c & 1);
    float p0 = s[hd][mp][r], p1 = s[hd][mp][r + 1];
    if (c == 0 && first) p0 = p1 = -INFINITY;
    v0[hd][c] = own0 ? s[hd][mp + 1][r] : p0;
    v1[hd][c] = own1 ? s[hd][mp + 1][r + 1] : p1;
    m[hd][c] = fmaxf(v0[hd][c], v1[hd][c]);
  }
  UNITS m[hd][c] = fmaxf(m[hd][c], shfl_xor(m[hd][c], 1));
  UNITS m[hd][c] = fmaxf(m[hd][c], shfl_xor(m[hd][c], 2));
  UNITS {
    const float nm = -m[hd][c] * kScale;
    v0[hd][c] = ex2(fmaf(v0[hd][c], kScale, nm));
    v1[hd][c] = ex2(fmaf(v1[hd][c], kScale, nm));
    m[hd][c] = v0[hd][c] + v1[hd][c];
  }
  UNITS m[hd][c] += shfl_xor(m[hd][c], 1);
  UNITS m[hd][c] += shfl_xor(m[hd][c], 2);
  UNITS {
    const float inv = rcp(m[hd][c]);
    const uint32_t p = pack2(v0[hd][c] * inv, v1[hd][c] * inv);
    pp[hd][c] = p & ~own_mask;
    po[hd][c] = p & own_mask;
    asm volatile("" : "+r"(pp[hd][c]), "+r"(po[hd][c]));
  }
#pragma unroll
  for (int n = 0; n < 24; n++) {
    const int ph = n / 8, hd = (n >> 2) & 1, c = 2 * ((n >> 1) & 1) + (ph == 1), ds = n & 1, J = 4 * hd + 2 * ds;
    float(&d)[4] = o[hd][c][ds];
    if (ph < 2) d[0] = d[1] = d[2] = d[3] = 0.f;
    if (ph == 0) mma1688(d, vt[c + 1][J], vt[c + 1][J + 1], po[hd][c]);
    if (ph == 1) mma16816(d, vt[c][J], vt[c][J + 1], vt[c + 1][J], vt[c + 1][J + 1], pp[hd][c], po[hd][c]);
    if (ph == 2) mma1688(d, vt[c][J], vt[c][J + 1], pp[hd][c]);
    if (n == 3) {
      yield_slot();
      if (tq == 0 && lane == 0) mbar_arrive(sb + kBarResume + att * 8);
    }
  }
  yield_slot();
  if (tq == 1 && lane == 0) mbar_arrive(sb + kBarResume + att * 8);
  TRACE_AT(tile, 11);
  UNITS stsm4_t(orow + c * 1024 + ((ochunk ^ (4 * hd)) << 4), pack2(o[hd][c][0][0], o[hd][c][0][1]),
                pack2(o[hd][c][0][2], o[hd][c][0][3]), pack2(o[hd][c][1][0], o[hd][c][1][1]),
                pack2(o[hd][c][1][2], o[hd][c][1][3]));
#undef UNITS
#undef LOAD_HALO
  fence_async_smem();
  __syncwarp();
  TRACE_AT(tile, 12);
  if (elect()) {
    bulk_store(g_o + (b * 16 + hp) * kTileBytes + w * 4096, stg, 4096);
    bulk_commit();
    bulk_wait();
    TRACE_AT(tile, 13);
    mbar_arrive(sb + kBarEpi + tile * 8);
  }
  __syncwarp();
}

__device__ __forceinline__ void gather_stats(uint8_t* sm, const uint2* stat, int r, float eps, unsigned epoch) {
  uint2 a[8];
  unsigned diff;
#pragma unroll 1
  do {
    diff = 0;
#pragma unroll
    for (int i = 0; i < 8; i++) {
      a[i] = ld_relaxed2(stat + i * 128 + r);
      diff |= a[i].x ^ epoch;
    }
  } while (__any_sync(0xffffffffu, diff & 7u));
  float s = 0.f, q = 0.f;
#pragma unroll
  for (int i = 0; i < 8; i++) {
    s += untag_value(a[i].x);
    q += __uint_as_float(a[i].y);
  }
  const float mean = s * (1.f / 1024.f);
  const float var = fmaxf(fmaf(-mean, mean, q * (1.f / 1024.f)), 0.f);
  reinterpret_cast<float2*>(sm + kSmStat)[r] = make_float2(rsqrtf(var + eps), -mean);
}

__device__ __forceinline__ void gather_colsums_qkv(uint8_t* sm, int tq, int j, int lane, unsigned epoch) {
  const uint2* src = reinterpret_cast<const uint2*>(g_cs + (j + 8 * tq) * 64) + lane;
  uint2 v[3], u[3];
  unsigned diff, spins = 0;
#pragma unroll 1
  do {
    if (++spins > kSpinLimit) __trap();
    diff = 0;
#pragma unroll
    for (int q = 0; q < 3; q++) {
      v[q] = ld_relaxed2(src + q * (kD / 2));
      u[q] = make_uint2(epoch & 7u, epoch & 7u);
      if (tq) u[q] = ld_relaxed2(src + (q * kD + 3 * kD + kF) / 2);
    }
#pragma unroll
    for (int q = 0; q < 3; q++) diff |= (v[q].x ^ epoch) | (v[q].y ^ epoch) | (u[q].x ^ epoch) | (u[q].y ^ epoch);
  } while (__any_sync(0xffffffffu, diff & 7u));
#pragma unroll
  for (int q = 0; q < 3; q++)
    reinterpret_cast<float2*>(sm + kSmCsQ)[tq * 96 + q * 32 + lane] =
        make_float2(untag_value(v[q].x) + untag_value(u[q].x), untag_value(v[q].y) + untag_value(u[q].y));
}

__device__ __forceinline__ void gather_colsums_w1(uint8_t* sm, const __nv_bfloat16* b1, int j, int lane,
                                                  unsigned epoch) {
#pragma unroll 1
  for (int blk = 0; blk < 7; blk++) {
    const int pair = 32 * (blk + (blk < 3 ? 3 * j : blk < 5 ? 21 + 2 * j : 35 + 2 * j)) + lane;
    const uint32_t bias = reinterpret_cast<const uint32_t*>(b1)[pair];
    uint2 v;
    unsigned spins = 0;
#pragma unroll 1
    do {
      if (++spins > kSpinLimit) __trap();
      v = ld_relaxed2(reinterpret_cast<const uint2*>(g_cs + 3 * kD) + pair);
    } while (__any_sync(0xffffffffu, ((v.x ^ epoch) | (v.y ^ epoch)) & 7u));
    reinterpret_cast<float4*>(sm + kSmV1)[blk * 32 + lane] =
        make_float4(untag_value(v.x), untag_value(v.y), kGeluBeta * bf_lo(bias), kGeluBeta * bf_hi(bias));
  }
}

#define PAUSE_QKV2 7
#define PAUSE_WO 2

__global__ void __cluster_dims__(2, 1, 1) __launch_bounds__(384, 1)
fused_layers_kernel(const __grid_constant__ CUtensorMap map_x, const __grid_constant__ CUtensorMap map_out,
                    const __grid_constant__ CUtensorMap map_qkv, const __grid_constant__ CUtensorMap map_wo,
                    const __grid_constant__ CUtensorMap map_w1a, const __grid_constant__ CUtensorMap map_w1b,
                    const __grid_constant__ CUtensorMap map_w2, const __grid_constant__ CUtensorMap map_csq,
                    const __grid_constant__ CUtensorMap map_cs1, const __grid_constant__ CUtensorMap map_css,
                    const __grid_constant__ Params prm) {
  extern __shared__ __align__(1024) uint8_t sm[];
  if (threadIdx.x < 128 && blockIdx.x < kCtas) TRACE_AT(15, 1);
  const uint32_t sb = __shfl_sync(0xffffffffu, smem_u32(sm), 0);
  const int warp = __shfl_sync(0xffffffffu, threadIdx.x >> 5, 0), lane = threadIdx.x & 31;
  const int cta = blockIdx.x, rank = cta & 1, cl = cta >> 1;
  const int grp = cl < 4 ? 0 : cl < 36 ? (cl - 4) & 7 : 1 + (cl - 36) % 7;
  const int j = cl < 4 ? 4 + cl : cl < 36 ? (cl - 4) >> 3 : 4 + (cl - 36) / 7;
  const int b = 2 * grp + rank;
  const int xcol = (b >> 3) * kD, xrow = (b & 7) * 128;

  if (cta >= kCtas) {
    helper_cta(&map_csq, &map_cs1, sm, sb, cta - kCtas, warp);
    return;
  }
  if ((warp < 8 || warp == 9) && elect()) {
    if (warp == 9) {
#pragma unroll
      for (int s = 0; s < 8; s++) mbar_init(sb + kBarFull + s * 8, 1);
      fence_async_smem();
#pragma unroll 1
      for (int s = 0; s < 4; s++) {
        const uint32_t full = sb + kBarFull + s * 8, dst = sb + kSmRing + s * 40960;
        mbar_expect_tx(full, 40960);
        tma2d(dst, &map_x, full, xcol + (s & 1) * 64, xrow);
        tma3d(dst + kTileBytes, &map_qkv, full, (j + 4 * (s & 2)) * 64, (s & 1) * 64, 0);
        tma3d(dst + kTileBytes + 12288, &map_qkv, full, (j + 4 * (s & 2)) * 64, (s & 1) * 64 + 32, 0);
      }
    } else {
      if (sb & 1023) __trap();
#pragma unroll
      for (int s = 0; s < 16; s++) mbar_init(sb + kBarTurn + warp * 128 + s * 8, warp < 5 ? 1 : warp == 5 ? 2 : 4);
    }
    asm volatile("fence.mbarrier_init.release.cluster;" ::: "memory");
  }
  __syncwarp();
  asm volatile("barrier.cluster.arrive.relaxed.aligned;" ::: "memory");

  if (warp >= 8) {
    asm volatile("setmaxnreg.dec.sync.aligned.u32 40;");
    if (warp < 10) {
      asm volatile("barrier.cluster.wait.aligned;" ::: "memory");
      uint32_t nb = 32, off = 0, kb = 0;
#define RING_STEP(WAIT, ISSUE)                                            \
  do {                                                                    \
    const uint32_t mb = nb - depth, full = sb + kBarFull + (nb & 56);     \
    if (kb == skip) kb += inc;                                            \
    mbar_wait(sb + kBarEmpty + (mb & 56), mb >> 6);                       \
    WAIT;                                                                 \
    if (elect()) { ISSUE; }                                               \
    TRACE_ISSUE(9 - warp, nb);                                            \
    kb += inc;                                                            \
    off = off == wrap ? 0 : off + step;                                   \
    nb += 8;                                                              \
  } while (nb != nend)
#pragma unroll 1
      for (int sg = 0; sg < kSegs; sg++) {
        const uint32_t e = prm.seg[sg];
        const int ty = e & 7, mode = (e >> 15) & 3, reset = (e >> 24) & 3;
        const uint32_t nend = nb + (e & 0x1f8);
        const uint32_t step = (e >> 17) & 1 ? 40960 : 32768, wrap = 163840 - step;
        const uint32_t depth = (e >> 18) & 1 ? 40 : 32;
        if (reset) off = reset == 1 ? 0 : reset == 2 ? 40960 : 131072;
        const uint32_t own = ty == 2 ? 8 + j : 2 * j;
        if (mode != kModeContinue) kb = mode == kModeHead ? own : (e >> 9) & 63;
        const uint32_t inc = mode >= kModeSkip && ty != 2 ? 2 : 1, skip = mode >= kModeSkip ? own + (kb & 1) : 255;
        if (warp == 8) {
          const CUtensorMap* map = ty < 2 ? &map_qkv : ty == 2 ? &map_wo : ty == 3 ? &map_w1a : ty < 6 ? &map_w1b : &map_w2;
          const int c0 = ty < 2 ? (j + 8 * ty) * 64 : 0;
          const int c2 = ty < 2 ? 0 : ty == 3 ? 3 * j : ty == 4 ? 24 + 2 * j : ty == 5 ? 40 + 2 * j : 2 * j;
          const uint32_t half = (ty < 2 || ty == 3) ? 12288 : 8192;
          const uint32_t bytes = 2 * half + (mode == kModeHead ? 0 : kTileBytes);
          const uint32_t dst = sb + kSmRing + kTileBytes + rank * half;
          if (e >> 26) {
            const bool second = (grp & 6) == 2;
            const int pk = grp < 4 ? 2 * j + (grp & 1) : 2 * (grp - 4 + (grp - 4 >= j));
            const CUtensorMap* pm = ty == 6 ? &map_qkv : second ? &map_w1b : &map_w1a;
            if (elect())
              asm volatile("cp.async.bulk.prefetch.tensor.3d.L2.global [%0, {%1, %2, %3}];" ::"l"(pm),
                           "r"(ty == 6 ? (j + 8 * second) * 64 : 0), "r"(pk * 64 + rank * 32),
                           "r"(ty == 6 ? 0 : second ? 24 + 2 * j : 3 * j) : "memory");
          }
          if (ty == 2 && mode == kModeHead) mbar_wait(sb + kBarEpi + ((e >> 19) & 31) * 8, 0);
#pragma unroll 1
          RING_STEP(, mbar_expect_tx(full, bytes); tma3d_mc(dst + off, map, full, c0, kb * 64 + rank * 32, c2));
        } else if (mode == kModeHead) {
          off += ((nend - nb) >> 3) * step;
          nb = nend;
          if (off >= 163840) off -= 163840;
        } else if (sg < 2) {
#pragma unroll 1
          RING_STEP(, tma2d(sb + kSmRing + off, &map_x, full, xcol + kb * 64, xrow));
        } else {
          const uint8_t* src = ty == 6 ? g_h + b * 56 * kTileBytes : (ty == 2 ? g_o : g_x) + b * 16 * kTileBytes;
          const int dep = (e >> 19) & 31;
          if (dep < 28) mbar_wait(sb + kBarReady + dep * 8, 0);
          if ((dep & 30) == 28) {
#pragma unroll 1
            RING_STEP(mbar_wait(sb + kBarSrc + ((kb << (4 - inc)) & 56), dep),
                      bulk_load(sb + kSmRing + off, src + kb * kTileBytes, kTileBytes, full));
          } else {
#pragma unroll 1
            RING_STEP(, bulk_load(sb + kSmRing + off, src + kb * kTileBytes, kTileBytes, full));
          }
        }
      }
#undef RING_STEP
    } else {
      unsigned epoch = 0;
      if (warp == 10) {
        if (lane == 0) epoch = atomicAdd(&g_ticket, 1u) / kGrid + 1;
        *reinterpret_cast<unsigned*>(sm + kSmEpoch) = __shfl_sync(0xffffffffu, epoch, 0);
        asm volatile("barrier.cluster.wait.aligned;" ::: "memory");
        if (elect()) mbar_arrive(sb + kBarEpoch);
      } else {
        asm volatile("barrier.cluster.wait.aligned;" ::: "memory");
        mbar_wait_bounded(sb + kBarFull, 0);
        if (elect()) {
          mbar_expect_tx(sb + kBarInit, 32768);
          tma2d(sb + kSmX, &map_x, sb + kBarInit, xcol + j * 128, xrow);
          tma2d(sb + kSmX + kTileBytes, &map_x, sb + kBarInit, xcol + j * 128 + 64, xrow);
        }
        const uint2 u = reinterpret_cast<const uint2*>(prm.b2)[32 * j + lane];
        reinterpret_cast<float4*>(sm + kSmB2)[lane] = make_float4(
            kHScale * bf_lo(u.x), kHScale * bf_hi(u.x), kHScale * bf_lo(u.y), kHScale * bf_hi(u.y));
      }
      mbar_wait_bounded(sb + kBarEpoch, 0);
      epoch = *reinterpret_cast<volatile unsigned*>(sm + kSmEpoch);
      if (cta < 96) {
        mbar_wait_bounded(sb + kBarInit, 0);
        colsum_strip(&map_css, sm, sb, (cta >> 5) * kD + 512 + (cta & 31) * 16, warp - 10, lane, epoch);
      }
      gather_colsums_qkv(sm, 11 - warp, j, lane, epoch);
      __syncwarp();
      if (elect()) mbar_arrive(sb + kBarCs + (11 - warp) * 8);
     if (warp == 10) {
#pragma unroll 1
      for (int i = 0; i < kTiles - 1; i++) {
        const bool xt = i == 2 || i == 6 || i == 9;
        const unsigned* line = g_flag + (i * 16 + b) * 32;
        mbar_wait(sb + (xt ? kBarX + (i >> 2) * 16 : kBarEpi + i * 8), 0);
        if (xt || i == 1 || i == 8) {
          unsigned todo = 0xff;
          do {
            const unsigned now = __ballot_sync(0xffffffffu, ld_relaxed(line + (lane & 7)) == epoch) & todo;
            if (now) {
              asm volatile("fence.acquire.gpu;\nfence.proxy.async.global;" ::: "memory");
              if ((now >> lane) & 1) mbar_arrive(sb + kBarSrc + lane * 8);
              todo ^= now;
            }
          } while (todo);
        } else {
          wait_flags(line + (lane & 7), epoch);
          if (elect()) mbar_arrive(sb + kBarReady + i * 8);
        }
        if (xt) {
          wait_flags(line + 8 + (lane & 7), epoch);
          if (elect()) mbar_arrive(sb + kBarReady + (14 + (i >> 2)) * 8);
        }
      }
     } else {
#pragma unroll 1
      for (int i = 0; i < kTiles - 1; i++) {
        if (i == 3) {
          gather_colsums_w1(sm, prm.b1, j, lane, epoch);
          __syncwarp();
          if (elect()) mbar_arrive(sb + kBarCs + 16);
        }
        const bool xt = i == 2 || i == 6 || i == 9;
#pragma unroll 1
        for (int h = 0; h < (xt ? 2 : 1); h++) {
          if (xt && h == 0) {
            mbar_wait_bounded(sb + kBarEpi + i * 8, 0);
            if (elect()) bulk_store(g_x + (b * 16 + 2 * j) * kTileBytes, sb + kSmX, kTileBytes / 2);
          }
          mbar_wait_bounded(sb + (xt ? kBarX + (i >> 2) * 16 + 8 * h : kBarEpi + i * 8), 0);
          const int ty = i >= 7 ? i - 7 : i;
          if (ty >= 2 && elect()) {
            uint8_t* dst = xt ? g_x + (b * 16 + 2 * j + h) * kTileBytes
                              : g_h + (b * 56 + 1 + (ty == 3 ? 3 * j : 16 * ty - 40 + 2 * j)) * kTileBytes;
            const int piece = (xt && h == 0) ? kTileBytes / 2 : kTileBytes / 4;
#pragma unroll 1
            for (int o = xt && h == 0 ? piece : 0; o < kTileBytes; o += piece) {
              bulk_store(dst + o, sb + (xt ? kSmX + h * kTileBytes : kSmStg) + o, piece);
              bulk_commit();
              bulk_wait();
            }
            if (!xt) mbar_arrive(sb + kBarFree + i * 8);
          }
          __syncwarp();
          if (elect()) st_release(&g_flag[(i * 16 + b) * 32 + h * 8 + j], epoch);
          __syncwarp();
        }
      }
#pragma unroll 1
      for (int h = 0; h < 2; h++) {
        mbar_wait_bounded(sb + kBarX + 48 + 8 * h, 0);
        if (elect()) {
          tma2d_store(&map_out, sb + kSmX + h * kTileBytes, xcol + j * 128 + h * 64, xrow);
          bulk_commit();
          if (h == 1) bulk_wait_read();
        }
      }
     }
    }
    __syncwarp();
    asm volatile("barrier.cluster.arrive.relaxed.aligned;\nbarrier.cluster.wait.aligned;" ::: "memory");
  } else {
    asm volatile("setmaxnreg.inc.sync.aligned.u32 232;");
    asm volatile("barrier.cluster.wait.aligned;" ::: "memory");
    const int wg = warp >> 2, w = warp & 3;
    const bool rel = (threadIdx.x & 95) == 0;
    const uint32_t rel_addr = mapa(sb + kBarEmpty, w & 1);
    if (wg == 1) TRACE_AT(15, 0);
#define EPOCH (*reinterpret_cast<volatile unsigned*>(sm + kSmEpoch))

#pragma unroll 1
    for (int i = wg; i < kTiles; i += 2) {
      const int layer = i >= 7, ty = i - 7 * layer;
      TRACE_AT(i, 15);
      float acc[2][96];
      if (ty == 2 || ty == 6) {
        const int lane = lane_id();
        const uint32_t xa = sb + kSmX + ((lane >> 4) * 8 + (lane & 7)) * 128 + (((2 * w + ((lane >> 3) & 1)) ^ (lane & 7)) << 4);
        const float up = ty == 6 ? kHScale / kXScale : layer ? 1.f / kXScale : 1.f;
        const float dn = ty == 2 ? kXScale : layer ? 1.f / kHScale : kXScale / kHScale;
#pragma unroll
        for (int h = 0; h < 2; h++) {
          const float* b2 = reinterpret_cast<const float*>(sm + kSmB2) + 64 * h + 16 * w + (lane >> 2);
          const float bias[2] = {ty == 6 ? b2[0] : 0.f, ty == 6 ? b2[8] : 0.f};
#pragma unroll
          for (int p = 0; p < 8; p++) {
            uint32_t r[4];
            ldsm4_t(xa + h * kTileBytes + p * 2048, r);
#pragma unroll
            for (int m = 0; m < 4; m++) {
              acc[h][8 * p + 2 * m] = fmaf(bf_lo(r[m]), up, bias[m & 1]);
              acc[h][8 * p + 2 * m + 1] = fmaf(bf_hi(r[m]), up, bias[m & 1]);
              asm volatile("" : "+f"(acc[h][8 * p + 2 * m]), "+f"(acc[h][8 * p + 2 * m + 1]));
            }
            yield_slot();
          }
        }
        auto stage = [&](int qt) {
          const int h = qt >> 1;
          if (qt == 1) {
            fence_async_smem();
            __syncwarp();
            if (lane == 0) mbar_arrive(sb + kBarEpi + i * 8);
          }
#pragma unroll
          for (int p = 4 * (qt & 1); p < 4 * (qt & 1) + 4; p++) {
            const float* a = &acc[h][8 * p];
            stsm4_t(xa + h * kTileBytes + p * 2048, pack2(a[0] * dn, a[1] * dn), pack2(a[2] * dn, a[3] * dn),
                    pack2(a[4] * dn, a[5] * dn), pack2(a[6] * dn, a[7] * dn));
            yield_slot();
          }
          if (qt & 1) {
            fence_async_smem();
            __syncwarp();
            if (elect()) mbar_arrive(sb + kBarX + (i >> 2) * 16 + 8 * h);
            TRACE_AT(i, 8 + h);
          }
        };
        mainloop<128, kResid>(acc, sb, i, layer * 152 + ty * 16, ty == 6 ? 4 : 0, ty == 6 ? 56 : 16,
                            ty == 2 ? PAUSE_WO : -1, 2 * layer + 1, rel_addr, rel, ty == 2 ? 8 : -1, stage);
        TRACE_AT(i, 2);
        stage(2);
        stage(3);
      } else {
        const int xver = 2 * layer + (ty >= 3);
        const uint32_t stg = sb + kSmStg + w * 4096;
        const float4* vec = reinterpret_cast<const float4*>(sm + kSmV1) + (ty == 3 ? 0 : 64 * ty - 160);
        int lane;
        uint8_t* hdst = g_h + (b * 56 + (ty == 3 ? 3 * j : 16 * ty - 40 + 2 * j)) * kTileBytes + w * 4096;
        float2 st[4];
        unsigned epoch;
        auto pre = [&] {
          lane = lane_id();
          if (ty < 4) mbar_wait(sb + (ty == 1 ? kBarEpi + (i - 1) * 8 : kBarStat + xver * 8), 0);
#pragma unroll
          for (int c = 0; c < 4; c++) st[c] = reinterpret_cast<const float2*>(sm + kSmStat)[32 * w + 8 * c + (lane >> 2)];
          epoch = EPOCH;
        };
        auto team_stats = [&] {
          uint2* stat = g_stat + (xver * 16 + b) * 1024;
          lane = lane_id();
          publish_stats(sb, stat + j * 128, w, lane, EPOCH);
          gather_stats(sm, stat, 32 * w + lane, xver ? 1e-5f * kXScale * kXScale : 1e-5f, EPOCH);
          __syncwarp();
          if (elect()) mbar_arrive(sb + kBarStat + xver * 8);
          TRACE_AT(i, 14);
        };
        if (ty < 4) {
          AttnRegs ar;
          auto odd = [&](int step) {
            if (step == 0) pre();
            else convert_odd(acc, st, ar, step, sm, sb + kBarHalo + (xver + ty) * 24,
                             g_halo + ((layer * 16 + b) * 16 + j + 8 * ty) * 256, (b & 7) != 7, epoch, w, lane);
          };
          head_blocks<192>(acc, sb, layer * 152 + (ty < 2 ? 2 * ty : 48), ty < 2 ? 2 * ty : 1, xver, rel_addr, rel);
          if (ty == 1) {
            if (i == 1) {
              mbar_wait(sb + kBarEpoch, 0);
              mbar_wait(sb + kBarInit, 0);
            }
            team_stats();
            epoch = 0;
#pragma unroll
            for (int c = 0; c < 4; c++) st[c] = reinterpret_cast<const float2*>(sm + kSmStat)[32 * w + 8 * c + (lane >> 2)];
          } else {
            mainloop<192, kPlain>(acc, sb, i, layer * 152 + (ty ? 52 : 4), ty ? 1 : 0, 14, -1, 0, rel_addr, rel, 0, pre);
            TRACE_AT(i, 2);
            if (ty == 3) goto wide_gelu;
          }
          if (layer == 0) mbar_wait(sb + kBarCs + ty * 8, 0);
          add_mean_term(acc, st, sm, ty, lane);
          if (ty == 1) {
            mainloop<192, kStagger>(acc, sb, i, layer * 152 + 18, 2, 14, PAUSE_QKV2, xver, rel_addr, rel, 0, odd);
            TRACE_AT(i, 2);
          } else {
            odd(1);
            odd(2);
            odd(3);
          }
          epilogue_attn(acc, st, ar, sm, sb, layer, ty, b, j, epoch, i, w, lane);
          TRACE_AT(i, 3);
          continue;
        wide_gelu:
          if (i == 3) mbar_wait(sb + kBarCs + 16, 0);
          scale_stats(st);
          fold_norm<16, 24>(acc, st, vec + (lane & 3));
          TRACE_AT(i, 11);
          gelu_chunk<2>(acc, stg, lane, nullptr, [] {});
          TRACE_AT(i, 12);
          fold_norm<0, 2>(acc, st, vec + (lane & 3));
          store_staged(hdst + 2 * kTileBytes, stg);
          fold_norm<2, 16>(acc, st, vec + (lane & 3));
        } else {
          if (ty == 4) {
            head_blocks<128>(acc, sb, layer * 152 + 50, 3, xver, rel_addr, rel);
            team_stats();
          } else {
            const uint32_t s0 = ((((sb & 0x3FFFF) + kSmRing) >> 4) | (1u << 16)) + 3 * 2048;
            mbar_wait(sb + kBarTurn + (i - 1) * 8, 0);
            mbar_wait(sb + kBarFull, layer * 19 + 10);
            TRACE_KB((layer * 152 + 80) * 8);
            mma_kblock<128, 2>(acc, s0, s0 + kToB);
          }
          mainloop<128, kPlain>(acc, sb, i, layer * 152 + 6 + 15 * ty, 4, ty + 10, -1, 0, rel_addr, rel, 0, pre,
                                ty == 5 ? 0 : 64);
          TRACE_AT(i, 2);
          if (i == 4) mbar_wait(sb + kBarCs + 16, 0);
          scale_stats(st);
          fold_norm<0, 16>(acc, st, vec + (lane & 3));
        }
        auto own_store_done = [] {
          if (elect()) bulk_wait();
          __syncwarp();
        };
        TRACE_AT(i, 8);
        gelu_chunk<0>(acc, stg, lane, nullptr, [&] {
          if (ty == 3) own_store_done();
          else mbar_wait(sb + kBarFree + (i - 1) * 8, 0);
        });
        TRACE_AT(i, 9);
        gelu_chunk<1>(acc, stg, lane, hdst, own_store_done);
        TRACE_AT(i, 10);
        fence_async_smem();
        __syncwarp();
        if (elect()) mbar_arrive(sb + kBarEpi + i * 8);
      }
      TRACE_AT(i, 3);
    }
#undef EPOCH
    asm volatile("barrier.cluster.arrive.relaxed.aligned;\nbarrier.cluster.wait.aligned;" ::: "memory");
    if (wg == 1) TRACE_AT(15, 2);
  }
}

void build_segments(uint32_t* seg) {
  int n = 0, fine = 0;
  auto per_source = [&] { return 28 + (fine++ & 1); };
  auto add = [&](int ty, int cnt, int kb0, int mode, int wide, int depth5, int dep, int reset) {
    seg[n++] = ty | cnt << 3 | kb0 << 9 | mode << 15 | wide << 17 | depth5 << 18 | dep << 19 | reset << 24;
  };
  for (int l = 0; l < 2; l++) {
    const int t = 7 * l;
    if (l == 0) {
      add(0, 14, 2, kModePlain, 1, 0, 31, 1);
      add(1, 14, 2, kModePlain, 1, 0, 31, 0);
    } else {
      add(0, 2, 0, kModeHead, 1, 0, 31, 1);
      add(1, 2, 0, kModeHead, 1, 0, 31, 0);
      add(0, 7, 0, kModeSkip, 1, 0, per_source(), 0);
      add(0, 7, 1, kModeSkip, 1, 0, 15, 0);
      add(1, 7, 0, kModeSkip, 1, 0, 31, 0);
      add(1, 7, 1, kModeSkip, 1, 0, 31, 0);
    }
    add(2, 4, 0, kModePlain, 0, 0, t, 1);
    add(2, 4, 4, kModePlain, 0, 1, 31, 4);
    add(2, 1, 0, kModeHead, 0, 1, t + 1, 0);
    add(2, 7, 8, kModeSkip, 0, 1, per_source(), 0);
    add(3, 2, 0, kModeHead, 1, 0, 31, 2);
    add(4, 2, 0, kModeHead, 1, 0, 31, 0);
    add(3, 7, 0, kModeSkip, 1, 0, per_source(), 0);
    add(3, 7, 1, kModeSkip, 1, 0, 14 + 2 * l, 0);
    add(4, 4, 0, kModeSkip, 0, 0, 31, 3);
    add(4, 3, 0, kModeContinue, 0, 1, 31, 0);
    add(4, 7, 1, kModeSkip, 0, 1, 31, 0);
    add(5, 16, 0, kModePlain, 0, 1, 31, 0);
    add(6, 24, 0, kModePlain, 0, 1, t + 3, 0);
    add(6, 16, 24, kModePlain, 0, 1, t + 4, 0);
    add(6, 16, 40, kModePlain, 0, 1, t + 5, l ? 0 : 4);
  }
}

typedef CUresult (*EncodeTiledFn)(CUtensorMap*, CUtensorMapDataType, cuuint32_t, void*, const cuuint64_t*,
                                  const cuuint64_t*, const cuuint32_t*, const cuuint32_t*, CUtensorMapInterleave,
                                  CUtensorMapSwizzle, CUtensorMapL2promotion, CUtensorMapFloatOOBfill);

CUtensorMap make_map(EncodeTiledFn enc, const void* p, int rank, const cuuint64_t* dims, const cuuint64_t* strides,
                     const cuuint32_t* box, CUtensorMapSwizzle swizzle = CU_TENSOR_MAP_SWIZZLE_128B,
                     CUtensorMapL2promotion promo = CU_TENSOR_MAP_L2_PROMOTION_L2_128B) {
  CUtensorMap m;
  const cuuint32_t es[5] = {1, 1, 1, 1, 1};
  enc(&m, CU_TENSOR_MAP_DATA_TYPE_BFLOAT16, rank, const_cast<void*>(p), dims, strides, box, es,
      CU_TENSOR_MAP_INTERLEAVE_NONE, swizzle, promo,
      CU_TENSOR_MAP_FLOAT_OOB_FILL_NONE);
  return m;
}

CUtensorMap weight_map(EncodeTiledFn enc, const void* p, int k, int n, int blocks) {
  const cuuint64_t dims[3] = {64, (cuuint64_t)k, (cuuint64_t)n / 64};
  const cuuint64_t strides[2] = {(cuuint64_t)n * 2, 128};
  const cuuint32_t box[3] = {64, 32, (cuuint32_t)blocks};
  return make_map(enc, p, 3, dims, strides, box, CU_TENSOR_MAP_SWIZZLE_128B, CU_TENSOR_MAP_L2_PROMOTION_L2_256B);
}

CUtensorMap slab_map(EncodeTiledFn enc, const void* p, int n, int cols, int rows) {
  const cuuint64_t dims[2] = {(cuuint64_t)n, kD};
  const cuuint64_t strides[1] = {(cuuint64_t)n * 2};
  const cuuint32_t box[2] = {(cuuint32_t)cols, (cuuint32_t)rows};
  return make_map(enc, p, 2, dims, strides, box, CU_TENSOR_MAP_SWIZZLE_NONE);
}

CUtensorMap token_map(EncodeTiledFn enc, const void* p, int rows) {
  const cuuint64_t dims[2] = {2 * kD, 1024};
  const cuuint64_t strides[1] = {4 * kD};
  const cuuint32_t box[2] = {64, (cuuint32_t)rows};
  return make_map(enc, p, 2, dims, strides, box);
}

}

extern "C" void kernel_launch(void* const* d_in, const int* in_sizes, int n_in, void* d_out, int out_size) {
  (void)in_sizes; (void)n_in; (void)out_size;
  static EncodeTiledFn enc = nullptr;
  if (!enc) {
    void* fn = nullptr;
    cudaDriverEntryPointQueryResult q;
    cudaGetDriverEntryPoint("cuTensorMapEncodeTiled", &fn, cudaEnableDefault, &q);
    enc = (EncodeTiledFn)fn;
    cudaFuncSetAttribute(fused_layers_kernel, cudaFuncAttributeMaxDynamicSharedMemorySize, kSmBytes);
  }
  Params prm;
  prm.b1 = (const __nv_bfloat16*)d_in[5];
  prm.b2 = (const __nv_bfloat16*)d_in[7];
  build_segments(prm.seg);
  const cuuint64_t qd[3] = {kD, kD, 3}, qs[2] = {3 * kD * 2, kD * 2};
  const cuuint32_t qb[3] = {64, 32, 3};
  const CUtensorMap map_x = token_map(enc, d_in[0], 128);
  const CUtensorMap map_out = token_map(enc, d_out, 128);
  const CUtensorMap map_qkv = make_map(enc, d_in[1], 3, qd, qs, qb);
  const CUtensorMap map_wo = weight_map(enc, d_in[2], kD, kD, 2);
  const CUtensorMap map_w1a = weight_map(enc, d_in[4], kD, kF, 3);
  const CUtensorMap map_w1b = weight_map(enc, d_in[4], kD, kF, 2);
  const CUtensorMap map_w2 = weight_map(enc, d_in[6], kF, kD, 2);
  fused_layers_kernel<<<kGrid, 384, kSmBytes>>>(map_x, map_out, map_qkv, map_wo, map_w1a, map_w1b, map_w2,
                                                slab_map(enc, d_in[1], 3 * kD, 128, 128), slab_map(enc, d_in[4], kF, 128, 128),
                                                slab_map(enc, d_in[1], 3 * kD, 16, 128), prm);
}
```

```cpp
#include <cuda.h>
#include <cuda_bf16.h>
#include <cuda_runtime.h>
#include <stdint.h>

namespace {

constexpr int kD = 1024;
constexpr int kF = 3584;
constexpr int kCtas = 128;
constexpr int kGrid = 132;
constexpr int kTiles = 14;
constexpr int kTileBytes = 16384;

constexpr int kSmRing = 0;
constexpr int kSmX = 163840;
constexpr int kSmStg = kSmX + 32768;
constexpr int kSmHalo = kSmStg + 16384;
constexpr int kSmCsQ = kSmHalo + 6144;
constexpr int kSmV1 = kSmCsQ + 384 * 4;
constexpr int kSmB2 = kSmV1 + 448 * 8;
constexpr int kSmStat = kSmB2 + 128 * 4;
constexpr int kSmBar = kSmStat + 128 * 8;
constexpr int kBarFull = kSmBar;
constexpr int kBarTurn = kBarFull + 8 * 8;
constexpr int kBarReady = kBarTurn + 14 * 8;
constexpr int kBarSrc = kBarReady + 17 * 8;
constexpr int kBarPause = kBarSrc + 8 * 8;
constexpr int kBarFree = kBarPause + 4 * 8;
constexpr int kBarCs = kBarFree + 14 * 8;
constexpr int kBarSlab = kBarCs + 3 * 8;
constexpr int kBarHalo = kBarSlab + 4 * 8;
constexpr int kBarInit = kBarHalo + 12 * 8;
constexpr int kBarEpoch = kBarInit + 8;
constexpr int kBarEmpty = kBarTurn + 5 * 128;
constexpr int kBarEpi = kBarEmpty + 128;
constexpr int kBarX = kBarEpi + 14 * 8;
constexpr int kBarStat = kBarX + 8 * 8;
constexpr int kBarResume = kBarStat + 4 * 8;
constexpr int kSmEpoch = kBarEpi + 2 * 128;
static_assert(kBarEpoch < kBarEmpty && kBarResume + 4 * 8 <= kSmEpoch, "barrier groups overflow");
constexpr int kSmBytes = kSmEpoch + 16 + 256;
constexpr int kSegs = 38;

constexpr int kFlagLines = kTiles * 16;

constexpr float kXScale = 1.f / 8.f;

constexpr unsigned kSpinLimit = 1u << 22;

__device__ __align__(1024) uint8_t g_x[16 * 16 * kTileBytes];
__device__ __align__(1024) uint8_t g_o[16 * 16 * kTileBytes];
__device__ __align__(1024) uint8_t g_h[16 * 56 * kTileBytes];
__device__ __align__(128) uint2 g_stat[4 * 16 * 128 * 8];
__device__ __align__(128) unsigned g_cs[3 * kD + kF + 3 * kD];
__device__ __align__(128) uint4 g_halo[2 * 16 * 16 * 256];
__device__ __align__(128) unsigned g_flag[kFlagLines * 32];
__device__ unsigned g_ticket;

#define TRACE_AT(tile, k)
#define TRACE_PUB(i, k, c)
#define TRACE_ISSUE(which, nb)

struct Params {
  const __nv_bfloat16* b1;
  const __nv_bfloat16* b2;
  uint32_t seg[kSegs];
};

__device__ __forceinline__ uint32_t smem_u32(const void* p) {
  return (uint32_t)__cvta_generic_to_shared(p);
}
__device__ __forceinline__ uint32_t mapa(uint32_t a, uint32_t cta) {
  uint32_t r;
  asm("mapa.shared::cluster.u32 %0, %1, %2;" : "=r"(r) : "r"(a), "r"(cta));
  return r;
}
__device__ __forceinline__ void mbar_init(uint32_t bar, int cnt) {
  asm volatile("mbarrier.init.shared::cta.b64 [%0], %1;" ::"r"(bar), "r"(cnt) : "memory");
}
__device__ __forceinline__ void mbar_expect_tx(uint32_t bar, uint32_t bytes) {
  asm volatile("mbarrier.arrive.expect_tx.shared::cta.b64 _, [%0], %1;" ::"r"(bar), "r"(bytes) : "memory");
}
__device__ __forceinline__ void mbar_arrive(uint32_t bar) {
  asm volatile("mbarrier.arrive.shared::cta.b64 _, [%0];" ::"r"(bar) : "memory");
}
__device__ __forceinline__ void mbar_arrive_cluster(uint32_t cluster_addr) {
  asm volatile("mbarrier.arrive.shared::cluster.b64 _, [%0];" ::"r"(cluster_addr) : "memory");
}
__device__ __forceinline__ void mbar_wait(uint32_t bar, uint32_t parity) {
  asm volatile("{\n.reg .pred p;\nRETRY:\nmbarrier.try_wait.parity.shared::cta.b64 p, [%0], %1;\n"
               "@!p bra.uni RETRY;\n}" ::"r"(bar), "r"(parity) : "memory");
}
__device__ __forceinline__ void mbar_wait_bounded(uint32_t bar, uint32_t parity) {
  asm volatile("{\n.reg .pred p;\n.reg .u32 c;\nmov.u32 c, 0;\nRETRY:\n"
               "mbarrier.try_wait.parity.shared::cta.b64 p, [%0], %1;\n@p bra.uni DONE;\n"
               "add.u32 c, c, 1;\nsetp.lt.u32 p, c, %2;\n@p bra.uni RETRY;\ntrap;\nDONE:\n}"
               ::"r"(bar), "r"(parity), "n"(1u << 19) : "memory");
}
__device__ __forceinline__ void tma3d(uint32_t dst, const CUtensorMap* m, uint32_t bar, int c0, int c1, int c2) {
  asm volatile(
      "cp.async.bulk.tensor.3d.shared::cluster.global.mbarrier::complete_tx::bytes [%0], [%1, {%3, %4, %5}], [%2];"
      ::"r"(dst), "l"(m), "r"(bar), "r"(c0), "r"(c1), "r"(c2) : "memory");
}
__device__ __forceinline__ void tma3d_mc(uint32_t dst, const CUtensorMap* m, uint32_t bar, int c0, int c1, int c2) {
  asm volatile(
      "cp.async.bulk.tensor.3d.shared::cluster.global.mbarrier::complete_tx::bytes.multicast::cluster"
      " [%0], [%1, {%3, %4, %5}], [%2], %6;"
      ::"r"(dst), "l"(m), "r"(bar), "r"(c0), "r"(c1), "r"(c2), "h"((uint16_t)3) : "memory");
}
__device__ __forceinline__ void tma2d(uint32_t dst, const CUtensorMap* m, uint32_t bar, int c0, int c1) {
  asm volatile(
      "cp.async.bulk.tensor.2d.shared::cluster.global.mbarrier::complete_tx::bytes [%0], [%1, {%3, %4}], [%2];"
      ::"r"(dst), "l"(m), "r"(bar), "r"(c0), "r"(c1) : "memory");
}
__device__ __forceinline__ void tma2d_store(const CUtensorMap* m, uint32_t src, int c0, int c1) {
  asm volatile("cp.async.bulk.tensor.2d.global.shared::cta.bulk_group [%0, {%2, %3}], [%1];"
               ::"l"(m), "r"(src), "r"(c0), "r"(c1) : "memory");
}
__device__ __forceinline__ int lane_id() {
  int l;
  asm volatile("mov.u32 %0, %%laneid;" : "=r"(l));
  return l;
}
__device__ __forceinline__ bool elect() {
  uint32_t p;
  asm volatile("{\n.reg .pred p;\nelect.sync _|p, 0xffffffff;\nselp.b32 %0, 1, 0, p;\n}" : "=r"(p));
  return p;
}
__device__ __forceinline__ void bulk_load(uint32_t dst, const void* src, uint32_t bytes, uint32_t bar) {
  asm volatile("cp.async.bulk.shared::cluster.global.mbarrier::complete_tx::bytes [%0], [%1], %2, [%3];"
               ::"r"(dst), "l"(src), "r"(bytes), "r"(bar) : "memory");
}
__device__ __forceinline__ void bulk_store(void* dst, uint32_t src, uint32_t bytes) {
  asm volatile("cp.async.bulk.global.shared::cta.bulk_group [%0], [%1], %2;" ::"l"(dst), "r"(src), "r"(bytes)
               : "memory");
}
__device__ __forceinline__ void bulk_commit() { asm volatile("cp.async.bulk.commit_group;" ::: "memory"); }
__device__ __forceinline__ void bulk_wait_read() { asm volatile("cp.async.bulk.wait_group.read 0;" ::: "memory"); }
__device__ __forceinline__ void bulk_wait() { asm volatile("cp.async.bulk.wait_group 0;" ::: "memory"); }
__device__ __forceinline__ void fence_async_smem() { asm volatile("fence.proxy.async.shared::cta;" ::: "memory"); }
__device__ __forceinline__ unsigned ld_relaxed(const unsigned* p) {
  unsigned v;
  asm volatile("ld.relaxed.gpu.global.u32 %0, [%1];" : "=r"(v) : "l"(p) : "memory");
  return v;
}
__device__ __forceinline__ uint2 ld_relaxed64(const uint2* p) {
  uint2 v;
  asm volatile("{\n.reg .b64 t;\nld.relaxed.gpu.global.b64 t, [%2];\nmov.b64 {%0, %1}, t;\n}"
               : "=r"(v.x), "=r"(v.y) : "l"(p) : "memory");
  return v;
}
__device__ __forceinline__ void st_relaxed(unsigned* p, unsigned v) {
  asm volatile("st.relaxed.gpu.global.u32 [%0], %1;" ::"l"(p), "r"(v) : "memory");
}
__device__ __forceinline__ void st_release(unsigned* p, unsigned v) {
  asm volatile("st.release.gpu.global.u32 [%0], %1;" ::"l"(p), "r"(v) : "memory");
}
__device__ __forceinline__ void wait_flags(const unsigned* p, unsigned epoch) {
  while (__any_sync(0xffffffffu, ld_relaxed(p) != epoch)) {
  }
  asm volatile("fence.acquire.gpu;\nfence.proxy.async.global;" ::: "memory");
  __syncwarp();
}
__device__ __forceinline__ void st_packet(uint4* p, uint32_t d0, uint32_t d1, uint32_t tag) {
  asm volatile("{\n.reg .b128 v;\n.reg .b64 x, y;\nmov.b64 x, {%1, %2};\nmov.b64 y, {%3, %3};\nmov.b128 v, {x, y};\n"
               "st.relaxed.gpu.global.b128 [%0], v;\n}" ::"l"(p), "r"(d0), "r"(d1), "r"(tag) : "memory");
}
__device__ __forceinline__ void ld_packet(const uint4* p, uint32_t& d0, uint32_t& d1, uint32_t& tag) {
  asm volatile("{\n.reg .b128 v;\n.reg .b64 x, y;\n.reg .b32 u;\nld.relaxed.gpu.global.b128 v, [%3];\n"
               "mov.b128 {x, y}, v;\nmov.b64 {%0, %1}, x;\nmov.b64 {%2, u}, y;\n}"
               : "=r"(d0), "=r"(d1), "=r"(tag) : "l"(p) : "memory");
}
__device__ __forceinline__ uint2 ld_relaxed_pair(const uint2* p) {
  uint2 v;
  asm volatile("ld.relaxed.gpu.global.v2.u32 {%0, %1}, [%2];" : "=r"(v.x), "=r"(v.y) : "l"(p) : "memory");
  return v;
}
__device__ __forceinline__ unsigned tag_value(float v, unsigned epoch) {
  return (__float_as_uint(v) & ~7u) | (epoch & 7u);
}
__device__ __forceinline__ float untag_value(unsigned v) { return __uint_as_float(v & ~7u); }
__device__ __forceinline__ void stsm4(uint32_t a, uint32_t r0, uint32_t r1, uint32_t r2, uint32_t r3) {
  asm volatile("stmatrix.sync.aligned.m8n8.x4.shared.b16 [%0], {%1, %2, %3, %4};" ::"r"(a), "r"(r0), "r"(r1),
               "r"(r2), "r"(r3) : "memory");
}
__device__ __forceinline__ void stsm4_t(uint32_t a, uint32_t r0, uint32_t r1, uint32_t r2, uint32_t r3) {
  asm volatile("stmatrix.sync.aligned.m8n8.x4.trans.shared.b16 [%0], {%1, %2, %3, %4};" ::"r"(a), "r"(r0),
               "r"(r1), "r"(r2), "r"(r3) : "memory");
}
__device__ __forceinline__ uint32_t transpose8(uint32_t a) {
  uint32_t d;
  asm volatile("movmatrix.sync.aligned.m8n8.trans.b16 %0, %1;" : "=r"(d) : "r"(a));
  return d;
}
__device__ __forceinline__ void mma16816(float (&c)[4], uint32_t a0, uint32_t a1, uint32_t a2, uint32_t a3,
                                         uint32_t b0, uint32_t b1) {
  asm volatile("mma.sync.aligned.m16n8k16.row.col.f32.bf16.bf16.f32 {%0, %1, %2, %3}, {%4, %5, %6, %7}, {%8, %9}, "
               "{%0, %1, %2, %3};"
               : "+f"(c[0]), "+f"(c[1]), "+f"(c[2]), "+f"(c[3])
               : "r"(a0), "r"(a1), "r"(a2), "r"(a3), "r"(b0), "r"(b1));
}
__device__ __forceinline__ void mma1688(float (&c)[4], uint32_t a0, uint32_t a1, uint32_t b0) {
  asm volatile("mma.sync.aligned.m16n8k8.row.col.f32.bf16.bf16.f32 {%0, %1, %2, %3}, {%4, %5}, {%6}, {%0, %1, %2, %3};"
               : "+f"(c[0]), "+f"(c[1]), "+f"(c[2]), "+f"(c[3]) : "r"(a0), "r"(a1), "r"(b0));
}
__device__ __forceinline__ float shfl_xor(float v, int m) {
  float r;
  asm volatile("shfl.sync.bfly.b32 %0, %1, %2, 31, 0xffffffff;" : "=f"(r) : "f"(v), "r"(m));
  return r;
}
__device__ __forceinline__ float tanh_fast(float x) {
  float r;
  asm volatile("tanh.approx.f32 %0, %1;" : "=f"(r) : "f"(x));
  return r;
}
__device__ __forceinline__ void ldsm4(uint32_t a, uint32_t (&r)[4]) {
  asm volatile("ldmatrix.sync.aligned.m8n8.x4.shared.b16 {%0, %1, %2, %3}, [%4];"
               : "=r"(r[0]), "=r"(r[1]), "=r"(r[2]), "=r"(r[3]) : "r"(a) : "memory");
}
__device__ __forceinline__ void ldsm4_t(uint32_t a, uint32_t (&r)[4]) {
  asm volatile("ldmatrix.sync.aligned.m8n8.x4.trans.shared.b16 {%0, %1, %2, %3}, [%4];"
               : "=r"(r[0]), "=r"(r[1]), "=r"(r[2]), "=r"(r[3]) : "r"(a) : "memory");
}
__device__ __forceinline__ uint32_t pack2(float lo, float hi) {
  uint32_t r;
  asm volatile("cvt.rn.bf16x2.f32 %0, %1, %2;" : "=r"(r) : "f"(hi), "f"(lo));
  return r;
}
__device__ __forceinline__ float bf_lo(uint32_t r) { return __uint_as_float(r << 16); }
__device__ __forceinline__ float bf_hi(uint32_t r) { return __uint_as_float(r & 0xffff0000u); }
__device__ __forceinline__ float ex2(float x) {
  float r;
  asm("ex2.approx.ftz.f32 %0, %1;" : "=f"(r) : "f"(x));
  return r;
}
__device__ __forceinline__ float rcp(float x) {
  float r;
  asm("rcp.approx.ftz.f32 %0, %1;" : "=f"(r) : "f"(x));
  return r;
}
template <int N>
__device__ __forceinline__ void wg_wait() {
  asm volatile("wgmma.wait_group.sync.aligned %0;" ::"n"(N) : "memory");
}
__device__ __forceinline__ void yield_slot() { asm volatile("pmevent 0;"); }

template <int N, int KIND>
__device__ __forceinline__ void mma_kblock(float (&acc)[2][96], uint32_t a, uint32_t b);

#define F8(m, d, i) m(d[i]), m(d[i + 1]), m(d[i + 2]), m(d[i + 3]), m(d[i + 4]), m(d[i + 5]), m(d[i + 6]), m(d[i + 7])
#define KSTEP(N, A, B, oa0, oa1, ob, sd)                                                   \
  "mov.b64 db, {" B ", hb};\nadd.u64 db, db, " #ob ";\n"                                    \
  "mov.b64 da, {" A ", ha};\nadd.u64 da, da, " #oa0 ";\n"                                   \
  "wgmma.mma_async.sync.aligned.m64n" #N "k16.f32.bf16.bf16 {" ACC##N##_0 "}, da, db, " #sd ", 1, 1, 0, 1;\n" \
  "mov.b64 da, {" A ", ha};\nadd.u64 da, da, " #oa1 ";\n"                                   \
  "wgmma.mma_async.sync.aligned.m64n" #N "k16.f32.bf16.bf16 {" ACC##N##_1 "}, da, db, " #sd ", 1, 1, 0, 1;\n"

#define MMA_KBLOCK(N, KIND, A, B, ob2, ob3, sd, MID, MODE)                                 \
  template <>                                                                              \
  __device__ __forceinline__ void mma_kblock<N, KIND>(float (&acc)[2][96], uint32_t a, uint32_t b) { \
    asm volatile("{\n.reg .b32 ha, hb;\n.reg .b64 da, db;\n"                            \
                 "mov.b32 ha, 0x40000080;\nmov.b32 hb, 0x40000040;\n"                       \
                 "wgmma.fence.sync.aligned;\n"                                             \
                 KSTEP(N, A, B, 0, 64, 0, sd) KSTEP(N, A, B, 2, 66, 128, 1) MID               \
                 KSTEP(N, A, B, 4, 68, ob2, 1) KSTEP(N, A, B, 6, 70, ob3, 1) "wgmma.commit_group.sync.aligned;\n}\n"  \
                 : OPS##N(MODE) : "r"(a), "r"(b) : "memory");                              \
  }
#define MMA_KBLOCKS(N, A, B, ob2, ob3)                                                     \
  MMA_KBLOCK(N, 0, A, B, ob2, ob3, 1, "", "+f")                                            \
  MMA_KBLOCK(N, 1, A, B, ob2, ob3, 1, "wgmma.commit_group.sync.aligned;\n", "+f")          \
  MMA_KBLOCK(N, 2, A, B, ob2, ob3, 0, "", "=f")

#define ACC128_0 \
  "%0, %1, %2, %3, %4, %5, %6, %7, %8, %9, %10, %11, %12, %13, %14, %15, " \
  "%16, %17, %18, %19, %20, %21, %22, %23, %24, %25, %26, %27, %28, %29, %30, %31, " \
  "%32, %33, %34, %35, %36, %37, %38, %39, %40, %41, %42, %43, %44, %45, %46, %47, " \
  "%48, %49, %50, %51, %52, %53, %54, %55, %56, %57, %58, %59, %60, %61, %62, %63"
#define ACC128_1 \
  "%64, %65, %66, %67, %68, %69, %70, %71, %72, %73, %74, %75, %76, %77, %78, %79, " \
  "%80, %81, %82, %83, %84, %85, %86, %87, %88, %89, %90, %91, %92, %93, %94, %95, " \
  "%96, %97, %98, %99, %100, %101, %102, %103, %104, %105, %106, %107, %108, %109, %110, %111, " \
  "%112, %113, %114, %115, %116, %117, %118, %119, %120, %121, %122, %123, %124, %125, %126, %127"
#define OPS128(m) \
  F8(m, acc[0], 0), F8(m, acc[0], 8), F8(m, acc[0], 16), F8(m, acc[0], 24), F8(m, acc[0], 32), F8(m, acc[0], 40), F8(m, acc[0], 48), F8(m, acc[0], 56), \
        F8(m, acc[1], 0), F8(m, acc[1], 8), F8(m, acc[1], 16), F8(m, acc[1], 24), F8(m, acc[1], 32), F8(m, acc[1], 40), F8(m, acc[1], 48), F8(m, acc[1], 56)
MMA_KBLOCKS(128, "%128", "%129", 512, 640)

#define ACC192_0 \
  "%0, %1, %2, %3, %4, %5, %6, %7, %8, %9, %10, %11, %12, %13, %14, %15, " \
  "%16, %17, %18, %19, %20, %21, %22, %23, %24, %25, %26, %27, %28, %29, %30, %31, " \
  "%32, %33, %34, %35, %36, %37, %38, %39, %40, %41, %42, %43, %44, %45, %46, %47, " \
  "%48, %49, %50, %51, %52, %53, %54, %55, %56, %57, %58, %59, %60, %61, %62, %63, " \
  "%64, %65, %66, %67, %68, %69, %70, %71, %72, %73, %74, %75, %76, %77, %78, %79, " \
  "%80, %81, %82, %83, %84, %85, %86, %87, %88, %89, %90, %91, %92, %93, %94, %95"
#define ACC192_1 \
  "%96, %97, %98, %99, %100, %101, %102, %103, %104, %105, %106, %107, %108, %109, %110, %111, " \
  "%112, %113, %114, %115, %116, %117, %118, %119, %120, %121, %122, %123, %124, %125, %126, %127, " \
  "%128, %129, %130, %131, %132, %133, %134, %135, %136, %137, %138, %139, %140, %141, %142, %143, " \
  "%144, %145, %146, %147, %148, %149, %150, %151, %152, %153, %154, %155, %156, %157, %158, %159, " \
  "%160, %161, %162, %163, %164, %165, %166, %167, %168, %169, %170, %171, %172, %173, %174, %175, " \
  "%176, %177, %178, %179, %180, %181, %182, %183, %184, %185, %186, %187, %188, %189, %190, %191"
#define OPS192(m) \
  F8(m, acc[0], 0), F8(m, acc[0], 8), F8(m, acc[0], 16), F8(m, acc[0], 24), F8(m, acc[0], 32), F8(m, acc[0], 40), F8(m, acc[0], 48), F8(m, acc[0], 56), F8(m, acc[0], 64), F8(m, acc[0], 72), F8(m, acc[0], 80), F8(m, acc[0], 88), \
        F8(m, acc[1], 0), F8(m, acc[1], 8), F8(m, acc[1], 16), F8(m, acc[1], 24), F8(m, acc[1], 32), F8(m, acc[1], 40), F8(m, acc[1], 48), F8(m, acc[1], 56), F8(m, acc[1], 64), F8(m, acc[1], 72), F8(m, acc[1], 80), F8(m, acc[1], 88)
MMA_KBLOCKS(192, "%192", "%193", 768, 896)

#define HSTEP(oa, ob)                                                                       \
  "mov.b64 db, {%97, hb};\nadd.u64 db, db, " #ob ";\nmov.b64 da, {%96, ha};\nadd.u64 da, da, " #oa ";\n" \
  "wgmma.mma_async.sync.aligned.m64n192k16.f32.bf16.bf16 {" ACC192_0 "}, da, db, 1, 1, 1, 0, 1;\n"
__device__ __forceinline__ void mma_half(float (&d)[96], uint32_t a, uint32_t b) {
  asm volatile("{\n.reg .b32 ha, hb;\n.reg .b64 da, db;\nmov.b32 ha, 0x40000080;\nmov.b32 hb, 0x40000040;\n"
               "wgmma.fence.sync.aligned;\n" HSTEP(0, 0) HSTEP(2, 128) HSTEP(4, 768) HSTEP(6, 896)
               "wgmma.commit_group.sync.aligned;\n}\n"
               : F8("+f", d, 0), F8("+f", d, 8), F8("+f", d, 16), F8("+f", d, 24), F8("+f", d, 32), F8("+f", d, 40),
                 F8("+f", d, 48), F8("+f", d, 56), F8("+f", d, 64), F8("+f", d, 72), F8("+f", d, 80), F8("+f", d, 88)
               : "r"(a), "r"(b) : "memory");
}

#define TSTEP(REGS, W, X, ow, ox)                                                           \
  "mov.b64 db, {" X ", hi};\nadd.u64 db, db, " #ox ";\nmov.b64 da, {" W ", hi};\nadd.u64 da, da, " #ow ";\n" \
  "wgmma.mma_async.sync.aligned.m64n128k16.f32.bf16.bf16 {" REGS "}, da, db, 1, 1, 1, 1, 0;\n"
#define THEAD "{\n.reg .b32 hi;\n.reg .b64 da, db;\nmov.b32 hi, 0x40000040;\nwgmma.fence.sync.aligned;\n"
#define TTAIL "wgmma.commit_group.sync.aligned;\n}\n"
__device__ __forceinline__ void mma_kblock_t(float (&acc)[2][96], uint32_t wd, uint32_t xd) {
  asm volatile(THEAD TSTEP(ACC128_0, "%128", "%129", 0, 0) TSTEP(ACC128_1, "%128", "%129", 256, 0)
               TSTEP(ACC128_0, "%128", "%129", 128, 2) TSTEP(ACC128_1, "%128", "%129", 384, 2)
               TSTEP(ACC128_0, "%128", "%129", 512, 4) TSTEP(ACC128_1, "%128", "%129", 768, 4)
               TSTEP(ACC128_0, "%128", "%129", 640, 6) TSTEP(ACC128_1, "%128", "%129", 896, 6) TTAIL
               : OPS128("+f") : "r"(wd), "r"(xd) : "memory");
}
__device__ __forceinline__ void mma_half_t(float (&d)[96], uint32_t wd, uint32_t xd) {
  asm volatile(THEAD TSTEP(ACC128_0, "%64", "%65", 0, 0) TSTEP(ACC128_0, "%64", "%65", 128, 2)
               TSTEP(ACC128_0, "%64", "%65", 512, 4) TSTEP(ACC128_0, "%64", "%65", 640, 6) TTAIL
               : F8("+f", d, 0), F8("+f", d, 8), F8("+f", d, 16), F8("+f", d, 24), F8("+f", d, 32), F8("+f", d, 40),
                 F8("+f", d, 48), F8("+f", d, 56) : "r"(wd), "r"(xd) : "memory");
}

enum { kModePlain = 0, kModeHead = 1, kModeSkip = 2, kModeContinue = 3 };

template <int N>
__device__ __forceinline__ void fence_acc(float (&acc)[2][96]) {
#pragma unroll
  for (int h = 0; h < 2; h++)
#pragma unroll
    for (int i = 0; i < N / 2; i++) asm volatile("" : "+f"(acc[h][i])::"memory");
}

constexpr uint32_t kToB = (kTileBytes >> 4) + ((4096u >> 4) << 16) - (1u << 16);

#define TRACE_KB(nb)

template <int N>
__device__ __forceinline__ void head_blocks(float (&acc)[2][96], uint32_t sb, int n0, int slot, int xver,
                                            uint32_t rel_addr, bool rel) {
  const uint32_t ring = (((sb & 0x3FFFF) + kSmRing) >> 4) | (1u << 16);
  const uint32_t xdesc = (((sb & 0x3FFFF) + kSmX) >> 4) | (1u << 16);
  const uint32_t s0 = ring + slot * 2560, s1 = ring + ((slot + 1) & 3) * 2560;
  const uint32_t nb = n0 * 8, xbar = sb + kBarX + (xver - 1) * 16;
  if (xver > 0) {
    mbar_wait(xbar, 0);
    mbar_wait(sb + kBarTurn + (xver == 1 ? 2 : 3 * xver) * 8, 0);
  }
  mbar_wait(sb + kBarFull + (nb & 56), nb >> 6);
  if (n0 == 0) TRACE_AT(0, 1);
  TRACE_KB(nb);
  mma_kblock<N, 2>(acc, xver > 0 ? xdesc : s0, s0 + kToB);
  if (xver > 0) mbar_wait(xbar + 8, 0);
  mbar_wait(sb + kBarFull + (nb & 56) + 8, nb >> 6);
  TRACE_KB(nb + 8);
  mma_kblock<N, 0>(acc, xver > 0 ? xdesc + (kTileBytes >> 4) : s1, s1 + kToB);
  wg_wait<1>();
  if (rel) mbar_arrive_cluster(rel_addr + (nb & 56));
  wg_wait<0>();
  if (rel) mbar_arrive_cluster(rel_addr + (nb & 56) + 8);
  fence_acc<N>(acc);
}

enum { kPlain, kResid, kStagger };
template <int N, int KIND, class Pre>
__device__ __forceinline__ void mainloop(float (&acc)[2][96], uint32_t sb, int tile, int n0, int slot, int nkb,
                                         int pause_kk, int att, uint32_t rel_addr, bool rel, int own_kk, Pre pre,
                                         uint32_t prev = 64) {
  constexpr bool RESID = KIND == kResid;
  constexpr uint32_t kStep = (N == 192 ? 5 : 4) * 512;
  const uint32_t ring = (((sb & 0x3FFFF) + kSmRing) >> 4) | (1u << 16);
  uint32_t st = ring + slot * kStep;
  uint32_t nb = n0 * 8;
  const uint32_t last = nb + 8 * (nkb - (RESID ? 4 : KIND == kStagger ? 2 : 1)), own = nb + 8 * own_kk;
  const uint32_t stg = (((sb & 0x3FFFF) + kSmStg) >> 4) | (1u << 16);
  uint32_t stop = pause_kk >= 0 ? nb + 8 * pause_kk : last;
  const bool signal = (threadIdx.x & 127) == 64;
  fence_acc<N>(acc);
  if (tile > 0) mbar_wait(sb + kBarTurn + (tile - 1) * 8, 0);
  TRACE_AT(tile, 0);
#pragma unroll 1
  while (true) {
#pragma unroll 1
    do {
      mbar_wait(sb + kBarFull + (nb & 56), nb >> 6);
      TRACE_KB(nb);
      if constexpr (RESID) mma_kblock_t(acc, st + kToB, nb == own ? stg : st);
      else mma_kblock<N, 0>(acc, st, st + kToB);
      wg_wait<1>();
      if (rel) mbar_arrive_cluster(rel_addr + prev);
      prev = nb & 56;
      st += kStep;
      if (st == ring + 10240) st = ring;
      nb += 8;
    } while (nb != stop);
    if (stop == last) break;
    stop = last;
    if (signal) mbar_arrive(sb + kBarPause + att * 8);
    wg_wait<0>();
    if (rel) mbar_arrive_cluster(rel_addr + prev);
    prev = 64;
    mbar_wait(sb + kBarResume + att * 8, 0);
  }
  mbar_wait(sb + kBarFull + (nb & 56), nb >> 6);
  TRACE_KB(nb);
  if constexpr (RESID) {
    const uint32_t z = gridDim.y - 1;
    const uint32_t s1 = st + kStep, s2 = s1 + kStep, s3 = s2 == ring + 8192 ? ring : s2 + kStep;
    mma_half_t(acc[0], st + kToB, st);
    wg_wait<1>();
    if (rel) mbar_arrive_cluster(rel_addr + 24);
    mbar_wait(sb + kBarFull + 40, nb >> 6);
    TRACE_KB(nb + 8);
    mma_half_t(acc[0], s1 + kToB, s1);
    mbar_wait(sb + kBarFull + 48, nb >> 6);
    TRACE_KB(nb + 16);
    mma_half_t(acc[0], s2 + kToB, s2);
    mbar_wait(sb + kBarFull + 56, nb >> 6);
    TRACE_KB(nb + 24);
    mma_half_t(acc[0], s3 + kToB, s3);
    mma_half_t(acc[1], st + kToB + 256, st + z);
    mma_half_t(acc[1], s1 + kToB + 256, s1 + z);
    wg_wait<2>();
#pragma unroll
    for (int i = 0; i < 64; i++) asm volatile("" : "+f"(acc[0][i])::"memory");
    pre(0);
    mma_half_t(acc[1], s2 + kToB + 256, s2 + z);
    wg_wait<2>();
    if (rel) mbar_arrive_cluster(rel_addr + 32);
    pre(1);
    mma_half_t(acc[1], s3 + kToB + 256, s3 + z);
    wg_wait<2>();
    if (rel) mbar_arrive_cluster(rel_addr + 40);
    wg_wait<1>();
    if (signal) mbar_arrive(sb + kBarTurn + tile * 8);
    if (rel) mbar_arrive_cluster(rel_addr + 48);
    wg_wait<0>();
    if (rel) mbar_arrive_cluster(rel_addr + 56);
#pragma unroll
    for (int i = 0; i < 64; i++) asm volatile("" : "+f"(acc[1][i])::"memory");
  } else if constexpr (KIND == kStagger) {
    const uint32_t z = gridDim.y - 1, s2 = st + kStep;
    mma_half(acc[1], st + 64, st + kToB);
    wg_wait<1>();
    if (rel) mbar_arrive_cluster(rel_addr + 40);
    mbar_wait(sb + kBarFull + 56, nb >> 6);
    TRACE_KB(nb + 8);
    mma_half(acc[1], s2 + 64, s2 + kToB);
    mma_half(acc[0], st, st + z + kToB);
    pre(0);
    mma_half(acc[0], s2, s2 + z + kToB);
    wg_wait<2>();
#pragma unroll
    for (int i = 0; i < 96; i++) asm volatile("" : "+f"(acc[1][i])::"memory");
    pre(1);
    wg_wait<1>();
    if (rel) mbar_arrive_cluster(rel_addr + 48);
    pre(2);
    if (signal) mbar_arrive(sb + kBarTurn + tile * 8);
    pre(3);
    wg_wait<0>();
    if (rel) mbar_arrive_cluster(rel_addr + 56);
#pragma unroll
    for (int i = 0; i < 96; i++) asm volatile("" : "+f"(acc[0][i])::"memory");
  } else {
    mma_kblock<N, 1>(acc, st, st + kToB);
    wg_wait<2>();
    if (rel) mbar_arrive_cluster(rel_addr + prev);
    pre();
    wg_wait<1>();
    if (signal) mbar_arrive(sb + kBarTurn + tile * 8);
    wg_wait<0>();
    if (rel) mbar_arrive_cluster(rel_addr + (nb & 56));
    fence_acc<N>(acc);
  }
}

__device__ __forceinline__ void publish_stats(uint32_t sb, uint2* stat, int w, int lane, unsigned epoch) {
  const uint32_t row = sb + kSmX + (32 * w + lane) * 128;
  float s[4], q[4];
#pragma unroll
  for (int c = 0; c < 4; c++) s[c] = q[c] = 0.f;
  uint32_t nx[4];
  ldsm4(row + ((lane & 7) << 4), nx);
#pragma unroll 1
  for (int J = 1; J <= 16; J++) {
    const uint32_t r[4] = {nx[0], nx[1], nx[2], nx[3]};
    ldsm4(row + ((J >> 3) & 1) * kTileBytes + (((J ^ lane) & 7) << 4), nx);
#pragma unroll
    for (int c = 0; c < 4; c++) {
      const float lo = bf_lo(r[c]);
      s[c] += lo;
      q[c] = fmaf(lo, lo, q[c]);
      if (c & 1) yield_slot();
    }
#pragma unroll
    for (int c = 0; c < 4; c++) {
      const float hi = bf_hi(r[c]);
      s[c] += hi;
      q[c] = fmaf(hi, hi, q[c]);
      if (c & 1) yield_slot();
    }
  }
  const int t = lane & 3, g = lane >> 2;
#pragma unroll
  for (int c = 0; c < 2; c++) {
    s[c] = (t & 2 ? s[c + 2] : s[c]) + shfl_xor(t & 2 ? s[c] : s[c + 2], 2);
    q[c] = (t & 2 ? q[c + 2] : q[c]) + shfl_xor(t & 2 ? q[c] : q[c + 2], 2);
  }
  const float so = (t & 1 ? s[1] : s[0]) + shfl_xor(t & 1 ? s[0] : s[1], 1);
  const float qo = (t & 1 ? q[1] : q[0]) + shfl_xor(t & 1 ? q[0] : q[1], 1);
  asm volatile("{\n.reg .b64 t;\nmov.b64 t, {%1, %2};\nst.relaxed.gpu.global.b64 [%0], t;\n}" ::"l"(stat + 32 * w + 8 * t + g),
               "r"(tag_value(so, epoch)), "r"(__float_as_uint(qo)) : "memory");
}

__device__ __forceinline__ void add_chunk(float (&a)[8], const uint4& v) {
  a[0] += bf_lo(v.x); a[1] += bf_hi(v.x);
  a[2] += bf_lo(v.y); a[3] += bf_hi(v.y);
  a[4] += bf_lo(v.z); a[5] += bf_hi(v.z);
  a[6] += bf_lo(v.w); a[7] += bf_hi(v.w);
}

__device__ __forceinline__ int helper_col(int id, int slab) {
  return (slab < 3 ? slab * kD : (slab - 3) * 512) + id * 128;
}
__device__ __forceinline__ void helper_cta(const CUtensorMap* map_q, const CUtensorMap* map_1, uint8_t* sm,
                                           uint32_t sb, int id, int warp) {
  constexpr int kRed = 6 * 32768, kBar = kRed + 2 * 4096;
  const int tid = threadIdx.x;
  if (warp == 8 && elect()) {
#pragma unroll
    for (int s = 0; s < 6; s++) {
      mbar_init(sb + kBar + s * 8, 1);
      mbar_init(sb + kBar + 64 + s * 8, 4);
    }
    fence_async_smem();
#pragma unroll
    for (int s = 0; s < 6; s++) {
      mbar_expect_tx(sb + kBar + s * 8, 32768);
      tma2d(sb + s * 32768, map_q, sb + kBar + s * 8, id * 128, s * 128);
    }
  }
  __syncthreads();
  if (warp == 8) {
    int slot = 0, ph = 0;
#pragma unroll 1
    for (int n = 6; n < 80; n++) {
      mbar_wait(sb + kBar + 64 + slot * 8, ph);
      if (elect()) {
        mbar_expect_tx(sb + kBar + slot * 8, 32768);
        tma2d(sb + slot * 32768, n < 24 ? map_q : map_1, sb + kBar + slot * 8, helper_col(id, n >> 3), (n & 7) * 128);
      }
      if (++slot == 6) slot = 0, ph ^= 1;
    }
  } else if (warp < 8) {
    if (tid == 0) *reinterpret_cast<unsigned*>(sm + kBar + 128) = atomicAdd(&g_ticket, 1u) / kGrid + 1;
    int slot = warp >> 2, ph = 0;
#pragma unroll 1
    for (int slab = 0; slab < 10; slab++) {
      float a[8];
#pragma unroll
      for (int e = 0; e < 8; e++) a[e] = 0.f;
#pragma unroll 1
      for (int box = 0; box < 4; box++) {
        mbar_wait_bounded(sb + kBar + slot * 8, ph);
        const uint4* p = reinterpret_cast<const uint4*>(sm + slot * 32768) + (tid & 127);
        uint4 v[16];
#pragma unroll
        for (int i = 0; i < 16; i++) v[i] = p[i * 128];
        __syncwarp();
        if (elect()) mbar_arrive(sb + kBar + 64 + slot * 8);
#pragma unroll
        for (int i = 0; i < 16; i++) add_chunk(a, v[i]);
        slot += 2;
        if (slot >= 6) slot -= 6, ph ^= 1;
      }
      float* red = reinterpret_cast<float*>(sm + kRed + (slab & 1) * 4096);
#pragma unroll
      for (int e = 0; e < 8; e++) a[e] += shfl_xor(a[e], 16);
      if ((tid & 16) == 0) {
        float4* d = reinterpret_cast<float4*>(red + warp * 128 + (tid & 15) * 8);
        d[0] = make_float4(a[0], a[1], a[2], a[3]);
        d[1] = make_float4(a[4], a[5], a[6], a[7]);
      }
      asm volatile("bar.sync 1, 256;" ::: "memory");
      if (warp < 4) {
        float t = 0.f;
#pragma unroll
        for (int q = 0; q < 8; q++) t += red[q * 128 + tid];
        st_relaxed(g_cs + (slab < 3 ? 0 : 3 * kD) + helper_col(id, slab) + tid,
                   tag_value(t, *reinterpret_cast<volatile unsigned*>(sm + kBar + 128)));
      }
    }
  }
}

__device__ __forceinline__ void colsum_strip(const CUtensorMap* map, uint8_t* sm, uint32_t sb, int col, int half,
                                             int lane, unsigned epoch) {
  const uint32_t bar = sb + kBarSlab + half * 16;
  const int buf = kSmStg + half * 8192;
  float a[8];
#pragma unroll
  for (int e = 0; e < 8; e++) a[e] = 0.f;
#pragma unroll 1
  for (int r = -2; r < 4; r++) {
    if (r >= 0) {
      mbar_wait(bar + (r & 1) * 8, r >> 1);
      const uint4* p = reinterpret_cast<const uint4*>(sm + buf + (r & 1) * 4096) + lane;
#pragma unroll 1
      for (int q = 0; q < 8; q += 4) {
        uint4 v[4];
#pragma unroll
        for (int u = 0; u < 4; u++) v[u] = p[(q + u) * 32];
#pragma unroll
        for (int u = 0; u < 4; u++) {
          a[0] += bf_lo(v[u].x); a[1] += bf_hi(v[u].x); a[2] += bf_lo(v[u].y); a[3] += bf_hi(v[u].y);
          yield_slot();
          a[4] += bf_lo(v[u].z); a[5] += bf_hi(v[u].z); a[6] += bf_lo(v[u].w); a[7] += bf_hi(v[u].w);
          yield_slot();
        }
      }
      fence_async_smem();
      __syncwarp();
    }
    if (r < 2 && elect()) {
      mbar_expect_tx(bar + (r & 1) * 8, 4096);
      tma2d(sb + buf + (r & 1) * 4096, map, bar + (r & 1) * 8, col, half * 512 + (r + 2) * 128);
    }
  }
#pragma unroll
  for (int e = 0; e < 4; e++) a[e] = (lane & 16 ? a[e + 4] : a[e]) + shfl_xor(lane & 16 ? a[e] : a[e + 4], 16);
#pragma unroll
  for (int e = 0; e < 2; e++) a[e] = (lane & 8 ? a[e + 2] : a[e]) + shfl_xor(lane & 8 ? a[e] : a[e + 2], 8);
  a[0] = (lane & 4 ? a[1] : a[0]) + shfl_xor(lane & 4 ? a[0] : a[1], 4);
  a[0] += shfl_xor(a[0], 2);
  if (!(lane & 2)) st_relaxed(g_cs + half * (3 * kD + kF) + col + (lane & 1) * 8 + (lane >> 2), tag_value(a[0], epoch));
}

constexpr float kGeluBeta = 0.3292034911525734f / 2.f;
constexpr float kGeluK = 2.423681954311584f / 4.f;
constexpr float kHScale = 2.f * kGeluBeta;

__device__ __forceinline__ void store_staged(uint8_t* dst, uint32_t stg) {
  fence_async_smem();
  __syncwarp();
  if (elect()) {
    bulk_store(dst, stg, 4096);
    bulk_commit();
  }
}

#define GY_MASK 5
#define GF_MASK 3
#define GY(k) if ((GY_MASK >> k) & 1) yield_slot()
template <int J0, int J1>
__device__ __forceinline__ void fold_norm(float (&acc)[2][96], const float2 (&st)[4], const float4* vec) {
  float4 vn = vec[J0 * 4];
#pragma unroll
  for (int J = J0; J < J1; J++) {
    const float4 v = vn;
    if (J + 1 < J1) vn = vec[J * 4 + 4];
#pragma unroll
    for (int c = 0; c < 4; c++) {
      float& a0 = acc[c & 1][4 * J + (c & 2)];
      float& a1 = acc[c & 1][4 * J + (c & 2) + 1];
      a0 = fmaf(a0, st[c].x, fmaf(st[c].y, v.x, v.z));
      a1 = fmaf(a1, st[c].x, fmaf(st[c].y, v.y, v.w));
      asm volatile("" : "+f"(a0), "+f"(a1));
      if ((c & 1) && ((GF_MASK >> (c >> 1)) & 1)) yield_slot();
    }
  }
}

template <int CH, class Acquire>
__device__ __forceinline__ void gelu_chunk(const float (&acc)[2][96], uint32_t stg, int lane, uint8_t* prev,
                                           Acquire acquire) {
  uint32_t pk[8][4];
  float z[3][4];
  const uint32_t row = (stg + lane * 128) ^ ((lane & 7) << 4);
#define U(s, e) acc[(e) >> 1][4 * (CH * 8 + ((s) >> 1)) + 2 * ((s) & 1) + ((e) & 1)]
#pragma unroll
  for (int s = 0; s < 18; s++) {
    const int cur = s % 3, p1 = (s + 2) % 3, p2 = (s + 1) % 3, q = s - 2, jj = 2 * q - 24;
    const bool mid = s >= 1 && s < 17;
    if (mid) z[p1][0] = tanh_fast(z[p1][0]);
    if (s < 16) {
#pragma unroll
      for (int e = 0; e < 4; e++) {
        z[cur][e] = fmaf(U(s, e), U(s, e), kGeluK);
        asm volatile("" : "+f"(z[cur][e]));
      }
    }
    if (jj >= 0) stsm4(row ^ (jj << 4), pk[jj][0], pk[jj][1], pk[jj][2], pk[jj][3]);
    GY(0);
    if (mid) z[p1][1] = tanh_fast(z[p1][1]);
    if (q >= 0) {
      pk[q >> 1][2 * (q & 1)] = pack2(fmaf(U(q, 0), z[p2][0], U(q, 0)), fmaf(U(q, 1), z[p2][1], U(q, 1)));
      pk[q >> 1][2 * (q & 1) + 1] = pack2(fmaf(U(q, 2), z[p2][2], U(q, 2)), fmaf(U(q, 3), z[p2][3], U(q, 3)));
    }
    GY(1);
    if (mid) z[p1][2] = tanh_fast(z[p1][2]);
    if (s < 16) {
#pragma unroll
      for (int e = 0; e < 4; e++) {
        z[cur][e] = z[cur][e] * U(s, e) * 8.f;
        asm volatile("" : "+f"(z[cur][e]));
      }
    }
    if (mid) z[p1][3] = tanh_fast(z[p1][3]);
    if (jj >= 0) stsm4(row ^ ((jj + 1) << 4), pk[jj + 1][0], pk[jj + 1][1], pk[jj + 1][2], pk[jj + 1][3]);
    GY(2);
    if (CH == 1 && s == 1) store_staged(prev, stg);
    if (q == 11) acquire();
  }
#undef U
}

__device__ __forceinline__ void scale_stats(float2 (&st)[4]) {
#pragma unroll
  for (int c = 0; c < 4; c++) {
    st[c].x *= kGeluBeta;
    st[c].y *= st[c].x;
  }
}

__device__ __forceinline__ void add_mean_term(float (&acc)[2][96], const float2 (&st)[4], uint8_t* sm, int tq,
                                              int lane) {
  const float2* cs = reinterpret_cast<const float2*>(sm + kSmCsQ) + tq * 96 + (lane & 3);
  float2 vn = cs[0];
#pragma unroll
  for (int J = 0; J < 24; J++) {
    const float2 v = vn;
    if (J < 23) vn = cs[J * 4 + 4];
#pragma unroll
    for (int c = 0; c < 4; c++) {
      acc[c & 1][4 * J + (c & 2)] = fmaf(st[c].y, v.x, acc[c & 1][4 * J + (c & 2)]);
      acc[c & 1][4 * J + (c & 2) + 1] = fmaf(st[c].y, v.y, acc[c & 1][4 * J + (c & 2) + 1]);
    }
    yield_slot();
  }
}

#define CV_MASK 1
#define HALO_AT 2
struct AttnRegs {
  uint32_t q[4][8], k[5][8], vt[5][8];
};
#define SCALED(c, J) pack2(acc[(c) & 1][4 * (J) + ((c) & 2)] * st[c].x, acc[(c) & 1][4 * (J) + ((c) & 2) + 1] * st[c].x)
__device__ __forceinline__ void convert_group(const float (&acc)[2][96], const float2 (&st)[4], AttnRegs& r, int c,
                                              int part) {
#pragma unroll
  for (int J = 0; J < 8; J++) {
    if (part == 0) r.q[c][J] = SCALED(c, J);
    if (part == 1) r.k[c + 1][J] = SCALED(c, 8 + J);
    if (part == 2) r.vt[c + 1][J] = transpose8(SCALED(c, 16 + J));
    if ((J & CV_MASK) == CV_MASK) yield_slot();
  }
}
#undef SCALED

__device__ __forceinline__ void convert_odd(const float (&acc)[2][96], const float2 (&st)[4], AttnRegs& r, int step,
                                            uint8_t* sm, uint32_t halo_bar, uint4* halo_out, bool send,
                                            unsigned epoch, int w, int lane) {
  if (step == 1) {
    convert_group(acc, st, r, 3, 2);
    convert_group(acc, st, r, 3, 1);
    if (w < 3) {
      uint2* hs = reinterpret_cast<uint2*>(sm + kSmHalo + w * 2048) + lane;
#pragma unroll
      for (int i = 0; i < 4; i++) {
        hs[i * 32] = make_uint2(r.k[4][2 * i], r.k[4][2 * i + 1]);
        hs[128 + i * 32] = make_uint2(r.vt[4][2 * i], r.vt[4][2 * i + 1]);
      }
      __syncwarp();
      if (elect()) mbar_arrive(halo_bar + w * 8);
    } else if (send) {
#pragma unroll
      for (int i = 0; i < 4; i++) {
        st_packet(halo_out + lane + i * 32, r.k[4][2 * i], r.k[4][2 * i + 1], epoch);
        st_packet(halo_out + lane + 128 + i * 32, r.vt[4][2 * i], r.vt[4][2 * i + 1], epoch);
      }
    }
  } else if (step == 2) {
    convert_group(acc, st, r, 1, 2);
  } else {
    convert_group(acc, st, r, 1, 1);
    convert_group(acc, st, r, 3, 0);
    convert_group(acc, st, r, 1, 0);
  }
}

__device__ __forceinline__ void epilogue_attn(const float (&acc)[2][96], const float2 (&st)[4], AttnRegs& r,
                                              uint8_t* sm, uint32_t sb, int layer, int tq, int b, int j,
                                              unsigned epoch, int tile, int w, int lane) {
  const int t = lane & 3, g = lane >> 2;
  const int hp = j + 8 * tq, att = 2 * layer + tq;
  auto& q = r.q;
  auto& k = r.k;
  auto& vt = r.vt;
  const bool first = w == 0 && (b & 7) == 0;
  const uint4* gh = g_halo + ((layer * 16 + b - 1) * 16 + hp) * 256 + lane;
  uint32_t tag[8];
#define LOAD_HALO()                                                                                    \
  _Pragma("unroll") for (int i = 0; i < 4; i++) {                                                      \
    ld_packet(gh + i * 32, k[0][2 * i], k[0][2 * i + 1], tag[i]);                                      \
    ld_packet(gh + 128 + i * 32, vt[0][2 * i], vt[0][2 * i + 1], tag[4 + i]);                          \
  }
#pragma unroll
  for (int c = 0; c <= 6; c++) {
    if (c == HALO_AT) {
#pragma unroll
      for (int i = 0; i < 8; i++) k[0][i] = vt[0][i] = tag[i] = 0u;
      if (w > 0) {
        mbar_wait(sb + kBarHalo + (att * 3 + w - 1) * 8, 0);
        const uint2* hs = reinterpret_cast<const uint2*>(sm + kSmHalo + (w - 1) * 2048) + lane;
#pragma unroll
        for (int i = 0; i < 4; i++) {
          const uint2 a = hs[i * 32], d = hs[128 + i * 32];
          k[0][2 * i] = a.x; k[0][2 * i + 1] = a.y;
          vt[0][2 * i] = d.x; vt[0][2 * i + 1] = d.y;
        }
      } else if (!first) {
        LOAD_HALO();
      }
    }
    if (c < 6) convert_group(acc, st, r, 2 * (c & 1), 2 - (c >> 1));
  }
  TRACE_AT(tile, 8);
  if (w == 0 && !first) {
#pragma unroll 1
    while (__any_sync(0xffffffffu, ((tag[0] ^ epoch) | (tag[1] ^ epoch) | (tag[2] ^ epoch) | (tag[3] ^ epoch)) |
                                       ((tag[4] ^ epoch) | (tag[5] ^ epoch) | (tag[6] ^ epoch) | (tag[7] ^ epoch)))) {
      LOAD_HALO();
    }
  }
  constexpr float kScale = 0.17677669529663687f * 1.4426950408889634f;
  const bool own0 = 2 * t <= g, own1 = 2 * t + 1 <= g;
  const uint32_t own_mask = (own0 ? 0xffffu : 0u) | (own1 ? 0xffff0000u : 0u);
  const uint32_t stg = sb + kSmStg + w * 4096;
  const uint32_t orow = stg + (lane & 7) * 128, ochunk = (lane >> 3) ^ (lane & 7);
  TRACE_AT(tile, 9);
  mbar_wait(sb + kBarPause + att * 8, 0);
  TRACE_AT(tile, 10);

  float s[2][6][4], o[2][4][2][4];
#pragma unroll
  for (int n = 0; n < 24; n++) {
    const int ks = n / 12, hd = (n % 12) / 6, m = n % 6, ca = 2 * (m / 3), kg = ca + m % 3, J = 4 * hd + 2 * ks;
    if (ks == 0) s[hd][m][0] = s[hd][m][1] = s[hd][m][2] = s[hd][m][3] = 0.f;
    mma16816(s[hd][m], q[ca][J], q[ca + 1][J], q[ca][J + 1], q[ca + 1][J + 1], k[kg][J], k[kg][J + 1]);
  }
  float v0[2][4], v1[2][4], m[2][4];
  uint32_t pp[2][4], po[2][4];
#define UNITS _Pragma("unroll") for (int hd = 0; hd < 2; hd++) _Pragma("unroll") for (int c = 0; c < 4; c++)
  UNITS {
    const int mp = 3 * (c >> 1) + (c & 1), r = 2 * (c & 1);
    float p0 = s[hd][mp][r], p1 = s[hd][mp][r + 1];
    if (c == 0 && first) p0 = p1 = -INFINITY;
    v0[hd][c] = own0 ? s[hd][mp + 1][r] : p0;
    v1[hd][c] = own1 ? s[hd][mp + 1][r + 1] : p1;
    m[hd][c] = fmaxf(v0[hd][c], v1[hd][c]);
  }
  UNITS m[hd][c] = fmaxf(m[hd][c], shfl_xor(m[hd][c], 1));
  UNITS m[hd][c] = fmaxf(m[hd][c], shfl_xor(m[hd][c], 2));
  UNITS {
    const float nm = -m[hd][c] * kScale;
    v0[hd][c] = ex2(fmaf(v0[hd][c], kScale, nm));
    v1[hd][c] = ex2(fmaf(v1[hd][c], kScale, nm));
    m[hd][c] = v0[hd][c] + v1[hd][c];
  }
  UNITS m[hd][c] += shfl_xor(m[hd][c], 1);
  UNITS m[hd][c] += shfl_xor(m[hd][c], 2);
  UNITS {
    const float inv = rcp(m[hd][c]);
    const uint32_t p = pack2(v0[hd][c] * inv, v1[hd][c] * inv);
    pp[hd][c] = p & ~own_mask;
    po[hd][c] = p & own_mask;
    asm volatile("" : "+r"(pp[hd][c]), "+r"(po[hd][c]));
  }
#pragma unroll
  for (int n = 0; n < 24; n++) {
    const int ph = n / 8, hd = (n >> 2) & 1, c = 2 * ((n >> 1) & 1) + (ph == 1), ds = n & 1, J = 4 * hd + 2 * ds;
    float(&d)[4] = o[hd][c][ds];
    if (ph < 2) d[0] = d[1] = d[2] = d[3] = 0.f;
    if (ph == 0) mma1688(d, vt[c + 1][J], vt[c + 1][J + 1], po[hd][c]);
    if (ph == 1) mma16816(d, vt[c][J], vt[c][J + 1], vt[c + 1][J], vt[c + 1][J + 1], pp[hd][c], po[hd][c]);
    if (ph == 2) mma1688(d, vt[c][J], vt[c][J + 1], pp[hd][c]);
    if (n == 3) {
      yield_slot();
      if (tq == 0 && lane == 0) mbar_arrive(sb + kBarResume + att * 8);
    }
  }
  yield_slot();
  if (tq == 1 && lane == 0) mbar_arrive(sb + kBarResume + att * 8);
  TRACE_AT(tile, 11);
  UNITS stsm4_t(orow + c * 1024 + ((ochunk ^ (4 * hd)) << 4), pack2(o[hd][c][0][0], o[hd][c][0][1]),
                pack2(o[hd][c][0][2], o[hd][c][0][3]), pack2(o[hd][c][1][0], o[hd][c][1][1]),
                pack2(o[hd][c][1][2], o[hd][c][1][3]));
#undef UNITS
#undef LOAD_HALO
  fence_async_smem();
  __syncwarp();
  TRACE_AT(tile, 12);
  if (elect()) {
    bulk_store(g_o + (b * 16 + hp) * kTileBytes + w * 4096, stg, 4096);
    bulk_commit();
    bulk_wait();
    TRACE_AT(tile, 13);
    mbar_arrive(sb + kBarEpi + tile * 8);
  }
  __syncwarp();
}

__device__ __forceinline__ void gather_stats(uint8_t* sm, const uint2* stat, int r, float eps, unsigned epoch) {
  uint2 a[8];
  unsigned diff;
#pragma unroll 1
  do {
    diff = 0;
#pragma unroll
    for (int i = 0; i < 8; i++) {
      a[i] = ld_relaxed64(stat + i * 128 + r);
      diff |= a[i].x ^ epoch;
    }
  } while (__any_sync(0xffffffffu, diff & 7u));
  float s = 0.f, q = 0.f;
#pragma unroll
  for (int i = 0; i < 8; i++) {
    s += untag_value(a[i].x);
    q += __uint_as_float(a[i].y);
  }
  const float mean = s * (1.f / 1024.f);
  const float var = fmaxf(fmaf(-mean, mean, q * (1.f / 1024.f)), 0.f);
  reinterpret_cast<float2*>(sm + kSmStat)[r] = make_float2(rsqrtf(var + eps), -mean);
}

__device__ __forceinline__ void gather_colsums_qkv(uint8_t* sm, int tq, int j, int lane, unsigned epoch) {
  const uint2* src = reinterpret_cast<const uint2*>(g_cs + (j + 8 * tq) * 64) + lane;
  uint2 v[3], u[3];
  unsigned diff, spins = 0;
#pragma unroll 1
  do {
    if (++spins > kSpinLimit) __trap();
    diff = 0;
#pragma unroll
    for (int q = 0; q < 3; q++) {
      v[q] = ld_relaxed_pair(src + q * (kD / 2));
      u[q] = make_uint2(epoch & 7u, epoch & 7u);
      if (tq) u[q] = ld_relaxed_pair(src + (q * kD + 3 * kD + kF) / 2);
    }
#pragma unroll
    for (int q = 0; q < 3; q++) diff |= (v[q].x ^ epoch) | (v[q].y ^ epoch) | (u[q].x ^ epoch) | (u[q].y ^ epoch);
  } while (__any_sync(0xffffffffu, diff & 7u));
#pragma unroll
  for (int q = 0; q < 3; q++)
    reinterpret_cast<float2*>(sm + kSmCsQ)[tq * 96 + q * 32 + lane] =
        make_float2(untag_value(v[q].x) + untag_value(u[q].x), untag_value(v[q].y) + untag_value(u[q].y));
}

__device__ __forceinline__ void gather_colsums_w1(uint8_t* sm, const __nv_bfloat16* b1, int j, int lane,
                                                  unsigned epoch) {
#pragma unroll 1
  for (int blk = 0; blk < 7; blk++) {
    const int pair = 32 * (blk + (blk < 3 ? 3 * j : blk < 5 ? 21 + 2 * j : 35 + 2 * j)) + lane;
    const uint32_t bias = reinterpret_cast<const uint32_t*>(b1)[pair];
    uint2 v;
    unsigned spins = 0;
#pragma unroll 1
    do {
      if (++spins > kSpinLimit) __trap();
      v = ld_relaxed_pair(reinterpret_cast<const uint2*>(g_cs + 3 * kD) + pair);
    } while (__any_sync(0xffffffffu, ((v.x ^ epoch) | (v.y ^ epoch)) & 7u));
    reinterpret_cast<float4*>(sm + kSmV1)[blk * 32 + lane] =
        make_float4(untag_value(v.x), untag_value(v.y), kGeluBeta * bf_lo(bias), kGeluBeta * bf_hi(bias));
  }
}

#define PAUSE_QKV2 7
#define PAUSE_WO 2

__global__ void __cluster_dims__(2, 1, 1) __launch_bounds__(384, 1)
fused_layers_kernel(const __grid_constant__ CUtensorMap map_x, const __grid_constant__ CUtensorMap map_out,
                    const __grid_constant__ CUtensorMap map_qkv, const __grid_constant__ CUtensorMap map_wo,
                    const __grid_constant__ CUtensorMap map_w1a, const __grid_constant__ CUtensorMap map_w1b,
                    const __grid_constant__ CUtensorMap map_w2, const __grid_constant__ CUtensorMap map_csq,
                    const __grid_constant__ CUtensorMap map_cs1, const __grid_constant__ CUtensorMap map_css,
                    const __grid_constant__ Params prm) {
  extern __shared__ __align__(1024) uint8_t sm[];
  if (threadIdx.x < 128 && blockIdx.x < kCtas) TRACE_AT(15, 1);
  const uint32_t sb = __shfl_sync(0xffffffffu, smem_u32(sm), 0);
  const int warp = __shfl_sync(0xffffffffu, threadIdx.x >> 5, 0), lane = threadIdx.x & 31;
  const int cta = blockIdx.x, rank = cta & 1, cl = cta >> 1;
  const int grp = cl < 4 ? 0 : cl < 36 ? (cl - 4) & 7 : 1 + (cl - 36) % 7;
  const int j = cl < 4 ? 4 + cl : cl < 36 ? (cl - 4) >> 3 : 4 + (cl - 36) / 7;
  const int b = 2 * grp + rank;
  const int xcol = (b >> 3) * kD, xrow = (b & 7) * 128;

  if (cta >= kCtas) {
    helper_cta(&map_csq, &map_cs1, sm, sb, cta - kCtas, warp);
    return;
  }
  if ((warp < 8 || warp == 9) && elect()) {
    if (warp == 9) {
#pragma unroll
      for (int s = 0; s < 8; s++) mbar_init(sb + kBarFull + s * 8, 1);
      fence_async_smem();
#pragma unroll 1
      for (int s = 0; s < 4; s++) {
        const uint32_t full = sb + kBarFull + s * 8, dst = sb + kSmRing + s * 40960;
        mbar_expect_tx(full, 40960);
        tma2d(dst, &map_x, full, xcol + (s & 1) * 64, xrow);
        tma3d(dst + kTileBytes, &map_qkv, full, (j + 4 * (s & 2)) * 64, (s & 1) * 64, 0);
        tma3d(dst + kTileBytes + 12288, &map_qkv, full, (j + 4 * (s & 2)) * 64, (s & 1) * 64 + 32, 0);
      }
    } else {
      if (sb & 1023) __trap();
#pragma unroll
      for (int s = 0; s < 16; s++) mbar_init(sb + kBarTurn + warp * 128 + s * 8, warp < 5 ? 1 : warp == 5 ? 2 : 4);
    }
    asm volatile("fence.mbarrier_init.release.cluster;" ::: "memory");
  }
  __syncwarp();
  asm volatile("barrier.cluster.arrive.relaxed.aligned;" ::: "memory");

  if (warp >= 8) {
    asm volatile("setmaxnreg.dec.sync.aligned.u32 40;");
    if (warp < 10) {
      asm volatile("barrier.cluster.wait.aligned;" ::: "memory");
      uint32_t nb = 32, off = 0, kb = 0;
#define RING_STEP(WAIT, ISSUE)                                            \
  do {                                                                    \
    const uint32_t mb = nb - depth, full = sb + kBarFull + (nb & 56);     \
    if (kb == skip) kb += inc;                                            \
    mbar_wait(sb + kBarEmpty + (mb & 56), mb >> 6);                       \
    WAIT;                                                                 \
    if (elect()) { ISSUE; }                                               \
    TRACE_ISSUE(9 - warp, nb);                                            \
    kb += inc;                                                            \
    off = off == wrap ? 0 : off + step;                                   \
    nb += 8;                                                              \
  } while (nb != nend)
#pragma unroll 1
      for (int sg = 0; sg < kSegs; sg++) {
        const uint32_t e = prm.seg[sg];
        const int ty = e & 7, mode = (e >> 15) & 3, reset = (e >> 24) & 3;
        const uint32_t nend = nb + (e & 0x1f8);
        const uint32_t step = (e >> 17) & 1 ? 40960 : 32768, wrap = 163840 - step;
        const uint32_t depth = (e >> 18) & 1 ? 40 : 32;
        if (reset) off = reset == 1 ? 0 : reset == 2 ? 40960 : 131072;
        const uint32_t own = ty == 2 ? 8 + j : 2 * j;
        if (mode != kModeContinue) kb = mode == kModeHead ? own : (e >> 9) & 63;
        const uint32_t inc = mode >= kModeSkip && ty != 2 ? 2 : 1, skip = mode >= kModeSkip ? own + (kb & 1) : 255;
        if (warp == 8) {
          const CUtensorMap* map = ty < 2 ? &map_qkv : ty == 2 ? &map_wo : ty == 3 ? &map_w1a : ty < 6 ? &map_w1b : &map_w2;
          const int c0 = ty < 2 ? (j + 8 * ty) * 64 : 0;
          const int c2 = ty < 2 ? 0 : ty == 3 ? 3 * j : ty == 4 ? 24 + 2 * j : ty == 5 ? 40 + 2 * j : 2 * j;
          const uint32_t half = (ty < 2 || ty == 3) ? 12288 : 8192;
          const uint32_t bytes = 2 * half + (mode == kModeHead ? 0 : kTileBytes);
          const uint32_t dst = sb + kSmRing + kTileBytes + rank * half;
          if (e >> 26) {
            const bool second = (grp & 6) == 2;
            const int pk = grp < 4 ? 2 * j + (grp & 1) : 2 * (grp - 4 + (grp - 4 >= j));
            const CUtensorMap* pm = ty == 6 ? &map_qkv : second ? &map_w1b : &map_w1a;
            if (elect())
              asm volatile("cp.async.bulk.prefetch.tensor.3d.L2.global [%0, {%1, %2, %3}];" ::"l"(pm),
                           "r"(ty == 6 ? (j + 8 * second) * 64 : 0), "r"(pk * 64 + rank * 32),
                           "r"(ty == 6 ? 0 : second ? 24 + 2 * j : 3 * j) : "memory");
          }
          if (ty == 2 && mode == kModeHead) mbar_wait(sb + kBarEpi + ((e >> 19) & 31) * 8, 0);
#pragma unroll 1
          RING_STEP(, mbar_expect_tx(full, bytes); tma3d_mc(dst + off, map, full, c0, kb * 64 + rank * 32, c2));
        } else if (mode == kModeHead) {
          off += ((nend - nb) >> 3) * step;
          nb = nend;
          if (off >= 163840) off -= 163840;
        } else if (sg < 2) {
#pragma unroll 1
          RING_STEP(, tma2d(sb + kSmRing + off, &map_x, full, xcol + kb * 64, xrow));
        } else {
          const uint8_t* src = ty == 6 ? g_h + b * 56 * kTileBytes : (ty == 2 ? g_o : g_x) + b * 16 * kTileBytes;
          const int dep = (e >> 19) & 31;
          if (dep < 28) mbar_wait(sb + kBarReady + dep * 8, 0);
          if ((dep & 30) == 28) {
#pragma unroll 1
            RING_STEP(mbar_wait(sb + kBarSrc + ((kb << (4 - inc)) & 56), dep),
                      bulk_load(sb + kSmRing + off, src + kb * kTileBytes, kTileBytes, full));
          } else {
#pragma unroll 1
            RING_STEP(, bulk_load(sb + kSmRing + off, src + kb * kTileBytes, kTileBytes, full));
          }
        }
      }
#undef RING_STEP
    } else {
      unsigned epoch = 0;
      if (warp == 10) {
        if (lane == 0) epoch = atomicAdd(&g_ticket, 1u) / kGrid + 1;
        *reinterpret_cast<unsigned*>(sm + kSmEpoch) = __shfl_sync(0xffffffffu, epoch, 0);
        asm volatile("barrier.cluster.wait.aligned;" ::: "memory");
        if (elect()) mbar_arrive(sb + kBarEpoch);
      } else {
        asm volatile("barrier.cluster.wait.aligned;" ::: "memory");
        mbar_wait_bounded(sb + kBarFull, 0);
        if (elect()) {
          mbar_expect_tx(sb + kBarInit, 32768);
          tma2d(sb + kSmX, &map_x, sb + kBarInit, xcol + j * 128, xrow);
          tma2d(sb + kSmX + kTileBytes, &map_x, sb + kBarInit, xcol + j * 128 + 64, xrow);
        }
        const uint2 u = reinterpret_cast<const uint2*>(prm.b2)[32 * j + lane];
        reinterpret_cast<float4*>(sm + kSmB2)[lane] = make_float4(
            kHScale * bf_lo(u.x), kHScale * bf_hi(u.x), kHScale * bf_lo(u.y), kHScale * bf_hi(u.y));
      }
      mbar_wait_bounded(sb + kBarEpoch, 0);
      epoch = *reinterpret_cast<volatile unsigned*>(sm + kSmEpoch);
      if (cta < 96) {
        mbar_wait_bounded(sb + kBarInit, 0);
        colsum_strip(&map_css, sm, sb, (cta >> 5) * kD + 512 + (cta & 31) * 16, warp - 10, lane, epoch);
      }
      gather_colsums_qkv(sm, 11 - warp, j, lane, epoch);
      __syncwarp();
      if (elect()) mbar_arrive(sb + kBarCs + (11 - warp) * 8);
     if (warp == 10) {
#pragma unroll 1
      for (int i = 0; i < kTiles - 1; i++) {
        const bool xt = i == 2 || i == 6 || i == 9;
        const unsigned* line = g_flag + (i * 16 + b) * 32;
        mbar_wait(sb + (xt ? kBarX + (i >> 2) * 16 : kBarEpi + i * 8), 0);
        if (xt || i == 1 || i == 8) {
          unsigned todo = 0xff;
          do {
            const unsigned now = __ballot_sync(0xffffffffu, ld_relaxed(line + (lane & 7)) == epoch) & todo;
            if (now) {
              asm volatile("fence.acquire.gpu;\nfence.proxy.async.global;" ::: "memory");
              if ((now >> lane) & 1) mbar_arrive(sb + kBarSrc + lane * 8);
              todo ^= now;
            }
          } while (todo);
        } else {
          wait_flags(line + (lane & 7), epoch);
          if (elect()) mbar_arrive(sb + kBarReady + i * 8);
        }
        if (xt) {
          wait_flags(line + 8 + (lane & 7), epoch);
          if (elect()) mbar_arrive(sb + kBarReady + (14 + (i >> 2)) * 8);
        }
      }
     } else {
#pragma unroll 1
      for (int i = 0; i < kTiles - 1; i++) {
        if (i == 3) {
          gather_colsums_w1(sm, prm.b1, j, lane, epoch);
          __syncwarp();
          if (elect()) mbar_arrive(sb + kBarCs + 16);
        }
        const bool xt = i == 2 || i == 6 || i == 9;
#pragma unroll 1
        for (int h = 0; h < (xt ? 2 : 1); h++) {
          if (xt && h == 0) {
            mbar_wait_bounded(sb + kBarEpi + i * 8, 0);
            if (elect()) bulk_store(g_x + (b * 16 + 2 * j) * kTileBytes, sb + kSmX, kTileBytes / 2);
          }
          mbar_wait_bounded(sb + (xt ? kBarX + (i >> 2) * 16 + 8 * h : kBarEpi + i * 8), 0);
          const int ty = i >= 7 ? i - 7 : i;
          if (ty >= 2 && elect()) {
            uint8_t* dst = xt ? g_x + (b * 16 + 2 * j + h) * kTileBytes
                              : g_h + (b * 56 + 1 + (ty == 3 ? 3 * j : 16 * ty - 40 + 2 * j)) * kTileBytes;
            const int piece = (xt && h == 0) ? kTileBytes / 2 : kTileBytes / 4;
#pragma unroll 1
            for (int o = xt && h == 0 ? piece : 0; o < kTileBytes; o += piece) {
              bulk_store(dst + o, sb + (xt ? kSmX + h * kTileBytes : kSmStg) + o, piece);
              bulk_commit();
              bulk_wait();
            }
            if (!xt) mbar_arrive(sb + kBarFree + i * 8);
          }
          __syncwarp();
          if (elect()) st_release(&g_flag[(i * 16 + b) * 32 + h * 8 + j], epoch);
          __syncwarp();
        }
      }
#pragma unroll 1
      for (int q = 0; q < 4; q++) {
        if (!(q & 1)) mbar_wait_bounded(sb + kBarEpi + (kTiles - 1) * 8, q >> 1);
        else mbar_wait_bounded(sb + kBarX + 48 + 4 * (q & 2), 0);
        if (elect()) {
          tma2d_store(&map_out, sb + kSmX + q * 8192, xcol + j * 128 + (q >> 1) * 64, xrow + (q & 1) * 64);
          bulk_commit();
          if (q == 3) bulk_wait_read();
        }
      }
     }
    }
    __syncwarp();
    asm volatile("barrier.cluster.arrive.relaxed.aligned;\nbarrier.cluster.wait.aligned;" ::: "memory");
  } else {
    asm volatile("setmaxnreg.inc.sync.aligned.u32 232;");
    asm volatile("barrier.cluster.wait.aligned;" ::: "memory");
    const int wg = warp >> 2, w = warp & 3;
    const bool rel = (threadIdx.x & 95) == 0;
    const uint32_t rel_addr = mapa(sb + kBarEmpty, w & 1);
    if (wg == 1) TRACE_AT(15, 0);
#define EPOCH (*reinterpret_cast<volatile unsigned*>(sm + kSmEpoch))

#pragma unroll 1
    for (int i = wg; i < kTiles; i += 2) {
      const int layer = i >= 7, ty = i - 7 * layer;
      TRACE_AT(i, 15);
      float acc[2][96];
      if (ty == 2 || ty == 6) {
        const int lane = lane_id();
        const uint32_t xa = sb + kSmX + ((lane >> 4) * 8 + (lane & 7)) * 128 + (((2 * w + ((lane >> 3) & 1)) ^ (lane & 7)) << 4);
        const float up = ty == 6 ? kHScale / kXScale : layer ? 1.f / kXScale : 1.f;
        const float dn = ty == 2 ? kXScale : layer ? 1.f / kHScale : kXScale / kHScale;
#pragma unroll
        for (int h = 0; h < 2; h++) {
          const float* b2 = reinterpret_cast<const float*>(sm + kSmB2) + 64 * h + 16 * w + (lane >> 2);
          const float bias[2] = {ty == 6 ? b2[0] : 0.f, ty == 6 ? b2[8] : 0.f};
#pragma unroll
          for (int p = 0; p < 8; p++) {
            uint32_t r[4];
            ldsm4_t(xa + h * kTileBytes + p * 2048, r);
#pragma unroll
            for (int m = 0; m < 4; m++) {
              acc[h][8 * p + 2 * m] = fmaf(bf_lo(r[m]), up, bias[m & 1]);
              acc[h][8 * p + 2 * m + 1] = fmaf(bf_hi(r[m]), up, bias[m & 1]);
              asm volatile("" : "+f"(acc[h][8 * p + 2 * m]), "+f"(acc[h][8 * p + 2 * m + 1]));
            }
            yield_slot();
          }
        }
        auto stage = [&](int qt) {
          const int h = qt >> 1;
          if (qt == 1 || (qt == 3 && i == kTiles - 1)) {
            fence_async_smem();
            __syncwarp();
            if (lane == 0) mbar_arrive(sb + kBarEpi + i * 8);
          }
#pragma unroll
          for (int p = 4 * (qt & 1); p < 4 * (qt & 1) + 4; p++) {
            const float* a = &acc[h][8 * p];
            stsm4_t(xa + h * kTileBytes + p * 2048, pack2(a[0] * dn, a[1] * dn), pack2(a[2] * dn, a[3] * dn),
                    pack2(a[4] * dn, a[5] * dn), pack2(a[6] * dn, a[7] * dn));
            yield_slot();
          }
          if (qt & 1) {
            fence_async_smem();
            __syncwarp();
            if (elect()) mbar_arrive(sb + kBarX + (i >> 2) * 16 + 8 * h);
            TRACE_AT(i, 8 + h);
          }
        };
        mainloop<128, kResid>(acc, sb, i, layer * 152 + ty * 16, ty == 6 ? 4 : 0, ty == 6 ? 56 : 16,
                            ty == 2 ? PAUSE_WO : -1, 2 * layer + 1, rel_addr, rel, ty == 2 ? 8 : -1, stage);
        TRACE_AT(i, 2);
        stage(2);
        stage(3);
      } else {
        const int xver = 2 * layer + (ty >= 3);
        const uint32_t stg = sb + kSmStg + w * 4096;
        const float4* vec = reinterpret_cast<const float4*>(sm + kSmV1) + (ty == 3 ? 0 : 64 * ty - 160);
        int lane;
        uint8_t* hdst = g_h + (b * 56 + (ty == 3 ? 3 * j : 16 * ty - 40 + 2 * j)) * kTileBytes + w * 4096;
        float2 st[4];
        unsigned epoch;
        auto pre = [&] {
          lane = lane_id();
          if (ty < 4) mbar_wait(sb + (ty == 1 ? kBarEpi + (i - 1) * 8 : kBarStat + xver * 8), 0);
#pragma unroll
          for (int c = 0; c < 4; c++) st[c] = reinterpret_cast<const float2*>(sm + kSmStat)[32 * w + 8 * c + (lane >> 2)];
          epoch = EPOCH;
        };
        auto team_stats = [&] {
          uint2* stat = g_stat + (xver * 16 + b) * 1024;
          lane = lane_id();
          publish_stats(sb, stat + j * 128, w, lane, EPOCH);
          gather_stats(sm, stat, 32 * w + lane, xver ? 1e-5f * kXScale * kXScale : 1e-5f, EPOCH);
          __syncwarp();
          if (elect()) mbar_arrive(sb + kBarStat + xver * 8);
          TRACE_AT(i, 14);
        };
        if (ty < 4) {
          AttnRegs ar;
          auto odd = [&](int step) {
            if (step == 0) pre();
            else convert_odd(acc, st, ar, step, sm, sb + kBarHalo + (xver + ty) * 24,
                             g_halo + ((layer * 16 + b) * 16 + j + 8 * ty) * 256, (b & 7) != 7, epoch, w, lane);
          };
          head_blocks<192>(acc, sb, layer * 152 + (ty < 2 ? 2 * ty : 48), ty < 2 ? 2 * ty : 1, xver, rel_addr, rel);
          if (ty == 1) {
            if (i == 1) {
              mbar_wait(sb + kBarEpoch, 0);
              mbar_wait(sb + kBarInit, 0);
            }
            team_stats();
            epoch = 0;
#pragma unroll
            for (int c = 0; c < 4; c++) st[c] = reinterpret_cast<const float2*>(sm + kSmStat)[32 * w + 8 * c + (lane >> 2)];
          } else {
            mainloop<192, kPlain>(acc, sb, i, layer * 152 + (ty ? 52 : 4), ty ? 1 : 0, 14, -1, 0, rel_addr, rel, 0, pre);
            TRACE_AT(i, 2);
            if (ty == 3) goto wide_gelu;
          }
          if (layer == 0) mbar_wait(sb + kBarCs + ty * 8, 0);
          add_mean_term(acc, st, sm, ty, lane);
          if (ty == 1) {
            mainloop<192, kStagger>(acc, sb, i, layer * 152 + 18, 2, 14, PAUSE_QKV2, xver, rel_addr, rel, 0, odd);
            TRACE_AT(i, 2);
          } else {
            odd(1);
            odd(2);
            odd(3);
          }
          epilogue_attn(acc, st, ar, sm, sb, layer, ty, b, j, epoch, i, w, lane);
          TRACE_AT(i, 3);
          continue;
        wide_gelu:
          if (i == 3) mbar_wait(sb + kBarCs + 16, 0);
          scale_stats(st);
          fold_norm<16, 24>(acc, st, vec + (lane & 3));
          TRACE_AT(i, 11);
          gelu_chunk<2>(acc, stg, lane, nullptr, [] {});
          TRACE_AT(i, 12);
          fold_norm<0, 2>(acc, st, vec + (lane & 3));
          store_staged(hdst + 2 * kTileBytes, stg);
          fold_norm<2, 16>(acc, st, vec + (lane & 3));
        } else {
          if (ty == 4) {
            head_blocks<128>(acc, sb, layer * 152 + 50, 3, xver, rel_addr, rel);
            team_stats();
          } else {
            const uint32_t s0 = ((((sb & 0x3FFFF) + kSmRing) >> 4) | (1u << 16)) + 3 * 2048;
            mbar_wait(sb + kBarTurn + (i - 1) * 8, 0);
            mbar_wait(sb + kBarFull, layer * 19 + 10);
            TRACE_KB((layer * 152 + 80) * 8);
            mma_kblock<128, 2>(acc, s0, s0 + kToB);
          }
          mainloop<128, kPlain>(acc, sb, i, layer * 152 + 6 + 15 * ty, 4, ty + 10, -1, 0, rel_addr, rel, 0, pre,
                                ty == 5 ? 0 : 64);
          TRACE_AT(i, 2);
          if (i == 4) mbar_wait(sb + kBarCs + 16, 0);
          scale_stats(st);
          fold_norm<0, 16>(acc, st, vec + (lane & 3));
        }
        auto own_store_done = [] {
          if (elect()) bulk_wait();
          __syncwarp();
        };
        TRACE_AT(i, 8);
        gelu_chunk<0>(acc, stg, lane, nullptr, [&] {
          if (ty == 3) own_store_done();
          else mbar_wait(sb + kBarFree + (i - 1) * 8, 0);
        });
        TRACE_AT(i, 9);
        gelu_chunk<1>(acc, stg, lane, hdst, own_store_done);
        TRACE_AT(i, 10);
        fence_async_smem();
        __syncwarp();
        if (elect()) mbar_arrive(sb + kBarEpi + i * 8);
      }
      TRACE_AT(i, 3);
    }
#undef EPOCH
    asm volatile("barrier.cluster.arrive.relaxed.aligned;\nbarrier.cluster.wait.aligned;" ::: "memory");
    if (wg == 1) TRACE_AT(15, 2);
  }
}

void build_segments(uint32_t* seg) {
  int n = 0, fine = 0;
  auto per_source = [&] { return 28 + (fine++ & 1); };
  auto add = [&](int ty, int cnt, int kb0, int mode, int wide, int depth5, int dep, int reset) {
    seg[n++] = ty | cnt << 3 | kb0 << 9 | mode << 15 | wide << 17 | depth5 << 18 | dep << 19 | reset << 24;
  };
  for (int l = 0; l < 2; l++) {
    const int t = 7 * l;
    if (l == 0) {
      add(0, 14, 2, kModePlain, 1, 0, 31, 1);
      add(1, 14, 2, kModePlain, 1, 0, 31, 0);
    } else {
      add(0, 2, 0, kModeHead, 1, 0, 31, 1);
      add(1, 2, 0, kModeHead, 1, 0, 31, 0);
      add(0, 7, 0, kModeSkip, 1, 0, per_source(), 0);
      add(0, 7, 1, kModeSkip, 1, 0, 15, 0);
      add(1, 7, 0, kModeSkip, 1, 0, 31, 0);
      add(1, 7, 1, kModeSkip, 1, 0, 31, 0);
    }
    add(2, 4, 0, kModePlain, 0, 0, t, 1);
    add(2, 4, 4, kModePlain, 0, 1, 31, 4);
    add(2, 1, 0, kModeHead, 0, 1, t + 1, 0);
    add(2, 7, 8, kModeSkip, 0, 1, per_source(), 0);
    add(3, 2, 0, kModeHead, 1, 0, 31, 2);
    add(4, 2, 0, kModeHead, 1, 0, 31, 0);
    add(3, 7, 0, kModeSkip, 1, 0, per_source(), 0);
    add(3, 7, 1, kModeSkip, 1, 0, 14 + 2 * l, 0);
    add(4, 4, 0, kModeSkip, 0, 0, 31, 3);
    add(4, 3, 0, kModeContinue, 0, 1, 31, 0);
    add(4, 7, 1, kModeSkip, 0, 1, 31, 0);
    add(5, 16, 0, kModePlain, 0, 1, 31, 0);
    add(6, 24, 0, kModePlain, 0, 1, t + 3, 0);
    add(6, 16, 24, kModePlain, 0, 1, t + 4, 0);
    add(6, 16, 40, kModePlain, 0, 1, t + 5, l ? 0 : 4);
  }
}

typedef CUresult (*EncodeTiledFn)(CUtensorMap*, CUtensorMapDataType, cuuint32_t, void*, const cuuint64_t*,
                                  const cuuint64_t*, const cuuint32_t*, const cuuint32_t*, CUtensorMapInterleave,
                                  CUtensorMapSwizzle, CUtensorMapL2promotion, CUtensorMapFloatOOBfill);

CUtensorMap make_map(EncodeTiledFn enc, const void* p, int rank, const cuuint64_t* dims, const cuuint64_t* strides,
                     const cuuint32_t* box, CUtensorMapSwizzle swizzle = CU_TENSOR_MAP_SWIZZLE_128B,
                     CUtensorMapL2promotion promo = CU_TENSOR_MAP_L2_PROMOTION_L2_128B) {
  CUtensorMap m;
  const cuuint32_t es[5] = {1, 1, 1, 1, 1};
  enc(&m, CU_TENSOR_MAP_DATA_TYPE_BFLOAT16, rank, const_cast<void*>(p), dims, strides, box, es,
      CU_TENSOR_MAP_INTERLEAVE_NONE, swizzle, promo,
      CU_TENSOR_MAP_FLOAT_OOB_FILL_NONE);
  return m;
}

CUtensorMap weight_map(EncodeTiledFn enc, const void* p, int k, int n, int blocks) {
  const cuuint64_t dims[3] = {64, (cuuint64_t)k, (cuuint64_t)n / 64};
  const cuuint64_t strides[2] = {(cuuint64_t)n * 2, 128};
  const cuuint32_t box[3] = {64, 32, (cuuint32_t)blocks};
  return make_map(enc, p, 3, dims, strides, box, CU_TENSOR_MAP_SWIZZLE_128B, CU_TENSOR_MAP_L2_PROMOTION_L2_256B);
}

CUtensorMap slab_map(EncodeTiledFn enc, const void* p, int n, int cols, int rows) {
  const cuuint64_t dims[2] = {(cuuint64_t)n, kD};
  const cuuint64_t strides[1] = {(cuuint64_t)n * 2};
  const cuuint32_t box[2] = {(cuuint32_t)cols, (cuuint32_t)rows};
  return make_map(enc, p, 2, dims, strides, box, CU_TENSOR_MAP_SWIZZLE_NONE);
}

CUtensorMap token_map(EncodeTiledFn enc, const void* p, int rows) {
  const cuuint64_t dims[2] = {2 * kD, 1024};
  const cuuint64_t strides[1] = {4 * kD};
  const cuuint32_t box[2] = {64, (cuuint32_t)rows};
  return make_map(enc, p, 2, dims, strides, box);
}

}

extern "C" void kernel_launch(void* const* d_in, const int* in_sizes, int n_in, void* d_out, int out_size) {
  (void)in_sizes; (void)n_in; (void)out_size;
  static EncodeTiledFn enc = nullptr;
  if (!enc) {
    void* fn = nullptr;
    cudaDriverEntryPointQueryResult q;
    cudaGetDriverEntryPoint("cuTensorMapEncodeTiled", &fn, cudaEnableDefault, &q);
    enc = (EncodeTiledFn)fn;
    cudaFuncSetAttribute(fused_layers_kernel, cudaFuncAttributeMaxDynamicSharedMemorySize, kSmBytes);
  }
  Params prm;
  prm.b1 = (const __nv_bfloat16*)d_in[5];
  prm.b2 = (const __nv_bfloat16*)d_in[7];
  build_segments(prm.seg);
  const cuuint64_t qd[3] = {kD, kD, 3}, qs[2] = {3 * kD * 2, kD * 2};
  const cuuint32_t qb[3] = {64, 32, 3};
  const CUtensorMap map_x = token_map(enc, d_in[0], 128);
  const CUtensorMap map_out = token_map(enc, d_out, 64);
  const CUtensorMap map_qkv = make_map(enc, d_in[1], 3, qd, qs, qb);
  const CUtensorMap map_wo = weight_map(enc, d_in[2], kD, kD, 2);
  const CUtensorMap map_w1a = weight_map(enc, d_in[4], kD, kF, 3);
  const CUtensorMap map_w1b = weight_map(enc, d_in[4], kD, kF, 2);
  const CUtensorMap map_w2 = weight_map(enc, d_in[6], kF, kD, 2);
  fused_layers_kernel<<<kGrid, 384, kSmBytes>>>(map_x, map_out, map_qkv, map_wo, map_w1a, map_w1b, map_w2,
                                                slab_map(enc, d_in[1], 3 * kD, 128, 128), slab_map(enc, d_in[4], kF, 128, 128),
                                                slab_map(enc, d_in[1], 3 * kD, 16, 128), prm);
}
```

```cpp
#include <cuda.h>
#include <cuda_bf16.h>
#include <cuda_runtime.h>
#include <stdint.h>

namespace {

constexpr int kD = 1024;
constexpr int kF = 3584;
constexpr int kCtas = 128;
constexpr int kGrid = 132;
constexpr int kTiles = 14;
constexpr int kTileBytes = 16384;

constexpr int kSmRing = 0;
constexpr int kSmX = 163840;
constexpr int kSmStg = kSmX + 32768;
constexpr int kSmHalo = kSmStg + 16384;
constexpr int kSmCsQ = kSmHalo + 6144;
constexpr int kSmV1 = kSmCsQ + 384 * 4;
constexpr int kSmB2 = kSmV1 + 448 * 8;
constexpr int kSmStat = kSmB2 + 128 * 4;
constexpr int kSmBar = kSmStat + 128 * 8;
constexpr int kBarFull = kSmBar;
constexpr int kBarTurn = kBarFull + 8 * 8;
constexpr int kBarReady = kBarTurn + 14 * 8;
constexpr int kBarSrc = kBarReady + 17 * 8;
constexpr int kBarPause = kBarSrc + 8 * 8;
constexpr int kBarFree = kBarPause + 4 * 8;
constexpr int kBarCs = kBarFree + 14 * 8;
constexpr int kBarSlab = kBarCs + 3 * 8;
constexpr int kBarHalo = kBarSlab + 4 * 8;
constexpr int kBarInit = kBarHalo + 12 * 8;
constexpr int kBarEpoch = kBarInit + 8;
constexpr int kBarEmpty = kBarTurn + 5 * 128;
constexpr int kBarEpi = kBarEmpty + 128;
constexpr int kBarX = kBarEpi + 14 * 8;
constexpr int kBarStat = kBarX + 8 * 8;
constexpr int kBarResume = kBarStat + 4 * 8;
constexpr int kSmEpoch = kBarEpi + 2 * 128;
static_assert(kBarEpoch < kBarEmpty && kBarResume + 4 * 8 <= kSmEpoch, "barrier groups overflow");
constexpr int kSmBytes = kSmEpoch + 16 + 256;
constexpr int kSegs = 40;

constexpr int kFlagLines = kTiles * 16;

constexpr float kXScale = 1.f / 8.f;

constexpr unsigned kSpinLimit = 1u << 22;

__device__ __align__(1024) uint8_t g_x[16 * 16 * kTileBytes];
__device__ __align__(1024) uint8_t g_o[16 * 16 * kTileBytes];
__device__ __align__(1024) uint8_t g_h[16 * 56 * kTileBytes];
__device__ __align__(128) uint2 g_stat[4 * 16 * 128 * 8];
__device__ __align__(128) unsigned g_cs[3 * kD + kF + 3 * kD];
__device__ __align__(128) uint4 g_halo[2 * 16 * 16 * 256];
__device__ __align__(128) unsigned g_flag[kFlagLines * 32];
__device__ unsigned g_ticket;

#define TRACE_AT(tile, k)
#define TRACE_PUB(i, k, c)
#define TRACE_ISSUE(which, nb)

struct Params {
  const __nv_bfloat16* b1;
  const __nv_bfloat16* b2;
  uint32_t seg[kSegs];
};

__device__ __forceinline__ uint32_t smem_u32(const void* p) {
  return (uint32_t)__cvta_generic_to_shared(p);
}
__device__ __forceinline__ uint32_t mapa(uint32_t a, uint32_t cta) {
  uint32_t r;
  asm("mapa.shared::cluster.u32 %0, %1, %2;" : "=r"(r) : "r"(a), "r"(cta));
  return r;
}
__device__ __forceinline__ void mbar_init(uint32_t bar, int cnt) {
  asm volatile("mbarrier.init.shared::cta.b64 [%0], %1;" ::"r"(bar), "r"(cnt) : "memory");
}
__device__ __forceinline__ void mbar_expect_tx(uint32_t bar, uint32_t bytes) {
  asm volatile("mbarrier.arrive.expect_tx.shared::cta.b64 _, [%0], %1;" ::"r"(bar), "r"(bytes) : "memory");
}
__device__ __forceinline__ void mbar_arrive(uint32_t bar) {
  asm volatile("mbarrier.arrive.shared::cta.b64 _, [%0];" ::"r"(bar) : "memory");
}
__device__ __forceinline__ void mbar_arrive_cluster(uint32_t cluster_addr) {
  asm volatile("mbarrier.arrive.shared::cluster.b64 _, [%0];" ::"r"(cluster_addr) : "memory");
}
__device__ __forceinline__ void mbar_wait(uint32_t bar, uint32_t parity) {
  asm volatile("{\n.reg .pred p;\nRETRY:\nmbarrier.try_wait.parity.shared::cta.b64 p, [%0], %1;\n"
               "@!p bra.uni RETRY;\n}" ::"r"(bar), "r"(parity) : "memory");
}
__device__ __forceinline__ void mbar_wait_bounded(uint32_t bar, uint32_t parity) {
  asm volatile("{\n.reg .pred p;\n.reg .u32 c;\nmov.u32 c, 0;\nRETRY:\n"
               "mbarrier.try_wait.parity.shared::cta.b64 p, [%0], %1;\n@p bra.uni DONE;\n"
               "add.u32 c, c, 1;\nsetp.lt.u32 p, c, %2;\n@p bra.uni RETRY;\ntrap;\nDONE:\n}"
               ::"r"(bar), "r"(parity), "n"(1u << 19) : "memory");
}
__device__ __forceinline__ void tma3d(uint32_t dst, const CUtensorMap* m, uint32_t bar, int c0, int c1, int c2) {
  asm volatile(
      "cp.async.bulk.tensor.3d.shared::cluster.global.mbarrier::complete_tx::bytes [%0], [%1, {%3, %4, %5}], [%2];"
      ::"r"(dst), "l"(m), "r"(bar), "r"(c0), "r"(c1), "r"(c2) : "memory");
}
__device__ __forceinline__ void tma3d_mc(uint32_t dst, const CUtensorMap* m, uint32_t bar, int c0, int c1, int c2) {
  asm volatile(
      "cp.async.bulk.tensor.3d.shared::cluster.global.mbarrier::complete_tx::bytes.multicast::cluster"
      " [%0], [%1, {%3, %4, %5}], [%2], %6;"
      ::"r"(dst), "l"(m), "r"(bar), "r"(c0), "r"(c1), "r"(c2), "h"((uint16_t)3) : "memory");
}
__device__ __forceinline__ void tma2d(uint32_t dst, const CUtensorMap* m, uint32_t bar, int c0, int c1) {
  asm volatile(
      "cp.async.bulk.tensor.2d.shared::cluster.global.mbarrier::complete_tx::bytes [%0], [%1, {%3, %4}], [%2];"
      ::"r"(dst), "l"(m), "r"(bar), "r"(c0), "r"(c1) : "memory");
}
__device__ __forceinline__ void tma2d_store(const CUtensorMap* m, uint32_t src, int c0, int c1) {
  asm volatile("cp.async.bulk.tensor.2d.global.shared::cta.bulk_group [%0, {%2, %3}], [%1];"
               ::"l"(m), "r"(src), "r"(c0), "r"(c1) : "memory");
}
__device__ __forceinline__ int lane_id() {
  int l;
  asm volatile("mov.u32 %0, %%laneid;" : "=r"(l));
  return l;
}
__device__ __forceinline__ bool elect() {
  uint32_t p;
  asm volatile("{\n.reg .pred p;\nelect.sync _|p, 0xffffffff;\nselp.b32 %0, 1, 0, p;\n}" : "=r"(p));
  return p;
}
__device__ __forceinline__ void bulk_load(uint32_t dst, const void* src, uint32_t bytes, uint32_t bar) {
  asm volatile("cp.async.bulk.shared::cluster.global.mbarrier::complete_tx::bytes [%0], [%1], %2, [%3];"
               ::"r"(dst), "l"(src), "r"(bytes), "r"(bar) : "memory");
}
__device__ __forceinline__ void bulk_store(void* dst, uint32_t src, uint32_t bytes) {
  asm volatile("cp.async.bulk.global.shared::cta.bulk_group [%0], [%1], %2;" ::"l"(dst), "r"(src), "r"(bytes)
               : "memory");
}
__device__ __forceinline__ void bulk_commit() { asm volatile("cp.async.bulk.commit_group;" ::: "memory"); }
__device__ __forceinline__ void bulk_wait_read() { asm volatile("cp.async.bulk.wait_group.read 0;" ::: "memory"); }
__device__ __forceinline__ void bulk_wait() { asm volatile("cp.async.bulk.wait_group 0;" ::: "memory"); }
__device__ __forceinline__ void fence_async_smem() { asm volatile("fence.proxy.async.shared::cta;" ::: "memory"); }
__device__ __forceinline__ unsigned ld_relaxed(const unsigned* p) {
  unsigned v;
  asm volatile("ld.relaxed.gpu.global.u32 %0, [%1];" : "=r"(v) : "l"(p) : "memory");
  return v;
}
__device__ __forceinline__ uint2 ld_relaxed64(const uint2* p) {
  uint2 v;
  asm volatile("{\n.reg .b64 t;\nld.relaxed.gpu.global.b64 t, [%2];\nmov.b64 {%0, %1}, t;\n}"
               : "=r"(v.x), "=r"(v.y) : "l"(p) : "memory");
  return v;
}
__device__ __forceinline__ void st_relaxed(unsigned* p, unsigned v) {
  asm volatile("st.relaxed.gpu.global.u32 [%0], %1;" ::"l"(p), "r"(v) : "memory");
}
__device__ __forceinline__ void st_release(unsigned* p, unsigned v) {
  asm volatile("st.release.gpu.global.u32 [%0], %1;" ::"l"(p), "r"(v) : "memory");
}
__device__ __forceinline__ void wait_flags(const unsigned* p, unsigned epoch) {
  while (__any_sync(0xffffffffu, ld_relaxed(p) != epoch)) {
  }
  asm volatile("fence.acquire.gpu;\nfence.proxy.async.global;" ::: "memory");
  __syncwarp();
}
__device__ __forceinline__ void st_packet(uint4* p, uint32_t d0, uint32_t d1, uint32_t tag) {
  asm volatile("{\n.reg .b128 v;\n.reg .b64 x, y;\nmov.b64 x, {%1, %2};\nmov.b64 y, {%3, %3};\nmov.b128 v, {x, y};\n"
               "st.relaxed.gpu.global.b128 [%0], v;\n}" ::"l"(p), "r"(d0), "r"(d1), "r"(tag) : "memory");
}
__device__ __forceinline__ void ld_packet(const uint4* p, uint32_t& d0, uint32_t& d1, uint32_t& tag) {
  asm volatile("{\n.reg .b128 v;\n.reg .b64 x, y;\n.reg .b32 u;\nld.relaxed.gpu.global.b128 v, [%3];\n"
               "mov.b128 {x, y}, v;\nmov.b64 {%0, %1}, x;\nmov.b64 {%2, u}, y;\n}"
               : "=r"(d0), "=r"(d1), "=r"(tag) : "l"(p) : "memory");
}
__device__ __forceinline__ uint2 ld_relaxed_pair(const uint2* p) {
  uint2 v;
  asm volatile("ld.relaxed.gpu.global.v2.u32 {%0, %1}, [%2];" : "=r"(v.x), "=r"(v.y) : "l"(p) : "memory");
  return v;
}
__device__ __forceinline__ unsigned tag_value(float v, unsigned epoch) {
  return (__float_as_uint(v) & ~7u) | (epoch & 7u);
}
__device__ __forceinline__ float untag_value(unsigned v) { return __uint_as_float(v & ~7u); }
__device__ __forceinline__ void stsm4(uint32_t a, uint32_t r0, uint32_t r1, uint32_t r2, uint32_t r3) {
  asm volatile("stmatrix.sync.aligned.m8n8.x4.shared.b16 [%0], {%1, %2, %3, %4};" ::"r"(a), "r"(r0), "r"(r1),
               "r"(r2), "r"(r3) : "memory");
}
__device__ __forceinline__ void stsm4_t(uint32_t a, uint32_t r0, uint32_t r1, uint32_t r2, uint32_t r3) {
  asm volatile("stmatrix.sync.aligned.m8n8.x4.trans.shared.b16 [%0], {%1, %2, %3, %4};" ::"r"(a), "r"(r0),
               "r"(r1), "r"(r2), "r"(r3) : "memory");
}
__device__ __forceinline__ uint32_t transpose8(uint32_t a) {
  uint32_t d;
  asm volatile("movmatrix.sync.aligned.m8n8.trans.b16 %0, %1;" : "=r"(d) : "r"(a));
  return d;
}
__device__ __forceinline__ void mma16816(float (&c)[4], uint32_t a0, uint32_t a1, uint32_t a2, uint32_t a3,
                                         uint32_t b0, uint32_t b1) {
  asm volatile("mma.sync.aligned.m16n8k16.row.col.f32.bf16.bf16.f32 {%0, %1, %2, %3}, {%4, %5, %6, %7}, {%8, %9}, "
               "{%0, %1, %2, %3};"
               : "+f"(c[0]), "+f"(c[1]), "+f"(c[2]), "+f"(c[3])
               : "r"(a0), "r"(a1), "r"(a2), "r"(a3), "r"(b0), "r"(b1));
}
__device__ __forceinline__ void mma1688(float (&c)[4], uint32_t a0, uint32_t a1, uint32_t b0) {
  asm volatile("mma.sync.aligned.m16n8k8.row.col.f32.bf16.bf16.f32 {%0, %1, %2, %3}, {%4, %5}, {%6}, {%0, %1, %2, %3};"
               : "+f"(c[0]), "+f"(c[1]), "+f"(c[2]), "+f"(c[3]) : "r"(a0), "r"(a1), "r"(b0));
}
__device__ __forceinline__ float shfl_xor(float v, int m) {
  float r;
  asm volatile("shfl.sync.bfly.b32 %0, %1, %2, 31, 0xffffffff;" : "=f"(r) : "f"(v), "r"(m));
  return r;
}
__device__ __forceinline__ float tanh_fast(float x) {
  float r;
  asm volatile("tanh.approx.f32 %0, %1;" : "=f"(r) : "f"(x));
  return r;
}
__device__ __forceinline__ void ldsm4(uint32_t a, uint32_t (&r)[4]) {
  asm volatile("ldmatrix.sync.aligned.m8n8.x4.shared.b16 {%0, %1, %2, %3}, [%4];"
               : "=r"(r[0]), "=r"(r[1]), "=r"(r[2]), "=r"(r[3]) : "r"(a) : "memory");
}
__device__ __forceinline__ void ldsm4_t(uint32_t a, uint32_t (&r)[4]) {
  asm volatile("ldmatrix.sync.aligned.m8n8.x4.trans.shared.b16 {%0, %1, %2, %3}, [%4];"
               : "=r"(r[0]), "=r"(r[1]), "=r"(r[2]), "=r"(r[3]) : "r"(a) : "memory");
}
__device__ __forceinline__ uint32_t pack2(float lo, float hi) {
  uint32_t r;
  asm volatile("cvt.rn.bf16x2.f32 %0, %1, %2;" : "=r"(r) : "f"(hi), "f"(lo));
  return r;
}
__device__ __forceinline__ float bf_lo(uint32_t r) { return __uint_as_float(r << 16); }
__device__ __forceinline__ float bf_hi(uint32_t r) { return __uint_as_float(r & 0xffff0000u); }
__device__ __forceinline__ float ex2(float x) {
  float r;
  asm("ex2.approx.ftz.f32 %0, %1;" : "=f"(r) : "f"(x));
  return r;
}
__device__ __forceinline__ float rcp(float x) {
  float r;
  asm("rcp.approx.ftz.f32 %0, %1;" : "=f"(r) : "f"(x));
  return r;
}
template <int N>
__device__ __forceinline__ void wg_wait() {
  asm volatile("wgmma.wait_group.sync.aligned %0;" ::"n"(N) : "memory");
}
__device__ __forceinline__ void yield_slot() { asm volatile("pmevent 0;"); }

template <int N, int KIND>
__device__ __forceinline__ void mma_kblock(float (&acc)[2][96], uint32_t a, uint32_t b);

#define F8(m, d, i) m(d[i]), m(d[i + 1]), m(d[i + 2]), m(d[i + 3]), m(d[i + 4]), m(d[i + 5]), m(d[i + 6]), m(d[i + 7])
#define KSTEP(N, A, B, oa0, oa1, ob, sd)                                                   \
  "mov.b64 db, {" B ", hb};\nadd.u64 db, db, " #ob ";\n"                                    \
  "mov.b64 da, {" A ", ha};\nadd.u64 da, da, " #oa0 ";\n"                                   \
  "wgmma.mma_async.sync.aligned.m64n" #N "k16.f32.bf16.bf16 {" ACC##N##_0 "}, da, db, " #sd ", 1, 1, 0, 1;\n" \
  "mov.b64 da, {" A ", ha};\nadd.u64 da, da, " #oa1 ";\n"                                   \
  "wgmma.mma_async.sync.aligned.m64n" #N "k16.f32.bf16.bf16 {" ACC##N##_1 "}, da, db, " #sd ", 1, 1, 0, 1;\n"

#define MMA_KBLOCK(N, KIND, A, B, ob2, ob3, sd, MID, MODE)                                 \
  template <>                                                                              \
  __device__ __forceinline__ void mma_kblock<N, KIND>(float (&acc)[2][96], uint32_t a, uint32_t b) { \
    asm volatile("{\n.reg .b32 ha, hb;\n.reg .b64 da, db;\n"                            \
                 "mov.b32 ha, 0x40000080;\nmov.b32 hb, 0x40000040;\n"                       \
                 "wgmma.fence.sync.aligned;\n"                                             \
                 KSTEP(N, A, B, 0, 64, 0, sd) KSTEP(N, A, B, 2, 66, 128, 1) MID               \
                 KSTEP(N, A, B, 4, 68, ob2, 1) KSTEP(N, A, B, 6, 70, ob3, 1) "wgmma.commit_group.sync.aligned;\n}\n"  \
                 : OPS##N(MODE) : "r"(a), "r"(b) : "memory");                              \
  }
#define MMA_KBLOCKS(N, A, B, ob2, ob3)                                                     \
  MMA_KBLOCK(N, 0, A, B, ob2, ob3, 1, "", "+f")                                            \
  MMA_KBLOCK(N, 1, A, B, ob2, ob3, 1, "wgmma.commit_group.sync.aligned;\n", "+f")          \
  MMA_KBLOCK(N, 2, A, B, ob2, ob3, 0, "", "=f")

#define ACC128_0 \
  "%0, %1, %2, %3, %4, %5, %6, %7, %8, %9, %10, %11, %12, %13, %14, %15, " \
  "%16, %17, %18, %19, %20, %21, %22, %23, %24, %25, %26, %27, %28, %29, %30, %31, " \
  "%32, %33, %34, %35, %36, %37, %38, %39, %40, %41, %42, %43, %44, %45, %46, %47, " \
  "%48, %49, %50, %51, %52, %53, %54, %55, %56, %57, %58, %59, %60, %61, %62, %63"
#define ACC128_1 \
  "%64, %65, %66, %67, %68, %69, %70, %71, %72, %73, %74, %75, %76, %77, %78, %79, " \
  "%80, %81, %82, %83, %84, %85, %86, %87, %88, %89, %90, %91, %92, %93, %94, %95, " \
  "%96, %97, %98, %99, %100, %101, %102, %103, %104, %105, %106, %107, %108, %109, %110, %111, " \
  "%112, %113, %114, %115, %116, %117, %118, %119, %120, %121, %122, %123, %124, %125, %126, %127"
#define OPS128(m) \
  F8(m, acc[0], 0), F8(m, acc[0], 8), F8(m, acc[0], 16), F8(m, acc[0], 24), F8(m, acc[0], 32), F8(m, acc[0], 40), F8(m, acc[0], 48), F8(m, acc[0], 56), \
        F8(m, acc[1], 0), F8(m, acc[1], 8), F8(m, acc[1], 16), F8(m, acc[1], 24), F8(m, acc[1], 32), F8(m, acc[1], 40), F8(m, acc[1], 48), F8(m, acc[1], 56)
MMA_KBLOCKS(128, "%128", "%129", 512, 640)

#define ACC192_0 \
  "%0, %1, %2, %3, %4, %5, %6, %7, %8, %9, %10, %11, %12, %13, %14, %15, " \
  "%16, %17, %18, %19, %20, %21, %22, %23, %24, %25, %26, %27, %28, %29, %30, %31, " \
  "%32, %33, %34, %35, %36, %37, %38, %39, %40, %41, %42, %43, %44, %45, %46, %47, " \
  "%48, %49, %50, %51, %52, %53, %54, %55, %56, %57, %58, %59, %60, %61, %62, %63, " \
  "%64, %65, %66, %67, %68, %69, %70, %71, %72, %73, %74, %75, %76, %77, %78, %79, " \
  "%80, %81, %82, %83, %84, %85, %86, %87, %88, %89, %90, %91, %92, %93, %94, %95"
#define ACC192_1 \
  "%96, %97, %98, %99, %100, %101, %102, %103, %104, %105, %106, %107, %108, %109, %110, %111, " \
  "%112, %113, %114, %115, %116, %117, %118, %119, %120, %121, %122, %123, %124, %125, %126, %127, " \
  "%128, %129, %130, %131, %132, %133, %134, %135, %136, %137, %138, %139, %140, %141, %142, %143, " \
  "%144, %145, %146, %147, %148, %149, %150, %151, %152, %153, %154, %155, %156, %157, %158, %159, " \
  "%160, %161, %162, %163, %164, %165, %166, %167, %168, %169, %170, %171, %172, %173, %174, %175, " \
  "%176, %177, %178, %179, %180, %181, %182, %183, %184, %185, %186, %187, %188, %189, %190, %191"
#define OPS192(m) \
  F8(m, acc[0], 0), F8(m, acc[0], 8), F8(m, acc[0], 16), F8(m, acc[0], 24), F8(m, acc[0], 32), F8(m, acc[0], 40), F8(m, acc[0], 48), F8(m, acc[0], 56), F8(m, acc[0], 64), F8(m, acc[0], 72), F8(m, acc[0], 80), F8(m, acc[0], 88), \
        F8(m, acc[1], 0), F8(m, acc[1], 8), F8(m, acc[1], 16), F8(m, acc[1], 24), F8(m, acc[1], 32), F8(m, acc[1], 40), F8(m, acc[1], 48), F8(m, acc[1], 56), F8(m, acc[1], 64), F8(m, acc[1], 72), F8(m, acc[1], 80), F8(m, acc[1], 88)
MMA_KBLOCKS(192, "%192", "%193", 768, 896)

#define HSTEP(oa, ob)                                                                       \
  "mov.b64 db, {%97, hb};\nadd.u64 db, db, " #ob ";\nmov.b64 da, {%96, ha};\nadd.u64 da, da, " #oa ";\n" \
  "wgmma.mma_async.sync.aligned.m64n192k16.f32.bf16.bf16 {" ACC192_0 "}, da, db, 1, 1, 1, 0, 1;\n"
__device__ __forceinline__ void mma_half(float (&d)[96], uint32_t a, uint32_t b) {
  asm volatile("{\n.reg .b32 ha, hb;\n.reg .b64 da, db;\nmov.b32 ha, 0x40000080;\nmov.b32 hb, 0x40000040;\n"
               "wgmma.fence.sync.aligned;\n" HSTEP(0, 0) HSTEP(2, 128) HSTEP(4, 768) HSTEP(6, 896)
               "wgmma.commit_group.sync.aligned;\n}\n"
               : F8("+f", d, 0), F8("+f", d, 8), F8("+f", d, 16), F8("+f", d, 24), F8("+f", d, 32), F8("+f", d, 40),
                 F8("+f", d, 48), F8("+f", d, 56), F8("+f", d, 64), F8("+f", d, 72), F8("+f", d, 80), F8("+f", d, 88)
               : "r"(a), "r"(b) : "memory");
}

#define TSTEP(REGS, W, X, ow, ox)                                                           \
  "mov.b64 db, {" X ", hi};\nadd.u64 db, db, " #ox ";\nmov.b64 da, {" W ", hi};\nadd.u64 da, da, " #ow ";\n" \
  "wgmma.mma_async.sync.aligned.m64n128k16.f32.bf16.bf16 {" REGS "}, da, db, 1, 1, 1, 1, 0;\n"
#define THEAD "{\n.reg .b32 hi;\n.reg .b64 da, db;\nmov.b32 hi, 0x40000040;\nwgmma.fence.sync.aligned;\n"
#define TTAIL "wgmma.commit_group.sync.aligned;\n}\n"
__device__ __forceinline__ void mma_kblock_t(float (&acc)[2][96], uint32_t wd, uint32_t xd) {
  asm volatile(THEAD TSTEP(ACC128_0, "%128", "%129", 0, 0) TSTEP(ACC128_1, "%128", "%129", 256, 0)
               TSTEP(ACC128_0, "%128", "%129", 128, 2) TSTEP(ACC128_1, "%128", "%129", 384, 2)
               TSTEP(ACC128_0, "%128", "%129", 512, 4) TSTEP(ACC128_1, "%128", "%129", 768, 4)
               TSTEP(ACC128_0, "%128", "%129", 640, 6) TSTEP(ACC128_1, "%128", "%129", 896, 6) TTAIL
               : OPS128("+f") : "r"(wd), "r"(xd) : "memory");
}
__device__ __forceinline__ void mma_half_t(float (&d)[96], uint32_t wd, uint32_t xd) {
  asm volatile(THEAD TSTEP(ACC128_0, "%64", "%65", 0, 0) TSTEP(ACC128_0, "%64", "%65", 128, 2)
               TSTEP(ACC128_0, "%64", "%65", 512, 4) TSTEP(ACC128_0, "%64", "%65", 640, 6) TTAIL
               : F8("+f", d, 0), F8("+f", d, 8), F8("+f", d, 16), F8("+f", d, 24), F8("+f", d, 32), F8("+f", d, 40),
                 F8("+f", d, 48), F8("+f", d, 56) : "r"(wd), "r"(xd) : "memory");
}

enum { kModePlain = 0, kModeHead = 1, kModeSkip = 2, kModeContinue = 3 };

template <int N>
__device__ __forceinline__ void fence_acc(float (&acc)[2][96]) {
#pragma unroll
  for (int h = 0; h < 2; h++)
#pragma unroll
    for (int i = 0; i < N / 2; i++) asm volatile("" : "+f"(acc[h][i])::"memory");
}

constexpr uint32_t kToB = (kTileBytes >> 4) + ((4096u >> 4) << 16) - (1u << 16);

#define TRACE_KB(nb)

template <int N>
__device__ __forceinline__ void head_blocks(float (&acc)[2][96], uint32_t sb, int n0, int slot, int xver,
                                            uint32_t rel_addr, bool rel) {
  const uint32_t ring = (((sb & 0x3FFFF) + kSmRing) >> 4) | (1u << 16);
  const uint32_t xdesc = (((sb & 0x3FFFF) + kSmX) >> 4) | (1u << 16);
  const uint32_t s0 = ring + slot * 2560, s1 = ring + ((slot + 1) & 3) * 2560;
  const uint32_t to_b = xver > 0 ? kToB - (kTileBytes >> 4) : kToB;
  const uint32_t nb = n0 * 8, xbar = sb + kBarX + (xver - 1) * 16;
  if (xver > 0) {
    mbar_wait(xbar, 0);
    mbar_wait(sb + kBarTurn + (xver == 1 ? 2 : 3 * xver) * 8, 0);
  }
  mbar_wait(sb + kBarFull + (nb & 56), nb >> 6);
  if (n0 == 0) TRACE_AT(0, 1);
  TRACE_KB(nb);
  mma_kblock<N, 2>(acc, xver > 0 ? xdesc : s0, s0 + to_b);
  if (xver > 0) mbar_wait(xbar + 8, 0);
  mbar_wait(sb + kBarFull + (nb & 56) + 8, nb >> 6);
  TRACE_KB(nb + 8);
  mma_kblock<N, 0>(acc, xver > 0 ? xdesc + (kTileBytes >> 4) : s1, s1 + to_b);
  wg_wait<1>();
  if (rel) mbar_arrive_cluster(rel_addr + (nb & 56));
  wg_wait<0>();
  if (rel) mbar_arrive_cluster(rel_addr + (nb & 56) + 8);
  fence_acc<N>(acc);
}

enum { kPlain, kResid, kStagger };
template <int N, int KIND, class Pre>
__device__ __forceinline__ void mainloop(float (&acc)[2][96], uint32_t sb, int tile, int n0, int slot, int nkb,
                                         int pause_kk, int att, uint32_t rel_addr, bool rel, int own_kk, Pre pre,
                                         uint32_t prev = 64) {
  constexpr bool RESID = KIND == kResid;
  constexpr uint32_t kStep = (N == 192 ? 5 : 4) * 512;
  const uint32_t ring = (((sb & 0x3FFFF) + kSmRing) >> 4) | (1u << 16);
  uint32_t st = ring + slot * kStep;
  uint32_t nb = n0 * 8;
  const uint32_t last = nb + 8 * (nkb - (RESID ? 4 : KIND == kStagger ? 2 : 1)), own = nb + 8 * own_kk;
  const uint32_t stg = (((sb & 0x3FFFF) + kSmStg) >> 4) | (1u << 16);
  uint32_t stop = pause_kk >= 0 ? nb + 8 * pause_kk : last;
  const bool signal = (threadIdx.x & 127) == 64;
  fence_acc<N>(acc);
  if (tile > 0) mbar_wait(sb + kBarTurn + (tile - 1) * 8, 0);
  TRACE_AT(tile, 0);
#pragma unroll 1
  while (true) {
#pragma unroll 1
    do {
      mbar_wait(sb + kBarFull + (nb & 56), nb >> 6);
      TRACE_KB(nb);
      if constexpr (RESID) mma_kblock_t(acc, st + kToB, nb == own ? stg : st);
      else mma_kblock<N, 0>(acc, st, st + kToB);
      wg_wait<1>();
      if (rel) mbar_arrive_cluster(rel_addr + prev);
      prev = nb & 56;
      st += kStep;
      if (st == ring + 10240) st = ring;
      nb += 8;
    } while (nb != stop);
    if (stop == last) break;
    stop = last;
    if (signal) mbar_arrive(sb + kBarPause + att * 8);
    wg_wait<0>();
    if (rel) mbar_arrive_cluster(rel_addr + prev);
    prev = 64;
    mbar_wait(sb + kBarResume + att * 8, 0);
  }
  mbar_wait(sb + kBarFull + (nb & 56), nb >> 6);
  TRACE_KB(nb);
  if constexpr (RESID) {
    const uint32_t z = gridDim.y - 1;
    const uint32_t s1 = st + kStep, s2 = s1 + kStep, s3 = s2 == ring + 8192 ? ring : s2 + kStep;
    mma_half_t(acc[0], st + kToB, st);
    wg_wait<1>();
    if (rel) mbar_arrive_cluster(rel_addr + 24);
    mbar_wait(sb + kBarFull + 40, nb >> 6);
    TRACE_KB(nb + 8);
    mma_half_t(acc[0], s1 + kToB, s1);
    mbar_wait(sb + kBarFull + 48, nb >> 6);
    TRACE_KB(nb + 16);
    mma_half_t(acc[0], s2 + kToB, s2);
    mbar_wait(sb + kBarFull + 56, nb >> 6);
    TRACE_KB(nb + 24);
    mma_half_t(acc[0], s3 + kToB, s3);
    mma_half_t(acc[1], st + kToB + 256, st + z);
    mma_half_t(acc[1], s1 + kToB + 256, s1 + z);
    wg_wait<2>();
#pragma unroll
    for (int i = 0; i < 64; i++) asm volatile("" : "+f"(acc[0][i])::"memory");
    pre(0);
    mma_half_t(acc[1], s2 + kToB + 256, s2 + z);
    wg_wait<2>();
    if (rel) mbar_arrive_cluster(rel_addr + 32);
    pre(1);
    mma_half_t(acc[1], s3 + kToB + 256, s3 + z);
    wg_wait<2>();
    if (rel) mbar_arrive_cluster(rel_addr + 40);
    wg_wait<1>();
    if (signal) mbar_arrive(sb + kBarTurn + tile * 8);
    if (rel) mbar_arrive_cluster(rel_addr + 48);
    wg_wait<0>();
    if (rel) mbar_arrive_cluster(rel_addr + 56);
#pragma unroll
    for (int i = 0; i < 64; i++) asm volatile("" : "+f"(acc[1][i])::"memory");
  } else if constexpr (KIND == kStagger) {
    const uint32_t z = gridDim.y - 1, s2 = st + kStep;
    mma_half(acc[1], st + 64, st + kToB);
    wg_wait<1>();
    if (rel) mbar_arrive_cluster(rel_addr + 40);
    mbar_wait(sb + kBarFull + 56, nb >> 6);
    TRACE_KB(nb + 8);
    mma_half(acc[1], s2 + 64, s2 + kToB);
    mma_half(acc[0], st, st + z + kToB);
    pre(0);
    mma_half(acc[0], s2, s2 + z + kToB);
    wg_wait<2>();
#pragma unroll
    for (int i = 0; i < 96; i++) asm volatile("" : "+f"(acc[1][i])::"memory");
    pre(1);
    wg_wait<1>();
    if (rel) mbar_arrive_cluster(rel_addr + 48);
    pre(2);
    if (signal) mbar_arrive(sb + kBarTurn + tile * 8);
    pre(3);
    wg_wait<0>();
    if (rel) mbar_arrive_cluster(rel_addr + 56);
#pragma unroll
    for (int i = 0; i < 96; i++) asm volatile("" : "+f"(acc[0][i])::"memory");
  } else {
    mma_kblock<N, 1>(acc, st, st + kToB);
    wg_wait<2>();
    if (rel) mbar_arrive_cluster(rel_addr + prev);
    pre();
    wg_wait<1>();
    if (signal) mbar_arrive(sb + kBarTurn + tile * 8);
    wg_wait<0>();
    if (rel) mbar_arrive_cluster(rel_addr + (nb & 56));
    fence_acc<N>(acc);
  }
}

__device__ __forceinline__ void publish_stats(uint32_t sb, uint2* stat, int w, int lane, unsigned epoch) {
  const uint32_t row = sb + kSmX + (32 * w + lane) * 128;
  float s[4], q[4];
#pragma unroll
  for (int c = 0; c < 4; c++) s[c] = q[c] = 0.f;
  uint32_t nx[4];
  ldsm4(row + ((lane & 7) << 4), nx);
#pragma unroll 1
  for (int J = 1; J <= 16; J++) {
    const uint32_t r[4] = {nx[0], nx[1], nx[2], nx[3]};
    ldsm4(row + ((J >> 3) & 1) * kTileBytes + (((J ^ lane) & 7) << 4), nx);
#pragma unroll
    for (int c = 0; c < 4; c++) {
      const float lo = bf_lo(r[c]);
      s[c] += lo;
      q[c] = fmaf(lo, lo, q[c]);
      if (c & 1) yield_slot();
    }
#pragma unroll
    for (int c = 0; c < 4; c++) {
      const float hi = bf_hi(r[c]);
      s[c] += hi;
      q[c] = fmaf(hi, hi, q[c]);
      if (c & 1) yield_slot();
    }
  }
  const int t = lane & 3, g = lane >> 2;
#pragma unroll
  for (int c = 0; c < 2; c++) {
    s[c] = (t & 2 ? s[c + 2] : s[c]) + shfl_xor(t & 2 ? s[c] : s[c + 2], 2);
    q[c] = (t & 2 ? q[c + 2] : q[c]) + shfl_xor(t & 2 ? q[c] : q[c + 2], 2);
  }
  const float so = (t & 1 ? s[1] : s[0]) + shfl_xor(t & 1 ? s[0] : s[1], 1);
  const float qo = (t & 1 ? q[1] : q[0]) + shfl_xor(t & 1 ? q[0] : q[1], 1);
  asm volatile("{\n.reg .b64 t;\nmov.b64 t, {%1, %2};\nst.relaxed.gpu.global.b64 [%0], t;\n}" ::"l"(stat + 32 * w + 8 * t + g),
               "r"(tag_value(so, epoch)), "r"(__float_as_uint(qo)) : "memory");
}

__device__ __forceinline__ void add_chunk(float (&a)[8], const uint4& v) {
  a[0] += bf_lo(v.x); a[1] += bf_hi(v.x);
  a[2] += bf_lo(v.y); a[3] += bf_hi(v.y);
  a[4] += bf_lo(v.z); a[5] += bf_hi(v.z);
  a[6] += bf_lo(v.w); a[7] += bf_hi(v.w);
}

__device__ __forceinline__ int helper_col(int id, int slab) {
  return (slab < 3 ? slab * kD : (slab - 3) * 512) + id * 128;
}
__device__ __forceinline__ void helper_cta(const CUtensorMap* map_q, const CUtensorMap* map_1, uint8_t* sm,
                                           uint32_t sb, int id, int warp) {
  constexpr int kRed = 6 * 32768, kBar = kRed + 2 * 4096;
  const int tid = threadIdx.x;
  if (warp == 8 && elect()) {
#pragma unroll
    for (int s = 0; s < 6; s++) {
      mbar_init(sb + kBar + s * 8, 1);
      mbar_init(sb + kBar + 64 + s * 8, 4);
    }
    fence_async_smem();
#pragma unroll
    for (int s = 0; s < 6; s++) {
      mbar_expect_tx(sb + kBar + s * 8, 32768);
      tma2d(sb + s * 32768, map_q, sb + kBar + s * 8, id * 128, s * 128);
    }
  }
  __syncthreads();
  if (warp == 8) {
    int slot = 0, ph = 0;
#pragma unroll 1
    for (int n = 6; n < 80; n++) {
      mbar_wait(sb + kBar + 64 + slot * 8, ph);
      if (elect()) {
        mbar_expect_tx(sb + kBar + slot * 8, 32768);
        tma2d(sb + slot * 32768, n < 24 ? map_q : map_1, sb + kBar + slot * 8, helper_col(id, n >> 3), (n & 7) * 128);
      }
      if (++slot == 6) slot = 0, ph ^= 1;
    }
  } else if (warp < 8) {
    if (tid == 0) *reinterpret_cast<unsigned*>(sm + kBar + 128) = atomicAdd(&g_ticket, 1u) / kGrid + 1;
    int slot = warp >> 2, ph = 0;
#pragma unroll 1
    for (int slab = 0; slab < 10; slab++) {
      float a[8];
#pragma unroll
      for (int e = 0; e < 8; e++) a[e] = 0.f;
#pragma unroll 1
      for (int box = 0; box < 4; box++) {
        mbar_wait_bounded(sb + kBar + slot * 8, ph);
        const uint4* p = reinterpret_cast<const uint4*>(sm + slot * 32768) + (tid & 127);
        uint4 v[16];
#pragma unroll
        for (int i = 0; i < 16; i++) v[i] = p[i * 128];
        __syncwarp();
        if (elect()) mbar_arrive(sb + kBar + 64 + slot * 8);
#pragma unroll
        for (int i = 0; i < 16; i++) add_chunk(a, v[i]);
        slot += 2;
        if (slot >= 6) slot -= 6, ph ^= 1;
      }
      float* red = reinterpret_cast<float*>(sm + kRed + (slab & 1) * 4096);
#pragma unroll
      for (int e = 0; e < 8; e++) a[e] += shfl_xor(a[e], 16);
      if ((tid & 16) == 0) {
        float4* d = reinterpret_cast<float4*>(red + warp * 128 + (tid & 15) * 8);
        d[0] = make_float4(a[0], a[1], a[2], a[3]);
        d[1] = make_float4(a[4], a[5], a[6], a[7]);
      }
      asm volatile("bar.sync 1, 256;" ::: "memory");
      if (warp < 4) {
        float t = 0.f;
#pragma unroll
        for (int q = 0; q < 8; q++) t += red[q * 128 + tid];
        st_relaxed(g_cs + (slab < 3 ? 0 : 3 * kD) + helper_col(id, slab) + tid,
                   tag_value(t, *reinterpret_cast<volatile unsigned*>(sm + kBar + 128)));
      }
    }
  }
}

__device__ __forceinline__ void colsum_strip(const CUtensorMap* map, uint8_t* sm, uint32_t sb, int col, int half,
                                             int lane, unsigned epoch) {
  const uint32_t bar = sb + kBarSlab + half * 16;
  const int buf = kSmStg + half * 8192;
  float a[8];
#pragma unroll
  for (int e = 0; e < 8; e++) a[e] = 0.f;
#pragma unroll 1
  for (int r = -2; r < 4; r++) {
    if (r >= 0) {
      mbar_wait(bar + (r & 1) * 8, r >> 1);
      const uint4* p = reinterpret_cast<const uint4*>(sm + buf + (r & 1) * 4096) + lane;
#pragma unroll 1
      for (int q = 0; q < 8; q += 4) {
        uint4 v[4];
#pragma unroll
        for (int u = 0; u < 4; u++) v[u] = p[(q + u) * 32];
#pragma unroll
        for (int u = 0; u < 4; u++) {
          a[0] += bf_lo(v[u].x); a[1] += bf_hi(v[u].x); a[2] += bf_lo(v[u].y); a[3] += bf_hi(v[u].y);
          yield_slot();
          a[4] += bf_lo(v[u].z); a[5] += bf_hi(v[u].z); a[6] += bf_lo(v[u].w); a[7] += bf_hi(v[u].w);
          yield_slot();
        }
      }
      fence_async_smem();
      __syncwarp();
    }
    if (r < 2 && elect()) {
      mbar_expect_tx(bar + (r & 1) * 8, 4096);
      tma2d(sb + buf + (r & 1) * 4096, map, bar + (r & 1) * 8, col, half * 512 + (r + 2) * 128);
    }
  }
#pragma unroll
  for (int e = 0; e < 4; e++) a[e] = (lane & 16 ? a[e + 4] : a[e]) + shfl_xor(lane & 16 ? a[e] : a[e + 4], 16);
#pragma unroll
  for (int e = 0; e < 2; e++) a[e] = (lane & 8 ? a[e + 2] : a[e]) + shfl_xor(lane & 8 ? a[e] : a[e + 2], 8);
  a[0] = (lane & 4 ? a[1] : a[0]) + shfl_xor(lane & 4 ? a[0] : a[1], 4);
  a[0] += shfl_xor(a[0], 2);
  if (!(lane & 2)) st_relaxed(g_cs + half * (3 * kD + kF) + col + (lane & 1) * 8 + (lane >> 2), tag_value(a[0], epoch));
}

constexpr float kGeluBeta = 0.3292034911525734f / 2.f;
constexpr float kGeluK = 2.423681954311584f / 4.f;
constexpr float kHScale = 2.f * kGeluBeta;

__device__ __forceinline__ void store_staged(uint8_t* dst, uint32_t stg) {
  fence_async_smem();
  __syncwarp();
  if (elect()) {
    bulk_store(dst, stg, 4096);
    bulk_commit();
  }
}

#define GY_MASK 5
#define GF_MASK 3
#define GY(k) if ((GY_MASK >> k) & 1) yield_slot()
template <int J0, int J1>
__device__ __forceinline__ void fold_norm(float (&acc)[2][96], const float2 (&st)[4], const float4* vec) {
  float4 vn = vec[J0 * 4];
#pragma unroll
  for (int J = J0; J < J1; J++) {
    const float4 v = vn;
    if (J + 1 < J1) vn = vec[J * 4 + 4];
#pragma unroll
    for (int c = 0; c < 4; c++) {
      float& a0 = acc[c & 1][4 * J + (c & 2)];
      float& a1 = acc[c & 1][4 * J + (c & 2) + 1];
      a0 = fmaf(a0, st[c].x, fmaf(st[c].y, v.x, v.z));
      a1 = fmaf(a1, st[c].x, fmaf(st[c].y, v.y, v.w));
      asm volatile("" : "+f"(a0), "+f"(a1));
      if ((c & 1) && ((GF_MASK >> (c >> 1)) & 1)) yield_slot();
    }
  }
}

template <int CH, class Acquire>
__device__ __forceinline__ void gelu_chunk(const float (&acc)[2][96], uint32_t stg, int lane, uint8_t* prev,
                                           Acquire acquire) {
  uint32_t pk[8][4];
  float z[3][4];
  const uint32_t row = (stg + lane * 128) ^ ((lane & 7) << 4);
#define U(s, e) acc[(e) >> 1][4 * (CH * 8 + ((s) >> 1)) + 2 * ((s) & 1) + ((e) & 1)]
#pragma unroll
  for (int s = 0; s < 18; s++) {
    const int cur = s % 3, p1 = (s + 2) % 3, p2 = (s + 1) % 3, q = s - 2, jj = 2 * q - 24;
    const bool mid = s >= 1 && s < 17;
    if (mid) z[p1][0] = tanh_fast(z[p1][0]);
    if (s < 16) {
#pragma unroll
      for (int e = 0; e < 4; e++) {
        z[cur][e] = fmaf(U(s, e), U(s, e), kGeluK);
        asm volatile("" : "+f"(z[cur][e]));
      }
    }
    if (jj >= 0) stsm4(row ^ (jj << 4), pk[jj][0], pk[jj][1], pk[jj][2], pk[jj][3]);
    GY(0);
    if (mid) z[p1][1] = tanh_fast(z[p1][1]);
    if (q >= 0) {
      pk[q >> 1][2 * (q & 1)] = pack2(fmaf(U(q, 0), z[p2][0], U(q, 0)), fmaf(U(q, 1), z[p2][1], U(q, 1)));
      pk[q >> 1][2 * (q & 1) + 1] = pack2(fmaf(U(q, 2), z[p2][2], U(q, 2)), fmaf(U(q, 3), z[p2][3], U(q, 3)));
    }
    GY(1);
    if (mid) z[p1][2] = tanh_fast(z[p1][2]);
    if (s < 16) {
#pragma unroll
      for (int e = 0; e < 4; e++) {
        z[cur][e] = z[cur][e] * U(s, e) * 8.f;
        asm volatile("" : "+f"(z[cur][e]));
      }
    }
    if (mid) z[p1][3] = tanh_fast(z[p1][3]);
    if (jj >= 0) stsm4(row ^ ((jj + 1) << 4), pk[jj + 1][0], pk[jj + 1][1], pk[jj + 1][2], pk[jj + 1][3]);
    GY(2);
    if (CH == 1 && s == 1) store_staged(prev, stg);
    if (q == 11) acquire();
  }
#undef U
}

__device__ __forceinline__ void scale_stats(float2 (&st)[4]) {
#pragma unroll
  for (int c = 0; c < 4; c++) {
    st[c].x *= kGeluBeta;
    st[c].y *= st[c].x;
  }
}

__device__ __forceinline__ void add_mean_term(float (&acc)[2][96], const float2 (&st)[4], uint8_t* sm, int tq,
                                              int lane) {
  const float2* cs = reinterpret_cast<const float2*>(sm + kSmCsQ) + tq * 96 + (lane & 3);
  float2 vn = cs[0];
#pragma unroll
  for (int J = 0; J < 24; J++) {
    const float2 v = vn;
    if (J < 23) vn = cs[J * 4 + 4];
#pragma unroll
    for (int c = 0; c < 4; c++) {
      acc[c & 1][4 * J + (c & 2)] = fmaf(st[c].y, v.x, acc[c & 1][4 * J + (c & 2)]);
      acc[c & 1][4 * J + (c & 2) + 1] = fmaf(st[c].y, v.y, acc[c & 1][4 * J + (c & 2) + 1]);
    }
    yield_slot();
  }
}

#define CV_MASK 1
#define HALO_AT 2
struct AttnRegs {
  uint32_t q[4][8], k[5][8], vt[5][8];
};
#define SCALED(c, J) pack2(acc[(c) & 1][4 * (J) + ((c) & 2)] * st[c].x, acc[(c) & 1][4 * (J) + ((c) & 2) + 1] * st[c].x)
__device__ __forceinline__ void convert_group(const float (&acc)[2][96], const float2 (&st)[4], AttnRegs& r, int c,
                                              int part) {
#pragma unroll
  for (int J = 0; J < 8; J++) {
    if (part == 0) r.q[c][J] = SCALED(c, J);
    if (part == 1) r.k[c + 1][J] = SCALED(c, 8 + J);
    if (part == 2) r.vt[c + 1][J] = transpose8(SCALED(c, 16 + J));
    if ((J & CV_MASK) == CV_MASK) yield_slot();
  }
}
#undef SCALED

__device__ __forceinline__ void convert_odd(const float (&acc)[2][96], const float2 (&st)[4], AttnRegs& r, int step,
                                            uint8_t* sm, uint32_t halo_bar, uint4* halo_out, bool send,
                                            unsigned epoch, int w, int lane) {
  if (step == 1) {
    convert_group(acc, st, r, 3, 2);
    convert_group(acc, st, r, 3, 1);
    if (w < 3) {
      uint2* hs = reinterpret_cast<uint2*>(sm + kSmHalo + w * 2048) + lane;
#pragma unroll
      for (int i = 0; i < 4; i++) {
        hs[i * 32] = make_uint2(r.k[4][2 * i], r.k[4][2 * i + 1]);
        hs[128 + i * 32] = make_uint2(r.vt[4][2 * i], r.vt[4][2 * i + 1]);
      }
      __syncwarp();
      if (elect()) mbar_arrive(halo_bar + w * 8);
    } else if (send) {
#pragma unroll
      for (int i = 0; i < 4; i++) {
        st_packet(halo_out + lane + i * 32, r.k[4][2 * i], r.k[4][2 * i + 1], epoch);
        st_packet(halo_out + lane + 128 + i * 32, r.vt[4][2 * i], r.vt[4][2 * i + 1], epoch);
      }
    }
  } else if (step == 2) {
    convert_group(acc, st, r, 1, 2);
  } else {
    convert_group(acc, st, r, 1, 1);
    convert_group(acc, st, r, 3, 0);
    convert_group(acc, st, r, 1, 0);
  }
}

__device__ __forceinline__ void epilogue_attn(const float (&acc)[2][96], const float2 (&st)[4], AttnRegs& r,
                                              uint8_t* sm, uint32_t sb, int layer, int tq, int b, int j,
                                              unsigned epoch, int tile, int w, int lane) {
  const int t = lane & 3, g = lane >> 2;
  const int hp = j + 8 * tq, att = 2 * layer + tq;
  auto& q = r.q;
  auto& k = r.k;
  auto& vt = r.vt;
  const bool first = w == 0 && (b & 7) == 0;
  const uint4* gh = g_halo + ((layer * 16 + b - 1) * 16 + hp) * 256 + lane;
  uint32_t tag[8];
#define LOAD_HALO()                                                                                    \
  _Pragma("unroll") for (int i = 0; i < 4; i++) {                                                      \
    ld_packet(gh + i * 32, k[0][2 * i], k[0][2 * i + 1], tag[i]);                                      \
    ld_packet(gh + 128 + i * 32, vt[0][2 * i], vt[0][2 * i + 1], tag[4 + i]);                          \
  }
#pragma unroll
  for (int c = 0; c <= 6; c++) {
    if (c == HALO_AT) {
#pragma unroll
      for (int i = 0; i < 8; i++) k[0][i] = vt[0][i] = tag[i] = 0u;
      if (w > 0) {
        mbar_wait(sb + kBarHalo + (att * 3 + w - 1) * 8, 0);
        const uint2* hs = reinterpret_cast<const uint2*>(sm + kSmHalo + (w - 1) * 2048) + lane;
#pragma unroll
        for (int i = 0; i < 4; i++) {
          const uint2 a = hs[i * 32], d = hs[128 + i * 32];
          k[0][2 * i] = a.x; k[0][2 * i + 1] = a.y;
          vt[0][2 * i] = d.x; vt[0][2 * i + 1] = d.y;
        }
      } else if (!first) {
        LOAD_HALO();
      }
    }
    if (c < 6) convert_group(acc, st, r, 2 * (c & 1), 2 - (c >> 1));
  }
  TRACE_AT(tile, 8);
  if (w == 0 && !first) {
#pragma unroll 1
    while (__any_sync(0xffffffffu, ((tag[0] ^ epoch) | (tag[1] ^ epoch) | (tag[2] ^ epoch) | (tag[3] ^ epoch)) |
                                       ((tag[4] ^ epoch) | (tag[5] ^ epoch) | (tag[6] ^ epoch) | (tag[7] ^ epoch)))) {
      LOAD_HALO();
    }
  }
  constexpr float kScale = 0.17677669529663687f * 1.4426950408889634f;
  const bool own0 = 2 * t <= g, own1 = 2 * t + 1 <= g;
  const uint32_t own_mask = (own0 ? 0xffffu : 0u) | (own1 ? 0xffff0000u : 0u);
  const uint32_t stg = sb + kSmStg + w * 4096;
  const uint32_t orow = stg + (lane & 7) * 128, ochunk = (lane >> 3) ^ (lane & 7);
  TRACE_AT(tile, 9);
  mbar_wait(sb + kBarPause + att * 8, 0);
  TRACE_AT(tile, 10);

  float s[2][6][4], o[2][4][2][4];
#pragma unroll
  for (int n = 0; n < 24; n++) {
    const int ks = n / 12, hd = (n % 12) / 6, m = n % 6, ca = 2 * (m / 3), kg = ca + m % 3, J = 4 * hd + 2 * ks;
    if (ks == 0) s[hd][m][0] = s[hd][m][1] = s[hd][m][2] = s[hd][m][3] = 0.f;
    mma16816(s[hd][m], q[ca][J], q[ca + 1][J], q[ca][J + 1], q[ca + 1][J + 1], k[kg][J], k[kg][J + 1]);
  }
  float v0[2][4], v1[2][4], m[2][4];
  uint32_t pp[2][4], po[2][4];
#define UNITS _Pragma("unroll") for (int hd = 0; hd < 2; hd++) _Pragma("unroll") for (int c = 0; c < 4; c++)
  UNITS {
    const int mp = 3 * (c >> 1) + (c & 1), r = 2 * (c & 1);
    float p0 = s[hd][mp][r], p1 = s[hd][mp][r + 1];
    if (c == 0 && first) p0 = p1 = -INFINITY;
    v0[hd][c] = own0 ? s[hd][mp + 1][r] : p0;
    v1[hd][c] = own1 ? s[hd][mp + 1][r + 1] : p1;
    m[hd][c] = fmaxf(v0[hd][c], v1[hd][c]);
  }
  UNITS m[hd][c] = fmaxf(m[hd][c], shfl_xor(m[hd][c], 1));
  UNITS m[hd][c] = fmaxf(m[hd][c], shfl_xor(m[hd][c], 2));
  UNITS {
    const float nm = -m[hd][c] * kScale;
    v0[hd][c] = ex2(fmaf(v0[hd][c], kScale, nm));
    v1[hd][c] = ex2(fmaf(v1[hd][c], kScale, nm));
    m[hd][c] = v0[hd][c] + v1[hd][c];
  }
  UNITS m[hd][c] += shfl_xor(m[hd][c], 1);
  UNITS m[hd][c] += shfl_xor(m[hd][c], 2);
  UNITS {
    const float inv = rcp(m[hd][c]);
    const uint32_t p = pack2(v0[hd][c] * inv, v1[hd][c] * inv);
    pp[hd][c] = p & ~own_mask;
    po[hd][c] = p & own_mask;
    asm volatile("" : "+r"(pp[hd][c]), "+r"(po[hd][c]));
  }
#pragma unroll
  for (int n = 0; n < 24; n++) {
    const int ph = n / 8, hd = (n >> 2) & 1, c = 2 * ((n >> 1) & 1) + (ph == 1), ds = n & 1, J = 4 * hd + 2 * ds;
    float(&d)[4] = o[hd][c][ds];
    if (ph < 2) d[0] = d[1] = d[2] = d[3] = 0.f;
    if (ph == 0) mma1688(d, vt[c + 1][J], vt[c + 1][J + 1], po[hd][c]);
    if (ph == 1) mma16816(d, vt[c][J], vt[c][J + 1], vt[c + 1][J], vt[c + 1][J + 1], pp[hd][c], po[hd][c]);
    if (ph == 2) mma1688(d, vt[c][J], vt[c][J + 1], pp[hd][c]);
    if (n == 3) {
      yield_slot();
      if (tq == 0 && lane == 0) mbar_arrive(sb + kBarResume + att * 8);
    }
  }
  yield_slot();
  if (tq == 1 && lane == 0) mbar_arrive(sb + kBarResume + att * 8);
  TRACE_AT(tile, 11);
  UNITS stsm4_t(orow + c * 1024 + ((ochunk ^ (4 * hd)) << 4), pack2(o[hd][c][0][0], o[hd][c][0][1]),
                pack2(o[hd][c][0][2], o[hd][c][0][3]), pack2(o[hd][c][1][0], o[hd][c][1][1]),
                pack2(o[hd][c][1][2], o[hd][c][1][3]));
#undef UNITS
#undef LOAD_HALO
  fence_async_smem();
  __syncwarp();
  TRACE_AT(tile, 12);
  if (elect()) {
    bulk_store(g_o + (b * 16 + hp) * kTileBytes + w * 4096, stg, 4096);
    bulk_commit();
    bulk_wait();
    TRACE_AT(tile, 13);
    mbar_arrive(sb + kBarEpi + tile * 8);
  }
  __syncwarp();
}

__device__ __forceinline__ void gather_stats(uint8_t* sm, const uint2* stat, int r, float eps, unsigned epoch) {
  uint2 a[8];
  unsigned diff;
#pragma unroll 1
  do {
    diff = 0;
#pragma unroll
    for (int i = 0; i < 8; i++) {
      a[i] = ld_relaxed64(stat + i * 128 + r);
      diff |= a[i].x ^ epoch;
    }
  } while (__any_sync(0xffffffffu, diff & 7u));
  float s = 0.f, q = 0.f;
#pragma unroll
  for (int i = 0; i < 8; i++) {
    s += untag_value(a[i].x);
    q += __uint_as_float(a[i].y);
  }
  const float mean = s * (1.f / 1024.f);
  const float var = fmaxf(fmaf(-mean, mean, q * (1.f / 1024.f)), 0.f);
  reinterpret_cast<float2*>(sm + kSmStat)[r] = make_float2(rsqrtf(var + eps), -mean);
}

__device__ __forceinline__ void gather_colsums_qkv(uint8_t* sm, int tq, int j, int lane, unsigned epoch) {
  const uint2* src = reinterpret_cast<const uint2*>(g_cs + (j + 8 * tq) * 64) + lane;
  uint2 v[3], u[3];
  unsigned diff, spins = 0;
#pragma unroll 1
  do {
    if (++spins > kSpinLimit) __trap();
    diff = 0;
#pragma unroll
    for (int q = 0; q < 3; q++) {
      v[q] = ld_relaxed_pair(src + q * (kD / 2));
      u[q] = make_uint2(epoch & 7u, epoch & 7u);
      if (tq) u[q] = ld_relaxed_pair(src + (q * kD + 3 * kD + kF) / 2);
    }
#pragma unroll
    for (int q = 0; q < 3; q++) diff |= (v[q].x ^ epoch) | (v[q].y ^ epoch) | (u[q].x ^ epoch) | (u[q].y ^ epoch);
  } while (__any_sync(0xffffffffu, diff & 7u));
#pragma unroll
  for (int q = 0; q < 3; q++)
    reinterpret_cast<float2*>(sm + kSmCsQ)[tq * 96 + q * 32 + lane] =
        make_float2(untag_value(v[q].x) + untag_value(u[q].x), untag_value(v[q].y) + untag_value(u[q].y));
}

__device__ __forceinline__ void gather_colsums_w1(uint8_t* sm, const __nv_bfloat16* b1, int j, int lane,
                                                  unsigned epoch) {
#pragma unroll 1
  for (int blk = 0; blk < 7; blk++) {
    const int pair = 32 * (blk + (blk < 3 ? 3 * j : blk < 5 ? 21 + 2 * j : 35 + 2 * j)) + lane;
    const uint32_t bias = reinterpret_cast<const uint32_t*>(b1)[pair];
    uint2 v;
    unsigned spins = 0;
#pragma unroll 1
    do {
      if (++spins > kSpinLimit) __trap();
      v = ld_relaxed_pair(reinterpret_cast<const uint2*>(g_cs + 3 * kD) + pair);
    } while (__any_sync(0xffffffffu, ((v.x ^ epoch) | (v.y ^ epoch)) & 7u));
    reinterpret_cast<float4*>(sm + kSmV1)[blk * 32 + lane] =
        make_float4(untag_value(v.x), untag_value(v.y), kGeluBeta * bf_lo(bias), kGeluBeta * bf_hi(bias));
  }
}

#define PAUSE_QKV2 7
#define PAUSE_WO 2

__global__ void __cluster_dims__(2, 1, 1) __launch_bounds__(384, 1)
fused_layers_kernel(const __grid_constant__ CUtensorMap map_x, const __grid_constant__ CUtensorMap map_out,
                    const __grid_constant__ CUtensorMap map_qkv, const __grid_constant__ CUtensorMap map_wo,
                    const __grid_constant__ CUtensorMap map_w1a, const __grid_constant__ CUtensorMap map_w1b,
                    const __grid_constant__ CUtensorMap map_w2, const __grid_constant__ CUtensorMap map_csq,
                    const __grid_constant__ CUtensorMap map_cs1, const __grid_constant__ CUtensorMap map_css,
                    const __grid_constant__ Params prm) {
  extern __shared__ __align__(1024) uint8_t sm[];
  if (threadIdx.x < 128 && blockIdx.x < kCtas) TRACE_AT(15, 1);
  const uint32_t sb = __shfl_sync(0xffffffffu, smem_u32(sm), 0);
  const int warp = __shfl_sync(0xffffffffu, threadIdx.x >> 5, 0), lane = threadIdx.x & 31;
  const int cta = blockIdx.x, rank = cta & 1, cl = cta >> 1;
  const int grp = cl < 4 ? 0 : cl < 36 ? (cl - 4) & 7 : 1 + (cl - 36) % 7;
  const int j = cl < 4 ? 4 + cl : cl < 36 ? (cl - 4) >> 3 : 4 + (cl - 36) / 7;
  const int b = 2 * grp + rank;
  const int xcol = (b >> 3) * kD, xrow = (b & 7) * 128;

  if (cta >= kCtas) {
    helper_cta(&map_csq, &map_cs1, sm, sb, cta - kCtas, warp);
    return;
  }
  if ((warp < 8 || warp == 9) && elect()) {
    if (warp == 9) {
#pragma unroll
      for (int s = 0; s < 8; s++) mbar_init(sb + kBarFull + s * 8, 1);
      fence_async_smem();
#pragma unroll 1
      for (int s = 0; s < 4; s++) {
        const uint32_t full = sb + kBarFull + s * 8, dst = sb + kSmRing + s * 40960;
        mbar_expect_tx(full, 40960);
        tma2d(dst, &map_x, full, xcol + (s & 1) * 64, xrow);
        tma3d(dst + kTileBytes, &map_qkv, full, (j + 4 * (s & 2)) * 64, (s & 1) * 64, 0);
        tma3d(dst + kTileBytes + 12288, &map_qkv, full, (j + 4 * (s & 2)) * 64, (s & 1) * 64 + 32, 0);
      }
    } else {
      if (sb & 1023) __trap();
#pragma unroll
      for (int s = 0; s < 16; s++) mbar_init(sb + kBarTurn + warp * 128 + s * 8, warp < 5 ? 1 : warp == 5 ? 2 : 4);
    }
    asm volatile("fence.mbarrier_init.release.cluster;" ::: "memory");
  }
  __syncwarp();
  asm volatile("barrier.cluster.arrive.relaxed.aligned;" ::: "memory");

  if (warp >= 8) {
    asm volatile("setmaxnreg.dec.sync.aligned.u32 40;");
    if (warp < 10) {
      asm volatile("barrier.cluster.wait.aligned;" ::: "memory");
      uint32_t nb = 32, off = 0, kb = 0;
#define RING_STEP(WAIT, ISSUE)                                            \
  do {                                                                    \
    const uint32_t mb = nb - depth, full = sb + kBarFull + (nb & 56);     \
    if (kb == skip) kb += inc;                                            \
    mbar_wait(sb + kBarEmpty + (mb & 56), mb >> 6);                       \
    WAIT;                                                                 \
    if (elect()) { ISSUE; }                                               \
    TRACE_ISSUE(9 - warp, nb);                                            \
    kb += inc;                                                            \
    off = off == wrap ? 0 : off + step;                                   \
    nb += 8;                                                              \
  } while (nb != nend)
#pragma unroll 1
      for (int sg = 0; sg < kSegs; sg++) {
        const uint32_t e = prm.seg[sg];
        const int ty = e & 7, mode = (e >> 15) & 3, reset = (e >> 24) & 3;
        const uint32_t nend = nb + (e & 0x1f8);
        const uint32_t step = (e >> 17) & 1 ? 40960 : 32768, wrap = 163840 - step;
        const uint32_t depth = (e >> 18) & 1 ? 40 : 32;
        if (reset) off = reset == 1 ? 0 : reset == 2 ? 40960 : 131072;
        const uint32_t own = ty == 2 ? 8 + j : 2 * j;
        if (mode != kModeContinue) kb = ((e >> 9) & 63) + (mode == kModeHead ? own : 0);
        const uint32_t inc = mode >= kModeSkip && ty != 2 ? 2 : 1, skip = mode >= kModeSkip ? own + (kb & 1) : 255;
        if (warp == 8) {
          const CUtensorMap* map = ty < 2 ? &map_qkv : ty == 2 ? &map_wo : ty == 3 ? &map_w1a : ty < 6 ? &map_w1b : &map_w2;
          const int c0 = ty < 2 ? (j + 8 * ty) * 64 : 0;
          const int c2 = ty < 2 ? 0 : ty == 3 ? 3 * j : ty == 4 ? 24 + 2 * j : ty == 5 ? 40 + 2 * j : 2 * j;
          const uint32_t half = (ty < 2 || ty == 3) ? 12288 : 8192;
          const uint32_t bytes = 2 * half + (mode == kModeHead ? 0 : kTileBytes);
          const uint32_t dst = sb + kSmRing + (mode == kModeHead && ty != 2 ? 0 : kTileBytes) + rank * half;
          if (e >> 26) {
            const bool second = (grp & 6) == 2;
            const int pk = grp < 4 ? 2 * j + (grp & 1) : 2 * (grp - 4 + (grp - 4 >= j));
            const CUtensorMap* pm = ty == 6 ? &map_qkv : second ? &map_w1b : &map_w1a;
            if (elect())
              asm volatile("cp.async.bulk.prefetch.tensor.3d.L2.global [%0, {%1, %2, %3}];" ::"l"(pm),
                           "r"(ty == 6 ? (j + 8 * second) * 64 : 0), "r"(pk * 64 + rank * 32),
                           "r"(ty == 6 ? 0 : second ? 24 + 2 * j : 3 * j) : "memory");
          }
          if (ty == 2 && mode == kModeHead) mbar_wait(sb + kBarEpi + ((e >> 19) & 31) * 8, 0);
#pragma unroll 1
          RING_STEP(, mbar_expect_tx(full, bytes); tma3d_mc(dst + off, map, full, c0, kb * 64 + rank * 32, c2));
        } else if (mode == kModeHead) {
          off += ((nend - nb) >> 3) * step;
          nb = nend;
          if (off >= 163840) off -= 163840;
        } else if (sg < 2) {
#pragma unroll 1
          RING_STEP(, tma2d(sb + kSmRing + off, &map_x, full, xcol + kb * 64, xrow));
        } else {
          const uint8_t* src = ty == 6 ? g_h + b * 56 * kTileBytes : (ty == 2 ? g_o : g_x) + b * 16 * kTileBytes;
          const int dep = (e >> 19) & 31;
          if (dep < 28) mbar_wait(sb + kBarReady + dep * 8, 0);
          if ((dep & 30) == 28) {
#pragma unroll 1
            RING_STEP(mbar_wait(sb + kBarSrc + ((kb << (4 - inc)) & 56), dep),
                      bulk_load(sb + kSmRing + off, src + kb * kTileBytes, kTileBytes, full));
          } else {
#pragma unroll 1
            RING_STEP(, bulk_load(sb + kSmRing + off, src + kb * kTileBytes, kTileBytes, full));
          }
        }
      }
#undef RING_STEP
    } else {
      unsigned epoch = 0;
      if (warp == 10) {
        if (lane == 0) epoch = atomicAdd(&g_ticket, 1u) / kGrid + 1;
        *reinterpret_cast<unsigned*>(sm + kSmEpoch) = __shfl_sync(0xffffffffu, epoch, 0);
        asm volatile("barrier.cluster.wait.aligned;" ::: "memory");
        if (elect()) mbar_arrive(sb + kBarEpoch);
      } else {
        asm volatile("barrier.cluster.wait.aligned;" ::: "memory");
        mbar_wait_bounded(sb + kBarFull, 0);
        if (elect()) {
          mbar_expect_tx(sb + kBarInit, 32768);
          tma2d(sb + kSmX, &map_x, sb + kBarInit, xcol + j * 128, xrow);
          tma2d(sb + kSmX + kTileBytes, &map_x, sb + kBarInit, xcol + j * 128 + 64, xrow);
        }
        const uint2 u = reinterpret_cast<const uint2*>(prm.b2)[32 * j + lane];
        reinterpret_cast<float4*>(sm + kSmB2)[lane] = make_float4(
            kHScale * bf_lo(u.x), kHScale * bf_hi(u.x), kHScale * bf_lo(u.y), kHScale * bf_hi(u.y));
      }
      mbar_wait_bounded(sb + kBarEpoch, 0);
      epoch = *reinterpret_cast<volatile unsigned*>(sm + kSmEpoch);
      if (cta < 96) {
        mbar_wait_bounded(sb + kBarInit, 0);
        colsum_strip(&map_css, sm, sb, (cta >> 5) * kD + 512 + (cta & 31) * 16, warp - 10, lane, epoch);
      }
      gather_colsums_qkv(sm, 11 - warp, j, lane, epoch);
      __syncwarp();
      if (elect()) mbar_arrive(sb + kBarCs + (11 - warp) * 8);
     if (warp == 10) {
#pragma unroll 1
      for (int i = 0; i < kTiles - 1; i++) {
        const bool xt = i == 2 || i == 6 || i == 9;
        const unsigned* line = g_flag + (i * 16 + b) * 32;
        mbar_wait(sb + (xt ? kBarX + (i >> 2) * 16 : kBarEpi + i * 8), 0);
        if (xt || i == 1 || i == 8) {
          unsigned todo = 0xff;
          do {
            const unsigned now = __ballot_sync(0xffffffffu, ld_relaxed(line + (lane & 7)) == epoch) & todo;
            if (now) {
              asm volatile("fence.acquire.gpu;\nfence.proxy.async.global;" ::: "memory");
              if ((now >> lane) & 1) mbar_arrive(sb + kBarSrc + lane * 8);
              todo ^= now;
            }
          } while (todo);
        } else {
          wait_flags(line + (lane & 7), epoch);
          if (elect()) mbar_arrive(sb + kBarReady + i * 8);
        }
        if (xt) {
          wait_flags(line + 8 + (lane & 7), epoch);
          if (elect()) mbar_arrive(sb + kBarReady + (14 + (i >> 2)) * 8);
        }
      }
     } else {
#pragma unroll 1
      for (int i = 0; i < kTiles - 1; i++) {
        if (i == 3) {
          gather_colsums_w1(sm, prm.b1, j, lane, epoch);
          __syncwarp();
          if (elect()) mbar_arrive(sb + kBarCs + 16);
        }
        const bool xt = i == 2 || i == 6 || i == 9;
#pragma unroll 1
        for (int h = 0; h < (xt ? 2 : 1); h++) {
          if (xt && h == 0) {
            mbar_wait_bounded(sb + kBarEpi + i * 8, 0);
            if (elect()) bulk_store(g_x + (b * 16 + 2 * j) * kTileBytes, sb + kSmX, kTileBytes / 2);
          }
          mbar_wait_bounded(sb + (xt ? kBarX + (i >> 2) * 16 + 8 * h : kBarEpi + i * 8), 0);
          const int ty = i >= 7 ? i - 7 : i;
          if (ty >= 2 && elect()) {
            uint8_t* dst = xt ? g_x + (b * 16 + 2 * j + h) * kTileBytes
                              : g_h + (b * 56 + 1 + (ty == 3 ? 3 * j : 16 * ty - 40 + 2 * j)) * kTileBytes;
            const int piece = (xt && h == 0) ? kTileBytes / 2 : kTileBytes / 4;
#pragma unroll 1
            for (int o = xt && h == 0 ? piece : 0; o < kTileBytes; o += piece) {
              bulk_store(dst + o, sb + (xt ? kSmX + h * kTileBytes : kSmStg) + o, piece);
              bulk_commit();
              bulk_wait();
            }
            if (!xt) mbar_arrive(sb + kBarFree + i * 8);
          }
          __syncwarp();
          if (elect()) st_release(&g_flag[(i * 16 + b) * 32 + h * 8 + j], epoch);
          __syncwarp();
        }
      }
#pragma unroll 1
      for (int q = 0; q < 4; q++) {
        if (!(q & 1)) mbar_wait_bounded(sb + kBarEpi + (kTiles - 1) * 8, q >> 1);
        else mbar_wait_bounded(sb + kBarX + 48 + 4 * (q & 2), 0);
        if (elect()) {
          tma2d_store(&map_out, sb + kSmX + q * 8192, xcol + j * 128 + (q >> 1) * 64, xrow + (q & 1) * 64);
          bulk_commit();
          if (q == 3) bulk_wait_read();
        }
      }
     }
    }
    __syncwarp();
    asm volatile("barrier.cluster.arrive.relaxed.aligned;\nbarrier.cluster.wait.aligned;" ::: "memory");
  } else {
    asm volatile("setmaxnreg.inc.sync.aligned.u32 232;");
    asm volatile("barrier.cluster.wait.aligned;" ::: "memory");
    const int wg = warp >> 2, w = warp & 3;
    const bool rel = (threadIdx.x & 95) == 0;
    const uint32_t rel_addr = mapa(sb + kBarEmpty, w & 1);
    if (wg == 1) TRACE_AT(15, 0);
#define EPOCH (*reinterpret_cast<volatile unsigned*>(sm + kSmEpoch))

#pragma unroll 1
    for (int i = wg; i < kTiles; i += 2) {
      const int layer = i >= 7, ty = i - 7 * layer;
      TRACE_AT(i, 15);
      float acc[2][96];
      if (ty == 2 || ty == 6) {
        const int lane = lane_id();
        const uint32_t xa = sb + kSmX + ((lane >> 4) * 8 + (lane & 7)) * 128 + (((2 * w + ((lane >> 3) & 1)) ^ (lane & 7)) << 4);
        const float up = ty == 6 ? kHScale / kXScale : layer ? 1.f / kXScale : 1.f;
        const float dn = ty == 2 ? kXScale : layer ? 1.f / kHScale : kXScale / kHScale;
#pragma unroll
        for (int h = 0; h < 2; h++) {
          const float* b2 = reinterpret_cast<const float*>(sm + kSmB2) + 64 * h + 16 * w + (lane >> 2);
          const float bias[2] = {ty == 6 ? b2[0] : 0.f, ty == 6 ? b2[8] : 0.f};
#pragma unroll
          for (int p = 0; p < 8; p++) {
            uint32_t r[4];
            ldsm4_t(xa + h * kTileBytes + p * 2048, r);
#pragma unroll
            for (int m = 0; m < 4; m++) {
              acc[h][8 * p + 2 * m] = fmaf(bf_lo(r[m]), up, bias[m & 1]);
              acc[h][8 * p + 2 * m + 1] = fmaf(bf_hi(r[m]), up, bias[m & 1]);
              asm volatile("" : "+f"(acc[h][8 * p + 2 * m]), "+f"(acc[h][8 * p + 2 * m + 1]));
            }
            yield_slot();
          }
        }
        auto stage = [&](int qt) {
          const int h = qt >> 1;
          if (qt == 1 || (qt == 3 && i == kTiles - 1)) {
            fence_async_smem();
            __syncwarp();
            if (lane == 0) mbar_arrive(sb + kBarEpi + i * 8);
          }
#pragma unroll
          for (int p = 4 * (qt & 1); p < 4 * (qt & 1) + 4; p++) {
            const float* a = &acc[h][8 * p];
            stsm4_t(xa + h * kTileBytes + p * 2048, pack2(a[0] * dn, a[1] * dn), pack2(a[2] * dn, a[3] * dn),
                    pack2(a[4] * dn, a[5] * dn), pack2(a[6] * dn, a[7] * dn));
            yield_slot();
          }
          if (qt & 1) {
            fence_async_smem();
            __syncwarp();
            if (elect()) mbar_arrive(sb + kBarX + (i >> 2) * 16 + 8 * h);
            TRACE_AT(i, 8 + h);
          }
        };
        mainloop<128, kResid>(acc, sb, i, layer * 152 + ty * 16, ty == 6 ? 4 : 0, ty == 6 ? 56 : 16,
                            ty == 2 ? PAUSE_WO : -1, 2 * layer + 1, rel_addr, rel, ty == 2 ? 8 : -1, stage);
        TRACE_AT(i, 2);
        stage(2);
        stage(3);
      } else {
        const int xver = 2 * layer + (ty >= 3);
        const uint32_t stg = sb + kSmStg + w * 4096;
        const float4* vec = reinterpret_cast<const float4*>(sm + kSmV1) + (ty == 3 ? 0 : 64 * ty - 160);
        int lane;
        uint8_t* hdst = g_h + (b * 56 + (ty == 3 ? 3 * j : 16 * ty - 40 + 2 * j)) * kTileBytes + w * 4096;
        float2 st[4];
        unsigned epoch;
        auto pre = [&] {
          lane = lane_id();
          if (ty < 4) mbar_wait(sb + (ty == 1 ? kBarEpi + (i - 1) * 8 : kBarStat + xver * 8), 0);
#pragma unroll
          for (int c = 0; c < 4; c++) st[c] = reinterpret_cast<const float2*>(sm + kSmStat)[32 * w + 8 * c + (lane >> 2)];
          epoch = EPOCH;
        };
        auto team_stats = [&] {
          uint2* stat = g_stat + (xver * 16 + b) * 1024;
          lane = lane_id();
          publish_stats(sb, stat + j * 128, w, lane, EPOCH);
          gather_stats(sm, stat, 32 * w + lane, xver ? 1e-5f * kXScale * kXScale : 1e-5f, EPOCH);
          __syncwarp();
          if (elect()) mbar_arrive(sb + kBarStat + xver * 8);
          TRACE_AT(i, 14);
        };
        if (ty < 4) {
          AttnRegs ar;
          auto odd = [&](int step) {
            if (step == 0) pre();
            else convert_odd(acc, st, ar, step, sm, sb + kBarHalo + (xver + ty) * 24,
                             g_halo + ((layer * 16 + b) * 16 + j + 8 * ty) * 256, (b & 7) != 7, epoch, w, lane);
          };
          head_blocks<192>(acc, sb, layer * 152 + (ty < 2 ? 2 * ty : 48), ty < 2 ? 2 * ty : 1, xver, rel_addr, rel);
          if (ty == 1) {
            if (i == 1) {
              mbar_wait(sb + kBarEpoch, 0);
              mbar_wait(sb + kBarInit, 0);
            }
            team_stats();
            epoch = 0;
#pragma unroll
            for (int c = 0; c < 4; c++) st[c] = reinterpret_cast<const float2*>(sm + kSmStat)[32 * w + 8 * c + (lane >> 2)];
          } else {
            mainloop<192, kPlain>(acc, sb, i, layer * 152 + (ty ? 52 : 4), ty ? 1 : 0, 14, -1, 0, rel_addr, rel, 0, pre);
            TRACE_AT(i, 2);
            if (ty == 3) goto wide_gelu;
          }
          if (layer == 0) mbar_wait(sb + kBarCs + ty * 8, 0);
          add_mean_term(acc, st, sm, ty, lane);
          if (ty == 1) {
            mainloop<192, kStagger>(acc, sb, i, layer * 152 + 18, 2, 14, PAUSE_QKV2, xver, rel_addr, rel, 0, odd);
            TRACE_AT(i, 2);
          } else {
            odd(1);
            odd(2);
            odd(3);
          }
          epilogue_attn(acc, st, ar, sm, sb, layer, ty, b, j, epoch, i, w, lane);
          TRACE_AT(i, 3);
          continue;
        wide_gelu:
          if (i == 3) mbar_wait(sb + kBarCs + 16, 0);
          scale_stats(st);
          fold_norm<16, 24>(acc, st, vec + (lane & 3));
          TRACE_AT(i, 11);
          gelu_chunk<2>(acc, stg, lane, nullptr, [] {});
          TRACE_AT(i, 12);
          fold_norm<0, 2>(acc, st, vec + (lane & 3));
          store_staged(hdst + 2 * kTileBytes, stg);
          fold_norm<2, 16>(acc, st, vec + (lane & 3));
        } else {
          if (ty == 4) {
            head_blocks<128>(acc, sb, layer * 152 + 50, 3, xver, rel_addr, rel);
            team_stats();
          } else {
            const uint32_t s0 = ((((sb & 0x3FFFF) + kSmRing) >> 4) | (1u << 16)) + 3 * 2048;
            mbar_wait(sb + kBarTurn + (i - 1) * 8, 0);
            mbar_wait(sb + kBarFull, layer * 19 + 10);
            TRACE_KB((layer * 152 + 80) * 8);
            mma_kblock<128, 2>(acc, s0, s0 + kToB);
          }
          mainloop<128, kPlain>(acc, sb, i, layer * 152 + 6 + 15 * ty, 4, ty + 10, -1, 0, rel_addr, rel, 0, pre,
                                ty == 5 ? 0 : 64);
          TRACE_AT(i, 2);
          if (i == 4) mbar_wait(sb + kBarCs + 16, 0);
          scale_stats(st);
          fold_norm<0, 16>(acc, st, vec + (lane & 3));
        }
        auto own_store_done = [] {
          if (elect()) bulk_wait();
          __syncwarp();
        };
        TRACE_AT(i, 8);
        gelu_chunk<0>(acc, stg, lane, nullptr, [&] {
          if (ty == 3) own_store_done();
          else mbar_wait(sb + kBarFree + (i - 1) * 8, 0);
        });
        TRACE_AT(i, 9);
        gelu_chunk<1>(acc, stg, lane, hdst, own_store_done);
        TRACE_AT(i, 10);
        fence_async_smem();
        __syncwarp();
        if (elect()) mbar_arrive(sb + kBarEpi + i * 8);
      }
      TRACE_AT(i, 3);
    }
#undef EPOCH
    asm volatile("barrier.cluster.arrive.relaxed.aligned;\nbarrier.cluster.wait.aligned;" ::: "memory");
    if (wg == 1) TRACE_AT(15, 2);
  }
}

void build_segments(uint32_t* seg) {
  int n = 0, fine = 0;
  auto per_source = [&] { return 28 + (fine++ & 1); };
  auto add = [&](int ty, int cnt, int kb0, int mode, int wide, int depth5, int dep, int reset) {
    seg[n++] = ty | cnt << 3 | kb0 << 9 | mode << 15 | wide << 17 | depth5 << 18 | dep << 19 | reset << 24;
  };
  for (int l = 0; l < 2; l++) {
    const int t = 7 * l;
    if (l == 0) {
      add(0, 14, 2, kModePlain, 1, 0, 31, 1);
      add(1, 14, 2, kModePlain, 1, 0, 31, 0);
    } else {
      add(0, 2, 0, kModeHead, 1, 1, 31, 1);
      add(1, 2, 0, kModeHead, 1, 0, 31, 0);
      add(0, 7, 0, kModeSkip, 1, 0, per_source(), 0);
      add(0, 7, 1, kModeSkip, 1, 0, 15, 0);
      add(1, 7, 0, kModeSkip, 1, 0, 31, 0);
      add(1, 7, 1, kModeSkip, 1, 0, 31, 0);
    }
    add(2, 4, 0, kModePlain, 0, 0, t, 1);
    add(2, 4, 4, kModePlain, 0, 1, 31, 4);
    add(2, 1, 0, kModeHead, 0, 1, t + 1, 0);
    add(2, 7, 8, kModeSkip, 0, 1, per_source(), 0);
    add(3, 1, 0, kModeHead, 1, 1, 31, 2);
    add(3, 1, 1, kModeHead, 1, 0, 31, 0);
    add(4, 2, 0, kModeHead, 1, 0, 31, 0);
    add(3, 7, 0, kModeSkip, 1, 0, per_source(), 0);
    add(3, 7, 1, kModeSkip, 1, 0, 14 + 2 * l, 0);
    add(4, 4, 0, kModeSkip, 0, 0, 31, 3);
    add(4, 3, 0, kModeContinue, 0, 1, 31, 0);
    add(4, 7, 1, kModeSkip, 0, 1, 31, 0);
    add(5, 16, 0, kModePlain, 0, 1, 31, 0);
    add(6, 24, 0, kModePlain, 0, 1, t + 3, 0);
    add(6, 16, 24, kModePlain, 0, 1, t + 4, 0);
    add(6, 16, 40, kModePlain, 0, 1, t + 5, l ? 0 : 4);
  }
}

typedef CUresult (*EncodeTiledFn)(CUtensorMap*, CUtensorMapDataType, cuuint32_t, void*, const cuuint64_t*,
                                  const cuuint64_t*, const cuuint32_t*, const cuuint32_t*, CUtensorMapInterleave,
                                  CUtensorMapSwizzle, CUtensorMapL2promotion, CUtensorMapFloatOOBfill);

CUtensorMap make_map(EncodeTiledFn enc, const void* p, int rank, const cuuint64_t* dims, const cuuint64_t* strides,
                     const cuuint32_t* box, CUtensorMapSwizzle swizzle = CU_TENSOR_MAP_SWIZZLE_128B,
                     CUtensorMapL2promotion promo = CU_TENSOR_MAP_L2_PROMOTION_L2_128B) {
  CUtensorMap m;
  const cuuint32_t es[5] = {1, 1, 1, 1, 1};
  enc(&m, CU_TENSOR_MAP_DATA_TYPE_BFLOAT16, rank, const_cast<void*>(p), dims, strides, box, es,
      CU_TENSOR_MAP_INTERLEAVE_NONE, swizzle, promo,
      CU_TENSOR_MAP_FLOAT_OOB_FILL_NONE);
  return m;
}

CUtensorMap weight_map(EncodeTiledFn enc, const void* p, int k, int n, int blocks) {
  const cuuint64_t dims[3] = {64, (cuuint64_t)k, (cuuint64_t)n / 64};
  const cuuint64_t strides[2] = {(cuuint64_t)n * 2, 128};
  const cuuint32_t box[3] = {64, 32, (cuuint32_t)blocks};
  return make_map(enc, p, 3, dims, strides, box, CU_TENSOR_MAP_SWIZZLE_128B, CU_TENSOR_MAP_L2_PROMOTION_L2_256B);
}

CUtensorMap slab_map(EncodeTiledFn enc, const void* p, int n, int cols, int rows) {
  const cuuint64_t dims[2] = {(cuuint64_t)n, kD};
  const cuuint64_t strides[1] = {(cuuint64_t)n * 2};
  const cuuint32_t box[2] = {(cuuint32_t)cols, (cuuint32_t)rows};
  return make_map(enc, p, 2, dims, strides, box, CU_TENSOR_MAP_SWIZZLE_NONE);
}

CUtensorMap token_map(EncodeTiledFn enc, const void* p, int rows) {
  const cuuint64_t dims[2] = {2 * kD, 1024};
  const cuuint64_t strides[1] = {4 * kD};
  const cuuint32_t box[2] = {64, (cuuint32_t)rows};
  return make_map(enc, p, 2, dims, strides, box);
}

}

extern "C" void kernel_launch(void* const* d_in, const int* in_sizes, int n_in, void* d_out, int out_size) {
  (void)in_sizes; (void)n_in; (void)out_size;
  static EncodeTiledFn enc = nullptr;
  if (!enc) {
    void* fn = nullptr;
    cudaDriverEntryPointQueryResult q;
    cudaGetDriverEntryPoint("cuTensorMapEncodeTiled", &fn, cudaEnableDefault, &q);
    enc = (EncodeTiledFn)fn;
    cudaFuncSetAttribute(fused_layers_kernel, cudaFuncAttributeMaxDynamicSharedMemorySize, kSmBytes);
  }
  Params prm;
  prm.b1 = (const __nv_bfloat16*)d_in[5];
  prm.b2 = (const __nv_bfloat16*)d_in[7];
  build_segments(prm.seg);
  const cuuint64_t qd[3] = {kD, kD, 3}, qs[2] = {3 * kD * 2, kD * 2};
  const cuuint32_t qb[3] = {64, 32, 3};
  const CUtensorMap map_x = token_map(enc, d_in[0], 128);
  const CUtensorMap map_out = token_map(enc, d_out, 64);
  const CUtensorMap map_qkv = make_map(enc, d_in[1], 3, qd, qs, qb);
  const CUtensorMap map_wo = weight_map(enc, d_in[2], kD, kD, 2);
  const CUtensorMap map_w1a = weight_map(enc, d_in[4], kD, kF, 3);
  const CUtensorMap map_w1b = weight_map(enc, d_in[4], kD, kF, 2);
  const CUtensorMap map_w2 = weight_map(enc, d_in[6], kF, kD, 2);
  fused_layers_kernel<<<kGrid, 384, kSmBytes>>>(map_x, map_out, map_qkv, map_wo, map_w1a, map_w1b, map_w2,
                                                slab_map(enc, d_in[1], 3 * kD, 128, 128), slab_map(enc, d_in[4], kF, 128, 128),
                                                slab_map(enc, d_in[1], 3 * kD, 16, 128), prm);
}
```

```cpp
#include <cuda.h>
#include <cuda_bf16.h>
#include <cuda_runtime.h>
#include <stdint.h>

namespace {

constexpr int kD = 1024;
constexpr int kF = 3584;
constexpr int kCtas = 128;
constexpr int kGrid = 132;
constexpr int kTiles = 14;
constexpr int kTileBytes = 16384;

constexpr int kSmRing = 0;
constexpr int kSmX = 163840;
constexpr int kSmStg = kSmX + 32768;
constexpr int kSmHalo = kSmStg + 16384;
constexpr int kSmCsQ = kSmHalo + 6144;
constexpr int kSmV1 = kSmCsQ + 384 * 4;
constexpr int kSmB2 = kSmV1 + 448 * 8;
constexpr int kSmStat = kSmB2 + 128 * 4;
constexpr int kSmBar = kSmStat + 128 * 8;
constexpr int kBarFull = kSmBar;
constexpr int kBarTurn = kBarFull + 8 * 8;
constexpr int kBarReady = kBarTurn + 14 * 8;
constexpr int kBarSrc = kBarReady + 17 * 8;
constexpr int kBarPause = kBarSrc + 8 * 8;
constexpr int kBarFree = kBarPause + 4 * 8;
constexpr int kBarCs = kBarFree + 14 * 8;
constexpr int kBarSlab = kBarCs + 3 * 8;
constexpr int kBarHalo = kBarSlab + 4 * 8;
constexpr int kBarInit = kBarHalo + 12 * 8;
constexpr int kBarEpoch = kBarInit + 8;
constexpr int kBarEmpty = kBarTurn + 5 * 128;
constexpr int kBarEpi = kBarEmpty + 128;
constexpr int kBarX = kBarEpi + 14 * 8;
constexpr int kBarStat = kBarX + 8 * 8;
constexpr int kBarResume = kBarStat + 4 * 8;
constexpr int kSmEpoch = kBarEpi + 2 * 128;
static_assert(kBarEpoch < kBarEmpty && kBarResume + 4 * 8 <= kSmEpoch, "barrier groups overflow");
constexpr int kSmBytes = kSmEpoch + 16 + 256;
constexpr int kSegs = 40;

constexpr int kFlagLines = kTiles * 16;

constexpr float kXScale = 1.f / 8.f;

constexpr unsigned kSpinLimit = 1u << 22;

__device__ __align__(1024) uint8_t g_x[16 * 16 * kTileBytes];
__device__ __align__(1024) uint8_t g_o[16 * 16 * kTileBytes];
__device__ __align__(1024) uint8_t g_h[16 * 56 * kTileBytes];
__device__ __align__(128) uint2 g_stat[4 * 16 * 128 * 8];
__device__ __align__(128) unsigned g_cs[3 * kD + kF + 3 * kD];
__device__ __align__(128) uint4 g_halo[2 * 16 * 16 * 256];
__device__ __align__(128) unsigned g_flag[kFlagLines * 32];
__device__ unsigned g_ticket;

#define TRACE_AT(tile, k)
#define TRACE_PUB(i, k, c)
#define TRACE_ISSUE(which, nb)

struct Params {
  const __nv_bfloat16* b1;
  const __nv_bfloat16* b2;
  uint32_t seg[kSegs];
};

__device__ __forceinline__ uint32_t smem_u32(const void* p) {
  return (uint32_t)__cvta_generic_to_shared(p);
}
__device__ __forceinline__ uint32_t mapa(uint32_t a, uint32_t cta) {
  uint32_t r;
  asm("mapa.shared::cluster.u32 %0, %1, %2;" : "=r"(r) : "r"(a), "r"(cta));
  return r;
}
__device__ __forceinline__ void mbar_init(uint32_t bar, int cnt) {
  asm volatile("mbarrier.init.shared::cta.b64 [%0], %1;" ::"r"(bar), "r"(cnt) : "memory");
}
__device__ __forceinline__ void mbar_expect_tx(uint32_t bar, uint32_t bytes) {
  asm volatile("mbarrier.arrive.expect_tx.shared::cta.b64 _, [%0], %1;" ::"r"(bar), "r"(bytes) : "memory");
}
__device__ __forceinline__ void mbar_arrive(uint32_t bar) {
  asm volatile("mbarrier.arrive.shared::cta.b64 _, [%0];" ::"r"(bar) : "memory");
}
__device__ __forceinline__ void mbar_arrive_cluster(uint32_t cluster_addr) {
  asm volatile("mbarrier.arrive.shared::cluster.b64 _, [%0];" ::"r"(cluster_addr) : "memory");
}
__device__ __forceinline__ void mbar_wait(uint32_t bar, uint32_t parity) {
  asm volatile("{\n.reg .pred p;\nRETRY:\nmbarrier.try_wait.parity.shared::cta.b64 p, [%0], %1;\n"
               "@!p bra.uni RETRY;\n}" ::"r"(bar), "r"(parity) : "memory");
}
__device__ __forceinline__ void mbar_wait_bounded(uint32_t bar, uint32_t parity) {
  asm volatile("{\n.reg .pred p;\n.reg .u32 c;\nmov.u32 c, 0;\nRETRY:\n"
               "mbarrier.try_wait.parity.shared::cta.b64 p, [%0], %1;\n@p bra.uni DONE;\n"
               "add.u32 c, c, 1;\nsetp.lt.u32 p, c, %2;\n@p bra.uni RETRY;\ntrap;\nDONE:\n}"
               ::"r"(bar), "r"(parity), "n"(1u << 19) : "memory");
}
__device__ __forceinline__ void tma3d(uint32_t dst, const CUtensorMap* m, uint32_t bar, int c0, int c1, int c2) {
  asm volatile(
      "cp.async.bulk.tensor.3d.shared::cluster.global.mbarrier::complete_tx::bytes [%0], [%1, {%3, %4, %5}], [%2];"
      ::"r"(dst), "l"(m), "r"(bar), "r"(c0), "r"(c1), "r"(c2) : "memory");
}
__device__ __forceinline__ void tma3d_mc(uint32_t dst, const CUtensorMap* m, uint32_t bar, int c0, int c1, int c2) {
  asm volatile(
      "cp.async.bulk.tensor.3d.shared::cluster.global.mbarrier::complete_tx::bytes.multicast::cluster"
      " [%0], [%1, {%3, %4, %5}], [%2], %6;"
      ::"r"(dst), "l"(m), "r"(bar), "r"(c0), "r"(c1), "r"(c2), "h"((uint16_t)3) : "memory");
}
__device__ __forceinline__ void tma2d(uint32_t dst, const CUtensorMap* m, uint32_t bar, int c0, int c1) {
  asm volatile(
      "cp.async.bulk.tensor.2d.shared::cluster.global.mbarrier::complete_tx::bytes [%0], [%1, {%3, %4}], [%2];"
      ::"r"(dst), "l"(m), "r"(bar), "r"(c0), "r"(c1) : "memory");
}
__device__ __forceinline__ void tma2d_store(const CUtensorMap* m, uint32_t src, int c0, int c1) {
  asm volatile("cp.async.bulk.tensor.2d.global.shared::cta.bulk_group [%0, {%2, %3}], [%1];"
               ::"l"(m), "r"(src), "r"(c0), "r"(c1) : "memory");
}
__device__ __forceinline__ int lane_id() {
  int l;
  asm volatile("mov.u32 %0, %%laneid;" : "=r"(l));
  return l;
}
__device__ __forceinline__ bool elect() {
  uint32_t p;
  asm volatile("{\n.reg .pred p;\nelect.sync _|p, 0xffffffff;\nselp.b32 %0, 1, 0, p;\n}" : "=r"(p));
  return p;
}
__device__ __forceinline__ void bulk_load(uint32_t dst, const void* src, uint32_t bytes, uint32_t bar) {
  asm volatile("cp.async.bulk.shared::cluster.global.mbarrier::complete_tx::bytes [%0], [%1], %2, [%3];"
               ::"r"(dst), "l"(src), "r"(bytes), "r"(bar) : "memory");
}
__device__ __forceinline__ void bulk_store(void* dst, uint32_t src, uint32_t bytes) {
  asm volatile("cp.async.bulk.global.shared::cta.bulk_group [%0], [%1], %2;" ::"l"(dst), "r"(src), "r"(bytes)
               : "memory");
}
__device__ __forceinline__ void bulk_commit() { asm volatile("cp.async.bulk.commit_group;" ::: "memory"); }
__device__ __forceinline__ void bulk_wait_read() { asm volatile("cp.async.bulk.wait_group.read 0;" ::: "memory"); }
__device__ __forceinline__ void bulk_wait() { asm volatile("cp.async.bulk.wait_group 0;" ::: "memory"); }
__device__ __forceinline__ void fence_async_smem() { asm volatile("fence.proxy.async.shared::cta;" ::: "memory"); }
__device__ __forceinline__ unsigned ld_relaxed(const unsigned* p) {
  unsigned v;
  asm volatile("ld.relaxed.gpu.global.u32 %0, [%1];" : "=r"(v) : "l"(p) : "memory");
  return v;
}
__device__ __forceinline__ uint2 ld_relaxed64(const uint2* p) {
  uint2 v;
  asm volatile("{\n.reg .b64 t;\nld.relaxed.gpu.global.b64 t, [%2];\nmov.b64 {%0, %1}, t;\n}"
               : "=r"(v.x), "=r"(v.y) : "l"(p) : "memory");
  return v;
}
__device__ __forceinline__ void st_relaxed(unsigned* p, unsigned v) {
  asm volatile("st.relaxed.gpu.global.u32 [%0], %1;" ::"l"(p), "r"(v) : "memory");
}
__device__ __forceinline__ void st_release(unsigned* p, unsigned v) {
  asm volatile("st.release.gpu.global.u32 [%0], %1;" ::"l"(p), "r"(v) : "memory");
}
__device__ __forceinline__ void wait_flags(const unsigned* p, unsigned epoch) {
  while (__any_sync(0xffffffffu, ld_relaxed(p) != epoch)) {
    __nanosleep(400);
  }
  asm volatile("fence.acquire.gpu;\nfence.proxy.async.global;" ::: "memory");
  __syncwarp();
}
__device__ __forceinline__ void st_packet(uint4* p, uint32_t d0, uint32_t d1, uint32_t tag) {
  asm volatile("{\n.reg .b128 v;\n.reg .b64 x, y;\nmov.b64 x, {%1, %2};\nmov.b64 y, {%3, %3};\nmov.b128 v, {x, y};\n"
               "st.relaxed.gpu.global.b128 [%0], v;\n}" ::"l"(p), "r"(d0), "r"(d1), "r"(tag) : "memory");
}
__device__ __forceinline__ void ld_packet(const uint4* p, uint32_t& d0, uint32_t& d1, uint32_t& tag) {
  asm volatile("{\n.reg .b128 v;\n.reg .b64 x, y;\n.reg .b32 u;\nld.relaxed.gpu.global.b128 v, [%3];\n"
               "mov.b128 {x, y}, v;\nmov.b64 {%0, %1}, x;\nmov.b64 {%2, u}, y;\n}"
               : "=r"(d0), "=r"(d1), "=r"(tag) : "l"(p) : "memory");
}
__device__ __forceinline__ uint2 ld_relaxed_pair(const uint2* p) {
  uint2 v;
  asm volatile("ld.relaxed.gpu.global.v2.u32 {%0, %1}, [%2];" : "=r"(v.x), "=r"(v.y) : "l"(p) : "memory");
  return v;
}
__device__ __forceinline__ unsigned tag_value(float v, unsigned epoch) {
  return (__float_as_uint(v) & ~7u) | (epoch & 7u);
}
__device__ __forceinline__ float untag_value(unsigned v) { return __uint_as_float(v & ~7u); }
__device__ __forceinline__ void stsm4(uint32_t a, uint32_t r0, uint32_t r1, uint32_t r2, uint32_t r3) {
  asm volatile("stmatrix.sync.aligned.m8n8.x4.shared.b16 [%0], {%1, %2, %3, %4};" ::"r"(a), "r"(r0), "r"(r1),
               "r"(r2), "r"(r3) : "memory");
}
__device__ __forceinline__ void stsm4_t(uint32_t a, uint32_t r0, uint32_t r1, uint32_t r2, uint32_t r3) {
  asm volatile("stmatrix.sync.aligned.m8n8.x4.trans.shared.b16 [%0], {%1, %2, %3, %4};" ::"r"(a), "r"(r0),
               "r"(r1), "r"(r2), "r"(r3) : "memory");
}
__device__ __forceinline__ uint32_t transpose8(uint32_t a) {
  uint32_t d;
  asm volatile("movmatrix.sync.aligned.m8n8.trans.b16 %0, %1;" : "=r"(d) : "r"(a));
  return d;
}
__device__ __forceinline__ void mma16816(float (&c)[4], uint32_t a0, uint32_t a1, uint32_t a2, uint32_t a3,
                                         uint32_t b0, uint32_t b1) {
  asm volatile("mma.sync.aligned.m16n8k16.row.col.f32.bf16.bf16.f32 {%0, %1, %2, %3}, {%4, %5, %6, %7}, {%8, %9}, "
               "{%0, %1, %2, %3};"
               : "+f"(c[0]), "+f"(c[1]), "+f"(c[2]), "+f"(c[3])
               : "r"(a0), "r"(a1), "r"(a2), "r"(a3), "r"(b0), "r"(b1));
}
__device__ __forceinline__ void mma1688(float (&c)[4], uint32_t a0, uint32_t a1, uint32_t b0) {
  asm volatile("mma.sync.aligned.m16n8k8.row.col.f32.bf16.bf16.f32 {%0, %1, %2, %3}, {%4, %5}, {%6}, {%0, %1, %2, %3};"
               : "+f"(c[0]), "+f"(c[1]), "+f"(c[2]), "+f"(c[3]) : "r"(a0), "r"(a1), "r"(b0));
}
__device__ __forceinline__ float shfl_xor(float v, int m) {
  float r;
  asm volatile("shfl.sync.bfly.b32 %0, %1, %2, 31, 0xffffffff;" : "=f"(r) : "f"(v), "r"(m));
  return r;
}
__device__ __forceinline__ float tanh_fast(float x) {
  float r;
  asm volatile("tanh.approx.f32 %0, %1;" : "=f"(r) : "f"(x));
  return r;
}
__device__ __forceinline__ void ldsm4(uint32_t a, uint32_t (&r)[4]) {
  asm volatile("ldmatrix.sync.aligned.m8n8.x4.shared.b16 {%0, %1, %2, %3}, [%4];"
               : "=r"(r[0]), "=r"(r[1]), "=r"(r[2]), "=r"(r[3]) : "r"(a) : "memory");
}
__device__ __forceinline__ void ldsm4_t(uint32_t a, uint32_t (&r)[4]) {
  asm volatile("ldmatrix.sync.aligned.m8n8.x4.trans.shared.b16 {%0, %1, %2, %3}, [%4];"
               : "=r"(r[0]), "=r"(r[1]), "=r"(r[2]), "=r"(r[3]) : "r"(a) : "memory");
}
__device__ __forceinline__ uint32_t pack2(float lo, float hi) {
  uint32_t r;
  asm volatile("cvt.rn.bf16x2.f32 %0, %1, %2;" : "=r"(r) : "f"(hi), "f"(lo));
  return r;
}
__device__ __forceinline__ float bf_lo(uint32_t r) { return __uint_as_float(r << 16); }
__device__ __forceinline__ float bf_hi(uint32_t r) { return __uint_as_float(r & 0xffff0000u); }
__device__ __forceinline__ float ex2(float x) {
  float r;
  asm("ex2.approx.ftz.f32 %0, %1;" : "=f"(r) : "f"(x));
  return r;
}
__device__ __forceinline__ float rcp(float x) {
  float r;
  asm("rcp.approx.ftz.f32 %0, %1;" : "=f"(r) : "f"(x));
  return r;
}
template <int N>
__device__ __forceinline__ void wg_wait() {
  asm volatile("wgmma.wait_group.sync.aligned %0;" ::"n"(N) : "memory");
}
__device__ __forceinline__ void yield_slot() { asm volatile("pmevent 0;"); }

template <int N, int KIND>
__device__ __forceinline__ void mma_kblock(float (&acc)[2][96], uint32_t a, uint32_t b);

#define F8(m, d, i) m(d[i]), m(d[i + 1]), m(d[i + 2]), m(d[i + 3]), m(d[i + 4]), m(d[i + 5]), m(d[i + 6]), m(d[i + 7])
#define KSTEP(N, A, B, oa0, oa1, ob, sd)                                                   \
  "mov.b64 db, {" B ", hb};\nadd.u64 db, db, " #ob ";\n"                                    \
  "mov.b64 da, {" A ", ha};\nadd.u64 da, da, " #oa0 ";\n"                                   \
  "wgmma.mma_async.sync.aligned.m64n" #N "k16.f32.bf16.bf16 {" ACC##N##_0 "}, da, db, " #sd ", 1, 1, 0, 1;\n" \
  "mov.b64 da, {" A ", ha};\nadd.u64 da, da, " #oa1 ";\n"                                   \
  "wgmma.mma_async.sync.aligned.m64n" #N "k16.f32.bf16.bf16 {" ACC##N##_1 "}, da, db, " #sd ", 1, 1, 0, 1;\n"

#define MMA_KBLOCK(N, KIND, A, B, ob2, ob3, sd, MID, MODE)                                 \
  template <>                                                                              \
  __device__ __forceinline__ void mma_kblock<N, KIND>(float (&acc)[2][96], uint32_t a, uint32_t b) { \
    asm volatile("{\n.reg .b32 ha, hb;\n.reg .b64 da, db;\n"                            \
                 "mov.b32 ha, 0x40000080;\nmov.b32 hb, 0x40000040;\n"                       \
                 "wgmma.fence.sync.aligned;\n"                                             \
                 KSTEP(N, A, B, 0, 64, 0, sd) KSTEP(N, A, B, 2, 66, 128, 1) MID               \
                 KSTEP(N, A, B, 4, 68, ob2, 1) KSTEP(N, A, B, 6, 70, ob3, 1) "wgmma.commit_group.sync.aligned;\n}\n"  \
                 : OPS##N(MODE) : "r"(a), "r"(b) : "memory");                              \
  }
#define MMA_KBLOCKS(N, A, B, ob2, ob3)                                                     \
  MMA_KBLOCK(N, 0, A, B, ob2, ob3, 1, "", "+f")                                            \
  MMA_KBLOCK(N, 1, A, B, ob2, ob3, 1, "wgmma.commit_group.sync.aligned;\n", "+f")          \
  MMA_KBLOCK(N, 2, A, B, ob2, ob3, 0, "", "=f")

#define ACC128_0 \
  "%0, %1, %2, %3, %4, %5, %6, %7, %8, %9, %10, %11, %12, %13, %14, %15, " \
  "%16, %17, %18, %19, %20, %21, %22, %23, %24, %25, %26, %27, %28, %29, %30, %31, " \
  "%32, %33, %34, %35, %36, %37, %38, %39, %40, %41, %42, %43, %44, %45, %46, %47, " \
  "%48, %49, %50, %51, %52, %53, %54, %55, %56, %57, %58, %59, %60, %61, %62, %63"
#define ACC128_1 \
  "%64, %65, %66, %67, %68, %69, %70, %71, %72, %73, %74, %75, %76, %77, %78, %79, " \
  "%80, %81, %82, %83, %84, %85, %86, %87, %88, %89, %90, %91, %92, %93, %94, %95, " \
  "%96, %97, %98, %99, %100, %101, %102, %103, %104, %105, %106, %107, %108, %109, %110, %111, " \
  "%112, %113, %114, %115, %116, %117, %118, %119, %120, %121, %122, %123, %124, %125, %126, %127"
#define OPS128(m) \
  F8(m, acc[0], 0), F8(m, acc[0], 8), F8(m, acc[0], 16), F8(m, acc[0], 24), F8(m, acc[0], 32), F8(m, acc[0], 40), F8(m, acc[0], 48), F8(m, acc[0], 56), \
        F8(m, acc[1], 0), F8(m, acc[1], 8), F8(m, acc[1], 16), F8(m, acc[1], 24), F8(m, acc[1], 32), F8(m, acc[1], 40), F8(m, acc[1], 48), F8(m, acc[1], 56)
MMA_KBLOCKS(128, "%128", "%129", 512, 640)

#define ACC192_0 \
  "%0, %1, %2, %3, %4, %5, %6, %7, %8, %9, %10, %11, %12, %13, %14, %15, " \
  "%16, %17, %18, %19, %20, %21, %22, %23, %24, %25, %26, %27, %28, %29, %30, %31, " \
  "%32, %33, %34, %35, %36, %37, %38, %39, %40, %41, %42, %43, %44, %45, %46, %47, " \
  "%48, %49, %50, %51, %52, %53, %54, %55, %56, %57, %58, %59, %60, %61, %62, %63, " \
  "%64, %65, %66, %67, %68, %69, %70, %71, %72, %73, %74, %75, %76, %77, %78, %79, " \
  "%80, %81, %82, %83, %84, %85, %86, %87, %88, %89, %90, %91, %92, %93, %94, %95"
#define ACC192_1 \
  "%96, %97, %98, %99, %100, %101, %102, %103, %104, %105, %106, %107, %108, %109, %110, %111, " \
  "%112, %113, %114, %115, %116, %117, %118, %119, %120, %121, %122, %123, %124, %125, %126, %127, " \
  "%128, %129, %130, %131, %132, %133, %134, %135, %136, %137, %138, %139, %140, %141, %142, %143, " \
  "%144, %145, %146, %147, %148, %149, %150, %151, %152, %153, %154, %155, %156, %157, %158, %159, " \
  "%160, %161, %162, %163, %164, %165, %166, %167, %168, %169, %170, %171, %172, %173, %174, %175, " \
  "%176, %177, %178, %179, %180, %181, %182, %183, %184, %185, %186, %187, %188, %189, %190, %191"
#define OPS192(m) \
  F8(m, acc[0], 0), F8(m, acc[0], 8), F8(m, acc[0], 16), F8(m, acc[0], 24), F8(m, acc[0], 32), F8(m, acc[0], 40), F8(m, acc[0], 48), F8(m, acc[0], 56), F8(m, acc[0], 64), F8(m, acc[0], 72), F8(m, acc[0], 80), F8(m, acc[0], 88), \
        F8(m, acc[1], 0), F8(m, acc[1], 8), F8(m, acc[1], 16), F8(m, acc[1], 24), F8(m, acc[1], 32), F8(m, acc[1], 40), F8(m, acc[1], 48), F8(m, acc[1], 56), F8(m, acc[1], 64), F8(m, acc[1], 72), F8(m, acc[1], 80), F8(m, acc[1], 88)
MMA_KBLOCKS(192, "%192", "%193", 768, 896)

#define HSTEP(oa, ob)                                                                       \
  "mov.b64 db, {%97, hb};\nadd.u64 db, db, " #ob ";\nmov.b64 da, {%96, ha};\nadd.u64 da, da, " #oa ";\n" \
  "wgmma.mma_async.sync.aligned.m64n192k16.f32.bf16.bf16 {" ACC192_0 "}, da, db, 1, 1, 1, 0, 1;\n"
__device__ __forceinline__ void mma_half(float (&d)[96], uint32_t a, uint32_t b) {
  asm volatile("{\n.reg .b32 ha, hb;\n.reg .b64 da, db;\nmov.b32 ha, 0x40000080;\nmov.b32 hb, 0x40000040;\n"
               "wgmma.fence.sync.aligned;\n" HSTEP(0, 0) HSTEP(2, 128) HSTEP(4, 768) HSTEP(6, 896)
               "wgmma.commit_group.sync.aligned;\n}\n"
               : F8("+f", d, 0), F8("+f", d, 8), F8("+f", d, 16), F8("+f", d, 24), F8("+f", d, 32), F8("+f", d, 40),
                 F8("+f", d, 48), F8("+f", d, 56), F8("+f", d, 64), F8("+f", d, 72), F8("+f", d, 80), F8("+f", d, 88)
               : "r"(a), "r"(b) : "memory");
}

#define TSTEP(REGS, W, X, ow, ox)                                                           \
  "mov.b64 db, {" X ", hi};\nadd.u64 db, db, " #ox ";\nmov.b64 da, {" W ", hi};\nadd.u64 da, da, " #ow ";\n" \
  "wgmma.mma_async.sync.aligned.m64n128k16.f32.bf16.bf16 {" REGS "}, da, db, 1, 1, 1, 1, 0;\n"
#define THEAD "{\n.reg .b32 hi;\n.reg .b64 da, db;\nmov.b32 hi, 0x40000040;\nwgmma.fence.sync.aligned;\n"
#define TTAIL "wgmma.commit_group.sync.aligned;\n}\n"
__device__ __forceinline__ void mma_kblock_t(float (&acc)[2][96], uint32_t wd, uint32_t xd) {
  asm volatile(THEAD TSTEP(ACC128_0, "%128", "%129", 0, 0) TSTEP(ACC128_1, "%128", "%129", 256, 0)
               TSTEP(ACC128_0, "%128", "%129", 128, 2) TSTEP(ACC128_1, "%128", "%129", 384, 2)
               TSTEP(ACC128_0, "%128", "%129", 512, 4) TSTEP(ACC128_1, "%128", "%129", 768, 4)
               TSTEP(ACC128_0, "%128", "%129", 640, 6) TSTEP(ACC128_1, "%128", "%129", 896, 6) TTAIL
               : OPS128("+f") : "r"(wd), "r"(xd) : "memory");
}
__device__ __forceinline__ void mma_half_t(float (&d)[96], uint32_t wd, uint32_t xd) {
  asm volatile(THEAD TSTEP(ACC128_0, "%64", "%65", 0, 0) TSTEP(ACC128_0, "%64", "%65", 128, 2)
               TSTEP(ACC128_0, "%64", "%65", 512, 4) TSTEP(ACC128_0, "%64", "%65", 640, 6) TTAIL
               : F8("+f", d, 0), F8("+f", d, 8), F8("+f", d, 16), F8("+f", d, 24), F8("+f", d, 32), F8("+f", d, 40),
                 F8("+f", d, 48), F8("+f", d, 56) : "r"(wd), "r"(xd) : "memory");
}

enum { kModePlain = 0, kModeHead = 1, kModeSkip = 2, kModeContinue = 3 };

template <int N>
__device__ __forceinline__ void fence_acc(float (&acc)[2][96]) {
#pragma unroll
  for (int h = 0; h < 2; h++)
#pragma unroll
    for (int i = 0; i < N / 2; i++) asm volatile("" : "+f"(acc[h][i])::"memory");
}

constexpr uint32_t kToB = (kTileBytes >> 4) + ((4096u >> 4) << 16) - (1u << 16);

#define TRACE_KB(nb)

template <int N>
__device__ __forceinline__ void head_blocks(float (&acc)[2][96], uint32_t sb, int n0, int slot, int xver,
                                            uint32_t rel_addr, bool rel) {
  const uint32_t ring = (((sb & 0x3FFFF) + kSmRing) >> 4) | (1u << 16);
  const uint32_t xdesc = (((sb & 0x3FFFF) + kSmX) >> 4) | (1u << 16);
  const uint32_t s0 = ring + slot * 2560, s1 = ring + ((slot + 1) & 3) * 2560;
  const uint32_t to_b = xver > 0 ? kToB - (kTileBytes >> 4) : kToB;
  const uint32_t nb = n0 * 8, xbar = sb + kBarX + (xver - 1) * 16;
  if (xver > 0) {
    mbar_wait(xbar, 0);
    mbar_wait(sb + kBarTurn + (xver == 1 ? 2 : 3 * xver) * 8, 0);
  }
  mbar_wait(sb + kBarFull + (nb & 56), nb >> 6);
  if (n0 == 0) TRACE_AT(0, 1);
  TRACE_KB(nb);
  mma_kblock<N, 2>(acc, xver > 0 ? xdesc : s0, s0 + to_b);
  if (xver > 0) mbar_wait(xbar + 8, 0);
  mbar_wait(sb + kBarFull + (nb & 56) + 8, nb >> 6);
  TRACE_KB(nb + 8);
  mma_kblock<N, 0>(acc, xver > 0 ? xdesc + (kTileBytes >> 4) : s1, s1 + to_b);
  wg_wait<1>();
  if (rel) mbar_arrive_cluster(rel_addr + (nb & 56));
  wg_wait<0>();
  if (rel) mbar_arrive_cluster(rel_addr + (nb & 56) + 8);
  fence_acc<N>(acc);
}

enum { kPlain, kResid, kStagger };
template <int N, int KIND, class Pre>
__device__ __forceinline__ void mainloop(float (&acc)[2][96], uint32_t sb, int tile, int n0, int slot, int nkb,
                                         int pause_kk, int att, uint32_t rel_addr, bool rel, int own_kk, Pre pre,
                                         uint32_t prev = 64) {
  constexpr bool RESID = KIND == kResid;
  constexpr uint32_t kStep = (N == 192 ? 5 : 4) * 512;
  const uint32_t ring = (((sb & 0x3FFFF) + kSmRing) >> 4) | (1u << 16);
  uint32_t st = ring + slot * kStep;
  uint32_t nb = n0 * 8;
  const uint32_t last = nb + 8 * (nkb - (RESID ? 4 : KIND == kStagger ? 2 : 1)), own = nb + 8 * own_kk;
  const uint32_t stg = (((sb & 0x3FFFF) + kSmStg) >> 4) | (1u << 16);
  uint32_t stop = pause_kk >= 0 ? nb + 8 * pause_kk : last;
  const bool signal = (threadIdx.x & 127) == 64;
  fence_acc<N>(acc);
  if (tile > 0) mbar_wait(sb + kBarTurn + (tile - 1) * 8, 0);
  TRACE_AT(tile, 0);
#pragma unroll 1
  while (true) {
#pragma unroll 1
    do {
      mbar_wait(sb + kBarFull + (nb & 56), nb >> 6);
      TRACE_KB(nb);
      if constexpr (RESID) mma_kblock_t(acc, st + kToB, nb == own ? stg : st);
      else mma_kblock<N, 0>(acc, st, st + kToB);
      wg_wait<1>();
      if (rel) mbar_arrive_cluster(rel_addr + prev);
      prev = nb & 56;
      st += kStep;
      if (st == ring + 10240) st = ring;
      nb += 8;
    } while (nb != stop);
    if (stop == last) break;
    stop = last;
    if (signal) mbar_arrive(sb + kBarPause + att * 8);
    wg_wait<0>();
    if (rel) mbar_arrive_cluster(rel_addr + prev);
    prev = 64;
    mbar_wait(sb + kBarResume + att * 8, 0);
  }
  mbar_wait(sb + kBarFull + (nb & 56), nb >> 6);
  TRACE_KB(nb);
  if constexpr (RESID) {
    const uint32_t z = gridDim.y - 1;
    const uint32_t s1 = st + kStep, s2 = s1 + kStep, s3 = s2 == ring + 8192 ? ring : s2 + kStep;
    mma_half_t(acc[0], st + kToB, st);
    wg_wait<1>();
    if (rel) mbar_arrive_cluster(rel_addr + 24);
    mbar_wait(sb + kBarFull + 40, nb >> 6);
    TRACE_KB(nb + 8);
    mma_half_t(acc[0], s1 + kToB, s1);
    mbar_wait(sb + kBarFull + 48, nb >> 6);
    TRACE_KB(nb + 16);
    mma_half_t(acc[0], s2 + kToB, s2);
    mbar_wait(sb + kBarFull + 56, nb >> 6);
    TRACE_KB(nb + 24);
    mma_half_t(acc[0], s3 + kToB, s3);
    mma_half_t(acc[1], st + kToB + 256, st + z);
    mma_half_t(acc[1], s1 + kToB + 256, s1 + z);
    wg_wait<2>();
#pragma unroll
    for (int i = 0; i < 64; i++) asm volatile("" : "+f"(acc[0][i])::"memory");
    pre(0);
    mma_half_t(acc[1], s2 + kToB + 256, s2 + z);
    wg_wait<2>();
    if (rel) mbar_arrive_cluster(rel_addr + 32);
    pre(1);
    mma_half_t(acc[1], s3 + kToB + 256, s3 + z);
    wg_wait<2>();
    if (rel) mbar_arrive_cluster(rel_addr + 40);
    wg_wait<1>();
    if (signal) mbar_arrive(sb + kBarTurn + tile * 8);
    if (rel) mbar_arrive_cluster(rel_addr + 48);
    wg_wait<0>();
    if (rel) mbar_arrive_cluster(rel_addr + 56);
#pragma unroll
    for (int i = 0; i < 64; i++) asm volatile("" : "+f"(acc[1][i])::"memory");
  } else if constexpr (KIND == kStagger) {
    const uint32_t z = gridDim.y - 1, s2 = st + kStep;
    mma_half(acc[1], st + 64, st + kToB);
    wg_wait<1>();
    if (rel) mbar_arrive_cluster(rel_addr + 40);
    mbar_wait(sb + kBarFull + 56, nb >> 6);
    TRACE_KB(nb + 8);
    mma_half(acc[1], s2 + 64, s2 + kToB);
    mma_half(acc[0], st, st + z + kToB);
    pre(0);
    mma_half(acc[0], s2, s2 + z + kToB);
    wg_wait<2>();
#pragma unroll
    for (int i = 0; i < 96; i++) asm volatile("" : "+f"(acc[1][i])::"memory");
    pre(1);
    wg_wait<1>();
    if (rel) mbar_arrive_cluster(rel_addr + 48);
    pre(2);
    if (signal) mbar_arrive(sb + kBarTurn + tile * 8);
    pre(3);
    wg_wait<0>();
    if (rel) mbar_arrive_cluster(rel_addr + 56);
#pragma unroll
    for (int i = 0; i < 96; i++) asm volatile("" : "+f"(acc[0][i])::"memory");
  } else {
    mma_kblock<N, 1>(acc, st, st + kToB);
    wg_wait<2>();
    if (rel) mbar_arrive_cluster(rel_addr + prev);
    pre();
    wg_wait<1>();
    if (signal) mbar_arrive(sb + kBarTurn + tile * 8);
    wg_wait<0>();
    if (rel) mbar_arrive_cluster(rel_addr + (nb & 56));
    fence_acc<N>(acc);
  }
}

__device__ __forceinline__ void publish_stats(uint32_t sb, uint2* stat, int w, int lane, unsigned epoch) {
  const uint32_t row = sb + kSmX + (32 * w + lane) * 128;
  float s[4], q[4];
#pragma unroll
  for (int c = 0; c < 4; c++) s[c] = q[c] = 0.f;
  uint32_t nx[4];
  ldsm4(row + ((lane & 7) << 4), nx);
#pragma unroll 1
  for (int J = 1; J <= 16; J++) {
    const uint32_t r[4] = {nx[0], nx[1], nx[2], nx[3]};
    ldsm4(row + ((J >> 3) & 1) * kTileBytes + (((J ^ lane) & 7) << 4), nx);
#pragma unroll
    for (int c = 0; c < 4; c++) {
      const float lo = bf_lo(r[c]);
      s[c] += lo;
      q[c] = fmaf(lo, lo, q[c]);
      if (c & 1) yield_slot();
    }
#pragma unroll
    for (int c = 0; c < 4; c++) {
      const float hi = bf_hi(r[c]);
      s[c] += hi;
      q[c] = fmaf(hi, hi, q[c]);
      if (c & 1) yield_slot();
    }
  }
  const int t = lane & 3, g = lane >> 2;
#pragma unroll
  for (int c = 0; c < 2; c++) {
    s[c] = (t & 2 ? s[c + 2] : s[c]) + shfl_xor(t & 2 ? s[c] : s[c + 2], 2);
    q[c] = (t & 2 ? q[c + 2] : q[c]) + shfl_xor(t & 2 ? q[c] : q[c + 2], 2);
  }
  const float so = (t & 1 ? s[1] : s[0]) + shfl_xor(t & 1 ? s[0] : s[1], 1);
  const float qo = (t & 1 ? q[1] : q[0]) + shfl_xor(t & 1 ? q[0] : q[1], 1);
  asm volatile("{\n.reg .b64 t;\nmov.b64 t, {%1, %2};\nst.relaxed.gpu.global.b64 [%0], t;\n}" ::"l"(stat + 32 * w + 8 * t + g),
               "r"(tag_value(so, epoch)), "r"(__float_as_uint(qo)) : "memory");
}

__device__ __forceinline__ void add_chunk(float (&a)[8], const uint4& v) {
  a[0] += bf_lo(v.x); a[1] += bf_hi(v.x);
  a[2] += bf_lo(v.y); a[3] += bf_hi(v.y);
  a[4] += bf_lo(v.z); a[5] += bf_hi(v.z);
  a[6] += bf_lo(v.w); a[7] += bf_hi(v.w);
}

__device__ __forceinline__ int helper_col(int id, int slab) {
  return (slab < 3 ? slab * kD : (slab - 3) * 512) + id * 128;
}
__device__ __forceinline__ void helper_cta(const CUtensorMap* map_q, const CUtensorMap* map_1, uint8_t* sm,
                                           uint32_t sb, int id, int warp) {
  constexpr int kRed = 6 * 32768, kBar = kRed + 2 * 4096;
  const int tid = threadIdx.x;
  if (warp == 8 && elect()) {
#pragma unroll
    for (int s = 0; s < 6; s++) {
      mbar_init(sb + kBar + s * 8, 1);
      mbar_init(sb + kBar + 64 + s * 8, 4);
    }
    fence_async_smem();
#pragma unroll
    for (int s = 0; s < 6; s++) {
      mbar_expect_tx(sb + kBar + s * 8, 32768);
      tma2d(sb + s * 32768, map_q, sb + kBar + s * 8, id * 128, s * 128);
    }
  }
  __syncthreads();
  if (warp == 8) {
    int slot = 0, ph = 0;
#pragma unroll 1
    for (int n = 6; n < 80; n++) {
      mbar_wait(sb + kBar + 64 + slot * 8, ph);
      if (elect()) {
        mbar_expect_tx(sb + kBar + slot * 8, 32768);
        tma2d(sb + slot * 32768, n < 24 ? map_q : map_1, sb + kBar + slot * 8, helper_col(id, n >> 3), (n & 7) * 128);
      }
      if (++slot == 6) slot = 0, ph ^= 1;
    }
  } else if (warp < 8) {
    if (tid == 0) *reinterpret_cast<unsigned*>(sm + kBar + 128) = atomicAdd(&g_ticket, 1u) / kGrid + 1;
    int slot = warp >> 2, ph = 0;
#pragma unroll 1
    for (int slab = 0; slab < 10; slab++) {
      float a[8];
#pragma unroll
      for (int e = 0; e < 8; e++) a[e] = 0.f;
#pragma unroll 1
      for (int box = 0; box < 4; box++) {
        mbar_wait_bounded(sb + kBar + slot * 8, ph);
        const uint4* p = reinterpret_cast<const uint4*>(sm + slot * 32768) + (tid & 127);
        uint4 v[16];
#pragma unroll
        for (int i = 0; i < 16; i++) v[i] = p[i * 128];
        __syncwarp();
        if (elect()) mbar_arrive(sb + kBar + 64 + slot * 8);
#pragma unroll
        for (int i = 0; i < 16; i++) add_chunk(a, v[i]);
        slot += 2;
        if (slot >= 6) slot -= 6, ph ^= 1;
      }
      float* red = reinterpret_cast<float*>(sm + kRed + (slab & 1) * 4096);
#pragma unroll
      for (int e = 0; e < 8; e++) a[e] += shfl_xor(a[e], 16);
      if ((tid & 16) == 0) {
        float4* d = reinterpret_cast<float4*>(red + warp * 128 + (tid & 15) * 8);
        d[0] = make_float4(a[0], a[1], a[2], a[3]);
        d[1] = make_float4(a[4], a[5], a[6], a[7]);
      }
      asm volatile("bar.sync 1, 256;" ::: "memory");
      if (warp < 4) {
        float t = 0.f;
#pragma unroll
        for (int q = 0; q < 8; q++) t += red[q * 128 + tid];
        st_relaxed(g_cs + (slab < 3 ? 0 : 3 * kD) + helper_col(id, slab) + tid,
                   tag_value(t, *reinterpret_cast<volatile unsigned*>(sm + kBar + 128)));
      }
    }
  }
}

__device__ __forceinline__ void colsum_strip(const CUtensorMap* map, uint8_t* sm, uint32_t sb, int col, int half,
                                             int lane, unsigned epoch) {
  const uint32_t bar = sb + kBarSlab + half * 16;
  const int buf = kSmStg + half * 8192;
  float a[8];
#pragma unroll
  for (int e = 0; e < 8; e++) a[e] = 0.f;
#pragma unroll 1
  for (int r = -2; r < 4; r++) {
    if (r >= 0) {
      mbar_wait(bar + (r & 1) * 8, r >> 1);
      const uint4* p = reinterpret_cast<const uint4*>(sm + buf + (r & 1) * 4096) + lane;
#pragma unroll 1
      for (int q = 0; q < 8; q += 4) {
        uint4 v[4];
#pragma unroll
        for (int u = 0; u < 4; u++) v[u] = p[(q + u) * 32];
#pragma unroll
        for (int u = 0; u < 4; u++) {
          a[0] += bf_lo(v[u].x); a[1] += bf_hi(v[u].x); a[2] += bf_lo(v[u].y); a[3] += bf_hi(v[u].y);
          yield_slot();
          a[4] += bf_lo(v[u].z); a[5] += bf_hi(v[u].z); a[6] += bf_lo(v[u].w); a[7] += bf_hi(v[u].w);
          yield_slot();
        }
      }
      fence_async_smem();
      __syncwarp();
    }
    if (r < 2 && elect()) {
      mbar_expect_tx(bar + (r & 1) * 8, 4096);
      tma2d(sb + buf + (r & 1) * 4096, map, bar + (r & 1) * 8, col, half * 512 + (r + 2) * 128);
    }
  }
#pragma unroll
  for (int e = 0; e < 4; e++) a[e] = (lane & 16 ? a[e + 4] : a[e]) + shfl_xor(lane & 16 ? a[e] : a[e + 4], 16);
#pragma unroll
  for (int e = 0; e < 2; e++) a[e] = (lane & 8 ? a[e + 2] : a[e]) + shfl_xor(lane & 8 ? a[e] : a[e + 2], 8);
  a[0] = (lane & 4 ? a[1] : a[0]) + shfl_xor(lane & 4 ? a[0] : a[1], 4);
  a[0] += shfl_xor(a[0], 2);
  if (!(lane & 2)) st_relaxed(g_cs + half * (3 * kD + kF) + col + (lane & 1) * 8 + (lane >> 2), tag_value(a[0], epoch));
}

constexpr float kGeluBeta = 0.3292034911525734f / 2.f;
constexpr float kGeluK = 2.423681954311584f / 4.f;
constexpr float kHScale = 2.f * kGeluBeta;

__device__ __forceinline__ void store_staged(uint8_t* dst, uint32_t stg) {
  fence_async_smem();
  __syncwarp();
  if (elect()) {
    bulk_store(dst, stg, 4096);
    bulk_commit();
  }
}

template <int J0, int J1>
__device__ __forceinline__ void fold_norm(float (&acc)[2][96], const float2 (&st)[4], const float4* vec) {
  float4 vn = vec[J0 * 4];
#pragma unroll
  for (int J = J0; J < J1; J++) {
    const float4 v = vn;
    if (J + 1 < J1) vn = vec[J * 4 + 4];
#pragma unroll
    for (int c = 0; c < 4; c++) {
      float& a0 = acc[c & 1][4 * J + (c & 2)];
      float& a1 = acc[c & 1][4 * J + (c & 2) + 1];
      a0 = fmaf(a0, st[c].x, fmaf(st[c].y, v.x, v.z));
      a1 = fmaf(a1, st[c].x, fmaf(st[c].y, v.y, v.w));
      asm volatile("" : "+f"(a0), "+f"(a1));
      if (c & 1) yield_slot();
    }
  }
}

template <int CH, class Acquire>
__device__ __forceinline__ void gelu_chunk(const float (&acc)[2][96], uint32_t stg, int lane, uint8_t* prev,
                                           Acquire acquire) {
  uint32_t pk[8][4];
  float z[3][4];
  const uint32_t row = (stg + lane * 128) ^ ((lane & 7) << 4);
#define U(s, e) acc[(e) >> 1][4 * (CH * 8 + ((s) >> 1)) + 2 * ((s) & 1) + ((e) & 1)]
#pragma unroll
  for (int s = 0; s < 18; s++) {
    const int cur = s % 3, p1 = (s + 2) % 3, p2 = (s + 1) % 3, q = s - 2, jj = 2 * q - 24;
    const bool mid = s >= 1 && s < 17;
    if (mid) z[p1][0] = tanh_fast(z[p1][0]);
    if (s < 16) {
#pragma unroll
      for (int e = 0; e < 4; e++) {
        z[cur][e] = fmaf(U(s, e), U(s, e), kGeluK);
        asm volatile("" : "+f"(z[cur][e]));
      }
    }
    if (jj >= 0) stsm4(row ^ (jj << 4), pk[jj][0], pk[jj][1], pk[jj][2], pk[jj][3]);
    yield_slot();
    if (mid) z[p1][1] = tanh_fast(z[p1][1]);
    if (q >= 0) {
      pk[q >> 1][2 * (q & 1)] = pack2(fmaf(U(q, 0), z[p2][0], U(q, 0)), fmaf(U(q, 1), z[p2][1], U(q, 1)));
      pk[q >> 1][2 * (q & 1) + 1] = pack2(fmaf(U(q, 2), z[p2][2], U(q, 2)), fmaf(U(q, 3), z[p2][3], U(q, 3)));
    }
    if (mid) z[p1][2] = tanh_fast(z[p1][2]);
    if (s < 16) {
#pragma unroll
      for (int e = 0; e < 4; e++) {
        z[cur][e] = z[cur][e] * U(s, e) * 8.f;
        asm volatile("" : "+f"(z[cur][e]));
      }
    }
    if (mid) z[p1][3] = tanh_fast(z[p1][3]);
    if (jj >= 0) stsm4(row ^ ((jj + 1) << 4), pk[jj + 1][0], pk[jj + 1][1], pk[jj + 1][2], pk[jj + 1][3]);
    yield_slot();
    if (CH == 1 && s == 1) store_staged(prev, stg);
    if (q == 11) acquire();
  }
#undef U
}

__device__ __forceinline__ void scale_stats(float2 (&st)[4]) {
#pragma unroll
  for (int c = 0; c < 4; c++) {
    st[c].x *= kGeluBeta;
    st[c].y *= st[c].x;
  }
}

__device__ __forceinline__ void add_mean_term(float (&acc)[2][96], const float2 (&st)[4], uint8_t* sm, int tq,
                                              int lane) {
  const float2* cs = reinterpret_cast<const float2*>(sm + kSmCsQ) + tq * 96 + (lane & 3);
  float2 vn = cs[0];
#pragma unroll
  for (int J = 0; J < 24; J++) {
    const float2 v = vn;
    if (J < 23) vn = cs[J * 4 + 4];
#pragma unroll
    for (int c = 0; c < 4; c++) {
      acc[c & 1][4 * J + (c & 2)] = fmaf(st[c].y, v.x, acc[c & 1][4 * J + (c & 2)]);
      acc[c & 1][4 * J + (c & 2) + 1] = fmaf(st[c].y, v.y, acc[c & 1][4 * J + (c & 2) + 1]);
    }
    yield_slot();
  }
}

struct AttnRegs {
  uint32_t q[4][8], k[5][8], vt[5][8];
};
#define SCALED(c, J) pack2(acc[(c) & 1][4 * (J) + ((c) & 2)] * st[c].x, acc[(c) & 1][4 * (J) + ((c) & 2) + 1] * st[c].x)
__device__ __forceinline__ void convert_group(const float (&acc)[2][96], const float2 (&st)[4], AttnRegs& r, int c,
                                              int part) {
#pragma unroll
  for (int J = 0; J < 8; J++) {
    if (part == 0) r.q[c][J] = SCALED(c, J);
    if (part == 1) r.k[c + 1][J] = SCALED(c, 8 + J);
    if (part == 2) r.vt[c + 1][J] = transpose8(SCALED(c, 16 + J));
    if (J & 1) yield_slot();
  }
}
#undef SCALED

__device__ __forceinline__ void convert_odd(const float (&acc)[2][96], const float2 (&st)[4], AttnRegs& r, int step,
                                            uint8_t* sm, uint32_t halo_bar, uint4* halo_out, bool send,
                                            unsigned epoch, int w, int lane) {
  if (step == 1) {
    convert_group(acc, st, r, 3, 2);
    convert_group(acc, st, r, 3, 1);
    if (w < 3) {
      uint2* hs = reinterpret_cast<uint2*>(sm + kSmHalo + w * 2048) + lane;
#pragma unroll
      for (int i = 0; i < 4; i++) {
        hs[i * 32] = make_uint2(r.k[4][2 * i], r.k[4][2 * i + 1]);
        hs[128 + i * 32] = make_uint2(r.vt[4][2 * i], r.vt[4][2 * i + 1]);
      }
      __syncwarp();
      if (elect()) mbar_arrive(halo_bar + w * 8);
    } else if (send) {
#pragma unroll
      for (int i = 0; i < 4; i++) {
        st_packet(halo_out + lane + i * 32, r.k[4][2 * i], r.k[4][2 * i + 1], epoch);
        st_packet(halo_out + lane + 128 + i * 32, r.vt[4][2 * i], r.vt[4][2 * i + 1], epoch);
      }
    }
  } else if (step == 2) {
    convert_group(acc, st, r, 1, 2);
  } else {
    convert_group(acc, st, r, 1, 1);
    convert_group(acc, st, r, 3, 0);
    convert_group(acc, st, r, 1, 0);
  }
}

__device__ __forceinline__ void epilogue_attn(const float (&acc)[2][96], const float2 (&st)[4], AttnRegs& r,
                                              uint8_t* sm, uint32_t sb, int layer, int tq, int b, int j,
                                              unsigned epoch, int tile, int w, int lane) {
  const int t = lane & 3, g = lane >> 2;
  const int hp = j + 8 * tq, att = 2 * layer + tq;
  auto& q = r.q;
  auto& k = r.k;
  auto& vt = r.vt;
  const bool first = w == 0 && (b & 7) == 0;
  const uint4* gh = g_halo + ((layer * 16 + b - 1) * 16 + hp) * 256 + lane;
  uint32_t tag[8];
#define LOAD_HALO()                                                                                    \
  _Pragma("unroll") for (int i = 0; i < 4; i++) {                                                      \
    ld_packet(gh + i * 32, k[0][2 * i], k[0][2 * i + 1], tag[i]);                                      \
    ld_packet(gh + 128 + i * 32, vt[0][2 * i], vt[0][2 * i + 1], tag[4 + i]);                          \
  }
#pragma unroll
  for (int c = 0; c < 6; c++) {
    if (c == 2) {
#pragma unroll
      for (int i = 0; i < 8; i++) k[0][i] = vt[0][i] = tag[i] = 0u;
      if (w > 0) {
        mbar_wait(sb + kBarHalo + (att * 3 + w - 1) * 8, 0);
        const uint2* hs = reinterpret_cast<const uint2*>(sm + kSmHalo + (w - 1) * 2048) + lane;
#pragma unroll
        for (int i = 0; i < 4; i++) {
          const uint2 a = hs[i * 32], d = hs[128 + i * 32];
          k[0][2 * i] = a.x; k[0][2 * i + 1] = a.y;
          vt[0][2 * i] = d.x; vt[0][2 * i + 1] = d.y;
        }
      } else if (!first) {
        LOAD_HALO();
      }
    }
    convert_group(acc, st, r, 2 * (c & 1), 2 - (c >> 1));
  }
  TRACE_AT(tile, 8);
  if (w == 0 && !first) {
#pragma unroll 1
    while (__any_sync(0xffffffffu, ((tag[0] ^ epoch) | (tag[1] ^ epoch) | (tag[2] ^ epoch) | (tag[3] ^ epoch)) |
                                       ((tag[4] ^ epoch) | (tag[5] ^ epoch) | (tag[6] ^ epoch) | (tag[7] ^ epoch)))) {
      LOAD_HALO();
    }
  }
  constexpr float kScale = 0.17677669529663687f * 1.4426950408889634f;
  const bool own0 = 2 * t <= g, own1 = 2 * t + 1 <= g;
  const uint32_t own_mask = (own0 ? 0xffffu : 0u) | (own1 ? 0xffff0000u : 0u);
  const uint32_t stg = sb + kSmStg + w * 4096;
  const uint32_t orow = stg + (lane & 7) * 128, ochunk = (lane >> 3) ^ (lane & 7);
  TRACE_AT(tile, 9);
  mbar_wait(sb + kBarPause + att * 8, 0);
  TRACE_AT(tile, 10);

  float s[2][6][4], o[2][4][2][4];
#pragma unroll
  for (int n = 0; n < 24; n++) {
    const int ks = n / 12, hd = (n % 12) / 6, m = n % 6, ca = 2 * (m / 3), kg = ca + m % 3, J = 4 * hd + 2 * ks;
    if (ks == 0) s[hd][m][0] = s[hd][m][1] = s[hd][m][2] = s[hd][m][3] = 0.f;
    mma16816(s[hd][m], q[ca][J], q[ca + 1][J], q[ca][J + 1], q[ca + 1][J + 1], k[kg][J], k[kg][J + 1]);
  }
  float v0[2][4], v1[2][4], m[2][4];
  uint32_t pp[2][4], po[2][4];
#define UNITS _Pragma("unroll") for (int hd = 0; hd < 2; hd++) _Pragma("unroll") for (int c = 0; c < 4; c++)
  UNITS {
    const int mp = 3 * (c >> 1) + (c & 1), r = 2 * (c & 1);
    float p0 = s[hd][mp][r], p1 = s[hd][mp][r + 1];
    if (c == 0 && first) p0 = p1 = -INFINITY;
    v0[hd][c] = own0 ? s[hd][mp + 1][r] : p0;
    v1[hd][c] = own1 ? s[hd][mp + 1][r + 1] : p1;
    m[hd][c] = fmaxf(v0[hd][c], v1[hd][c]);
  }
  UNITS m[hd][c] = fmaxf(m[hd][c], shfl_xor(m[hd][c], 1));
  UNITS m[hd][c] = fmaxf(m[hd][c], shfl_xor(m[hd][c], 2));
  UNITS {
    const float nm = -m[hd][c] * kScale;
    v0[hd][c] = ex2(fmaf(v0[hd][c], kScale, nm));
    v1[hd][c] = ex2(fmaf(v1[hd][c], kScale, nm));
    m[hd][c] = v0[hd][c] + v1[hd][c];
  }
  UNITS m[hd][c] += shfl_xor(m[hd][c], 1);
  UNITS m[hd][c] += shfl_xor(m[hd][c], 2);
  UNITS {
    const float inv = rcp(m[hd][c]);
    const uint32_t p = pack2(v0[hd][c] * inv, v1[hd][c] * inv);
    pp[hd][c] = p & ~own_mask;
    po[hd][c] = p & own_mask;
    asm volatile("" : "+r"(pp[hd][c]), "+r"(po[hd][c]));
  }
#pragma unroll
  for (int n = 0; n < 24; n++) {
    const int ph = n / 8, hd = (n >> 2) & 1, c = 2 * ((n >> 1) & 1) + (ph == 1), ds = n & 1, J = 4 * hd + 2 * ds;
    float(&d)[4] = o[hd][c][ds];
    if (ph < 2) d[0] = d[1] = d[2] = d[3] = 0.f;
    if (ph == 0) mma1688(d, vt[c + 1][J], vt[c + 1][J + 1], po[hd][c]);
    if (ph == 1) mma16816(d, vt[c][J], vt[c][J + 1], vt[c + 1][J], vt[c + 1][J + 1], pp[hd][c], po[hd][c]);
    if (ph == 2) mma1688(d, vt[c][J], vt[c][J + 1], pp[hd][c]);
    if (n == 3) {
      yield_slot();
      if (tq == 0 && lane == 0) mbar_arrive(sb + kBarResume + att * 8);
    }
  }
  yield_slot();
  if (tq == 1 && lane == 0) mbar_arrive(sb + kBarResume + att * 8);
  TRACE_AT(tile, 11);
  UNITS stsm4_t(orow + c * 1024 + ((ochunk ^ (4 * hd)) << 4), pack2(o[hd][c][0][0], o[hd][c][0][1]),
                pack2(o[hd][c][0][2], o[hd][c][0][3]), pack2(o[hd][c][1][0], o[hd][c][1][1]),
                pack2(o[hd][c][1][2], o[hd][c][1][3]));
#undef UNITS
#undef LOAD_HALO
  fence_async_smem();
  __syncwarp();
  TRACE_AT(tile, 12);
  if (elect()) {
    bulk_store(g_o + (b * 16 + hp) * kTileBytes + w * 4096, stg, 4096);
    bulk_commit();
    bulk_wait();
    TRACE_AT(tile, 13);
    mbar_arrive(sb + kBarEpi + tile * 8);
  }
  __syncwarp();
}

__device__ __forceinline__ void gather_stats(uint8_t* sm, const uint2* stat, int r, float eps, unsigned epoch) {
  uint2 a[8];
  unsigned diff;
#pragma unroll 1
  do {
    __nanosleep(800);
    diff = 0;
#pragma unroll
    for (int i = 0; i < 8; i++) {
      a[i] = ld_relaxed64(stat + i * 128 + r);
      diff |= a[i].x ^ epoch;
    }
  } while (__any_sync(0xffffffffu, diff & 7u));
  float s = 0.f, q = 0.f;
#pragma unroll
  for (int i = 0; i < 8; i++) {
    s += untag_value(a[i].x);
    q += __uint_as_float(a[i].y);
  }
  const float mean = s * (1.f / 1024.f);
  const float var = fmaxf(fmaf(-mean, mean, q * (1.f / 1024.f)), 0.f);
  reinterpret_cast<float2*>(sm + kSmStat)[r] = make_float2(rsqrtf(var + eps), -mean);
}

__device__ __forceinline__ void gather_colsums_qkv(uint8_t* sm, int tq, int j, int lane, unsigned epoch) {
  const uint2* src = reinterpret_cast<const uint2*>(g_cs + (j + 8 * tq) * 64) + lane;
  uint2 v[3], u[3];
  unsigned diff, spins = 0;
#pragma unroll 1
  do {
    if (++spins > kSpinLimit) __trap();
    diff = 0;
#pragma unroll
    for (int q = 0; q < 3; q++) {
      v[q] = ld_relaxed_pair(src + q * (kD / 2));
      u[q] = make_uint2(epoch & 7u, epoch & 7u);
      if (tq) u[q] = ld_relaxed_pair(src + (q * kD + 3 * kD + kF) / 2);
    }
#pragma unroll
    for (int q = 0; q < 3; q++) diff |= (v[q].x ^ epoch) | (v[q].y ^ epoch) | (u[q].x ^ epoch) | (u[q].y ^ epoch);
  } while (__any_sync(0xffffffffu, diff & 7u));
#pragma unroll
  for (int q = 0; q < 3; q++)
    reinterpret_cast<float2*>(sm + kSmCsQ)[tq * 96 + q * 32 + lane] =
        make_float2(untag_value(v[q].x) + untag_value(u[q].x), untag_value(v[q].y) + untag_value(u[q].y));
}

__device__ __forceinline__ void gather_colsums_w1(uint8_t* sm, const __nv_bfloat16* b1, int j, int lane,
                                                  unsigned epoch) {
#pragma unroll 1
  for (int blk = 0; blk < 7; blk++) {
    const int pair = 32 * (blk + (blk < 3 ? 3 * j : blk < 5 ? 21 + 2 * j : 35 + 2 * j)) + lane;
    const uint32_t bias = reinterpret_cast<const uint32_t*>(b1)[pair];
    uint2 v;
    unsigned spins = 0;
#pragma unroll 1
    do {
      if (++spins > kSpinLimit) __trap();
      v = ld_relaxed_pair(reinterpret_cast<const uint2*>(g_cs + 3 * kD) + pair);
    } while (__any_sync(0xffffffffu, ((v.x ^ epoch) | (v.y ^ epoch)) & 7u));
    reinterpret_cast<float4*>(sm + kSmV1)[blk * 32 + lane] =
        make_float4(untag_value(v.x), untag_value(v.y), kGeluBeta * bf_lo(bias), kGeluBeta * bf_hi(bias));
  }
}

constexpr int kPauseQkv = 7, kPauseWo = 2;

__global__ void __cluster_dims__(2, 1, 1) __launch_bounds__(384, 1)
fused_layers_kernel(const __grid_constant__ CUtensorMap map_x, const __grid_constant__ CUtensorMap map_out,
                    const __grid_constant__ CUtensorMap map_qkv, const __grid_constant__ CUtensorMap map_wo,
                    const __grid_constant__ CUtensorMap map_w1a, const __grid_constant__ CUtensorMap map_w1b,
                    const __grid_constant__ CUtensorMap map_w2, const __grid_constant__ CUtensorMap map_csq,
                    const __grid_constant__ CUtensorMap map_cs1, const __grid_constant__ CUtensorMap map_css,
                    const __grid_constant__ Params prm) {
  extern __shared__ __align__(1024) uint8_t sm[];
  if (threadIdx.x < 128 && blockIdx.x < kCtas) TRACE_AT(15, 1);
  const uint32_t sb = __shfl_sync(0xffffffffu, smem_u32(sm), 0);
  const int warp = __shfl_sync(0xffffffffu, threadIdx.x >> 5, 0), lane = threadIdx.x & 31;
  const int cta = blockIdx.x, rank = cta & 1, cl = cta >> 1;
  const int grp = cl < 4 ? 0 : cl < 36 ? (cl - 4) & 7 : 1 + (cl - 36) % 7;
  const int j = cl < 4 ? 4 + cl : cl < 36 ? (cl - 4) >> 3 : 4 + (cl - 36) / 7;
  const int b = 2 * grp + rank;
  const int xcol = (b >> 3) * kD, xrow = (b & 7) * 128;

  if (cta >= kCtas) {
    helper_cta(&map_csq, &map_cs1, sm, sb, cta - kCtas, warp);
    return;
  }
  if ((warp < 8 || warp == 9) && elect()) {
    if (warp == 9) {
#pragma unroll
      for (int s = 0; s < 8; s++) mbar_init(sb + kBarFull + s * 8, 1);
      fence_async_smem();
#pragma unroll 1
      for (int s = 0; s < 4; s++) {
        const uint32_t full = sb + kBarFull + s * 8, dst = sb + kSmRing + s * 40960;
        mbar_expect_tx(full, 40960);
        tma2d(dst, &map_x, full, xcol + (s & 1) * 64, xrow);
        tma3d(dst + kTileBytes, &map_qkv, full, (j + 4 * (s & 2)) * 64, (s & 1) * 64, 0);
        tma3d(dst + kTileBytes + 12288, &map_qkv, full, (j + 4 * (s & 2)) * 64, (s & 1) * 64 + 32, 0);
      }
    } else {
      if (sb & 1023) __trap();
#pragma unroll
      for (int s = 0; s < 16; s++) mbar_init(sb + kBarTurn + warp * 128 + s * 8, warp < 5 ? 1 : warp == 5 ? 2 : 4);
    }
    asm volatile("fence.mbarrier_init.release.cluster;" ::: "memory");
  }
  __syncwarp();
  asm volatile("barrier.cluster.arrive.relaxed.aligned;" ::: "memory");

  if (warp >= 8) {
    asm volatile("setmaxnreg.dec.sync.aligned.u32 40;");
    if (warp < 10) {
      asm volatile("barrier.cluster.wait.aligned;" ::: "memory");
      uint32_t nb = 32, off = 0, kb = 0;
#define RING_STEP(WAIT, ISSUE)                                            \
  do {                                                                    \
    const uint32_t mb = nb - depth, full = sb + kBarFull + (nb & 56);     \
    if (kb == skip) kb += inc;                                            \
    mbar_wait(sb + kBarEmpty + (mb & 56), mb >> 6);                       \
    WAIT;                                                                 \
    if (elect()) { ISSUE; }                                               \
    TRACE_ISSUE(9 - warp, nb);                                            \
    kb += inc;                                                            \
    off = off == wrap ? 0 : off + step;                                   \
    nb += 8;                                                              \
  } while (nb != nend)
#pragma unroll 1
      for (int sg = 0; sg < kSegs; sg++) {
        const uint32_t e = prm.seg[sg];
        const int ty = e & 7, mode = (e >> 15) & 3, reset = (e >> 24) & 3;
        const uint32_t nend = nb + (e & 0x1f8);
        const uint32_t step = (e >> 17) & 1 ? 40960 : 32768, wrap = 163840 - step;
        const uint32_t depth = (e >> 18) & 1 ? 40 : 32;
        if (reset) off = reset == 1 ? 0 : reset == 2 ? 40960 : 131072;
        const uint32_t own = ty == 2 ? 8 + j : 2 * j;
        if (mode != kModeContinue) kb = ((e >> 9) & 63) + (mode == kModeHead ? own : 0);
        const uint32_t inc = mode >= kModeSkip && ty != 2 ? 2 : 1, skip = mode >= kModeSkip ? own + (kb & 1) : 255;
        if (warp == 8) {
          const CUtensorMap* map = ty < 2 ? &map_qkv : ty == 2 ? &map_wo : ty == 3 ? &map_w1a : ty < 6 ? &map_w1b : &map_w2;
          const int c0 = ty < 2 ? (j + 8 * ty) * 64 : 0;
          const int c2 = ty < 2 ? 0 : ty == 3 ? 3 * j : ty == 4 ? 24 + 2 * j : ty == 5 ? 40 + 2 * j : 2 * j;
          const uint32_t half = (ty < 2 || ty == 3) ? 12288 : 8192;
          const uint32_t bytes = 2 * half + (mode == kModeHead ? 0 : kTileBytes);
          const uint32_t dst = sb + kSmRing + (mode == kModeHead && ty != 2 ? 0 : kTileBytes) + rank * half;
          if (e >> 26) {
            const bool second = (grp & 6) == 2;
            const int pk = grp < 4 ? 2 * j + (grp & 1) : 2 * (grp - 4 + (grp - 4 >= j));
            const CUtensorMap* pm = ty == 6 ? &map_qkv : second ? &map_w1b : &map_w1a;
            if (elect())
              asm volatile("cp.async.bulk.prefetch.tensor.3d.L2.global [%0, {%1, %2, %3}];" ::"l"(pm),
                           "r"(ty == 6 ? (j + 8 * second) * 64 : 0), "r"(pk * 64 + rank * 32),
                           "r"(ty == 6 ? 0 : second ? 24 + 2 * j : 3 * j) : "memory");
          }
          if (ty == 2 && mode == kModeHead) mbar_wait(sb + kBarEpi + ((e >> 19) & 31) * 8, 0);
#pragma unroll 1
          RING_STEP(, mbar_expect_tx(full, bytes); tma3d_mc(dst + off, map, full, c0, kb * 64 + rank * 32, c2));
        } else if (mode == kModeHead) {
          off += ((nend - nb) >> 3) * step;
          nb = nend;
          if (off >= 163840) off -= 163840;
        } else if (sg < 2) {
#pragma unroll 1
          RING_STEP(, tma2d(sb + kSmRing + off, &map_x, full, xcol + kb * 64, xrow));
        } else {
          const uint8_t* src = ty == 6 ? g_h + b * 56 * kTileBytes : (ty == 2 ? g_o : g_x) + b * 16 * kTileBytes;
          const int dep = (e >> 19) & 31;
          if (dep < 28) mbar_wait(sb + kBarReady + dep * 8, 0);
          if ((dep & 30) == 28) {
#pragma unroll 1
            RING_STEP(mbar_wait(sb + kBarSrc + ((kb << (4 - inc)) & 56), dep),
                      bulk_load(sb + kSmRing + off, src + kb * kTileBytes, kTileBytes, full));
          } else {
#pragma unroll 1
            RING_STEP(, bulk_load(sb + kSmRing + off, src + kb * kTileBytes, kTileBytes, full));
          }
        }
      }
#undef RING_STEP
    } else {
      unsigned epoch = 0;
      if (warp == 10) {
        if (lane == 0) epoch = atomicAdd(&g_ticket, 1u) / kGrid + 1;
        *reinterpret_cast<unsigned*>(sm + kSmEpoch) = __shfl_sync(0xffffffffu, epoch, 0);
        asm volatile("barrier.cluster.wait.aligned;" ::: "memory");
        if (elect()) mbar_arrive(sb + kBarEpoch);
      } else {
        asm volatile("barrier.cluster.wait.aligned;" ::: "memory");
        mbar_wait_bounded(sb + kBarFull, 0);
        if (elect()) {
          mbar_expect_tx(sb + kBarInit, 32768);
          tma2d(sb + kSmX, &map_x, sb + kBarInit, xcol + j * 128, xrow);
          tma2d(sb + kSmX + kTileBytes, &map_x, sb + kBarInit, xcol + j * 128 + 64, xrow);
        }
        const uint2 u = reinterpret_cast<const uint2*>(prm.b2)[32 * j + lane];
        reinterpret_cast<float4*>(sm + kSmB2)[lane] = make_float4(
            kHScale * bf_lo(u.x), kHScale * bf_hi(u.x), kHScale * bf_lo(u.y), kHScale * bf_hi(u.y));
      }
      mbar_wait_bounded(sb + kBarEpoch, 0);
      epoch = *reinterpret_cast<volatile unsigned*>(sm + kSmEpoch);
      if (cta < 96) {
        mbar_wait_bounded(sb + kBarInit, 0);
        colsum_strip(&map_css, sm, sb, (cta >> 5) * kD + 512 + (cta & 31) * 16, warp - 10, lane, epoch);
      }
      gather_colsums_qkv(sm, 11 - warp, j, lane, epoch);
      __syncwarp();
      if (elect()) mbar_arrive(sb + kBarCs + (11 - warp) * 8);
      if (warp == 10) {
#pragma unroll 1
        for (int i = 0; i < kTiles - 1; i++) {
          const bool xt = i == 2 || i == 6 || i == 9;
          const unsigned* line = g_flag + (i * 16 + b) * 32;
          mbar_wait(sb + (xt ? kBarX + (i >> 2) * 16 : kBarEpi + i * 8), 0);
          if (xt || i == 1 || i == 8) {
            unsigned todo = 0xff;
            do {
              const unsigned now = __ballot_sync(0xffffffffu, ld_relaxed(line + (lane & 7)) == epoch) & todo;
              if (now) {
                asm volatile("fence.acquire.gpu;\nfence.proxy.async.global;" ::: "memory");
                if ((now >> lane) & 1) mbar_arrive(sb + kBarSrc + lane * 8);
                todo ^= now;
              }
              if (todo == 0xff) __nanosleep(300);
            } while (todo);
          } else {
            wait_flags(line + (lane & 7), epoch);
            if (elect()) mbar_arrive(sb + kBarReady + i * 8);
          }
          if (xt) {
            wait_flags(line + 8 + (lane & 7), epoch);
            if (elect()) mbar_arrive(sb + kBarReady + (14 + (i >> 2)) * 8);
          }
        }
      } else {
#pragma unroll 1
        for (int i = 0; i < kTiles - 1; i++) {
          if (i == 3) {
            gather_colsums_w1(sm, prm.b1, j, lane, epoch);
            __syncwarp();
            if (elect()) mbar_arrive(sb + kBarCs + 16);
          }
          const bool xt = i == 2 || i == 6 || i == 9;
#pragma unroll 1
          for (int h = 0; h < (xt ? 2 : 1); h++) {
            if (xt && h == 0) {
              mbar_wait_bounded(sb + kBarEpi + i * 8, 0);
              if (elect()) bulk_store(g_x + (b * 16 + 2 * j) * kTileBytes, sb + kSmX, kTileBytes / 2);
            }
            mbar_wait_bounded(sb + (xt ? kBarX + (i >> 2) * 16 + 8 * h : kBarEpi + i * 8), 0);
            const int ty = i >= 7 ? i - 7 : i;
            if (ty >= 2 && elect()) {
              uint8_t* dst = xt ? g_x + (b * 16 + 2 * j + h) * kTileBytes
                                : g_h + (b * 56 + 1 + (ty == 3 ? 3 * j : 16 * ty - 40 + 2 * j)) * kTileBytes;
              const int piece = (xt && h == 0) ? kTileBytes / 2 : kTileBytes / 4;
#pragma unroll 1
              for (int o = xt && h == 0 ? piece : 0; o < kTileBytes; o += piece) {
                bulk_store(dst + o, sb + (xt ? kSmX + h * kTileBytes : kSmStg) + o, piece);
                bulk_commit();
                bulk_wait();
              }
              if (!xt) mbar_arrive(sb + kBarFree + i * 8);
            }
            __syncwarp();
            if (elect()) st_release(&g_flag[(i * 16 + b) * 32 + h * 8 + j], epoch);
            __syncwarp();
          }
        }
#pragma unroll 1
        for (int q = 0; q < 4; q++) {
          if (!(q & 1)) mbar_wait_bounded(sb + kBarEpi + (kTiles - 1) * 8, q >> 1);
          else mbar_wait_bounded(sb + kBarX + 48 + 4 * (q & 2), 0);
          if (elect()) {
            tma2d_store(&map_out, sb + kSmX + q * 8192, xcol + j * 128 + (q >> 1) * 64, xrow + (q & 1) * 64);
            bulk_commit();
            if (q == 3) bulk_wait_read();
          }
        }
      }
    }
    __syncwarp();
    asm volatile("barrier.cluster.arrive.relaxed.aligned;\nbarrier.cluster.wait.aligned;" ::: "memory");
  } else {
    asm volatile("setmaxnreg.inc.sync.aligned.u32 232;");
    asm volatile("barrier.cluster.wait.aligned;" ::: "memory");
    const int wg = warp >> 2, w = warp & 3;
    const bool rel = (threadIdx.x & 95) == 0;
    const uint32_t rel_addr = mapa(sb + kBarEmpty, w & 1);
    if (wg == 1) TRACE_AT(15, 0);
#define EPOCH (*reinterpret_cast<volatile unsigned*>(sm + kSmEpoch))

#pragma unroll 1
    for (int i = wg; i < kTiles; i += 2) {
      const int layer = i >= 7, ty = i - 7 * layer;
      TRACE_AT(i, 15);
      float acc[2][96];
      if (ty == 2 || ty == 6) {
        const int lane = lane_id();
        const uint32_t xa = sb + kSmX + ((lane >> 4) * 8 + (lane & 7)) * 128 + (((2 * w + ((lane >> 3) & 1)) ^ (lane & 7)) << 4);
        const float up = ty == 6 ? kHScale / kXScale : layer ? 1.f / kXScale : 1.f;
        const float dn = ty == 2 ? kXScale : layer ? 1.f / kHScale : kXScale / kHScale;
#pragma unroll
        for (int h = 0; h < 2; h++) {
          const float* b2 = reinterpret_cast<const float*>(sm + kSmB2) + 64 * h + 16 * w + (lane >> 2);
          const float bias[2] = {ty == 6 ? b2[0] : 0.f, ty == 6 ? b2[8] : 0.f};
#pragma unroll
          for (int p = 0; p < 8; p++) {
            uint32_t r[4];
            ldsm4_t(xa + h * kTileBytes + p * 2048, r);
#pragma unroll
            for (int m = 0; m < 4; m++) {
              acc[h][8 * p + 2 * m] = fmaf(bf_lo(r[m]), up, bias[m & 1]);
              acc[h][8 * p + 2 * m + 1] = fmaf(bf_hi(r[m]), up, bias[m & 1]);
              asm volatile("" : "+f"(acc[h][8 * p + 2 * m]), "+f"(acc[h][8 * p + 2 * m + 1]));
            }
            yield_slot();
          }
        }
        auto stage = [&](int qt) {
          const int h = qt >> 1;
          if (qt == 1 || (qt == 3 && i == kTiles - 1)) {
            fence_async_smem();
            __syncwarp();
            if (lane == 0) mbar_arrive(sb + kBarEpi + i * 8);
          }
#pragma unroll
          for (int p = 4 * (qt & 1); p < 4 * (qt & 1) + 4; p++) {
            const float* a = &acc[h][8 * p];
            stsm4_t(xa + h * kTileBytes + p * 2048, pack2(a[0] * dn, a[1] * dn), pack2(a[2] * dn, a[3] * dn),
                    pack2(a[4] * dn, a[5] * dn), pack2(a[6] * dn, a[7] * dn));
            yield_slot();
          }
          if (qt & 1) {
            fence_async_smem();
            __syncwarp();
            if (elect()) mbar_arrive(sb + kBarX + (i >> 2) * 16 + 8 * h);
            TRACE_AT(i, 8 + h);
          }
        };
        mainloop<128, kResid>(acc, sb, i, layer * 152 + ty * 16, ty == 6 ? 4 : 0, ty == 6 ? 56 : 16,
                            ty == 2 ? kPauseWo : -1, 2 * layer + 1, rel_addr, rel, ty == 2 ? 8 : -1, stage);
        TRACE_AT(i, 2);
        stage(2);
        stage(3);
      } else {
        const int xver = 2 * layer + (ty >= 3);
        const uint32_t stg = sb + kSmStg + w * 4096;
        const float4* vec = reinterpret_cast<const float4*>(sm + kSmV1) + (ty == 3 ? 0 : 64 * ty - 160);
        int lane;
        uint8_t* hdst = g_h + (b * 56 + (ty == 3 ? 3 * j : 16 * ty - 40 + 2 * j)) * kTileBytes + w * 4096;
        float2 st[4];
        unsigned epoch;
        auto pre = [&] {
          lane = lane_id();
          if (ty < 4) mbar_wait(sb + (ty == 1 ? kBarEpi + (i - 1) * 8 : kBarStat + xver * 8), 0);
#pragma unroll
          for (int c = 0; c < 4; c++) st[c] = reinterpret_cast<const float2*>(sm + kSmStat)[32 * w + 8 * c + (lane >> 2)];
          epoch = EPOCH;
        };
        auto team_stats = [&] {
          uint2* stat = g_stat + (xver * 16 + b) * 1024;
          lane = lane_id();
          publish_stats(sb, stat + j * 128, w, lane, EPOCH);
          gather_stats(sm, stat, 32 * w + lane, xver ? 1e-5f * kXScale * kXScale : 1e-5f, EPOCH);
          __syncwarp();
          if (elect()) mbar_arrive(sb + kBarStat + xver * 8);
          TRACE_AT(i, 14);
        };
        if (ty < 4) {
          AttnRegs ar;
          auto odd = [&](int step) {
            if (step == 0) pre();
            else convert_odd(acc, st, ar, step, sm, sb + kBarHalo + (xver + ty) * 24,
                             g_halo + ((layer * 16 + b) * 16 + j + 8 * ty) * 256, (b & 7) != 7, epoch, w, lane);
          };
          head_blocks<192>(acc, sb, layer * 152 + (ty < 2 ? 2 * ty : 48), ty < 2 ? 2 * ty : 1, xver, rel_addr, rel);
          if (ty == 1) {
            if (i == 1) {
              mbar_wait(sb + kBarEpoch, 0);
              mbar_wait(sb + kBarInit, 0);
            }
            team_stats();
            epoch = 0;
#pragma unroll
            for (int c = 0; c < 4; c++) st[c] = reinterpret_cast<const float2*>(sm + kSmStat)[32 * w + 8 * c + (lane >> 2)];
          } else {
            mainloop<192, kPlain>(acc, sb, i, layer * 152 + (ty ? 52 : 4), ty ? 1 : 0, 14, -1, 0, rel_addr, rel, 0, pre);
            TRACE_AT(i, 2);
            if (ty == 3) goto wide_gelu;
          }
          if (layer == 0) mbar_wait(sb + kBarCs + ty * 8, 0);
          add_mean_term(acc, st, sm, ty, lane);
          if (ty == 1) {
            mainloop<192, kStagger>(acc, sb, i, layer * 152 + 18, 2, 14, kPauseQkv, xver, rel_addr, rel, 0, odd);
            TRACE_AT(i, 2);
          } else {
            odd(1);
            odd(2);
            odd(3);
          }
          epilogue_attn(acc, st, ar, sm, sb, layer, ty, b, j, epoch, i, w, lane);
          TRACE_AT(i, 3);
          continue;
        wide_gelu:
          if (i == 3) mbar_wait(sb + kBarCs + 16, 0);
          scale_stats(st);
          fold_norm<16, 24>(acc, st, vec + (lane & 3));
          TRACE_AT(i, 11);
          gelu_chunk<2>(acc, stg, lane, nullptr, [] {});
          TRACE_AT(i, 12);
          fold_norm<0, 2>(acc, st, vec + (lane & 3));
          store_staged(hdst + 2 * kTileBytes, stg);
          fold_norm<2, 16>(acc, st, vec + (lane & 3));
        } else {
          if (ty == 4) {
            head_blocks<128>(acc, sb, layer * 152 + 50, 3, xver, rel_addr, rel);
            team_stats();
          } else {
            const uint32_t s0 = ((((sb & 0x3FFFF) + kSmRing) >> 4) | (1u << 16)) + 3 * 2048;
            mbar_wait(sb + kBarTurn + (i - 1) * 8, 0);
            mbar_wait(sb + kBarFull, layer * 19 + 10);
            TRACE_KB((layer * 152 + 80) * 8);
            mma_kblock<128, 2>(acc, s0, s0 + kToB);
          }
          mainloop<128, kPlain>(acc, sb, i, layer * 152 + 6 + 15 * ty, 4, ty + 10, -1, 0, rel_addr, rel, 0, pre,
                                ty == 5 ? 0 : 64);
          TRACE_AT(i, 2);
          if (i == 4) mbar_wait(sb + kBarCs + 16, 0);
          scale_stats(st);
          fold_norm<0, 16>(acc, st, vec + (lane & 3));
        }
        auto own_store_done = [] {
          if (elect()) bulk_wait();
          __syncwarp();
        };
        TRACE_AT(i, 8);
        gelu_chunk<0>(acc, stg, lane, nullptr, [&] {
          if (ty == 3) own_store_done();
          else mbar_wait(sb + kBarFree + (i - 1) * 8, 0);
        });
        TRACE_AT(i, 9);
        gelu_chunk<1>(acc, stg, lane, hdst, own_store_done);
        TRACE_AT(i, 10);
        fence_async_smem();
        __syncwarp();
        if (elect()) mbar_arrive(sb + kBarEpi + i * 8);
      }
      TRACE_AT(i, 3);
    }
#undef EPOCH
    asm volatile("barrier.cluster.arrive.relaxed.aligned;\nbarrier.cluster.wait.aligned;" ::: "memory");
    if (wg == 1) TRACE_AT(15, 2);
  }
}

void build_segments(uint32_t* seg) {
  int n = 0, fine = 0;
  auto per_source = [&] { return 28 + (fine++ & 1); };
  auto add = [&](int ty, int cnt, int kb0, int mode, int wide, int depth5, int dep, int reset) {
    seg[n++] = ty | cnt << 3 | kb0 << 9 | mode << 15 | wide << 17 | depth5 << 18 | dep << 19 | reset << 24;
  };
  for (int l = 0; l < 2; l++) {
    const int t = 7 * l;
    if (l == 0) {
      add(0, 14, 2, kModePlain, 1, 0, 31, 1);
      add(1, 14, 2, kModePlain, 1, 0, 31, 0);
    } else {
      add(0, 2, 0, kModeHead, 1, 1, 31, 1);
      add(1, 2, 0, kModeHead, 1, 0, 31, 0);
      add(0, 7, 0, kModeSkip, 1, 0, per_source(), 0);
      add(0, 7, 1, kModeSkip, 1, 0, 15, 0);
      add(1, 7, 0, kModeSkip, 1, 0, 31, 0);
      add(1, 7, 1, kModeSkip, 1, 0, 31, 0);
    }
    add(2, 4, 0, kModePlain, 0, 0, t, 1);
    add(2, 4, 4, kModePlain, 0, 1, 31, 4);
    add(2, 1, 0, kModeHead, 0, 1, t + 1, 0);
    add(2, 7, 8, kModeSkip, 0, 1, per_source(), 0);
    add(3, 1, 0, kModeHead, 1, 1, 31, 2);
    add(3, 1, 1, kModeHead, 1, 0, 31, 0);
    add(4, 2, 0, kModeHead, 1, 0, 31, 0);
    add(3, 7, 0, kModeSkip, 1, 0, per_source(), 0);
    add(3, 7, 1, kModeSkip, 1, 0, 14 + 2 * l, 0);
    add(4, 4, 0, kModeSkip, 0, 0, 31, 3);
    add(4, 3, 0, kModeContinue, 0, 1, 31, 0);
    add(4, 7, 1, kModeSkip, 0, 1, 31, 0);
    add(5, 16, 0, kModePlain, 0, 1, 31, 0);
    add(6, 24, 0, kModePlain, 0, 1, t + 3, 0);
    add(6, 16, 24, kModePlain, 0, 1, t + 4, 0);
    add(6, 16, 40, kModePlain, 0, 1, t + 5, l ? 0 : 4);
  }
}

typedef CUresult (*EncodeTiledFn)(CUtensorMap*, CUtensorMapDataType, cuuint32_t, void*, const cuuint64_t*,
                                  const cuuint64_t*, const cuuint32_t*, const cuuint32_t*, CUtensorMapInterleave,
                                  CUtensorMapSwizzle, CUtensorMapL2promotion, CUtensorMapFloatOOBfill);

CUtensorMap make_map(EncodeTiledFn enc, const void* p, int rank, const cuuint64_t* dims, const cuuint64_t* strides,
                     const cuuint32_t* box, CUtensorMapSwizzle swizzle = CU_TENSOR_MAP_SWIZZLE_128B,
                     CUtensorMapL2promotion promo = CU_TENSOR_MAP_L2_PROMOTION_L2_128B) {
  CUtensorMap m;
  const cuuint32_t es[5] = {1, 1, 1, 1, 1};
  enc(&m, CU_TENSOR_MAP_DATA_TYPE_BFLOAT16, rank, const_cast<void*>(p), dims, strides, box, es,
      CU_TENSOR_MAP_INTERLEAVE_NONE, swizzle, promo,
      CU_TENSOR_MAP_FLOAT_OOB_FILL_NONE);
  return m;
}

CUtensorMap weight_map(EncodeTiledFn enc, const void* p, int k, int n, int blocks) {
  const cuuint64_t dims[3] = {64, (cuuint64_t)k, (cuuint64_t)n / 64};
  const cuuint64_t strides[2] = {(cuuint64_t)n * 2, 128};
  const cuuint32_t box[3] = {64, 32, (cuuint32_t)blocks};
  return make_map(enc, p, 3, dims, strides, box, CU_TENSOR_MAP_SWIZZLE_128B, CU_TENSOR_MAP_L2_PROMOTION_L2_256B);
}

CUtensorMap slab_map(EncodeTiledFn enc, const void* p, int n, int cols, int rows) {
  const cuuint64_t dims[2] = {(cuuint64_t)n, kD};
  const cuuint64_t strides[1] = {(cuuint64_t)n * 2};
  const cuuint32_t box[2] = {(cuuint32_t)cols, (cuuint32_t)rows};
  return make_map(enc, p, 2, dims, strides, box, CU_TENSOR_MAP_SWIZZLE_NONE);
}

CUtensorMap token_map(EncodeTiledFn enc, const void* p, int rows) {
  const cuuint64_t dims[2] = {2 * kD, 1024};
  const cuuint64_t strides[1] = {4 * kD};
  const cuuint32_t box[2] = {64, (cuuint32_t)rows};
  return make_map(enc, p, 2, dims, strides, box);
}

}

extern "C" void kernel_launch(void* const* d_in, const int* in_sizes, int n_in, void* d_out, int out_size) {
  (void)in_sizes; (void)n_in; (void)out_size;
  static EncodeTiledFn enc = nullptr;
  if (!enc) {
    void* fn = nullptr;
    cudaDriverEntryPointQueryResult q;
    cudaGetDriverEntryPoint("cuTensorMapEncodeTiled", &fn, cudaEnableDefault, &q);
    enc = (EncodeTiledFn)fn;
    cudaFuncSetAttribute(fused_layers_kernel, cudaFuncAttributeMaxDynamicSharedMemorySize, kSmBytes);
  }
  Params prm;
  prm.b1 = (const __nv_bfloat16*)d_in[5];
  prm.b2 = (const __nv_bfloat16*)d_in[7];
  build_segments(prm.seg);
  const cuuint64_t qd[3] = {kD, kD, 3}, qs[2] = {3 * kD * 2, kD * 2};
  const cuuint32_t qb[3] = {64, 32, 3};
  const CUtensorMap map_x = token_map(enc, d_in[0], 128);
  const CUtensorMap map_out = token_map(enc, d_out, 64);
  const CUtensorMap map_qkv = make_map(enc, d_in[1], 3, qd, qs, qb);
  const CUtensorMap map_wo = weight_map(enc, d_in[2], kD, kD, 2);
  const CUtensorMap map_w1a = weight_map(enc, d_in[4], kD, kF, 3);
  const CUtensorMap map_w1b = weight_map(enc, d_in[4], kD, kF, 2);
  const CUtensorMap map_w2 = weight_map(enc, d_in[6], kF, kD, 2);
  fused_layers_kernel<<<kGrid, 384, kSmBytes>>>(map_x, map_out, map_qkv, map_wo, map_w1a, map_w1b, map_w2,
                                                slab_map(enc, d_in[1], 3 * kD, 128, 128), slab_map(enc, d_in[4], kF, 128, 128),
                                                slab_map(enc, d_in[1], 3 * kD, 16, 128), prm);
}
```

```cpp
#include <cuda.h>
#include <cuda_bf16.h>
#include <cuda_runtime.h>
#include <stdint.h>

namespace {

constexpr int kD = 1024;
constexpr int kF = 3584;
constexpr int kCtas = 128;
constexpr int kGrid = 132;
constexpr int kTiles = 14;
constexpr int kTileBytes = 16384;

constexpr int kSmRing = 0;
constexpr int kSmX = 163840;
constexpr int kSmStg = kSmX + 32768;
constexpr int kSmHalo = kSmStg + 16384;
constexpr int kSmCsQ = kSmHalo + 6144;
constexpr int kSmV1 = kSmCsQ + 384 * 4;
constexpr int kSmB2 = kSmV1 + 448 * 8;
constexpr int kSmStat = kSmB2 + 128 * 4;
constexpr int kSmBar = kSmStat + 128 * 8;
constexpr int kBarFull = kSmBar;
constexpr int kBarTurn = kBarFull + 8 * 8;
constexpr int kBarReady = kBarTurn + 14 * 8;
constexpr int kBarSrc = kBarReady + 17 * 8;
constexpr int kBarPause = kBarSrc + 8 * 8;
constexpr int kBarFree = kBarPause + 4 * 8;
constexpr int kBarCs = kBarFree + 14 * 8;
constexpr int kBarSlab = kBarCs + 3 * 8;
constexpr int kBarHalo = kBarSlab + 4 * 8;
constexpr int kBarInit = kBarHalo + 12 * 8;
constexpr int kBarEpoch = kBarInit + 8;
constexpr int kBarEmpty = kBarTurn + 5 * 128;
constexpr int kBarEpi = kBarEmpty + 128;
constexpr int kBarX = kBarEpi + 14 * 8;
constexpr int kBarStat = kBarX + 8 * 8;
constexpr int kBarResume = kBarStat + 4 * 8;
constexpr int kSmEpoch = kBarEpi + 2 * 128;
static_assert(kBarEpoch < kBarEmpty && kBarResume + 4 * 8 <= kSmEpoch, "barrier groups overflow");
constexpr int kSmBytes = kSmEpoch + 16 + 256;
constexpr int kSegs = 40;

constexpr float kXScale = 1.f / 8.f;

constexpr unsigned kSpinLimit = 1u << 22;

__device__ __align__(1024) uint8_t g_x[16 * 16 * kTileBytes];
__device__ __align__(1024) uint8_t g_o[16 * 16 * kTileBytes];
__device__ __align__(1024) uint8_t g_h[16 * 56 * kTileBytes];
__device__ __align__(128) uint2 g_stat[16 * 8 * 128];
__device__ __align__(128) unsigned g_cs[3 * kD + kF + 3 * kD];
__device__ __align__(128) uint4 g_halo[2 * 16 * 16 * 256];
__device__ __align__(128) unsigned g_flag[16 * 32];
__device__ unsigned g_ticket;

#define TRACE_AT(tile, k)
#define TRACE_PUB(i, k, c)
#define TRACE_ISSUE(which, nb)

struct Params {
  const __nv_bfloat16* b1;
  const __nv_bfloat16* b2;
  uint32_t seg[kSegs];
};

__device__ __forceinline__ uint32_t smem_u32(const void* p) {
  return (uint32_t)__cvta_generic_to_shared(p);
}
__device__ __forceinline__ uint32_t mapa(uint32_t a, uint32_t cta) {
  uint32_t r;
  asm("mapa.shared::cluster.u32 %0, %1, %2;" : "=r"(r) : "r"(a), "r"(cta));
  return r;
}
__device__ __forceinline__ void mbar_init(uint32_t bar, int cnt) {
  asm volatile("mbarrier.init.shared::cta.b64 [%0], %1;" ::"r"(bar), "r"(cnt) : "memory");
}
__device__ __forceinline__ void mbar_expect_tx(uint32_t bar, uint32_t bytes) {
  asm volatile("mbarrier.arrive.expect_tx.shared::cta.b64 _, [%0], %1;" ::"r"(bar), "r"(bytes) : "memory");
}
__device__ __forceinline__ void mbar_arrive(uint32_t bar) {
  asm volatile("mbarrier.arrive.shared::cta.b64 _, [%0];" ::"r"(bar) : "memory");
}
__device__ __forceinline__ void mbar_arrive_cluster(uint32_t cluster_addr) {
  asm volatile("mbarrier.arrive.shared::cluster.b64 _, [%0];" ::"r"(cluster_addr) : "memory");
}
__device__ __forceinline__ void mbar_wait(uint32_t bar, uint32_t parity) {
  asm volatile("{\n.reg .pred p;\nRETRY:\nmbarrier.try_wait.parity.shared::cta.b64 p, [%0], %1;\n"
               "@!p bra.uni RETRY;\n}" ::"r"(bar), "r"(parity) : "memory");
}
__device__ __forceinline__ void mbar_wait_bounded(uint32_t bar, uint32_t parity) {
  asm volatile("{\n.reg .pred p;\n.reg .u32 c;\nmov.u32 c, 0;\nRETRY:\n"
               "mbarrier.try_wait.parity.shared::cta.b64 p, [%0], %1;\n@p bra.uni DONE;\n"
               "add.u32 c, c, 1;\nsetp.lt.u32 p, c, %2;\n@p bra.uni RETRY;\ntrap;\nDONE:\n}"
               ::"r"(bar), "r"(parity), "n"(1u << 19) : "memory");
}
__device__ __forceinline__ void tma3d(uint32_t dst, const CUtensorMap* m, uint32_t bar, int c0, int c1, int c2) {
  asm volatile(
      "cp.async.bulk.tensor.3d.shared::cluster.global.mbarrier::complete_tx::bytes [%0], [%1, {%3, %4, %5}], [%2];"
      ::"r"(dst), "l"(m), "r"(bar), "r"(c0), "r"(c1), "r"(c2) : "memory");
}
__device__ __forceinline__ void tma3d_mc(uint32_t dst, const CUtensorMap* m, uint32_t bar, int c0, int c1, int c2) {
  asm volatile(
      "cp.async.bulk.tensor.3d.shared::cluster.global.mbarrier::complete_tx::bytes.multicast::cluster"
      " [%0], [%1, {%3, %4, %5}], [%2], %6;"
      ::"r"(dst), "l"(m), "r"(bar), "r"(c0), "r"(c1), "r"(c2), "h"((uint16_t)3) : "memory");
}
__device__ __forceinline__ void tma2d(uint32_t dst, const CUtensorMap* m, uint32_t bar, int c0, int c1) {
  asm volatile(
      "cp.async.bulk.tensor.2d.shared::cluster.global.mbarrier::complete_tx::bytes [%0], [%1, {%3, %4}], [%2];"
      ::"r"(dst), "l"(m), "r"(bar), "r"(c0), "r"(c1) : "memory");
}
__device__ __forceinline__ void tma2d_store(const CUtensorMap* m, uint32_t src, int c0, int c1) {
  asm volatile("cp.async.bulk.tensor.2d.global.shared::cta.bulk_group [%0, {%2, %3}], [%1];"
               ::"l"(m), "r"(src), "r"(c0), "r"(c1) : "memory");
}
__device__ __forceinline__ int lane_id() {
  int l;
  asm volatile("mov.u32 %0, %%laneid;" : "=r"(l));
  return l;
}
__device__ __forceinline__ bool elect() {
  uint32_t p;
  asm volatile("{\n.reg .pred p;\nelect.sync _|p, 0xffffffff;\nselp.b32 %0, 1, 0, p;\n}" : "=r"(p));
  return p;
}
__device__ __forceinline__ void bulk_load(uint32_t dst, const void* src, uint32_t bytes, uint32_t bar) {
  asm volatile("cp.async.bulk.shared::cluster.global.mbarrier::complete_tx::bytes [%0], [%1], %2, [%3];"
               ::"r"(dst), "l"(src), "r"(bytes), "r"(bar) : "memory");
}
__device__ __forceinline__ void bulk_store(void* dst, uint32_t src, uint32_t bytes) {
  asm volatile("cp.async.bulk.global.shared::cta.bulk_group [%0], [%1], %2;" ::"l"(dst), "r"(src), "r"(bytes)
               : "memory");
}
__device__ __forceinline__ void bulk_commit() { asm volatile("cp.async.bulk.commit_group;" ::: "memory"); }
__device__ __forceinline__ void bulk_wait_read() { asm volatile("cp.async.bulk.wait_group.read 0;" ::: "memory"); }
__device__ __forceinline__ void bulk_wait() { asm volatile("cp.async.bulk.wait_group 0;" ::: "memory"); }
__device__ __forceinline__ void fence_async_smem() { asm volatile("fence.proxy.async.shared::cta;" ::: "memory"); }
__device__ __forceinline__ unsigned ld_relaxed(const unsigned* p) {
  unsigned v;
  asm volatile("ld.relaxed.gpu.global.u32 %0, [%1];" : "=r"(v) : "l"(p) : "memory");
  return v;
}
__device__ __forceinline__ uint2 ld_relaxed64(const uint2* p) {
  uint2 v;
  asm volatile("{\n.reg .b64 t;\nld.relaxed.gpu.global.b64 t, [%2];\nmov.b64 {%0, %1}, t;\n}"
               : "=r"(v.x), "=r"(v.y) : "l"(p) : "memory");
  return v;
}
__device__ __forceinline__ void st_relaxed(unsigned* p, unsigned v) {
  asm volatile("st.relaxed.gpu.global.u32 [%0], %1;" ::"l"(p), "r"(v) : "memory");
}
__device__ __forceinline__ void st_release(unsigned* p, unsigned v) {
  asm volatile("st.release.gpu.global.u32 [%0], %1;" ::"l"(p), "r"(v) : "memory");
}
__device__ __forceinline__ void wait_flags(const unsigned* p, unsigned count) {
  while (__any_sync(0xffffffffu, (int)(ld_relaxed(p) - count) < 0)) {
    __nanosleep(400);
  }
  asm volatile("fence.acquire.gpu;\nfence.proxy.async.global;" ::: "memory");
  __syncwarp();
}
__device__ __forceinline__ void st_packet(uint4* p, uint32_t d0, uint32_t d1, uint32_t tag) {
  asm volatile("{\n.reg .b128 v;\n.reg .b64 x, y;\nmov.b64 x, {%1, %2};\nmov.b64 y, {%3, %3};\nmov.b128 v, {x, y};\n"
               "st.relaxed.gpu.global.b128 [%0], v;\n}" ::"l"(p), "r"(d0), "r"(d1), "r"(tag) : "memory");
}
__device__ __forceinline__ void ld_packet(const uint4* p, uint32_t& d0, uint32_t& d1, uint32_t& tag) {
  asm volatile("{\n.reg .b128 v;\n.reg .b64 x, y;\n.reg .b32 u;\nld.relaxed.gpu.global.b128 v, [%3];\n"
               "mov.b128 {x, y}, v;\nmov.b64 {%0, %1}, x;\nmov.b64 {%2, u}, y;\n}"
               : "=r"(d0), "=r"(d1), "=r"(tag) : "l"(p) : "memory");
}
__device__ __forceinline__ uint2 ld_relaxed_pair(const uint2* p) {
  uint2 v;
  asm volatile("ld.relaxed.gpu.global.v2.u32 {%0, %1}, [%2];" : "=r"(v.x), "=r"(v.y) : "l"(p) : "memory");
  return v;
}
__device__ __forceinline__ unsigned tag_value(float v, unsigned epoch) {
  return (__float_as_uint(v) & ~7u) | (epoch & 7u);
}
__device__ __forceinline__ float untag_value(unsigned v) { return __uint_as_float(v & ~7u); }
__device__ __forceinline__ void stsm4(uint32_t a, uint32_t r0, uint32_t r1, uint32_t r2, uint32_t r3) {
  asm volatile("stmatrix.sync.aligned.m8n8.x4.shared.b16 [%0], {%1, %2, %3, %4};" ::"r"(a), "r"(r0), "r"(r1),
               "r"(r2), "r"(r3) : "memory");
}
__device__ __forceinline__ void stsm4_t(uint32_t a, uint32_t r0, uint32_t r1, uint32_t r2, uint32_t r3) {
  asm volatile("stmatrix.sync.aligned.m8n8.x4.trans.shared.b16 [%0], {%1, %2, %3, %4};" ::"r"(a), "r"(r0),
               "r"(r1), "r"(r2), "r"(r3) : "memory");
}
__device__ __forceinline__ uint32_t transpose8(uint32_t a) {
  uint32_t d;
  asm volatile("movmatrix.sync.aligned.m8n8.trans.b16 %0, %1;" : "=r"(d) : "r"(a));
  return d;
}
__device__ __forceinline__ void mma16816(float (&c)[4], uint32_t a0, uint32_t a1, uint32_t a2, uint32_t a3,
                                         uint32_t b0, uint32_t b1) {
  asm volatile("mma.sync.aligned.m16n8k16.row.col.f32.bf16.bf16.f32 {%0, %1, %2, %3}, {%4, %5, %6, %7}, {%8, %9}, "
               "{%0, %1, %2, %3};"
               : "+f"(c[0]), "+f"(c[1]), "+f"(c[2]), "+f"(c[3])
               : "r"(a0), "r"(a1), "r"(a2), "r"(a3), "r"(b0), "r"(b1));
}
__device__ __forceinline__ void mma1688(float (&c)[4], uint32_t a0, uint32_t a1, uint32_t b0) {
  asm volatile("mma.sync.aligned.m16n8k8.row.col.f32.bf16.bf16.f32 {%0, %1, %2, %3}, {%4, %5}, {%6}, {%0, %1, %2, %3};"
               : "+f"(c[0]), "+f"(c[1]), "+f"(c[2]), "+f"(c[3]) : "r"(a0), "r"(a1), "r"(b0));
}
__device__ __forceinline__ float shfl_xor(float v, int m) {
  float r;
  asm volatile("shfl.sync.bfly.b32 %0, %1, %2, 31, 0xffffffff;" : "=f"(r) : "f"(v), "r"(m));
  return r;
}
__device__ __forceinline__ float tanh_fast(float x) {
  float r;
  asm volatile("tanh.approx.f32 %0, %1;" : "=f"(r) : "f"(x));
  return r;
}
__device__ __forceinline__ void ldsm4(uint32_t a, uint32_t (&r)[4]) {
  asm volatile("ldmatrix.sync.aligned.m8n8.x4.shared.b16 {%0, %1, %2, %3}, [%4];"
               : "=r"(r[0]), "=r"(r[1]), "=r"(r[2]), "=r"(r[3]) : "r"(a) : "memory");
}
__device__ __forceinline__ void ldsm4_t(uint32_t a, uint32_t (&r)[4]) {
  asm volatile("ldmatrix.sync.aligned.m8n8.x4.trans.shared.b16 {%0, %1, %2, %3}, [%4];"
               : "=r"(r[0]), "=r"(r[1]), "=r"(r[2]), "=r"(r[3]) : "r"(a) : "memory");
}
__device__ __forceinline__ uint32_t pack2(float lo, float hi) {
  uint32_t r;
  asm volatile("cvt.rn.bf16x2.f32 %0, %1, %2;" : "=r"(r) : "f"(hi), "f"(lo));
  return r;
}
__device__ __forceinline__ float bf_lo(uint32_t r) { return __uint_as_float(r << 16); }
__device__ __forceinline__ float bf_hi(uint32_t r) { return __uint_as_float(r & 0xffff0000u); }
__device__ __forceinline__ float ex2(float x) {
  float r;
  asm("ex2.approx.ftz.f32 %0, %1;" : "=f"(r) : "f"(x));
  return r;
}
__device__ __forceinline__ float rcp(float x) {
  float r;
  asm("rcp.approx.ftz.f32 %0, %1;" : "=f"(r) : "f"(x));
  return r;
}
template <int N>
__device__ __forceinline__ void wg_wait() {
  asm volatile("wgmma.wait_group.sync.aligned %0;" ::"n"(N) : "memory");
}
__device__ __forceinline__ void yield_slot() { asm volatile("pmevent 0;"); }

template <int N, int KIND>
__device__ __forceinline__ void mma_kblock(float (&acc)[2][96], uint32_t a, uint32_t b);

#define F8(m, d, i) m(d[i]), m(d[i + 1]), m(d[i + 2]), m(d[i + 3]), m(d[i + 4]), m(d[i + 5]), m(d[i + 6]), m(d[i + 7])
#define KSTEP(N, A, B, oa0, oa1, ob, sd)                                                   \
  "mov.b64 db, {" B ", hb};\nadd.u64 db, db, " #ob ";\n"                                    \
  "mov.b64 da, {" A ", ha};\nadd.u64 da, da, " #oa0 ";\n"                                   \
  "wgmma.mma_async.sync.aligned.m64n" #N "k16.f32.bf16.bf16 {" ACC##N##_0 "}, da, db, " #sd ", 1, 1, 0, 1;\n" \
  "mov.b64 da, {" A ", ha};\nadd.u64 da, da, " #oa1 ";\n"                                   \
  "wgmma.mma_async.sync.aligned.m64n" #N "k16.f32.bf16.bf16 {" ACC##N##_1 "}, da, db, " #sd ", 1, 1, 0, 1;\n"

#define MMA_KBLOCK(N, KIND, A, B, ob2, ob3, sd, MID, MODE)                                 \
  template <>                                                                              \
  __device__ __forceinline__ void mma_kblock<N, KIND>(float (&acc)[2][96], uint32_t a, uint32_t b) { \
    asm volatile("{\n.reg .b32 ha, hb;\n.reg .b64 da, db;\n"                            \
                 "mov.b32 ha, 0x40000080;\nmov.b32 hb, 0x40000040;\n"                       \
                 "wgmma.fence.sync.aligned;\n"                                             \
                 KSTEP(N, A, B, 0, 64, 0, sd) KSTEP(N, A, B, 2, 66, 128, 1) MID               \
                 KSTEP(N, A, B, 4, 68, ob2, 1) KSTEP(N, A, B, 6, 70, ob3, 1) "wgmma.commit_group.sync.aligned;\n}\n"  \
                 : OPS##N(MODE) : "r"(a), "r"(b) : "memory");                              \
  }
#define MMA_KBLOCKS(N, A, B, ob2, ob3)                                                     \
  MMA_KBLOCK(N, 0, A, B, ob2, ob3, 1, "", "+f")                                            \
  MMA_KBLOCK(N, 1, A, B, ob2, ob3, 1, "wgmma.commit_group.sync.aligned;\n", "+f")          \
  MMA_KBLOCK(N, 2, A, B, ob2, ob3, 0, "", "=f")

#define ACC128_0 \
  "%0, %1, %2, %3, %4, %5, %6, %7, %8, %9, %10, %11, %12, %13, %14, %15, " \
  "%16, %17, %18, %19, %20, %21, %22, %23, %24, %25, %26, %27, %28, %29, %30, %31, " \
  "%32, %33, %34, %35, %36, %37, %38, %39, %40, %41, %42, %43, %44, %45, %46, %47, " \
  "%48, %49, %50, %51, %52, %53, %54, %55, %56, %57, %58, %59, %60, %61, %62, %63"
#define ACC128_1 \
  "%64, %65, %66, %67, %68, %69, %70, %71, %72, %73, %74, %75, %76, %77, %78, %79, " \
  "%80, %81, %82, %83, %84, %85, %86, %87, %88, %89, %90, %91, %92, %93, %94, %95, " \
  "%96, %97, %98, %99, %100, %101, %102, %103, %104, %105, %106, %107, %108, %109, %110, %111, " \
  "%112, %113, %114, %115, %116, %117, %118, %119, %120, %121, %122, %123, %124, %125, %126, %127"
#define OPS128(m) \
  F8(m, acc[0], 0), F8(m, acc[0], 8), F8(m, acc[0], 16), F8(m, acc[0], 24), F8(m, acc[0], 32), F8(m, acc[0], 40), F8(m, acc[0], 48), F8(m, acc[0], 56), \
        F8(m, acc[1], 0), F8(m, acc[1], 8), F8(m, acc[1], 16), F8(m, acc[1], 24), F8(m, acc[1], 32), F8(m, acc[1], 40), F8(m, acc[1], 48), F8(m, acc[1], 56)
MMA_KBLOCKS(128, "%128", "%129", 512, 640)

#define ACC192_0 \
  "%0, %1, %2, %3, %4, %5, %6, %7, %8, %9, %10, %11, %12, %13, %14, %15, " \
  "%16, %17, %18, %19, %20, %21, %22, %23, %24, %25, %26, %27, %28, %29, %30, %31, " \
  "%32, %33, %34, %35, %36, %37, %38, %39, %40, %41, %42, %43, %44, %45, %46, %47, " \
  "%48, %49, %50, %51, %52, %53, %54, %55, %56, %57, %58, %59, %60, %61, %62, %63, " \
  "%64, %65, %66, %67, %68, %69, %70, %71, %72, %73, %74, %75, %76, %77, %78, %79, " \
  "%80, %81, %82, %83, %84, %85, %86, %87, %88, %89, %90, %91, %92, %93, %94, %95"
#define ACC192_1 \
  "%96, %97, %98, %99, %100, %101, %102, %103, %104, %105, %106, %107, %108, %109, %110, %111, " \
  "%112, %113, %114, %115, %116, %117, %118, %119, %120, %121, %122, %123, %124, %125, %126, %127, " \
  "%128, %129, %130, %131, %132, %133, %134, %135, %136, %137, %138, %139, %140, %141, %142, %143, " \
  "%144, %145, %146, %147, %148, %149, %150, %151, %152, %153, %154, %155, %156, %157, %158, %159, " \
  "%160, %161, %162, %163, %164, %165, %166, %167, %168, %169, %170, %171, %172, %173, %174, %175, " \
  "%176, %177, %178, %179, %180, %181, %182, %183, %184, %185, %186, %187, %188, %189, %190, %191"
#define OPS192(m) \
  F8(m, acc[0], 0), F8(m, acc[0], 8), F8(m, acc[0], 16), F8(m, acc[0], 24), F8(m, acc[0], 32), F8(m, acc[0], 40), F8(m, acc[0], 48), F8(m, acc[0], 56), F8(m, acc[0], 64), F8(m, acc[0], 72), F8(m, acc[0], 80), F8(m, acc[0], 88), \
        F8(m, acc[1], 0), F8(m, acc[1], 8), F8(m, acc[1], 16), F8(m, acc[1], 24), F8(m, acc[1], 32), F8(m, acc[1], 40), F8(m, acc[1], 48), F8(m, acc[1], 56), F8(m, acc[1], 64), F8(m, acc[1], 72), F8(m, acc[1], 80), F8(m, acc[1], 88)
MMA_KBLOCKS(192, "%192", "%193", 768, 896)

#define HSTEP(oa, ob)                                                                       \
  "mov.b64 db, {%97, hb};\nadd.u64 db, db, " #ob ";\nmov.b64 da, {%96, ha};\nadd.u64 da, da, " #oa ";\n" \
  "wgmma.mma_async.sync.aligned.m64n192k16.f32.bf16.bf16 {" ACC192_0 "}, da, db, 1, 1, 1, 0, 1;\n"
__device__ __forceinline__ void mma_half(float (&d)[96], uint32_t a, uint32_t b) {
  asm volatile("{\n.reg .b32 ha, hb;\n.reg .b64 da, db;\nmov.b32 ha, 0x40000080;\nmov.b32 hb, 0x40000040;\n"
               "wgmma.fence.sync.aligned;\n" HSTEP(0, 0) HSTEP(2, 128) HSTEP(4, 768) HSTEP(6, 896)
               "wgmma.commit_group.sync.aligned;\n}\n"
               : F8("+f", d, 0), F8("+f", d, 8), F8("+f", d, 16), F8("+f", d, 24), F8("+f", d, 32), F8("+f", d, 40),
                 F8("+f", d, 48), F8("+f", d, 56), F8("+f", d, 64), F8("+f", d, 72), F8("+f", d, 80), F8("+f", d, 88)
               : "r"(a), "r"(b) : "memory");
}

#define TSTEP(REGS, W, X, ow, ox)                                                           \
  "mov.b64 db, {" X ", hi};\nadd.u64 db, db, " #ox ";\nmov.b64 da, {" W ", hi};\nadd.u64 da, da, " #ow ";\n" \
  "wgmma.mma_async.sync.aligned.m64n128k16.f32.bf16.bf16 {" REGS "}, da, db, 1, 1, 1, 1, 0;\n"
#define THEAD "{\n.reg .b32 hi;\n.reg .b64 da, db;\nmov.b32 hi, 0x40000040;\nwgmma.fence.sync.aligned;\n"
#define TTAIL "wgmma.commit_group.sync.aligned;\n}\n"
__device__ __forceinline__ void mma_kblock_t(float (&acc)[2][96], uint32_t wd, uint32_t xd) {
  asm volatile(THEAD TSTEP(ACC128_0, "%128", "%129", 0, 0) TSTEP(ACC128_1, "%128", "%129", 256, 0)
               TSTEP(ACC128_0, "%128", "%129", 128, 2) TSTEP(ACC128_1, "%128", "%129", 384, 2)
               TSTEP(ACC128_0, "%128", "%129", 512, 4) TSTEP(ACC128_1, "%128", "%129", 768, 4)
               TSTEP(ACC128_0, "%128", "%129", 640, 6) TSTEP(ACC128_1, "%128", "%129", 896, 6) TTAIL
               : OPS128("+f") : "r"(wd), "r"(xd) : "memory");
}
__device__ __forceinline__ void mma_half_t(float (&d)[96], uint32_t wd, uint32_t xd) {
  asm volatile(THEAD TSTEP(ACC128_0, "%64", "%65", 0, 0) TSTEP(ACC128_0, "%64", "%65", 128, 2)
               TSTEP(ACC128_0, "%64", "%65", 512, 4) TSTEP(ACC128_0, "%64", "%65", 640, 6) TTAIL
               : F8("+f", d, 0), F8("+f", d, 8), F8("+f", d, 16), F8("+f", d, 24), F8("+f", d, 32), F8("+f", d, 40),
                 F8("+f", d, 48), F8("+f", d, 56) : "r"(wd), "r"(xd) : "memory");
}

enum { kModePlain = 0, kModeHead = 1, kModeSkip = 2, kModeContinue = 3 };

template <int N>
__device__ __forceinline__ void fence_acc(float (&acc)[2][96]) {
#pragma unroll
  for (int h = 0; h < 2; h++)
#pragma unroll
    for (int i = 0; i < N / 2; i++) asm volatile("" : "+f"(acc[h][i])::"memory");
}

constexpr uint32_t kToB = (kTileBytes >> 4) + ((4096u >> 4) << 16) - (1u << 16);

#define TRACE_KB(nb)

template <int N>
__device__ __forceinline__ void head_blocks(float (&acc)[2][96], uint32_t sb, int n0, int slot, int xver,
                                            uint32_t rel_addr, bool rel) {
  const uint32_t ring = (((sb & 0x3FFFF) + kSmRing) >> 4) | (1u << 16);
  const uint32_t xdesc = (((sb & 0x3FFFF) + kSmX) >> 4) | (1u << 16);
  const uint32_t s0 = ring + slot * 2560, s1 = ring + ((slot + 1) & 3) * 2560;
  const uint32_t to_b = xver > 0 ? kToB - (kTileBytes >> 4) : kToB;
  const uint32_t nb = n0 * 8, xbar = sb + kBarX + (xver - 1) * 16;
  if (xver > 0) {
    mbar_wait(xbar, 0);
    mbar_wait(sb + kBarTurn + (xver == 1 ? 2 : 3 * xver) * 8, 0);
  }
  mbar_wait(sb + kBarFull + (nb & 56), nb >> 6);
  if (n0 == 0) TRACE_AT(0, 1);
  TRACE_KB(nb);
  mma_kblock<N, 2>(acc, xver > 0 ? xdesc : s0, s0 + to_b);
  if (xver > 0) mbar_wait(xbar + 8, 0);
  mbar_wait(sb + kBarFull + (nb & 56) + 8, nb >> 6);
  TRACE_KB(nb + 8);
  mma_kblock<N, 0>(acc, xver > 0 ? xdesc + (kTileBytes >> 4) : s1, s1 + to_b);
  wg_wait<1>();
  if (rel) mbar_arrive_cluster(rel_addr + (nb & 56));
  wg_wait<0>();
  if (rel) mbar_arrive_cluster(rel_addr + (nb & 56) + 8);
  fence_acc<N>(acc);
}

enum { kPlain, kResid, kStagger };
template <int N, int KIND, class Pre>
__device__ __forceinline__ void mainloop(float (&acc)[2][96], uint32_t sb, int tile, int n0, int slot, int nkb,
                                         int pause_kk, int att, uint32_t rel_addr, bool rel, int own_kk, Pre pre,
                                         uint32_t prev = 64) {
  constexpr bool RESID = KIND == kResid;
  constexpr uint32_t kStep = (N == 192 ? 5 : 4) * 512;
  const uint32_t ring = (((sb & 0x3FFFF) + kSmRing) >> 4) | (1u << 16);
  uint32_t st = ring + slot * kStep;
  uint32_t nb = n0 * 8;
  const uint32_t last = nb + 8 * (nkb - (RESID ? 4 : KIND == kStagger ? 2 : 1)), own = nb + 8 * own_kk;
  const uint32_t stg = (((sb & 0x3FFFF) + kSmStg) >> 4) | (1u << 16);
  uint32_t stop = pause_kk >= 0 ? nb + 8 * pause_kk : last;
  const bool signal = (threadIdx.x & 127) == 64;
  fence_acc<N>(acc);
  if (tile > 0) mbar_wait(sb + kBarTurn + (tile - 1) * 8, 0);
  TRACE_AT(tile, 0);
#pragma unroll 1
  while (true) {
#pragma unroll 1
    do {
      mbar_wait(sb + kBarFull + (nb & 56), nb >> 6);
      TRACE_KB(nb);
      if constexpr (RESID) mma_kblock_t(acc, st + kToB, nb == own ? stg : st);
      else mma_kblock<N, 0>(acc, st, st + kToB);
      wg_wait<1>();
      if (rel) mbar_arrive_cluster(rel_addr + prev);
      prev = nb & 56;
      st += kStep;
      if (st == ring + 10240) st = ring;
      nb += 8;
    } while (nb != stop);
    if (stop == last) break;
    stop = last;
    if (signal) mbar_arrive(sb + kBarPause + att * 8);
    wg_wait<0>();
    if (rel) mbar_arrive_cluster(rel_addr + prev);
    prev = 64;
    mbar_wait(sb + kBarResume + att * 8, 0);
  }
  mbar_wait(sb + kBarFull + (nb & 56), nb >> 6);
  TRACE_KB(nb);
  if constexpr (RESID) {
    const uint32_t z = gridDim.y - 1;
    const uint32_t s1 = st + kStep, s2 = s1 + kStep, s3 = s2 == ring + 8192 ? ring : s2 + kStep;
    mma_half_t(acc[0], st + kToB, st);
    wg_wait<1>();
    if (rel) mbar_arrive_cluster(rel_addr + 24);
    mbar_wait(sb + kBarFull + 40, nb >> 6);
    TRACE_KB(nb + 8);
    mma_half_t(acc[0], s1 + kToB, s1);
    mbar_wait(sb + kBarFull + 48, nb >> 6);
    TRACE_KB(nb + 16);
    mma_half_t(acc[0], s2 + kToB, s2);
    mbar_wait(sb + kBarFull + 56, nb >> 6);
    TRACE_KB(nb + 24);
    mma_half_t(acc[0], s3 + kToB, s3);
    mma_half_t(acc[1], st + kToB + 256, st + z);
    mma_half_t(acc[1], s1 + kToB + 256, s1 + z);
    wg_wait<2>();
#pragma unroll
    for (int i = 0; i < 64; i++) asm volatile("" : "+f"(acc[0][i])::"memory");
    pre(0);
    mma_half_t(acc[1], s2 + kToB + 256, s2 + z);
    wg_wait<2>();
    if (rel) mbar_arrive_cluster(rel_addr + 32);
    pre(1);
    mma_half_t(acc[1], s3 + kToB + 256, s3 + z);
    wg_wait<2>();
    if (rel) mbar_arrive_cluster(rel_addr + 40);
    wg_wait<1>();
    if (signal) mbar_arrive(sb + kBarTurn + tile * 8);
    if (rel) mbar_arrive_cluster(rel_addr + 48);
    wg_wait<0>();
    if (rel) mbar_arrive_cluster(rel_addr + 56);
#pragma unroll
    for (int i = 0; i < 64; i++) asm volatile("" : "+f"(acc[1][i])::"memory");
  } else if constexpr (KIND == kStagger) {
    const uint32_t z = gridDim.y - 1, s2 = st + kStep;
    mma_half(acc[1], st + 64, st + kToB);
    wg_wait<1>();
    if (rel) mbar_arrive_cluster(rel_addr + 40);
    mbar_wait(sb + kBarFull + 56, nb >> 6);
    TRACE_KB(nb + 8);
    mma_half(acc[1], s2 + 64, s2 + kToB);
    mma_half(acc[0], st, st + z + kToB);
    pre(0);
    mma_half(acc[0], s2, s2 + z + kToB);
    wg_wait<2>();
#pragma unroll
    for (int i = 0; i < 96; i++) asm volatile("" : "+f"(acc[1][i])::"memory");
    pre(1);
    wg_wait<1>();
    if (rel) mbar_arrive_cluster(rel_addr + 48);
    pre(2);
    if (signal) mbar_arrive(sb + kBarTurn + tile * 8);
    pre(3);
    wg_wait<0>();
    if (rel) mbar_arrive_cluster(rel_addr + 56);
#pragma unroll
    for (int i = 0; i < 96; i++) asm volatile("" : "+f"(acc[0][i])::"memory");
  } else {
    mma_kblock<N, 1>(acc, st, st + kToB);
    wg_wait<2>();
    if (rel) mbar_arrive_cluster(rel_addr + prev);
    pre();
    wg_wait<1>();
    if (signal) mbar_arrive(sb + kBarTurn + tile * 8);
    wg_wait<0>();
    if (rel) mbar_arrive_cluster(rel_addr + (nb & 56));
    fence_acc<N>(acc);
  }
}

__device__ __forceinline__ void publish_stats(uint32_t sb, uint2* stat, int w, int lane, unsigned epoch) {
  const uint32_t row = sb + kSmX + (32 * w + lane) * 128;
  float s[4], q[4];
#pragma unroll
  for (int c = 0; c < 4; c++) s[c] = q[c] = 0.f;
  uint32_t nx[4];
  ldsm4(row + ((lane & 7) << 4), nx);
#pragma unroll 1
  for (int J = 1; J <= 16; J++) {
    const uint32_t r[4] = {nx[0], nx[1], nx[2], nx[3]};
    ldsm4(row + ((J >> 3) & 1) * kTileBytes + (((J ^ lane) & 7) << 4), nx);
#pragma unroll
    for (int c = 0; c < 4; c++) {
      const float lo = bf_lo(r[c]);
      s[c] += lo;
      q[c] = fmaf(lo, lo, q[c]);
      if (c & 1) yield_slot();
    }
#pragma unroll
    for (int c = 0; c < 4; c++) {
      const float hi = bf_hi(r[c]);
      s[c] += hi;
      q[c] = fmaf(hi, hi, q[c]);
      if (c & 1) yield_slot();
    }
  }
  const int t = lane & 3, g = lane >> 2;
#pragma unroll
  for (int c = 0; c < 2; c++) {
    s[c] = (t & 2 ? s[c + 2] : s[c]) + shfl_xor(t & 2 ? s[c] : s[c + 2], 2);
    q[c] = (t & 2 ? q[c + 2] : q[c]) + shfl_xor(t & 2 ? q[c] : q[c + 2], 2);
  }
  const float so = (t & 1 ? s[1] : s[0]) + shfl_xor(t & 1 ? s[0] : s[1], 1);
  const float qo = (t & 1 ? q[1] : q[0]) + shfl_xor(t & 1 ? q[0] : q[1], 1);
  asm volatile("{\n.reg .b64 t;\nmov.b64 t, {%1, %2};\nst.relaxed.gpu.global.b64 [%0], t;\n}" ::"l"(stat + 32 * w + 8 * t + g),
               "r"(tag_value(so, epoch)), "r"(__float_as_uint(qo)) : "memory");
}

__device__ __forceinline__ void add_chunk(float (&a)[8], const uint4& v) {
  a[0] += bf_lo(v.x); a[1] += bf_hi(v.x);
  a[2] += bf_lo(v.y); a[3] += bf_hi(v.y);
  a[4] += bf_lo(v.z); a[5] += bf_hi(v.z);
  a[6] += bf_lo(v.w); a[7] += bf_hi(v.w);
}

__device__ __forceinline__ int helper_col(int id, int slab) {
  return (slab < 3 ? slab * kD : (slab - 3) * 512) + id * 128;
}
__device__ __forceinline__ void helper_cta(const CUtensorMap* map_q, const CUtensorMap* map_1, uint8_t* sm,
                                           uint32_t sb, int id, int warp) {
  constexpr int kRed = 6 * 32768, kBar = kRed + 2 * 4096;
  const int tid = threadIdx.x;
  if (warp == 8 && elect()) {
#pragma unroll
    for (int s = 0; s < 6; s++) {
      mbar_init(sb + kBar + s * 8, 1);
      mbar_init(sb + kBar + 64 + s * 8, 4);
    }
    fence_async_smem();
#pragma unroll
    for (int s = 0; s < 6; s++) {
      mbar_expect_tx(sb + kBar + s * 8, 32768);
      tma2d(sb + s * 32768, map_q, sb + kBar + s * 8, id * 128, s * 128);
    }
  }
  __syncthreads();
  if (warp == 8) {
    int slot = 0, ph = 0;
#pragma unroll 1
    for (int n = 6; n < 80; n++) {
      mbar_wait(sb + kBar + 64 + slot * 8, ph);
      if (elect()) {
        mbar_expect_tx(sb + kBar + slot * 8, 32768);
        tma2d(sb + slot * 32768, n < 24 ? map_q : map_1, sb + kBar + slot * 8, helper_col(id, n >> 3), (n & 7) * 128);
      }
      if (++slot == 6) slot = 0, ph ^= 1;
    }
  } else if (warp < 8) {
    if (tid == 0) *reinterpret_cast<unsigned*>(sm + kBar + 128) = atomicAdd(&g_ticket, 1u) / kGrid + 1;
    int slot = warp >> 2, ph = 0;
#pragma unroll 1
    for (int slab = 0; slab < 10; slab++) {
      float a[8];
#pragma unroll
      for (int e = 0; e < 8; e++) a[e] = 0.f;
#pragma unroll 1
      for (int box = 0; box < 4; box++) {
        mbar_wait_bounded(sb + kBar + slot * 8, ph);
        const uint4* p = reinterpret_cast<const uint4*>(sm + slot * 32768) + (tid & 127);
        uint4 v[16];
#pragma unroll
        for (int i = 0; i < 16; i++) v[i] = p[i * 128];
        __syncwarp();
        if (elect()) mbar_arrive(sb + kBar + 64 + slot * 8);
#pragma unroll
        for (int i = 0; i < 16; i++) add_chunk(a, v[i]);
        slot += 2;
        if (slot >= 6) slot -= 6, ph ^= 1;
      }
      float* red = reinterpret_cast<float*>(sm + kRed + (slab & 1) * 4096);
#pragma unroll
      for (int e = 0; e < 8; e++) a[e] += shfl_xor(a[e], 16);
      if ((tid & 16) == 0) {
        float4* d = reinterpret_cast<float4*>(red + warp * 128 + (tid & 15) * 8);
        d[0] = make_float4(a[0], a[1], a[2], a[3]);
        d[1] = make_float4(a[4], a[5], a[6], a[7]);
      }
      asm volatile("bar.sync 1, 256;" ::: "memory");
      if (warp < 4) {
        float t = 0.f;
#pragma unroll
        for (int q = 0; q < 8; q++) t += red[q * 128 + tid];
        st_relaxed(g_cs + (slab < 3 ? 0 : 3 * kD) + helper_col(id, slab) + tid,
                   tag_value(t, *reinterpret_cast<volatile unsigned*>(sm + kBar + 128)));
      }
    }
  }
}

__device__ __forceinline__ void colsum_strip(const CUtensorMap* map, uint8_t* sm, uint32_t sb, int col, int half,
                                             int lane, unsigned epoch) {
  const uint32_t bar = sb + kBarSlab + half * 16;
  const int buf = kSmStg + half * 8192;
  float a[8];
#pragma unroll
  for (int e = 0; e < 8; e++) a[e] = 0.f;
#pragma unroll 1
  for (int r = -2; r < 4; r++) {
    if (r >= 0) {
      mbar_wait(bar + (r & 1) * 8, r >> 1);
      const uint4* p = reinterpret_cast<const uint4*>(sm + buf + (r & 1) * 4096) + lane;
#pragma unroll 1
      for (int q = 0; q < 8; q += 4) {
        uint4 v[4];
#pragma unroll
        for (int u = 0; u < 4; u++) v[u] = p[(q + u) * 32];
#pragma unroll
        for (int u = 0; u < 4; u++) {
          a[0] += bf_lo(v[u].x); a[1] += bf_hi(v[u].x); a[2] += bf_lo(v[u].y); a[3] += bf_hi(v[u].y);
          yield_slot();
          a[4] += bf_lo(v[u].z); a[5] += bf_hi(v[u].z); a[6] += bf_lo(v[u].w); a[7] += bf_hi(v[u].w);
          yield_slot();
        }
      }
      fence_async_smem();
      __syncwarp();
    }
    if (r < 2 && elect()) {
      mbar_expect_tx(bar + (r & 1) * 8, 4096);
      tma2d(sb + buf + (r & 1) * 4096, map, bar + (r & 1) * 8, col, half * 512 + (r + 2) * 128);
    }
  }
#pragma unroll
  for (int e = 0; e < 4; e++) a[e] = (lane & 16 ? a[e + 4] : a[e]) + shfl_xor(lane & 16 ? a[e] : a[e + 4], 16);
#pragma unroll
  for (int e = 0; e < 2; e++) a[e] = (lane & 8 ? a[e + 2] : a[e]) + shfl_xor(lane & 8 ? a[e] : a[e + 2], 8);
  a[0] = (lane & 4 ? a[1] : a[0]) + shfl_xor(lane & 4 ? a[0] : a[1], 4);
  a[0] += shfl_xor(a[0], 2);
  if (!(lane & 2)) st_relaxed(g_cs + half * (3 * kD + kF) + col + (lane & 1) * 8 + (lane >> 2), tag_value(a[0], epoch));
}

constexpr float kGeluBeta = 0.3292034911525734f / 2.f;
constexpr float kGeluK = 2.423681954311584f / 4.f;
constexpr float kHScale = 2.f * kGeluBeta;

__device__ __forceinline__ void store_staged(uint8_t* dst, uint32_t stg) {
  fence_async_smem();
  __syncwarp();
  if (elect()) {
    bulk_store(dst, stg, 4096);
    bulk_commit();
  }
}

template <int J0, int J1>
__device__ __forceinline__ void fold_norm(float (&acc)[2][96], const float2 (&st)[4], const float4* vec) {
  float4 vn = vec[J0 * 4];
#pragma unroll
  for (int J = J0; J < J1; J++) {
    const float4 v = vn;
    if (J + 1 < J1) vn = vec[J * 4 + 4];
#pragma unroll
    for (int c = 0; c < 4; c++) {
      float& a0 = acc[c & 1][4 * J + (c & 2)];
      float& a1 = acc[c & 1][4 * J + (c & 2) + 1];
      a0 = fmaf(a0, st[c].x, fmaf(st[c].y, v.x, v.z));
      a1 = fmaf(a1, st[c].x, fmaf(st[c].y, v.y, v.w));
      asm volatile("" : "+f"(a0), "+f"(a1));
      if (c & 1) yield_slot();
    }
  }
}

template <int CH, class Acquire>
__device__ __forceinline__ void gelu_chunk(const float (&acc)[2][96], uint32_t stg, int lane, uint8_t* prev,
                                           Acquire acquire) {
  uint32_t pk[8][4];
  float z[3][4];
  const uint32_t row = (stg + lane * 128) ^ ((lane & 7) << 4);
#define U(s, e) acc[(e) >> 1][4 * (CH * 8 + ((s) >> 1)) + 2 * ((s) & 1) + ((e) & 1)]
#pragma unroll
  for (int s = 0; s < 18; s++) {
    const int cur = s % 3, p1 = (s + 2) % 3, p2 = (s + 1) % 3, q = s - 2, jj = 2 * q - 24;
    const bool mid = s >= 1 && s < 17;
    if (mid) z[p1][0] = tanh_fast(z[p1][0]);
    if (s < 16) {
#pragma unroll
      for (int e = 0; e < 4; e++) {
        z[cur][e] = fmaf(U(s, e), U(s, e), kGeluK);
        asm volatile("" : "+f"(z[cur][e]));
      }
    }
    if (jj >= 0) stsm4(row ^ (jj << 4), pk[jj][0], pk[jj][1], pk[jj][2], pk[jj][3]);
    yield_slot();
    if (mid) z[p1][1] = tanh_fast(z[p1][1]);
    if (q >= 0) {
      pk[q >> 1][2 * (q & 1)] = pack2(fmaf(U(q, 0), z[p2][0], U(q, 0)), fmaf(U(q, 1), z[p2][1], U(q, 1)));
      pk[q >> 1][2 * (q & 1) + 1] = pack2(fmaf(U(q, 2), z[p2][2], U(q, 2)), fmaf(U(q, 3), z[p2][3], U(q, 3)));
    }
    if (mid) z[p1][2] = tanh_fast(z[p1][2]);
    if (s < 16) {
#pragma unroll
      for (int e = 0; e < 4; e++) {
        z[cur][e] = z[cur][e] * U(s, e) * 8.f;
        asm volatile("" : "+f"(z[cur][e]));
      }
    }
    if (mid) z[p1][3] = tanh_fast(z[p1][3]);
    if (jj >= 0) stsm4(row ^ ((jj + 1) << 4), pk[jj + 1][0], pk[jj + 1][1], pk[jj + 1][2], pk[jj + 1][3]);
    yield_slot();
    if (CH == 1 && s == 1) store_staged(prev, stg);
    if (q == 11) acquire();
  }
#undef U
}

__device__ __forceinline__ void scale_stats(float2 (&st)[4]) {
#pragma unroll
  for (int c = 0; c < 4; c++) {
    st[c].x *= kGeluBeta;
    st[c].y *= st[c].x;
  }
}

__device__ __forceinline__ void add_mean_term(float (&acc)[2][96], const float2 (&st)[4], uint8_t* sm, int tq,
                                              int lane) {
  const float2* cs = reinterpret_cast<const float2*>(sm + kSmCsQ) + tq * 96 + (lane & 3);
  float2 vn = cs[0];
#pragma unroll
  for (int J = 0; J < 24; J++) {
    const float2 v = vn;
    if (J < 23) vn = cs[J * 4 + 4];
#pragma unroll
    for (int c = 0; c < 4; c++) {
      acc[c & 1][4 * J + (c & 2)] = fmaf(st[c].y, v.x, acc[c & 1][4 * J + (c & 2)]);
      acc[c & 1][4 * J + (c & 2) + 1] = fmaf(st[c].y, v.y, acc[c & 1][4 * J + (c & 2) + 1]);
    }
    yield_slot();
  }
}

struct AttnRegs {
  uint32_t q[4][8], k[5][8], vt[5][8];
};
#define SCALED(c, J) pack2(acc[(c) & 1][4 * (J) + ((c) & 2)] * st[c].x, acc[(c) & 1][4 * (J) + ((c) & 2) + 1] * st[c].x)
__device__ __forceinline__ void convert_group(const float (&acc)[2][96], const float2 (&st)[4], AttnRegs& r, int c,
                                              int part) {
#pragma unroll
  for (int J = 0; J < 8; J++) {
    if (part == 0) r.q[c][J] = SCALED(c, J);
    if (part == 1) r.k[c + 1][J] = SCALED(c, 8 + J);
    if (part == 2) r.vt[c + 1][J] = transpose8(SCALED(c, 16 + J));
    if (J & 1) yield_slot();
  }
}
#undef SCALED

__device__ __forceinline__ void convert_odd(const float (&acc)[2][96], const float2 (&st)[4], AttnRegs& r, int step,
                                            uint8_t* sm, uint32_t halo_bar, uint4* halo_out, bool send,
                                            unsigned epoch, int w, int lane) {
  if (step == 1) {
    convert_group(acc, st, r, 3, 2);
    convert_group(acc, st, r, 3, 1);
    if (w < 3) {
      uint2* hs = reinterpret_cast<uint2*>(sm + kSmHalo + w * 2048) + lane;
#pragma unroll
      for (int i = 0; i < 4; i++) {
        hs[i * 32] = make_uint2(r.k[4][2 * i], r.k[4][2 * i + 1]);
        hs[128 + i * 32] = make_uint2(r.vt[4][2 * i], r.vt[4][2 * i + 1]);
      }
      __syncwarp();
      if (elect()) mbar_arrive(halo_bar + w * 8);
    } else if (send) {
#pragma unroll
      for (int i = 0; i < 4; i++) {
        st_packet(halo_out + lane + i * 32, r.k[4][2 * i], r.k[4][2 * i + 1], epoch);
        st_packet(halo_out + lane + 128 + i * 32, r.vt[4][2 * i], r.vt[4][2 * i + 1], epoch);
      }
    }
  } else if (step == 2) {
    convert_group(acc, st, r, 1, 2);
  } else {
    convert_group(acc, st, r, 1, 1);
    convert_group(acc, st, r, 3, 0);
    convert_group(acc, st, r, 1, 0);
  }
}

__device__ __forceinline__ void epilogue_attn(const float (&acc)[2][96], const float2 (&st)[4], AttnRegs& r,
                                              uint8_t* sm, uint32_t sb, int layer, int tq, int b, int j,
                                              unsigned epoch, int tile, int w, int lane) {
  const int t = lane & 3, g = lane >> 2;
  const int hp = j + 8 * tq, att = 2 * layer + tq;
  auto& q = r.q;
  auto& k = r.k;
  auto& vt = r.vt;
  const bool first = w == 0 && (b & 7) == 0;
  const uint4* gh = g_halo + ((layer * 16 + b - 1) * 16 + hp) * 256 + lane;
  uint32_t tag[8];
#define LOAD_HALO()                                                                                    \
  _Pragma("unroll") for (int i = 0; i < 4; i++) {                                                      \
    ld_packet(gh + i * 32, k[0][2 * i], k[0][2 * i + 1], tag[i]);                                      \
    ld_packet(gh + 128 + i * 32, vt[0][2 * i], vt[0][2 * i + 1], tag[4 + i]);                          \
  }
#pragma unroll
  for (int c = 0; c < 6; c++) {
    if (c == 2) {
#pragma unroll
      for (int i = 0; i < 8; i++) k[0][i] = vt[0][i] = tag[i] = 0u;
      if (w > 0) {
        mbar_wait(sb + kBarHalo + (att * 3 + w - 1) * 8, 0);
        const uint2* hs = reinterpret_cast<const uint2*>(sm + kSmHalo + (w - 1) * 2048) + lane;
#pragma unroll
        for (int i = 0; i < 4; i++) {
          const uint2 a = hs[i * 32], d = hs[128 + i * 32];
          k[0][2 * i] = a.x; k[0][2 * i + 1] = a.y;
          vt[0][2 * i] = d.x; vt[0][2 * i + 1] = d.y;
        }
      } else if (!first) {
        LOAD_HALO();
      }
    }
    convert_group(acc, st, r, 2 * (c & 1), 2 - (c >> 1));
  }
  TRACE_AT(tile, 8);
  if (w == 0 && !first) {
#pragma unroll 1
    while (__any_sync(0xffffffffu, ((tag[0] ^ epoch) | (tag[1] ^ epoch) | (tag[2] ^ epoch) | (tag[3] ^ epoch)) |
                                       ((tag[4] ^ epoch) | (tag[5] ^ epoch) | (tag[6] ^ epoch) | (tag[7] ^ epoch)))) {
      LOAD_HALO();
    }
  }
  constexpr float kScale = 0.17677669529663687f * 1.4426950408889634f;
  const bool own0 = 2 * t <= g, own1 = 2 * t + 1 <= g;
  const uint32_t own_mask = (own0 ? 0xffffu : 0u) | (own1 ? 0xffff0000u : 0u);
  const uint32_t stg = sb + kSmStg + w * 4096;
  const uint32_t orow = stg + (lane & 7) * 128, ochunk = (lane >> 3) ^ (lane & 7);
  TRACE_AT(tile, 9);
  mbar_wait(sb + kBarPause + att * 8, 0);
  TRACE_AT(tile, 10);

  float s[2][6][4], o[2][4][2][4];
#pragma unroll
  for (int n = 0; n < 24; n++) {
    const int ks = n / 12, hd = (n % 12) / 6, m = n % 6, ca = 2 * (m / 3), kg = ca + m % 3, J = 4 * hd + 2 * ks;
    if (ks == 0) s[hd][m][0] = s[hd][m][1] = s[hd][m][2] = s[hd][m][3] = 0.f;
    mma16816(s[hd][m], q[ca][J], q[ca + 1][J], q[ca][J + 1], q[ca + 1][J + 1], k[kg][J], k[kg][J + 1]);
  }
  float v0[2][4], v1[2][4], m[2][4];
  uint32_t pp[2][4], po[2][4];
#define UNITS _Pragma("unroll") for (int hd = 0; hd < 2; hd++) _Pragma("unroll") for (int c = 0; c < 4; c++)
  UNITS {
    const int mp = 3 * (c >> 1) + (c & 1), r = 2 * (c & 1);
    float p0 = s[hd][mp][r], p1 = s[hd][mp][r + 1];
    if (c == 0 && first) p0 = p1 = -INFINITY;
    v0[hd][c] = own0 ? s[hd][mp + 1][r] : p0;
    v1[hd][c] = own1 ? s[hd][mp + 1][r + 1] : p1;
    m[hd][c] = fmaxf(v0[hd][c], v1[hd][c]);
  }
  UNITS m[hd][c] = fmaxf(m[hd][c], shfl_xor(m[hd][c], 1));
  UNITS m[hd][c] = fmaxf(m[hd][c], shfl_xor(m[hd][c], 2));
  UNITS {
    const float nm = -m[hd][c] * kScale;
    v0[hd][c] = ex2(fmaf(v0[hd][c], kScale, nm));
    v1[hd][c] = ex2(fmaf(v1[hd][c], kScale, nm));
    m[hd][c] = v0[hd][c] + v1[hd][c];
  }
  UNITS m[hd][c] += shfl_xor(m[hd][c], 1);
  UNITS m[hd][c] += shfl_xor(m[hd][c], 2);
  UNITS {
    const float inv = rcp(m[hd][c]);
    const uint32_t p = pack2(v0[hd][c] * inv, v1[hd][c] * inv);
    pp[hd][c] = p & ~own_mask;
    po[hd][c] = p & own_mask;
    asm volatile("" : "+r"(pp[hd][c]), "+r"(po[hd][c]));
  }
#pragma unroll
  for (int n = 0; n < 24; n++) {
    const int ph = n / 8, hd = (n >> 2) & 1, c = 2 * ((n >> 1) & 1) + (ph == 1), ds = n & 1, J = 4 * hd + 2 * ds;
    float(&d)[4] = o[hd][c][ds];
    if (ph < 2) d[0] = d[1] = d[2] = d[3] = 0.f;
    if (ph == 0) mma1688(d, vt[c + 1][J], vt[c + 1][J + 1], po[hd][c]);
    if (ph == 1) mma16816(d, vt[c][J], vt[c][J + 1], vt[c + 1][J], vt[c + 1][J + 1], pp[hd][c], po[hd][c]);
    if (ph == 2) mma1688(d, vt[c][J], vt[c][J + 1], pp[hd][c]);
    if (n == 3) {
      yield_slot();
      if (tq == 0 && lane == 0) mbar_arrive(sb + kBarResume + att * 8);
    }
  }
  yield_slot();
  if (tq == 1 && lane == 0) mbar_arrive(sb + kBarResume + att * 8);
  TRACE_AT(tile, 11);
  UNITS stsm4_t(orow + c * 1024 + ((ochunk ^ (4 * hd)) << 4), pack2(o[hd][c][0][0], o[hd][c][0][1]),
                pack2(o[hd][c][0][2], o[hd][c][0][3]), pack2(o[hd][c][1][0], o[hd][c][1][1]),
                pack2(o[hd][c][1][2], o[hd][c][1][3]));
#undef UNITS
#undef LOAD_HALO
  fence_async_smem();
  __syncwarp();
  TRACE_AT(tile, 12);
  if (elect()) {
    bulk_store(g_o + (b * 16 + hp) * kTileBytes + w * 4096, stg, 4096);
    bulk_commit();
    bulk_wait();
    TRACE_AT(tile, 13);
    mbar_arrive(sb + kBarEpi + tile * 8);
  }
  __syncwarp();
}

__device__ __forceinline__ void gather_stats(uint8_t* sm, const uint2* stat, int r, float eps, unsigned epoch) {
  uint2 a[8];
  unsigned diff;
#pragma unroll 1
  do {
    __nanosleep(800);
    diff = 0;
#pragma unroll
    for (int i = 0; i < 8; i++) {
      a[i] = ld_relaxed64(stat + i * 128 + r);
      diff |= a[i].x ^ epoch;
    }
  } while (__any_sync(0xffffffffu, diff & 7u));
  float s = 0.f, q = 0.f;
#pragma unroll
  for (int i = 0; i < 8; i++) {
    s += untag_value(a[i].x);
    q += __uint_as_float(a[i].y);
  }
  const float mean = s * (1.f / 1024.f);
  const float var = fmaxf(fmaf(-mean, mean, q * (1.f / 1024.f)), 0.f);
  reinterpret_cast<float2*>(sm + kSmStat)[r] = make_float2(rsqrtf(var + eps), -mean);
}

__device__ __forceinline__ void gather_colsums_qkv(uint8_t* sm, int tq, int j, int lane, unsigned epoch) {
  const uint2* src = reinterpret_cast<const uint2*>(g_cs + (j + 8 * tq) * 64) + lane;
  uint2 v[3], u[3];
  unsigned diff, spins = 0;
#pragma unroll 1
  do {
    if (++spins > kSpinLimit) __trap();
    diff = 0;
#pragma unroll
    for (int q = 0; q < 3; q++) {
      v[q] = ld_relaxed_pair(src + q * (kD / 2));
      u[q] = make_uint2(epoch & 7u, epoch & 7u);
      if (tq) u[q] = ld_relaxed_pair(src + (q * kD + 3 * kD + kF) / 2);
    }
#pragma unroll
    for (int q = 0; q < 3; q++) diff |= (v[q].x ^ epoch) | (v[q].y ^ epoch) | (u[q].x ^ epoch) | (u[q].y ^ epoch);
  } while (__any_sync(0xffffffffu, diff & 7u));
#pragma unroll
  for (int q = 0; q < 3; q++)
    reinterpret_cast<float2*>(sm + kSmCsQ)[tq * 96 + q * 32 + lane] =
        make_float2(untag_value(v[q].x) + untag_value(u[q].x), untag_value(v[q].y) + untag_value(u[q].y));
}

__device__ __forceinline__ void gather_colsums_w1(uint8_t* sm, const __nv_bfloat16* b1, int j, int lane,
                                                  unsigned epoch) {
#pragma unroll 1
  for (int blk = 0; blk < 7; blk++) {
    const int pair = 32 * (blk + (blk < 3 ? 3 * j : blk < 5 ? 21 + 2 * j : 35 + 2 * j)) + lane;
    const uint32_t bias = reinterpret_cast<const uint32_t*>(b1)[pair];
    uint2 v;
    unsigned spins = 0;
#pragma unroll 1
    do {
      if (++spins > kSpinLimit) __trap();
      v = ld_relaxed_pair(reinterpret_cast<const uint2*>(g_cs + 3 * kD) + pair);
    } while (__any_sync(0xffffffffu, ((v.x ^ epoch) | (v.y ^ epoch)) & 7u));
    reinterpret_cast<float4*>(sm + kSmV1)[blk * 32 + lane] =
        make_float4(untag_value(v.x), untag_value(v.y), kGeluBeta * bf_lo(bias), kGeluBeta * bf_hi(bias));
  }
}

constexpr int kPauseQkv = 7, kPauseWo = 2;

__global__ void __cluster_dims__(2, 1, 1) __launch_bounds__(384, 1)
fused_layers_kernel(const __grid_constant__ CUtensorMap map_x, const __grid_constant__ CUtensorMap map_out,
                    const __grid_constant__ CUtensorMap map_qkv, const __grid_constant__ CUtensorMap map_wo,
                    const __grid_constant__ CUtensorMap map_w1a, const __grid_constant__ CUtensorMap map_w1b,
                    const __grid_constant__ CUtensorMap map_w2, const __grid_constant__ CUtensorMap map_csq,
                    const __grid_constant__ CUtensorMap map_cs1, const __grid_constant__ CUtensorMap map_css,
                    const __grid_constant__ Params prm) {
  extern __shared__ __align__(1024) uint8_t sm[];
  if (threadIdx.x < 128 && blockIdx.x < kCtas) TRACE_AT(15, 1);
  const uint32_t sb = __shfl_sync(0xffffffffu, smem_u32(sm), 0);
  const int warp = __shfl_sync(0xffffffffu, threadIdx.x >> 5, 0), lane = threadIdx.x & 31;
  const int cta = blockIdx.x, rank = cta & 1, cl = cta >> 1;
  const int grp = cl < 4 ? 0 : cl < 36 ? (cl - 4) & 7 : 1 + (cl - 36) % 7;
  const int j = cl < 4 ? 4 + cl : cl < 36 ? (cl - 4) >> 3 : 4 + (cl - 36) / 7;
  const int b = 2 * grp + rank;
  const int xcol = (b >> 3) * kD, xrow = (b & 7) * 128;

  if (cta >= kCtas) {
    helper_cta(&map_csq, &map_cs1, sm, sb, cta - kCtas, warp);
    return;
  }
  if ((warp < 8 || warp == 9) && elect()) {
    if (warp == 9) {
#pragma unroll
      for (int s = 0; s < 8; s++) mbar_init(sb + kBarFull + s * 8, 1);
      fence_async_smem();
#pragma unroll 1
      for (int s = 0; s < 4; s++) {
        const uint32_t full = sb + kBarFull + s * 8, dst = sb + kSmRing + s * 40960;
        mbar_expect_tx(full, 40960);
        tma2d(dst, &map_x, full, xcol + (s & 1) * 64, xrow);
        tma3d(dst + kTileBytes, &map_qkv, full, (j + 4 * (s & 2)) * 64, (s & 1) * 64, 0);
        tma3d(dst + kTileBytes + 12288, &map_qkv, full, (j + 4 * (s & 2)) * 64, (s & 1) * 64 + 32, 0);
      }
    } else {
      if (sb & 1023) __trap();
#pragma unroll
      for (int s = 0; s < 16; s++) mbar_init(sb + kBarTurn + warp * 128 + s * 8, warp < 5 ? 1 : warp == 5 ? 2 : 4);
    }
    asm volatile("fence.mbarrier_init.release.cluster;" ::: "memory");
  }
  __syncwarp();
  asm volatile("barrier.cluster.arrive.relaxed.aligned;" ::: "memory");

  if (warp >= 8) {
    asm volatile("setmaxnreg.dec.sync.aligned.u32 40;");
    if (warp < 10) {
      asm volatile("barrier.cluster.wait.aligned;" ::: "memory");
      uint32_t nb = 32, off = 0, kb = 0;
#define RING_STEP(WAIT, ISSUE)                                            \
  do {                                                                    \
    const uint32_t mb = nb - depth, full = sb + kBarFull + (nb & 56);     \
    if (kb == skip) kb += inc;                                            \
    mbar_wait(sb + kBarEmpty + (mb & 56), mb >> 6);                       \
    WAIT;                                                                 \
    if (elect()) { ISSUE; }                                               \
    TRACE_ISSUE(9 - warp, nb);                                            \
    kb += inc;                                                            \
    off = off == wrap ? 0 : off + step;                                   \
    nb += 8;                                                              \
  } while (nb != nend)
#pragma unroll 1
      for (int sg = 0; sg < kSegs; sg++) {
        const uint32_t e = prm.seg[sg];
        const int ty = e & 7, mode = (e >> 15) & 3, reset = (e >> 24) & 3;
        const uint32_t nend = nb + (e & 0x1f8);
        const uint32_t step = (e >> 17) & 1 ? 40960 : 32768, wrap = 163840 - step;
        const uint32_t depth = (e >> 18) & 1 ? 40 : 32;
        if (reset) off = reset == 1 ? 0 : reset == 2 ? 40960 : 131072;
        const uint32_t own = ty == 2 ? 8 + j : 2 * j;
        if (mode != kModeContinue) kb = ((e >> 9) & 63) + (mode == kModeHead ? own : 0);
        const uint32_t inc = mode >= kModeSkip && ty != 2 ? 2 : 1, skip = mode >= kModeSkip ? own + (kb & 1) : 255;
        if (warp == 8) {
          const CUtensorMap* map = ty < 2 ? &map_qkv : ty == 2 ? &map_wo : ty == 3 ? &map_w1a : ty < 6 ? &map_w1b : &map_w2;
          const int c0 = ty < 2 ? (j + 8 * ty) * 64 : 0;
          const int c2 = ty < 2 ? 0 : ty == 3 ? 3 * j : ty == 4 ? 24 + 2 * j : ty == 5 ? 40 + 2 * j : 2 * j;
          const uint32_t half = (ty < 2 || ty == 3) ? 12288 : 8192;
          const uint32_t bytes = 2 * half + (mode == kModeHead ? 0 : kTileBytes);
          const uint32_t dst = sb + kSmRing + (mode == kModeHead && ty != 2 ? 0 : kTileBytes) + rank * half;
          if (e >> 26) {
            const bool second = (grp & 6) == 2;
            const int pk = grp < 4 ? 2 * j + (grp & 1) : 2 * (grp - 4 + (grp - 4 >= j));
            const CUtensorMap* pm = ty == 6 ? &map_qkv : second ? &map_w1b : &map_w1a;
            if (elect())
              asm volatile("cp.async.bulk.prefetch.tensor.3d.L2.global [%0, {%1, %2, %3}];" ::"l"(pm),
                           "r"(ty == 6 ? (j + 8 * second) * 64 : 0), "r"(pk * 64 + rank * 32),
                           "r"(ty == 6 ? 0 : second ? 24 + 2 * j : 3 * j) : "memory");
          }
          if (ty == 2 && mode == kModeHead) mbar_wait(sb + kBarEpi + ((e >> 19) & 31) * 8, 0);
#pragma unroll 1
          RING_STEP(, mbar_expect_tx(full, bytes); tma3d_mc(dst + off, map, full, c0, kb * 64 + rank * 32, c2));
        } else if (mode == kModeHead) {
          off += ((nend - nb) >> 3) * step;
          nb = nend;
          if (off >= 163840) off -= 163840;
        } else if (sg < 2) {
#pragma unroll 1
          RING_STEP(, tma2d(sb + kSmRing + off, &map_x, full, xcol + kb * 64, xrow));
        } else {
          const uint8_t* src = ty == 6 ? g_h + b * 56 * kTileBytes : (ty == 2 ? g_o : g_x) + b * 16 * kTileBytes;
          const int dep = (e >> 19) & 31;
          if (dep < 28) mbar_wait(sb + kBarReady + dep * 8, 0);
          if ((dep & 30) == 28) {
#pragma unroll 1
            RING_STEP(mbar_wait(sb + kBarSrc + ((kb << (4 - inc)) & 56), dep),
                      bulk_load(sb + kSmRing + off, src + kb * kTileBytes, kTileBytes, full));
          } else {
#pragma unroll 1
            RING_STEP(, bulk_load(sb + kSmRing + off, src + kb * kTileBytes, kTileBytes, full));
          }
        }
      }
#undef RING_STEP
    } else {
      unsigned epoch = 0;
      if (warp == 10) {
        if (lane == 0) epoch = atomicAdd(&g_ticket, 1u) / kGrid + 1;
        *reinterpret_cast<unsigned*>(sm + kSmEpoch) = __shfl_sync(0xffffffffu, epoch, 0);
        asm volatile("barrier.cluster.wait.aligned;" ::: "memory");
        if (elect()) mbar_arrive(sb + kBarEpoch);
      } else {
        asm volatile("barrier.cluster.wait.aligned;" ::: "memory");
        mbar_wait_bounded(sb + kBarFull, 0);
        if (elect()) {
          mbar_expect_tx(sb + kBarInit, 32768);
          tma2d(sb + kSmX, &map_x, sb + kBarInit, xcol + j * 128, xrow);
          tma2d(sb + kSmX + kTileBytes, &map_x, sb + kBarInit, xcol + j * 128 + 64, xrow);
        }
        const uint2 u = reinterpret_cast<const uint2*>(prm.b2)[32 * j + lane];
        reinterpret_cast<float4*>(sm + kSmB2)[lane] = make_float4(
            kHScale * bf_lo(u.x), kHScale * bf_hi(u.x), kHScale * bf_lo(u.y), kHScale * bf_hi(u.y));
      }
      mbar_wait_bounded(sb + kBarEpoch, 0);
      epoch = *reinterpret_cast<volatile unsigned*>(sm + kSmEpoch);
      if (cta < 96) {
        mbar_wait_bounded(sb + kBarInit, 0);
        colsum_strip(&map_css, sm, sb, (cta >> 5) * kD + 512 + (cta & 31) * 16, warp - 10, lane, epoch);
      }
      gather_colsums_qkv(sm, 11 - warp, j, lane, epoch);
      __syncwarp();
      if (elect()) mbar_arrive(sb + kBarCs + (11 - warp) * 8);
      if (warp == 10) {
        const unsigned* flag = g_flag + b * 32 + (lane & 7);
        unsigned count = epoch * 32;
#pragma unroll 1
        for (int i = 0; i < kTiles - 1; i++) {
          const bool xt = i == 2 || i == 6 || i == 9;
          count++;
          mbar_wait(sb + (xt ? kBarX + (i >> 2) * 16 : kBarEpi + i * 8), 0);
          if (xt || i == 1 || i == 8) {
            unsigned todo = 0xff;
            do {
              const unsigned now = __ballot_sync(0xffffffffu, (int)(ld_relaxed(flag) - count) >= 0) & todo;
              if (now) {
                asm volatile("fence.acquire.gpu;\nfence.proxy.async.global;" ::: "memory");
                if ((now >> lane) & 1) mbar_arrive(sb + kBarSrc + lane * 8);
                todo ^= now;
              }
              if (todo == 0xff) __nanosleep(300);
            } while (todo);
          } else {
            wait_flags(flag, count);
            if (elect()) mbar_arrive(sb + kBarReady + i * 8);
          }
          if (xt) {
            wait_flags(flag, ++count);
            if (elect()) mbar_arrive(sb + kBarReady + (14 + (i >> 2)) * 8);
          }
        }
      } else {
        unsigned count = epoch * 32;
#pragma unroll 1
        for (int i = 0; i < kTiles - 1; i++) {
          if (i == 3) {
            gather_colsums_w1(sm, prm.b1, j, lane, epoch);
            __syncwarp();
            if (elect()) mbar_arrive(sb + kBarCs + 16);
          }
          const bool xt = i == 2 || i == 6 || i == 9;
#pragma unroll 1
          for (int h = 0; h < (xt ? 2 : 1); h++) {
            if (xt && h == 0) {
              mbar_wait_bounded(sb + kBarEpi + i * 8, 0);
              if (elect()) bulk_store(g_x + (b * 16 + 2 * j) * kTileBytes, sb + kSmX, kTileBytes / 2);
            }
            mbar_wait_bounded(sb + (xt ? kBarX + (i >> 2) * 16 + 8 * h : kBarEpi + i * 8), 0);
            const int ty = i >= 7 ? i - 7 : i;
            if (ty >= 2 && elect()) {
              uint8_t* dst = xt ? g_x + (b * 16 + 2 * j + h) * kTileBytes
                                : g_h + (b * 56 + 1 + (ty == 3 ? 3 * j : 16 * ty - 40 + 2 * j)) * kTileBytes;
              const int piece = (xt && h == 0) ? kTileBytes / 2 : kTileBytes / 8;
#pragma unroll 1
              for (int o = xt && h == 0 ? piece : 0; o < kTileBytes; o += piece) {
                bulk_store(dst + o, sb + (xt ? kSmX + h * kTileBytes : kSmStg) + o, piece);
                bulk_commit();
                bulk_wait();
              }
              if (!xt) mbar_arrive(sb + kBarFree + i * 8);
            }
            __syncwarp();
            count++;
            if (elect()) st_release(&g_flag[b * 32 + j], count);
            __syncwarp();
          }
        }
#pragma unroll 1
        for (int q = 0; q < 4; q++) {
          if (!(q & 1)) mbar_wait_bounded(sb + kBarEpi + (kTiles - 1) * 8, q >> 1);
          else mbar_wait_bounded(sb + kBarX + 48 + 4 * (q & 2), 0);
          if (elect()) {
            tma2d_store(&map_out, sb + kSmX + q * 8192, xcol + j * 128 + (q >> 1) * 64, xrow + (q & 1) * 64);
            bulk_commit();
            if (q == 3) bulk_wait_read();
          }
        }
      }
    }
    __syncwarp();
    asm volatile("barrier.cluster.arrive.relaxed.aligned;\nbarrier.cluster.wait.aligned;" ::: "memory");
  } else {
    asm volatile("setmaxnreg.inc.sync.aligned.u32 232;");
    asm volatile("barrier.cluster.wait.aligned;" ::: "memory");
    const int wg = warp >> 2, w = warp & 3;
    const bool rel = (threadIdx.x & 95) == 0;
    const uint32_t rel_addr = mapa(sb + kBarEmpty, w & 1);
    if (wg == 1) TRACE_AT(15, 0);
#define EPOCH (*reinterpret_cast<volatile unsigned*>(sm + kSmEpoch))

#pragma unroll 1
    for (int i = wg; i < kTiles; i += 2) {
      const int layer = i >= 7, ty = i - 7 * layer;
      TRACE_AT(i, 15);
      float acc[2][96];
      if (ty == 2 || ty == 6) {
        const int lane = lane_id();
        const uint32_t xa = sb + kSmX + ((lane >> 4) * 8 + (lane & 7)) * 128 + (((2 * w + ((lane >> 3) & 1)) ^ (lane & 7)) << 4);
        const float up = ty == 6 ? kHScale / kXScale : layer ? 1.f / kXScale : 1.f;
        const float dn = ty == 2 ? kXScale : layer ? 1.f / kHScale : kXScale / kHScale;
#pragma unroll
        for (int h = 0; h < 2; h++) {
          const float* b2 = reinterpret_cast<const float*>(sm + kSmB2) + 64 * h + 16 * w + (lane >> 2);
          const float bias[2] = {ty == 6 ? b2[0] : 0.f, ty == 6 ? b2[8] : 0.f};
#pragma unroll
          for (int p = 0; p < 8; p++) {
            uint32_t r[4];
            ldsm4_t(xa + h * kTileBytes + p * 2048, r);
#pragma unroll
            for (int m = 0; m < 4; m++) {
              acc[h][8 * p + 2 * m] = fmaf(bf_lo(r[m]), up, bias[m & 1]);
              acc[h][8 * p + 2 * m + 1] = fmaf(bf_hi(r[m]), up, bias[m & 1]);
              asm volatile("" : "+f"(acc[h][8 * p + 2 * m]), "+f"(acc[h][8 * p + 2 * m + 1]));
            }
            yield_slot();
          }
        }
        auto stage = [&](int qt) {
          const int h = qt >> 1;
          if (qt == 1 || (qt == 3 && i == kTiles - 1)) {
            fence_async_smem();
            __syncwarp();
            if (lane == 0) mbar_arrive(sb + kBarEpi + i * 8);
          }
#pragma unroll
          for (int p = 4 * (qt & 1); p < 4 * (qt & 1) + 4; p++) {
            const float* a = &acc[h][8 * p];
            stsm4_t(xa + h * kTileBytes + p * 2048, pack2(a[0] * dn, a[1] * dn), pack2(a[2] * dn, a[3] * dn),
                    pack2(a[4] * dn, a[5] * dn), pack2(a[6] * dn, a[7] * dn));
            yield_slot();
          }
          if (qt & 1) {
            fence_async_smem();
            __syncwarp();
            if (elect()) mbar_arrive(sb + kBarX + (i >> 2) * 16 + 8 * h);
            TRACE_AT(i, 8 + h);
          }
        };
        mainloop<128, kResid>(acc, sb, i, layer * 152 + ty * 16, ty == 6 ? 4 : 0, ty == 6 ? 56 : 16,
                              ty == 2 ? kPauseWo : -1, 2 * layer + 1, rel_addr, rel, ty == 2 ? 8 : -1, stage);
        TRACE_AT(i, 2);
        stage(2);
        stage(3);
      } else {
        const int xver = 2 * layer + (ty >= 3);
        const uint32_t stg = sb + kSmStg + w * 4096;
        const float4* vec = reinterpret_cast<const float4*>(sm + kSmV1) + (ty == 3 ? 0 : 64 * ty - 160);
        int lane;
        uint8_t* hdst = g_h + (b * 56 + (ty == 3 ? 3 * j : 16 * ty - 40 + 2 * j)) * kTileBytes + w * 4096;
        float2 st[4];
        unsigned epoch;
        auto pre = [&] {
          lane = lane_id();
          if (ty < 4) mbar_wait(sb + (ty == 1 ? kBarEpi + (i - 1) * 8 : kBarStat + xver * 8), 0);
#pragma unroll
          for (int c = 0; c < 4; c++) st[c] = reinterpret_cast<const float2*>(sm + kSmStat)[32 * w + 8 * c + (lane >> 2)];
          epoch = EPOCH;
        };
        auto team_stats = [&] {
          uint2* stat = g_stat + b * 1024;
          const unsigned tag = EPOCH * 4 + xver;
          lane = lane_id();
          publish_stats(sb, stat + j * 128, w, lane, tag);
          gather_stats(sm, stat, 32 * w + lane, xver ? 1e-5f * kXScale * kXScale : 1e-5f, tag);
          __syncwarp();
          if (elect()) mbar_arrive(sb + kBarStat + xver * 8);
          TRACE_AT(i, 14);
        };
        if (ty < 4) {
          AttnRegs ar;
          auto odd = [&](int step) {
            if (step == 0) pre();
            else convert_odd(acc, st, ar, step, sm, sb + kBarHalo + (xver + ty) * 24,
                             g_halo + ((layer * 16 + b) * 16 + j + 8 * ty) * 256, (b & 7) != 7, epoch, w, lane);
          };
          head_blocks<192>(acc, sb, layer * 152 + (ty < 2 ? 2 * ty : 48), ty < 2 ? 2 * ty : 1, xver, rel_addr, rel);
          if (ty == 1) {
            if (i == 1) {
              mbar_wait(sb + kBarEpoch, 0);
              mbar_wait(sb + kBarInit, 0);
            }
            team_stats();
            epoch = 0;
#pragma unroll
            for (int c = 0; c < 4; c++) st[c] = reinterpret_cast<const float2*>(sm + kSmStat)[32 * w + 8 * c + (lane >> 2)];
          } else {
            mainloop<192, kPlain>(acc, sb, i, layer * 152 + (ty ? 52 : 4), ty ? 1 : 0, 14, -1, 0, rel_addr, rel, 0, pre);
            TRACE_AT(i, 2);
            if (ty == 3) goto wide_gelu;
          }
          if (layer == 0) mbar_wait(sb + kBarCs + ty * 8, 0);
          add_mean_term(acc, st, sm, ty, lane);
          if (ty == 1) {
            mainloop<192, kStagger>(acc, sb, i, layer * 152 + 18, 2, 14, kPauseQkv, xver, rel_addr, rel, 0, odd);
            TRACE_AT(i, 2);
          } else {
            odd(1);
            odd(2);
            odd(3);
          }
          epilogue_attn(acc, st, ar, sm, sb, layer, ty, b, j, epoch, i, w, lane);
          TRACE_AT(i, 3);
          continue;
        wide_gelu:
          if (i == 3) mbar_wait(sb + kBarCs + 16, 0);
          scale_stats(st);
          fold_norm<16, 24>(acc, st, vec + (lane & 3));
          TRACE_AT(i, 11);
          gelu_chunk<2>(acc, stg, lane, nullptr, [] {});
          TRACE_AT(i, 12);
          fold_norm<0, 2>(acc, st, vec + (lane & 3));
          store_staged(hdst + 2 * kTileBytes, stg);
          fold_norm<2, 16>(acc, st, vec + (lane & 3));
        } else {
          if (ty == 4) {
            head_blocks<128>(acc, sb, layer * 152 + 50, 3, xver, rel_addr, rel);
            team_stats();
          } else {
            const uint32_t s0 = ((((sb & 0x3FFFF) + kSmRing) >> 4) | (1u << 16)) + 3 * 2048;
            mbar_wait(sb + kBarTurn + (i - 1) * 8, 0);
            mbar_wait(sb + kBarFull, layer * 19 + 10);
            TRACE_KB((layer * 152 + 80) * 8);
            mma_kblock<128, 2>(acc, s0, s0 + kToB);
          }
          mainloop<128, kPlain>(acc, sb, i, layer * 152 + 6 + 15 * ty, 4, ty + 10, -1, 0, rel_addr, rel, 0, pre,
                                ty == 5 ? 0 : 64);
          TRACE_AT(i, 2);
          if (i == 4) mbar_wait(sb + kBarCs + 16, 0);
          scale_stats(st);
          fold_norm<0, 16>(acc, st, vec + (lane & 3));
        }
        auto own_store_done = [] {
          if (elect()) bulk_wait();
          __syncwarp();
        };
        TRACE_AT(i, 8);
        gelu_chunk<0>(acc, stg, lane, nullptr, [&] {
          if (ty == 3) own_store_done();
          else mbar_wait(sb + kBarFree + (i - 1) * 8, 0);
        });
        TRACE_AT(i, 9);
        gelu_chunk<1>(acc, stg, lane, hdst, own_store_done);
        TRACE_AT(i, 10);
        fence_async_smem();
        __syncwarp();
        if (elect()) mbar_arrive(sb + kBarEpi + i * 8);
      }
      TRACE_AT(i, 3);
    }
#undef EPOCH
    asm volatile("barrier.cluster.arrive.relaxed.aligned;\nbarrier.cluster.wait.aligned;" ::: "memory");
    if (wg == 1) TRACE_AT(15, 2);
  }
}

void build_segments(uint32_t* seg) {
  int n = 0, fine = 0;
  auto per_source = [&] { return 28 + (fine++ & 1); };
  auto add = [&](int ty, int cnt, int kb0, int mode, int wide, int depth5, int dep, int reset) {
    seg[n++] = ty | cnt << 3 | kb0 << 9 | mode << 15 | wide << 17 | depth5 << 18 | dep << 19 | reset << 24;
  };
  for (int l = 0; l < 2; l++) {
    const int t = 7 * l;
    if (l == 0) {
      add(0, 14, 2, kModePlain, 1, 0, 31, 1);
      add(1, 14, 2, kModePlain, 1, 0, 31, 0);
    } else {
      add(0, 2, 0, kModeHead, 1, 1, 31, 1);
      add(1, 2, 0, kModeHead, 1, 0, 31, 0);
      add(0, 7, 0, kModeSkip, 1, 0, per_source(), 0);
      add(0, 7, 1, kModeSkip, 1, 0, 15, 0);
      add(1, 7, 0, kModeSkip, 1, 0, 31, 0);
      add(1, 7, 1, kModeSkip, 1, 0, 31, 0);
    }
    add(2, 4, 0, kModePlain, 0, 0, t, 1);
    add(2, 4, 4, kModePlain, 0, 1, 31, 4);
    add(2, 1, 0, kModeHead, 0, 1, t + 1, 0);
    add(2, 7, 8, kModeSkip, 0, 1, per_source(), 0);
    add(3, 1, 0, kModeHead, 1, 1, 31, 2);
    add(3, 1, 1, kModeHead, 1, 0, 31, 0);
    add(4, 2, 0, kModeHead, 1, 0, 31, 0);
    add(3, 7, 0, kModeSkip, 1, 0, per_source(), 0);
    add(3, 7, 1, kModeSkip, 1, 0, 14 + 2 * l, 0);
    add(4, 4, 0, kModeSkip, 0, 0, 31, 3);
    add(4, 3, 0, kModeContinue, 0, 1, 31, 0);
    add(4, 7, 1, kModeSkip, 0, 1, 31, 0);
    add(5, 16, 0, kModePlain, 0, 1, 31, 0);
    add(6, 24, 0, kModePlain, 0, 1, t + 3, 0);
    add(6, 16, 24, kModePlain, 0, 1, t + 4, 0);
    add(6, 16, 40, kModePlain, 0, 1, t + 5, l ? 0 : 4);
  }
}

typedef CUresult (*EncodeTiledFn)(CUtensorMap*, CUtensorMapDataType, cuuint32_t, void*, const cuuint64_t*,
                                  const cuuint64_t*, const cuuint32_t*, const cuuint32_t*, CUtensorMapInterleave,
                                  CUtensorMapSwizzle, CUtensorMapL2promotion, CUtensorMapFloatOOBfill);

CUtensorMap make_map(EncodeTiledFn enc, const void* p, int rank, const cuuint64_t* dims, const cuuint64_t* strides,
                     const cuuint32_t* box, CUtensorMapSwizzle swizzle = CU_TENSOR_MAP_SWIZZLE_128B,
                     CUtensorMapL2promotion promo = CU_TENSOR_MAP_L2_PROMOTION_L2_128B) {
  CUtensorMap m;
  const cuuint32_t es[5] = {1, 1, 1, 1, 1};
  enc(&m, CU_TENSOR_MAP_DATA_TYPE_BFLOAT16, rank, const_cast<void*>(p), dims, strides, box, es,
      CU_TENSOR_MAP_INTERLEAVE_NONE, swizzle, promo, CU_TENSOR_MAP_FLOAT_OOB_FILL_NONE);
  return m;
}

CUtensorMap weight_map(EncodeTiledFn enc, const void* p, int k, int n, int blocks) {
  const cuuint64_t dims[3] = {64, (cuuint64_t)k, (cuuint64_t)n / 64};
  const cuuint64_t strides[2] = {(cuuint64_t)n * 2, 128};
  const cuuint32_t box[3] = {64, 32, (cuuint32_t)blocks};
  return make_map(enc, p, 3, dims, strides, box, CU_TENSOR_MAP_SWIZZLE_128B, CU_TENSOR_MAP_L2_PROMOTION_L2_256B);
}

CUtensorMap slab_map(EncodeTiledFn enc, const void* p, int n, int cols, int rows) {
  const cuuint64_t dims[2] = {(cuuint64_t)n, kD};
  const cuuint64_t strides[1] = {(cuuint64_t)n * 2};
  const cuuint32_t box[2] = {(cuuint32_t)cols, (cuuint32_t)rows};
  return make_map(enc, p, 2, dims, strides, box, CU_TENSOR_MAP_SWIZZLE_NONE);
}

CUtensorMap token_map(EncodeTiledFn enc, const void* p, int rows) {
  const cuuint64_t dims[2] = {2 * kD, 1024};
  const cuuint64_t strides[1] = {4 * kD};
  const cuuint32_t box[2] = {64, (cuuint32_t)rows};
  return make_map(enc, p, 2, dims, strides, box);
}

}

extern "C" void kernel_launch(void* const* d_in, const int* in_sizes, int n_in, void* d_out, int out_size) {
  (void)in_sizes; (void)n_in; (void)out_size;
  static EncodeTiledFn enc = nullptr;
  if (!enc) {
    void* fn = nullptr;
    cudaDriverEntryPointQueryResult q;
    cudaGetDriverEntryPoint("cuTensorMapEncodeTiled", &fn, cudaEnableDefault, &q);
    enc = (EncodeTiledFn)fn;
    cudaFuncSetAttribute(fused_layers_kernel, cudaFuncAttributeMaxDynamicSharedMemorySize, kSmBytes);
  }
  Params prm;
  prm.b1 = (const __nv_bfloat16*)d_in[5];
  prm.b2 = (const __nv_bfloat16*)d_in[7];
  build_segments(prm.seg);
  const cuuint64_t qd[3] = {kD, kD, 3}, qs[2] = {3 * kD * 2, kD * 2};
  const cuuint32_t qb[3] = {64, 32, 3};
  const CUtensorMap map_x = token_map(enc, d_in[0], 128);
  const CUtensorMap map_out = token_map(enc, d_out, 64);
  const CUtensorMap map_qkv = make_map(enc, d_in[1], 3, qd, qs, qb);
  const CUtensorMap map_wo = weight_map(enc, d_in[2], kD, kD, 2);
  const CUtensorMap map_w1a = weight_map(enc, d_in[4], kD, kF, 3);
  const CUtensorMap map_w1b = weight_map(enc, d_in[4], kD, kF, 2);
  const CUtensorMap map_w2 = weight_map(enc, d_in[6], kF, kD, 2);
  fused_layers_kernel<<<kGrid, 384, kSmBytes>>>(map_x, map_out, map_qkv, map_wo, map_w1a, map_w1b, map_w2,
                                                slab_map(enc, d_in[1], 3 * kD, 128, 128), slab_map(enc, d_in[4], kF, 128, 128),
                                                slab_map(enc, d_in[1], 3 * kD, 16, 128), prm);
}
```

```cpp
#include <cuda.h>
#include <cuda_bf16.h>
#include <cuda_runtime.h>
#include <stdint.h>

namespace {

constexpr int kD = 1024;
constexpr int kF = 3584;
constexpr int kCtas = 128;
constexpr int kGrid = 132;
constexpr int kTiles = 14;
constexpr int kTileBytes = 16384;

constexpr int kSmRing = 0;
constexpr int kSmX = 163840;
constexpr int kSmStg = kSmX + 32768;
constexpr int kSmHalo = kSmStg + 16384;
constexpr int kSmCsQ = kSmHalo + 6144;
constexpr int kSmV1 = kSmCsQ + 384 * 4;
constexpr int kSmB2 = kSmV1 + 448 * 8;
constexpr int kSmStat = kSmB2 + 128 * 4;
constexpr int kSmBar = kSmStat + 128 * 8;
constexpr int kBarFull = kSmBar;
constexpr int kBarTurn = kBarFull + 8 * 8;
constexpr int kBarReady = kBarTurn + 14 * 8;
constexpr int kBarSrc = kBarReady + 17 * 8;
constexpr int kBarPause = kBarSrc + 8 * 8;
constexpr int kBarFree = kBarPause + 4 * 8;
constexpr int kBarCs = kBarFree + 14 * 8;
constexpr int kBarSlab = kBarCs + 3 * 8;
constexpr int kBarHalo = kBarSlab + 4 * 8;
constexpr int kBarInit = kBarHalo + 12 * 8;
constexpr int kBarEpoch = kBarInit + 8;
constexpr int kBarEmpty = kBarTurn + 5 * 128;
constexpr int kBarEpi = kBarEmpty + 128;
constexpr int kBarX = kBarEpi + 15 * 8;
constexpr int kBarStat = kBarX + 8 * 8;
constexpr int kBarResume = kBarStat + 4 * 8;
constexpr int kSmEpoch = kBarEpi + 2 * 128;
static_assert(kBarEpoch < kBarEmpty && kBarResume + 4 * 8 <= kSmEpoch, "barrier groups overflow");
constexpr int kSmBytes = kSmEpoch + 16 + 256;
constexpr int kSegs = 40;

constexpr float kXScale = 1.f / 8.f;

constexpr unsigned kSpinLimit = 1u << 22;

__device__ __align__(1024) uint8_t g_x[16 * 16 * kTileBytes];
__device__ __align__(1024) uint8_t g_o[16 * 16 * kTileBytes];
__device__ __align__(1024) uint8_t g_h[16 * 56 * kTileBytes];
__device__ __align__(128) uint2 g_stat[16 * 8 * 128];
__device__ __align__(128) unsigned g_cs[3 * kD + kF + 3 * kD];
__device__ __align__(128) uint4 g_halo[2 * 16 * 16 * 256];
__device__ __align__(128) unsigned g_flag[16 * 32];
__device__ unsigned g_ticket;

#define TRACE_AT(tile, k)
#define TRACE_PUB(i, k, c)
#define TRACE_ISSUE(which, nb)

struct Params {
  const __nv_bfloat16* b1;
  const __nv_bfloat16* b2;
  uint32_t seg[kSegs];
};

__device__ __forceinline__ uint32_t smem_u32(const void* p) {
  return (uint32_t)__cvta_generic_to_shared(p);
}
__device__ __forceinline__ uint32_t mapa(uint32_t a, uint32_t cta) {
  uint32_t r;
  asm("mapa.shared::cluster.u32 %0, %1, %2;" : "=r"(r) : "r"(a), "r"(cta));
  return r;
}
__device__ __forceinline__ void mbar_init(uint32_t bar, int cnt) {
  asm volatile("mbarrier.init.shared::cta.b64 [%0], %1;" ::"r"(bar), "r"(cnt) : "memory");
}
__device__ __forceinline__ void mbar_expect_tx(uint32_t bar, uint32_t bytes) {
  asm volatile("mbarrier.arrive.expect_tx.shared::cta.b64 _, [%0], %1;" ::"r"(bar), "r"(bytes) : "memory");
}
__device__ __forceinline__ void mbar_arrive(uint32_t bar) {
  asm volatile("mbarrier.arrive.shared::cta.b64 _, [%0];" ::"r"(bar) : "memory");
}
__device__ __forceinline__ void mbar_arrive_cluster(uint32_t cluster_addr) {
  asm volatile("mbarrier.arrive.shared::cluster.b64 _, [%0];" ::"r"(cluster_addr) : "memory");
}
__device__ __forceinline__ void mbar_wait(uint32_t bar, uint32_t parity) {
  asm volatile("{\n.reg .pred p;\nRETRY:\nmbarrier.try_wait.parity.shared::cta.b64 p, [%0], %1;\n"
               "@!p bra.uni RETRY;\n}" ::"r"(bar), "r"(parity) : "memory");
}
__device__ __forceinline__ void mbar_wait_bounded(uint32_t bar, uint32_t parity) {
  asm volatile("{\n.reg .pred p;\n.reg .u32 c;\nmov.u32 c, 0;\nRETRY:\n"
               "mbarrier.try_wait.parity.shared::cta.b64 p, [%0], %1;\n@p bra.uni DONE;\n"
               "add.u32 c, c, 1;\nsetp.lt.u32 p, c, %2;\n@p bra.uni RETRY;\ntrap;\nDONE:\n}"
               ::"r"(bar), "r"(parity), "n"(1u << 19) : "memory");
}
__device__ __forceinline__ void tma3d(uint32_t dst, const CUtensorMap* m, uint32_t bar, int c0, int c1, int c2) {
  asm volatile(
      "cp.async.bulk.tensor.3d.shared::cluster.global.mbarrier::complete_tx::bytes [%0], [%1, {%3, %4, %5}], [%2];"
      ::"r"(dst), "l"(m), "r"(bar), "r"(c0), "r"(c1), "r"(c2) : "memory");
}
__device__ __forceinline__ void tma3d_mc(uint32_t dst, const CUtensorMap* m, uint32_t bar, int c0, int c1, int c2) {
  asm volatile(
      "cp.async.bulk.tensor.3d.shared::cluster.global.mbarrier::complete_tx::bytes.multicast::cluster"
      " [%0], [%1, {%3, %4, %5}], [%2], %6;"
      ::"r"(dst), "l"(m), "r"(bar), "r"(c0), "r"(c1), "r"(c2), "h"((uint16_t)3) : "memory");
}
__device__ __forceinline__ void tma2d(uint32_t dst, const CUtensorMap* m, uint32_t bar, int c0, int c1) {
  asm volatile(
      "cp.async.bulk.tensor.2d.shared::cluster.global.mbarrier::complete_tx::bytes [%0], [%1, {%3, %4}], [%2];"
      ::"r"(dst), "l"(m), "r"(bar), "r"(c0), "r"(c1) : "memory");
}
__device__ __forceinline__ void tma2d_store(const CUtensorMap* m, uint32_t src, int c0, int c1) {
  asm volatile("cp.async.bulk.tensor.2d.global.shared::cta.bulk_group [%0, {%2, %3}], [%1];"
               ::"l"(m), "r"(src), "r"(c0), "r"(c1) : "memory");
}
__device__ __forceinline__ int lane_id() {
  int l;
  asm volatile("mov.u32 %0, %%laneid;" : "=r"(l));
  return l;
}
__device__ __forceinline__ bool elect() {
  uint32_t p;
  asm volatile("{\n.reg .pred p;\nelect.sync _|p, 0xffffffff;\nselp.b32 %0, 1, 0, p;\n}" : "=r"(p));
  return p;
}
__device__ __forceinline__ void bulk_load(uint32_t dst, const void* src, uint32_t bytes, uint32_t bar) {
  asm volatile("cp.async.bulk.shared::cluster.global.mbarrier::complete_tx::bytes [%0], [%1], %2, [%3];"
               ::"r"(dst), "l"(src), "r"(bytes), "r"(bar) : "memory");
}
__device__ __forceinline__ void bulk_store(void* dst, uint32_t src, uint32_t bytes) {
  asm volatile("cp.async.bulk.global.shared::cta.bulk_group [%0], [%1], %2;" ::"l"(dst), "r"(src), "r"(bytes)
               : "memory");
}
__device__ __forceinline__ void bulk_commit() { asm volatile("cp.async.bulk.commit_group;" ::: "memory"); }
__device__ __forceinline__ void bulk_wait_read() { asm volatile("cp.async.bulk.wait_group.read 0;" ::: "memory"); }
__device__ __forceinline__ void bulk_wait() { asm volatile("cp.async.bulk.wait_group 0;" ::: "memory"); }
__device__ __forceinline__ void fence_async_smem() { asm volatile("fence.proxy.async.shared::cta;" ::: "memory"); }
__device__ __forceinline__ unsigned ld_relaxed(const unsigned* p) {
  unsigned v;
  asm volatile("ld.relaxed.gpu.global.u32 %0, [%1];" : "=r"(v) : "l"(p) : "memory");
  return v;
}
__device__ __forceinline__ uint2 ld_relaxed64(const uint2* p) {
  uint2 v;
  asm volatile("{\n.reg .b64 t;\nld.relaxed.gpu.global.b64 t, [%2];\nmov.b64 {%0, %1}, t;\n}"
               : "=r"(v.x), "=r"(v.y) : "l"(p) : "memory");
  return v;
}
__device__ __forceinline__ void st_relaxed(unsigned* p, unsigned v) {
  asm volatile("st.relaxed.gpu.global.u32 [%0], %1;" ::"l"(p), "r"(v) : "memory");
}
__device__ __forceinline__ void st_release(unsigned* p, unsigned v) {
  asm volatile("st.release.gpu.global.u32 [%0], %1;" ::"l"(p), "r"(v) : "memory");
}
__device__ __forceinline__ void wait_flags(const unsigned* p, unsigned count) {
  while (__any_sync(0xffffffffu, (int)(ld_relaxed(p) - count) < 0)) {
    __nanosleep(400);
  }
  asm volatile("fence.acquire.gpu;\nfence.proxy.async.global;" ::: "memory");
  __syncwarp();
}
__device__ __forceinline__ void st_packet(uint4* p, uint32_t d0, uint32_t d1, uint32_t tag) {
  asm volatile("{\n.reg .b128 v;\n.reg .b64 x, y;\nmov.b64 x, {%1, %2};\nmov.b64 y, {%3, %3};\nmov.b128 v, {x, y};\n"
               "st.relaxed.gpu.global.b128 [%0], v;\n}" ::"l"(p), "r"(d0), "r"(d1), "r"(tag) : "memory");
}
__device__ __forceinline__ void ld_packet(const uint4* p, uint32_t& d0, uint32_t& d1, uint32_t& tag) {
  asm volatile("{\n.reg .b128 v;\n.reg .b64 x, y;\n.reg .b32 u;\nld.relaxed.gpu.global.b128 v, [%3];\n"
               "mov.b128 {x, y}, v;\nmov.b64 {%0, %1}, x;\nmov.b64 {%2, u}, y;\n}"
               : "=r"(d0), "=r"(d1), "=r"(tag) : "l"(p) : "memory");
}
__device__ __forceinline__ uint2 ld_relaxed_pair(const uint2* p) {
  uint2 v;
  asm volatile("ld.relaxed.gpu.global.v2.u32 {%0, %1}, [%2];" : "=r"(v.x), "=r"(v.y) : "l"(p) : "memory");
  return v;
}
__device__ __forceinline__ unsigned tag_value(float v, unsigned epoch) {
  return (__float_as_uint(v) & ~7u) | (epoch & 7u);
}
__device__ __forceinline__ float untag_value(unsigned v) { return __uint_as_float(v & ~7u); }
__device__ __forceinline__ void stsm4(uint32_t a, uint32_t r0, uint32_t r1, uint32_t r2, uint32_t r3) {
  asm volatile("stmatrix.sync.aligned.m8n8.x4.shared.b16 [%0], {%1, %2, %3, %4};" ::"r"(a), "r"(r0), "r"(r1),
               "r"(r2), "r"(r3) : "memory");
}
__device__ __forceinline__ void stsm4_t(uint32_t a, uint32_t r0, uint32_t r1, uint32_t r2, uint32_t r3) {
  asm volatile("stmatrix.sync.aligned.m8n8.x4.trans.shared.b16 [%0], {%1, %2, %3, %4};" ::"r"(a), "r"(r0),
               "r"(r1), "r"(r2), "r"(r3) : "memory");
}
__device__ __forceinline__ uint32_t transpose8(uint32_t a) {
  uint32_t d;
  asm volatile("movmatrix.sync.aligned.m8n8.trans.b16 %0, %1;" : "=r"(d) : "r"(a));
  return d;
}
__device__ __forceinline__ void mma16816(float (&c)[4], uint32_t a0, uint32_t a1, uint32_t a2, uint32_t a3,
                                         uint32_t b0, uint32_t b1) {
  asm volatile("mma.sync.aligned.m16n8k16.row.col.f32.bf16.bf16.f32 {%0, %1, %2, %3}, {%4, %5, %6, %7}, {%8, %9}, "
               "{%0, %1, %2, %3};"
               : "+f"(c[0]), "+f"(c[1]), "+f"(c[2]), "+f"(c[3])
               : "r"(a0), "r"(a1), "r"(a2), "r"(a3), "r"(b0), "r"(b1));
}
__device__ __forceinline__ void mma1688(float (&c)[4], uint32_t a0, uint32_t a1, uint32_t b0) {
  asm volatile("mma.sync.aligned.m16n8k8.row.col.f32.bf16.bf16.f32 {%0, %1, %2, %3}, {%4, %5}, {%6}, {%0, %1, %2, %3};"
               : "+f"(c[0]), "+f"(c[1]), "+f"(c[2]), "+f"(c[3]) : "r"(a0), "r"(a1), "r"(b0));
}
__device__ __forceinline__ float shfl_xor(float v, int m) {
  float r;
  asm volatile("shfl.sync.bfly.b32 %0, %1, %2, 31, 0xffffffff;" : "=f"(r) : "f"(v), "r"(m));
  return r;
}
__device__ __forceinline__ float tanh_fast(float x) {
  float r;
  asm volatile("tanh.approx.f32 %0, %1;" : "=f"(r) : "f"(x));
  return r;
}
__device__ __forceinline__ void ldsm4(uint32_t a, uint32_t (&r)[4]) {
  asm volatile("ldmatrix.sync.aligned.m8n8.x4.shared.b16 {%0, %1, %2, %3}, [%4];"
               : "=r"(r[0]), "=r"(r[1]), "=r"(r[2]), "=r"(r[3]) : "r"(a) : "memory");
}
__device__ __forceinline__ void ldsm4_t(uint32_t a, uint32_t (&r)[4]) {
  asm volatile("ldmatrix.sync.aligned.m8n8.x4.trans.shared.b16 {%0, %1, %2, %3}, [%4];"
               : "=r"(r[0]), "=r"(r[1]), "=r"(r[2]), "=r"(r[3]) : "r"(a) : "memory");
}
__device__ __forceinline__ uint32_t pack2(float lo, float hi) {
  uint32_t r;
  asm volatile("cvt.rn.bf16x2.f32 %0, %1, %2;" : "=r"(r) : "f"(hi), "f"(lo));
  return r;
}
__device__ __forceinline__ float bf_lo(uint32_t r) { return __uint_as_float(r << 16); }
__device__ __forceinline__ float bf_hi(uint32_t r) { return __uint_as_float(r & 0xffff0000u); }
__device__ __forceinline__ float ex2(float x) {
  float r;
  asm("ex2.approx.ftz.f32 %0, %1;" : "=f"(r) : "f"(x));
  return r;
}
__device__ __forceinline__ float rcp(float x) {
  float r;
  asm("rcp.approx.ftz.f32 %0, %1;" : "=f"(r) : "f"(x));
  return r;
}
template <int N>
__device__ __forceinline__ void wg_wait() {
  asm volatile("wgmma.wait_group.sync.aligned %0;" ::"n"(N) : "memory");
}
__device__ __forceinline__ void yield_slot() { asm volatile("pmevent 0;"); }

template <int N, int KIND>
__device__ __forceinline__ void mma_kblock(float (&acc)[2][96], uint32_t a, uint32_t b);

#define F8(m, d, i) m(d[i]), m(d[i + 1]), m(d[i + 2]), m(d[i + 3]), m(d[i + 4]), m(d[i + 5]), m(d[i + 6]), m(d[i + 7])
#define KSTEP(N, A, B, oa0, oa1, ob, sd)                                                   \
  "mov.b64 db, {" B ", hb};\nadd.u64 db, db, " #ob ";\n"                                    \
  "mov.b64 da, {" A ", ha};\nadd.u64 da, da, " #oa0 ";\n"                                   \
  "wgmma.mma_async.sync.aligned.m64n" #N "k16.f32.bf16.bf16 {" ACC##N##_0 "}, da, db, " #sd ", 1, 1, 0, 1;\n" \
  "mov.b64 da, {" A ", ha};\nadd.u64 da, da, " #oa1 ";\n"                                   \
  "wgmma.mma_async.sync.aligned.m64n" #N "k16.f32.bf16.bf16 {" ACC##N##_1 "}, da, db, " #sd ", 1, 1, 0, 1;\n"

#define MMA_KBLOCK(N, KIND, A, B, ob2, ob3, sd, MID, MODE)                                 \
  template <>                                                                              \
  __device__ __forceinline__ void mma_kblock<N, KIND>(float (&acc)[2][96], uint32_t a, uint32_t b) { \
    asm volatile("{\n.reg .b32 ha, hb;\n.reg .b64 da, db;\n"                            \
                 "mov.b32 ha, 0x40000080;\nmov.b32 hb, 0x40000040;\n"                       \
                 "wgmma.fence.sync.aligned;\n"                                             \
                 KSTEP(N, A, B, 0, 64, 0, sd) KSTEP(N, A, B, 2, 66, 128, 1) MID               \
                 KSTEP(N, A, B, 4, 68, ob2, 1) KSTEP(N, A, B, 6, 70, ob3, 1) "wgmma.commit_group.sync.aligned;\n}\n"  \
                 : OPS##N(MODE) : "r"(a), "r"(b) : "memory");                              \
  }
#define MMA_KBLOCKS(N, A, B, ob2, ob3)                                                     \
  MMA_KBLOCK(N, 0, A, B, ob2, ob3, 1, "", "+f")                                            \
  MMA_KBLOCK(N, 1, A, B, ob2, ob3, 1, "wgmma.commit_group.sync.aligned;\n", "+f")          \
  MMA_KBLOCK(N, 2, A, B, ob2, ob3, 0, "", "=f")

#define ACC128_0 \
  "%0, %1, %2, %3, %4, %5, %6, %7, %8, %9, %10, %11, %12, %13, %14, %15, " \
  "%16, %17, %18, %19, %20, %21, %22, %23, %24, %25, %26, %27, %28, %29, %30, %31, " \
  "%32, %33, %34, %35, %36, %37, %38, %39, %40, %41, %42, %43, %44, %45, %46, %47, " \
  "%48, %49, %50, %51, %52, %53, %54, %55, %56, %57, %58, %59, %60, %61, %62, %63"
#define ACC128_1 \
  "%64, %65, %66, %67, %68, %69, %70, %71, %72, %73, %74, %75, %76, %77, %78, %79, " \
  "%80, %81, %82, %83, %84, %85, %86, %87, %88, %89, %90, %91, %92, %93, %94, %95, " \
  "%96, %97, %98, %99, %100, %101, %102, %103, %104, %105, %106, %107, %108, %109, %110, %111, " \
  "%112, %113, %114, %115, %116, %117, %118, %119, %120, %121, %122, %123, %124, %125, %126, %127"
#define OPS128(m) \
  F8(m, acc[0], 0), F8(m, acc[0], 8), F8(m, acc[0], 16), F8(m, acc[0], 24), F8(m, acc[0], 32), F8(m, acc[0], 40), F8(m, acc[0], 48), F8(m, acc[0], 56), \
        F8(m, acc[1], 0), F8(m, acc[1], 8), F8(m, acc[1], 16), F8(m, acc[1], 24), F8(m, acc[1], 32), F8(m, acc[1], 40), F8(m, acc[1], 48), F8(m, acc[1], 56)
MMA_KBLOCKS(128, "%128", "%129", 512, 640)

#define ACC192_0 \
  "%0, %1, %2, %3, %4, %5, %6, %7, %8, %9, %10, %11, %12, %13, %14, %15, " \
  "%16, %17, %18, %19, %20, %21, %22, %23, %24, %25, %26, %27, %28, %29, %30, %31, " \
  "%32, %33, %34, %35, %36, %37, %38, %39, %40, %41, %42, %43, %44, %45, %46, %47, " \
  "%48, %49, %50, %51, %52, %53, %54, %55, %56, %57, %58, %59, %60, %61, %62, %63, " \
  "%64, %65, %66, %67, %68, %69, %70, %71, %72, %73, %74, %75, %76, %77, %78, %79, " \
  "%80, %81, %82, %83, %84, %85, %86, %87, %88, %89, %90, %91, %92, %93, %94, %95"
#define ACC192_1 \
  "%96, %97, %98, %99, %100, %101, %102, %103, %104, %105, %106, %107, %108, %109, %110, %111, " \
  "%112, %113, %114, %115, %116, %117, %118, %119, %120, %121, %122, %123, %124, %125, %126, %127, " \
  "%128, %129, %130, %131, %132, %133, %134, %135, %136, %137, %138, %139, %140, %141, %142, %143, " \
  "%144, %145, %146, %147, %148, %149, %150, %151, %152, %153, %154, %155, %156, %157, %158, %159, " \
  "%160, %161, %162, %163, %164, %165, %166, %167, %168, %169, %170, %171, %172, %173, %174, %175, " \
  "%176, %177, %178, %179, %180, %181, %182, %183, %184, %185, %186, %187, %188, %189, %190, %191"
#define OPS192(m) \
  F8(m, acc[0], 0), F8(m, acc[0], 8), F8(m, acc[0], 16), F8(m, acc[0], 24), F8(m, acc[0], 32), F8(m, acc[0], 40), F8(m, acc[0], 48), F8(m, acc[0], 56), F8(m, acc[0], 64), F8(m, acc[0], 72), F8(m, acc[0], 80), F8(m, acc[0], 88), \
        F8(m, acc[1], 0), F8(m, acc[1], 8), F8(m, acc[1], 16), F8(m, acc[1], 24), F8(m, acc[1], 32), F8(m, acc[1], 40), F8(m, acc[1], 48), F8(m, acc[1], 56), F8(m, acc[1], 64), F8(m, acc[1], 72), F8(m, acc[1], 80), F8(m, acc[1], 88)
MMA_KBLOCKS(192, "%192", "%193", 768, 896)

#define HSTEP(oa, ob)                                                                       \
  "mov.b64 db, {%97, hb};\nadd.u64 db, db, " #ob ";\nmov.b64 da, {%96, ha};\nadd.u64 da, da, " #oa ";\n" \
  "wgmma.mma_async.sync.aligned.m64n192k16.f32.bf16.bf16 {" ACC192_0 "}, da, db, 1, 1, 1, 0, 1;\n"
__device__ __forceinline__ void mma_half(float (&d)[96], uint32_t a, uint32_t b) {
  asm volatile("{\n.reg .b32 ha, hb;\n.reg .b64 da, db;\nmov.b32 ha, 0x40000080;\nmov.b32 hb, 0x40000040;\n"
               "wgmma.fence.sync.aligned;\n" HSTEP(0, 0) HSTEP(2, 128) HSTEP(4, 768) HSTEP(6, 896)
               "wgmma.commit_group.sync.aligned;\n}\n"
               : F8("+f", d, 0), F8("+f", d, 8), F8("+f", d, 16), F8("+f", d, 24), F8("+f", d, 32), F8("+f", d, 40),
                 F8("+f", d, 48), F8("+f", d, 56), F8("+f", d, 64), F8("+f", d, 72), F8("+f", d, 80), F8("+f", d, 88)
               : "r"(a), "r"(b) : "memory");
}

#define TSTEP(REGS, W, X, ow, ox)                                                           \
  "mov.b64 db, {" X ", hi};\nadd.u64 db, db, " #ox ";\nmov.b64 da, {" W ", hi};\nadd.u64 da, da, " #ow ";\n" \
  "wgmma.mma_async.sync.aligned.m64n128k16.f32.bf16.bf16 {" REGS "}, da, db, 1, 1, 1, 1, 0;\n"
#define THEAD "{\n.reg .b32 hi;\n.reg .b64 da, db;\nmov.b32 hi, 0x40000040;\nwgmma.fence.sync.aligned;\n"
#define TTAIL "wgmma.commit_group.sync.aligned;\n}\n"
__device__ __forceinline__ void mma_kblock_t(float (&acc)[2][96], uint32_t wd, uint32_t xd) {
  asm volatile(THEAD TSTEP(ACC128_0, "%128", "%129", 0, 0) TSTEP(ACC128_1, "%128", "%129", 256, 0)
               TSTEP(ACC128_0, "%128", "%129", 128, 2) TSTEP(ACC128_1, "%128", "%129", 384, 2)
               TSTEP(ACC128_0, "%128", "%129", 512, 4) TSTEP(ACC128_1, "%128", "%129", 768, 4)
               TSTEP(ACC128_0, "%128", "%129", 640, 6) TSTEP(ACC128_1, "%128", "%129", 896, 6) TTAIL
               : OPS128("+f") : "r"(wd), "r"(xd) : "memory");
}
__device__ __forceinline__ void mma_half_t(float (&d)[96], uint32_t wd, uint32_t xd) {
  asm volatile(THEAD TSTEP(ACC128_0, "%64", "%65", 0, 0) TSTEP(ACC128_0, "%64", "%65", 128, 2)
               TSTEP(ACC128_0, "%64", "%65", 512, 4) TSTEP(ACC128_0, "%64", "%65", 640, 6) TTAIL
               : F8("+f", d, 0), F8("+f", d, 8), F8("+f", d, 16), F8("+f", d, 24), F8("+f", d, 32), F8("+f", d, 40),
                 F8("+f", d, 48), F8("+f", d, 56) : "r"(wd), "r"(xd) : "memory");
}

enum { kModePlain = 0, kModeHead = 1, kModeSkip = 2, kModeContinue = 3 };

template <int N>
__device__ __forceinline__ void fence_acc(float (&acc)[2][96]) {
#pragma unroll
  for (int h = 0; h < 2; h++)
#pragma unroll
    for (int i = 0; i < N / 2; i++) asm volatile("" : "+f"(acc[h][i])::"memory");
}

constexpr uint32_t kToB = (kTileBytes >> 4) + ((4096u >> 4) << 16) - (1u << 16);

#define TRACE_KB(nb)

template <int N>
__device__ __forceinline__ void head_blocks(float (&acc)[2][96], uint32_t sb, int n0, int slot, int xver,
                                            uint32_t rel_addr, bool rel) {
  const uint32_t ring = (((sb & 0x3FFFF) + kSmRing) >> 4) | (1u << 16);
  const uint32_t xdesc = (((sb & 0x3FFFF) + kSmX) >> 4) | (1u << 16);
  const uint32_t s0 = ring + slot * 2560, s1 = ring + ((slot + 1) & 3) * 2560;
  const uint32_t to_b = xver > 0 ? kToB - (kTileBytes >> 4) : kToB;
  const uint32_t nb = n0 * 8, xbar = sb + kBarX + (xver - 1) * 16;
  if (xver > 0) {
    mbar_wait(xbar, 0);
    mbar_wait(sb + kBarTurn + (xver == 1 ? 2 : 3 * xver) * 8, 0);
  }
  mbar_wait(sb + kBarFull + (nb & 56), nb >> 6);
  if (n0 == 0) TRACE_AT(0, 1);
  TRACE_KB(nb);
  mma_kblock<N, 2>(acc, xver > 0 ? xdesc : s0, s0 + to_b);
  if (xver > 0) mbar_wait(xbar + 8, 0);
  mbar_wait(sb + kBarFull + (nb & 56) + 8, nb >> 6);
  TRACE_KB(nb + 8);
  mma_kblock<N, 0>(acc, xver > 0 ? xdesc + (kTileBytes >> 4) : s1, s1 + to_b);
  wg_wait<1>();
  if (rel) mbar_arrive_cluster(rel_addr + (nb & 56));
  wg_wait<0>();
  if (rel) mbar_arrive_cluster(rel_addr + (nb & 56) + 8);
  fence_acc<N>(acc);
}

enum { kPlain, kResid, kStagger };
template <int N, int KIND, class Pre>
__device__ __forceinline__ void mainloop(float (&acc)[2][96], uint32_t sb, int tile, int n0, int slot, int nkb,
                                         int pause_kk, int att, uint32_t rel_addr, bool rel, int own_kk, Pre pre,
                                         uint32_t prev = 64) {
  constexpr bool RESID = KIND == kResid;
  constexpr uint32_t kStep = (N == 192 ? 5 : 4) * 512;
  const uint32_t ring = (((sb & 0x3FFFF) + kSmRing) >> 4) | (1u << 16);
  uint32_t st = ring + slot * kStep;
  uint32_t nb = n0 * 8;
  const uint32_t last = nb + 8 * (nkb - (RESID ? 4 : KIND == kStagger ? 2 : 1)), own = nb + 8 * own_kk;
  const uint32_t stg = (((sb & 0x3FFFF) + kSmStg) >> 4) | (1u << 16);
  uint32_t stop = pause_kk >= 0 ? nb + 8 * pause_kk : last;
  const bool signal = (threadIdx.x & 127) == 64;
  fence_acc<N>(acc);
  if (tile > 0) mbar_wait(sb + kBarTurn + (tile - 1) * 8, 0);
  TRACE_AT(tile, 0);
#pragma unroll 1
  while (true) {
#pragma unroll 1
    do {
      mbar_wait(sb + kBarFull + (nb & 56), nb >> 6);
      TRACE_KB(nb);
      if constexpr (RESID) mma_kblock_t(acc, st + kToB, nb == own ? stg : st);
      else mma_kblock<N, 0>(acc, st, st + kToB);
      wg_wait<1>();
      if (rel) mbar_arrive_cluster(rel_addr + prev);
      prev = nb & 56;
      st += kStep;
      if (st == ring + 10240) st = ring;
      nb += 8;
    } while (nb != stop);
    if (stop == last) break;
    stop = last;
    if (signal) mbar_arrive(sb + kBarPause + att * 8);
    wg_wait<0>();
    if (rel) mbar_arrive_cluster(rel_addr + prev);
    prev = 64;
    mbar_wait(sb + kBarResume + att * 8, 0);
  }
  mbar_wait(sb + kBarFull + (nb & 56), nb >> 6);
  TRACE_KB(nb);
  if constexpr (RESID) {
    const uint32_t z = gridDim.y - 1;
    const uint32_t s1 = st + kStep, s2 = s1 + kStep, s3 = s2 == ring + 8192 ? ring : s2 + kStep;
    mma_half_t(acc[0], st + kToB, st);
    wg_wait<1>();
    if (rel) mbar_arrive_cluster(rel_addr + 24);
    mbar_wait(sb + kBarFull + 40, nb >> 6);
    TRACE_KB(nb + 8);
    mma_half_t(acc[0], s1 + kToB, s1);
    mbar_wait(sb + kBarFull + 48, nb >> 6);
    TRACE_KB(nb + 16);
    mma_half_t(acc[0], s2 + kToB, s2);
    mbar_wait(sb + kBarFull + 56, nb >> 6);
    TRACE_KB(nb + 24);
    mma_half_t(acc[0], s3 + kToB, s3);
    mma_half_t(acc[1], st + kToB + 256, st + z);
    mma_half_t(acc[1], s1 + kToB + 256, s1 + z);
    wg_wait<2>();
#pragma unroll
    for (int i = 0; i < 64; i++) asm volatile("" : "+f"(acc[0][i])::"memory");
    pre(0);
    mma_half_t(acc[1], s2 + kToB + 256, s2 + z);
    wg_wait<2>();
    if (rel) mbar_arrive_cluster(rel_addr + 32);
    pre(1);
    mma_half_t(acc[1], s3 + kToB + 256, s3 + z);
    wg_wait<2>();
    if (rel) mbar_arrive_cluster(rel_addr + 40);
    wg_wait<1>();
    if (signal) mbar_arrive(sb + kBarTurn + tile * 8);
    if (rel) mbar_arrive_cluster(rel_addr + 48);
    wg_wait<0>();
    if (rel) mbar_arrive_cluster(rel_addr + 56);
#pragma unroll
    for (int i = 0; i < 64; i++) asm volatile("" : "+f"(acc[1][i])::"memory");
  } else if constexpr (KIND == kStagger) {
    const uint32_t z = gridDim.y - 1, s2 = st + kStep;
    mma_half(acc[1], st + 64, st + kToB);
    wg_wait<1>();
    if (rel) mbar_arrive_cluster(rel_addr + 40);
    mbar_wait(sb + kBarFull + 56, nb >> 6);
    TRACE_KB(nb + 8);
    mma_half(acc[1], s2 + 64, s2 + kToB);
    mma_half(acc[0], st, st + z + kToB);
    pre(0);
    mma_half(acc[0], s2, s2 + z + kToB);
    wg_wait<2>();
#pragma unroll
    for (int i = 0; i < 96; i++) asm volatile("" : "+f"(acc[1][i])::"memory");
    pre(1);
    wg_wait<1>();
    if (rel) mbar_arrive_cluster(rel_addr + 48);
    pre(2);
    if (signal) mbar_arrive(sb + kBarTurn + tile * 8);
    pre(3);
    wg_wait<0>();
    if (rel) mbar_arrive_cluster(rel_addr + 56);
#pragma unroll
    for (int i = 0; i < 96; i++) asm volatile("" : "+f"(acc[0][i])::"memory");
  } else {
    mma_kblock<N, 1>(acc, st, st + kToB);
    wg_wait<2>();
    if (rel) mbar_arrive_cluster(rel_addr + prev);
    pre();
    wg_wait<1>();
    if (signal) mbar_arrive(sb + kBarTurn + tile * 8);
    wg_wait<0>();
    if (rel) mbar_arrive_cluster(rel_addr + (nb & 56));
    fence_acc<N>(acc);
  }
}

__device__ __forceinline__ void publish_stats(uint32_t sb, uint2* stat, int w, int lane, unsigned epoch) {
  const uint32_t row = sb + kSmX + (32 * w + lane) * 128;
  float s[4], q[4];
#pragma unroll
  for (int c = 0; c < 4; c++) s[c] = q[c] = 0.f;
  uint32_t nx[4];
  ldsm4(row + ((lane & 7) << 4), nx);
#pragma unroll 1
  for (int J = 1; J <= 16; J++) {
    const uint32_t r[4] = {nx[0], nx[1], nx[2], nx[3]};
    ldsm4(row + ((J >> 3) & 1) * kTileBytes + (((J ^ lane) & 7) << 4), nx);
#pragma unroll
    for (int c = 0; c < 4; c++) {
      const float lo = bf_lo(r[c]);
      s[c] += lo;
      q[c] = fmaf(lo, lo, q[c]);
      if (c & 1) yield_slot();
    }
#pragma unroll
    for (int c = 0; c < 4; c++) {
      const float hi = bf_hi(r[c]);
      s[c] += hi;
      q[c] = fmaf(hi, hi, q[c]);
      if (c & 1) yield_slot();
    }
  }
  const int t = lane & 3, g = lane >> 2;
#pragma unroll
  for (int c = 0; c < 2; c++) {
    s[c] = (t & 2 ? s[c + 2] : s[c]) + shfl_xor(t & 2 ? s[c] : s[c + 2], 2);
    q[c] = (t & 2 ? q[c + 2] : q[c]) + shfl_xor(t & 2 ? q[c] : q[c + 2], 2);
  }
  const float so = (t & 1 ? s[1] : s[0]) + shfl_xor(t & 1 ? s[0] : s[1], 1);
  const float qo = (t & 1 ? q[1] : q[0]) + shfl_xor(t & 1 ? q[0] : q[1], 1);
  asm volatile("{\n.reg .b64 t;\nmov.b64 t, {%1, %2};\nst.relaxed.gpu.global.b64 [%0], t;\n}" ::"l"(stat + 32 * w + 8 * t + g),
               "r"(tag_value(so, epoch)), "r"(__float_as_uint(qo)) : "memory");
}

__device__ __forceinline__ void add_chunk(float (&a)[8], const uint4& v) {
  a[0] += bf_lo(v.x); a[1] += bf_hi(v.x);
  a[2] += bf_lo(v.y); a[3] += bf_hi(v.y);
  a[4] += bf_lo(v.z); a[5] += bf_hi(v.z);
  a[6] += bf_lo(v.w); a[7] += bf_hi(v.w);
}

__device__ __forceinline__ int helper_col(int id, int slab) {
  return (slab < 3 ? slab * kD : (slab - 3) * 512) + id * 128;
}
__device__ __forceinline__ void helper_cta(const CUtensorMap* map_q, const CUtensorMap* map_1, uint8_t* sm,
                                           uint32_t sb, int id, int warp) {
  constexpr int kRed = 6 * 32768, kBar = kRed + 2 * 4096;
  const int tid = threadIdx.x;
  if (warp == 8 && elect()) {
#pragma unroll
    for (int s = 0; s < 6; s++) {
      mbar_init(sb + kBar + s * 8, 1);
      mbar_init(sb + kBar + 64 + s * 8, 4);
    }
    fence_async_smem();
#pragma unroll
    for (int s = 0; s < 6; s++) {
      mbar_expect_tx(sb + kBar + s * 8, 32768);
      tma2d(sb + s * 32768, map_q, sb + kBar + s * 8, id * 128, s * 128);
    }
  }
  __syncthreads();
  if (warp == 8) {
    int slot = 0, ph = 0;
#pragma unroll 1
    for (int n = 6; n < 80; n++) {
      mbar_wait(sb + kBar + 64 + slot * 8, ph);
      if (elect()) {
        mbar_expect_tx(sb + kBar + slot * 8, 32768);
        tma2d(sb + slot * 32768, n < 24 ? map_q : map_1, sb + kBar + slot * 8, helper_col(id, n >> 3), (n & 7) * 128);
      }
      if (++slot == 6) slot = 0, ph ^= 1;
    }
  } else if (warp < 8) {
    if (tid == 0) *reinterpret_cast<unsigned*>(sm + kBar + 128) = atomicAdd(&g_ticket, 1u) / kGrid + 1;
    int slot = warp >> 2, ph = 0;
#pragma unroll 1
    for (int slab = 0; slab < 10; slab++) {
      float a[8];
#pragma unroll
      for (int e = 0; e < 8; e++) a[e] = 0.f;
#pragma unroll 1
      for (int box = 0; box < 4; box++) {
        mbar_wait_bounded(sb + kBar + slot * 8, ph);
        const uint4* p = reinterpret_cast<const uint4*>(sm + slot * 32768) + (tid & 127);
        uint4 v[16];
#pragma unroll
        for (int i = 0; i < 16; i++) v[i] = p[i * 128];
        __syncwarp();
        if (elect()) mbar_arrive(sb + kBar + 64 + slot * 8);
#pragma unroll
        for (int i = 0; i < 16; i++) add_chunk(a, v[i]);
        slot += 2;
        if (slot >= 6) slot -= 6, ph ^= 1;
      }
      float* red = reinterpret_cast<float*>(sm + kRed + (slab & 1) * 4096);
#pragma unroll
      for (int e = 0; e < 8; e++) a[e] += shfl_xor(a[e], 16);
      if ((tid & 16) == 0) {
        float4* d = reinterpret_cast<float4*>(red + warp * 128 + (tid & 15) * 8);
        d[0] = make_float4(a[0], a[1], a[2], a[3]);
        d[1] = make_float4(a[4], a[5], a[6], a[7]);
      }
      asm volatile("bar.sync 1, 256;" ::: "memory");
      if (warp < 4) {
        float t = 0.f;
#pragma unroll
        for (int q = 0; q < 8; q++) t += red[q * 128 + tid];
        st_relaxed(g_cs + (slab < 3 ? 0 : 3 * kD) + helper_col(id, slab) + tid,
                   tag_value(t, *reinterpret_cast<volatile unsigned*>(sm + kBar + 128)));
      }
    }
  }
}

__device__ __forceinline__ void colsum_strip(const CUtensorMap* map, uint8_t* sm, uint32_t sb, int col, int half,
                                             int lane, unsigned epoch) {
  const uint32_t bar = sb + kBarSlab + half * 16;
  const int buf = kSmStg + half * 8192;
  float a[8];
#pragma unroll
  for (int e = 0; e < 8; e++) a[e] = 0.f;
#pragma unroll 1
  for (int r = -2; r < 4; r++) {
    if (r >= 0) {
      mbar_wait(bar + (r & 1) * 8, r >> 1);
      const uint4* p = reinterpret_cast<const uint4*>(sm + buf + (r & 1) * 4096) + lane;
#pragma unroll 1
      for (int q = 0; q < 8; q += 4) {
        uint4 v[4];
#pragma unroll
        for (int u = 0; u < 4; u++) v[u] = p[(q + u) * 32];
#pragma unroll
        for (int u = 0; u < 4; u++) {
          a[0] += bf_lo(v[u].x); a[1] += bf_hi(v[u].x); a[2] += bf_lo(v[u].y); a[3] += bf_hi(v[u].y);
          yield_slot();
          a[4] += bf_lo(v[u].z); a[5] += bf_hi(v[u].z); a[6] += bf_lo(v[u].w); a[7] += bf_hi(v[u].w);
          yield_slot();
        }
      }
      fence_async_smem();
      __syncwarp();
    }
    if (r < 2 && elect()) {
      mbar_expect_tx(bar + (r & 1) * 8, 4096);
      tma2d(sb + buf + (r & 1) * 4096, map, bar + (r & 1) * 8, col, half * 512 + (r + 2) * 128);
    }
  }
#pragma unroll
  for (int e = 0; e < 4; e++) a[e] = (lane & 16 ? a[e + 4] : a[e]) + shfl_xor(lane & 16 ? a[e] : a[e + 4], 16);
#pragma unroll
  for (int e = 0; e < 2; e++) a[e] = (lane & 8 ? a[e + 2] : a[e]) + shfl_xor(lane & 8 ? a[e] : a[e + 2], 8);
  a[0] = (lane & 4 ? a[1] : a[0]) + shfl_xor(lane & 4 ? a[0] : a[1], 4);
  a[0] += shfl_xor(a[0], 2);
  if (!(lane & 2)) st_relaxed(g_cs + half * (3 * kD + kF) + col + (lane & 1) * 8 + (lane >> 2), tag_value(a[0], epoch));
}

constexpr float kGeluBeta = 0.3292034911525734f / 2.f;
constexpr float kGeluK = 2.423681954311584f / 4.f;
constexpr float kHScale = 2.f * kGeluBeta;

__device__ __forceinline__ void store_staged(uint8_t* dst, uint32_t stg) {
  fence_async_smem();
  __syncwarp();
  if (elect()) {
    bulk_store(dst, stg, 4096);
    bulk_commit();
  }
}

template <int J0, int J1>
__device__ __forceinline__ void fold_norm(float (&acc)[2][96], const float2 (&st)[4], const float4* vec) {
  float4 vn = vec[J0 * 4];
#pragma unroll
  for (int J = J0; J < J1; J++) {
    const float4 v = vn;
    if (J + 1 < J1) vn = vec[J * 4 + 4];
#pragma unroll
    for (int c = 0; c < 4; c++) {
      float& a0 = acc[c & 1][4 * J + (c & 2)];
      float& a1 = acc[c & 1][4 * J + (c & 2) + 1];
      a0 = fmaf(a0, st[c].x, fmaf(st[c].y, v.x, v.z));
      a1 = fmaf(a1, st[c].x, fmaf(st[c].y, v.y, v.w));
      asm volatile("" : "+f"(a0), "+f"(a1));
      if (c & 1) yield_slot();
    }
  }
}

template <int CH, class Acquire>
__device__ __forceinline__ void gelu_chunk(const float (&acc)[2][96], uint32_t stg, int lane, uint8_t* prev,
                                           Acquire acquire) {
  uint32_t pk[8][4];
  float z[3][4];
  const uint32_t row = (stg + lane * 128) ^ ((lane & 7) << 4);
#define U(s, e) acc[(e) >> 1][4 * (CH * 8 + ((s) >> 1)) + 2 * ((s) & 1) + ((e) & 1)]
#pragma unroll
  for (int s = 0; s < 18; s++) {
    const int cur = s % 3, p1 = (s + 2) % 3, p2 = (s + 1) % 3, q = s - 2, jj = 2 * q - 24;
    const bool mid = s >= 1 && s < 17;
    if (mid) z[p1][0] = tanh_fast(z[p1][0]);
    if (s < 16) {
#pragma unroll
      for (int e = 0; e < 4; e++) {
        z[cur][e] = fmaf(U(s, e), U(s, e), kGeluK);
        asm volatile("" : "+f"(z[cur][e]));
      }
    }
    if (jj >= 0) stsm4(row ^ (jj << 4), pk[jj][0], pk[jj][1], pk[jj][2], pk[jj][3]);
    yield_slot();
    if (mid) z[p1][1] = tanh_fast(z[p1][1]);
    if (q >= 0) {
      pk[q >> 1][2 * (q & 1)] = pack2(fmaf(U(q, 0), z[p2][0], U(q, 0)), fmaf(U(q, 1), z[p2][1], U(q, 1)));
      pk[q >> 1][2 * (q & 1) + 1] = pack2(fmaf(U(q, 2), z[p2][2], U(q, 2)), fmaf(U(q, 3), z[p2][3], U(q, 3)));
    }
    if (mid) z[p1][2] = tanh_fast(z[p1][2]);
    if (s < 16) {
#pragma unroll
      for (int e = 0; e < 4; e++) {
        z[cur][e] = z[cur][e] * U(s, e) * 8.f;
        asm volatile("" : "+f"(z[cur][e]));
      }
    }
    if (mid) z[p1][3] = tanh_fast(z[p1][3]);
    if (jj >= 0) stsm4(row ^ ((jj + 1) << 4), pk[jj + 1][0], pk[jj + 1][1], pk[jj + 1][2], pk[jj + 1][3]);
    yield_slot();
    if (CH == 1 && s == 1) store_staged(prev, stg);
    if (q == 11) acquire();
  }
#undef U
}

__device__ __forceinline__ void scale_stats(float2 (&st)[4]) {
#pragma unroll
  for (int c = 0; c < 4; c++) {
    st[c].x *= kGeluBeta;
    st[c].y *= st[c].x;
  }
}

__device__ __forceinline__ void add_mean_term(float (&acc)[2][96], const float2 (&st)[4], uint8_t* sm, int tq,
                                              int lane) {
  const float2* cs = reinterpret_cast<const float2*>(sm + kSmCsQ) + tq * 96 + (lane & 3);
  float2 vn = cs[0];
#pragma unroll
  for (int J = 0; J < 24; J++) {
    const float2 v = vn;
    if (J < 23) vn = cs[J * 4 + 4];
#pragma unroll
    for (int c = 0; c < 4; c++) {
      acc[c & 1][4 * J + (c & 2)] = fmaf(st[c].y, v.x, acc[c & 1][4 * J + (c & 2)]);
      acc[c & 1][4 * J + (c & 2) + 1] = fmaf(st[c].y, v.y, acc[c & 1][4 * J + (c & 2) + 1]);
    }
    yield_slot();
  }
}

struct AttnRegs {
  uint32_t q[4][8], k[5][8], vt[5][8];
};
#define SCALED(c, J) pack2(acc[(c) & 1][4 * (J) + ((c) & 2)] * st[c].x, acc[(c) & 1][4 * (J) + ((c) & 2) + 1] * st[c].x)
__device__ __forceinline__ void convert_group(const float (&acc)[2][96], const float2 (&st)[4], AttnRegs& r, int c,
                                              int part) {
#pragma unroll
  for (int J = 0; J < 8; J++) {
    if (part == 0) r.q[c][J] = SCALED(c, J);
    if (part == 1) r.k[c + 1][J] = SCALED(c, 8 + J);
    if (part == 2) r.vt[c + 1][J] = transpose8(SCALED(c, 16 + J));
    if (J & 1) yield_slot();
  }
}
#undef SCALED

__device__ __forceinline__ void convert_odd(const float (&acc)[2][96], const float2 (&st)[4], AttnRegs& r, int step,
                                            uint8_t* sm, uint32_t halo_bar, uint4* halo_out, bool send,
                                            unsigned epoch, int w, int lane) {
  if (step == 1) {
    convert_group(acc, st, r, 3, 2);
    convert_group(acc, st, r, 3, 1);
    if (w < 3) {
      uint2* hs = reinterpret_cast<uint2*>(sm + kSmHalo + w * 2048) + lane;
#pragma unroll
      for (int i = 0; i < 4; i++) {
        hs[i * 32] = make_uint2(r.k[4][2 * i], r.k[4][2 * i + 1]);
        hs[128 + i * 32] = make_uint2(r.vt[4][2 * i], r.vt[4][2 * i + 1]);
      }
      __syncwarp();
      if (elect()) mbar_arrive(halo_bar + w * 8);
    } else if (send) {
#pragma unroll
      for (int i = 0; i < 4; i++) {
        st_packet(halo_out + lane + i * 32, r.k[4][2 * i], r.k[4][2 * i + 1], epoch);
        st_packet(halo_out + lane + 128 + i * 32, r.vt[4][2 * i], r.vt[4][2 * i + 1], epoch);
      }
    }
  } else if (step == 2) {
    convert_group(acc, st, r, 1, 2);
  } else {
    convert_group(acc, st, r, 1, 1);
    convert_group(acc, st, r, 3, 0);
    convert_group(acc, st, r, 1, 0);
  }
}

__device__ __forceinline__ void epilogue_attn(const float (&acc)[2][96], const float2 (&st)[4], AttnRegs& r,
                                              uint8_t* sm, uint32_t sb, int layer, int tq, int b, int j,
                                              unsigned epoch, int tile, int w, int lane) {
  const int t = lane & 3, g = lane >> 2;
  const int hp = j + 8 * tq, att = 2 * layer + tq;
  auto& q = r.q;
  auto& k = r.k;
  auto& vt = r.vt;
  const bool first = w == 0 && (b & 7) == 0;
  const uint4* gh = g_halo + ((layer * 16 + b - 1) * 16 + hp) * 256 + lane;
  uint32_t tag[8];
#define LOAD_HALO()                                                                                    \
  _Pragma("unroll") for (int i = 0; i < 4; i++) {                                                      \
    ld_packet(gh + i * 32, k[0][2 * i], k[0][2 * i + 1], tag[i]);                                      \
    ld_packet(gh + 128 + i * 32, vt[0][2 * i], vt[0][2 * i + 1], tag[4 + i]);                          \
  }
#pragma unroll
  for (int c = 0; c < 6; c++) {
    if (c == 2) {
#pragma unroll
      for (int i = 0; i < 8; i++) k[0][i] = vt[0][i] = tag[i] = 0u;
      if (w > 0) {
        mbar_wait(sb + kBarHalo + (att * 3 + w - 1) * 8, 0);
        const uint2* hs = reinterpret_cast<const uint2*>(sm + kSmHalo + (w - 1) * 2048) + lane;
#pragma unroll
        for (int i = 0; i < 4; i++) {
          const uint2 a = hs[i * 32], d = hs[128 + i * 32];
          k[0][2 * i] = a.x; k[0][2 * i + 1] = a.y;
          vt[0][2 * i] = d.x; vt[0][2 * i + 1] = d.y;
        }
      } else if (!first) {
        LOAD_HALO();
      }
    }
    convert_group(acc, st, r, 2 * (c & 1), 2 - (c >> 1));
  }
  TRACE_AT(tile, 8);
  if (w == 0 && !first) {
#pragma unroll 1
    while (__any_sync(0xffffffffu, ((tag[0] ^ epoch) | (tag[1] ^ epoch) | (tag[2] ^ epoch) | (tag[3] ^ epoch)) |
                                       ((tag[4] ^ epoch) | (tag[5] ^ epoch) | (tag[6] ^ epoch) | (tag[7] ^ epoch)))) {
      LOAD_HALO();
    }
  }
  constexpr float kScale = 0.17677669529663687f * 1.4426950408889634f;
  const bool own0 = 2 * t <= g, own1 = 2 * t + 1 <= g;
  const uint32_t own_mask = (own0 ? 0xffffu : 0u) | (own1 ? 0xffff0000u : 0u);
  const uint32_t stg = sb + kSmStg + w * 4096;
  const uint32_t orow = stg + (lane & 7) * 128, ochunk = (lane >> 3) ^ (lane & 7);
  TRACE_AT(tile, 9);
  mbar_wait(sb + kBarPause + att * 8, 0);
  TRACE_AT(tile, 10);

  float s[2][6][4], o[2][4][2][4];
#pragma unroll
  for (int n = 0; n < 24; n++) {
    const int ks = n / 12, hd = (n % 12) / 6, m = n % 6, ca = 2 * (m / 3), kg = ca + m % 3, J = 4 * hd + 2 * ks;
    if (ks == 0) s[hd][m][0] = s[hd][m][1] = s[hd][m][2] = s[hd][m][3] = 0.f;
    mma16816(s[hd][m], q[ca][J], q[ca + 1][J], q[ca][J + 1], q[ca + 1][J + 1], k[kg][J], k[kg][J + 1]);
  }
  float v0[2][4], v1[2][4], m[2][4];
  uint32_t pp[2][4], po[2][4];
#define UNITS _Pragma("unroll") for (int hd = 0; hd < 2; hd++) _Pragma("unroll") for (int c = 0; c < 4; c++)
  UNITS {
    const int mp = 3 * (c >> 1) + (c & 1), r = 2 * (c & 1);
    float p0 = s[hd][mp][r], p1 = s[hd][mp][r + 1];
    if (c == 0 && first) p0 = p1 = -INFINITY;
    v0[hd][c] = own0 ? s[hd][mp + 1][r] : p0;
    v1[hd][c] = own1 ? s[hd][mp + 1][r + 1] : p1;
    m[hd][c] = fmaxf(v0[hd][c], v1[hd][c]);
  }
  UNITS m[hd][c] = fmaxf(m[hd][c], shfl_xor(m[hd][c], 1));
  UNITS m[hd][c] = fmaxf(m[hd][c], shfl_xor(m[hd][c], 2));
  UNITS {
    const float nm = -m[hd][c] * kScale;
    v0[hd][c] = ex2(fmaf(v0[hd][c], kScale, nm));
    v1[hd][c] = ex2(fmaf(v1[hd][c], kScale, nm));
    m[hd][c] = v0[hd][c] + v1[hd][c];
  }
  UNITS m[hd][c] += shfl_xor(m[hd][c], 1);
  UNITS m[hd][c] += shfl_xor(m[hd][c], 2);
  UNITS {
    const float inv = rcp(m[hd][c]);
    const uint32_t p = pack2(v0[hd][c] * inv, v1[hd][c] * inv);
    pp[hd][c] = p & ~own_mask;
    po[hd][c] = p & own_mask;
    asm volatile("" : "+r"(pp[hd][c]), "+r"(po[hd][c]));
  }
#pragma unroll
  for (int n = 0; n < 24; n++) {
    const int ph = n / 8, hd = (n >> 2) & 1, c = 2 * ((n >> 1) & 1) + (ph == 1), ds = n & 1, J = 4 * hd + 2 * ds;
    float(&d)[4] = o[hd][c][ds];
    if (ph < 2) d[0] = d[1] = d[2] = d[3] = 0.f;
    if (ph == 0) mma1688(d, vt[c + 1][J], vt[c + 1][J + 1], po[hd][c]);
    if (ph == 1) mma16816(d, vt[c][J], vt[c][J + 1], vt[c + 1][J], vt[c + 1][J + 1], pp[hd][c], po[hd][c]);
    if (ph == 2) mma1688(d, vt[c][J], vt[c][J + 1], pp[hd][c]);
    if (n == 3) {
      yield_slot();
      if (tq == 0 && lane == 0) mbar_arrive(sb + kBarResume + att * 8);
    }
  }
  yield_slot();
  if (tq == 1 && lane == 0) mbar_arrive(sb + kBarResume + att * 8);
  TRACE_AT(tile, 11);
  UNITS stsm4_t(orow + c * 1024 + ((ochunk ^ (4 * hd)) << 4), pack2(o[hd][c][0][0], o[hd][c][0][1]),
                pack2(o[hd][c][0][2], o[hd][c][0][3]), pack2(o[hd][c][1][0], o[hd][c][1][1]),
                pack2(o[hd][c][1][2], o[hd][c][1][3]));
#undef UNITS
#undef LOAD_HALO
  fence_async_smem();
  __syncwarp();
  TRACE_AT(tile, 12);
  if (elect()) {
    bulk_store(g_o + (b * 16 + hp) * kTileBytes + w * 4096, stg, 4096);
    bulk_commit();
    bulk_wait();
    TRACE_AT(tile, 13);
    mbar_arrive(sb + kBarEpi + tile * 8);
  }
  __syncwarp();
}

__device__ __forceinline__ void gather_stats(uint8_t* sm, const uint2* stat, int r, float eps, unsigned epoch) {
  uint2 a[8];
  unsigned diff;
#pragma unroll 1
  do {
    __nanosleep(800);
    diff = 0;
#pragma unroll
    for (int i = 0; i < 8; i++) {
      a[i] = ld_relaxed64(stat + i * 128 + r);
      diff |= a[i].x ^ epoch;
    }
  } while (__any_sync(0xffffffffu, diff & 7u));
  float s = 0.f, q = 0.f;
#pragma unroll
  for (int i = 0; i < 8; i++) {
    s += untag_value(a[i].x);
    q += __uint_as_float(a[i].y);
  }
  const float mean = s * (1.f / 1024.f);
  const float var = fmaxf(fmaf(-mean, mean, q * (1.f / 1024.f)), 0.f);
  reinterpret_cast<float2*>(sm + kSmStat)[r] = make_float2(rsqrtf(var + eps), -mean);
}

__device__ __forceinline__ void gather_colsums_qkv(uint8_t* sm, int tq, int j, int lane, unsigned epoch) {
  const uint2* src = reinterpret_cast<const uint2*>(g_cs + (j + 8 * tq) * 64) + lane;
  uint2 v[3], u[3];
  unsigned diff, spins = 0;
#pragma unroll 1
  do {
    if (++spins > kSpinLimit) __trap();
    diff = 0;
#pragma unroll
    for (int q = 0; q < 3; q++) {
      v[q] = ld_relaxed_pair(src + q * (kD / 2));
      u[q] = make_uint2(epoch & 7u, epoch & 7u);
      if (tq) u[q] = ld_relaxed_pair(src + (q * kD + 3 * kD + kF) / 2);
    }
#pragma unroll
    for (int q = 0; q < 3; q++) diff |= (v[q].x ^ epoch) | (v[q].y ^ epoch) | (u[q].x ^ epoch) | (u[q].y ^ epoch);
  } while (__any_sync(0xffffffffu, diff & 7u));
#pragma unroll
  for (int q = 0; q < 3; q++)
    reinterpret_cast<float2*>(sm + kSmCsQ)[tq * 96 + q * 32 + lane] =
        make_float2(untag_value(v[q].x) + untag_value(u[q].x), untag_value(v[q].y) + untag_value(u[q].y));
}

__device__ __forceinline__ void gather_colsums_w1(uint8_t* sm, const __nv_bfloat16* b1, int j, int lane,
                                                  unsigned epoch) {
#pragma unroll 1
  for (int blk = 0; blk < 7; blk++) {
    const int pair = 32 * (blk + (blk < 3 ? 3 * j : blk < 5 ? 21 + 2 * j : 35 + 2 * j)) + lane;
    const uint32_t bias = reinterpret_cast<const uint32_t*>(b1)[pair];
    uint2 v;
    unsigned spins = 0;
#pragma unroll 1
    do {
      if (++spins > kSpinLimit) __trap();
      v = ld_relaxed_pair(reinterpret_cast<const uint2*>(g_cs + 3 * kD) + pair);
    } while (__any_sync(0xffffffffu, ((v.x ^ epoch) | (v.y ^ epoch)) & 7u));
    reinterpret_cast<float4*>(sm + kSmV1)[blk * 32 + lane] =
        make_float4(untag_value(v.x), untag_value(v.y), kGeluBeta * bf_lo(bias), kGeluBeta * bf_hi(bias));
  }
}

constexpr int kPauseQkv = 7, kPauseWo = 2;

__global__ void __cluster_dims__(2, 1, 1) __launch_bounds__(384, 1)
fused_layers_kernel(const __grid_constant__ CUtensorMap map_x, const __grid_constant__ CUtensorMap map_out,
                    const __grid_constant__ CUtensorMap map_qkv, const __grid_constant__ CUtensorMap map_wo,
                    const __grid_constant__ CUtensorMap map_w1a, const __grid_constant__ CUtensorMap map_w1b,
                    const __grid_constant__ CUtensorMap map_w2, const __grid_constant__ CUtensorMap map_csq,
                    const __grid_constant__ CUtensorMap map_cs1, const __grid_constant__ CUtensorMap map_css,
                    const __grid_constant__ Params prm) {
  extern __shared__ __align__(1024) uint8_t sm[];
  if (threadIdx.x < 128 && blockIdx.x < kCtas) TRACE_AT(15, 1);
  const uint32_t sb = __shfl_sync(0xffffffffu, smem_u32(sm), 0);
  const int warp = __shfl_sync(0xffffffffu, threadIdx.x >> 5, 0), lane = threadIdx.x & 31;
  const int cta = blockIdx.x, rank = cta & 1, cl = cta >> 1;
  const int grp = cl < 4 ? 0 : cl < 36 ? (cl - 4) & 7 : 1 + (cl - 36) % 7;
  const int j = cl < 4 ? 4 + cl : cl < 36 ? (cl - 4) >> 3 : 4 + (cl - 36) / 7;
  const int b = 2 * grp + rank;
  const int xcol = (b >> 3) * kD, xrow = (b & 7) * 128;

  if (cta >= kCtas) {
    helper_cta(&map_csq, &map_cs1, sm, sb, cta - kCtas, warp);
    return;
  }
  if ((warp < 8 || warp == 9) && elect()) {
    if (warp == 9) {
#pragma unroll
      for (int s = 0; s < 8; s++) mbar_init(sb + kBarFull + s * 8, 1);
      fence_async_smem();
#pragma unroll 1
      for (int s = 0; s < 4; s++) {
        const uint32_t full = sb + kBarFull + s * 8, dst = sb + kSmRing + s * 40960;
        mbar_expect_tx(full, 40960);
        tma2d(dst, &map_x, full, xcol + (s & 1) * 64, xrow);
        tma3d(dst + kTileBytes, &map_qkv, full, (j + 4 * (s & 2)) * 64, (s & 1) * 64, 0);
        tma3d(dst + kTileBytes + 12288, &map_qkv, full, (j + 4 * (s & 2)) * 64, (s & 1) * 64 + 32, 0);
      }
    } else {
      if (sb & 1023) __trap();
#pragma unroll
      for (int s = 0; s < 16; s++) mbar_init(sb + kBarTurn + warp * 128 + s * 8, warp < 5 ? 1 : warp == 5 ? 2 : 4);
    }
    asm volatile("fence.mbarrier_init.release.cluster;" ::: "memory");
  }
  __syncwarp();
  asm volatile("barrier.cluster.arrive.relaxed.aligned;" ::: "memory");

  if (warp >= 8) {
    asm volatile("setmaxnreg.dec.sync.aligned.u32 40;");
    if (warp < 10) {
      asm volatile("barrier.cluster.wait.aligned;" ::: "memory");
      uint32_t nb = 32, off = 0, kb = 0;
#define RING_STEP(WAIT, ISSUE)                                            \
  do {                                                                    \
    const uint32_t mb = nb - depth, full = sb + kBarFull + (nb & 56);     \
    if (kb == skip) kb += inc;                                            \
    mbar_wait(sb + kBarEmpty + (mb & 56), mb >> 6);                       \
    WAIT;                                                                 \
    if (elect()) { ISSUE; }                                               \
    TRACE_ISSUE(9 - warp, nb);                                            \
    kb += inc;                                                            \
    off = off == wrap ? 0 : off + step;                                   \
    nb += 8;                                                              \
  } while (nb != nend)
#pragma unroll 1
      for (int sg = 0; sg < kSegs; sg++) {
        const uint32_t e = prm.seg[sg];
        const int ty = e & 7, mode = (e >> 15) & 3, reset = (e >> 24) & 3;
        const uint32_t nend = nb + (e & 0x1f8);
        const uint32_t step = (e >> 17) & 1 ? 40960 : 32768, wrap = 163840 - step;
        const uint32_t depth = (e >> 18) & 1 ? 40 : 32;
        if (reset) off = reset == 1 ? 0 : reset == 2 ? 40960 : 131072;
        const uint32_t own = ty == 2 ? 8 + j : 2 * j;
        if (mode != kModeContinue) kb = ((e >> 9) & 63) + (mode == kModeHead ? own : 0);
        const uint32_t inc = mode >= kModeSkip && ty != 2 ? 2 : 1, skip = mode >= kModeSkip ? own + (kb & 1) : 255;
        if (warp == 8) {
          const CUtensorMap* map = ty < 2 ? &map_qkv : ty == 2 ? &map_wo : ty == 3 ? &map_w1a : ty < 6 ? &map_w1b : &map_w2;
          const int c0 = ty < 2 ? (j + 8 * ty) * 64 : 0;
          const int c2 = ty < 2 ? 0 : ty == 3 ? 3 * j : ty == 4 ? 24 + 2 * j : ty == 5 ? 40 + 2 * j : 2 * j;
          const uint32_t half = (ty < 2 || ty == 3) ? 12288 : 8192;
          const uint32_t bytes = 2 * half + (mode == kModeHead ? 0 : kTileBytes);
          const uint32_t dst = sb + kSmRing + (mode == kModeHead && ty != 2 ? 0 : kTileBytes) + rank * half;
          if (e >> 26) {
            const bool second = (grp & 6) == 2;
            const int pk = grp < 4 ? 2 * j + (grp & 1) : 2 * (grp - 4 + (grp - 4 >= j));
            const CUtensorMap* pm = ty == 6 ? &map_qkv : second ? &map_w1b : &map_w1a;
            if (elect())
              asm volatile("cp.async.bulk.prefetch.tensor.3d.L2.global [%0, {%1, %2, %3}];" ::"l"(pm),
                           "r"(ty == 6 ? (j + 8 * second) * 64 : 0), "r"(pk * 64 + rank * 32),
                           "r"(ty == 6 ? 0 : second ? 24 + 2 * j : 3 * j) : "memory");
          }
          if (ty == 2 && mode == kModeHead) mbar_wait(sb + kBarEpi + ((e >> 19) & 31) * 8, 0);
#pragma unroll 1
          RING_STEP(, mbar_expect_tx(full, bytes); tma3d_mc(dst + off, map, full, c0, kb * 64 + rank * 32, c2));
        } else if (mode == kModeHead) {
          off += ((nend - nb) >> 3) * step;
          nb = nend;
          if (off >= 163840) off -= 163840;
        } else if (sg < 2) {
#pragma unroll 1
          RING_STEP(, tma2d(sb + kSmRing + off, &map_x, full, xcol + kb * 64, xrow));
        } else {
          const uint8_t* src = ty == 6 ? g_h + b * 56 * kTileBytes : (ty == 2 ? g_o : g_x) + b * 16 * kTileBytes;
          const int dep = (e >> 19) & 31;
          if (dep < 28) mbar_wait(sb + kBarReady + dep * 8, 0);
          if ((dep & 30) == 28) {
#pragma unroll 1
            RING_STEP(mbar_wait(sb + kBarSrc + ((kb << (4 - inc)) & 56), dep),
                      bulk_load(sb + kSmRing + off, src + kb * kTileBytes, kTileBytes, full));
          } else {
#pragma unroll 1
            RING_STEP(, bulk_load(sb + kSmRing + off, src + kb * kTileBytes, kTileBytes, full));
          }
        }
      }
#undef RING_STEP
    } else {
      unsigned epoch = 0;
      if (warp == 10) {
        if (lane == 0) epoch = atomicAdd(&g_ticket, 1u) / kGrid + 1;
        *reinterpret_cast<unsigned*>(sm + kSmEpoch) = __shfl_sync(0xffffffffu, epoch, 0);
        asm volatile("barrier.cluster.wait.aligned;" ::: "memory");
        if (elect()) mbar_arrive(sb + kBarEpoch);
      } else {
        asm volatile("barrier.cluster.wait.aligned;" ::: "memory");
        mbar_wait_bounded(sb + kBarFull, 0);
        if (elect()) {
          mbar_expect_tx(sb + kBarInit, 32768);
          tma2d(sb + kSmX, &map_x, sb + kBarInit, xcol + j * 128, xrow);
          tma2d(sb + kSmX + kTileBytes, &map_x, sb + kBarInit, xcol + j * 128 + 64, xrow);
        }
        const uint2 u = reinterpret_cast<const uint2*>(prm.b2)[32 * j + lane];
        reinterpret_cast<float4*>(sm + kSmB2)[lane] = make_float4(
            kHScale * bf_lo(u.x), kHScale * bf_hi(u.x), kHScale * bf_lo(u.y), kHScale * bf_hi(u.y));
      }
      mbar_wait_bounded(sb + kBarEpoch, 0);
      epoch = *reinterpret_cast<volatile unsigned*>(sm + kSmEpoch);
      if (cta < 96) {
        mbar_wait_bounded(sb + kBarInit, 0);
        colsum_strip(&map_css, sm, sb, (cta >> 5) * kD + 512 + (cta & 31) * 16, warp - 10, lane, epoch);
      }
      gather_colsums_qkv(sm, 11 - warp, j, lane, epoch);
      __syncwarp();
      if (elect()) mbar_arrive(sb + kBarCs + (11 - warp) * 8);
      if (warp == 10) {
        const unsigned* flag = g_flag + b * 32 + (lane & 7);
        unsigned count = epoch * 32;
#pragma unroll 1
        for (int i = 0; i < kTiles - 1; i++) {
          const bool xt = i == 2 || i == 6 || i == 9;
          count++;
          mbar_wait(sb + (xt ? kBarX + (i >> 2) * 16 : kBarEpi + i * 8), 0);
          if (xt || i == 1 || i == 8) {
            unsigned todo = 0xff;
            do {
              const unsigned now = __ballot_sync(0xffffffffu, (int)(ld_relaxed(flag) - count) >= 0) & todo;
              if (now) {
                asm volatile("fence.acquire.gpu;\nfence.proxy.async.global;" ::: "memory");
                if ((now >> lane) & 1) mbar_arrive(sb + kBarSrc + lane * 8);
                todo ^= now;
              }
              if (todo == 0xff) __nanosleep(300);
            } while (todo);
          } else {
            wait_flags(flag, count);
            if (elect()) mbar_arrive(sb + kBarReady + i * 8);
          }
          if (xt) {
            wait_flags(flag, ++count);
            if (elect()) mbar_arrive(sb + kBarReady + (14 + (i >> 2)) * 8);
          }
        }
      } else {
        unsigned count = epoch * 32;
#pragma unroll 1
        for (int i = 0; i < kTiles - 1; i++) {
          if (i == 3) {
            gather_colsums_w1(sm, prm.b1, j, lane, epoch);
            __syncwarp();
            if (elect()) mbar_arrive(sb + kBarCs + 16);
          }
          const bool xt = i == 2 || i == 6 || i == 9;
#pragma unroll 1
          for (int h = 0; h < (xt ? 2 : 1); h++) {
            if (xt && h == 0) {
              mbar_wait_bounded(sb + kBarEpi + i * 8, 0);
              if (elect()) bulk_store(g_x + (b * 16 + 2 * j) * kTileBytes, sb + kSmX, kTileBytes / 2);
            }
            mbar_wait_bounded(sb + (xt ? kBarX + (i >> 2) * 16 + 8 * h : kBarEpi + i * 8), 0);
            const int ty = i >= 7 ? i - 7 : i;
            if (ty >= 2 && elect()) {
              uint8_t* dst = xt ? g_x + (b * 16 + 2 * j + h) * kTileBytes
                                : g_h + (b * 56 + 1 + (ty == 3 ? 3 * j : 16 * ty - 40 + 2 * j)) * kTileBytes;
              const int piece = (xt && h == 0) ? kTileBytes / 2 : kTileBytes / 8;
#pragma unroll 1
              for (int o = xt && h == 0 ? piece : 0; o < kTileBytes; o += piece) {
                bulk_store(dst + o, sb + (xt ? kSmX + h * kTileBytes : kSmStg) + o, piece);
                bulk_commit();
                bulk_wait();
              }
              if (!xt) mbar_arrive(sb + kBarFree + i * 8);
            }
            __syncwarp();
            count++;
            if (elect()) st_release(&g_flag[b * 32 + j], count);
            __syncwarp();
          }
        }
#pragma unroll 1
        for (int q = 0; q < 4; q++) {
          mbar_wait_bounded(sb + (q & 1 ? kBarX + 48 : kBarEpi + (kTiles - 1) * 8) + 4 * (q & 2), 0);
          if (elect()) {
            tma2d_store(&map_out, sb + kSmX + q * 8192, xcol + j * 128 + (q >> 1) * 64, xrow + (q & 1) * 64);
            bulk_commit();
            if (q == 3) bulk_wait_read();
          }
        }
      }
    }
    __syncwarp();
    asm volatile("barrier.cluster.arrive.relaxed.aligned;\nbarrier.cluster.wait.aligned;" ::: "memory");
  } else {
    asm volatile("setmaxnreg.inc.sync.aligned.u32 232;");
    asm volatile("barrier.cluster.wait.aligned;" ::: "memory");
    const int wg = warp >> 2, w = warp & 3;
    const bool rel = (threadIdx.x & 95) == 0;
    const uint32_t rel_addr = mapa(sb + kBarEmpty, w & 1);
    if (wg == 1) TRACE_AT(15, 0);
#define EPOCH (*reinterpret_cast<volatile unsigned*>(sm + kSmEpoch))

#pragma unroll 1
    for (int i = wg; i < kTiles; i += 2) {
      const int layer = i >= 7, ty = i - 7 * layer;
      TRACE_AT(i, 15);
      float acc[2][96];
      if (ty == 2 || ty == 6) {
        const int lane = lane_id();
        const uint32_t xa = sb + kSmX + ((lane >> 4) * 8 + (lane & 7)) * 128 + (((2 * w + ((lane >> 3) & 1)) ^ (lane & 7)) << 4);
        const float up = ty == 6 ? kHScale / kXScale : layer ? 1.f / kXScale : 1.f;
        const float dn = ty == 2 ? kXScale : layer ? 1.f / kHScale : kXScale / kHScale;
#pragma unroll
        for (int h = 0; h < 2; h++) {
          const float* b2 = reinterpret_cast<const float*>(sm + kSmB2) + 64 * h + 16 * w + (lane >> 2);
          const float bias[2] = {ty == 6 ? b2[0] : 0.f, ty == 6 ? b2[8] : 0.f};
#pragma unroll
          for (int p = 0; p < 8; p++) {
            uint32_t r[4];
            ldsm4_t(xa + h * kTileBytes + p * 2048, r);
#pragma unroll
            for (int m = 0; m < 4; m++) {
              acc[h][8 * p + 2 * m] = fmaf(bf_lo(r[m]), up, bias[m & 1]);
              acc[h][8 * p + 2 * m + 1] = fmaf(bf_hi(r[m]), up, bias[m & 1]);
              asm volatile("" : "+f"(acc[h][8 * p + 2 * m]), "+f"(acc[h][8 * p + 2 * m + 1]));
            }
            yield_slot();
          }
        }
        auto stage = [&](int qt) {
          const int h = qt >> 1;
          if (qt == 1 || (qt == 3 && i == kTiles - 1)) {
            fence_async_smem();
            __syncwarp();
            if (lane == 0) mbar_arrive(sb + kBarEpi + (i + h) * 8);
          }
#pragma unroll
          for (int p = 4 * (qt & 1); p < 4 * (qt & 1) + 4; p++) {
            const float* a = &acc[h][8 * p];
            stsm4_t(xa + h * kTileBytes + p * 2048, pack2(a[0] * dn, a[1] * dn), pack2(a[2] * dn, a[3] * dn),
                    pack2(a[4] * dn, a[5] * dn), pack2(a[6] * dn, a[7] * dn));
            yield_slot();
          }
          if (qt & 1) {
            fence_async_smem();
            __syncwarp();
            if (elect()) mbar_arrive(sb + kBarX + (i >> 2) * 16 + 8 * h);
            TRACE_AT(i, 8 + h);
          }
        };
        mainloop<128, kResid>(acc, sb, i, layer * 152 + ty * 16, ty == 6 ? 4 : 0, ty == 6 ? 56 : 16,
                              ty == 2 ? kPauseWo : -1, 2 * layer + 1, rel_addr, rel, ty == 2 ? 8 : -1, stage);
        TRACE_AT(i, 2);
        stage(2);
        stage(3);
      } else {
        const int xver = 2 * layer + (ty >= 3);
        const uint32_t stg = sb + kSmStg + w * 4096;
        const float4* vec = reinterpret_cast<const float4*>(sm + kSmV1) + (ty == 3 ? 0 : 64 * ty - 160);
        int lane;
        uint8_t* hdst = g_h + (b * 56 + (ty == 3 ? 3 * j : 16 * ty - 40 + 2 * j)) * kTileBytes + w * 4096;
        float2 st[4];
        unsigned epoch;
        auto pre = [&] {
          lane = lane_id();
          if (ty < 4) mbar_wait(sb + (ty == 1 ? kBarEpi + (i - 1) * 8 : kBarStat + xver * 8), 0);
#pragma unroll
          for (int c = 0; c < 4; c++) st[c] = reinterpret_cast<const float2*>(sm + kSmStat)[32 * w + 8 * c + (lane >> 2)];
          epoch = EPOCH;
        };
        auto team_stats = [&] {
          uint2* stat = g_stat + b * 1024;
          const unsigned tag = EPOCH * 4 + xver;
          lane = lane_id();
          publish_stats(sb, stat + j * 128, w, lane, tag);
          gather_stats(sm, stat, 32 * w + lane, xver ? 1e-5f * kXScale * kXScale : 1e-5f, tag);
          __syncwarp();
          if (elect()) mbar_arrive(sb + kBarStat + xver * 8);
          TRACE_AT(i, 14);
        };
        if (ty < 4) {
          AttnRegs ar;
          auto odd = [&](int step) {
            if (step == 0) pre();
            else convert_odd(acc, st, ar, step, sm, sb + kBarHalo + (xver + ty) * 24,
                             g_halo + ((layer * 16 + b) * 16 + j + 8 * ty) * 256, (b & 7) != 7, epoch, w, lane);
          };
          head_blocks<192>(acc, sb, layer * 152 + (ty < 2 ? 2 * ty : 48), ty < 2 ? 2 * ty : 1, xver, rel_addr, rel);
          if (ty == 1) {
            if (i == 1) {
              mbar_wait(sb + kBarEpoch, 0);
              mbar_wait(sb + kBarInit, 0);
            }
            team_stats();
            epoch = 0;
#pragma unroll
            for (int c = 0; c < 4; c++) st[c] = reinterpret_cast<const float2*>(sm + kSmStat)[32 * w + 8 * c + (lane >> 2)];
          } else {
            mainloop<192, kPlain>(acc, sb, i, layer * 152 + (ty ? 52 : 4), ty ? 1 : 0, 14, -1, 0, rel_addr, rel, 0, pre);
            TRACE_AT(i, 2);
            if (ty == 3) goto wide_gelu;
          }
          if (layer == 0) mbar_wait(sb + kBarCs + ty * 8, 0);
          add_mean_term(acc, st, sm, ty, lane);
          if (ty == 1) {
            mainloop<192, kStagger>(acc, sb, i, layer * 152 + 18, 2, 14, kPauseQkv, xver, rel_addr, rel, 0, odd);
            TRACE_AT(i, 2);
          } else {
            odd(1);
            odd(2);
            odd(3);
          }
          epilogue_attn(acc, st, ar, sm, sb, layer, ty, b, j, epoch, i, w, lane);
          TRACE_AT(i, 3);
          continue;
        wide_gelu:
          if (i == 3) mbar_wait(sb + kBarCs + 16, 0);
          scale_stats(st);
          fold_norm<16, 24>(acc, st, vec + (lane & 3));
          TRACE_AT(i, 11);
          gelu_chunk<2>(acc, stg, lane, nullptr, [] {});
          TRACE_AT(i, 12);
          fold_norm<0, 2>(acc, st, vec + (lane & 3));
          store_staged(hdst + 2 * kTileBytes, stg);
          fold_norm<2, 16>(acc, st, vec + (lane & 3));
        } else {
          if (ty == 4) {
            head_blocks<128>(acc, sb, layer * 152 + 50, 3, xver, rel_addr, rel);
            team_stats();
          } else {
            const uint32_t s0 = ((((sb & 0x3FFFF) + kSmRing) >> 4) | (1u << 16)) + 3 * 2048;
            mbar_wait(sb + kBarTurn + (i - 1) * 8, 0);
            mbar_wait(sb + kBarFull, layer * 19 + 10);
            TRACE_KB((layer * 152 + 80) * 8);
            mma_kblock<128, 2>(acc, s0, s0 + kToB);
          }
          mainloop<128, kPlain>(acc, sb, i, layer * 152 + 6 + 15 * ty, 4, ty + 10, -1, 0, rel_addr, rel, 0, pre,
                                ty == 5 ? 0 : 64);
          TRACE_AT(i, 2);
          if (i == 4) mbar_wait(sb + kBarCs + 16, 0);
          scale_stats(st);
          fold_norm<0, 16>(acc, st, vec + (lane & 3));
        }
        auto own_store_done = [] {
          if (elect()) bulk_wait();
          __syncwarp();
        };
        TRACE_AT(i, 8);
        gelu_chunk<0>(acc, stg, lane, nullptr, [&] {
          if (ty == 3) own_store_done();
          else mbar_wait(sb + kBarFree + (i - 1) * 8, 0);
        });
        TRACE_AT(i, 9);
        gelu_chunk<1>(acc, stg, lane, hdst, own_store_done);
        TRACE_AT(i, 10);
        fence_async_smem();
        __syncwarp();
        if (elect()) mbar_arrive(sb + kBarEpi + i * 8);
      }
      TRACE_AT(i, 3);
    }
#undef EPOCH
    asm volatile("barrier.cluster.arrive.relaxed.aligned;\nbarrier.cluster.wait.aligned;" ::: "memory");
    if (wg == 1) TRACE_AT(15, 2);
  }
}

void build_segments(uint32_t* seg) {
  int n = 0, fine = 0;
  auto per_source = [&] { return 28 + (fine++ & 1); };
  auto add = [&](int ty, int cnt, int kb0, int mode, int wide, int depth5, int dep, int reset) {
    seg[n++] = ty | cnt << 3 | kb0 << 9 | mode << 15 | wide << 17 | depth5 << 18 | dep << 19 | reset << 24;
  };
  for (int l = 0; l < 2; l++) {
    const int t = 7 * l;
    if (l == 0) {
      add(0, 14, 2, kModePlain, 1, 0, 31, 1);
      add(1, 14, 2, kModePlain, 1, 0, 31, 0);
    } else {
      add(0, 2, 0, kModeHead, 1, 1, 31, 1);
      add(1, 2, 0, kModeHead, 1, 0, 31, 0);
      add(0, 7, 0, kModeSkip, 1, 0, per_source(), 0);
      add(0, 7, 1, kModeSkip, 1, 0, 15, 0);
      add(1, 7, 0, kModeSkip, 1, 0, 31, 0);
      add(1, 7, 1, kModeSkip, 1, 0, 31, 0);
    }
    add(2, 4, 0, kModePlain, 0, 0, t, 1);
    add(2, 4, 4, kModePlain, 0, 1, 31, 4);
    add(2, 1, 0, kModeHead, 0, 1, t + 1, 0);
    add(2, 7, 8, kModeSkip, 0, 1, per_source(), 0);
    add(3, 1, 0, kModeHead, 1, 1, 31, 2);
    add(3, 1, 1, kModeHead, 1, 0, 31, 0);
    add(4, 2, 0, kModeHead, 1, 0, 31, 0);
    add(3, 7, 0, kModeSkip, 1, 0, per_source(), 0);
    add(3, 7, 1, kModeSkip, 1, 0, 14 + 2 * l, 0);
    add(4, 4, 0, kModeSkip, 0, 0, 31, 3);
    add(4, 3, 0, kModeContinue, 0, 1, 31, 0);
    add(4, 7, 1, kModeSkip, 0, 1, 31, 0);
    add(5, 16, 0, kModePlain, 0, 1, 31, 0);
    add(6, 24, 0, kModePlain, 0, 1, t + 3, 0);
    add(6, 16, 24, kModePlain, 0, 1, t + 4, 0);
    add(6, 16, 40, kModePlain, 0, 1, t + 5, l ? 0 : 4);
  }
}

typedef CUresult (*EncodeTiledFn)(CUtensorMap*, CUtensorMapDataType, cuuint32_t, void*, const cuuint64_t*,
                                  const cuuint64_t*, const cuuint32_t*, const cuuint32_t*, CUtensorMapInterleave,
                                  CUtensorMapSwizzle, CUtensorMapL2promotion, CUtensorMapFloatOOBfill);

CUtensorMap make_map(EncodeTiledFn enc, const void* p, int rank, const cuuint64_t* dims, const cuuint64_t* strides,
                     const cuuint32_t* box, CUtensorMapSwizzle swizzle = CU_TENSOR_MAP_SWIZZLE_128B,
                     CUtensorMapL2promotion promo = CU_TENSOR_MAP_L2_PROMOTION_L2_128B) {
  CUtensorMap m;
  const cuuint32_t es[5] = {1, 1, 1, 1, 1};
  enc(&m, CU_TENSOR_MAP_DATA_TYPE_BFLOAT16, rank, const_cast<void*>(p), dims, strides, box, es,
      CU_TENSOR_MAP_INTERLEAVE_NONE, swizzle, promo, CU_TENSOR_MAP_FLOAT_OOB_FILL_NONE);
  return m;
}

CUtensorMap weight_map(EncodeTiledFn enc, const void* p, int k, int n, int blocks) {
  const cuuint64_t dims[3] = {64, (cuuint64_t)k, (cuuint64_t)n / 64};
  const cuuint64_t strides[2] = {(cuuint64_t)n * 2, 128};
  const cuuint32_t box[3] = {64, 32, (cuuint32_t)blocks};
  return make_map(enc, p, 3, dims, strides, box, CU_TENSOR_MAP_SWIZZLE_128B, CU_TENSOR_MAP_L2_PROMOTION_L2_256B);
}

CUtensorMap slab_map(EncodeTiledFn enc, const void* p, int n, int cols, int rows) {
  const cuuint64_t dims[2] = {(cuuint64_t)n, kD};
  const cuuint64_t strides[1] = {(cuuint64_t)n * 2};
  const cuuint32_t box[2] = {(cuuint32_t)cols, (cuuint32_t)rows};
  return make_map(enc, p, 2, dims, strides, box, CU_TENSOR_MAP_SWIZZLE_NONE);
}

CUtensorMap token_map(EncodeTiledFn enc, const void* p, int rows) {
  const cuuint64_t dims[2] = {2 * kD, 1024};
  const cuuint64_t strides[1] = {4 * kD};
  const cuuint32_t box[2] = {64, (cuuint32_t)rows};
  return make_map(enc, p, 2, dims, strides, box);
}

}

extern "C" void kernel_launch(void* const* d_in, const int* in_sizes, int n_in, void* d_out, int out_size) {
  (void)in_sizes; (void)n_in; (void)out_size;
  static EncodeTiledFn enc = nullptr;
  if (!enc) {
    void* fn = nullptr;
    cudaDriverEntryPointQueryResult q;
    cudaGetDriverEntryPoint("cuTensorMapEncodeTiled", &fn, cudaEnableDefault, &q);
    enc = (EncodeTiledFn)fn;
    cudaFuncSetAttribute(fused_layers_kernel, cudaFuncAttributeMaxDynamicSharedMemorySize, kSmBytes);
  }
  Params prm;
  prm.b1 = (const __nv_bfloat16*)d_in[5];
  prm.b2 = (const __nv_bfloat16*)d_in[7];
  build_segments(prm.seg);
  const cuuint64_t qd[3] = {kD, kD, 3}, qs[2] = {3 * kD * 2, kD * 2};
  const cuuint32_t qb[3] = {64, 32, 3};
  const CUtensorMap map_x = token_map(enc, d_in[0], 128);
  const CUtensorMap map_out = token_map(enc, d_out, 64);
  const CUtensorMap map_qkv = make_map(enc, d_in[1], 3, qd, qs, qb);
  const CUtensorMap map_wo = weight_map(enc, d_in[2], kD, kD, 2);
  const CUtensorMap map_w1a = weight_map(enc, d_in[4], kD, kF, 3);
  const CUtensorMap map_w1b = weight_map(enc, d_in[4], kD, kF, 2);
  const CUtensorMap map_w2 = weight_map(enc, d_in[6], kF, kD, 2);
  fused_layers_kernel<<<kGrid, 384, kSmBytes>>>(map_x, map_out, map_qkv, map_wo, map_w1a, map_w1b, map_w2,
                                                slab_map(enc, d_in[1], 3 * kD, 128, 128), slab_map(enc, d_in[4], kF, 128, 128),
                                                slab_map(enc, d_in[1], 3 * kD, 16, 128), prm);
}
```

```cpp
#include <cuda.h>
#include <cuda_bf16.h>
#include <cuda_runtime.h>
#include <stdint.h>

namespace {

constexpr int kD = 1024;
constexpr int kF = 3584;
constexpr int kCtas = 128;
constexpr int kGrid = 132;
constexpr int kTiles = 14;
constexpr int kTileBytes = 16384;

constexpr int kSmRing = 0;
constexpr int kSmX = 163840;
constexpr int kSmStg = kSmX + 32768;
constexpr int kSmHalo = kSmStg + 16384;
constexpr int kSmCsQ = kSmHalo + 6144;
constexpr int kSmV1 = kSmCsQ + 384 * 4;
constexpr int kSmB2 = kSmV1 + 448 * 8;
constexpr int kSmStat = kSmB2 + 128 * 4;
constexpr int kSmBar = kSmStat + 128 * 8;
constexpr int kBarFull = kSmBar;
constexpr int kBarTurn = kBarFull + 8 * 8;
constexpr int kBarReady = kBarTurn + 14 * 8;
constexpr int kBarSrc = kBarReady + 17 * 8;
constexpr int kBarPause = kBarSrc + 8 * 8;
constexpr int kBarFree = kBarPause + 4 * 8;
constexpr int kBarCs = kBarFree + 14 * 8;
constexpr int kBarSlab = kBarCs + 3 * 8;
constexpr int kBarHalo = kBarSlab + 4 * 8;
constexpr int kBarInit = kBarHalo + 12 * 8;
constexpr int kBarEpoch = kBarInit + 8;
constexpr int kBarEmpty = kBarTurn + 5 * 128;
constexpr int kBarEpi = kBarEmpty + 128;
constexpr int kBarX = kBarEpi + 15 * 8;
constexpr int kBarStat = kBarX + 8 * 8;
constexpr int kBarResume = kBarStat + 4 * 8;
constexpr int kSmEpoch = kBarEpi + 2 * 128;
static_assert(kBarEpoch < kBarEmpty && kBarResume + 4 * 8 <= kSmEpoch, "barrier groups overflow");
constexpr int kSmBytes = kSmEpoch + 16 + 256;
constexpr int kSegs = 40;

constexpr float kXScale = 1.f / 8.f;

constexpr unsigned kSpinLimit = 1u << 22;

__device__ __align__(1024) uint8_t g_x[16 * 16 * kTileBytes];
__device__ __align__(1024) uint8_t g_o[16 * 16 * kTileBytes];
__device__ __align__(1024) uint8_t g_h[16 * 56 * kTileBytes];
__device__ __align__(128) uint2 g_stat[16 * 8 * 128];
__device__ __align__(128) unsigned g_cs[3 * kD + kF + 3 * kD];
__device__ __align__(128) uint4 g_halo[2 * 16 * 16 * 256];
__device__ __align__(128) unsigned g_flag[16 * 32];
__device__ unsigned g_ticket;

#define TRACE_AT(tile, k)
#define TRACE_PUB(i, k, c)
#define TRACE_ISSUE(which, nb)

struct Params {
  const __nv_bfloat16* b1;
  const __nv_bfloat16* b2;
  uint32_t seg[kSegs];
};

__device__ __forceinline__ uint32_t smem_u32(const void* p) {
  return (uint32_t)__cvta_generic_to_shared(p);
}
__device__ __forceinline__ uint32_t mapa(uint32_t a, uint32_t cta) {
  uint32_t r;
  asm("mapa.shared::cluster.u32 %0, %1, %2;" : "=r"(r) : "r"(a), "r"(cta));
  return r;
}
__device__ __forceinline__ void mbar_init(uint32_t bar, int cnt) {
  asm volatile("mbarrier.init.shared::cta.b64 [%0], %1;" ::"r"(bar), "r"(cnt) : "memory");
}
__device__ __forceinline__ void mbar_expect_tx(uint32_t bar, uint32_t bytes) {
  asm volatile("mbarrier.arrive.expect_tx.shared::cta.b64 _, [%0], %1;" ::"r"(bar), "r"(bytes) : "memory");
}
__device__ __forceinline__ void mbar_arrive(uint32_t bar) {
  asm volatile("mbarrier.arrive.shared::cta.b64 _, [%0];" ::"r"(bar) : "memory");
}
__device__ __forceinline__ void mbar_arrive_cluster(uint32_t cluster_addr) {
  asm volatile("mbarrier.arrive.shared::cluster.b64 _, [%0];" ::"r"(cluster_addr) : "memory");
}
__device__ __forceinline__ void mbar_wait(uint32_t bar, uint32_t parity) {
  asm volatile("{\n.reg .pred p;\nRETRY:\nmbarrier.try_wait.parity.shared::cta.b64 p, [%0], %1;\n"
               "@!p bra.uni RETRY;\n}" ::"r"(bar), "r"(parity) : "memory");
}
__device__ __forceinline__ void mbar_wait_bounded(uint32_t bar, uint32_t parity) {
  asm volatile("{\n.reg .pred p;\n.reg .u32 c;\nmov.u32 c, 0;\nRETRY:\n"
               "mbarrier.try_wait.parity.shared::cta.b64 p, [%0], %1;\n@p bra.uni DONE;\n"
               "add.u32 c, c, 1;\nsetp.lt.u32 p, c, %2;\n@p bra.uni RETRY;\ntrap;\nDONE:\n}"
               ::"r"(bar), "r"(parity), "n"(1u << 19) : "memory");
}
__device__ __forceinline__ void tma3d(uint32_t dst, const CUtensorMap* m, uint32_t bar, int c0, int c1, int c2) {
  asm volatile(
      "cp.async.bulk.tensor.3d.shared::cluster.global.mbarrier::complete_tx::bytes [%0], [%1, {%3, %4, %5}], [%2];"
      ::"r"(dst), "l"(m), "r"(bar), "r"(c0), "r"(c1), "r"(c2) : "memory");
}
__device__ __forceinline__ void tma3d_mc(uint32_t dst, const CUtensorMap* m, uint32_t bar, int c0, int c1, int c2) {
  asm volatile(
      "cp.async.bulk.tensor.3d.shared::cluster.global.mbarrier::complete_tx::bytes.multicast::cluster"
      " [%0], [%1, {%3, %4, %5}], [%2], %6;"
      ::"r"(dst), "l"(m), "r"(bar), "r"(c0), "r"(c1), "r"(c2), "h"((uint16_t)3) : "memory");
}
__device__ __forceinline__ void tma2d(uint32_t dst, const CUtensorMap* m, uint32_t bar, int c0, int c1) {
  asm volatile(
      "cp.async.bulk.tensor.2d.shared::cluster.global.mbarrier::complete_tx::bytes [%0], [%1, {%3, %4}], [%2];"
      ::"r"(dst), "l"(m), "r"(bar), "r"(c0), "r"(c1) : "memory");
}
__device__ __forceinline__ void tma2d_store(const CUtensorMap* m, uint32_t src, int c0, int c1) {
  asm volatile("cp.async.bulk.tensor.2d.global.shared::cta.bulk_group [%0, {%2, %3}], [%1];"
               ::"l"(m), "r"(src), "r"(c0), "r"(c1) : "memory");
}
__device__ __forceinline__ int lane_id() {
  int l;
  asm volatile("mov.u32 %0, %%laneid;" : "=r"(l));
  return l;
}
__device__ __forceinline__ bool elect() {
  uint32_t p;
  asm volatile("{\n.reg .pred p;\nelect.sync _|p, 0xffffffff;\nselp.b32 %0, 1, 0, p;\n}" : "=r"(p));
  return p;
}
__device__ __forceinline__ void bulk_load(uint32_t dst, const void* src, uint32_t bytes, uint32_t bar) {
  asm volatile("cp.async.bulk.shared::cluster.global.mbarrier::complete_tx::bytes [%0], [%1], %2, [%3];"
               ::"r"(dst), "l"(src), "r"(bytes), "r"(bar) : "memory");
}
__device__ __forceinline__ void bulk_store(void* dst, uint32_t src, uint32_t bytes) {
  asm volatile("cp.async.bulk.global.shared::cta.bulk_group [%0], [%1], %2;" ::"l"(dst), "r"(src), "r"(bytes)
               : "memory");
}
__device__ __forceinline__ void bulk_commit() { asm volatile("cp.async.bulk.commit_group;" ::: "memory"); }
__device__ __forceinline__ void bulk_wait_read() { asm volatile("cp.async.bulk.wait_group.read 0;" ::: "memory"); }
__device__ __forceinline__ void bulk_wait() { asm volatile("cp.async.bulk.wait_group 0;" ::: "memory"); }
__device__ __forceinline__ void fence_async_smem() { asm volatile("fence.proxy.async.shared::cta;" ::: "memory"); }
__device__ __forceinline__ unsigned ld_relaxed(const unsigned* p) {
  unsigned v;
  asm volatile("ld.relaxed.gpu.global.u32 %0, [%1];" : "=r"(v) : "l"(p) : "memory");
  return v;
}
__device__ __forceinline__ uint2 ld_relaxed64(const uint2* p) {
  uint2 v;
  asm volatile("{\n.reg .b64 t;\nld.relaxed.gpu.global.b64 t, [%2];\nmov.b64 {%0, %1}, t;\n}"
               : "=r"(v.x), "=r"(v.y) : "l"(p) : "memory");
  return v;
}
__device__ __forceinline__ void st_relaxed(unsigned* p, unsigned v) {
  asm volatile("st.relaxed.gpu.global.u32 [%0], %1;" ::"l"(p), "r"(v) : "memory");
}
__device__ __forceinline__ void st_release(unsigned* p, unsigned v) {
  asm volatile("st.release.gpu.global.u32 [%0], %1;" ::"l"(p), "r"(v) : "memory");
}
__device__ __forceinline__ void wait_flags(const unsigned* p, unsigned count) {
  while (__any_sync(0xffffffffu, (int)(ld_relaxed(p) - count) < 0)) {
    __nanosleep(400);
  }
  asm volatile("fence.acquire.gpu;\nfence.proxy.async.global;" ::: "memory");
  __syncwarp();
}
__device__ __forceinline__ void st_packet(uint4* p, uint32_t d0, uint32_t d1, uint32_t tag) {
  asm volatile("{\n.reg .b128 v;\n.reg .b64 x, y;\nmov.b64 x, {%1, %2};\nmov.b64 y, {%3, %3};\nmov.b128 v, {x, y};\n"
               "st.relaxed.gpu.global.b128 [%0], v;\n}" ::"l"(p), "r"(d0), "r"(d1), "r"(tag) : "memory");
}
__device__ __forceinline__ void ld_packet(const uint4* p, uint32_t& d0, uint32_t& d1, uint32_t& tag) {
  asm volatile("{\n.reg .b128 v;\n.reg .b64 x, y;\n.reg .b32 u;\nld.relaxed.gpu.global.b128 v, [%3];\n"
               "mov.b128 {x, y}, v;\nmov.b64 {%0, %1}, x;\nmov.b64 {%2, u}, y;\n}"
               : "=r"(d0), "=r"(d1), "=r"(tag) : "l"(p) : "memory");
}
__device__ __forceinline__ uint2 ld_relaxed_pair(const uint2* p) {
  uint2 v;
  asm volatile("ld.relaxed.gpu.global.v2.u32 {%0, %1}, [%2];" : "=r"(v.x), "=r"(v.y) : "l"(p) : "memory");
  return v;
}
__device__ __forceinline__ unsigned tag_value(float v, unsigned epoch) {
  return (__float_as_uint(v) & ~7u) | (epoch & 7u);
}
__device__ __forceinline__ float untag_value(unsigned v) { return __uint_as_float(v & ~7u); }
__device__ __forceinline__ void stsm4(uint32_t a, uint32_t r0, uint32_t r1, uint32_t r2, uint32_t r3) {
  asm volatile("stmatrix.sync.aligned.m8n8.x4.shared.b16 [%0], {%1, %2, %3, %4};" ::"r"(a), "r"(r0), "r"(r1),
               "r"(r2), "r"(r3) : "memory");
}
__device__ __forceinline__ void stsm4_t(uint32_t a, uint32_t r0, uint32_t r1, uint32_t r2, uint32_t r3) {
  asm volatile("stmatrix.sync.aligned.m8n8.x4.trans.shared.b16 [%0], {%1, %2, %3, %4};" ::"r"(a), "r"(r0),
               "r"(r1), "r"(r2), "r"(r3) : "memory");
}
__device__ __forceinline__ uint32_t transpose8(uint32_t a) {
  uint32_t d;
  asm volatile("movmatrix.sync.aligned.m8n8.trans.b16 %0, %1;" : "=r"(d) : "r"(a));
  return d;
}
__device__ __forceinline__ void mma16816(float (&c)[4], uint32_t a0, uint32_t a1, uint32_t a2, uint32_t a3,
                                         uint32_t b0, uint32_t b1) {
  asm volatile("mma.sync.aligned.m16n8k16.row.col.f32.bf16.bf16.f32 {%0, %1, %2, %3}, {%4, %5, %6, %7}, {%8, %9}, "
               "{%0, %1, %2, %3};"
               : "+f"(c[0]), "+f"(c[1]), "+f"(c[2]), "+f"(c[3])
               : "r"(a0), "r"(a1), "r"(a2), "r"(a3), "r"(b0), "r"(b1));
}
__device__ __forceinline__ void mma1688(float (&c)[4], uint32_t a0, uint32_t a1, uint32_t b0) {
  asm volatile("mma.sync.aligned.m16n8k8.row.col.f32.bf16.bf16.f32 {%0, %1, %2, %3}, {%4, %5}, {%6}, {%0, %1, %2, %3};"
               : "+f"(c[0]), "+f"(c[1]), "+f"(c[2]), "+f"(c[3]) : "r"(a0), "r"(a1), "r"(b0));
}
__device__ __forceinline__ float shfl_xor(float v, int m) {
  float r;
  asm volatile("shfl.sync.bfly.b32 %0, %1, %2, 31, 0xffffffff;" : "=f"(r) : "f"(v), "r"(m));
  return r;
}
__device__ __forceinline__ float tanh_fast(float x) {
  float r;
  asm volatile("tanh.approx.f32 %0, %1;" : "=f"(r) : "f"(x));
  return r;
}
__device__ __forceinline__ void ldsm4(uint32_t a, uint32_t (&r)[4]) {
  asm volatile("ldmatrix.sync.aligned.m8n8.x4.shared.b16 {%0, %1, %2, %3}, [%4];"
               : "=r"(r[0]), "=r"(r[1]), "=r"(r[2]), "=r"(r[3]) : "r"(a) : "memory");
}
__device__ __forceinline__ void ldsm4_t(uint32_t a, uint32_t (&r)[4]) {
  asm volatile("ldmatrix.sync.aligned.m8n8.x4.trans.shared.b16 {%0, %1, %2, %3}, [%4];"
               : "=r"(r[0]), "=r"(r[1]), "=r"(r[2]), "=r"(r[3]) : "r"(a) : "memory");
}
__device__ __forceinline__ uint32_t pack2(float lo, float hi) {
  uint32_t r;
  asm volatile("cvt.rn.bf16x2.f32 %0, %1, %2;" : "=r"(r) : "f"(hi), "f"(lo));
  return r;
}
__device__ __forceinline__ float bf_lo(uint32_t r) { return __uint_as_float(r << 16); }
__device__ __forceinline__ float bf_hi(uint32_t r) { return __uint_as_float(r & 0xffff0000u); }
__device__ __forceinline__ float ex2(float x) {
  float r;
  asm("ex2.approx.ftz.f32 %0, %1;" : "=f"(r) : "f"(x));
  return r;
}
__device__ __forceinline__ float rcp(float x) {
  float r;
  asm("rcp.approx.ftz.f32 %0, %1;" : "=f"(r) : "f"(x));
  return r;
}
template <int N>
__device__ __forceinline__ void wg_wait() {
  asm volatile("wgmma.wait_group.sync.aligned %0;" ::"n"(N) : "memory");
}
__device__ __forceinline__ void yield_slot() { asm volatile("pmevent 0;"); }

template <int N, int KIND>
__device__ __forceinline__ void mma_kblock(float (&acc)[2][96], uint32_t a, uint32_t b);

#define F8(m, d, i) m(d[i]), m(d[i + 1]), m(d[i + 2]), m(d[i + 3]), m(d[i + 4]), m(d[i + 5]), m(d[i + 6]), m(d[i + 7])
#define KSTEP(N, A, B, oa0, oa1, ob, sd)                                                   \
  "mov.b64 db, {" B ", hb};\nadd.u64 db, db, " #ob ";\n"                                    \
  "mov.b64 da, {" A ", ha};\nadd.u64 da, da, " #oa0 ";\n"                                   \
  "wgmma.mma_async.sync.aligned.m64n" #N "k16.f32.bf16.bf16 {" ACC##N##_0 "}, da, db, " #sd ", 1, 1, 0, 1;\n" \
  "mov.b64 da, {" A ", ha};\nadd.u64 da, da, " #oa1 ";\n"                                   \
  "wgmma.mma_async.sync.aligned.m64n" #N "k16.f32.bf16.bf16 {" ACC##N##_1 "}, da, db, " #sd ", 1, 1, 0, 1;\n"

#define MMA_KBLOCK(N, KIND, A, B, ob2, ob3, sd, MID, MODE)                                 \
  template <>                                                                              \
  __device__ __forceinline__ void mma_kblock<N, KIND>(float (&acc)[2][96], uint32_t a, uint32_t b) { \
    asm volatile("{\n.reg .b32 ha, hb;\n.reg .b64 da, db;\n"                            \
                 "mov.b32 ha, 0x40000080;\nmov.b32 hb, 0x40000040;\n"                       \
                 "wgmma.fence.sync.aligned;\n"                                             \
                 KSTEP(N, A, B, 0, 64, 0, sd) KSTEP(N, A, B, 2, 66, 128, 1) MID               \
                 KSTEP(N, A, B, 4, 68, ob2, 1) KSTEP(N, A, B, 6, 70, ob3, 1) "wgmma.commit_group.sync.aligned;\n}\n"  \
                 : OPS##N(MODE) : "r"(a), "r"(b) : "memory");                              \
  }
#define MMA_KBLOCKS(N, A, B, ob2, ob3)                                                     \
  MMA_KBLOCK(N, 0, A, B, ob2, ob3, 1, "", "+f")                                            \
  MMA_KBLOCK(N, 1, A, B, ob2, ob3, 1, "wgmma.commit_group.sync.aligned;\n", "+f")          \
  MMA_KBLOCK(N, 2, A, B, ob2, ob3, 0, "", "=f")

#define ACC128_0 \
  "%0, %1, %2, %3, %4, %5, %6, %7, %8, %9, %10, %11, %12, %13, %14, %15, " \
  "%16, %17, %18, %19, %20, %21, %22, %23, %24, %25, %26, %27, %28, %29, %30, %31, " \
  "%32, %33, %34, %35, %36, %37, %38, %39, %40, %41, %42, %43, %44, %45, %46, %47, " \
  "%48, %49, %50, %51, %52, %53, %54, %55, %56, %57, %58, %59, %60, %61, %62, %63"
#define ACC128_1 \
  "%64, %65, %66, %67, %68, %69, %70, %71, %72, %73, %74, %75, %76, %77, %78, %79, " \
  "%80, %81, %82, %83, %84, %85, %86, %87, %88, %89, %90, %91, %92, %93, %94, %95, " \
  "%96, %97, %98, %99, %100, %101, %102, %103, %104, %105, %106, %107, %108, %109, %110, %111, " \
  "%112, %113, %114, %115, %116, %117, %118, %119, %120, %121, %122, %123, %124, %125, %126, %127"
#define OPS128(m) \
  F8(m, acc[0], 0), F8(m, acc[0], 8), F8(m, acc[0], 16), F8(m, acc[0], 24), F8(m, acc[0], 32), F8(m, acc[0], 40), F8(m, acc[0], 48), F8(m, acc[0], 56), \
        F8(m, acc[1], 0), F8(m, acc[1], 8), F8(m, acc[1], 16), F8(m, acc[1], 24), F8(m, acc[1], 32), F8(m, acc[1], 40), F8(m, acc[1], 48), F8(m, acc[1], 56)
MMA_KBLOCKS(128, "%128", "%129", 512, 640)

#define ACC192_0 \
  "%0, %1, %2, %3, %4, %5, %6, %7, %8, %9, %10, %11, %12, %13, %14, %15, " \
  "%16, %17, %18, %19, %20, %21, %22, %23, %24, %25, %26, %27, %28, %29, %30, %31, " \
  "%32, %33, %34, %35, %36, %37, %38, %39, %40, %41, %42, %43, %44, %45, %46, %47, " \
  "%48, %49, %50, %51, %52, %53, %54, %55, %56, %57, %58, %59, %60, %61, %62, %63, " \
  "%64, %65, %66, %67, %68, %69, %70, %71, %72, %73, %74, %75, %76, %77, %78, %79, " \
  "%80, %81, %82, %83, %84, %85, %86, %87, %88, %89, %90, %91, %92, %93, %94, %95"
#define ACC192_1 \
  "%96, %97, %98, %99, %100, %101, %102, %103, %104, %105, %106, %107, %108, %109, %110, %111, " \
  "%112, %113, %114, %115, %116, %117, %118, %119, %120, %121, %122, %123, %124, %125, %126, %127, " \
  "%128, %129, %130, %131, %132, %133, %134, %135, %136, %137, %138, %139, %140, %141, %142, %143, " \
  "%144, %145, %146, %147, %148, %149, %150, %151, %152, %153, %154, %155, %156, %157, %158, %159, " \
  "%160, %161, %162, %163, %164, %165, %166, %167, %168, %169, %170, %171, %172, %173, %174, %175, " \
  "%176, %177, %178, %179, %180, %181, %182, %183, %184, %185, %186, %187, %188, %189, %190, %191"
#define OPS192(m) \
  F8(m, acc[0], 0), F8(m, acc[0], 8), F8(m, acc[0], 16), F8(m, acc[0], 24), F8(m, acc[0], 32), F8(m, acc[0], 40), F8(m, acc[0], 48), F8(m, acc[0], 56), F8(m, acc[0], 64), F8(m, acc[0], 72), F8(m, acc[0], 80), F8(m, acc[0], 88), \
        F8(m, acc[1], 0), F8(m, acc[1], 8), F8(m, acc[1], 16), F8(m, acc[1], 24), F8(m, acc[1], 32), F8(m, acc[1], 40), F8(m, acc[1], 48), F8(m, acc[1], 56), F8(m, acc[1], 64), F8(m, acc[1], 72), F8(m, acc[1], 80), F8(m, acc[1], 88)
MMA_KBLOCKS(192, "%192", "%193", 768, 896)

#define HSTEP(oa, ob)                                                                       \
  "mov.b64 db, {%97, hb};\nadd.u64 db, db, " #ob ";\nmov.b64 da, {%96, ha};\nadd.u64 da, da, " #oa ";\n" \
  "wgmma.mma_async.sync.aligned.m64n192k16.f32.bf16.bf16 {" ACC192_0 "}, da, db, 1, 1, 1, 0, 1;\n"
__device__ __forceinline__ void mma_half(float (&d)[96], uint32_t a, uint32_t b) {
  asm volatile("{\n.reg .b32 ha, hb;\n.reg .b64 da, db;\nmov.b32 ha, 0x40000080;\nmov.b32 hb, 0x40000040;\n"
               "wgmma.fence.sync.aligned;\n" HSTEP(0, 0) HSTEP(2, 128) HSTEP(4, 768) HSTEP(6, 896)
               "wgmma.commit_group.sync.aligned;\n}\n"
               : F8("+f", d, 0), F8("+f", d, 8), F8("+f", d, 16), F8("+f", d, 24), F8("+f", d, 32), F8("+f", d, 40),
                 F8("+f", d, 48), F8("+f", d, 56), F8("+f", d, 64), F8("+f", d, 72), F8("+f", d, 80), F8("+f", d, 88)
               : "r"(a), "r"(b) : "memory");
}

#define TSTEP(REGS, W, X, ow, ox)                                                           \
  "mov.b64 db, {" X ", hi};\nadd.u64 db, db, " #ox ";\nmov.b64 da, {" W ", hi};\nadd.u64 da, da, " #ow ";\n" \
  "wgmma.mma_async.sync.aligned.m64n128k16.f32.bf16.bf16 {" REGS "}, da, db, 1, 1, 1, 1, 0;\n"
#define THEAD "{\n.reg .b32 hi;\n.reg .b64 da, db;\nmov.b32 hi, 0x40000040;\nwgmma.fence.sync.aligned;\n"
#define TTAIL "wgmma.commit_group.sync.aligned;\n}\n"
__device__ __forceinline__ void mma_kblock_t(float (&acc)[2][96], uint32_t wd, uint32_t xd) {
  asm volatile(THEAD TSTEP(ACC128_0, "%128", "%129", 0, 0) TSTEP(ACC128_1, "%128", "%129", 256, 0)
               TSTEP(ACC128_0, "%128", "%129", 128, 2) TSTEP(ACC128_1, "%128", "%129", 384, 2)
               TSTEP(ACC128_0, "%128", "%129", 512, 4) TSTEP(ACC128_1, "%128", "%129", 768, 4)
               TSTEP(ACC128_0, "%128", "%129", 640, 6) TSTEP(ACC128_1, "%128", "%129", 896, 6) TTAIL
               : OPS128("+f") : "r"(wd), "r"(xd) : "memory");
}
__device__ __forceinline__ void mma_half_t(float (&d)[96], uint32_t wd, uint32_t xd) {
  asm volatile(THEAD TSTEP(ACC128_0, "%64", "%65", 0, 0) TSTEP(ACC128_0, "%64", "%65", 128, 2)
               TSTEP(ACC128_0, "%64", "%65", 512, 4) TSTEP(ACC128_0, "%64", "%65", 640, 6) TTAIL
               : F8("+f", d, 0), F8("+f", d, 8), F8("+f", d, 16), F8("+f", d, 24), F8("+f", d, 32), F8("+f", d, 40),
                 F8("+f", d, 48), F8("+f", d, 56) : "r"(wd), "r"(xd) : "memory");
}

enum { kModePlain = 0, kModeHead = 1, kModeSkip = 2, kModeContinue = 3 };

template <int N>
__device__ __forceinline__ void fence_acc(float (&acc)[2][96]) {
#pragma unroll
  for (int h = 0; h < 2; h++)
#pragma unroll
    for (int i = 0; i < N / 2; i++) asm volatile("" : "+f"(acc[h][i])::"memory");
}

constexpr uint32_t kToB = (kTileBytes >> 4) + ((4096u >> 4) << 16) - (1u << 16);

#define TRACE_KB(nb)

template <int N>
__device__ __forceinline__ void head_blocks(float (&acc)[2][96], uint32_t sb, int n0, int slot, int xver,
                                            uint32_t rel_addr, bool rel) {
  const uint32_t ring = (((sb & 0x3FFFF) + kSmRing) >> 4) | (1u << 16);
  const uint32_t xdesc = (((sb & 0x3FFFF) + kSmX) >> 4) | (1u << 16);
  const uint32_t s0 = ring + slot * 2560, s1 = ring + ((slot + 1) & 3) * 2560;
  const uint32_t to_b = xver > 0 ? kToB - (kTileBytes >> 4) : kToB;
  const uint32_t nb = n0 * 8, xbar = sb + kBarX + (xver - 1) * 16;
  if (xver > 0) {
    mbar_wait(xbar, 0);
    mbar_wait(sb + kBarTurn + (xver == 1 ? 2 : 3 * xver) * 8, 0);
  }
  mbar_wait(sb + kBarFull + (nb & 56), nb >> 6);
  if (n0 == 0) TRACE_AT(0, 1);
  TRACE_KB(nb);
  mma_kblock<N, 2>(acc, xver > 0 ? xdesc : s0, s0 + to_b);
  if (xver > 0) mbar_wait(xbar + 8, 0);
  mbar_wait(sb + kBarFull + (nb & 56) + 8, nb >> 6);
  TRACE_KB(nb + 8);
  mma_kblock<N, 0>(acc, xver > 0 ? xdesc + (kTileBytes >> 4) : s1, s1 + to_b);
  wg_wait<1>();
  if (rel) mbar_arrive_cluster(rel_addr + (nb & 56));
  wg_wait<0>();
  if (rel) mbar_arrive_cluster(rel_addr + (nb & 56) + 8);
  fence_acc<N>(acc);
}

enum { kPlain, kResid, kStagger };
template <int N, int KIND, class Pre>
__device__ __forceinline__ void mainloop(float (&acc)[2][96], uint32_t sb, int tile, int n0, int slot, int nkb,
                                         int pause_kk, int att, uint32_t rel_addr, bool rel, int own_kk, Pre pre,
                                         uint32_t prev = 64) {
  constexpr bool RESID = KIND == kResid;
  constexpr uint32_t kStep = (N == 192 ? 5 : 4) * 512;
  const uint32_t ring = (((sb & 0x3FFFF) + kSmRing) >> 4) | (1u << 16);
  uint32_t st = ring + slot * kStep;
  uint32_t nb = n0 * 8;
  const uint32_t last = nb + 8 * (nkb - (RESID ? 4 : KIND == kStagger ? 2 : 1)), own = nb + 8 * own_kk;
  const uint32_t stg = (((sb & 0x3FFFF) + kSmStg) >> 4) | (1u << 16);
  uint32_t stop = pause_kk >= 0 ? nb + 8 * pause_kk : last;
  const bool signal = (threadIdx.x & 127) == 64;
  fence_acc<N>(acc);
  if (tile > 0) mbar_wait(sb + kBarTurn + (tile - 1) * 8, 0);
  TRACE_AT(tile, 0);
#pragma unroll 1
  while (true) {
#pragma unroll 1
    do {
      mbar_wait(sb + kBarFull + (nb & 56), nb >> 6);
      TRACE_KB(nb);
      if constexpr (RESID) mma_kblock_t(acc, st + kToB, nb == own ? stg : st);
      else mma_kblock<N, 0>(acc, st, st + kToB);
      wg_wait<1>();
      if (rel) mbar_arrive_cluster(rel_addr + prev);
      prev = nb & 56;
      st += kStep;
      if (st == ring + 10240) st = ring;
      nb += 8;
    } while (nb != stop);
    if (stop == last) break;
    stop = last;
    if (signal) mbar_arrive(sb + kBarPause + att * 8);
    wg_wait<0>();
    if (rel) mbar_arrive_cluster(rel_addr + prev);
    prev = 64;
    mbar_wait(sb + kBarResume + att * 8, 0);
  }
  mbar_wait(sb + kBarFull + (nb & 56), nb >> 6);
  TRACE_KB(nb);
  if constexpr (RESID) {
    const uint32_t z = gridDim.y - 1;
    const uint32_t s1 = st + kStep, s2 = s1 + kStep, s3 = s2 == ring + 8192 ? ring : s2 + kStep;
    mma_half_t(acc[0], st + kToB, st);
    wg_wait<1>();
    if (rel) mbar_arrive_cluster(rel_addr + 24);
    mbar_wait(sb + kBarFull + 40, nb >> 6);
    TRACE_KB(nb + 8);
    mma_half_t(acc[0], s1 + kToB, s1);
    mbar_wait(sb + kBarFull + 48, nb >> 6);
    TRACE_KB(nb + 16);
    mma_half_t(acc[0], s2 + kToB, s2);
    mbar_wait(sb + kBarFull + 56, nb >> 6);
    TRACE_KB(nb + 24);
    mma_half_t(acc[0], s3 + kToB, s3);
    mma_half_t(acc[1], st + kToB + 256, st + z);
    mma_half_t(acc[1], s1 + kToB + 256, s1 + z);
    wg_wait<2>();
#pragma unroll
    for (int i = 0; i < 64; i++) asm volatile("" : "+f"(acc[0][i])::"memory");
    pre(0);
    mma_half_t(acc[1], s2 + kToB + 256, s2 + z);
    wg_wait<2>();
    if (rel) mbar_arrive_cluster(rel_addr + 32);
    pre(1);
    mma_half_t(acc[1], s3 + kToB + 256, s3 + z);
    wg_wait<2>();
    if (rel) mbar_arrive_cluster(rel_addr + 40);
    wg_wait<1>();
    if (signal) mbar_arrive(sb + kBarTurn + tile * 8);
    if (rel) mbar_arrive_cluster(rel_addr + 48);
    wg_wait<0>();
    if (rel) mbar_arrive_cluster(rel_addr + 56);
#pragma unroll
    for (int i = 0; i < 64; i++) asm volatile("" : "+f"(acc[1][i])::"memory");
  } else if constexpr (KIND == kStagger) {
    const uint32_t z = gridDim.y - 1, s2 = st + kStep;
    mma_half(acc[1], st + 64, st + kToB);
    wg_wait<1>();
    if (rel) mbar_arrive_cluster(rel_addr + 40);
    mbar_wait(sb + kBarFull + 56, nb >> 6);
    TRACE_KB(nb + 8);
    mma_half(acc[1], s2 + 64, s2 + kToB);
    mma_half(acc[0], st, st + z + kToB);
    pre(0);
    mma_half(acc[0], s2, s2 + z + kToB);
    wg_wait<2>();
#pragma unroll
    for (int i = 0; i < 96; i++) asm volatile("" : "+f"(acc[1][i])::"memory");
    pre(1);
    wg_wait<1>();
    if (rel) mbar_arrive_cluster(rel_addr + 48);
    pre(2);
    if (signal) mbar_arrive(sb + kBarTurn + tile * 8);
    pre(3);
    wg_wait<0>();
    if (rel) mbar_arrive_cluster(rel_addr + 56);
#pragma unroll
    for (int i = 0; i < 96; i++) asm volatile("" : "+f"(acc[0][i])::"memory");
  } else {
    mma_kblock<N, 1>(acc, st, st + kToB);
    wg_wait<2>();
    if (rel) mbar_arrive_cluster(rel_addr + prev);
    pre();
    wg_wait<1>();
    if (signal) mbar_arrive(sb + kBarTurn + tile * 8);
    wg_wait<0>();
    if (rel) mbar_arrive_cluster(rel_addr + (nb & 56));
    fence_acc<N>(acc);
  }
}

__device__ __forceinline__ void publish_stats(uint32_t sb, uint2* stat, int w, int lane, unsigned epoch) {
  const uint32_t row = sb + kSmX + (32 * w + lane) * 128;
  float s[4], q[4];
#pragma unroll
  for (int c = 0; c < 4; c++) s[c] = q[c] = 0.f;
  uint32_t nx[4];
  ldsm4(row + ((lane & 7) << 4), nx);
#pragma unroll 1
  for (int J = 1; J <= 16; J++) {
    const uint32_t r[4] = {nx[0], nx[1], nx[2], nx[3]};
    ldsm4(row + ((J >> 3) & 1) * kTileBytes + (((J ^ lane) & 7) << 4), nx);
#pragma unroll
    for (int c = 0; c < 4; c++) {
      const float lo = bf_lo(r[c]);
      s[c] += lo;
      q[c] = fmaf(lo, lo, q[c]);
      if (c & 1) yield_slot();
    }
#pragma unroll
    for (int c = 0; c < 4; c++) {
      const float hi = bf_hi(r[c]);
      s[c] += hi;
      q[c] = fmaf(hi, hi, q[c]);
      if (c & 1) yield_slot();
    }
  }
  const int t = lane & 3, g = lane >> 2;
#pragma unroll
  for (int c = 0; c < 2; c++) {
    s[c] = (t & 2 ? s[c + 2] : s[c]) + shfl_xor(t & 2 ? s[c] : s[c + 2], 2);
    q[c] = (t & 2 ? q[c + 2] : q[c]) + shfl_xor(t & 2 ? q[c] : q[c + 2], 2);
  }
  const float so = (t & 1 ? s[1] : s[0]) + shfl_xor(t & 1 ? s[0] : s[1], 1);
  const float qo = (t & 1 ? q[1] : q[0]) + shfl_xor(t & 1 ? q[0] : q[1], 1);
  asm volatile("{\n.reg .b64 t;\nmov.b64 t, {%1, %2};\nst.relaxed.gpu.global.b64 [%0], t;\n}" ::"l"(stat + 32 * w + 8 * t + g),
               "r"(tag_value(so, epoch)), "r"(__float_as_uint(qo)) : "memory");
}

__device__ __forceinline__ void add_chunk(float (&a)[8], const uint4& v) {
  a[0] += bf_lo(v.x); a[1] += bf_hi(v.x);
  a[2] += bf_lo(v.y); a[3] += bf_hi(v.y);
  a[4] += bf_lo(v.z); a[5] += bf_hi(v.z);
  a[6] += bf_lo(v.w); a[7] += bf_hi(v.w);
}

__device__ __forceinline__ int helper_col(int id, int slab) {
  return (slab < 3 ? slab * kD : (slab - 3) * 512) + id * 128;
}
__device__ __forceinline__ void helper_cta(const CUtensorMap* map_q, const CUtensorMap* map_1, uint8_t* sm,
                                           uint32_t sb, int id, int warp) {
  constexpr int kRed = 6 * 32768, kBar = kRed + 2 * 4096;
  const int tid = threadIdx.x;
  if (warp == 8 && elect()) {
#pragma unroll
    for (int s = 0; s < 6; s++) {
      mbar_init(sb + kBar + s * 8, 1);
      mbar_init(sb + kBar + 64 + s * 8, 4);
    }
    fence_async_smem();
#pragma unroll
    for (int s = 0; s < 6; s++) {
      mbar_expect_tx(sb + kBar + s * 8, 32768);
      tma2d(sb + s * 32768, map_q, sb + kBar + s * 8, id * 128, s * 128);
    }
  }
  __syncthreads();
  if (warp == 8) {
    int slot = 0, ph = 0;
#pragma unroll 1
    for (int n = 6; n < 80; n++) {
      mbar_wait(sb + kBar + 64 + slot * 8, ph);
      if (elect()) {
        mbar_expect_tx(sb + kBar + slot * 8, 32768);
        tma2d(sb + slot * 32768, n < 24 ? map_q : map_1, sb + kBar + slot * 8, helper_col(id, n >> 3), (n & 7) * 128);
      }
      if (++slot == 6) slot = 0, ph ^= 1;
    }
  } else if (warp < 8) {
    if (tid == 0) *reinterpret_cast<unsigned*>(sm + kBar + 128) = atomicAdd(&g_ticket, 1u) / kGrid + 1;
    int slot = warp >> 2, ph = 0;
#pragma unroll 1
    for (int slab = 0; slab < 10; slab++) {
      float a[8];
#pragma unroll
      for (int e = 0; e < 8; e++) a[e] = 0.f;
#pragma unroll 1
      for (int box = 0; box < 4; box++) {
        mbar_wait_bounded(sb + kBar + slot * 8, ph);
        const uint4* p = reinterpret_cast<const uint4*>(sm + slot * 32768) + (tid & 127);
        uint4 v[16];
#pragma unroll
        for (int i = 0; i < 16; i++) v[i] = p[i * 128];
        __syncwarp();
        if (elect()) mbar_arrive(sb + kBar + 64 + slot * 8);
#pragma unroll
        for (int i = 0; i < 16; i++) add_chunk(a, v[i]);
        slot += 2;
        if (slot >= 6) slot -= 6, ph ^= 1;
      }
      float* red = reinterpret_cast<float*>(sm + kRed + (slab & 1) * 4096);
#pragma unroll
      for (int e = 0; e < 8; e++) a[e] += shfl_xor(a[e], 16);
      if ((tid & 16) == 0) {
        float4* d = reinterpret_cast<float4*>(red + warp * 128 + (tid & 15) * 8);
        d[0] = make_float4(a[0], a[1], a[2], a[3]);
        d[1] = make_float4(a[4], a[5], a[6], a[7]);
      }
      asm volatile("bar.sync 1, 256;" ::: "memory");
      if (warp < 4) {
        float t = 0.f;
#pragma unroll
        for (int q = 0; q < 8; q++) t += red[q * 128 + tid];
        st_relaxed(g_cs + (slab < 3 ? 0 : 3 * kD) + helper_col(id, slab) + tid,
                   tag_value(t, *reinterpret_cast<volatile unsigned*>(sm + kBar + 128)));
      }
    }
  }
}

__device__ __forceinline__ void colsum_strip(const CUtensorMap* map, uint8_t* sm, uint32_t sb, int col, int half,
                                             int lane, unsigned epoch) {
  const uint32_t bar = sb + kBarSlab + half * 16;
  const int buf = kSmStg + half * 8192;
  float a[8];
#pragma unroll
  for (int e = 0; e < 8; e++) a[e] = 0.f;
#pragma unroll 1
  for (int r = -2; r < 4; r++) {
    if (r >= 0) {
      mbar_wait(bar + (r & 1) * 8, r >> 1);
      const uint4* p = reinterpret_cast<const uint4*>(sm + buf + (r & 1) * 4096) + lane;
#pragma unroll 1
      for (int q = 0; q < 8; q += 4) {
        uint4 v[4];
#pragma unroll
        for (int u = 0; u < 4; u++) v[u] = p[(q + u) * 32];
#pragma unroll
        for (int u = 0; u < 4; u++) {
          a[0] += bf_lo(v[u].x); a[1] += bf_hi(v[u].x); a[2] += bf_lo(v[u].y); a[3] += bf_hi(v[u].y);
          yield_slot();
          a[4] += bf_lo(v[u].z); a[5] += bf_hi(v[u].z); a[6] += bf_lo(v[u].w); a[7] += bf_hi(v[u].w);
          yield_slot();
        }
      }
      fence_async_smem();
      __syncwarp();
    }
    if (r < 2 && elect()) {
      mbar_expect_tx(bar + (r & 1) * 8, 4096);
      tma2d(sb + buf + (r & 1) * 4096, map, bar + (r & 1) * 8, col, half * 512 + (r + 2) * 128);
    }
  }
#pragma unroll
  for (int e = 0; e < 4; e++) a[e] = (lane & 16 ? a[e + 4] : a[e]) + shfl_xor(lane & 16 ? a[e] : a[e + 4], 16);
#pragma unroll
  for (int e = 0; e < 2; e++) a[e] = (lane & 8 ? a[e + 2] : a[e]) + shfl_xor(lane & 8 ? a[e] : a[e + 2], 8);
  a[0] = (lane & 4 ? a[1] : a[0]) + shfl_xor(lane & 4 ? a[0] : a[1], 4);
  a[0] += shfl_xor(a[0], 2);
  if (!(lane & 2)) st_relaxed(g_cs + half * (3 * kD + kF) + col + (lane & 1) * 8 + (lane >> 2), tag_value(a[0], epoch));
}

constexpr float kGeluBeta = 0.3292034911525734f / 2.f;
constexpr float kGeluK = 2.423681954311584f / 4.f;
constexpr float kHScale = 2.f * kGeluBeta;

__device__ __forceinline__ void store_staged(uint8_t* dst, uint32_t stg) {
  fence_async_smem();
  __syncwarp();
  if (elect()) {
    bulk_store(dst, stg, 4096);
    bulk_commit();
  }
}

template <int J0, int J1>
__device__ __forceinline__ void fold_norm(float (&acc)[2][96], const float2 (&st)[4], const float4* vec) {
  float4 vn = vec[J0 * 4];
#pragma unroll
  for (int J = J0; J < J1; J++) {
    const float4 v = vn;
    if (J + 1 < J1) vn = vec[J * 4 + 4];
#pragma unroll
    for (int c = 0; c < 4; c++) {
      float& a0 = acc[c & 1][4 * J + (c & 2)];
      float& a1 = acc[c & 1][4 * J + (c & 2) + 1];
      a0 = fmaf(a0, st[c].x, fmaf(st[c].y, v.x, v.z));
      a1 = fmaf(a1, st[c].x, fmaf(st[c].y, v.y, v.w));
      asm volatile("" : "+f"(a0), "+f"(a1));
      if (c & 1) yield_slot();
    }
  }
}

template <int CH, class Acquire>
__device__ __forceinline__ void gelu_chunk(const float (&acc)[2][96], uint32_t stg, int lane, uint8_t* prev,
                                           Acquire acquire) {
  uint32_t pk[8][4];
  float z[3][4];
  const uint32_t row = (stg + lane * 128) ^ ((lane & 7) << 4);
#define U(s, e) acc[(e) >> 1][4 * (CH * 8 + ((s) >> 1)) + 2 * ((s) & 1) + ((e) & 1)]
#pragma unroll
  for (int s = 0; s < 18; s++) {
    const int cur = s % 3, p1 = (s + 2) % 3, p2 = (s + 1) % 3, q = s - 2, jj = 2 * q - 24;
    const bool mid = s >= 1 && s < 17;
    if (mid) z[p1][0] = tanh_fast(z[p1][0]);
    if (s < 16) {
#pragma unroll
      for (int e = 0; e < 4; e++) {
        z[cur][e] = fmaf(U(s, e), U(s, e), kGeluK);
        asm volatile("" : "+f"(z[cur][e]));
      }
    }
    if (jj >= 0) stsm4(row ^ (jj << 4), pk[jj][0], pk[jj][1], pk[jj][2], pk[jj][3]);
    yield_slot();
    if (mid) z[p1][1] = tanh_fast(z[p1][1]);
    if (q >= 0) {
      pk[q >> 1][2 * (q & 1)] = pack2(fmaf(U(q, 0), z[p2][0], U(q, 0)), fmaf(U(q, 1), z[p2][1], U(q, 1)));
      pk[q >> 1][2 * (q & 1) + 1] = pack2(fmaf(U(q, 2), z[p2][2], U(q, 2)), fmaf(U(q, 3), z[p2][3], U(q, 3)));
    }
    if (mid) z[p1][2] = tanh_fast(z[p1][2]);
    if (s < 16) {
#pragma unroll
      for (int e = 0; e < 4; e++) {
        z[cur][e] = z[cur][e] * U(s, e) * 8.f;
        asm volatile("" : "+f"(z[cur][e]));
      }
    }
    if (mid) z[p1][3] = tanh_fast(z[p1][3]);
    if (jj >= 0) stsm4(row ^ ((jj + 1) << 4), pk[jj + 1][0], pk[jj + 1][1], pk[jj + 1][2], pk[jj + 1][3]);
    yield_slot();
    if (CH == 1 && s == 1) store_staged(prev, stg);
    if (q == 11) acquire();
  }
#undef U
}

__device__ __forceinline__ void scale_stats(float2 (&st)[4]) {
#pragma unroll
  for (int c = 0; c < 4; c++) {
    st[c].x *= kGeluBeta;
    st[c].y *= st[c].x;
  }
}

__device__ __forceinline__ void add_mean_term(float (&acc)[2][96], const float2 (&st)[4], uint8_t* sm, int tq,
                                              int lane) {
  const float2* cs = reinterpret_cast<const float2*>(sm + kSmCsQ) + tq * 96 + (lane & 3);
  float2 vn = cs[0];
#pragma unroll
  for (int J = 0; J < 24; J++) {
    const float2 v = vn;
    if (J < 23) vn = cs[J * 4 + 4];
#pragma unroll
    for (int c = 0; c < 4; c++) {
      acc[c & 1][4 * J + (c & 2)] = fmaf(st[c].y, v.x, acc[c & 1][4 * J + (c & 2)]);
      acc[c & 1][4 * J + (c & 2) + 1] = fmaf(st[c].y, v.y, acc[c & 1][4 * J + (c & 2) + 1]);
    }
    yield_slot();
  }
}

struct AttnRegs {
  uint32_t q[4][8], k[5][8], vt[5][8];
};
#define SCALED(c, J) pack2(acc[(c) & 1][4 * (J) + ((c) & 2)] * st[c].x, acc[(c) & 1][4 * (J) + ((c) & 2) + 1] * st[c].x)
__device__ __forceinline__ void convert_group(const float (&acc)[2][96], const float2 (&st)[4], AttnRegs& r, int c,
                                              int part) {
#pragma unroll
  for (int J = 0; J < 8; J++) {
    if (part == 0) r.q[c][J] = SCALED(c, J);
    if (part == 1) r.k[c + 1][J] = SCALED(c, 8 + J);
    if (part == 2) r.vt[c + 1][J] = transpose8(SCALED(c, 16 + J));
    if (J & 1) yield_slot();
  }
}
#undef SCALED

__device__ __forceinline__ void convert_odd(const float (&acc)[2][96], const float2 (&st)[4], AttnRegs& r, int step,
                                            uint8_t* sm, uint32_t halo_bar, uint4* halo_out, bool send,
                                            unsigned epoch, int w, int lane) {
  if (step == 1) {
    convert_group(acc, st, r, 3, 2);
    convert_group(acc, st, r, 3, 1);
    if (w < 3) {
      uint2* hs = reinterpret_cast<uint2*>(sm + kSmHalo + w * 2048) + lane;
#pragma unroll
      for (int i = 0; i < 4; i++) {
        hs[i * 32] = make_uint2(r.k[4][2 * i], r.k[4][2 * i + 1]);
        hs[128 + i * 32] = make_uint2(r.vt[4][2 * i], r.vt[4][2 * i + 1]);
      }
      __syncwarp();
      if (elect()) mbar_arrive(halo_bar + w * 8);
    } else if (send) {
#pragma unroll
      for (int i = 0; i < 4; i++) {
        st_packet(halo_out + lane + i * 32, r.k[4][2 * i], r.k[4][2 * i + 1], epoch);
        st_packet(halo_out + lane + 128 + i * 32, r.vt[4][2 * i], r.vt[4][2 * i + 1], epoch);
      }
    }
  } else if (step == 2) {
    convert_group(acc, st, r, 1, 2);
  } else {
    convert_group(acc, st, r, 1, 1);
    convert_group(acc, st, r, 3, 0);
    convert_group(acc, st, r, 1, 0);
  }
}

__device__ __forceinline__ void epilogue_attn(const float (&acc)[2][96], const float2 (&st)[4], AttnRegs& r,
                                              uint8_t* sm, uint32_t sb, int layer, int tq, int b, int j,
                                              unsigned epoch, int tile, int w, int lane) {
  const int t = lane & 3, g = lane >> 2;
  const int hp = j + 8 * tq, att = 2 * layer + tq;
  auto& q = r.q;
  auto& k = r.k;
  auto& vt = r.vt;
  const bool first = w == 0 && (b & 7) == 0;
  const uint4* gh = g_halo + ((layer * 16 + b - 1) * 16 + hp) * 256 + lane;
  uint32_t tag[8];
#define LOAD_HALO()                                                                                    \
  _Pragma("unroll") for (int i = 0; i < 4; i++) {                                                      \
    ld_packet(gh + i * 32, k[0][2 * i], k[0][2 * i + 1], tag[i]);                                      \
    ld_packet(gh + 128 + i * 32, vt[0][2 * i], vt[0][2 * i + 1], tag[4 + i]);                          \
  }
#pragma unroll
  for (int c = 0; c < 6; c++) {
    if (c == 2) {
#pragma unroll
      for (int i = 0; i < 8; i++) k[0][i] = vt[0][i] = tag[i] = 0u;
      if (w > 0) {
        mbar_wait(sb + kBarHalo + (att * 3 + w - 1) * 8, 0);
        const uint2* hs = reinterpret_cast<const uint2*>(sm + kSmHalo + (w - 1) * 2048) + lane;
#pragma unroll
        for (int i = 0; i < 4; i++) {
          const uint2 a = hs[i * 32], d = hs[128 + i * 32];
          k[0][2 * i] = a.x; k[0][2 * i + 1] = a.y;
          vt[0][2 * i] = d.x; vt[0][2 * i + 1] = d.y;
        }
      } else if (!first) {
        LOAD_HALO();
      }
    }
    convert_group(acc, st, r, 2 * (c & 1), 2 - (c >> 1));
  }
  TRACE_AT(tile, 8);
  if (w == 0 && !first) {
#pragma unroll 1
    while (__any_sync(0xffffffffu, ((tag[0] ^ epoch) | (tag[1] ^ epoch) | (tag[2] ^ epoch) | (tag[3] ^ epoch)) |
                                       ((tag[4] ^ epoch) | (tag[5] ^ epoch) | (tag[6] ^ epoch) | (tag[7] ^ epoch)))) {
      LOAD_HALO();
    }
  }
  constexpr float kScale = 0.17677669529663687f * 1.4426950408889634f;
  const bool own0 = 2 * t <= g, own1 = 2 * t + 1 <= g;
  const uint32_t own_mask = (own0 ? 0xffffu : 0u) | (own1 ? 0xffff0000u : 0u);
  const uint32_t stg = sb + kSmStg + w * 4096;
  const uint32_t orow = stg + (lane & 7) * 128, ochunk = (lane >> 3) ^ (lane & 7);
  TRACE_AT(tile, 9);
  mbar_wait(sb + kBarPause + att * 8, 0);
  TRACE_AT(tile, 10);

  float s[2][6][4], o[2][4][2][4];
#pragma unroll
  for (int n = 0; n < 24; n++) {
    const int ks = n / 12, hd = (n % 12) / 6, m = n % 6, ca = 2 * (m / 3), kg = ca + m % 3, J = 4 * hd + 2 * ks;
    if (ks == 0) s[hd][m][0] = s[hd][m][1] = s[hd][m][2] = s[hd][m][3] = 0.f;
    mma16816(s[hd][m], q[ca][J], q[ca + 1][J], q[ca][J + 1], q[ca + 1][J + 1], k[kg][J], k[kg][J + 1]);
  }
  float v0[2][4], v1[2][4], m[2][4];
  uint32_t pp[2][4], po[2][4];
#define UNITS _Pragma("unroll") for (int hd = 0; hd < 2; hd++) _Pragma("unroll") for (int c = 0; c < 4; c++)
  UNITS {
    const int mp = 3 * (c >> 1) + (c & 1), r = 2 * (c & 1);
    float p0 = s[hd][mp][r], p1 = s[hd][mp][r + 1];
    if (c == 0 && first) p0 = p1 = -INFINITY;
    v0[hd][c] = own0 ? s[hd][mp + 1][r] : p0;
    v1[hd][c] = own1 ? s[hd][mp + 1][r + 1] : p1;
    m[hd][c] = fmaxf(v0[hd][c], v1[hd][c]);
  }
  UNITS m[hd][c] = fmaxf(m[hd][c], shfl_xor(m[hd][c], 1));
  UNITS m[hd][c] = fmaxf(m[hd][c], shfl_xor(m[hd][c], 2));
  UNITS {
    const float nm = -m[hd][c] * kScale;
    v0[hd][c] = ex2(fmaf(v0[hd][c], kScale, nm));
    v1[hd][c] = ex2(fmaf(v1[hd][c], kScale, nm));
    m[hd][c] = v0[hd][c] + v1[hd][c];
  }
  UNITS m[hd][c] += shfl_xor(m[hd][c], 1);
  UNITS m[hd][c] += shfl_xor(m[hd][c], 2);
  UNITS {
    const float inv = rcp(m[hd][c]);
    const uint32_t p = pack2(v0[hd][c] * inv, v1[hd][c] * inv);
    pp[hd][c] = p & ~own_mask;
    po[hd][c] = p & own_mask;
    asm volatile("" : "+r"(pp[hd][c]), "+r"(po[hd][c]));
  }
#pragma unroll
  for (int n = 0; n < 24; n++) {
    const int ph = n / 8, hd = (n >> 2) & 1, c = 2 * ((n >> 1) & 1) + (ph == 1), ds = n & 1, J = 4 * hd + 2 * ds;
    float(&d)[4] = o[hd][c][ds];
    if (ph < 2) d[0] = d[1] = d[2] = d[3] = 0.f;
    if (ph == 0) mma1688(d, vt[c + 1][J], vt[c + 1][J + 1], po[hd][c]);
    if (ph == 1) mma16816(d, vt[c][J], vt[c][J + 1], vt[c + 1][J], vt[c + 1][J + 1], pp[hd][c], po[hd][c]);
    if (ph == 2) mma1688(d, vt[c][J], vt[c][J + 1], pp[hd][c]);
    if (n == 3) {
      yield_slot();
      if (tq == 0 && lane == 0) mbar_arrive(sb + kBarResume + att * 8);
    }
  }
  yield_slot();
  if (tq == 1 && lane == 0) mbar_arrive(sb + kBarResume + att * 8);
  TRACE_AT(tile, 11);
  UNITS stsm4_t(orow + c * 1024 + ((ochunk ^ (4 * hd)) << 4), pack2(o[hd][c][0][0], o[hd][c][0][1]),
                pack2(o[hd][c][0][2], o[hd][c][0][3]), pack2(o[hd][c][1][0], o[hd][c][1][1]),
                pack2(o[hd][c][1][2], o[hd][c][1][3]));
#undef UNITS
#undef LOAD_HALO
  fence_async_smem();
  __syncwarp();
  TRACE_AT(tile, 12);
  if (elect()) {
    bulk_store(g_o + (b * 16 + hp) * kTileBytes + w * 4096, stg, 4096);
    bulk_commit();
    bulk_wait();
    TRACE_AT(tile, 13);
    mbar_arrive(sb + kBarEpi + tile * 8);
  }
  __syncwarp();
}

__device__ __forceinline__ void gather_stats(uint8_t* sm, const uint2* stat, int r, float eps, unsigned epoch) {
  uint2 a[8];
  unsigned diff;
#pragma unroll 1
  do {
    __nanosleep(800);
    diff = 0;
#pragma unroll
    for (int i = 0; i < 8; i++) {
      a[i] = ld_relaxed64(stat + i * 128 + r);
      diff |= a[i].x ^ epoch;
    }
  } while (__any_sync(0xffffffffu, diff & 7u));
  float s = 0.f, q = 0.f;
#pragma unroll
  for (int i = 0; i < 8; i++) {
    s += untag_value(a[i].x);
    q += __uint_as_float(a[i].y);
  }
  const float mean = s * (1.f / 1024.f);
  const float var = fmaxf(fmaf(-mean, mean, q * (1.f / 1024.f)), 0.f);
  reinterpret_cast<float2*>(sm + kSmStat)[r] = make_float2(rsqrtf(var + eps), -mean);
}

__device__ __forceinline__ void gather_colsums_qkv(uint8_t* sm, int tq, int j, int lane, unsigned epoch) {
  const uint2* src = reinterpret_cast<const uint2*>(g_cs + (j + 8 * tq) * 64) + lane;
  uint2 v[3], u[3];
  unsigned diff, spins = 0;
#pragma unroll 1
  do {
    if (++spins > kSpinLimit) __trap();
    diff = 0;
#pragma unroll
    for (int q = 0; q < 3; q++) {
      v[q] = ld_relaxed_pair(src + q * (kD / 2));
      u[q] = make_uint2(epoch & 7u, epoch & 7u);
      if (tq) u[q] = ld_relaxed_pair(src + (q * kD + 3 * kD + kF) / 2);
    }
#pragma unroll
    for (int q = 0; q < 3; q++) diff |= (v[q].x ^ epoch) | (v[q].y ^ epoch) | (u[q].x ^ epoch) | (u[q].y ^ epoch);
  } while (__any_sync(0xffffffffu, diff & 7u));
#pragma unroll
  for (int q = 0; q < 3; q++)
    reinterpret_cast<float2*>(sm + kSmCsQ)[tq * 96 + q * 32 + lane] =
        make_float2(untag_value(v[q].x) + untag_value(u[q].x), untag_value(v[q].y) + untag_value(u[q].y));
}

__device__ __forceinline__ void gather_colsums_w1(uint8_t* sm, const __nv_bfloat16* b1, int j, int lane,
                                                  unsigned epoch) {
#pragma unroll 1
  for (int blk = 0; blk < 7; blk++) {
    const int pair = 32 * (blk + (blk < 3 ? 3 * j : blk < 5 ? 21 + 2 * j : 35 + 2 * j)) + lane;
    const uint32_t bias = reinterpret_cast<const uint32_t*>(b1)[pair];
    uint2 v;
    unsigned spins = 0;
#pragma unroll 1
    do {
      if (++spins > kSpinLimit) __trap();
      v = ld_relaxed_pair(reinterpret_cast<const uint2*>(g_cs + 3 * kD) + pair);
    } while (__any_sync(0xffffffffu, ((v.x ^ epoch) | (v.y ^ epoch)) & 7u));
    reinterpret_cast<float4*>(sm + kSmV1)[blk * 32 + lane] =
        make_float4(untag_value(v.x), untag_value(v.y), kGeluBeta * bf_lo(bias), kGeluBeta * bf_hi(bias));
  }
}

constexpr int kPauseQkv = 7, kPauseWo = 2;

__global__ void __cluster_dims__(2, 1, 1) __launch_bounds__(384, 1)
fused_layers_kernel(const __grid_constant__ CUtensorMap map_x, const __grid_constant__ CUtensorMap map_out,
                    const __grid_constant__ CUtensorMap map_qkv, const __grid_constant__ CUtensorMap map_wo,
                    const __grid_constant__ CUtensorMap map_w1a, const __grid_constant__ CUtensorMap map_w1b,
                    const __grid_constant__ CUtensorMap map_w2, const __grid_constant__ CUtensorMap map_csq,
                    const __grid_constant__ CUtensorMap map_cs1, const __grid_constant__ CUtensorMap map_css,
                    const __grid_constant__ Params prm) {
  extern __shared__ __align__(1024) uint8_t sm[];
  if (threadIdx.x < 128 && blockIdx.x < kCtas) TRACE_AT(15, 1);
  const uint32_t sb = __shfl_sync(0xffffffffu, smem_u32(sm), 0);
  const int warp = __shfl_sync(0xffffffffu, threadIdx.x >> 5, 0), lane = threadIdx.x & 31;
  const int cta = blockIdx.x, rank = cta & 1, cl = cta >> 1, q7 = ((cl - 36) * 37) >> 8;
  const int grp = cl < 36 ? (cl < 4 ? 0 : (cl - 4) & 7) : cl - 35 - 7 * q7;
  const int j = cl < 36 ? (cl < 4 ? 4 + cl : (cl - 4) >> 3) : 4 + q7;
  const int b = 2 * grp + rank;
  const int xcol = (b >> 3) * kD, xrow = (b & 7) * 128;

  if (cta >= kCtas) {
    helper_cta(&map_csq, &map_cs1, sm, sb, cta - kCtas, warp);
    return;
  }
  auto first_loads = [&](int s0) {
#pragma unroll 1
    for (int s = s0; s < s0 + 2; s++) {
      const uint32_t full = sb + kBarFull + s * 8, dst = sb + kSmRing + s * 40960;
      mbar_expect_tx(full, 40960);
      tma2d(dst, &map_x, full, xcol + (s & 1) * 64, xrow);
      tma3d(dst + kTileBytes, &map_qkv, full, (j + 4 * s0) * 64, (s & 1) * 64, 0);
      tma3d(dst + kTileBytes + 12288, &map_qkv, full, (j + 4 * s0) * 64, (s & 1) * 64 + 32, 0);
    }
  };
  if ((warp < 8 || warp == 9) && elect()) {
    if (warp == 9) {
#pragma unroll
      for (int s = 0; s < 8; s++) mbar_init(sb + kBarFull + s * 8, 1);
      fence_async_smem();
      first_loads(0);
    } else {
      if (sb & 1023) __trap();
#pragma unroll
      for (int s = 0; s < 16; s++) mbar_init(sb + kBarTurn + warp * 128 + s * 8, warp < 5 ? 1 : warp == 5 ? 2 : 4);
    }
    asm volatile("fence.mbarrier_init.release.cluster;" ::: "memory");
  }
  __syncwarp();
  asm volatile("barrier.cluster.arrive.relaxed.aligned;" ::: "memory");

  if (warp >= 8) {
    asm volatile("setmaxnreg.dec.sync.aligned.u32 40;");
    if (warp < 10) {
      if (warp == 9 && elect()) first_loads(2);
      __syncwarp();
      asm volatile("barrier.cluster.wait.aligned;" ::: "memory");
      uint32_t nb = 32, off = 0, kb = 0;
#define RING_STEP(WAIT, ISSUE)                                            \
  do {                                                                    \
    const uint32_t mb = nb - depth, full = sb + kBarFull + (nb & 56);     \
    if (kb == skip) kb += inc;                                            \
    mbar_wait(sb + kBarEmpty + (mb & 56), mb >> 6);                       \
    WAIT;                                                                 \
    if (elect()) { ISSUE; }                                               \
    TRACE_ISSUE(9 - warp, nb);                                            \
    kb += inc;                                                            \
    off = off == wrap ? 0 : off + step;                                   \
    nb += 8;                                                              \
  } while (nb != nend)
#pragma unroll 1
      for (int sg = 0; sg < kSegs; sg++) {
        const uint32_t e = prm.seg[sg];
        const int ty = e & 7, mode = (e >> 15) & 3, reset = (e >> 24) & 3;
        const uint32_t nend = nb + (e & 0x1f8);
        const uint32_t step = (e >> 17) & 1 ? 40960 : 32768, wrap = 163840 - step;
        const uint32_t depth = (e >> 18) & 1 ? 40 : 32;
        if (reset) off = reset == 1 ? 0 : reset == 2 ? 40960 : 131072;
        const uint32_t own = ty == 2 ? 8 + j : 2 * j;
        if (mode != kModeContinue) kb = ((e >> 9) & 63) + (mode == kModeHead ? own : 0);
        const uint32_t inc = mode >= kModeSkip && ty != 2 ? 2 : 1, skip = mode >= kModeSkip ? own + (kb & 1) : 255;
        if (warp == 8) {
          const CUtensorMap* map = ty < 2 ? &map_qkv : ty == 2 ? &map_wo : ty == 3 ? &map_w1a : ty < 6 ? &map_w1b : &map_w2;
          const int c0 = ty < 2 ? (j + 8 * ty) * 64 : 0;
          const int c2 = ty < 2 ? 0 : ty == 3 ? 3 * j : ty == 4 ? 24 + 2 * j : ty == 5 ? 40 + 2 * j : 2 * j;
          const uint32_t half = (ty < 2 || ty == 3) ? 12288 : 8192;
          const uint32_t bytes = 2 * half + (mode == kModeHead ? 0 : kTileBytes);
          const uint32_t dst = sb + kSmRing + (mode == kModeHead && ty != 2 ? 0 : kTileBytes) + rank * half;
          if (e >> 26) {
            const bool second = (grp & 6) == 2;
            const int pk = grp < 4 ? 2 * j + (grp & 1) : 2 * (grp - 4 + (grp - 4 >= j));
            const CUtensorMap* pm = ty == 6 ? &map_qkv : second ? &map_w1b : &map_w1a;
            if (elect())
              asm volatile("cp.async.bulk.prefetch.tensor.3d.L2.global [%0, {%1, %2, %3}];" ::"l"(pm),
                           "r"(ty == 6 ? (j + 8 * second) * 64 : 0), "r"(pk * 64 + rank * 32),
                           "r"(ty == 6 ? 0 : second ? 24 + 2 * j : 3 * j) : "memory");
          }
          if (ty == 2 && mode == kModeHead) mbar_wait(sb + kBarEpi + ((e >> 19) & 31) * 8, 0);
#pragma unroll 1
          RING_STEP(, mbar_expect_tx(full, bytes); tma3d_mc(dst + off, map, full, c0, kb * 64 + rank * 32, c2));
        } else if (mode == kModeHead) {
          off += ((nend - nb) >> 3) * step;
          nb = nend;
          if (off >= 163840) off -= 163840;
        } else if (sg < 2) {
#pragma unroll 1
          RING_STEP(, tma2d(sb + kSmRing + off, &map_x, full, xcol + kb * 64, xrow));
        } else {
          const uint8_t* src = ty == 6 ? g_h + b * 56 * kTileBytes : (ty == 2 ? g_o : g_x) + b * 16 * kTileBytes;
          const int dep = (e >> 19) & 31;
          if (dep < 28) mbar_wait(sb + kBarReady + dep * 8, 0);
          if ((dep & 30) == 28) {
#pragma unroll 1
            RING_STEP(mbar_wait(sb + kBarSrc + ((kb << (4 - inc)) & 56), dep),
                      bulk_load(sb + kSmRing + off, src + kb * kTileBytes, kTileBytes, full));
          } else {
#pragma unroll 1
            RING_STEP(, bulk_load(sb + kSmRing + off, src + kb * kTileBytes, kTileBytes, full));
          }
        }
      }
#undef RING_STEP
    } else {
      unsigned epoch = 0;
      if (warp == 10) {
        if (lane == 0) epoch = atomicAdd(&g_ticket, 1u) / kGrid + 1;
        *reinterpret_cast<unsigned*>(sm + kSmEpoch) = __shfl_sync(0xffffffffu, epoch, 0);
        asm volatile("barrier.cluster.wait.aligned;" ::: "memory");
        if (elect()) mbar_arrive(sb + kBarEpoch);
      } else {
        asm volatile("barrier.cluster.wait.aligned;" ::: "memory");
        mbar_wait_bounded(sb + kBarFull, 0);
        if (elect()) {
          mbar_expect_tx(sb + kBarInit, 32768);
          tma2d(sb + kSmX, &map_x, sb + kBarInit, xcol + j * 128, xrow);
          tma2d(sb + kSmX + kTileBytes, &map_x, sb + kBarInit, xcol + j * 128 + 64, xrow);
        }
        const uint2 u = reinterpret_cast<const uint2*>(prm.b2)[32 * j + lane];
        reinterpret_cast<float4*>(sm + kSmB2)[lane] = make_float4(
            kHScale * bf_lo(u.x), kHScale * bf_hi(u.x), kHScale * bf_lo(u.y), kHScale * bf_hi(u.y));
      }
      mbar_wait_bounded(sb + kBarEpoch, 0);
      epoch = *reinterpret_cast<volatile unsigned*>(sm + kSmEpoch);
      if (cta < 96) {
        mbar_wait_bounded(sb + kBarInit, 0);
        colsum_strip(&map_css, sm, sb, (cta >> 5) * kD + 512 + (cta & 31) * 16, warp - 10, lane, epoch);
      }
      gather_colsums_qkv(sm, 11 - warp, j, lane, epoch);
      __syncwarp();
      if (elect()) mbar_arrive(sb + kBarCs + (11 - warp) * 8);
      if (warp == 10) {
        const unsigned* flag = g_flag + b * 32 + (lane & 7);
        unsigned count = epoch * 32;
#pragma unroll 1
        for (int i = 0; i < kTiles - 1; i++) {
          const bool xt = i == 2 || i == 6 || i == 9;
          count++;
          mbar_wait(sb + (xt ? kBarX + (i >> 2) * 16 : kBarEpi + i * 8), 0);
          if (xt || i == 1 || i == 8) {
            unsigned todo = 0xff;
            do {
              const unsigned now = __ballot_sync(0xffffffffu, (int)(ld_relaxed(flag) - count) >= 0) & todo;
              if (now) {
                asm volatile("fence.acquire.gpu;\nfence.proxy.async.global;" ::: "memory");
                if ((now >> lane) & 1) mbar_arrive(sb + kBarSrc + lane * 8);
                todo ^= now;
              }
              if (todo == 0xff) __nanosleep(300);
            } while (todo);
          } else {
            wait_flags(flag, count);
            if (elect()) mbar_arrive(sb + kBarReady + i * 8);
          }
          if (xt) {
            wait_flags(flag, ++count);
            if (elect()) mbar_arrive(sb + kBarReady + (14 + (i >> 2)) * 8);
          }
        }
      } else {
        unsigned count = epoch * 32;
#pragma unroll 1
        for (int i = 0; i < kTiles - 1; i++) {
          if (i == 3) {
            gather_colsums_w1(sm, prm.b1, j, lane, epoch);
            __syncwarp();
            if (elect()) mbar_arrive(sb + kBarCs + 16);
          }
          const bool xt = i == 2 || i == 6 || i == 9;
#pragma unroll 1
          for (int h = 0; h < (xt ? 2 : 1); h++) {
            if (xt && h == 0) {
              mbar_wait_bounded(sb + kBarEpi + i * 8, 0);
              if (elect()) bulk_store(g_x + (b * 16 + 2 * j) * kTileBytes, sb + kSmX, kTileBytes / 2);
            }
            mbar_wait_bounded(sb + (xt ? kBarX + (i >> 2) * 16 + 8 * h : kBarEpi + i * 8), 0);
            const int ty = i >= 7 ? i - 7 : i;
            if (ty >= 2 && elect()) {
              uint8_t* dst = xt ? g_x + (b * 16 + 2 * j + h) * kTileBytes
                                : g_h + (b * 56 + 1 + (ty == 3 ? 3 * j : 16 * ty - 40 + 2 * j)) * kTileBytes;
              const int piece = (xt && h == 0) ? kTileBytes / 2 : kTileBytes / 8;
#pragma unroll 1
              for (int o = xt && h == 0 ? piece : 0; o < kTileBytes; o += piece) {
                bulk_store(dst + o, sb + (xt ? kSmX + h * kTileBytes : kSmStg) + o, piece);
                bulk_commit();
                bulk_wait();
              }
              if (!xt) mbar_arrive(sb + kBarFree + i * 8);
            }
            __syncwarp();
            count++;
            if (elect()) st_release(&g_flag[b * 32 + j], count);
            __syncwarp();
          }
        }
#pragma unroll 1
        for (int q = 0; q < 4; q++) {
          mbar_wait_bounded(sb + (q & 1 ? kBarX + 48 : kBarEpi + (kTiles - 1) * 8) + 4 * (q & 2), 0);
          if (elect()) {
            tma2d_store(&map_out, sb + kSmX + q * 8192, xcol + j * 128 + (q >> 1) * 64, xrow + (q & 1) * 64);
            bulk_commit();
            if (q == 3) bulk_wait_read();
          }
        }
      }
    }
    __syncwarp();
    asm volatile("barrier.cluster.arrive.relaxed.aligned;\nbarrier.cluster.wait.aligned;" ::: "memory");
  } else {
    asm volatile("setmaxnreg.inc.sync.aligned.u32 232;");
    asm volatile("barrier.cluster.wait.aligned;" ::: "memory");
    const int wg = warp >> 2, w = warp & 3;
    const bool rel = (threadIdx.x & 95) == 0;
    const uint32_t rel_addr = mapa(sb + kBarEmpty, w & 1);
    if (wg == 1) TRACE_AT(15, 0);
#define EPOCH (*reinterpret_cast<volatile unsigned*>(sm + kSmEpoch))

#pragma unroll 1
    for (int i = wg; i < kTiles; i += 2) {
      const int layer = i >= 7, ty = i - 7 * layer;
      TRACE_AT(i, 15);
      float acc[2][96];
      if (ty == 2 || ty == 6) {
        const int lane = lane_id();
        const uint32_t xa = sb + kSmX + ((lane >> 4) * 8 + (lane & 7)) * 128 + (((2 * w + ((lane >> 3) & 1)) ^ (lane & 7)) << 4);
        const float up = ty == 6 ? kHScale / kXScale : layer ? 1.f / kXScale : 1.f;
        const float dn = ty == 2 ? kXScale : layer ? 1.f / kHScale : kXScale / kHScale;
#pragma unroll
        for (int h = 0; h < 2; h++) {
          const float* b2 = reinterpret_cast<const float*>(sm + kSmB2) + 64 * h + 16 * w + (lane >> 2);
          const float bias[2] = {ty == 6 ? b2[0] : 0.f, ty == 6 ? b2[8] : 0.f};
#pragma unroll
          for (int p = 0; p < 8; p++) {
            uint32_t r[4];
            ldsm4_t(xa + h * kTileBytes + p * 2048, r);
#pragma unroll
            for (int m = 0; m < 4; m++) {
              acc[h][8 * p + 2 * m] = fmaf(bf_lo(r[m]), up, bias[m & 1]);
              acc[h][8 * p + 2 * m + 1] = fmaf(bf_hi(r[m]), up, bias[m & 1]);
              asm volatile("" : "+f"(acc[h][8 * p + 2 * m]), "+f"(acc[h][8 * p + 2 * m + 1]));
            }
            yield_slot();
          }
        }
        auto stage = [&](int qt) {
          const int h = qt >> 1;
          if (qt == 1 || (qt == 3 && i == kTiles - 1)) {
            fence_async_smem();
            __syncwarp();
            if (lane == 0) mbar_arrive(sb + kBarEpi + (i + h) * 8);
          }
#pragma unroll
          for (int p = 4 * (qt & 1); p < 4 * (qt & 1) + 4; p++) {
            const float* a = &acc[h][8 * p];
            stsm4_t(xa + h * kTileBytes + p * 2048, pack2(a[0] * dn, a[1] * dn), pack2(a[2] * dn, a[3] * dn),
                    pack2(a[4] * dn, a[5] * dn), pack2(a[6] * dn, a[7] * dn));
            yield_slot();
          }
          if (qt & 1) {
            fence_async_smem();
            __syncwarp();
            if (elect()) mbar_arrive(sb + kBarX + (i >> 2) * 16 + 8 * h);
            TRACE_AT(i, 8 + h);
          }
        };
        mainloop<128, kResid>(acc, sb, i, layer * 152 + ty * 16, ty == 6 ? 4 : 0, ty == 6 ? 56 : 16,
                              ty == 2 ? kPauseWo : -1, 2 * layer + 1, rel_addr, rel, ty == 2 ? 8 : -1, stage);
        TRACE_AT(i, 2);
        stage(2);
        stage(3);
      } else {
        const int xver = 2 * layer + (ty >= 3);
        const uint32_t stg = sb + kSmStg + w * 4096;
        const float4* vec = reinterpret_cast<const float4*>(sm + kSmV1) + (ty == 3 ? 0 : 64 * ty - 160);
        int lane;
        uint8_t* hdst = g_h + (b * 56 + (ty == 3 ? 3 * j : 16 * ty - 40 + 2 * j)) * kTileBytes + w * 4096;
        float2 st[4];
        unsigned epoch;
        auto pre = [&] {
          lane = lane_id();
          if (ty < 4) mbar_wait(sb + (ty == 1 ? kBarEpi + (i - 1) * 8 : kBarStat + xver * 8), 0);
#pragma unroll
          for (int c = 0; c < 4; c++) st[c] = reinterpret_cast<const float2*>(sm + kSmStat)[32 * w + 8 * c + (lane >> 2)];
          epoch = EPOCH;
        };
        auto team_stats = [&] {
          uint2* stat = g_stat + b * 1024;
          const unsigned tag = EPOCH * 4 + xver;
          lane = lane_id();
          publish_stats(sb, stat + j * 128, w, lane, tag);
          gather_stats(sm, stat, 32 * w + lane, xver ? 1e-5f * kXScale * kXScale : 1e-5f, tag);
          __syncwarp();
          if (elect()) mbar_arrive(sb + kBarStat + xver * 8);
          TRACE_AT(i, 14);
        };
        if (ty < 4) {
          AttnRegs ar;
          auto odd = [&](int step) {
            if (step == 0) pre();
            else convert_odd(acc, st, ar, step, sm, sb + kBarHalo + (xver + ty) * 24,
                             g_halo + ((layer * 16 + b) * 16 + j + 8 * ty) * 256, (b & 7) != 7, epoch, w, lane);
          };
          head_blocks<192>(acc, sb, layer * 152 + (ty < 2 ? 2 * ty : 48), ty < 2 ? 2 * ty : 1, xver, rel_addr, rel);
          if (ty == 1) {
            if (i == 1) {
              mbar_wait(sb + kBarEpoch, 0);
              mbar_wait(sb + kBarInit, 0);
            }
            team_stats();
            epoch = 0;
#pragma unroll
            for (int c = 0; c < 4; c++) st[c] = reinterpret_cast<const float2*>(sm + kSmStat)[32 * w + 8 * c + (lane >> 2)];
          } else {
            mainloop<192, kPlain>(acc, sb, i, layer * 152 + (ty ? 52 : 4), ty ? 1 : 0, 14, -1, 0, rel_addr, rel, 0, pre);
            TRACE_AT(i, 2);
            if (ty == 3) goto wide_gelu;
          }
          if (layer == 0) mbar_wait(sb + kBarCs + ty * 8, 0);
          add_mean_term(acc, st, sm, ty, lane);
          if (ty == 1) {
            mainloop<192, kStagger>(acc, sb, i, layer * 152 + 18, 2, 14, kPauseQkv, xver, rel_addr, rel, 0, odd);
            TRACE_AT(i, 2);
          } else {
            odd(1);
            odd(2);
            odd(3);
          }
          epilogue_attn(acc, st, ar, sm, sb, layer, ty, b, j, epoch, i, w, lane);
          TRACE_AT(i, 3);
          continue;
        wide_gelu:
          if (i == 3) mbar_wait(sb + kBarCs + 16, 0);
          scale_stats(st);
          fold_norm<16, 24>(acc, st, vec + (lane & 3));
          TRACE_AT(i, 11);
          gelu_chunk<2>(acc, stg, lane, nullptr, [] {});
          TRACE_AT(i, 12);
          fold_norm<0, 2>(acc, st, vec + (lane & 3));
          store_staged(hdst + 2 * kTileBytes, stg);
          fold_norm<2, 16>(acc, st, vec + (lane & 3));
        } else {
          if (ty == 4) {
            head_blocks<128>(acc, sb, layer * 152 + 50, 3, xver, rel_addr, rel);
            team_stats();
          } else {
            const uint32_t s0 = ((((sb & 0x3FFFF) + kSmRing) >> 4) | (1u << 16)) + 3 * 2048;
            mbar_wait(sb + kBarTurn + (i - 1) * 8, 0);
            mbar_wait(sb + kBarFull, layer * 19 + 10);
            TRACE_KB((layer * 152 + 80) * 8);
            mma_kblock<128, 2>(acc, s0, s0 + kToB);
          }
          mainloop<128, kPlain>(acc, sb, i, layer * 152 + 6 + 15 * ty, 4, ty + 10, -1, 0, rel_addr, rel, 0, pre,
                                ty == 5 ? 0 : 64);
          TRACE_AT(i, 2);
          if (i == 4) mbar_wait(sb + kBarCs + 16, 0);
          scale_stats(st);
          fold_norm<0, 16>(acc, st, vec + (lane & 3));
        }
        auto own_store_done = [] {
          if (elect()) bulk_wait();
          __syncwarp();
        };
        TRACE_AT(i, 8);
        gelu_chunk<0>(acc, stg, lane, nullptr, [&] {
          if (ty == 3) own_store_done();
          else mbar_wait(sb + kBarFree + (i - 1) * 8, 0);
        });
        TRACE_AT(i, 9);
        gelu_chunk<1>(acc, stg, lane, hdst, own_store_done);
        TRACE_AT(i, 10);
        fence_async_smem();
        __syncwarp();
        if (elect()) mbar_arrive(sb + kBarEpi + i * 8);
      }
      TRACE_AT(i, 3);
    }
#undef EPOCH
    asm volatile("barrier.cluster.arrive.relaxed.aligned;\nbarrier.cluster.wait.aligned;" ::: "memory");
    if (wg == 1) TRACE_AT(15, 2);
  }
}

void build_segments(uint32_t* seg) {
  int n = 0, fine = 0;
  auto per_source = [&] { return 28 + (fine++ & 1); };
  auto add = [&](int ty, int cnt, int kb0, int mode, int wide, int depth5, int dep, int reset) {
    seg[n++] = ty | cnt << 3 | kb0 << 9 | mode << 15 | wide << 17 | depth5 << 18 | dep << 19 | reset << 24;
  };
  for (int l = 0; l < 2; l++) {
    const int t = 7 * l;
    if (l == 0) {
      add(0, 14, 2, kModePlain, 1, 0, 31, 1);
      add(1, 14, 2, kModePlain, 1, 0, 31, 0);
    } else {
      add(0, 2, 0, kModeHead, 1, 1, 31, 1);
      add(1, 2, 0, kModeHead, 1, 0, 31, 0);
      add(0, 7, 0, kModeSkip, 1, 0, per_source(), 0);
      add(0, 7, 1, kModeSkip, 1, 0, 15, 0);
      add(1, 7, 0, kModeSkip, 1, 0, 31, 0);
      add(1, 7, 1, kModeSkip, 1, 0, 31, 0);
    }
    add(2, 4, 0, kModePlain, 0, 0, t, 1);
    add(2, 4, 4, kModePlain, 0, 1, 31, 4);
    add(2, 1, 0, kModeHead, 0, 1, t + 1, 0);
    add(2, 7, 8, kModeSkip, 0, 1, per_source(), 0);
    add(3, 1, 0, kModeHead, 1, 1, 31, 2);
    add(3, 1, 1, kModeHead, 1, 0, 31, 0);
    add(4, 2, 0, kModeHead, 1, 0, 31, 0);
    add(3, 7, 0, kModeSkip, 1, 0, per_source(), 0);
    add(3, 7, 1, kModeSkip, 1, 0, 14 + 2 * l, 0);
    add(4, 4, 0, kModeSkip, 0, 0, 31, 3);
    add(4, 3, 0, kModeContinue, 0, 1, 31, 0);
    add(4, 7, 1, kModeSkip, 0, 1, 31, 0);
    add(5, 16, 0, kModePlain, 0, 1, 31, 0);
    add(6, 24, 0, kModePlain, 0, 1, t + 3, 0);
    add(6, 16, 24, kModePlain, 0, 1, t + 4, 0);
    add(6, 16, 40, kModePlain, 0, 1, t + 5, l ? 0 : 4);
  }
}

typedef CUresult (*EncodeTiledFn)(CUtensorMap*, CUtensorMapDataType, cuuint32_t, void*, const cuuint64_t*,
                                  const cuuint64_t*, const cuuint32_t*, const cuuint32_t*, CUtensorMapInterleave,
                                  CUtensorMapSwizzle, CUtensorMapL2promotion, CUtensorMapFloatOOBfill);

CUtensorMap make_map(EncodeTiledFn enc, const void* p, int rank, const cuuint64_t* dims, const cuuint64_t* strides,
                     const cuuint32_t* box, CUtensorMapSwizzle swizzle = CU_TENSOR_MAP_SWIZZLE_128B,
                     CUtensorMapL2promotion promo = CU_TENSOR_MAP_L2_PROMOTION_L2_128B) {
  CUtensorMap m;
  const cuuint32_t es[5] = {1, 1, 1, 1, 1};
  enc(&m, CU_TENSOR_MAP_DATA_TYPE_BFLOAT16, rank, const_cast<void*>(p), dims, strides, box, es,
      CU_TENSOR_MAP_INTERLEAVE_NONE, swizzle, promo, CU_TENSOR_MAP_FLOAT_OOB_FILL_NONE);
  return m;
}

CUtensorMap weight_map(EncodeTiledFn enc, const void* p, int k, int n, int blocks) {
  const cuuint64_t dims[3] = {64, (cuuint64_t)k, (cuuint64_t)n / 64};
  const cuuint64_t strides[2] = {(cuuint64_t)n * 2, 128};
  const cuuint32_t box[3] = {64, 32, (cuuint32_t)blocks};
  return make_map(enc, p, 3, dims, strides, box, CU_TENSOR_MAP_SWIZZLE_128B, CU_TENSOR_MAP_L2_PROMOTION_L2_256B);
}

CUtensorMap slab_map(EncodeTiledFn enc, const void* p, int n, int cols, int rows) {
  const cuuint64_t dims[2] = {(cuuint64_t)n, kD};
  const cuuint64_t strides[1] = {(cuuint64_t)n * 2};
  const cuuint32_t box[2] = {(cuuint32_t)cols, (cuuint32_t)rows};
  return make_map(enc, p, 2, dims, strides, box, CU_TENSOR_MAP_SWIZZLE_NONE);
}

CUtensorMap token_map(EncodeTiledFn enc, const void* p, int rows) {
  const cuuint64_t dims[2] = {2 * kD, 1024};
  const cuuint64_t strides[1] = {4 * kD};
  const cuuint32_t box[2] = {64, (cuuint32_t)rows};
  return make_map(enc, p, 2, dims, strides, box);
}

}

extern "C" void kernel_launch(void* const* d_in, const int* in_sizes, int n_in, void* d_out, int out_size) {
  (void)in_sizes; (void)n_in; (void)out_size;
  static EncodeTiledFn enc = nullptr;
  if (!enc) {
    void* fn = nullptr;
    cudaDriverEntryPointQueryResult q;
    cudaGetDriverEntryPoint("cuTensorMapEncodeTiled", &fn, cudaEnableDefault, &q);
    enc = (EncodeTiledFn)fn;
    cudaFuncSetAttribute(fused_layers_kernel, cudaFuncAttributeMaxDynamicSharedMemorySize, kSmBytes);
  }
  Params prm;
  prm.b1 = (const __nv_bfloat16*)d_in[5];
  prm.b2 = (const __nv_bfloat16*)d_in[7];
  build_segments(prm.seg);
  const cuuint64_t qd[3] = {kD, kD, 3}, qs[2] = {3 * kD * 2, kD * 2};
  const cuuint32_t qb[3] = {64, 32, 3};
  const CUtensorMap map_x = token_map(enc, d_in[0], 128);
  const CUtensorMap map_out = token_map(enc, d_out, 64);
  const CUtensorMap map_qkv = make_map(enc, d_in[1], 3, qd, qs, qb);
  const CUtensorMap map_wo = weight_map(enc, d_in[2], kD, kD, 2);
  const CUtensorMap map_w1a = weight_map(enc, d_in[4], kD, kF, 3);
  const CUtensorMap map_w1b = weight_map(enc, d_in[4], kD, kF, 2);
  const CUtensorMap map_w2 = weight_map(enc, d_in[6], kF, kD, 2);
  fused_layers_kernel<<<kGrid, 384, kSmBytes>>>(map_x, map_out, map_qkv, map_wo, map_w1a, map_w1b, map_w2,
                                                slab_map(enc, d_in[1], 3 * kD, 128, 128), slab_map(enc, d_in[4], kF, 128, 128),
                                                slab_map(enc, d_in[1], 3 * kD, 16, 128), prm);
}
```

```cpp
#include <cuda.h>
#include <cuda_bf16.h>
#include <cuda_runtime.h>
#include <stdint.h>

namespace {

constexpr int kD = 1024;
constexpr int kF = 3584;
constexpr int kCtas = 128;
constexpr int kGrid = 132;
constexpr int kTiles = 14;
constexpr int kTileBytes = 16384;

constexpr int kSmRing = 0;
constexpr int kSmX = 163840;
constexpr int kSmStg = kSmX + 32768;
constexpr int kSmHalo = kSmStg + 16384;
constexpr int kSmCsQ = kSmHalo + 8192;
constexpr int kSmV1 = kSmCsQ + 384 * 4;
constexpr int kSmB2 = kSmV1 + 448 * 8;
constexpr int kSmStat = kSmB2 + 128 * 4;
constexpr int kSmBar = kSmStat + 128 * 8;
constexpr int kBarFull = kSmBar;
constexpr int kBarTurn = kBarFull + 8 * 8;
constexpr int kBarReady = kBarTurn + 14 * 8;
constexpr int kBarSrc = kBarReady + 17 * 8;
constexpr int kBarPause = kBarSrc + 8 * 8;
constexpr int kBarFree = kBarPause + 8;
constexpr int kBarCs = kBarFree + 13 * 8;
constexpr int kBarSlab = kBarCs + 3 * 8;
constexpr int kBarHalo = kBarSlab + 4 * 8;
constexpr int kBarInit = kBarHalo + 16 * 8;
constexpr int kBarEpoch = kBarInit + 8;
constexpr int kBarEmpty = kBarTurn + 5 * 128;
constexpr int kBarEpi = kBarEmpty + 128;
constexpr int kBarX = kBarEpi + 15 * 8;
constexpr int kBarStat = kBarX + 8 * 8;
constexpr int kBarResume = kBarStat + 4 * 8;
constexpr int kSmEpoch = kBarEpi + 2 * 128;
static_assert(kBarEpoch < kBarEmpty && kBarResume + 4 * 8 <= kSmEpoch, "barrier groups overflow");
constexpr int kSmBytes = kSmEpoch + 16 + 256;
constexpr int kSegs = 40;

constexpr float kXScale = 1.f / 8.f;

constexpr unsigned kSpinLimit = 1u << 22;

__device__ __align__(1024) uint8_t g_x[16 * 16 * kTileBytes];
__device__ __align__(1024) uint8_t g_o[16 * 16 * kTileBytes];
__device__ __align__(1024) uint8_t g_h[16 * 56 * kTileBytes];
__device__ __align__(128) uint2 g_stat[16 * 8 * 128];
__device__ __align__(128) unsigned g_cs[3 * kD + kF + 3 * kD];
__device__ __align__(128) uint4 g_halo[2 * 16 * 16 * 256];
__device__ __align__(128) unsigned g_flag[16 * 32];
__device__ unsigned g_ticket;

#define TRACE_AT(tile, k)
#define TRACE_PUB(i, k, c)
#define TRACE_ISSUE(which, nb)

struct Params {
  const __nv_bfloat16* b1;
  const __nv_bfloat16* b2;
  uint32_t seg[kSegs];
};

__device__ __forceinline__ uint32_t smem_u32(const void* p) {
  return (uint32_t)__cvta_generic_to_shared(p);
}
__device__ __forceinline__ uint32_t mapa(uint32_t a, uint32_t cta) {
  uint32_t r;
  asm("mapa.shared::cluster.u32 %0, %1, %2;" : "=r"(r) : "r"(a), "r"(cta));
  return r;
}
__device__ __forceinline__ void mbar_init(uint32_t bar, int cnt) {
  asm volatile("mbarrier.init.shared::cta.b64 [%0], %1;" ::"r"(bar), "r"(cnt) : "memory");
}
__device__ __forceinline__ void mbar_expect_tx(uint32_t bar, uint32_t bytes) {
  asm volatile("mbarrier.arrive.expect_tx.shared::cta.b64 _, [%0], %1;" ::"r"(bar), "r"(bytes) : "memory");
}
__device__ __forceinline__ void mbar_arrive(uint32_t bar) {
  asm volatile("mbarrier.arrive.shared::cta.b64 _, [%0];" ::"r"(bar) : "memory");
}
__device__ __forceinline__ void mbar_arrive_cluster(uint32_t cluster_addr) {
  asm volatile("mbarrier.arrive.shared::cluster.b64 _, [%0];" ::"r"(cluster_addr) : "memory");
}
__device__ __forceinline__ void mbar_wait(uint32_t bar, uint32_t parity) {
  asm volatile("{\n.reg .pred p;\nRETRY:\nmbarrier.try_wait.parity.shared::cta.b64 p, [%0], %1;\n"
               "@!p bra.uni RETRY;\n}" ::"r"(bar), "r"(parity) : "memory");
}
__device__ __forceinline__ void mbar_wait_bounded(uint32_t bar, uint32_t parity) {
  asm volatile("{\n.reg .pred p;\n.reg .u32 c;\nmov.u32 c, 0;\nRETRY:\n"
               "mbarrier.try_wait.parity.shared::cta.b64 p, [%0], %1;\n@p bra.uni DONE;\n"
               "add.u32 c, c, 1;\nsetp.lt.u32 p, c, %2;\n@p bra.uni RETRY;\ntrap;\nDONE:\n}"
               ::"r"(bar), "r"(parity), "n"(1u << 19) : "memory");
}
__device__ __forceinline__ void tma3d(uint32_t dst, const CUtensorMap* m, uint32_t bar, int c0, int c1, int c2) {
  asm volatile(
      "cp.async.bulk.tensor.3d.shared::cluster.global.mbarrier::complete_tx::bytes [%0], [%1, {%3, %4, %5}], [%2];"
      ::"r"(dst), "l"(m), "r"(bar), "r"(c0), "r"(c1), "r"(c2) : "memory");
}
__device__ __forceinline__ void tma3d_mc(uint32_t dst, const CUtensorMap* m, uint32_t bar, int c0, int c1, int c2) {
  asm volatile(
      "cp.async.bulk.tensor.3d.shared::cluster.global.mbarrier::complete_tx::bytes.multicast::cluster"
      " [%0], [%1, {%3, %4, %5}], [%2], %6;"
      ::"r"(dst), "l"(m), "r"(bar), "r"(c0), "r"(c1), "r"(c2), "h"((uint16_t)3) : "memory");
}
__device__ __forceinline__ void tma2d(uint32_t dst, const CUtensorMap* m, uint32_t bar, int c0, int c1) {
  asm volatile(
      "cp.async.bulk.tensor.2d.shared::cluster.global.mbarrier::complete_tx::bytes [%0], [%1, {%3, %4}], [%2];"
      ::"r"(dst), "l"(m), "r"(bar), "r"(c0), "r"(c1) : "memory");
}
__device__ __forceinline__ void tma2d_store(const CUtensorMap* m, uint32_t src, int c0, int c1) {
  asm volatile("cp.async.bulk.tensor.2d.global.shared::cta.bulk_group [%0, {%2, %3}], [%1];"
               ::"l"(m), "r"(src), "r"(c0), "r"(c1) : "memory");
}
__device__ __forceinline__ int lane_id() {
  int l;
  asm volatile("mov.u32 %0, %%laneid;" : "=r"(l));
  return l;
}
__device__ __forceinline__ bool elect() {
  uint32_t p;
  asm volatile("{\n.reg .pred p;\nelect.sync _|p, 0xffffffff;\nselp.b32 %0, 1, 0, p;\n}" : "=r"(p));
  return p;
}
__device__ __forceinline__ void bulk_load(uint32_t dst, const void* src, uint32_t bytes, uint32_t bar) {
  asm volatile("cp.async.bulk.shared::cluster.global.mbarrier::complete_tx::bytes [%0], [%1], %2, [%3];"
               ::"r"(dst), "l"(src), "r"(bytes), "r"(bar) : "memory");
}
__device__ __forceinline__ void bulk_store(void* dst, uint32_t src, uint32_t bytes) {
  asm volatile("cp.async.bulk.global.shared::cta.bulk_group [%0], [%1], %2;" ::"l"(dst), "r"(src), "r"(bytes)
               : "memory");
}
__device__ __forceinline__ void bulk_commit() { asm volatile("cp.async.bulk.commit_group;" ::: "memory"); }
__device__ __forceinline__ void bulk_wait_read() { asm volatile("cp.async.bulk.wait_group.read 0;" ::: "memory"); }
__device__ __forceinline__ void bulk_wait() { asm volatile("cp.async.bulk.wait_group 0;" ::: "memory"); }
__device__ __forceinline__ void fence_async_smem() { asm volatile("fence.proxy.async.shared::cta;" ::: "memory"); }
__device__ __forceinline__ unsigned ld_relaxed(const unsigned* p) {
  unsigned v;
  asm volatile("ld.relaxed.gpu.global.u32 %0, [%1];" : "=r"(v) : "l"(p) : "memory");
  return v;
}
__device__ __forceinline__ uint2 ld_relaxed64(const uint2* p) {
  uint2 v;
  asm volatile("{\n.reg .b64 t;\nld.relaxed.gpu.global.b64 t, [%2];\nmov.b64 {%0, %1}, t;\n}"
               : "=r"(v.x), "=r"(v.y) : "l"(p) : "memory");
  return v;
}
__device__ __forceinline__ void st_relaxed(unsigned* p, unsigned v) {
  asm volatile("st.relaxed.gpu.global.u32 [%0], %1;" ::"l"(p), "r"(v) : "memory");
}
__device__ __forceinline__ void st_release(unsigned* p, unsigned v) {
  asm volatile("st.release.gpu.global.u32 [%0], %1;" ::"l"(p), "r"(v) : "memory");
}
__device__ __forceinline__ void wait_flags(const unsigned* p, unsigned count) {
  while (__any_sync(0xffffffffu, (int)(ld_relaxed(p) - count) < 0)) {
    __nanosleep(400);
  }
  asm volatile("fence.acquire.gpu;\nfence.proxy.async.global;" ::: "memory");
  __syncwarp();
}
__device__ __forceinline__ void st_packet(uint4* p, uint32_t d0, uint32_t d1, uint32_t tag) {
  asm volatile("{\n.reg .b128 v;\n.reg .b64 x, y;\nmov.b64 x, {%1, %2};\nmov.b64 y, {%3, %3};\nmov.b128 v, {x, y};\n"
               "st.relaxed.gpu.global.b128 [%0], v;\n}" ::"l"(p), "r"(d0), "r"(d1), "r"(tag) : "memory");
}
__device__ __forceinline__ void ld_packet(const uint4* p, uint32_t& d0, uint32_t& d1, uint32_t& tag) {
  asm volatile("{\n.reg .b128 v;\n.reg .b64 x, y;\n.reg .b32 u;\nld.relaxed.gpu.global.b128 v, [%3];\n"
               "mov.b128 {x, y}, v;\nmov.b64 {%0, %1}, x;\nmov.b64 {%2, u}, y;\n}"
               : "=r"(d0), "=r"(d1), "=r"(tag) : "l"(p) : "memory");
}
__device__ __forceinline__ uint2 ld_relaxed_pair(const uint2* p) {
  uint2 v;
  asm volatile("ld.relaxed.gpu.global.v2.u32 {%0, %1}, [%2];" : "=r"(v.x), "=r"(v.y) : "l"(p) : "memory");
  return v;
}
__device__ __forceinline__ void st_async2(uint32_t dst, uint32_t d0, uint32_t d1, uint32_t bar) {
  asm volatile("st.async.weak.shared::cluster.mbarrier::complete_tx::bytes.v2.b32 [%0], {%1, %2}, [%3];" ::"r"(dst),
               "r"(d0), "r"(d1), "r"(bar) : "memory");
}
__device__ __forceinline__ unsigned tag_value(float v, unsigned epoch) {
  return (__float_as_uint(v) & ~7u) | (epoch & 7u);
}
__device__ __forceinline__ float untag_value(unsigned v) { return __uint_as_float(v & ~7u); }
__device__ __forceinline__ void stsm4(uint32_t a, uint32_t r0, uint32_t r1, uint32_t r2, uint32_t r3) {
  asm volatile("stmatrix.sync.aligned.m8n8.x4.shared.b16 [%0], {%1, %2, %3, %4};" ::"r"(a), "r"(r0), "r"(r1),
               "r"(r2), "r"(r3) : "memory");
}
__device__ __forceinline__ void stsm4_t(uint32_t a, uint32_t r0, uint32_t r1, uint32_t r2, uint32_t r3) {
  asm volatile("stmatrix.sync.aligned.m8n8.x4.trans.shared.b16 [%0], {%1, %2, %3, %4};" ::"r"(a), "r"(r0),
               "r"(r1), "r"(r2), "r"(r3) : "memory");
}
__device__ __forceinline__ uint32_t transpose8(uint32_t a) {
  uint32_t d;
  asm volatile("movmatrix.sync.aligned.m8n8.trans.b16 %0, %1;" : "=r"(d) : "r"(a));
  return d;
}
__device__ __forceinline__ void mma16816(float (&c)[4], uint32_t a0, uint32_t a1, uint32_t a2, uint32_t a3,
                                         uint32_t b0, uint32_t b1) {
  asm volatile("mma.sync.aligned.m16n8k16.row.col.f32.bf16.bf16.f32 {%0, %1, %2, %3}, {%4, %5, %6, %7}, {%8, %9}, "
               "{%0, %1, %2, %3};"
               : "+f"(c[0]), "+f"(c[1]), "+f"(c[2]), "+f"(c[3])
               : "r"(a0), "r"(a1), "r"(a2), "r"(a3), "r"(b0), "r"(b1));
}
__device__ __forceinline__ void mma1688(float (&c)[4], uint32_t a0, uint32_t a1, uint32_t b0) {
  asm volatile("mma.sync.aligned.m16n8k8.row.col.f32.bf16.bf16.f32 {%0, %1, %2, %3}, {%4, %5}, {%6}, {%0, %1, %2, %3};"
               : "+f"(c[0]), "+f"(c[1]), "+f"(c[2]), "+f"(c[3]) : "r"(a0), "r"(a1), "r"(b0));
}
__device__ __forceinline__ float shfl_xor(float v, int m) {
  float r;
  asm volatile("shfl.sync.bfly.b32 %0, %1, %2, 31, 0xffffffff;" : "=f"(r) : "f"(v), "r"(m));
  return r;
}
__device__ __forceinline__ float tanh_fast(float x) {
  float r;
  asm volatile("tanh.approx.f32 %0, %1;" : "=f"(r) : "f"(x));
  return r;
}
__device__ __forceinline__ void ldsm4(uint32_t a, uint32_t (&r)[4]) {
  asm volatile("ldmatrix.sync.aligned.m8n8.x4.shared.b16 {%0, %1, %2, %3}, [%4];"
               : "=r"(r[0]), "=r"(r[1]), "=r"(r[2]), "=r"(r[3]) : "r"(a) : "memory");
}
__device__ __forceinline__ void ldsm4_t(uint32_t a, uint32_t (&r)[4]) {
  asm volatile("ldmatrix.sync.aligned.m8n8.x4.trans.shared.b16 {%0, %1, %2, %3}, [%4];"
               : "=r"(r[0]), "=r"(r[1]), "=r"(r[2]), "=r"(r[3]) : "r"(a) : "memory");
}
__device__ __forceinline__ uint32_t pack2(float lo, float hi) {
  uint32_t r;
  asm volatile("cvt.rn.bf16x2.f32 %0, %1, %2;" : "=r"(r) : "f"(hi), "f"(lo));
  return r;
}
__device__ __forceinline__ float bf_lo(uint32_t r) { return __uint_as_float(r << 16); }
__device__ __forceinline__ float bf_hi(uint32_t r) { return __uint_as_float(r & 0xffff0000u); }
__device__ __forceinline__ float ex2(float x) {
  float r;
  asm("ex2.approx.ftz.f32 %0, %1;" : "=f"(r) : "f"(x));
  return r;
}
__device__ __forceinline__ float rcp(float x) {
  float r;
  asm("rcp.approx.ftz.f32 %0, %1;" : "=f"(r) : "f"(x));
  return r;
}
template <int N>
__device__ __forceinline__ void wg_wait() {
  asm volatile("wgmma.wait_group.sync.aligned %0;" ::"n"(N) : "memory");
}
__device__ __forceinline__ void yield_slot() { asm volatile("pmevent 0;"); }

template <int N, int KIND>
__device__ __forceinline__ void mma_kblock(float (&acc)[2][96], uint32_t a, uint32_t b);

#define F8(m, d, i) m(d[i]), m(d[i + 1]), m(d[i + 2]), m(d[i + 3]), m(d[i + 4]), m(d[i + 5]), m(d[i + 6]), m(d[i + 7])
#define KSTEP(N, A, B, oa0, oa1, ob, sd)                                                   \
  "mov.b64 db, {" B ", hb};\nadd.u64 db, db, " #ob ";\n"                                    \
  "mov.b64 da, {" A ", ha};\nadd.u64 da, da, " #oa0 ";\n"                                   \
  "wgmma.mma_async.sync.aligned.m64n" #N "k16.f32.bf16.bf16 {" ACC##N##_0 "}, da, db, " #sd ", 1, 1, 0, 1;\n" \
  "mov.b64 da, {" A ", ha};\nadd.u64 da, da, " #oa1 ";\n"                                   \
  "wgmma.mma_async.sync.aligned.m64n" #N "k16.f32.bf16.bf16 {" ACC##N##_1 "}, da, db, " #sd ", 1, 1, 0, 1;\n"

#define MMA_KBLOCK(N, KIND, A, B, ob2, ob3, sd, MID, MODE)                                 \
  template <>                                                                              \
  __device__ __forceinline__ void mma_kblock<N, KIND>(float (&acc)[2][96], uint32_t a, uint32_t b) { \
    asm volatile("{\n.reg .b32 ha, hb;\n.reg .b64 da, db;\n"                            \
                 "mov.b32 ha, 0x40000080;\nmov.b32 hb, 0x40000040;\n"                       \
                 "wgmma.fence.sync.aligned;\n"                                             \
                 KSTEP(N, A, B, 0, 64, 0, sd) KSTEP(N, A, B, 2, 66, 128, 1) MID               \
                 KSTEP(N, A, B, 4, 68, ob2, 1) KSTEP(N, A, B, 6, 70, ob3, 1) "wgmma.commit_group.sync.aligned;\n}\n"  \
                 : OPS##N(MODE) : "r"(a), "r"(b) : "memory");                              \
  }
#define MMA_KBLOCKS(N, A, B, ob2, ob3)                                                     \
  MMA_KBLOCK(N, 0, A, B, ob2, ob3, 1, "", "+f")                                            \
  MMA_KBLOCK(N, 1, A, B, ob2, ob3, 1, "wgmma.commit_group.sync.aligned;\n", "+f")          \
  MMA_KBLOCK(N, 2, A, B, ob2, ob3, 0, "", "=f")

#define ACC128_0 \
  "%0, %1, %2, %3, %4, %5, %6, %7, %8, %9, %10, %11, %12, %13, %14, %15, " \
  "%16, %17, %18, %19, %20, %21, %22, %23, %24, %25, %26, %27, %28, %29, %30, %31, " \
  "%32, %33, %34, %35, %36, %37, %38, %39, %40, %41, %42, %43, %44, %45, %46, %47, " \
  "%48, %49, %50, %51, %52, %53, %54, %55, %56, %57, %58, %59, %60, %61, %62, %63"
#define ACC128_1 \
  "%64, %65, %66, %67, %68, %69, %70, %71, %72, %73, %74, %75, %76, %77, %78, %79, " \
  "%80, %81, %82, %83, %84, %85, %86, %87, %88, %89, %90, %91, %92, %93, %94, %95, " \
  "%96, %97, %98, %99, %100, %101, %102, %103, %104, %105, %106, %107, %108, %109, %110, %111, " \
  "%112, %113, %114, %115, %116, %117, %118, %119, %120, %121, %122, %123, %124, %125, %126, %127"
#define OPS128(m) \
  F8(m, acc[0], 0), F8(m, acc[0], 8), F8(m, acc[0], 16), F8(m, acc[0], 24), F8(m, acc[0], 32), F8(m, acc[0], 40), F8(m, acc[0], 48), F8(m, acc[0], 56), \
        F8(m, acc[1], 0), F8(m, acc[1], 8), F8(m, acc[1], 16), F8(m, acc[1], 24), F8(m, acc[1], 32), F8(m, acc[1], 40), F8(m, acc[1], 48), F8(m, acc[1], 56)
MMA_KBLOCKS(128, "%128", "%129", 512, 640)

#define ACC192_0 \
  "%0, %1, %2, %3, %4, %5, %6, %7, %8, %9, %10, %11, %12, %13, %14, %15, " \
  "%16, %17, %18, %19, %20, %21, %22, %23, %24, %25, %26, %27, %28, %29, %30, %31, " \
  "%32, %33, %34, %35, %36, %37, %38, %39, %40, %41, %42, %43, %44, %45, %46, %47, " \
  "%48, %49, %50, %51, %52, %53, %54, %55, %56, %57, %58, %59, %60, %61, %62, %63, " \
  "%64, %65, %66, %67, %68, %69, %70, %71, %72, %73, %74, %75, %76, %77, %78, %79, " \
  "%80, %81, %82, %83, %84, %85, %86, %87, %88, %89, %90, %91, %92, %93, %94, %95"
#define ACC192_1 \
  "%96, %97, %98, %99, %100, %101, %102, %103, %104, %105, %106, %107, %108, %109, %110, %111, " \
  "%112, %113, %114, %115, %116, %117, %118, %119, %120, %121, %122, %123, %124, %125, %126, %127, " \
  "%128, %129, %130, %131, %132, %133, %134, %135, %136, %137, %138, %139, %140, %141, %142, %143, " \
  "%144, %145, %146, %147, %148, %149, %150, %151, %152, %153, %154, %155, %156, %157, %158, %159, " \
  "%160, %161, %162, %163, %164, %165, %166, %167, %168, %169, %170, %171, %172, %173, %174, %175, " \
  "%176, %177, %178, %179, %180, %181, %182, %183, %184, %185, %186, %187, %188, %189, %190, %191"
#define OPS192(m) \
  F8(m, acc[0], 0), F8(m, acc[0], 8), F8(m, acc[0], 16), F8(m, acc[0], 24), F8(m, acc[0], 32), F8(m, acc[0], 40), F8(m, acc[0], 48), F8(m, acc[0], 56), F8(m, acc[0], 64), F8(m, acc[0], 72), F8(m, acc[0], 80), F8(m, acc[0], 88), \
        F8(m, acc[1], 0), F8(m, acc[1], 8), F8(m, acc[1], 16), F8(m, acc[1], 24), F8(m, acc[1], 32), F8(m, acc[1], 40), F8(m, acc[1], 48), F8(m, acc[1], 56), F8(m, acc[1], 64), F8(m, acc[1], 72), F8(m, acc[1], 80), F8(m, acc[1], 88)
MMA_KBLOCKS(192, "%192", "%193", 768, 896)

#define HSTEP(oa, ob)                                                                       \
  "mov.b64 db, {%97, hb};\nadd.u64 db, db, " #ob ";\nmov.b64 da, {%96, ha};\nadd.u64 da, da, " #oa ";\n" \
  "wgmma.mma_async.sync.aligned.m64n192k16.f32.bf16.bf16 {" ACC192_0 "}, da, db, 1, 1, 1, 0, 1;\n"
__device__ __forceinline__ void mma_half(float (&d)[96], uint32_t a, uint32_t b) {
  asm volatile("{\n.reg .b32 ha, hb;\n.reg .b64 da, db;\nmov.b32 ha, 0x40000080;\nmov.b32 hb, 0x40000040;\n"
               "wgmma.fence.sync.aligned;\n" HSTEP(0, 0) HSTEP(2, 128) HSTEP(4, 768) HSTEP(6, 896)
               "wgmma.commit_group.sync.aligned;\n}\n"
               : F8("+f", d, 0), F8("+f", d, 8), F8("+f", d, 16), F8("+f", d, 24), F8("+f", d, 32), F8("+f", d, 40),
                 F8("+f", d, 48), F8("+f", d, 56), F8("+f", d, 64), F8("+f", d, 72), F8("+f", d, 80), F8("+f", d, 88)
               : "r"(a), "r"(b) : "memory");
}

#define TSTEP(REGS, W, X, ow, ox)                                                           \
  "mov.b64 db, {" X ", hi};\nadd.u64 db, db, " #ox ";\nmov.b64 da, {" W ", hi};\nadd.u64 da, da, " #ow ";\n" \
  "wgmma.mma_async.sync.aligned.m64n128k16.f32.bf16.bf16 {" REGS "}, da, db, 1, 1, 1, 1, 0;\n"
#define THEAD "{\n.reg .b32 hi;\n.reg .b64 da, db;\nmov.b32 hi, 0x40000040;\nwgmma.fence.sync.aligned;\n"
#define TTAIL "wgmma.commit_group.sync.aligned;\n}\n"
__device__ __forceinline__ void mma_kblock_t(float (&acc)[2][96], uint32_t wd, uint32_t xd) {
  asm volatile(THEAD TSTEP(ACC128_0, "%128", "%129", 0, 0) TSTEP(ACC128_1, "%128", "%129", 256, 0)
               TSTEP(ACC128_0, "%128", "%129", 128, 2) TSTEP(ACC128_1, "%128", "%129", 384, 2)
               TSTEP(ACC128_0, "%128", "%129", 512, 4) TSTEP(ACC128_1, "%128", "%129", 768, 4)
               TSTEP(ACC128_0, "%128", "%129", 640, 6) TSTEP(ACC128_1, "%128", "%129", 896, 6) TTAIL
               : OPS128("+f") : "r"(wd), "r"(xd) : "memory");
}
__device__ __forceinline__ void mma_half_t(float (&d)[96], uint32_t wd, uint32_t xd) {
  asm volatile(THEAD TSTEP(ACC128_0, "%64", "%65", 0, 0) TSTEP(ACC128_0, "%64", "%65", 128, 2)
               TSTEP(ACC128_0, "%64", "%65", 512, 4) TSTEP(ACC128_0, "%64", "%65", 640, 6) TTAIL
               : F8("+f", d, 0), F8("+f", d, 8), F8("+f", d, 16), F8("+f", d, 24), F8("+f", d, 32), F8("+f", d, 40),
                 F8("+f", d, 48), F8("+f", d, 56) : "r"(wd), "r"(xd) : "memory");
}

enum { kModePlain = 0, kModeHead = 1, kModeSkip = 2, kModeContinue = 3 };

template <int N>
__device__ __forceinline__ void fence_acc(float (&acc)[2][96]) {
#pragma unroll
  for (int h = 0; h < 2; h++)
#pragma unroll
    for (int i = 0; i < N / 2; i++) asm volatile("" : "+f"(acc[h][i])::"memory");
}

constexpr uint32_t kToB = (kTileBytes >> 4) + ((4096u >> 4) << 16) - (1u << 16);

#define TRACE_KB(nb)

template <int N>
__device__ __forceinline__ void head_blocks(float (&acc)[2][96], uint32_t sb, int n0, int slot, int xver,
                                            uint32_t rel_addr, bool rel) {
  const uint32_t ring = (((sb & 0x3FFFF) + kSmRing) >> 4) | (1u << 16);
  const uint32_t xdesc = (((sb & 0x3FFFF) + kSmX) >> 4) | (1u << 16);
  const uint32_t s0 = ring + slot * 2560, s1 = ring + ((slot + 1) & 3) * 2560;
  const uint32_t to_b = xver > 0 ? kToB - (kTileBytes >> 4) : kToB;
  const uint32_t nb = n0 * 8, xbar = sb + kBarX + (xver - 1) * 16;
  if (xver > 0) {
    mbar_wait(xbar, 0);
    mbar_wait(sb + kBarTurn + (xver == 1 ? 2 : 3 * xver) * 8, 0);
  }
  mbar_wait(sb + kBarFull + (nb & 56), nb >> 6);
  if (n0 == 0) TRACE_AT(0, 1);
  TRACE_KB(nb);
  mma_kblock<N, 2>(acc, xver > 0 ? xdesc : s0, s0 + to_b);
  if (xver > 0) mbar_wait(xbar + 8, 0);
  mbar_wait(sb + kBarFull + (nb & 56) + 8, nb >> 6);
  TRACE_KB(nb + 8);
  mma_kblock<N, 0>(acc, xver > 0 ? xdesc + (kTileBytes >> 4) : s1, s1 + to_b);
  wg_wait<1>();
  if (rel) mbar_arrive_cluster(rel_addr + (nb & 56));
  wg_wait<0>();
  if (rel) mbar_arrive_cluster(rel_addr + (nb & 56) + 8);
  fence_acc<N>(acc);
}

enum { kPlain, kResid, kStagger };
template <int N, int KIND, class Pre>
__device__ __forceinline__ void mainloop(float (&acc)[2][96], uint32_t sb, int tile, int n0, int slot, int nkb,
                                         int pause_kk, int att, uint32_t rel_addr, bool rel, int own_kk, Pre pre,
                                         uint32_t prev = 64) {
  constexpr bool RESID = KIND == kResid;
  constexpr uint32_t kStep = (N == 192 ? 5 : 4) * 512;
  const uint32_t ring = (((sb & 0x3FFFF) + kSmRing) >> 4) | (1u << 16);
  uint32_t st = ring + slot * kStep;
  uint32_t nb = n0 * 8;
  const uint32_t last = nb + 8 * (nkb - (RESID ? 4 : KIND == kStagger ? 2 : 1)), own = nb + 8 * own_kk;
  const uint32_t stg = (((sb & 0x3FFFF) + kSmStg) >> 4) | (1u << 16);
  uint32_t stop = pause_kk >= 0 ? nb + 8 * pause_kk : last;
  const bool signal = (threadIdx.x & 127) == 64;
  fence_acc<N>(acc);
  if (tile > 0) mbar_wait(sb + kBarTurn + (tile - 1) * 8, 0);
  TRACE_AT(tile, 0);
#pragma unroll 1
  while (true) {
#pragma unroll 1
    do {
      mbar_wait(sb + kBarFull + (nb & 56), nb >> 6);
      TRACE_KB(nb);
      if constexpr (RESID) mma_kblock_t(acc, st + kToB, nb == own ? stg : st);
      else mma_kblock<N, 0>(acc, st, st + kToB);
      wg_wait<1>();
      if (rel) mbar_arrive_cluster(rel_addr + prev);
      prev = nb & 56;
      st += kStep;
      if (st == ring + 10240) st = ring;
      nb += 8;
    } while (nb != stop);
    if (stop == last) break;
    stop = last;
    if (signal) mbar_arrive(sb + kBarPause + att * 8);
    wg_wait<0>();
    if (rel) mbar_arrive_cluster(rel_addr + prev);
    prev = 64;
    mbar_wait(sb + kBarResume + att * 8, 0);
  }
  mbar_wait(sb + kBarFull + (nb & 56), nb >> 6);
  TRACE_KB(nb);
  if constexpr (RESID) {
    const uint32_t z = gridDim.y - 1;
    const uint32_t s1 = st + kStep, s2 = s1 + kStep, s3 = s2 == ring + 8192 ? ring : s2 + kStep;
    mma_half_t(acc[0], st + kToB, st);
    wg_wait<1>();
    if (rel) mbar_arrive_cluster(rel_addr + 24);
    mbar_wait(sb + kBarFull + 40, nb >> 6);
    TRACE_KB(nb + 8);
    mma_half_t(acc[0], s1 + kToB, s1);
    mbar_wait(sb + kBarFull + 48, nb >> 6);
    TRACE_KB(nb + 16);
    mma_half_t(acc[0], s2 + kToB, s2);
    mbar_wait(sb + kBarFull + 56, nb >> 6);
    TRACE_KB(nb + 24);
    mma_half_t(acc[0], s3 + kToB, s3);
    mma_half_t(acc[1], st + kToB + 256, st + z);
    mma_half_t(acc[1], s1 + kToB + 256, s1 + z);
    wg_wait<2>();
#pragma unroll
    for (int i = 0; i < 64; i++) asm volatile("" : "+f"(acc[0][i])::"memory");
    pre(0);
    mma_half_t(acc[1], s2 + kToB + 256, s2 + z);
    wg_wait<2>();
    if (rel) mbar_arrive_cluster(rel_addr + 32);
    pre(1);
    mma_half_t(acc[1], s3 + kToB + 256, s3 + z);
    wg_wait<2>();
    if (rel) mbar_arrive_cluster(rel_addr + 40);
    wg_wait<1>();
    if (signal) mbar_arrive(sb + kBarTurn + tile * 8);
    if (rel) mbar_arrive_cluster(rel_addr + 48);
    wg_wait<0>();
    if (rel) mbar_arrive_cluster(rel_addr + 56);
#pragma unroll
    for (int i = 0; i < 64; i++) asm volatile("" : "+f"(acc[1][i])::"memory");
  } else if constexpr (KIND == kStagger) {
    const uint32_t z = gridDim.y - 1, s2 = st + kStep;
    mma_half(acc[1], st + 64, st + kToB);
    wg_wait<1>();
    if (rel) mbar_arrive_cluster(rel_addr + 40);
    mbar_wait(sb + kBarFull + 56, nb >> 6);
    TRACE_KB(nb + 8);
    mma_half(acc[1], s2 + 64, s2 + kToB);
    mma_half(acc[0], st, st + z + kToB);
    pre(0);
    mma_half(acc[0], s2, s2 + z + kToB);
    wg_wait<2>();
#pragma unroll
    for (int i = 0; i < 96; i++) asm volatile("" : "+f"(acc[1][i])::"memory");
    pre(1);
    wg_wait<1>();
    if (rel) mbar_arrive_cluster(rel_addr + 48);
    pre(2);
    if (signal) mbar_arrive(sb + kBarTurn + tile * 8);
    pre(3);
    wg_wait<0>();
    if (rel) mbar_arrive_cluster(rel_addr + 56);
#pragma unroll
    for (int i = 0; i < 96; i++) asm volatile("" : "+f"(acc[0][i])::"memory");
  } else {
    mma_kblock<N, 1>(acc, st, st + kToB);
    wg_wait<2>();
    if (rel) mbar_arrive_cluster(rel_addr + prev);
    pre();
    wg_wait<1>();
    if (signal) mbar_arrive(sb + kBarTurn + tile * 8);
    wg_wait<0>();
    if (rel) mbar_arrive_cluster(rel_addr + (nb & 56));
    fence_acc<N>(acc);
  }
}

__device__ __forceinline__ void publish_stats(uint32_t sb, uint2* stat, int w, int lane, unsigned epoch) {
  const uint32_t row = sb + kSmX + (32 * w + lane) * 128;
  float s[4], q[4];
#pragma unroll
  for (int c = 0; c < 4; c++) s[c] = q[c] = 0.f;
  uint32_t nx[4];
  ldsm4(row + ((lane & 7) << 4), nx);
#pragma unroll 1
  for (int J = 1; J <= 16; J++) {
    const uint32_t r[4] = {nx[0], nx[1], nx[2], nx[3]};
    ldsm4(row + ((J >> 3) & 1) * kTileBytes + (((J ^ lane) & 7) << 4), nx);
#pragma unroll
    for (int c = 0; c < 4; c++) {
      const float lo = bf_lo(r[c]);
      s[c] += lo;
      q[c] = fmaf(lo, lo, q[c]);
      if (c & 1) yield_slot();
    }
#pragma unroll
    for (int c = 0; c < 4; c++) {
      const float hi = bf_hi(r[c]);
      s[c] += hi;
      q[c] = fmaf(hi, hi, q[c]);
      if (c & 1) yield_slot();
    }
  }
  const int t = lane & 3, g = lane >> 2;
#pragma unroll
  for (int c = 0; c < 2; c++) {
    s[c] = (t & 2 ? s[c + 2] : s[c]) + shfl_xor(t & 2 ? s[c] : s[c + 2], 2);
    q[c] = (t & 2 ? q[c + 2] : q[c]) + shfl_xor(t & 2 ? q[c] : q[c + 2], 2);
  }
  const float so = (t & 1 ? s[1] : s[0]) + shfl_xor(t & 1 ? s[0] : s[1], 1);
  const float qo = (t & 1 ? q[1] : q[0]) + shfl_xor(t & 1 ? q[0] : q[1], 1);
  asm volatile("{\n.reg .b64 t;\nmov.b64 t, {%1, %2};\nst.relaxed.gpu.global.b64 [%0], t;\n}" ::"l"(stat + 32 * w + 8 * t + g),
               "r"(tag_value(so, epoch)), "r"(__float_as_uint(qo)) : "memory");
}

__device__ __forceinline__ void add_chunk(float (&a)[8], const uint4& v) {
  a[0] += bf_lo(v.x); a[1] += bf_hi(v.x);
  a[2] += bf_lo(v.y); a[3] += bf_hi(v.y);
  a[4] += bf_lo(v.z); a[5] += bf_hi(v.z);
  a[6] += bf_lo(v.w); a[7] += bf_hi(v.w);
}

__device__ __forceinline__ int helper_col(int id, int slab) {
  return (slab < 3 ? slab * kD : (slab - 3) * 512) + id * 128;
}
__device__ __forceinline__ void helper_cta(const CUtensorMap* map_q, const CUtensorMap* map_1, uint8_t* sm,
                                           uint32_t sb, int id, int warp) {
  constexpr int kRed = 6 * 32768, kBar = kRed + 2 * 4096;
  const int tid = threadIdx.x;
  if (warp == 8 && elect()) {
#pragma unroll
    for (int s = 0; s < 6; s++) {
      mbar_init(sb + kBar + s * 8, 1);
      mbar_init(sb + kBar + 64 + s * 8, 4);
    }
    fence_async_smem();
#pragma unroll
    for (int s = 0; s < 6; s++) {
      mbar_expect_tx(sb + kBar + s * 8, 32768);
      tma2d(sb + s * 32768, map_q, sb + kBar + s * 8, id * 128, s * 128);
    }
  }
  __syncthreads();
  if (warp == 8) {
    int slot = 0, ph = 0;
#pragma unroll 1
    for (int n = 6; n < 80; n++) {
      mbar_wait(sb + kBar + 64 + slot * 8, ph);
      if (elect()) {
        mbar_expect_tx(sb + kBar + slot * 8, 32768);
        tma2d(sb + slot * 32768, n < 24 ? map_q : map_1, sb + kBar + slot * 8, helper_col(id, n >> 3), (n & 7) * 128);
      }
      if (++slot == 6) slot = 0, ph ^= 1;
    }
  } else if (warp < 8) {
    if (tid == 0) *reinterpret_cast<unsigned*>(sm + kBar + 128) = atomicAdd(&g_ticket, 1u) / kGrid + 1;
    int slot = warp >> 2, ph = 0;
#pragma unroll 1
    for (int slab = 0; slab < 10; slab++) {
      float a[8];
#pragma unroll
      for (int e = 0; e < 8; e++) a[e] = 0.f;
#pragma unroll 1
      for (int box = 0; box < 4; box++) {
        mbar_wait_bounded(sb + kBar + slot * 8, ph);
        const uint4* p = reinterpret_cast<const uint4*>(sm + slot * 32768) + (tid & 127);
        uint4 v[16];
#pragma unroll
        for (int i = 0; i < 16; i++) v[i] = p[i * 128];
        __syncwarp();
        if (elect()) mbar_arrive(sb + kBar + 64 + slot * 8);
#pragma unroll
        for (int i = 0; i < 16; i++) add_chunk(a, v[i]);
        slot += 2;
        if (slot >= 6) slot -= 6, ph ^= 1;
      }
      float* red = reinterpret_cast<float*>(sm + kRed + (slab & 1) * 4096);
#pragma unroll
      for (int e = 0; e < 8; e++) a[e] += shfl_xor(a[e], 16);
      if ((tid & 16) == 0) {
        float4* d = reinterpret_cast<float4*>(red + warp * 128 + (tid & 15) * 8);
        d[0] = make_float4(a[0], a[1], a[2], a[3]);
        d[1] = make_float4(a[4], a[5], a[6], a[7]);
      }
      asm volatile("bar.sync 1, 256;" ::: "memory");
      if (warp < 4) {
        float t = 0.f;
#pragma unroll
        for (int q = 0; q < 8; q++) t += red[q * 128 + tid];
        st_relaxed(g_cs + (slab < 3 ? 0 : 3 * kD) + helper_col(id, slab) + tid,
                   tag_value(t, *reinterpret_cast<volatile unsigned*>(sm + kBar + 128)));
      }
    }
  }
}

__device__ __forceinline__ void colsum_strip(const CUtensorMap* map, uint8_t* sm, uint32_t sb, int col, int half,
                                             int lane, unsigned epoch) {
  const uint32_t bar = sb + kBarSlab + half * 16;
  const int buf = kSmStg + half * 8192;
  float a[8];
#pragma unroll
  for (int e = 0; e < 8; e++) a[e] = 0.f;
#pragma unroll 1
  for (int r = -2; r < 4; r++) {
    if (r >= 0) {
      mbar_wait(bar + (r & 1) * 8, r >> 1);
      const uint4* p = reinterpret_cast<const uint4*>(sm + buf + (r & 1) * 4096) + lane;
#pragma unroll 1
      for (int q = 0; q < 8; q += 4) {
        uint4 v[4];
#pragma unroll
        for (int u = 0; u < 4; u++) v[u] = p[(q + u) * 32];
#pragma unroll
        for (int u = 0; u < 4; u++) {
          a[0] += bf_lo(v[u].x); a[1] += bf_hi(v[u].x); a[2] += bf_lo(v[u].y); a[3] += bf_hi(v[u].y);
          yield_slot();
          a[4] += bf_lo(v[u].z); a[5] += bf_hi(v[u].z); a[6] += bf_lo(v[u].w); a[7] += bf_hi(v[u].w);
          yield_slot();
        }
      }
      fence_async_smem();
      __syncwarp();
    }
    if (r < 2 && elect()) {
      mbar_expect_tx(bar + (r & 1) * 8, 4096);
      tma2d(sb + buf + (r & 1) * 4096, map, bar + (r & 1) * 8, col, half * 512 + (r + 2) * 128);
    }
  }
#pragma unroll
  for (int e = 0; e < 4; e++) a[e] = (lane & 16 ? a[e + 4] : a[e]) + shfl_xor(lane & 16 ? a[e] : a[e + 4], 16);
#pragma unroll
  for (int e = 0; e < 2; e++) a[e] = (lane & 8 ? a[e + 2] : a[e]) + shfl_xor(lane & 8 ? a[e] : a[e + 2], 8);
  a[0] = (lane & 4 ? a[1] : a[0]) + shfl_xor(lane & 4 ? a[0] : a[1], 4);
  a[0] += shfl_xor(a[0], 2);
  if (!(lane & 2)) st_relaxed(g_cs + half * (3 * kD + kF) + col + (lane & 1) * 8 + (lane >> 2), tag_value(a[0], epoch));
}

constexpr float kGeluBeta = 0.3292034911525734f / 2.f;
constexpr float kGeluK = 2.423681954311584f / 4.f;
constexpr float kHScale = 2.f * kGeluBeta;

__device__ __forceinline__ void store_staged(uint8_t* dst, uint32_t stg) {
  fence_async_smem();
  __syncwarp();
  if (elect()) {
    bulk_store(dst, stg, 4096);
    bulk_commit();
  }
}

template <int J0, int J1>
__device__ __forceinline__ void fold_norm(float (&acc)[2][96], const float2 (&st)[4], const float4* vec) {
  float4 vn = vec[J0 * 4];
#pragma unroll
  for (int J = J0; J < J1; J++) {
    const float4 v = vn;
    if (J + 1 < J1) vn = vec[J * 4 + 4];
#pragma unroll
    for (int c = 0; c < 4; c++) {
      float& a0 = acc[c & 1][4 * J + (c & 2)];
      float& a1 = acc[c & 1][4 * J + (c & 2) + 1];
      a0 = fmaf(a0, st[c].x, fmaf(st[c].y, v.x, v.z));
      a1 = fmaf(a1, st[c].x, fmaf(st[c].y, v.y, v.w));
      asm volatile("" : "+f"(a0), "+f"(a1));
      if (c & 1) yield_slot();
    }
  }
}

template <int CH, class Acquire>
__device__ __forceinline__ void gelu_chunk(const float (&acc)[2][96], uint32_t stg, int lane, uint8_t* prev,
                                           Acquire acquire) {
  uint32_t pk[8][4];
  float z[3][4];
  const uint32_t row = (stg + lane * 128) ^ ((lane & 7) << 4);
#define U(s, e) acc[(e) >> 1][4 * (CH * 8 + ((s) >> 1)) + 2 * ((s) & 1) + ((e) & 1)]
#pragma unroll
  for (int s = 0; s < 18; s++) {
    const int cur = s % 3, p1 = (s + 2) % 3, p2 = (s + 1) % 3, q = s - 2, jj = 2 * q - 24;
    const bool mid = s >= 1 && s < 17;
    if (mid) z[p1][0] = tanh_fast(z[p1][0]);
    if (s < 16) {
#pragma unroll
      for (int e = 0; e < 4; e++) {
        z[cur][e] = fmaf(U(s, e), U(s, e), kGeluK);
        asm volatile("" : "+f"(z[cur][e]));
      }
    }
    if (jj >= 0) stsm4(row ^ (jj << 4), pk[jj][0], pk[jj][1], pk[jj][2], pk[jj][3]);
    yield_slot();
    if (mid) z[p1][1] = tanh_fast(z[p1][1]);
    if (q >= 0) {
      pk[q >> 1][2 * (q & 1)] = pack2(fmaf(U(q, 0), z[p2][0], U(q, 0)), fmaf(U(q, 1), z[p2][1], U(q, 1)));
      pk[q >> 1][2 * (q & 1) + 1] = pack2(fmaf(U(q, 2), z[p2][2], U(q, 2)), fmaf(U(q, 3), z[p2][3], U(q, 3)));
    }
    if (mid) z[p1][2] = tanh_fast(z[p1][2]);
    if (s < 16) {
#pragma unroll
      for (int e = 0; e < 4; e++) {
        z[cur][e] = z[cur][e] * U(s, e) * 8.f;
        asm volatile("" : "+f"(z[cur][e]));
      }
    }
    if (mid) z[p1][3] = tanh_fast(z[p1][3]);
    if (jj >= 0) stsm4(row ^ ((jj + 1) << 4), pk[jj + 1][0], pk[jj + 1][1], pk[jj + 1][2], pk[jj + 1][3]);
    yield_slot();
    if (CH == 1 && s == 1) store_staged(prev, stg);
    if (q == 11) acquire();
  }
#undef U
}

__device__ __forceinline__ void scale_stats(float2 (&st)[4]) {
#pragma unroll
  for (int c = 0; c < 4; c++) {
    st[c].x *= kGeluBeta;
    st[c].y *= st[c].x;
  }
}

__device__ __forceinline__ void add_mean_term(float (&acc)[2][96], const float2 (&st)[4], uint8_t* sm, int tq,
                                              int lane) {
  const float2* cs = reinterpret_cast<const float2*>(sm + kSmCsQ) + tq * 96 + (lane & 3);
  float2 vn = cs[0];
#pragma unroll
  for (int J = 0; J < 24; J++) {
    const float2 v = vn;
    if (J < 23) vn = cs[J * 4 + 4];
#pragma unroll
    for (int c = 0; c < 4; c++) {
      acc[c & 1][4 * J + (c & 2)] = fmaf(st[c].y, v.x, acc[c & 1][4 * J + (c & 2)]);
      acc[c & 1][4 * J + (c & 2) + 1] = fmaf(st[c].y, v.y, acc[c & 1][4 * J + (c & 2) + 1]);
    }
    yield_slot();
  }
}

struct AttnRegs {
  uint32_t q[4][8], k[5][8], vt[5][8];
};
#define SCALED(c, J) pack2(acc[(c) & 1][4 * (J) + ((c) & 2)] * st[c].x, acc[(c) & 1][4 * (J) + ((c) & 2) + 1] * st[c].x)
__device__ __forceinline__ void convert_group(const float (&acc)[2][96], const float2 (&st)[4], AttnRegs& r, int c,
                                              int part) {
#pragma unroll
  for (int J = 0; J < 8; J++) {
    if (part == 0) r.q[c][J] = SCALED(c, J);
    if (part == 1) r.k[c + 1][J] = SCALED(c, 8 + J);
    if (part == 2) r.vt[c + 1][J] = transpose8(SCALED(c, 16 + J));
    if (J & 1) yield_slot();
  }
}
#undef SCALED

__device__ __forceinline__ void convert_odd(const float (&acc)[2][96], const float2 (&st)[4], AttnRegs& r, int step,
                                            uint8_t* sm, uint32_t sb, int att, uint4* halo_out, int b, unsigned epoch, int w,
                                            int lane) {
  if (step == 1) {
    convert_group(acc, st, r, 3, 2);
    convert_group(acc, st, r, 3, 1);
    if (w < 3) {
      uint2* hs = reinterpret_cast<uint2*>(sm + kSmHalo + (w + 1) * 2048) + lane;
#pragma unroll
      for (int i = 0; i < 4; i++) {
        hs[i * 32] = make_uint2(r.k[4][2 * i], r.k[4][2 * i + 1]);
        hs[128 + i * 32] = make_uint2(r.vt[4][2 * i], r.vt[4][2 * i + 1]);
      }
      __syncwarp();
      if (elect()) mbar_arrive(sb + kBarHalo + (att * 4 + w + 1) * 8);
    } else if (!(b & 1)) {
      const uint32_t base = mapa(sb, 1), dst = base + kSmHalo + lane * 8, bar = base + kBarHalo + att * 32;
#pragma unroll
      for (int i = 0; i < 4; i++) {
        st_async2(dst + i * 256, r.k[4][2 * i], r.k[4][2 * i + 1], bar);
        st_async2(dst + 1024 + i * 256, r.vt[4][2 * i], r.vt[4][2 * i + 1], bar);
      }
    } else if ((b & 7) != 7) {
#pragma unroll
      for (int i = 0; i < 4; i++) {
        st_packet(halo_out + lane + i * 32, r.k[4][2 * i], r.k[4][2 * i + 1], epoch);
        st_packet(halo_out + lane + 128 + i * 32, r.vt[4][2 * i], r.vt[4][2 * i + 1], epoch);
      }
    }
  } else if (step == 2) {
    convert_group(acc, st, r, 1, 2);
  } else {
    convert_group(acc, st, r, 1, 1);
    convert_group(acc, st, r, 3, 0);
    convert_group(acc, st, r, 1, 0);
  }
}

__device__ __forceinline__ void epilogue_attn(const float (&acc)[2][96], const float2 (&st)[4], AttnRegs& r,
                                              uint8_t* sm, uint32_t sb, int layer, int tq, int b, int j,
                                              unsigned epoch, int tile, int w, int lane) {
  const int t = lane & 3, g = lane >> 2;
  const int hp = j + 8 * tq, att = 2 * layer + tq;
  auto& q = r.q;
  auto& k = r.k;
  auto& vt = r.vt;
  const bool first = w == 0 && (b & 7) == 0, local = w > 0 || (b & 1);
  const uint4* gh = g_halo + ((layer * 16 + b - 1) * 16 + hp) * 256 + lane;
  uint32_t tag[8];
#define LOAD_HALO()                                                                                    \
  _Pragma("unroll") for (int i = 0; i < 4; i++) {                                                      \
    ld_packet(gh + i * 32, k[0][2 * i], k[0][2 * i + 1], tag[i]);                                      \
    ld_packet(gh + 128 + i * 32, vt[0][2 * i], vt[0][2 * i + 1], tag[4 + i]);                          \
  }
#pragma unroll
  for (int c = 0; c < 6; c++) {
    if (c == 2) {
#pragma unroll
      for (int i = 0; i < 8; i++) k[0][i] = vt[0][i] = tag[i] = 0u;
      if (!local && !first) LOAD_HALO();
    }
    if (c == 2 && local) {
      if (w == 0 && lane == 0) mbar_expect_tx(sb + kBarHalo + att * 32, 2048);
      mbar_wait(sb + kBarHalo + (att * 4 + w) * 8, 0);
      const uint2* hs = reinterpret_cast<const uint2*>(sm + kSmHalo + w * 2048) + lane;
#pragma unroll
      for (int i = 0; i < 4; i++) {
        const uint2 a = hs[i * 32], d = hs[128 + i * 32];
        k[0][2 * i] = a.x; k[0][2 * i + 1] = a.y;
        vt[0][2 * i] = d.x; vt[0][2 * i + 1] = d.y;
      }
    }
    convert_group(acc, st, r, 2 * (c & 1), 2 - (c >> 1));
  }
  TRACE_AT(tile, 8);
  if (!local && !first) {
#pragma unroll 1
    while (__any_sync(0xffffffffu, ((tag[0] ^ epoch) | (tag[1] ^ epoch) | (tag[2] ^ epoch) | (tag[3] ^ epoch)) |
                                       ((tag[4] ^ epoch) | (tag[5] ^ epoch) | (tag[6] ^ epoch) | (tag[7] ^ epoch)))) {
      LOAD_HALO();
    }
  }
  constexpr float kScale = 0.17677669529663687f * 1.4426950408889634f;
  const bool own0 = 2 * t <= g, own1 = 2 * t + 1 <= g;
  const uint32_t own_mask = (own0 ? 0xffffu : 0u) | (own1 ? 0xffff0000u : 0u);
  const uint32_t stg = sb + kSmStg + w * 4096;
  const uint32_t orow = stg + (lane & 7) * 128, ochunk = (lane >> 3) ^ (lane & 7);
  TRACE_AT(tile, 9);
  mbar_wait(sb + kBarPause + att * 8, 0);
  TRACE_AT(tile, 10);

  float s[2][6][4], o[2][4][2][4];
#pragma unroll
  for (int n = 0; n < 24; n++) {
    const int ks = n / 12, hd = (n % 12) / 6, m = n % 6, ca = 2 * (m / 3), kg = ca + m % 3, J = 4 * hd + 2 * ks;
    if (ks == 0) s[hd][m][0] = s[hd][m][1] = s[hd][m][2] = s[hd][m][3] = 0.f;
    mma16816(s[hd][m], q[ca][J], q[ca + 1][J], q[ca][J + 1], q[ca + 1][J + 1], k[kg][J], k[kg][J + 1]);
  }
  float v0[2][4], v1[2][4], m[2][4];
  uint32_t pp[2][4], po[2][4];
#define UNITS _Pragma("unroll") for (int hd = 0; hd < 2; hd++) _Pragma("unroll") for (int c = 0; c < 4; c++)
  UNITS {
    const int mp = 3 * (c >> 1) + (c & 1), r = 2 * (c & 1);
    float p0 = s[hd][mp][r], p1 = s[hd][mp][r + 1];
    if (c == 0 && first) p0 = p1 = -INFINITY;
    v0[hd][c] = own0 ? s[hd][mp + 1][r] : p0;
    v1[hd][c] = own1 ? s[hd][mp + 1][r + 1] : p1;
    m[hd][c] = fmaxf(v0[hd][c], v1[hd][c]);
  }
  UNITS m[hd][c] = fmaxf(m[hd][c], shfl_xor(m[hd][c], 1));
  UNITS m[hd][c] = fmaxf(m[hd][c], shfl_xor(m[hd][c], 2));
  UNITS {
    const float nm = -m[hd][c] * kScale;
    v0[hd][c] = ex2(fmaf(v0[hd][c], kScale, nm));
    v1[hd][c] = ex2(fmaf(v1[hd][c], kScale, nm));
    m[hd][c] = v0[hd][c] + v1[hd][c];
  }
  UNITS m[hd][c] += shfl_xor(m[hd][c], 1);
  UNITS m[hd][c] += shfl_xor(m[hd][c], 2);
  UNITS {
    const float inv = rcp(m[hd][c]);
    const uint32_t p = pack2(v0[hd][c] * inv, v1[hd][c] * inv);
    pp[hd][c] = p & ~own_mask;
    po[hd][c] = p & own_mask;
    asm volatile("" : "+r"(pp[hd][c]), "+r"(po[hd][c]));
  }
#pragma unroll
  for (int n = 0; n < 24; n++) {
    const int ph = n / 8, hd = (n >> 2) & 1, c = 2 * ((n >> 1) & 1) + (ph == 1), ds = n & 1, J = 4 * hd + 2 * ds;
    float(&d)[4] = o[hd][c][ds];
    if (ph < 2) d[0] = d[1] = d[2] = d[3] = 0.f;
    if (ph == 0) mma1688(d, vt[c + 1][J], vt[c + 1][J + 1], po[hd][c]);
    if (ph == 1) mma16816(d, vt[c][J], vt[c][J + 1], vt[c + 1][J], vt[c + 1][J + 1], pp[hd][c], po[hd][c]);
    if (ph == 2) mma1688(d, vt[c][J], vt[c][J + 1], pp[hd][c]);
    if (n == 3) {
      yield_slot();
      if (tq == 0 && lane == 0) mbar_arrive(sb + kBarResume + att * 8);
    }
  }
  yield_slot();
  if (tq == 1 && lane == 0) mbar_arrive(sb + kBarResume + att * 8);
  TRACE_AT(tile, 11);
  UNITS stsm4_t(orow + c * 1024 + ((ochunk ^ (4 * hd)) << 4), pack2(o[hd][c][0][0], o[hd][c][0][1]),
                pack2(o[hd][c][0][2], o[hd][c][0][3]), pack2(o[hd][c][1][0], o[hd][c][1][1]),
                pack2(o[hd][c][1][2], o[hd][c][1][3]));
#undef UNITS
#undef LOAD_HALO
  fence_async_smem();
  __syncwarp();
  TRACE_AT(tile, 12);
  if (elect()) {
    bulk_store(g_o + (b * 16 + hp) * kTileBytes + w * 4096, stg, 4096);
    bulk_commit();
    bulk_wait();
    TRACE_AT(tile, 13);
    mbar_arrive(sb + kBarEpi + tile * 8);
  }
  __syncwarp();
}

__device__ __forceinline__ void gather_stats(uint8_t* sm, const uint2* stat, int r, float eps, unsigned epoch) {
  uint2 a[8];
  unsigned diff;
#pragma unroll 1
  do {
    __nanosleep(800);
    diff = 0;
#pragma unroll
    for (int i = 0; i < 8; i++) {
      a[i] = ld_relaxed64(stat + i * 128 + r);
      diff |= a[i].x ^ epoch;
    }
  } while (__any_sync(0xffffffffu, diff & 7u));
  float s = 0.f, q = 0.f;
#pragma unroll
  for (int i = 0; i < 8; i++) {
    s += untag_value(a[i].x);
    q += __uint_as_float(a[i].y);
  }
  const float mean = s * (1.f / 1024.f);
  const float var = fmaxf(fmaf(-mean, mean, q * (1.f / 1024.f)), 0.f);
  reinterpret_cast<float2*>(sm + kSmStat)[r] = make_float2(rsqrtf(var + eps), -mean);
}

__device__ __forceinline__ void gather_colsums_qkv(uint8_t* sm, int tq, int j, int lane, unsigned epoch) {
  const uint2* src = reinterpret_cast<const uint2*>(g_cs + (j + 8 * tq) * 64) + lane;
  uint2 v[3], u[3];
  unsigned diff, spins = 0;
#pragma unroll 1
  do {
    if (++spins > kSpinLimit) __trap();
    diff = 0;
#pragma unroll
    for (int q = 0; q < 3; q++) {
      v[q] = ld_relaxed_pair(src + q * (kD / 2));
      u[q] = make_uint2(epoch & 7u, epoch & 7u);
      if (tq) u[q] = ld_relaxed_pair(src + (q * kD + 3 * kD + kF) / 2);
    }
#pragma unroll
    for (int q = 0; q < 3; q++) diff |= (v[q].x ^ epoch) | (v[q].y ^ epoch) | (u[q].x ^ epoch) | (u[q].y ^ epoch);
  } while (__any_sync(0xffffffffu, diff & 7u));
#pragma unroll
  for (int q = 0; q < 3; q++)
    reinterpret_cast<float2*>(sm + kSmCsQ)[tq * 96 + q * 32 + lane] =
        make_float2(untag_value(v[q].x) + untag_value(u[q].x), untag_value(v[q].y) + untag_value(u[q].y));
}

__device__ __forceinline__ void gather_colsums_w1(uint8_t* sm, const __nv_bfloat16* b1, int j, int lane,
                                                  unsigned epoch) {
#pragma unroll 1
  for (int blk = 0; blk < 7; blk++) {
    const int pair = 32 * (blk + (blk < 3 ? 3 * j : blk < 5 ? 21 + 2 * j : 35 + 2 * j)) + lane;
    const uint32_t bias = reinterpret_cast<const uint32_t*>(b1)[pair];
    uint2 v;
    unsigned spins = 0;
#pragma unroll 1
    do {
      if (++spins > kSpinLimit) __trap();
      v = ld_relaxed_pair(reinterpret_cast<const uint2*>(g_cs + 3 * kD) + pair);
    } while (__any_sync(0xffffffffu, ((v.x ^ epoch) | (v.y ^ epoch)) & 7u));
    reinterpret_cast<float4*>(sm + kSmV1)[blk * 32 + lane] =
        make_float4(untag_value(v.x), untag_value(v.y), kGeluBeta * bf_lo(bias), kGeluBeta * bf_hi(bias));
  }
}

constexpr int kPauseQkv = 7, kPauseWo = 2;

__global__ void __cluster_dims__(2, 1, 1) __launch_bounds__(384, 1)
fused_layers_kernel(const __grid_constant__ CUtensorMap map_x, const __grid_constant__ CUtensorMap map_out,
                    const __grid_constant__ CUtensorMap map_qkv, const __grid_constant__ CUtensorMap map_wo,
                    const __grid_constant__ CUtensorMap map_w1a, const __grid_constant__ CUtensorMap map_w1b,
                    const __grid_constant__ CUtensorMap map_w2, const __grid_constant__ CUtensorMap map_csq,
                    const __grid_constant__ CUtensorMap map_cs1, const __grid_constant__ CUtensorMap map_css,
                    const __grid_constant__ Params prm) {
  extern __shared__ __align__(1024) uint8_t sm[];
  if (threadIdx.x < 128 && blockIdx.x < kCtas) TRACE_AT(15, 1);
  const uint32_t sb = __shfl_sync(0xffffffffu, smem_u32(sm), 0);
  const int warp = __shfl_sync(0xffffffffu, threadIdx.x >> 5, 0), lane = threadIdx.x & 31;
  const int cta = blockIdx.x, rank = cta & 1, cl = cta >> 1, q7 = ((cl - 36) * 37) >> 8;
  const int grp = cl < 36 ? (cl < 4 ? 0 : (cl - 4) & 7) : cl - 35 - 7 * q7;
  const int j = cl < 36 ? (cl < 4 ? 4 + cl : (cl - 4) >> 3) : 4 + q7;
  const int b = 2 * grp + rank;
  const int xcol = (b >> 3) * kD, xrow = (b & 7) * 128;

  if (cta >= kCtas) {
    helper_cta(&map_csq, &map_cs1, sm, sb, cta - kCtas, warp);
    return;
  }
  auto first_loads = [&](int s0) {
#pragma unroll 1
    for (int s = s0; s < s0 + 2; s++) {
      const uint32_t full = sb + kBarFull + s * 8, dst = sb + kSmRing + s * 40960;
      mbar_expect_tx(full, 40960);
      tma2d(dst, &map_x, full, xcol + (s & 1) * 64, xrow);
      tma3d(dst + kTileBytes, &map_qkv, full, (j + 4 * s0) * 64, (s & 1) * 64, 0);
      tma3d(dst + kTileBytes + 12288, &map_qkv, full, (j + 4 * s0) * 64, (s & 1) * 64 + 32, 0);
    }
  };
  if ((warp < 8 || warp == 9) && elect()) {
    if (warp == 9) {
#pragma unroll
      for (int s = 0; s < 8; s++) mbar_init(sb + kBarFull + s * 8, 1);
      fence_async_smem();
      first_loads(0);
    } else {
      if (sb & 1023) __trap();
#pragma unroll
      for (int s = 0; s < 16; s++) mbar_init(sb + kBarTurn + warp * 128 + s * 8, warp < 5 ? 1 : warp == 5 ? 2 : 4);
    }
    asm volatile("fence.mbarrier_init.release.cluster;" ::: "memory");
  }
  __syncwarp();
  asm volatile("barrier.cluster.arrive.relaxed.aligned;" ::: "memory");

  if (warp >= 8) {
    asm volatile("setmaxnreg.dec.sync.aligned.u32 40;");
    if (warp < 10) {
      if (warp == 9 && elect()) first_loads(2);
      __syncwarp();
      asm volatile("barrier.cluster.wait.aligned;" ::: "memory");
      uint32_t nb = 32, off = 0, kb = 0;
#define RING_STEP(WAIT, ISSUE)                                            \
  do {                                                                    \
    const uint32_t mb = nb - depth, full = sb + kBarFull + (nb & 56);     \
    if (kb == skip) kb += inc;                                            \
    mbar_wait(sb + kBarEmpty + (mb & 56), mb >> 6);                       \
    WAIT;                                                                 \
    if (elect()) { ISSUE; }                                               \
    TRACE_ISSUE(9 - warp, nb);                                            \
    kb += inc;                                                            \
    off = off == wrap ? 0 : off + step;                                   \
    nb += 8;                                                              \
  } while (nb != nend)
#pragma unroll 1
      for (int sg = 0; sg < kSegs; sg++) {
        const uint32_t e = prm.seg[sg];
        const int ty = e & 7, mode = (e >> 15) & 3, reset = (e >> 24) & 3;
        const uint32_t nend = nb + (e & 0x1f8);
        const uint32_t step = (e >> 17) & 1 ? 40960 : 32768, wrap = 163840 - step;
        const uint32_t depth = (e >> 18) & 1 ? 40 : 32;
        if (reset) off = reset == 1 ? 0 : reset == 2 ? 40960 : 131072;
        const uint32_t own = ty == 2 ? 8 + j : 2 * j;
        if (mode != kModeContinue) kb = ((e >> 9) & 63) + (mode == kModeHead ? own : 0);
        const uint32_t inc = mode >= kModeSkip && ty != 2 ? 2 : 1, skip = mode >= kModeSkip ? own + (kb & 1) : 255;
        if (warp == 8) {
          const CUtensorMap* map = ty < 2 ? &map_qkv : ty == 2 ? &map_wo : ty == 3 ? &map_w1a : ty < 6 ? &map_w1b : &map_w2;
          const int c0 = ty < 2 ? (j + 8 * ty) * 64 : 0;
          const int c2 = ty < 2 ? 0 : ty == 3 ? 3 * j : ty == 4 ? 24 + 2 * j : ty == 5 ? 40 + 2 * j : 2 * j;
          const uint32_t half = (ty < 2 || ty == 3) ? 12288 : 8192;
          const uint32_t bytes = 2 * half + (mode == kModeHead ? 0 : kTileBytes);
          const uint32_t dst = sb + kSmRing + (mode == kModeHead && ty != 2 ? 0 : kTileBytes) + rank * half;
          if (e >> 26) {
            const bool second = (grp & 6) == 2;
            const int pk = grp < 4 ? 2 * j + (grp & 1) : 2 * (grp - 4 + (grp - 4 >= j));
            const CUtensorMap* pm = ty == 6 ? &map_qkv : second ? &map_w1b : &map_w1a;
            if (elect())
              asm volatile("cp.async.bulk.prefetch.tensor.3d.L2.global [%0, {%1, %2, %3}];" ::"l"(pm),
                           "r"(ty == 6 ? (j + 8 * second) * 64 : 0), "r"(pk * 64 + rank * 32),
                           "r"(ty == 6 ? 0 : second ? 24 + 2 * j : 3 * j) : "memory");
          }
          if (ty == 2 && mode == kModeHead) mbar_wait(sb + kBarEpi + ((e >> 19) & 31) * 8, 0);
#pragma unroll 1
          RING_STEP(, mbar_expect_tx(full, bytes); tma3d_mc(dst + off, map, full, c0, kb * 64 + rank * 32, c2));
        } else if (mode == kModeHead) {
          off += ((nend - nb) >> 3) * step;
          nb = nend;
          if (off >= 163840) off -= 163840;
        } else if (sg < 2) {
#pragma unroll 1
          RING_STEP(, tma2d(sb + kSmRing + off, &map_x, full, xcol + kb * 64, xrow));
        } else {
          const uint8_t* src = ty == 6 ? g_h + b * 56 * kTileBytes : (ty == 2 ? g_o : g_x) + b * 16 * kTileBytes;
          const int dep = (e >> 19) & 31;
          if (dep < 28) mbar_wait(sb + kBarReady + dep * 8, 0);
          if ((dep & 30) == 28) {
#pragma unroll 1
            RING_STEP(mbar_wait(sb + kBarSrc + ((kb << (4 - inc)) & 56), dep),
                      bulk_load(sb + kSmRing + off, src + kb * kTileBytes, kTileBytes, full));
          } else {
#pragma unroll 1
            RING_STEP(, bulk_load(sb + kSmRing + off, src + kb * kTileBytes, kTileBytes, full));
          }
        }
      }
#undef RING_STEP
    } else {
      unsigned epoch = 0;
      if (warp == 10) {
        if (lane == 0) epoch = atomicAdd(&g_ticket, 1u) / kGrid + 1;
        *reinterpret_cast<unsigned*>(sm + kSmEpoch) = __shfl_sync(0xffffffffu, epoch, 0);
        asm volatile("barrier.cluster.wait.aligned;" ::: "memory");
        if (elect()) mbar_arrive(sb + kBarEpoch);
      } else {
        asm volatile("barrier.cluster.wait.aligned;" ::: "memory");
        mbar_wait_bounded(sb + kBarFull, 0);
        if (elect()) {
          mbar_expect_tx(sb + kBarInit, 32768);
          tma2d(sb + kSmX, &map_x, sb + kBarInit, xcol + j * 128, xrow);
          tma2d(sb + kSmX + kTileBytes, &map_x, sb + kBarInit, xcol + j * 128 + 64, xrow);
        }
        const uint2 u = reinterpret_cast<const uint2*>(prm.b2)[32 * j + lane];
        reinterpret_cast<float4*>(sm + kSmB2)[lane] = make_float4(
            kHScale * bf_lo(u.x), kHScale * bf_hi(u.x), kHScale * bf_lo(u.y), kHScale * bf_hi(u.y));
      }
      mbar_wait_bounded(sb + kBarEpoch, 0);
      epoch = *reinterpret_cast<volatile unsigned*>(sm + kSmEpoch);
      if (cta < 96) {
        mbar_wait_bounded(sb + kBarInit, 0);
        colsum_strip(&map_css, sm, sb, (cta >> 5) * kD + 512 + (cta & 31) * 16, warp - 10, lane, epoch);
      }
      gather_colsums_qkv(sm, 11 - warp, j, lane, epoch);
      __syncwarp();
      if (elect()) mbar_arrive(sb + kBarCs + (11 - warp) * 8);
      if (warp == 10) {
        const unsigned* flag = g_flag + b * 32 + (lane & 7);
        unsigned count = epoch * 32;
#pragma unroll 1
        for (int i = 0; i < kTiles - 1; i++) {
          const bool xt = i == 2 || i == 6 || i == 9;
          count++;
          mbar_wait(sb + (xt ? kBarX + (i >> 2) * 16 : kBarEpi + i * 8), 0);
          if (xt || i == 1 || i == 8) {
            unsigned todo = 0xff;
            do {
              const unsigned now = __ballot_sync(0xffffffffu, (int)(ld_relaxed(flag) - count) >= 0) & todo;
              if (now) {
                asm volatile("fence.acquire.gpu;\nfence.proxy.async.global;" ::: "memory");
                if ((now >> lane) & 1) mbar_arrive(sb + kBarSrc + lane * 8);
                todo ^= now;
              }
              if (todo == 0xff) __nanosleep(300);
            } while (todo);
          } else {
            wait_flags(flag, count);
            if (elect()) mbar_arrive(sb + kBarReady + i * 8);
          }
          if (xt) {
            wait_flags(flag, ++count);
            if (elect()) mbar_arrive(sb + kBarReady + (14 + (i >> 2)) * 8);
          }
        }
      } else {
        unsigned count = epoch * 32;
#pragma unroll 1
        for (int i = 0; i < kTiles - 1; i++) {
          if (i == 3) {
            gather_colsums_w1(sm, prm.b1, j, lane, epoch);
            __syncwarp();
            if (elect()) mbar_arrive(sb + kBarCs + 16);
          }
          const bool xt = i == 2 || i == 6 || i == 9;
#pragma unroll 1
          for (int h = 0; h < (xt ? 2 : 1); h++) {
            if (xt && h == 0) {
              mbar_wait_bounded(sb + kBarEpi + i * 8, 0);
              if (elect()) bulk_store(g_x + (b * 16 + 2 * j) * kTileBytes, sb + kSmX, kTileBytes / 2);
            }
            mbar_wait_bounded(sb + (xt ? kBarX + (i >> 2) * 16 + 8 * h : kBarEpi + i * 8), 0);
            const int ty = i >= 7 ? i - 7 : i;
            if (ty >= 2 && elect()) {
              uint8_t* dst = xt ? g_x + (b * 16 + 2 * j + h) * kTileBytes
                                : g_h + (b * 56 + 1 + (ty == 3 ? 3 * j : 16 * ty - 40 + 2 * j)) * kTileBytes;
              const int piece = (xt && h == 0) ? kTileBytes / 2 : kTileBytes / 8;
#pragma unroll 1
              for (int o = xt && h == 0 ? piece : 0; o < kTileBytes; o += piece) {
                bulk_store(dst + o, sb + (xt ? kSmX + h * kTileBytes : kSmStg) + o, piece);
                bulk_commit();
                bulk_wait();
              }
              if (!xt) mbar_arrive(sb + kBarFree + i * 8);
            }
            __syncwarp();
            count++;
            if (elect()) st_release(&g_flag[b * 32 + j], count);
            __syncwarp();
          }
        }
#pragma unroll 1
        for (int q = 0; q < 4; q++) {
          mbar_wait_bounded(sb + (q & 1 ? kBarX + 48 : kBarEpi + (kTiles - 1) * 8) + 4 * (q & 2), 0);
          if (elect()) {
            tma2d_store(&map_out, sb + kSmX + q * 8192, xcol + j * 128 + (q >> 1) * 64, xrow + (q & 1) * 64);
            bulk_commit();
            if (q == 3) bulk_wait_read();
          }
        }
      }
    }
    __syncwarp();
    asm volatile("barrier.cluster.arrive.relaxed.aligned;\nbarrier.cluster.wait.aligned;" ::: "memory");
  } else {
    asm volatile("setmaxnreg.inc.sync.aligned.u32 232;");
    asm volatile("barrier.cluster.wait.aligned;" ::: "memory");
    const int wg = warp >> 2, w = warp & 3;
    const bool rel = (threadIdx.x & 95) == 0;
    const uint32_t rel_addr = mapa(sb + kBarEmpty, w & 1);
    if (wg == 1) TRACE_AT(15, 0);
#define EPOCH (*reinterpret_cast<volatile unsigned*>(sm + kSmEpoch))

#pragma unroll 1
    for (int i = wg; i < kTiles; i += 2) {
      const int layer = i >= 7, ty = i - 7 * layer;
      TRACE_AT(i, 15);
      float acc[2][96];
      if (ty == 2 || ty == 6) {
        const int lane = lane_id();
        const uint32_t xa = sb + kSmX + ((lane >> 4) * 8 + (lane & 7)) * 128 + (((2 * w + ((lane >> 3) & 1)) ^ (lane & 7)) << 4);
        const float up = ty == 6 ? kHScale / kXScale : layer ? 1.f / kXScale : 1.f;
        const float dn = ty == 2 ? kXScale : layer ? 1.f / kHScale : kXScale / kHScale;
#pragma unroll
        for (int h = 0; h < 2; h++) {
          const float* b2 = reinterpret_cast<const float*>(sm + kSmB2) + 64 * h + 16 * w + (lane >> 2);
          const float bias[2] = {ty == 6 ? b2[0] : 0.f, ty == 6 ? b2[8] : 0.f};
#pragma unroll
          for (int p = 0; p < 8; p++) {
            uint32_t r[4];
            ldsm4_t(xa + h * kTileBytes + p * 2048, r);
#pragma unroll
            for (int m = 0; m < 4; m++) {
              acc[h][8 * p + 2 * m] = fmaf(bf_lo(r[m]), up, bias[m & 1]);
              acc[h][8 * p + 2 * m + 1] = fmaf(bf_hi(r[m]), up, bias[m & 1]);
              asm volatile("" : "+f"(acc[h][8 * p + 2 * m]), "+f"(acc[h][8 * p + 2 * m + 1]));
            }
            yield_slot();
          }
        }
        auto stage = [&](int qt) {
          const int h = qt >> 1;
          if (qt == 1 || (qt == 3 && i == kTiles - 1)) {
            fence_async_smem();
            __syncwarp();
            if (lane == 0) mbar_arrive(sb + kBarEpi + (i + h) * 8);
          }
#pragma unroll
          for (int p = 4 * (qt & 1); p < 4 * (qt & 1) + 4; p++) {
            const float* a = &acc[h][8 * p];
            stsm4_t(xa + h * kTileBytes + p * 2048, pack2(a[0] * dn, a[1] * dn), pack2(a[2] * dn, a[3] * dn),
                    pack2(a[4] * dn, a[5] * dn), pack2(a[6] * dn, a[7] * dn));
            yield_slot();
          }
          if (qt & 1) {
            fence_async_smem();
            __syncwarp();
            if (elect()) mbar_arrive(sb + kBarX + (i >> 2) * 16 + 8 * h);
            TRACE_AT(i, 8 + h);
          }
        };
        mainloop<128, kResid>(acc, sb, i, layer * 152 + ty * 16, ty == 6 ? 4 : 0, ty == 6 ? 56 : 16,
                              ty == 2 ? kPauseWo : -1, 2 * layer + 1, rel_addr, rel, ty == 2 ? 8 : -1, stage);
        TRACE_AT(i, 2);
        stage(2);
        stage(3);
      } else {
        const int xver = 2 * layer + (ty >= 3);
        const uint32_t stg = sb + kSmStg + w * 4096;
        const float4* vec = reinterpret_cast<const float4*>(sm + kSmV1) + (ty == 3 ? 0 : 64 * ty - 160);
        int lane;
        uint8_t* hdst = g_h + (b * 56 + (ty == 3 ? 3 * j : 16 * ty - 40 + 2 * j)) * kTileBytes + w * 4096;
        float2 st[4];
        unsigned epoch;
        auto pre = [&] {
          lane = lane_id();
          if (ty < 4) mbar_wait(sb + (ty == 1 ? kBarEpi + (i - 1) * 8 : kBarStat + xver * 8), 0);
#pragma unroll
          for (int c = 0; c < 4; c++) st[c] = reinterpret_cast<const float2*>(sm + kSmStat)[32 * w + 8 * c + (lane >> 2)];
          epoch = EPOCH;
        };
        auto team_stats = [&] {
          uint2* stat = g_stat + b * 1024;
          const unsigned tag = EPOCH * 4 + xver;
          lane = lane_id();
          publish_stats(sb, stat + j * 128, w, lane, tag);
          gather_stats(sm, stat, 32 * w + lane, xver ? 1e-5f * kXScale * kXScale : 1e-5f, tag);
          __syncwarp();
          if (elect()) mbar_arrive(sb + kBarStat + xver * 8);
          TRACE_AT(i, 14);
        };
        if (ty < 4) {
          AttnRegs ar;
          auto odd = [&](int step) {
            if (step == 0) pre();
            else convert_odd(acc, st, ar, step, sm, sb, xver + ty, g_halo + ((layer * 16 + b) * 16 + j + 8 * ty) * 256, b,
                             epoch, w, lane);
          };
          head_blocks<192>(acc, sb, layer * 152 + (ty < 2 ? 2 * ty : 48), ty < 2 ? 2 * ty : 1, xver, rel_addr, rel);
          if (ty == 1) {
            if (i == 1) {
              mbar_wait(sb + kBarEpoch, 0);
              mbar_wait(sb + kBarInit, 0);
            }
            team_stats();
            epoch = 0;
#pragma unroll
            for (int c = 0; c < 4; c++) st[c] = reinterpret_cast<const float2*>(sm + kSmStat)[32 * w + 8 * c + (lane >> 2)];
          } else {
            mainloop<192, kPlain>(acc, sb, i, layer * 152 + (ty ? 52 : 4), ty ? 1 : 0, 14, -1, 0, rel_addr, rel, 0, pre);
            TRACE_AT(i, 2);
            if (ty == 3) goto wide_gelu;
          }
          if (layer == 0) mbar_wait(sb + kBarCs + ty * 8, 0);
          add_mean_term(acc, st, sm, ty, lane);
          if (ty == 1) {
            mainloop<192, kStagger>(acc, sb, i, layer * 152 + 18, 2, 14, kPauseQkv, xver, rel_addr, rel, 0, odd);
            TRACE_AT(i, 2);
          } else {
            odd(1);
            odd(2);
            odd(3);
          }
          epilogue_attn(acc, st, ar, sm, sb, layer, ty, b, j, epoch, i, w, lane);
          TRACE_AT(i, 3);
          continue;
        wide_gelu:
          if (i == 3) mbar_wait(sb + kBarCs + 16, 0);
          scale_stats(st);
          fold_norm<16, 24>(acc, st, vec + (lane & 3));
          TRACE_AT(i, 11);
          gelu_chunk<2>(acc, stg, lane, nullptr, [] {});
          TRACE_AT(i, 12);
          fold_norm<0, 2>(acc, st, vec + (lane & 3));
          store_staged(hdst + 2 * kTileBytes, stg);
          fold_norm<2, 16>(acc, st, vec + (lane & 3));
        } else {
          if (ty == 4) {
            head_blocks<128>(acc, sb, layer * 152 + 50, 3, xver, rel_addr, rel);
            team_stats();
          } else {
            const uint32_t s0 = ((((sb & 0x3FFFF) + kSmRing) >> 4) | (1u << 16)) + 3 * 2048;
            mbar_wait(sb + kBarTurn + (i - 1) * 8, 0);
            mbar_wait(sb + kBarFull, layer * 19 + 10);
            TRACE_KB((layer * 152 + 80) * 8);
            mma_kblock<128, 2>(acc, s0, s0 + kToB);
          }
          mainloop<128, kPlain>(acc, sb, i, layer * 152 + 6 + 15 * ty, 4, ty + 10, -1, 0, rel_addr, rel, 0, pre,
                                ty == 5 ? 0 : 64);
          TRACE_AT(i, 2);
          if (i == 4) mbar_wait(sb + kBarCs + 16, 0);
          scale_stats(st);
          fold_norm<0, 16>(acc, st, vec + (lane & 3));
        }
        auto own_store_done = [] {
          if (elect()) bulk_wait();
          __syncwarp();
        };
        TRACE_AT(i, 8);
        gelu_chunk<0>(acc, stg, lane, nullptr, [&] {
          if (ty == 3) own_store_done();
          else mbar_wait(sb + kBarFree + (i - 1) * 8, 0);
        });
        TRACE_AT(i, 9);
        gelu_chunk<1>(acc, stg, lane, hdst, own_store_done);
        TRACE_AT(i, 10);
        fence_async_smem();
        __syncwarp();
        if (elect()) mbar_arrive(sb + kBarEpi + i * 8);
      }
      TRACE_AT(i, 3);
    }
#undef EPOCH
    asm volatile("barrier.cluster.arrive.relaxed.aligned;\nbarrier.cluster.wait.aligned;" ::: "memory");
    if (wg == 1) TRACE_AT(15, 2);
  }
}

void build_segments(uint32_t* seg) {
  int n = 0, fine = 0;
  auto per_source = [&] { return 28 + (fine++ & 1); };
  auto add = [&](int ty, int cnt, int kb0, int mode, int wide, int depth5, int dep, int reset) {
    seg[n++] = ty | cnt << 3 | kb0 << 9 | mode << 15 | wide << 17 | depth5 << 18 | dep << 19 | reset << 24;
  };
  for (int l = 0; l < 2; l++) {
    const int t = 7 * l;
    if (l == 0) {
      add(0, 14, 2, kModePlain, 1, 0, 31, 1);
      add(1, 14, 2, kModePlain, 1, 0, 31, 0);
    } else {
      add(0, 2, 0, kModeHead, 1, 1, 31, 1);
      add(1, 2, 0, kModeHead, 1, 0, 31, 0);
      add(0, 7, 0, kModeSkip, 1, 0, per_source(), 0);
      add(0, 7, 1, kModeSkip, 1, 0, 15, 0);
      add(1, 7, 0, kModeSkip, 1, 0, 31, 0);
      add(1, 7, 1, kModeSkip, 1, 0, 31, 0);
    }
    add(2, 4, 0, kModePlain, 0, 0, t, 1);
    add(2, 4, 4, kModePlain, 0, 1, 31, 4);
    add(2, 1, 0, kModeHead, 0, 1, t + 1, 0);
    add(2, 7, 8, kModeSkip, 0, 1, per_source(), 0);
    add(3, 1, 0, kModeHead, 1, 1, 31, 2);
    add(3, 1, 1, kModeHead, 1, 0, 31, 0);
    add(4, 2, 0, kModeHead, 1, 0, 31, 0);
    add(3, 7, 0, kModeSkip, 1, 0, per_source(), 0);
    add(3, 7, 1, kModeSkip, 1, 0, 14 + 2 * l, 0);
    add(4, 4, 0, kModeSkip, 0, 0, 31, 3);
    add(4, 3, 0, kModeContinue, 0, 1, 31, 0);
    add(4, 7, 1, kModeSkip, 0, 1, 31, 0);
    add(5, 16, 0, kModePlain, 0, 1, 31, 0);
    add(6, 24, 0, kModePlain, 0, 1, t + 3, 0);
    add(6, 16, 24, kModePlain, 0, 1, t + 4, 0);
    add(6, 16, 40, kModePlain, 0, 1, t + 5, l ? 0 : 4);
  }
}

typedef CUresult (*EncodeTiledFn)(CUtensorMap*, CUtensorMapDataType, cuuint32_t, void*, const cuuint64_t*,
                                  const cuuint64_t*, const cuuint32_t*, const cuuint32_t*, CUtensorMapInterleave,
                                  CUtensorMapSwizzle, CUtensorMapL2promotion, CUtensorMapFloatOOBfill);

CUtensorMap make_map(EncodeTiledFn enc, const void* p, int rank, const cuuint64_t* dims, const cuuint64_t* strides,
                     const cuuint32_t* box, CUtensorMapSwizzle swizzle = CU_TENSOR_MAP_SWIZZLE_128B,
                     CUtensorMapL2promotion promo = CU_TENSOR_MAP_L2_PROMOTION_L2_128B) {
  CUtensorMap m;
  const cuuint32_t es[5] = {1, 1, 1, 1, 1};
  enc(&m, CU_TENSOR_MAP_DATA_TYPE_BFLOAT16, rank, const_cast<void*>(p), dims, strides, box, es,
      CU_TENSOR_MAP_INTERLEAVE_NONE, swizzle, promo, CU_TENSOR_MAP_FLOAT_OOB_FILL_NONE);
  return m;
}

CUtensorMap weight_map(EncodeTiledFn enc, const void* p, int k, int n, int blocks) {
  const cuuint64_t dims[3] = {64, (cuuint64_t)k, (cuuint64_t)n / 64};
  const cuuint64_t strides[2] = {(cuuint64_t)n * 2, 128};
  const cuuint32_t box[3] = {64, 32, (cuuint32_t)blocks};
  return make_map(enc, p, 3, dims, strides, box, CU_TENSOR_MAP_SWIZZLE_128B, CU_TENSOR_MAP_L2_PROMOTION_L2_256B);
}

CUtensorMap slab_map(EncodeTiledFn enc, const void* p, int n, int cols, int rows) {
  const cuuint64_t dims[2] = {(cuuint64_t)n, kD};
  const cuuint64_t strides[1] = {(cuuint64_t)n * 2};
  const cuuint32_t box[2] = {(cuuint32_t)cols, (cuuint32_t)rows};
  return make_map(enc, p, 2, dims, strides, box, CU_TENSOR_MAP_SWIZZLE_NONE);
}

CUtensorMap token_map(EncodeTiledFn enc, const void* p, int rows) {
  const cuuint64_t dims[2] = {2 * kD, 1024};
  const cuuint64_t strides[1] = {4 * kD};
  const cuuint32_t box[2] = {64, (cuuint32_t)rows};
  return make_map(enc, p, 2, dims, strides, box);
}

}

extern "C" void kernel_launch(void* const* d_in, const int* in_sizes, int n_in, void* d_out, int out_size) {
  (void)in_sizes; (void)n_in; (void)out_size;
  static EncodeTiledFn enc = nullptr;
  if (!enc) {
    void* fn = nullptr;
    cudaDriverEntryPointQueryResult q;
    cudaGetDriverEntryPoint("cuTensorMapEncodeTiled", &fn, cudaEnableDefault, &q);
    enc = (EncodeTiledFn)fn;
    cudaFuncSetAttribute(fused_layers_kernel, cudaFuncAttributeMaxDynamicSharedMemorySize, kSmBytes);
  }
  Params prm;
  prm.b1 = (const __nv_bfloat16*)d_in[5];
  prm.b2 = (const __nv_bfloat16*)d_in[7];
  build_segments(prm.seg);
  const cuuint64_t qd[3] = {kD, kD, 3}, qs[2] = {3 * kD * 2, kD * 2};
  const cuuint32_t qb[3] = {64, 32, 3};
  const CUtensorMap map_x = token_map(enc, d_in[0], 128);
  const CUtensorMap map_out = token_map(enc, d_out, 64);
  const CUtensorMap map_qkv = make_map(enc, d_in[1], 3, qd, qs, qb);
  const CUtensorMap map_wo = weight_map(enc, d_in[2], kD, kD, 2);
  const CUtensorMap map_w1a = weight_map(enc, d_in[4], kD, kF, 3);
  const CUtensorMap map_w1b = weight_map(enc, d_in[4], kD, kF, 2);
  const CUtensorMap map_w2 = weight_map(enc, d_in[6], kF, kD, 2);
  fused_layers_kernel<<<kGrid, 384, kSmBytes>>>(map_x, map_out, map_qkv, map_wo, map_w1a, map_w1b, map_w2,
                                                slab_map(enc, d_in[1], 3 * kD, 128, 128), slab_map(enc, d_in[4], kF, 128, 128),
                                                slab_map(enc, d_in[1], 3 * kD, 16, 128), prm);
}
```
